```python
import torch

def _softmax(x, axis=-1):
    return torch.softmax(x, dim=axis)

def _gelu(x):
    return torch.nn.functional.gelu(x, approximate='tanh')

def _silu(x):
    return torch.nn.functional.silu(x)

def _sigmoid(x):
    return torch.sigmoid(x)

def _layernorm(x, axis=-1, eps=1e-05):
    m = x.mean(dim=axis, keepdim=True)
    v = x.var(dim=axis, keepdim=True, unbiased=False)
    return (x - m) / torch.sqrt(v + eps)

def _scatter_add(tgt, idx, src, axis=0):
    return tgt.clone().index_add_(axis, idx, src)

def _segment_sum(src, seg, n):
    out = torch.zeros((n,) + src.shape[1:], dtype=src.dtype)
    return out.index_add_(0, seg, src)

def _pad(x, pw):
    flat = tuple((v for pair in reversed(pw) for v in pair))
    return torch.nn.functional.pad(x, flat)
kernel_name = 'interleave_layers__ssm_conv_s4d__memory_aug_recurrent_mem_tr__prompt'

def setup_inputs():

    _w = lambda a: (lambda t: t.to(torch.bfloat16) if t.is_floating_point() else t)(torch.as_tensor(a))

    def _A_setup():
        Bsz, L, D, N = (1, 2048, 512, 128)
        return {'u': _w((lambda *s: torch.randn(*s, dtype=torch.bfloat16) * 0.05)(Bsz, L, D)), 'log_A_real': _w((lambda *s: torch.randn(*s, dtype=torch.bfloat16) * 3.2)(D, N) * 0.5), 'A_imag': _w((lambda *s: torch.randn(*s, dtype=torch.bfloat16) * 0.05)(D, N) * 3.14), 'C_real': _w((lambda *s: torch.randn(*s, dtype=torch.bfloat16) * 0.05)(D, N) / N ** 0.5), 'C_imag': _w((lambda *s: torch.randn(*s, dtype=torch.bfloat16) * 0.05)(D, N) / N ** 0.5), 'log_dt': _w((lambda *s: torch.randn(*s, dtype=torch.bfloat16) * 0.05)(D) * 0.5 - 4.0), 'D_skip': _w((lambda *s: torch.randn(*s, dtype=torch.bfloat16) * 0.05)(D))}
    _A_in = _A_setup()

    def _B_setup():
        B, S, Dm = (1, 2048, 512)
        H, Dh = (32, 128)
        M, seg = (8, 32)
        seg = min(seg, S)
        S = S // seg * seg
        return {'x': _w((lambda *s: torch.randn(*s, dtype=torch.bfloat16) * 0.05)(B, S, Dm)), 'mem0': _w((lambda *s: torch.randn(*s, dtype=torch.bfloat16) * 0.8)(B, M, Dm)), 'Wq': _w((lambda *s: torch.randn(*s, dtype=torch.bfloat16) * 1.6)(Dm, H, Dh) * Dm ** (-0.5)), 'Wk': _w((lambda *s: torch.randn(*s, dtype=torch.bfloat16) * 1.6)(Dm, H, Dh) * Dm ** (-0.5)), 'Wv': _w((lambda *s: torch.randn(*s, dtype=torch.bfloat16) * 0.8)(Dm, H, Dh) * Dm ** (-0.5)), 'Wo': _w((lambda *s: torch.randn(*s, dtype=torch.bfloat16) * 0.8)(H, Dh, Dm) * (H * Dh) ** (-0.5)), 'seg_len': seg}
    _B_in = _B_setup()
    return {'A_u': _A_in['u'], 'A_log_A_real': _A_in['log_A_real'], 'A_A_imag': _A_in['A_imag'], 'A_C_real': _A_in['C_real'], 'A_C_imag': _A_in['C_imag'], 'A_log_dt': _A_in['log_dt'], 'A_D_skip': _A_in['D_skip'], 'B_x': _B_in['x'], 'B_mem0': _B_in['mem0'], 'B_Wq': _B_in['Wq'], 'B_Wk': _B_in['Wk'], 'B_Wv': _B_in['Wv'], 'B_Wo': _B_in['Wo'], 'B_seg_len': _B_in['seg_len']}

def reference(A_u, A_log_A_real, A_A_imag, A_C_real, A_C_imag, A_log_dt, A_D_skip, B_x, B_mem0, B_Wq, B_Wk, B_Wv, B_Wo, B_seg_len):

    def _A_ref(u, log_A_real, A_imag, C_real, C_imag, log_dt, D_skip):
        L = u.shape[1]
        dt = torch.exp(log_dt)
        A = -torch.exp(log_A_real) + 1j * A_imag
        C = (C_real + 1j * C_imag) * dt[:, None]
        pos = (lambda x, dt: x.to(dt))(torch.arange(L), log_dt.dtype)
        P = torch.exp((A * dt[:, None])[:, :, None] * pos[None, None, :])
        K = 2.0 * torch.einsum('dn,dnl->dl', C, P).real
        L2 = 2 * L
        u_t = (lambda x, *d: x.permute(*d))(u, 0, 2, 1)
        Kf = (lambda x, *a, **k: torch.fft.rfft(x.float(), *a, **k))(K, L2)
        Uf = (lambda x, *a, **k: torch.fft.rfft(x.float(), *a, **k))(u_t, L2)
        y = (lambda x, *a, **k: torch.fft.irfft(x, *a, **k).to(torch.bfloat16))(Uf * Kf[None, :, :], L2)[:, :, :L]
        y = (lambda x, *d: x.permute(*d))(y, 0, 2, 1)
        return y + u * D_skip[None, None, :]

    def _B_ref(x, mem0, Wq, Wk, Wv, Wo, seg_len):
        B, S, Dm = x.shape
        H, Dh = (Wq.shape[1], Wq.shape[2])
        M = mem0.shape[1]
        scale = Dh ** (-0.5)
        n_seg = S // seg_len
        L = M + seg_len
        idx = torch.arange(L)
        mask = (idx[:, None] < M) | (idx[:, None] >= idx[None, :])
        mem = mem0
        outs = []
        for s in range(n_seg):
            xs = x[:, s * seg_len:(s + 1) * seg_len, :].clone()
            h = torch.concatenate([mem, xs], axis=1)
            q = torch.einsum('btd,dhe->bhte', h, Wq)
            k = torch.einsum('btd,dhe->bhte', h, Wk)
            v = torch.einsum('btd,dhe->bhte', h, Wv)
            scores = torch.einsum('bhqe,bhke->bhqk', q, k) * scale
            scores = torch.where(mask[None, None], scores, -1000000000.0)
            p = _softmax(scores, axis=-1)
            o = torch.einsum('bhqk,bhke->bhqe', p, v)
            o = torch.einsum('bhte,hed->btd', o, Wo)
            mem = o[:, :M, :].clone()
            outs.append(o[:, M:, :])
        return torch.concatenate(outs, axis=1)
    x = A_u
    x = x + _A_ref(_layernorm(x, axis=-1), A_log_A_real, A_A_imag, A_C_real, A_C_imag, A_log_dt, A_D_skip)
    x = x + _B_ref(_layernorm(x, axis=-1), B_mem0, B_Wq, B_Wk, B_Wv, B_Wo, B_seg_len)
    x = x + _A_ref(_layernorm(x, axis=-1), A_log_A_real, A_A_imag, A_C_real, A_C_imag, A_log_dt, A_D_skip)
    x = x + _B_ref(_layernorm(x, axis=-1), B_mem0, B_Wq, B_Wk, B_Wv, B_Wo, B_seg_len)
    return x
```

```cpp
#include <cuda_runtime.h>
#include <cuda_bf16.h>
#include <cuda.h>
#include <stdint.h>
#include <string.h>
#include <math.h>

namespace {

constexpr int NCL = 66;
constexpr int MAXT = 64;
constexpr int OPS1 = 8;
constexpr int MAXSPLIT = 16;
constexpr int HSPLIT = 10;
constexpr int PW = 144;

__device__ uint4 g_xA[2][16 * 8 * 1024];
__device__ float2 g_st[2][16 * 2048];
__device__ float2 g_st2[16 * 16 * 128];
__device__ uint4 g_qkv[2][64 * 64 * 768];
__device__ uint4 g_o[2][16 * 64 * 1024];
__device__ uint4 g_pp[2][16 * MAXSPLIT * 8192];
__device__ uint4 g_acc[7 * 2048];
__device__ unsigned g_gate[32];
__device__ uint32_t g_P[16 * 16 * 32 * PW];
__device__ uint4 g_u[16 * 16 * 512];
__device__ float4 g_carry[3][16 * 16 * 4 * 256];
__device__ float g_cs[2 * 12288 + 64];
__device__ unsigned g_cnt[9 * 16 * 32];
__device__ uint32_t g_ln0[2048];

enum { C_QKV0 = 0, C_QKV1 = 1, C_O0 = 2, C_O1 = 3, C_OP0 = 4, C_OP1 = 5, C_CV = 6, C_ST = 7, C_H = 8 };
__device__ __forceinline__ unsigned* cnt_ptr(int kind, int chunk) { return g_cnt + (kind * 16 + chunk) * 32; }

enum { T_END = 0, T_QKV = 1, T_OP = 2, T_CV = 3, T_FIN = 4 };
struct ProArgs { const __nv_bfloat16 *x, *lAr, *Ai, *Cr, *Ci, *ldt, *Dk, *Wq, *Wk, *Wv, *Wo, *mem0; };
struct Params {
    CUtensorMap tm[5];
    CUtensorMap t3[4];
    ProArgs pa;
    int dopro;
    const __nv_bfloat16* mem0;
    const __nv_bfloat16* Wo;
    const __nv_bfloat16* Dskip;
    __nv_bfloat16* out;
    int rec0;
    int chains;
    int lag;
    int b1, e0, nit;
    int zero, gpit;
    int dostats;
    int nst[2];
    uint32_t task[NCL][MAXT];
};

__device__ __forceinline__ uint32_t smem_u32(const void* p) { return (uint32_t)__cvta_generic_to_shared(p); }
__device__ __forceinline__ uint32_t mapa(uint32_t a, uint32_t r) {
    uint32_t o; asm("mapa.shared::cluster.u32 %0,%1,%2;" : "=r"(o) : "r"(a), "r"(r)); return o;
}
__device__ __forceinline__ void mbar_init(uint32_t b, int c) { asm volatile("mbarrier.init.shared::cta.b64 [%0],%1;" ::"r"(b), "r"(c) : "memory"); }
__device__ __forceinline__ void mbar_expect(uint32_t b, int bytes) { asm volatile("mbarrier.arrive.expect_tx.shared::cta.b64 _,[%0],%1;" ::"r"(b), "r"(bytes) : "memory"); }
__device__ __forceinline__ void mbar_arrive(uint32_t b) { asm volatile("mbarrier.arrive.shared::cta.b64 _,[%0];" ::"r"(b) : "memory"); }
__device__ __forceinline__ void mbar_arrive_cluster(uint32_t b) { asm volatile("mbarrier.arrive.shared::cluster.b64 _,[%0];" ::"r"(b) : "memory"); }
__device__ __forceinline__ void mbar_wait(uint32_t b, uint32_t ph) {
    asm volatile(
        "{.reg .pred p; .reg .u32 n; mov.u32 n,0;\n"
        "W%=: mbarrier.try_wait.parity.shared::cta.b64 p,[%0],%1;\n"
        "@p bra D%=;\n"
        "add.u32 n,n,1; setp.lt.u32 p,n,2000000; @p bra W%=;\n"
        "trap;\n"
        "D%=: }" ::"r"(b), "r"(ph) : "memory");
}
__device__ __forceinline__ bool wait_lds128(uint32_t b, uint32_t ph, uint32_t a, uint4& v) {
    uint32_t ok;
    asm volatile("{.reg .pred p; mbarrier.try_wait.parity.shared::cta.b64 p,[%5],%6,20000; ld.shared.v4.u32 {%0,%1,%2,%3},[%7]; selp.u32 %4,1,0,p;}"
                 : "=r"(v.x), "=r"(v.y), "=r"(v.z), "=r"(v.w), "=r"(ok) : "r"(b), "r"(ph), "r"(a) : "memory");
    return ok;
}
__device__ __forceinline__ bool wait_lds64(uint32_t b, uint32_t ph, uint32_t a, uint2& v) {
    uint32_t ok;
    asm volatile("{.reg .pred p; mbarrier.try_wait.parity.shared::cta.b64 p,[%3],%4,20000; ld.shared.v2.u32 {%0,%1},[%5]; selp.u32 %2,1,0,p;}"
                 : "=r"(v.x), "=r"(v.y), "=r"(ok) : "r"(b), "r"(ph), "r"(a) : "memory");
    return ok;
}
template <int PH> __device__ __forceinline__ void mbar_wait_c(uint32_t b) {
    asm volatile(
        "{.reg .pred p; .reg .u32 n; mov.u32 n,%2;\n"
        "W%=: mbarrier.try_wait.parity.shared::cta.b64 p,[%0],%1;\n"
        "@p bra D%=;\n"
        "add.u32 n,n,1; setp.lt.u32 p,n,2000000; @p bra W%=;\n"
        "trap;\n"
        "D%=: }" ::"r"(b), "n"(PH), "n"(PH) : "memory");
}
__device__ __forceinline__ void bar_sync(int id, int n) { asm volatile("bar.sync %0,%1;" ::"r"(id), "r"(n) : "memory"); }
__device__ __forceinline__ void bar_arrive(int id, int n) { asm volatile("bar.arrive %0,%1;" ::"r"(id), "r"(n) : "memory"); }
__device__ __forceinline__ void cluster_sync() { asm volatile("barrier.cluster.arrive.relaxed.aligned; barrier.cluster.wait.aligned;" ::: "memory"); }
__device__ __forceinline__ void fence_async() { asm volatile("fence.proxy.async;" ::: "memory"); }
__device__ __forceinline__ void fence_async_smem() { asm volatile("fence.proxy.async.shared::cta;" ::: "memory"); }
#define EFR 1
#define EFW 2
constexpr uint64_t POL_N = 0x1000000000000000ull, POL_F = 0x12F0000000000000ull;
constexpr uint64_t POL_LAST = EFR ? POL_F : POL_N  , POL_LATE = EFW ? POL_F : POL_N  , POL_SOON = EFW > 1 ? POL_F : POL_N;
__device__ __forceinline__ void bulk_g2s(uint32_t dst, const void* src, int bytes, uint32_t bar, uint64_t pol) {
    asm volatile("cp.async.bulk.shared::cluster.global.mbarrier::complete_tx::bytes.L2::cache_hint [%0],[%1],%2,[%3],%4;" ::"r"(dst), "l"(src), "r"(bytes), "r"(bar), "l"(pol) : "memory");
}
__device__ __forceinline__ void bulk_g2s_mc(uint32_t dst, const void* src, int bytes, uint32_t bar, uint64_t pol) {
    asm volatile("cp.async.bulk.shared::cluster.global.mbarrier::complete_tx::bytes.multicast::cluster.L2::cache_hint [%0],[%1],%2,[%3],%4,%5;" ::"r"(dst), "l"(src), "r"(bytes), "r"(bar), "h"((uint16_t)3), "l"(pol) : "memory");
}
__device__ __forceinline__ void bulk_s2s(uint32_t dst, uint32_t src, int bytes, uint32_t bar) {
    asm volatile("cp.async.bulk.shared::cluster.shared::cta.mbarrier::complete_tx::bytes [%0],[%1],%2,[%3];" ::"r"(dst), "r"(src), "r"(bytes), "r"(bar) : "memory");
}
__device__ __forceinline__ bool elect() {
    uint32_t r; asm volatile("{.reg .pred p; elect.sync _|p,0xffffffff; selp.u32 %0,1,0,p;}" : "=r"(r)); return r;
}
__device__ __forceinline__ void stg128(uint4* p, uint4 v, uint64_t pol) {
    asm volatile("st.global.L2::cache_hint.v4.u32 [%0],{%1,%2,%3,%4},%5;" ::"l"(p), "r"(v.x), "r"(v.y), "r"(v.z), "r"(v.w), "l"(pol));
}
__device__ __forceinline__ void stg32(uint32_t* p, uint32_t v, uint64_t pol) { asm volatile("st.global.L2::cache_hint.u32 [%0],%1,%2;" ::"l"(p), "r"(v), "l"(pol)); }
__device__ __forceinline__ uint4 ldcg128_last(const uint4* p) {
    uint4 v; asm volatile("ld.global.cg.L2::cache_hint.v4.u32 {%0,%1,%2,%3},[%4],%5;" : "=r"(v.x), "=r"(v.y), "=r"(v.z), "=r"(v.w) : "l"(p), "l"(POL_LAST) : "memory"); return v;
}
__device__ __forceinline__ void tma2d(uint32_t dst, const CUtensorMap* tm, int x, int y, uint32_t bar) {
    asm volatile("cp.async.bulk.tensor.2d.shared::cluster.global.mbarrier::complete_tx::bytes [%0],[%1,{%2,%3}],[%4];" ::"r"(dst), "l"(tm), "r"(x), "r"(y), "r"(bar) : "memory");
}
__device__ __forceinline__ void tma3d(uint32_t dst, const CUtensorMap* tm, int y, int z, uint32_t bar) {
    asm volatile("cp.async.bulk.tensor.3d.shared::cluster.global.mbarrier::complete_tx::bytes [%0],[%1,{0,%2,%3}],[%4];" ::"r"(dst), "l"(tm), "r"(y), "r"(z), "r"(bar) : "memory");
}
__device__ __forceinline__ void st_async4(uint32_t a, uint32_t x, uint32_t y, uint32_t z, uint32_t w, uint32_t mb) {
    asm volatile("st.async.shared::cluster.mbarrier::complete_tx::bytes.v4.b32 [%0],{%1,%2,%3,%4},[%5];" ::"r"(a), "r"(x), "r"(y), "r"(z), "r"(w), "r"(mb) : "memory");
}
__device__ __forceinline__ void st_async2(uint32_t a, uint32_t x, uint32_t y, uint32_t mb) {
    asm volatile("st.async.shared::cluster.mbarrier::complete_tx::bytes.v2.b32 [%0],{%1,%2},[%3];" ::"r"(a), "r"(x), "r"(y), "r"(mb) : "memory");
}
#define LDSQ "ld.shared"
__device__ __forceinline__ uint4 lds128(uint32_t a) { uint4 v; asm volatile(LDSQ ".v4.u32 {%0,%1,%2,%3},[%4];" : "=r"(v.x), "=r"(v.y), "=r"(v.z), "=r"(v.w) : "r"(a) : "memory"); return v; }
__device__ __forceinline__ uint2 lds64(uint32_t a) { uint2 v; asm volatile(LDSQ ".v2.u32 {%0,%1},[%2];" : "=r"(v.x), "=r"(v.y) : "r"(a) : "memory"); return v; }
__device__ __forceinline__ uint32_t lds32(uint32_t a) { uint32_t v; asm volatile(LDSQ ".u32 %0,[%1];" : "=r"(v) : "r"(a) : "memory"); return v; }
__device__ __forceinline__ void sts128(uint32_t a, uint32_t x, uint32_t y, uint32_t z, uint32_t w) { asm volatile("st.shared.v4.u32 [%0],{%1,%2,%3,%4};" ::"r"(a), "r"(x), "r"(y), "r"(z), "r"(w) : "memory"); }
__device__ __forceinline__ void sts64(uint32_t a, uint32_t x, uint32_t y) { asm volatile("st.shared.v2.u32 [%0],{%1,%2};" ::"r"(a), "r"(x), "r"(y) : "memory"); }
__device__ __forceinline__ void sts32(uint32_t a, uint32_t x) { asm volatile("st.shared.u32 [%0],%1;" ::"r"(a), "r"(x) : "memory"); }
__device__ __forceinline__ uint4 ldsm4(uint32_t a) { uint4 v; asm volatile("ldmatrix.sync.aligned.m8n8.x4.shared.b16 {%0,%1,%2,%3},[%4];" : "=r"(v.x), "=r"(v.y), "=r"(v.z), "=r"(v.w) : "r"(a) : "memory"); return v; }
__device__ __forceinline__ uint4 ldsm4t(uint32_t a) { uint4 v; asm volatile("ldmatrix.sync.aligned.m8n8.x4.trans.shared.b16 {%0,%1,%2,%3},[%4];" : "=r"(v.x), "=r"(v.y), "=r"(v.z), "=r"(v.w) : "r"(a) : "memory"); return v; }
__device__ __forceinline__ uint32_t movm(uint32_t a) { uint32_t d; asm volatile("movmatrix.sync.aligned.m8n8.trans.b16 %0,%1;" : "=r"(d) : "r"(a)); return d; }
__device__ __forceinline__ uint32_t pack2(float lo, float hi) { uint32_t d; asm("cvt.rn.bf16x2.f32 %0,%1,%2;" : "=r"(d) : "f"(hi), "f"(lo)); return d; }
__device__ __forceinline__ uint32_t hadd2(uint32_t a, uint32_t b) { uint32_t d; asm("add.rn.bf16x2 %0,%1,%2;" : "=r"(d) : "r"(a), "r"(b)); return d; }
__device__ __forceinline__ float blo(uint32_t v) { return __uint_as_float(v << 16); }
__device__ __forceinline__ float bhi(uint32_t v) { return __uint_as_float(v & 0xffff0000u); }
__device__ __forceinline__ float rbf(float x) { return __uint_as_float(pack2(0.f, x)); }
__device__ __forceinline__ float ex2(float x) { float y; asm("ex2.approx.ftz.f32 %0,%1;" : "=f"(y) : "f"(x)); return y; }
__device__ __forceinline__ float rcp(float x) { float y; asm("rcp.approx.ftz.f32 %0,%1;" : "=f"(y) : "f"(x)); return y; }
__device__ __forceinline__ void mma16(float* c, uint32_t a0, uint32_t a1, uint32_t a2, uint32_t a3, uint32_t b0, uint32_t b1) {
    asm volatile("mma.sync.aligned.m16n8k16.row.col.f32.bf16.bf16.f32 {%0,%1,%2,%3},{%4,%5,%6,%7},{%8,%9},{%0,%1,%2,%3};"
                 : "+f"(c[0]), "+f"(c[1]), "+f"(c[2]), "+f"(c[3]) : "r"(a0), "r"(a1), "r"(a2), "r"(a3), "r"(b0), "r"(b1));
}
__device__ __forceinline__ void mma8(float* c, uint32_t a0, uint32_t a1, uint32_t b0) {
    asm volatile("mma.sync.aligned.m16n8k8.row.col.f32.bf16.bf16.f32 {%0,%1,%2,%3},{%4,%5},{%6},{%0,%1,%2,%3};"
                 : "+f"(c[0]), "+f"(c[1]), "+f"(c[2]), "+f"(c[3]) : "r"(a0), "r"(a1), "r"(b0));
}
__device__ __forceinline__ uint4 ld_rlx128(const uint4* p) {
    uint4 v;
    asm volatile("{.reg .b128 t; ld.relaxed.gpu.global.b128 t,[%4]; mov.b128 {%0,%1,%2,%3},t;}" : "=r"(v.x), "=r"(v.y), "=r"(v.z), "=r"(v.w) : "l"(p) : "memory");
    return v;
}
__device__ __forceinline__ void st_rlx128(uint4* p, uint32_t x, uint32_t y, uint32_t z, uint32_t w) {
    asm volatile("{.reg .b128 t; mov.b128 t,{%1,%2,%3,%4}; st.relaxed.gpu.global.b128 [%0],t;}" ::"l"(p), "r"(x), "r"(y), "r"(z), "r"(w) : "memory");
}
__device__ __forceinline__ uint4 ldcg128(const uint4* p) { uint4 v; asm volatile("ld.global.cg.v4.u32 {%0,%1,%2,%3},[%4];" : "=r"(v.x), "=r"(v.y), "=r"(v.z), "=r"(v.w) : "l"(p) : "memory"); return v; }
__device__ __forceinline__ void red_release(unsigned* p, unsigned v) {
    asm volatile("fence.proxy.async; red.relaxed.gpu.global.add.u32 [%0],%1;" ::"l"(p), "r"(v) : "memory");
}
__device__ __forceinline__ void wait_cnt(const unsigned* p, unsigned target) {
    unsigned v; int n = 0;
    while (true) {
        asm volatile("ld.acquire.gpu.global.u32 %0,[%1];" : "=r"(v) : "l"(p) : "memory");
        if (v >= target) break;
        if (++n > 3000000) __trap();
        __nanosleep(40);
    }
}
__device__ __forceinline__ void wait_cnt_warp(const unsigned* p, unsigned target) {
    unsigned v; int n = 0;
    while (true) {
        asm volatile("ld.acquire.gpu.global.u32 %0,[%1];" : "=r"(v) : "l"(p) : "memory");
        if (__all_sync(0xffffffffu, v >= target)) break;
        if (++n > 3000000) __trap();
        __nanosleep(40);
    }
}
__device__ __forceinline__ uint64_t mkdesc(uint32_t addr, uint32_t lbo, uint32_t sbo, uint32_t sw) {
    return (uint64_t)((addr & 0x3FFFF) >> 4) | ((uint64_t)(lbo >> 4) << 16) | ((uint64_t)(sbo >> 4) << 32) | ((uint64_t)sw << 62);
}
__device__ __forceinline__ void wg_fence() { asm volatile("wgmma.fence.sync.aligned;" ::: "memory"); }
__device__ __forceinline__ void wg_commit() { asm volatile("wgmma.commit_group.sync.aligned;" ::: "memory"); }
template <int N> __device__ __forceinline__ void wg_wait() { asm volatile("wgmma.wait_group.sync.aligned %0;" ::"n"(N) : "memory"); }
#define R8(c, o) "+f"(c[o]), "+f"(c[o + 1]), "+f"(c[o + 2]), "+f"(c[o + 3]), "+f"(c[o + 4]), "+f"(c[o + 5]), "+f"(c[o + 6]), "+f"(c[o + 7])
#define R32(c, o) R8(c, o), R8(c, o + 8), R8(c, o + 16), R8(c, o + 24)
#define S32A "%0,%1,%2,%3,%4,%5,%6,%7,%8,%9,%10,%11,%12,%13,%14,%15,%16,%17,%18,%19,%20,%21,%22,%23,%24,%25,%26,%27,%28,%29,%30,%31"
#define S32B ",%32,%33,%34,%35,%36,%37,%38,%39,%40,%41,%42,%43,%44,%45,%46,%47,%48,%49,%50,%51,%52,%53,%54,%55,%56,%57,%58,%59,%60,%61,%62,%63"
#define S32C ",%64,%65,%66,%67,%68,%69,%70,%71,%72,%73,%74,%75,%76,%77,%78,%79,%80,%81,%82,%83,%84,%85,%86,%87,%88,%89,%90,%91,%92,%93,%94,%95"
#define S32D ",%96,%97,%98,%99,%100,%101,%102,%103,%104,%105,%106,%107,%108,%109,%110,%111,%112,%113,%114,%115,%116,%117,%118,%119,%120,%121,%122,%123,%124,%125,%126,%127"
__device__ __forceinline__ void wgmma256(float* c, uint64_t da, uint64_t db, int acc) {
    asm volatile("{.reg .pred p; setp.ne.b32 p,%130,0; wgmma.mma_async.sync.aligned.m64n256k16.f32.bf16.bf16 {" S32A S32B S32C S32D "},%128,%129,p,1,1,0,1;}"
                 : R32(c, 0), R32(c, 32), R32(c, 64), R32(c, 96) : "l"(da), "l"(db), "r"(acc));
}
__device__ __forceinline__ void wgmma192(float* c, uint64_t da, uint64_t db, int acc) {
    asm volatile("{.reg .pred p; setp.ne.b32 p,%98,0; wgmma.mma_async.sync.aligned.m64n192k16.f32.bf16.bf16 {" S32A S32B S32C "},%96,%97,p,1,1,0,1;}"
                 : R32(c, 0), R32(c, 32), R32(c, 64) : "l"(da), "l"(db), "r"(acc));
}
__device__ __forceinline__ void wgmma8_first(float* c, uint64_t da, uint64_t db) {
    asm volatile("wgmma.mma_async.sync.aligned.m64n8k16.f32.bf16.bf16 {%0,%1,%2,%3},%4,%5,0,1,1,1,0;"
                 : "=f"(c[0]), "=f"(c[1]), "=f"(c[2]), "=f"(c[3]) : "l"(da), "l"(db));
}
template <int ACC> __device__ __forceinline__ void wgmma16_ta(float* c, float* e, uint64_t da, uint64_t db) {
    if (ACC) asm volatile("wgmma.mma_async.sync.aligned.m64n16k16.f32.bf16.bf16 {%0,%1,%2,%3,%4,%5,%6,%7},%8,%9,1,1,1,1,0;"
                 : "+f"(c[0]), "+f"(c[1]), "+f"(c[2]), "+f"(c[3]), "+f"(e[0]), "+f"(e[1]), "+f"(e[2]), "+f"(e[3]) : "l"(da), "l"(db));
    else asm volatile("wgmma.mma_async.sync.aligned.m64n16k16.f32.bf16.bf16 {%0,%1,%2,%3,%4,%5,%6,%7},%8,%9,0,1,1,1,0;"
                 : "=f"(c[0]), "=f"(c[1]), "=f"(c[2]), "=f"(c[3]), "=f"(e[0]), "=f"(e[1]), "=f"(e[2]), "=f"(e[3]) : "l"(da), "l"(db));
}
__device__ __forceinline__ void wgmma8_ta(float* c, uint64_t da, uint64_t db) {
    asm volatile("wgmma.mma_async.sync.aligned.m64n8k16.f32.bf16.bf16 {%0,%1,%2,%3},%4,%5,1,1,1,1,0;"
                 : "+f"(c[0]), "+f"(c[1]), "+f"(c[2]), "+f"(c[3]) : "l"(da), "l"(db));
}
template <int N> __device__ __forceinline__ void reg_inc() { asm volatile("setmaxnreg.inc.sync.aligned.u32 %0;" ::"n"(N)); }
template <int N> __device__ __forceinline__ void reg_dec() { asm volatile("setmaxnreg.dec.sync.aligned.u32 %0;" ::"n"(N)); }

#define PROF(cond, idx) do {} while (0)
#define CPROF(k) do {} while (0)

constexpr int S_GATE = 232440, S_XBAR = 232432;
constexpr float SC_LOG2E = 0.08838834764831845f * 1.4426950408889634f;

__device__ __forceinline__ float2 ln_finish(float mean, float var) {
    float sd; asm("sqrt.approx.f32 %0,%1;" : "=f"(sd) : "f"(rbf(rbf(var) + 1e-5f)));
    sd = rbf(sd);
    return make_float2(rbf(mean), sd);
}

__device__ __forceinline__ float2 row_stats512(const uint4* src, int s1, int s2) {
    const int g = (threadIdx.x & 31) >> 2;
    uint4 v[16];
#pragma unroll
    for (int i = 0; i < 16; i++) v[i] = ldcg128(src + (i >> 1) * s1 + (i & 1) * s2);
    float a[4] = {0, 0, 0, 0}, q0[4] = {0, 0, 0, 0}, q1[4] = {0, 0, 0, 0};
#pragma unroll
    for (int i = 0; i < 16; i++) {
        mma16(a, v[i].x, v[i].y, v[i].z, v[i].w, 0x3f803f80u, 0x3f803f80u);
        mma8(q0, v[i].x, v[i].y, v[i].x); mma8(q1, v[i].x, v[i].y, v[i].y);
        mma8(q0, v[i].z, v[i].w, v[i].z); mma8(q1, v[i].z, v[i].w, v[i].w);
    }
    const float sum = a[0] + a[2], sq = (g & 1) ? q0[1] + q1[3] : q0[0] + q1[2];
    return make_float2(sum, fmaxf(sq - sum * sum * (1.f / 512.f), 0.f));
}
__device__ __forceinline__ void x1_stats(int rg) {
    const int lane = threadIdx.x & 31, g = lane >> 2, c = lane & 3;
    const float2 r = row_stats512(g_xA[0] + (rg >> 4) * 8192 + (rg & 15) * 64 + c * 8 + g, 1024, 32);
    if (c == (g >> 1)) { g_st[0][rg * 8 + g] = r; g_ln0[rg * 8 + g] = 0; }
    __syncwarp();
    if (lane == 0) red_release(cnt_ptr(C_ST, rg >> 4), 1);
}
__global__ void stats_kernel() { x1_stats(blockIdx.x * 4 + (threadIdx.x >> 5)); }

#define NT 8
#define RH 104
#define RW0 200
#define NTO 12
#define DP1 0
#define DPW (NT - 1)
#define GPW 0
#define GPJ 0
#define NIP 0
#define PACE 2
#define EARLY 0
#define LATET 0
#define BULKX 2
#define G2I 4
#define XG 1
#define CHKB 8
constexpr int TILE = 20480;
constexpr int R_WV = 0, R_WO = 65536, R_T = 131072, R_M = R_T + 2 * TILE  , R_LOC = R_M + 8192  ,
              R_REM = R_LOC + 12288  , R_O = R_REM + 24576  , R_SX = R_O + 4096  ,
              R_IL = R_SX + 10240  , R_BAR = 231936, R_Z = R_BAR + 128  , R_STQ = 0, R_STK = 65536, R_STV = 131072;
static_assert(R_IL + 512 <= R_BAR && R_BAR + 256 <= S_XBAR, "smem map");
enum { RB_INIT = 0, RB_T = 2  , RB_QK = 4  , RB_V = 8  , RB_N = 12 };
enum { NB_MF = 1  , NB_LOC = 3  , NB_PAIR = 5  , NB_O = 9  , NB_XG = 11  , NB_W = 13 };
__device__ __forceinline__ uint32_t clk32() { return (uint32_t)clock64(); }

__device__ __forceinline__ char* acc_base() { return (char*)(((size_t)g_acc + 131071) & ~(size_t)131071); }
__device__ __forceinline__ uint32_t acc_slice(uint32_t s6) { return (s6 & 1) * 256 + (s6 >> 1) * 1024; }
__device__ __forceinline__ uint32_t acc_main(uint32_t rank, uint32_t tid) { return acc_slice(rank * 32 + (tid >> 3)) + (tid & 7) * 16; }
__device__ __forceinline__ uint32_t acc_extra(uint32_t rank, uint32_t tid) { return 65536 + acc_slice(((tid >> 5) & 1) + rank * 4 + (tid >> 6) * 8) + (tid & 31) * 4; }
__device__ __forceinline__ uint32_t acc_slot(uint32_t s) { return (s & 1) * 128 + (s & 2) * 256; }
__device__ __forceinline__ void acc_init(const __nv_bfloat16* mem0, int i) {
    const uint32_t tid = i & 255, rank = (i >> 8) & 1, slot = (i >> 9) & 3, X = i >> 11;
    uint32_t v[5] = {0, 0, 0, 0, 0};
    if (slot == 3) {
        const uint16_t* m = (const uint16_t*)mem0 + (tid & 3) * 1024 + rank * 256 + (tid >> 5) * 32 + ((tid >> 2) & 7);
#pragma unroll
        for (int k = 0; k < 4; k++) v[k] = __ldg(m + k * 8) | ((uint32_t)__ldg(m + k * 8 + 512) << 16);
        v[4] = (v[3] >> 16) | 0x42000000u; v[3] = (v[3] & 0xffff) | 0x42000000u;
    }
    *(uint4*)(acc_base() + X * 32768 + acc_slot(slot) + acc_main(rank, tid)) = make_uint4(v[0], v[1], v[2], v[3]);
    *(uint32_t*)(acc_base() + X * 1024 + acc_slot(slot) + acc_extra(rank, tid)) = v[4];
}
__global__ void acc_init_kernel(const __nv_bfloat16* mem0) { acc_init(mem0, blockIdx.x * 256 + threadIdx.x); }

struct RecW { uint32_t am, ae, ah, dp, lw, lww, sb, bar, zero, ts, tn; };
__device__ __forceinline__ uint32_t vadd(uint32_t a, uint32_t b) { uint32_t d; asm volatile("add.u32 %0,%1,%2;" : "=r"(d) : "r"(a), "r"(b)); return d; }
__device__ __forceinline__ uint32_t vshr(uint32_t a, int n) { uint32_t d; asm volatile("shr.u32 %0,%1,%2;" : "=r"(d) : "r"(a), "r"(n)); return d; }
__device__ __forceinline__ uint64_t gptr(uint32_t lo, uint32_t hi) { uint64_t d; asm("mov.b64 %0,{%1,%2};" : "=l"(d) : "r"(lo), "r"(hi)); return d; }
__device__ __forceinline__ void sfence(uint32_t zero) { asm volatile("{.reg .pred p; setp.ne.u32 p,%0,0; @p exit;}" ::"r"(zero) : "memory"); }
#define SF sfence(k.zero)
#define TS(i) do {} while (0)
#define TSN(i) do {} while (0)
#define TSET(it, slot) do {} while (0)
struct Gat { uint32_t x, y, z, w, e; };
template <int X>
__device__ __forceinline__ void gat_issue(Gat& g, const RecW& k, int s, uint32_t dep) {
    const uint32_t o = acc_slot(s + 3) + dep;
    asm volatile("{.reg .b128 t; ld.relaxed.gpu.global.b128 t,[%5+%7]; mov.b128 {%0,%1,%2,%3},t; ld.relaxed.gpu.global.u32 %4,[%6+%8];}"
                 : "=r"(g.x), "=r"(g.y), "=r"(g.z), "=r"(g.w), "=r"(g.e) : "l"(gptr(k.am + o, k.ah)), "l"(gptr(k.ae + o, k.ah)), "n"(X * 32768), "n"(X * 1024) : "memory");
}
template <int X>
__device__ __forceinline__ void gat_finish(Gat& g, const RecW& k, int s) {
    asm volatile("{.reg .pred p; .reg .b32 c,n,u,v; .reg .b64 a,b; .reg .b128 t;\n"
                 "prmt.b32 c,%3,%4,0x7632; setp.eq.u32 p,c,0x42004200; vote.sync.all.pred p,p,0xffffffff; @p bra.uni D%=;\n"
                 "add.u32 n,%8,3;\n"
                 "G%=: and.b32 v,n,1; and.b32 u,n,2; shl.b32 v,v,7; mad.lo.u32 u,u,256,v;\n"
                 "add.u32 v,u,%5; add.u32 u,u,%6; mov.b64 a,{v,%9}; mov.b64 b,{u,%9};\n"
                 "ld.relaxed.gpu.global.u32 %4,[b+%11]; ld.relaxed.gpu.global.b128 t,[a+%10]; mov.b128 {%0,%1,%2,%3},t;\n"
                 "prmt.b32 c,%3,%4,0x7632; setp.eq.u32 p,c,0x42004200; vote.sync.all.pred p,p,0xffffffff; @p bra.uni D%=;\n"
                 "add.u32 n,n,4; setp.lt.u32 p,n,8000000; @p bra.uni G%=; trap;\n"
                 "D%=: prmt.b32 %3,%3,%4,0x5410; stmatrix.sync.aligned.m8n8.x4.trans.shared.b16 [%7],{%0,%1,%2,%3};}"
                 : "+r"(g.x), "+r"(g.y), "+r"(g.z), "+r"(g.w), "+r"(g.e)
                 : "r"(k.am), "r"(k.ae), "r"(k.lww + R_M + X * 4096), "r"(s), "r"(k.ah), "n"(X * 32768), "n"(X * 1024) : "memory");
}
#define WLD(base, i) wt[i] = lds128(k.lww + (base) + (i) * 4096)
template <int PASS, int X>
__device__ __forceinline__ void rec_qkv(const RecW& k, int s, const uint32_t (*wq)[4], const uint32_t (*wk)[4], uint4* wt, uint4* wo, uint4& mf, Gat& g2, int s2) {
    constexpr bool BWD = PASS == 2;
    float aq[4] = {0, 0, 0, 0}, ak[4] = {0, 0, 0, 0}, av[4] = {0, 0, 0, 0};
    const uint32_t ma = k.lw + R_M + X * 4096;
    if (BWD && CHKB == 8) { TS(1); gat_finish<1>(g2, k, s2); bar_sync(NB_MF + 1, 256); mf = ldsm4(ma + 7 * 512); TS(2); }
    if (!BWD) mf = ldsm4(ma);
#pragma unroll
    for (int ii = 0; ii < 8; ii++) {
        const int i = BWD ? 7 - ii : ii;
        if (PASS == 1 && ii == CHKB) { TS(1); gat_finish<1>(g2, k, s2); bar_sync(NB_MF + 1, 256); TS(2); }
        const uint4 m = mf;
        if (ii < 7) mf = ldsm4(ma + (BWD ? i - 1 : i + 1) * 512);
        else if (PASS == 1 && CHKB < 8) mf = ldsm4(ma + 4096 + 7 * 512);
        if (PASS == 1 && ii == G2I && G2I) gat_issue<1>(g2, k, s2, 0);
        SF;
#pragma unroll
        for (int hh = 0; hh < 2; hh++) {
            const int h = BWD ? 1 - hh : hh, ks = 2 * i + h;
            const uint32_t b0 = h ? m.z : m.x, b1 = h ? m.w : m.y;
            mma16(aq, wq[ks][0], wq[ks][1], wq[ks][2], wq[ks][3], b0, b1);
            mma16(ak, wk[ks][0], wk[ks][1], wk[ks][2], wk[ks][3], b0, b1);
            SF;
            mma16(av, wt[ks].x, wt[ks].y, wt[ks].z, wt[ks].w, b0, b1);
            SF;
            if (!BWD && ks + NT < 16) WLD(R_WV, ks + NT < 16 ? ks + NT : 0);
            if (BWD && ks >= NT) WLD(R_WV, ks >= NT ? ks - NT : 0);
            if (PASS != 1 && 2 * ii + hh + NIP >= 16) wo[(2 * ii + hh + NIP) & 15] = lds128(k.lww + R_WO + ((2 * ii + hh + NIP) & 15) * 4096);
            SF;
        }
    }
    const uint32_t ro = k.dp + R_REM + (X * 2 + (s & 1)) * 6144, bar = k.bar + k.dp + X * 16;
    const uint32_t ra = vadd(k.lww, ro), va = vshr(k.lww, 1) + (k.sb >> 1) + 4096;
    const uint32_t x0 = movm(pack2(aq[0], aq[1])), x1 = movm(pack2(aq[2], aq[3])), x2 = movm(pack2(ak[0], ak[1])), x3 = movm(pack2(ak[2], ak[3]));
    const uint32_t v0 = pack2(av[0], av[1]), v1 = pack2(av[2], av[3]);
    if (!(BULKX & 1)) st_async4(ra, x0, x1, x2, x3, bar + RB_QK * 8);
    sts128(k.lww + R_LOC + X * 6144, x0, x1, x2, x3);
    sts64(va + R_LOC + X * 6144, v0, v1);
    if (BULKX & 4) fence_async_smem();
    bar_arrive(NB_LOC + X, 320);
    if (!(BULKX & 2)) st_async2(va + ro, v0, v1, bar + RB_V * 8);
    SF;
    TS(BWD ? 4 : 3);
}
template <bool BWD, int X>
__device__ __forceinline__ void rec_out(const RecW& k, int s, uint4* wt, Gat& g1, int s1) {
    if (BWD) { WLD(R_WO, 17 - NTO); WLD(R_WO, 16 - NTO); }
    TS(BWD ? 8 : 5);
    bar_sync(NB_O + X, 320);
    float r0[4] = {0, 0, 0, 0}, r1[4] = {0, 0, 0, 0};
    const uint32_t oa = k.lw + R_O + X * 2048;
    uint4 bn = ldsm4(oa + (BWD ? 3 : 0) * 512);
    TS(BWD ? 9 : 6);
    uint2 il;
    uint64_t pm, pe;
#pragma unroll
    for (int ii = 0; ii < 4; ii++) {
        const int i = BWD ? 3 - ii : ii;
        const uint4 b = bn;
        if (ii < 3) bn = ldsm4(oa + (BWD ? i - 1 : i + 1) * 512);
        else { il = lds64(k.lw + R_IL + X * 8); pm = gptr(vadd(k.am, acc_slot(s)), k.ah); pe = gptr(vadd(k.ae, acc_slot(s)), k.ah); }
        SF;
        if (BWD && EARLY == ii + 1) { gat_issue<0>(g1, k, s1 + 1, 0); SF; }
#pragma unroll
        for (int nn = 0; nn < 4; nn++) {
            const int n = BWD ? 3 - nn : nn, f = 4 * i + n, nx = BWD ? f - NTO + 2 : f + NTO - 2;
            mma16((n & 1) ? r1 : r0, wt[f].x, wt[f].y, wt[f].z, wt[f].w, n >> 1 ? b.z : b.x, n >> 1 ? b.w : b.y);
            SF;
            if (ii * 4 + nn >= 2 && nx >= 0 && nx < 16) WLD(R_WO, nx & 15);
            SF;
        }
    }
    const float i0 = __uint_as_float(il.x), i1 = __uint_as_float(il.y);
    asm volatile("red.relaxed.gpu.global.add.noftz.v4.bf16x2 [%0+%5],{%1,%2,%3,%4};" ::"l"(pm),
                 "r"(pack2(r0[0] * i0, r0[1] * i1)), "r"(pack2(r0[2] * i0, r0[3] * i1)), "r"(pack2(r1[0] * i0, r1[1] * i1)), "r"(pack2(r1[2] * i0, 1.f)), "n"(X * 32768) : "memory");
    asm volatile("red.relaxed.gpu.global.add.noftz.bf16x2 [%0+%2],%1;" ::"l"(pe), "r"(pack2(r1[3] * i1, 1.f)), "n"(X * 1024) : "memory");
    if (XG) bar_arrive(NB_XG + X, 320);
    SF;
    TS(BWD ? 10 : 7);
}
__device__ __forceinline__ uint32_t pause(uint32_t v, int n) {
#pragma unroll
    for (int i = 0; i < n; i++) asm volatile("shfl.sync.bfly.b32 %0,%0,0,0x1f,0xffffffff;" : "+r"(v));
    return v;
}
template <bool DUAL, int X>
__device__ __forceinline__ void rec_step(const RecW& k, int s, int s2, const uint32_t (*wq)[4], const uint32_t (*wk)[4], uint4* wt) {
    Gat g1, g2;
    uint4 wo[16], mf;
    bar_sync(NB_MF + X, 256);
    if (DUAL && !G2I) gat_issue<1>(g2, k, s2, 0);
    rec_qkv<DUAL ? 1 : 0, X>(k, s, wq, wk, wt, wo, mf, g2, s2);
    if (DUAL) rec_qkv<2, 1>(k, s2, wq, wk, wt, wo, mf, g2, s2);
    uint32_t wa = k.lww;
#pragma unroll
    for (int i = NIP; i < NTO; i++) {
        wo[i] = lds128(wa + R_WO + i * 4096);
        if ((i - NIP) % PACE == PACE - 1) wa = k.lww + (wo[i].x & k.zero);
        SF;
    }
    rec_out<false, X>(k, s, wo, g1, s);
    if (DUAL) rec_out<true, 1>(k, s2, wo, g1, s);
    if (DUAL && !EARLY) { gat_issue<0>(g1, k, s + 1, 0); SF; }
#pragma unroll
    for (int i = 0; i < NT; i++) { WLD(R_WV, i); SF; }
    if (!DUAL) gat_issue<X>(g1, k, s + 1, pause(wt[DPW].x & k.zero, DP1));
    TS(12);
    gat_finish<X>(g1, k, s + 1);
    TS(11);
}

__device__ __forceinline__ void rec_fetch(const CUtensorMap* tm, uint32_t dst, int x, int y, int nx, uint32_t bar) {
#pragma unroll 1
    for (int j = 0; j < 8; j++) tma2d(dst + j * 8192, tm, x + (j / (8 / nx)) * 64, y + (j % (8 / nx)) * 64, bar);
}
__device__ __forceinline__ void rec_weights(const Params& p, uint32_t sb, int head, uint32_t rank, int w) {
    const int lane = threadIdx.x & 31, t = w & 3, WG = w >> 2;
    uint32_t wq[16][4], wk[16][4];
    const uint32_t rowo = (((lane >> 4) << 3) + (lane & 7)) * 128;
    const uint32_t woff = sb + WG * 32768 + rowo + (((2 * t + ((lane >> 3) & 1)) ^ (lane & 7)) << 4);
    const uint32_t lw = sb + lane * 16;
    PROF(threadIdx.x == 0, 3501);
    if (w >= 4 && p.dostats) { wait_cnt_warp(g_gate, lds32(sb + S_GATE)); x1_stats((head * 2 + rank) * 4 + w - 4); }
    PROF(threadIdx.x == 0, 3502);
    mbar_wait(sb + R_BAR + RB_INIT * 8, 0);
    PROF(threadIdx.x == 0, 3503);
#pragma unroll
    for (int ks = 0; ks < 16; ks++) {
        uint4 a = ldsm4t(woff + R_STQ + ks * 2048), b = ldsm4t(woff + R_STK + ks * 2048);
        wq[ks][0] = a.x; wq[ks][1] = a.y; wq[ks][2] = a.z; wq[ks][3] = a.w;
        wk[ks][0] = b.x; wk[ks][1] = b.y; wk[ks][2] = b.z; wk[ks][3] = b.w;
    }
    bar_sync(NB_W, 256);
#pragma unroll 4
    for (int ks = 0; ks < 16; ks++) { const uint4 a = ldsm4t(woff + R_STV + ks * 2048); sts128(lw + w * 512 + R_WV + ks * 4096, a.x, a.y, a.z, a.w); }
    bar_sync(NB_W, 256);
    if (threadIdx.x == 0) {
        mbar_expect(sb + R_BAR + RB_INIT * 8, 65536);
        rec_fetch(&p.tm[4], sb + R_STV, rank * 256, head * 128, 4, sb + R_BAR + RB_INIT * 8);
    }
    __syncwarp();
    mbar_wait(sb + R_BAR + RB_INIT * 8, 1);
#pragma unroll 4
    for (int f = 0; f < 16; f++) {
        const uint4 a = ldsm4t(sb + R_STV + (w >> 1) * 16384 + (f >> 1) * 2048 + rowo + ((((w & 1) * 4 + (f & 1) * 2 + ((lane >> 3) & 1)) ^ (lane & 7)) << 4));
        sts128(lw + w * 512 + R_WO + f * 4096, a.x, a.y, a.z, a.w);
    }
    PROF(threadIdx.x == 0, 3504);
    __syncthreads();
    cluster_sync();
    PROF(threadIdx.x == 0, 3505);
    RecW k;
    k.am = __shfl_sync(0xffffffffu, (uint32_t)(size_t)acc_base() + acc_main(rank, threadIdx.x), lane);
    k.ae = __shfl_sync(0xffffffffu, (uint32_t)(size_t)acc_base() + acc_extra(rank, threadIdx.x), lane);
    k.ah = (uint32_t)((size_t)acc_base() >> 32);
    k.sb = sb; k.zero = p.zero;

    k.dp = mapa(sb, rank ^ 1) - sb;
    k.lww = __shfl_sync(0xffffffffu, lw + w * 512, lane);
    k.lw = k.lww - w * 512;
    k.bar = sb + R_BAR + WG * 8;
    int it = 0;
    uint4 wt[16];
#pragma unroll
    for (int i = 0; i < NT; i++) WLD(R_WV, i);
    if (p.e0) {
        Gat g = {0, 0, 0, 0, 0}; gat_finish<0>(g, k, 0);
#pragma unroll 1
        for (; it < min(p.b1, p.e0); it++) { TSET(it, w == GPW ? 0 : 3); rec_step<false, 0>(k, it, it, wq, wk, wt); }
#pragma unroll 1
        for (; it < p.e0; it++) { TSET(it, w == GPW ? 0 : 3); rec_step<true, 0>(k, it, it - p.b1, wq, wk, wt); }
    }
    if (it < p.nit) {
        Gat g = {0, 0, 0, 0, 0}; gat_finish<1>(g, k, it - p.b1);
#pragma unroll 1
        for (; it < p.nit; it++) { TSET(it, w == GPW ? 0 : 3); rec_step<false, 1>(k, it - p.b1, it - p.b1, wq, wk, wt); }
    }
}

__device__ __forceinline__ void mma16_top(float* c, uint32_t a0, uint32_t a2, uint32_t b0, uint32_t b1) {
    asm volatile("{.reg .b32 j; mma.sync.aligned.m16n8k16.row.col.f32.bf16.bf16.f32 {%0,%1,%2,%3},{%4,j,%5,j},{%6,%7},{%0,%1,%2,%3};}"
                 : "+f"(c[0]), "+f"(c[1]), "+f"(c[2]), "+f"(c[3]) : "r"(a0), "r"(a2), "r"(b0), "r"(b1));
}
__device__ __forceinline__ void rec_load_tile(uint32_t sb, int X, int s, int head, uint32_t rank) {
    const uint32_t bar = sb + R_BAR + (RB_T + X) * 8;
    const uint4* src = g_qkv[X] + (size_t)(s * 32 + head) * 1536;
    mbar_expect(bar, TILE);
    bulk_g2s(sb + R_T + X * TILE, src + 512, 16384, bar, POL_LAST);
    bulk_g2s(sb + R_T + X * TILE + 16384, src + rank * 256, 4096, bar, POL_LAST);
}
__device__ __forceinline__ bool chunk_ready(int X, int s) {
    unsigned v;
    asm volatile("ld.relaxed.gpu.global.u32 %0,[%1];" : "=r"(v) : "l"(cnt_ptr(C_QKV0 + X, s >> 2)) : "memory");
    return __all_sync(0xffffffffu, v >= 384);
}
template <int MT>
__device__ __forceinline__ void rec_xattn(const RecW& k, uint32_t sb, int lane, uint32_t ta, uint32_t la, uint32_t sxw, uint32_t sxr, int X, int j, int s, int head, bool early, const uint4 (*V)[4], const uint32_t (*vm)[2]) {
    constexpr int NTL = 3 + 2 * MT;
    const int g = lane >> 2, c = lane & 3;
    float S[NTL][4];
    uint4 u;
#pragma unroll
    for (int i = 0; i < NTL; i++) S[i][0] = S[i][1] = S[i][2] = S[i][3] = 0;
#pragma unroll
    for (int t = 0; t < 4; t++) {
        const uint4 q = lds128(ta + 16384 + t * 512);
        if (!(t & 1)) u = lds128(la + t * 256);
        mma16(S[0], q.x, q.y, q.z, q.w, (t & 1) ? u.z : u.x, (t & 1) ? u.w : u.y);
#pragma unroll
        for (int m = 0; m <= MT; m++) {
            const uint4 kk = lds128(ta + m * 4096 + t * 512);
            mma16(S[1 + 2 * m], q.x, q.y, q.z, q.w, kk.x, kk.y); mma16(S[2 + 2 * m], q.x, q.y, q.z, q.w, kk.z, kk.w);
        }
    }
#pragma unroll
    for (int i = 0; i < NTL; i++) sts128(sxw + i * 512, __float_as_uint(S[i][0]), __float_as_uint(S[i][1]), __float_as_uint(S[i][2]), __float_as_uint(S[i][3]));
    bar_sync(NB_PAIR + X, 64);
    TS(9);
    if (early) { if (elect()) rec_load_tile(sb, X, s + 1, head, MT); }
    __syncwarp();
#pragma unroll
    for (int i = 0; i < NTL; i++) {
        const uint4 r = lds128(sxr + i * 512);
        S[i][0] += __uint_as_float(r.x); S[i][1] += __uint_as_float(r.y); S[i][2] += __uint_as_float(r.z); S[i][3] += __uint_as_float(r.w);
    }
    const float NEG = -__int_as_float(0x7f800000);
    if (2 * c > g) { S[NTL - 2][0] = NEG; S[NTL - 1][2] = NEG; }
    if (2 * c + 1 > g) { S[NTL - 2][1] = NEG; S[NTL - 1][3] = NEG; }
    float m0 = fmaxf(S[0][0], S[0][1]), m1 = fmaxf(S[0][2], S[0][3]);
#pragma unroll
    for (int i = 1; i < NTL; i++) { if (i < NTL - 1) m0 = fmaxf(m0, fmaxf(S[i][0], S[i][1])); m1 = fmaxf(m1, fmaxf(S[i][2], S[i][3])); }
    m0 = fmaxf(m0, __shfl_xor_sync(0xffffffffu, m0, 1)); m1 = fmaxf(m1, __shfl_xor_sync(0xffffffffu, m1, 1));
    m0 = fmaxf(m0, __shfl_xor_sync(0xffffffffu, m0, 2)); m1 = fmaxf(m1, __shfl_xor_sync(0xffffffffu, m1, 2));
    m0 *= -SC_LOG2E; m1 *= -SC_LOG2E;
    uint32_t P[NTL][2];
#pragma unroll
    for (int i = 0; i < NTL; i++) {
        P[i][0] = i < NTL - 1 ? pack2(ex2(fmaf(S[i][0], SC_LOG2E, m0)), ex2(fmaf(S[i][1], SC_LOG2E, m0))) : 0u;
        P[i][1] = pack2(ex2(fmaf(S[i][2], SC_LOG2E, m1)), ex2(fmaf(S[i][3], SC_LOG2E, m1)));
    }
    float l[4] = {0, 0, 0, 0};
#pragma unroll
    for (int i = 0; i < NTL; i++) mma8(l, P[i][0], P[i][1], 0x3f803f80u);
    const float l0 = rcp(l[0]), l1 = rcp(l[2]);
    const uint32_t st = sxr + ((lane >> 3) & 1) * 896 - (lane >> 4) * 128;
#pragma unroll
    for (int t = 0; t < 4; t++) {
        float a[4] = {0, 0, 0, 0}, b[4] = {0, 0, 0, 0};
        mma8(a, P[0][0], P[0][1], vm[t][0]);
        mma8(b, P[0][0], P[0][1], vm[t][1]);
#pragma unroll
        for (int m = 0; m <= MT; m++) {
            mma8(a, P[1 + 2 * m][0], P[1 + 2 * m][1], V[m][t].x); mma8(b, P[1 + 2 * m][0], P[1 + 2 * m][1], V[m][t].y);
            mma8(a, P[2 + 2 * m][0], P[2 + 2 * m][1], V[m][t].z); mma8(b, P[2 + 2 * m][0], P[2 + 2 * m][1], V[m][t].w);
        }
        asm volatile("stmatrix.sync.aligned.m8n8.x4.shared.b16 [%0],{%1,%2,%3,%4};" ::"r"(st + t * 256), "r"(pack2(a[0] * l0, a[1] * l0)), "r"(pack2(a[2] * l1, a[3] * l1)),
                     "r"(pack2(b[0] * l0, b[1] * l0)), "r"(pack2(b[2] * l1, b[3] * l1)) : "memory");
    }
}
__device__ __forceinline__ void rec_publish(int X, int s) {
    asm volatile("cp.async.bulk.wait_group 0; red.relaxed.gpu.global.add.u32 [%0],1;" ::"l"(cnt_ptr(C_O0 + X, s >> 2)) : "memory");
}
__device__ __forceinline__ void rec_attn(const Params& p, uint32_t sb, int X, int j, int head, uint32_t rank) {
    const int lane = __shfl_sync(0xffffffffu, threadIdx.x & 31, threadIdx.x & 31);
    const uint32_t lw = sb + lane * 16;
    const uint32_t ta = lw + R_T + X * TILE + j * 2048, la = lw + R_LOC + X * 6144 + j * 2048;
    const uint32_t vo = 4096 - j * 1024 - lane * 8;
    const uint32_t sxw = lw + R_SX + (X * 2 + j) * 2560, sxr = lw + R_SX + (X * 2 + (j ^ 1)) * 2560;
    const uint32_t bar = sb + R_BAR + (X * 2 + j) * 8;
    const uint32_t dp = mapa(sb, rank ^ 1) - sb;
    RecW k; k.zero = p.zero; k.lw = lw; k.sb = sb;
    char* zp = acc_base() + (j ? X * 32768 + acc_main(rank, head * 8) : X * 1024 + acc_extra(rank, head * 8));
    if (j == 0) {
        wait_cnt_warp(cnt_ptr(C_QKV0 + X, 0), 384);
        if (lane == 0) rec_load_tile(sb, X, 0, head, rank);
    }
    if (lane == 0) { mbar_expect(bar + RB_QK * 8, 2048); mbar_expect(bar + RB_V * 8, 1024); }
    __syncwarp();
#pragma unroll 1
    for (int s = 0; s < 64; s++) {
        const uint32_t ra = vadd(la, (R_REM - R_LOC) + (X + (s & 1)) * 6144);
        uint4 K[2][4];
        TSET(X ? s + p.b1 : s, j == GPJ ? 1 + X : 3);
        TS(0);
        mbar_wait(sb + R_BAR + (RB_T + X) * 8, s & 1);
        TS(1);
#pragma unroll
        for (int i = 0; i < 8; i++) K[i >> 2][i & 3] = lds128(ta + (i >> 2) * 4096 + (i & 3) * 512);
        asm volatile("cp.async.bulk.wait_group.read 0;" ::: "memory");
        bar_sync(NB_LOC + X, 320);
        if (BULKX) {
            if (!(BULKX & 4)) fence_async_smem();
            if (elect()) {
                const uint32_t src = sb + R_LOC + X * 6144, dst = sb + dp + R_REM + (X * 2 + (s & 1)) * 6144;
                if (BULKX & 1) bulk_s2s(dst + j * 2048, src + j * 2048, 2048, bar + dp + RB_QK * 8);
                if (BULKX & 2) bulk_s2s(dst + 4096 + j * 1024, src + 4096 + j * 1024, 1024, bar + dp + RB_V * 8);
            }
            __syncwarp();
        }
        PROF(lane == 0 && j == 0, X * 64 + s);
        uint4 u[4];
#pragma unroll
        for (int t = 0; t < 4; t++) u[t] = lds128(la + t * 512);
        TS(2);
        mbar_wait(bar + RB_QK * 8, s & 1);
        TS(3);
        float S[5][4];
#pragma unroll
        for (int i = 0; i < 5; i++) S[i][0] = S[i][1] = S[i][2] = S[i][3] = 0;
#pragma unroll
        for (int t = 0; t < 4; t++) {
            const uint4 r = lds128(ra + t * 512);
            u[t].x = hadd2(u[t].x, r.x); u[t].y = hadd2(u[t].y, r.y); u[t].z = hadd2(u[t].z, r.z); u[t].w = hadd2(u[t].w, r.w);
        }
#pragma unroll
        for (int t = 0; t < 4; t++) {
            mma16_top(S[1], u[t].x, u[t].y, K[0][t].x, K[0][t].y); mma16_top(S[2], u[t].x, u[t].y, K[0][t].z, K[0][t].w);
            mma16_top(S[3], u[t].x, u[t].y, K[1][t].x, K[1][t].y); mma16_top(S[4], u[t].x, u[t].y, K[1][t].z, K[1][t].w);
            mma16_top(S[0], u[t].x, u[t].y, u[t].z, u[t].w);
        }
        sts128(sxw, __float_as_uint(S[1][0]), __float_as_uint(S[1][1]), __float_as_uint(S[2][0]), __float_as_uint(S[2][1]));
        sts128(sxw + 512, __float_as_uint(S[3][0]), __float_as_uint(S[3][1]), __float_as_uint(S[4][0]), __float_as_uint(S[4][1]));
        sts64(sxw + 1024, __float_as_uint(S[0][0]), __float_as_uint(S[0][1]));
        TS(4);
        bar_sync(NB_PAIR + X, 64);
        {
            const uint4 r = lds128(sxr), q = lds128(sxr + 512);
            const uint2 o = lds64(sxr + 1024);
            S[1][0] += __uint_as_float(r.x); S[1][1] += __uint_as_float(r.y); S[2][0] += __uint_as_float(r.z); S[2][1] += __uint_as_float(r.w);
            S[3][0] += __uint_as_float(q.x); S[3][1] += __uint_as_float(q.y); S[4][0] += __uint_as_float(q.z); S[4][1] += __uint_as_float(q.w);
            S[0][0] += __uint_as_float(o.x); S[0][1] += __uint_as_float(o.y);
        }
        float m = fmaxf(fmaxf(fmaxf(S[1][0], S[1][1]), fmaxf(S[2][0], S[2][1])), fmaxf(fmaxf(S[3][0], S[3][1]), fmaxf(S[4][0], S[4][1])));
        m = fmaxf(m, fmaxf(S[0][0], S[0][1]));
        m = fmaxf(m, __shfl_xor_sync(0xffffffffu, m, 1));
        m = fmaxf(m, __shfl_xor_sync(0xffffffffu, m, 2));
        uint4 V[2][4];
#pragma unroll
        for (int i = 0; i < 8; i++) V[i >> 2][i & 3] = lds128(ta + 8192 + (i >> 2) * 4096 + (i & 3) * 512);
        TS(5);
        mbar_wait(bar + RB_V * 8, s & 1);
        TS(6);
        uint32_t vm[4][2];
#pragma unroll
        for (int t = 0; t < 4; t++) {
            const uint2 a = lds64(la + vo + t * 256), b = lds64(ra + vo + t * 256);
            vm[t][0] = hadd2(a.x, b.x); vm[t][1] = hadd2(a.y, b.y);
        }
        m *= -SC_LOG2E;
        uint32_t P[5];
#pragma unroll
        for (int i = 1; i < 6; i++) P[i % 5] = pack2(ex2(fmaf(S[i % 5][0], SC_LOG2E, m)), ex2(fmaf(S[i % 5][1], SC_LOG2E, m)));
        float o[4][4], l[4] = {0, 0, 0, 0};
        const uint32_t ONE = 0x3f803f80u;
#pragma unroll
        for (int t = 0; t < 4; t++) { o[t][0] = o[t][1] = o[t][2] = o[t][3] = 0; mma16(o[t], V[0][t].x, V[0][t].y, V[0][t].z, V[0][t].w, P[1], P[2]); }
        mma16_top(l, ONE, ONE, P[1], P[2]);
#pragma unroll
        for (int t = 0; t < 4; t++) mma16(o[t], V[1][t].x, V[1][t].y, V[1][t].z, V[1][t].w, P[3], P[4]);
        mma16_top(l, ONE, ONE, P[3], P[4]);
        mma8(l, ONE, ONE, P[0]);
#pragma unroll
        for (int t = 0; t < 4; t++) mma8(o[t], vm[t][0], vm[t][1], P[0]);
        if (j == 0) sts64(lw + R_IL + X * 8, __float_as_uint(rcp(l[0])), __float_as_uint(rcp(l[1])));
#pragma unroll
        for (int t = 0; t < 4; t += 2)
            asm volatile("stmatrix.sync.aligned.m8n8.x4.trans.shared.b16 [%0],{%1,%2,%3,%4};" ::"r"(lw + R_O + X * 2048 + j * 1024 + t * 256),
                         "r"(pack2(o[t][0], o[t][1])), "r"(pack2(o[t][2], o[t][3])), "r"(pack2(o[t + 1][0], o[t + 1][1])), "r"(pack2(o[t + 1][2], o[t + 1][3])) : "memory");
        bar_arrive(NB_O + X, 320);
        TS(7);
#pragma unroll
        for (int t = 0; t < 4; t += 2) sts128(ra + t * 256, u[t].z, u[t].w, u[t + 1].z, u[t + 1].w);
        if (elect()) { mbar_expect(bar + RB_QK * 8, 2048); mbar_expect(bar + RB_V * 8, 1024); if (s) rec_publish(X, s - 1); }
        bool early = !j && s < 63 && !LATET;
        if (early && (s & 3) == 3) early = chunk_ready(X, s + 1);
        if (XG) bar_sync(NB_XG + X, 320); else bar_sync(NB_PAIR + X, 64);
        TS(8);
        if (rank) rec_xattn<1>(k, sb, lane, ta, ra, sxw, sxr, X, j, s, head, early, V, vm); else rec_xattn<0>(k, sb, lane, ta, ra, sxw, sxr, X, j, s, head, early, V, vm);
        fence_async_smem();
        __syncwarp();
        if (elect()) {
            asm volatile("cp.async.bulk.global.shared::cta.bulk_group.L2::cache_hint [%0],[%1],%2,%3;" ::"l"(g_o[X] + ((s >> 2) * 64 + head * 2 + j) * 1024 + ((s & 3) * 2 + rank) * 128),
                         "r"(sb + R_SX + (X * 2 + (j ^ 1)) * 2560), "r"(2048), "l"((X && s < 40) ? POL_LATE : POL_SOON) : "memory");
            asm volatile("cp.async.bulk.global.shared::cta.bulk_group [%0],[%1],%2;" ::"l"(zp + acc_slot(s + 2)), "r"(sb + R_Z), "r"(j ? 128 : 32) : "memory");
            asm volatile("cp.async.bulk.commit_group;" ::: "memory");
        }
        TS(10);
        if (!j && s < 63 && !early) {
            wait_cnt_warp(cnt_ptr(C_QKV0 + X, (s + 1) >> 2), 384);
            if (lane == 0) rec_load_tile(sb, X, s + 1, head, rank);
        }
        __syncwarp();
        TS(11);
    }
    if (elect()) rec_publish(X, 63);
}

__device__ __forceinline__ void rec_init(const Params& p, uint32_t sb, int head, uint32_t rank) {
    const uint32_t b = sb + R_BAR;
    const int i = threadIdx.x - 320;
    if (i >= 0 && i < RB_N) {
        mbar_init(b + i * 8, 1);
        asm volatile("fence.mbarrier_init.release.cluster;" ::: "memory");
    }
    if (i == 0) mbar_expect(b + RB_INIT * 8, 196608);
    if (i >= 0 && i < 32) sts32(sb + R_Z + i * 4, 0);
}

constexpr int NSTG = 4, STG_B = 49152;
constexpr int NSB = 7;
constexpr int B_OUT = NSTG * STG_B  , B_UT = B_OUT, B_YT = B_UT + 8192  ,
              B_ST = B_OUT + 8 * NSB * 512  , B_BAR = 231936;
static_assert(B_ST + 4096 <= B_BAR && B_YT + 10240 <= B_ST, "smem map");
enum { BB_FULL = 0, BB_EMPTY = 4, BB_STF = 8  , BB_STE = 10  , BB_SF = 12  , BB_DONE = 13  , BB_N = 15 };
enum { NB_C = 11, NB_WG = 12   };

__device__ __forceinline__ void bulk_init(uint32_t sb) {
    const int i = threadIdx.x - 320;
    if (i >= 0 && i < BB_N) {
        mbar_init(sb + B_BAR + i * 8, (i >= BB_EMPTY && i < BB_EMPTY + 4) ? 4 : (i >= BB_STF && i < BB_STF + 2) ? 2 : i >= BB_DONE ? 8 : 1);
        asm volatile("fence.mbarrier_init.release.cluster;" ::: "memory");
    }
}

__device__ __forceinline__ void bulk_producer(const Params& p, uint32_t sb, int cl, uint32_t rank) {
    if (threadIdx.x != 256) return;
    int st = 0; uint32_t ph = 1;
    bool gated = false;
#pragma unroll 1
    for (int ti = 0; ti < MAXT; ti++) {
        const uint32_t tk = p.task[cl][ti];
        const int type = tk & 7, layer = (tk >> 3) & 1, ch = (tk >> 4) & 15, a = (tk >> 8) & 255, b = (tk >> 16) & 255;
        if (type == T_END) break;
        if (type == T_QKV || type == T_OP) {
            const bool qkv = type == T_QKV, first = qkv && !layer;
            const uint4* A = (qkv ? g_xA[layer] + ch * 8192 : g_o[layer] + (ch * 64 + a) * 1024) + rank * 512;
            const int nkb = qkv ? 8 : b, blk = (qkv ? a : 192) + rank * 4, row = qkv ? 0 : a * 64;
            const unsigned* dep = first ? g_gate : cnt_ptr(qkv ? C_CV : C_O0 + layer, ch);
            const unsigned need = first ? lds32(sb + S_GATE) : qkv ? 16 : 512;
            int pend = 0;
            if (!(tk >> 31) && !(first && gated)) {
                unsigned v;
                asm volatile("ld.relaxed.gpu.global.u32 %0,[%1];" : "=r"(v) : "l"(dep) : "memory");
                if (v < need) pend = first ? 2 : NSTG;
                gated = true;
            }
#pragma unroll 1
            for (int kb = 0; kb < nkb; kb++) {
                mbar_wait(sb + B_BAR + (BB_EMPTY + st) * 8, ph);
                mbar_expect(sb + B_BAR + (BB_FULL + st) * 8, STG_B);
                tma3d(sb + st * STG_B + 16384, &p.t3[blk >> 6], row + kb * 64, blk & 63, sb + B_BAR + (BB_FULL + st) * 8);
                int k = kb;
                if (kb == pend - 1) { wait_cnt(dep, need); k = 0; }
                if (kb >= pend - 1) {
#pragma unroll 1
                    for (; k <= kb; k++) {
                        const int s2 = (st + k - kb) & (NSTG - 1);
                        bulk_g2s_mc(sb + s2 * STG_B + rank * 8192, A + k * 1024, 8192, sb + B_BAR + (BB_FULL + s2) * 8, qkv ? POL_N : POL_LAST);
                    }
                }
                if (++st == NSTG) { st = 0; ph ^= 1; }
            }
        } else if (type == T_CV) {
            const int q = a + rank, jhi = layer ? b : min(ch, 1), jlo = layer ? (tk >> 24) & 127 : 0;
            if (jhi && !(tk >> 31)) wait_cnt(cnt_ptr(C_CV, ch - (layer ? jlo : 1)), 16);
            if (!layer && ch) {
                const int n = min(ch, 3);
                const uint32_t full = sb + B_BAR + (BB_FULL + st) * 8;
                mbar_wait(sb + B_BAR + (BB_EMPTY + st) * 8, ph);
                mbar_expect(full, n * 16384);
#pragma unroll 1
                for (int i = 0; i < n; i++) {
                    if (i && !(tk >> 31)) wait_cnt(cnt_ptr(C_H, ch - (i != 1)), ch - (i != 1) >= HSPLIT ? 32 : 16);
                    bulk_g2s(sb + st * STG_B + i * 16384, g_carry[i] + ((ch - (i != 1)) * 16 + q) * 1024, 16384, full, POL_LAST);
                }
                if (++st == NSTG) { st = 0; ph ^= 1; }
            }
#pragma unroll 1
            for (int j = jhi; j >= jlo; j--) {
                const uint32_t full = sb + B_BAR + (BB_FULL + st) * 8, dst = sb + st * STG_B;
                mbar_wait(sb + B_BAR + (BB_EMPTY + st) * 8, ph);
                mbar_expect(full, 32 * PW * 4 + (j ? 8192 : 0));
                bulk_g2s(dst, g_P + (q * 16 + j) * 32 * PW, 32 * PW * 4, full, POL_N);
                if (j) bulk_g2s(dst + 20480, g_u + (q * 16 + ch - j) * 512, 8192, full, POL_N);
                if (++st == NSTG) { st = 0; ph ^= 1; }
            }
        }
    }
}

__device__ __forceinline__ void bulk_stats(const Params& p, uint32_t sb, int cl, uint32_t rank) {
    const int r0 = threadIdx.x - 288;
    int n = 0;
    bool gated = false;
    for (int ti = 0; ti < MAXT; ti++) {
        const uint32_t tk = p.task[cl][ti];
        const int type = tk & 7, layer = (tk >> 3) & 1, ch = (tk >> 4) & 15;
        if (type == T_END) break;
        if (type != T_QKV) continue;
        if (!(tk >> 31)) {
            if (!gated) { wait_cnt_warp(g_gate, lds32(sb + S_GATE)); gated = true; }
            wait_cnt_warp(cnt_ptr(layer ? C_CV : C_ST, ch), 16);
        }
        const int np = p.nst[layer];
        const float n0 = 512.f / np, in0 = np * (1.f / 512.f);
        mbar_wait(sb + B_BAR + (BB_STE + (n & 1)) * 8, ((n >> 1) & 1) ^ 1);
        {
            const int nb = (tk >> 16) & 255;
            if (r0 < nb * 16) {
                const float4* cp = (const float4*)g_cs + (((tk >> 8) & 255) + rank * nb) * 16 + r0;
                const float4 cs = __ldcg(cp), ct = __ldcg(cp + 3072);
                sts128(sb + B_ST + (n & 1) * 2048 + 1024 + r0 * 16, __float_as_uint(cs.x + ct.x), __float_as_uint(cs.y + ct.y), __float_as_uint(cs.z + ct.z), __float_as_uint(cs.w + ct.w));
            }
        }
        const float4* src = (const float4*)(g_st[layer] + ch * 128) + r0;
        const float4 f = __ldcg(src);
        const float m0 = f.x * in0, m1 = f.z * in0;
        float sd0 = 0, sq0 = 0, M0 = f.y, sd1 = 0, sq1 = 0, M1 = f.w;
#pragma unroll 5
        for (int i = 1; i < np; i++) {
            const float4 v = __ldcg(src + i * 1024);
            const float d0 = v.x * in0 - m0, d1 = v.z * in0 - m1;
            sd0 += d0; sq0 += d0 * d0; M0 += v.y; sd1 += d1; sq1 += d1 * d1; M1 += v.w;
        }
        const float b0 = sd0 / np, b1 = sd1 / np;
        const float2 o0 = ln_finish(m0 + b0, (M0 + fmaxf(n0 * (sq0 - np * b0 * b0), 0.f)) * (1.f / 512.f));
        const float2 o1 = ln_finish(m1 + b1, (M1 + fmaxf(n0 * (sq1 - np * b1 * b1), 0.f)) * (1.f / 512.f));
        sts128(sb + B_ST + (n & 1) * 2048 + r0 * 16, __float_as_uint(o0.x), __float_as_uint(1.f / o0.y), __float_as_uint(o1.x), __float_as_uint(1.f / o1.y));
        __syncwarp();
        if ((r0 & 31) == 0) mbar_arrive(sb + B_BAR + (BB_STF + (n & 1)) * 8);
        n++;
    }
}

__device__ __forceinline__ uint4* qkv_dst(int layer, int ch, int w, int blk);
__device__ __forceinline__ uint4* op_dst(int layer, int ch, int slot, int w, uint32_t rank);
__device__ __forceinline__ uint64_t out_pol(int type, int layer, int ch) { return (type == T_QKV ? (!layer && ch > 1) : (layer && ch < 10)) ? POL_LATE : POL_SOON; }
__device__ __forceinline__ void bulk_release(const Params& p, uint32_t sb, int cl, uint32_t rank) {
    if ((threadIdx.x & 31) != 0) return;
    int nd = 0, nq = 0;
    for (int ti = 0; ti < MAXT; ti++) {
        const uint32_t tk = p.task[cl][ti];
        const int type = tk & 7, layer = (tk >> 3) & 1, ch = (tk >> 4) & 15, a = (tk >> 8) & 255, b = (tk >> 16) & 255;
        if (type == T_END) break;
        if (type == T_FIN) continue;
        mbar_wait(sb + B_BAR + (BB_DONE + (nd & 1)) * 8, (nd >> 1) & 1);
        nd++;
        if (type == T_QKV) { mbar_arrive(sb + B_BAR + (BB_STE + (nq & 1)) * 8); nq++; }
        if (type != T_CV) {
#pragma unroll 1
            for (int w = 0; w < 8; w++) {
                const uint4* dst = type == T_QKV ? qkv_dst(layer, ch, w, a + rank * 4 + 2) + (8 - NSB) * 32 : op_dst(layer, ch, (tk >> 24) & 127, w, rank) + (16 - NSB) * 32;
                asm volatile("cp.async.bulk.global.shared::cta.bulk_group.L2::cache_hint [%0],[%1],%2,%3;" ::"l"(dst), "r"(sb + B_OUT + w * NSB * 512), "r"(NSB * 512), "l"(out_pol(type, layer, ch)) : "memory");
            }
            asm volatile("cp.async.bulk.commit_group;" ::: "memory");
            asm volatile("cp.async.bulk.wait_group 0;" ::: "memory");
        }
        mbar_arrive(sb + B_BAR + BB_SF * 8);
        if (!(tk >> 31)) red_release(cnt_ptr(type == T_QKV ? C_QKV0 + layer : type == T_OP ? C_OP0 + layer : layer ? C_H : C_CV, ch), type == T_CV ? 1 : 2 * b);
        PROF(true, 3600 + ti * 4 + 3);
    }
}

template <int NB>
__device__ __forceinline__ void gemm_main(float* acc, uint32_t sb, uint32_t peer, int nkb, int& st, uint32_t& ph) {
    const int wg = threadIdx.x >> 7;
    const bool el = (threadIdx.x & 127) == 0;
    int prev = -1;
#pragma unroll
    for (int i = 0; i < NB * 32; i++) acc[i] = 0.f;
#pragma unroll 1
    for (int kb = 0; kb < nkb; kb++) {
        mbar_wait(sb + B_BAR + (BB_FULL + st) * 8, ph);
        const uint64_t da = mkdesc(sb + st * STG_B + wg * 8192, 128, 1024, 0), db = mkdesc(sb + st * STG_B + 16384, 8192, 1024, 1);
        wg_fence();
#pragma unroll
        for (int kk = 0; kk < 4; kk++) {
            if (NB == 4) wgmma256(acc, da + kk * 16, db + kk * 128, kb | kk);
            else wgmma192(acc, da + kk * 16, db + kk * 128, kb | kk);
        }
        wg_commit();
        wg_wait<1>();
        if (prev >= 0) {
            if (el) { mbar_arrive_cluster(mapa(sb + B_BAR + (BB_EMPTY + prev) * 8, 0)); mbar_arrive_cluster(mapa(sb + B_BAR + (BB_EMPTY + prev) * 8, 1)); }
        }
        prev = st;
        if (++st == NSTG) { st = 0; ph ^= 1; }
    }
    wg_wait<0>();
    if (el) { mbar_arrive_cluster(mapa(sb + B_BAR + (BB_EMPTY + prev) * 8, 0)); mbar_arrive_cluster(mapa(sb + B_BAR + (BB_EMPTY + prev) * 8, 1)); }
}

__device__ __forceinline__ uint4* qkv_dst(int layer, int ch, int w, int blk) {
    return g_qkv[layer] + (size_t)((ch * 4 + (w >> 1)) * 32 + ((blk & 63) >> 1)) * 1536 + (blk >> 6) * 512 + (w & 1) * 256;
}
__device__ __forceinline__ uint4* op_dst(int layer, int ch, int slot, int w, uint32_t rank) {
    return g_pp[layer] + (size_t)(ch * MAXSPLIT + slot) * 8192 + (w * 32 + rank * 16) * 32;
}
template <bool VT>
__device__ __forceinline__ void qkv_epilogue(const float* acc, uint32_t sb, int layer, int ch, int blk0, int n, int nd) {
    const bool isk = blk0 >= 64;
    const int lane = threadIdx.x & 31, w = threadIdx.x >> 5, g = lane >> 2, c = lane & 3;
    mbar_wait(sb + B_BAR + (BB_STF + (n & 1)) * 8, (n >> 1) & 1);
    mbar_wait(sb + B_BAR + BB_SF * 8, (nd & 1) ^ 1);
    const uint32_t stb = sb + B_ST + (n & 1) * 2048;
    const uint2 s0 = lds64(stb + (w * 16 + g) * 8), s1 = lds64(stb + (w * 16 + g + 8) * 8);
    const float mu0 = -__uint_as_float(s0.x), r0 = __uint_as_float(s0.y), mu1 = -__uint_as_float(s1.x), r1 = __uint_as_float(s1.y);
    uint32_t dep = 0; asm volatile("" : "+r"(dep)::"memory");
    uint4* dst = qkv_dst(layer, ch, w, blk0) + lane;
    const uint64_t pol = out_pol(T_QKV, layer, ch);
#pragma unroll
    for (int j = 0; j < 16; j++) {
        const float* a = acc + j * 8;
        float2 ca, cb;
        asm("ld.shared.v2.f32 {%0,%1},[%2];" : "=f"(ca.x), "=f"(ca.y) : "r"(stb + 1024 + (j * 16 + 2 * c) * 4 + dep));
        asm("ld.shared.v2.f32 {%0,%1},[%2];" : "=f"(cb.x), "=f"(cb.y) : "r"(stb + 1024 + (j * 16 + 8 + 2 * c) * 4 + dep));
        uint4 v;
        v.x = pack2(fmaf(mu0, ca.x, a[0]) * r0, fmaf(mu0, ca.y, a[1]) * r0);
        v.y = pack2(fmaf(mu1, ca.x, a[2]) * r1, fmaf(mu1, ca.y, a[3]) * r1);
        v.z = pack2(fmaf(mu0, cb.x, a[4]) * r0, fmaf(mu0, cb.y, a[5]) * r0);
        v.w = pack2(fmaf(mu1, cb.x, a[6]) * r1, fmaf(mu1, cb.y, a[7]) * r1);
        if (VT) v = make_uint4(movm(v.x), movm(v.z), movm(v.y), movm(v.w));
        else if (isk) v = make_uint4(v.x, v.z, v.y, v.w);
        if (j < 16 - NSB) stg128(dst + (j >> 3) * 1536 + (j & 7) * 32, v, pol);
        else asm volatile("st.shared.v4.u32 [%0],{%1,%2,%3,%4};" ::"r"(sb + B_OUT + (w * NSB + j - (16 - NSB)) * 512 + lane * 16), "r"(v.x), "r"(v.y), "r"(v.z), "r"(v.w));
    }
    fence_async_smem();
}

template <int NB>
__device__ __forceinline__ void load_resid(uint32_t* r, int layer, int ch, int w, int cb) {
    const uint32_t* rp = (const uint32_t*)(g_xA[layer] + (ch * 8 + (cb >> 2)) * 1024 + w * 128 + (cb & 3) * 16) + (threadIdx.x & 31);
#pragma unroll
    for (int i = 0; i < NB * 4; i++) r[i] = __ldcg(rp + (i >> 1) * 32 + (i & 1) * 256);
}
template <int NB, int NS>
__device__ __forceinline__ void sum_partials(float* x, const uint32_t* r, int layer, int ch, int w, int cb, int ns) {
    const uint4* src = g_pp[layer] + (size_t)ch * MAXSPLIT * 8192 + (w * 32 + cb) * 32 + (threadIdx.x & 31);
    const int dg = ((threadIdx.x & 31) >> 2) - 2 * (threadIdx.x & 3);
    const uint32_t idm = dg == 0 ? 0x00003f80u : dg == 1 ? 0x3f800000u : 0u;
    uint4 v[NB][NS];
#pragma unroll
    for (int b = 0; b < NB; b++)
#pragma unroll
        for (int s = 0; s < NS; s++) { v[b][s] = make_uint4(0, 0, 0, 0); if (s < ns) v[b][s] = ldcg128_last(src + b * 32 + s * 8192); }
#pragma unroll
    for (int b = 0; b < NB; b++) {
        float* y = x + b * 8;
#pragma unroll
        for (int i = 0; i < 8; i++) y[i] = 0;
#pragma unroll
        for (int s = 0; s < NS; s++) { mma8(y, v[b][s].x, v[b][s].y, idm); mma8(y + 4, v[b][s].z, v[b][s].w, idm); }
#pragma unroll
        for (int i = 0; i < 4; i++) { y[2 * i] = rbf(rbf(y[2 * i]) + blo(r[b * 4 + i])); y[2 * i + 1] = rbf(rbf(y[2 * i + 1]) + bhi(r[b * 4 + i])); }
    }
}

__device__ __forceinline__ float4 row_stats32(const float* x) {
    float a = (x[0] + x[1]) + (x[4] + x[5]) + (x[8] + x[9]) + (x[12] + x[13]);
    float b = (x[2] + x[3]) + (x[6] + x[7]) + (x[10] + x[11]) + (x[14] + x[15]);
    a += __shfl_xor_sync(0xffffffffu, a, 1); b += __shfl_xor_sync(0xffffffffu, b, 1);
    a += __shfl_xor_sync(0xffffffffu, a, 2); b += __shfl_xor_sync(0xffffffffu, b, 2);
    const float ma = a * (1.f / 32.f), mb = b * (1.f / 32.f);
    float qa = 0, qb = 0;
#pragma unroll
    for (int i = 0; i < 4; i++) {
        float d0 = x[4 * i] - ma, d1 = x[4 * i + 1] - ma, d2 = x[4 * i + 2] - mb, d3 = x[4 * i + 3] - mb;
        qa += d0 * d0 + d1 * d1; qb += d2 * d2 + d3 * d3;
    }
    qa += __shfl_xor_sync(0xffffffffu, qa, 1); qb += __shfl_xor_sync(0xffffffffu, qb, 1);
    qa += __shfl_xor_sync(0xffffffffu, qa, 2); qb += __shfl_xor_sync(0xffffffffu, qb, 2);
    return make_float4(a, qa, b, qb);
}

__device__ __forceinline__ void conv_stage(float* Y, uint32_t pbase, uint32_t ubase) {
    const int lane = threadIdx.x & 31, w = threadIdx.x >> 5, g = lane >> 2, c = lane & 3;
#pragma unroll
    for (int cp = 0; cp < 2; cp++) {
        const int chl = w * 4 + cp * 2 + (lane >> 4);
        const uint4 b = ldsm4(ubase + chl * 256 + ((lane >> 3) & 1) * 128 + (((lane & 7) ^ (chl & 7)) << 4));
#pragma unroll
        for (int h = 0; h < 2; h++) {
            const uint32_t pa = pbase + ((w * 4 + cp * 2 + h) * PW + 16 + g - 2 * c) * 4;
            uint32_t lo = lds32(pa - 32);
#pragma unroll
            for (int d = 0; d < 8; d++) {
                const uint32_t a0 = lds32(pa + d * 64), a1 = lds32(pa + d * 64 + 32);
                mma16(Y + ((cp * 2 + h) * 8 + d) * 4, a0, a1, lo, a0, h ? b.z : b.x, h ? b.w : b.y);
                lo = a1;
            }
        }
    }
}

__device__ __forceinline__ void conv_combine(const float* y8, float* cur, float* nxt) {
    const int lane = threadIdx.x & 31, c = lane & 3;
    cur[0] = y8[0]; cur[1] = y8[1] + y8[4]; cur[2] = y8[2]; cur[3] = y8[3] + y8[6];
    nxt[0] = y8[29]; nxt[1] = 0.f; nxt[2] = y8[31]; nxt[3] = 0.f;
#pragma unroll
    for (int e = 1; e < 4; e++) {
        const int src = (lane & ~3) | ((c - e) & 3);
        const float v0 = __shfl_sync(0xffffffffu, y8[8 * e] + y8[8 * e - 3], src), v1 = __shfl_sync(0xffffffffu, y8[8 * e + 1] + y8[8 * e + 4], src);
        const float v2 = __shfl_sync(0xffffffffu, y8[8 * e + 2] + y8[8 * e - 1], src), v3 = __shfl_sync(0xffffffffu, y8[8 * e + 3] + y8[8 * e + 6], src);
        if (c >= e) { cur[0] += v0; cur[1] += v1; cur[2] += v2; cur[3] += v3; }
        else { nxt[0] += v0; nxt[1] += v1; nxt[2] += v2; nxt[3] += v3; }
    }
}

__device__ __forceinline__ void conv_task(const Params& p, float* Y, uint32_t sb, int ch, int q, bool hist, int hhi, int hlo, bool dry, int& st, uint32_t& ph, int nd) {
    const int tid = threadIdx.x, lane = tid & 31, w = tid >> 5, g = lane >> 2, c = lane & 3;
    const bool el = (tid & 127) == 0;
#pragma unroll
    for (int i = 0; i < 128; i++) Y[i] = 0;
    const int jhi = hist ? hhi : min(ch, 1), jlo = hist ? hlo : 1;
    uint32_t rs[8], dk[4];
    if (!hist) {
        load_resid<2>(rs, 0, ch, w, 2 * q);
#pragma unroll
        for (int i = 0; i < 4; i++) dk[i] = __ldg((const uint32_t*)(p.Dskip + q * 32 + i * 8 + 2 * c));
        if (ch) {
            mbar_wait(sb + B_BAR + (BB_FULL + st) * 8, ph);
#pragma unroll 1
            for (int i = 0; i < 3 && i < ch; i++) {
#pragma unroll
                for (int k = 0; k < 4; k++) {
                    const uint4 cr = lds128(sb + st * STG_B + i * 16384 + k * 4096 + tid * 16);
                    Y[k * 32] += __uint_as_float(cr.x); Y[k * 32 + 1] += __uint_as_float(cr.y); Y[k * 32 + 2] += __uint_as_float(cr.z); Y[k * 32 + 3] += __uint_as_float(cr.w);
                }
            }
            bar_sync(NB_WG + (w >> 2), 128);
            if (el) { mbar_arrive_cluster(mapa(sb + B_BAR + (BB_EMPTY + st) * 8, 0)); mbar_arrive_cluster(mapa(sb + B_BAR + (BB_EMPTY + st) * 8, 1)); }
            if (++st == NSTG) { st = 0; ph ^= 1; }
        }
    }
    for (int j = jhi; j >= jlo; j--) {
        mbar_wait(sb + B_BAR + (BB_FULL + st) * 8, ph);
        conv_stage(Y, sb + st * STG_B, sb + st * STG_B + 20480);
        bar_sync(NB_WG + (w >> 2), 128);
        if (el) { mbar_arrive_cluster(mapa(sb + B_BAR + (BB_EMPTY + st) * 8, 0)); mbar_arrive_cluster(mapa(sb + B_BAR + (BB_EMPTY + st) * 8, 1)); }
        if (++st == NSTG) { st = 0; ph ^= 1; }
    }
    mbar_wait(sb + B_BAR + BB_SF * 8, (nd & 1) ^ 1);
    if (hist) {
        if (jhi < ch) wait_cnt_warp(cnt_ptr(C_H, ch), 16);
#pragma unroll
        for (int k = 0; k < 4; k++) {
            float4* d1 = g_carry[1] + ((ch * 16 + q) * 4 + k) * 256 + tid;
            float4* d2 = g_carry[2] + ((ch * 16 + q) * 4 + k) * 256 + tid;
            float4 o1 = make_float4(0, 0, 0, 0), o2 = o1;
            if (jhi < ch) { o1 = __ldcg(d1); o2 = __ldcg(d2); }
            float cur[4], nxt[4];
            conv_combine(Y + k * 32, cur, nxt);
            *d1 = make_float4(cur[0] + o1.x, cur[1] + o1.y, cur[2] + o1.z, cur[3] + o1.w);
            *d2 = make_float4(nxt[0] + o2.x, nxt[1] + o2.y, nxt[2] + o2.z, nxt[3] + o2.w);
        }
        return;
    }
    mbar_wait(sb + B_BAR + (BB_FULL + st) * 8, ph);
    wait_cnt_warp(cnt_ptr(C_OP0, ch), dry ? 0 : 256);
    PROF(tid == 0, 2048 + ch * 8);
    float x[16];
    sum_partials<2, OPS1>(x, rs, 0, ch, w, 2 * q, OPS1);
    if (x[0] == 1.2345e30f) PROF(true, 0);
    PROF(tid == 0, 2048 + ch * 8 + 1);
    float2 ln0, ln1;
    {
        const float4 s = row_stats32(x);
        float2* dst = g_st2 + (ch * 16 + q) * 128 + w * 16 + g;
        if (c == 0 && !dry) asm volatile("st.relaxed.gpu.global.b64 [%0],%1;" ::"l"(dst), "l"(((uint64_t)__float_as_uint(s.y) << 32) | __float_as_uint(s.x)) : "memory");
        if (c == 1 && !dry) asm volatile("st.relaxed.gpu.global.b64 [%0],%1;" ::"l"(dst + 8), "l"(((uint64_t)__float_as_uint(s.w) << 32) | __float_as_uint(s.z)) : "memory");
        const float2* src = g_st2 + (ch * 16 + (lane >> 4) * 8) * 128 + w * 16 + (lane & 15);
        uint64_t v[8];
        int n = 0;
        while (true) {
            bool bad = false;
#pragma unroll
            for (int i = 0; i < 8; i++) asm volatile("ld.relaxed.gpu.global.b64 %0,[%1];" : "=l"(v[i]) : "l"(src + i * 128) : "memory");
#pragma unroll
            for (int i = 0; i < 8; i++) bad = bad || (uint32_t)(v[i] >> 32) == 0xffffffffu;
            if (!__any_sync(0xffffffffu, bad && !dry)) break;
            if (++n > 2000000) __trap();
        }
        float sm = 0;
#pragma unroll
        for (int i = 0; i < 8; i++) sm += __uint_as_float((uint32_t)v[i]);
        sm += __shfl_xor_sync(0xffffffffu, sm, 16);
        const float mean = sm * (1.f / 512.f);
        float M2 = 0;
#pragma unroll
        for (int i = 0; i < 8; i++) { const float d = __uint_as_float((uint32_t)v[i]) * (1.f / 32.f) - mean; M2 += __uint_as_float((uint32_t)(v[i] >> 32)) + 32.f * d * d; }
        M2 += __shfl_xor_sync(0xffffffffu, M2, 16);
        const float2 o = ln_finish(mean, M2 * (1.f / 512.f));
        ln0.x = __shfl_sync(0xffffffffu, o.x, g); ln0.y = __shfl_sync(0xffffffffu, o.y, g);
        ln1.x = __shfl_sync(0xffffffffu, o.x, g + 8); ln1.y = __shfl_sync(0xffffffffu, o.y, g + 8);
    }
    PROF(tid == 0, 2048 + ch * 8 + 2);
    uint32_t u[8];
#pragma unroll
    for (int i = 0; i < 8; i++) {
        const float2 l = (i & 1) ? ln1 : ln0;
        u[i] = pack2(__fdividef(rbf(x[2 * i] - l.x), l.y), __fdividef(rbf(x[2 * i + 1] - l.x), l.y));
        const int chl = (i >> 1) * 8 + g;
        sts32(sb + B_UT + chl * 256 + (i & 1) * 128 + ((w ^ g) << 4) + c * 4, movm(u[i]));
    }
    fence_async_smem();
    bar_sync(NB_C, 256);
    if (tid == 0 && ch < 15) {
        asm volatile("cp.async.bulk.global.shared::cta.bulk_group [%0],[%1],%2;" ::"l"(g_u + (q * 16 + ch) * 512), "r"(sb + B_UT), "r"(8192) : "memory");
        asm volatile("cp.async.bulk.commit_group;" ::: "memory");
    }
    PROF(tid == 0, 2048 + ch * 8 + 3);
    conv_stage(Y, sb + st * STG_B, sb + B_UT);
    uint32_t yp[4][2];
    {
        float y[4][4];
#pragma unroll
        for (int k = 0; k < 4; k++) {
            float nxt[4];
            conv_combine(Y + k * 32, y[k], nxt);
            g_carry[0][((ch * 16 + q) * 4 + k) * 256 + tid] = make_float4(nxt[0], nxt[1], nxt[2], nxt[3]);
        }
#pragma unroll
        for (int i = 0; i < 4; i++) { yp[i][0] = pack2(y[0][i], y[1][i]); yp[i][1] = pack2(y[2][i], y[3][i]); }
    }
#pragma unroll
    for (int i = 0; i < 4; i++) sts64(sb + B_YT + (16 * (2 * c + (i & 1)) + g + (i >> 1) * 8) * 80 + w * 8, yp[i][0], yp[i][1]);
    bar_sync(NB_C, 256);
    if (el) { mbar_arrive_cluster(mapa(sb + B_BAR + (BB_EMPTY + st) * 8, 0)); mbar_arrive_cluster(mapa(sb + B_BAR + (BB_EMPTY + st) * 8, 1)); }
    if (++st == NSTG) { st = 0; ph ^= 1; }
    PROF(tid == 0, 2048 + ch * 8 + 4);
    uint32_t xo[8];
    uint32_t* dA = (uint32_t*)(g_xA[1] + (ch * 8 + (q >> 1)) * 1024 + (w * 2) * 64 + (q & 1) * 32) + lane;
#pragma unroll
    for (int i = 0; i < 8; i++) {
        const int col = (i >> 1) * 8 + 2 * c;
        const uint32_t yv = lds32(sb + B_YT + (w * 16 + g + (i & 1) * 8) * 80 + col * 2);
        const uint32_t dv = dk[i >> 1];
        x[2 * i] = rbf(x[2 * i] + rbf(blo(yv) + rbf(blo(u[i]) * blo(dv))));
        x[2 * i + 1] = rbf(x[2 * i + 1] + rbf(bhi(yv) + rbf(bhi(u[i]) * bhi(dv))));
        xo[i] = pack2(x[2 * i], x[2 * i + 1]);
        dA[(i >> 1) * 32 + (i & 1) * 256] = xo[i];
    }
    {
        const float4 s = row_stats32(x);
        float2* dst = g_st[1] + q * 2048 + ch * 128 + w * 16 + g;
        if (c == 0) dst[0] = make_float2(s.x, s.y);
        if (c == 1) dst[8] = make_float2(s.z, s.w);
    }
    PROF(tid == 0, 2048 + ch * 8 + 5);
    if (tid == 0) asm volatile("cp.async.bulk.wait_group 0;" ::: "memory");
    PROF(tid == 0, 2048 + ch * 8 + 6);
}

template <int NB, int NS>
__device__ __forceinline__ void fin_blocks(const Params& p, int ch, int cb0, int ncb, int ns, bool dry) {
    const int lane = threadIdx.x & 31, w = threadIdx.x >> 5, g = lane >> 2, c = lane & 3;
    uint32_t rs[NB * 4];
    wait_cnt_warp(cnt_ptr(C_CV, ch), dry ? 0 : 16);
    load_resid<NB>(rs, 1, ch, w, cb0);
    wait_cnt_warp(cnt_ptr(C_OP1, ch), dry ? 0 : 256);
    for (int cb = cb0; cb < cb0 + ncb; cb += NB) {
        float x[NB * 8];
        if (cb != cb0) load_resid<NB>(rs, 1, ch, w, cb);
        sum_partials<NB, NS>(x, rs, 1, ch, w, cb, ns);
#pragma unroll
        for (int b = 0; b < NB; b += 2) {
#pragma unroll
            for (int h = 0; h < 2; h++) {
                const float* y = x + b * 8 + h * 2;
                uint32_t v0 = pack2(y[0], y[1]), v1 = pack2(y[4], y[5]), v2 = pack2(y[8], y[9]), v3 = pack2(y[12], y[13]);
                uint32_t t0 = (c & 1) ? v0 : v1, t1 = (c & 1) ? v2 : v3;
                t0 = __shfl_xor_sync(0xffffffffu, t0, 1); t1 = __shfl_xor_sync(0xffffffffu, t1, 1);
                if (c & 1) { v0 = t0; v2 = t1; } else { v1 = t0; v3 = t1; }
                t0 = (c & 2) ? v0 : v2; t1 = (c & 2) ? v1 : v3;
                t0 = __shfl_xor_sync(0xffffffffu, t0, 2); t1 = __shfl_xor_sync(0xffffffffu, t1, 2);
                if (c & 2) { v0 = t0; v1 = t1; } else { v2 = t0; v3 = t1; }
                stg128((uint4*)(p.out + (size_t)(ch * 128 + w * 16 + g + h * 8) * 512 + (cb + b) * 16 + c * 8), make_uint4(v0, v1, v2, v3), POL_LATE);
            }
        }
    }
}
__device__ __forceinline__ void fin_task(const Params& p, int ch, int cb0, int ncb, int nsplit, bool dry) {
    fin_blocks<2, 16>(p, ch, cb0, ncb, nsplit, dry);
}

__device__ __forceinline__ void bulk_consumer(const Params& p, uint32_t sb, int cl, uint32_t rank) {
    int st = 0; uint32_t ph = 0; int nq = 0, nd = 0;
    const uint32_t peer = 0;
    for (int ti = 0; ti < MAXT; ti++) {
        const uint32_t tk = p.task[cl][ti];
        const int type = tk & 7, layer = (tk >> 3) & 1, ch = (tk >> 4) & 15, a = (tk >> 8) & 255, b = (tk >> 16) & 255, cc = (tk >> 24) & 127;
        const bool dry = tk >> 31;
        if (type == T_END) break;
        PROF(threadIdx.x == 0, 3600 + ti * 4);
        if (type == T_QKV || type == T_OP) {
            float acc[128];
            gemm_main<4>(acc, sb, peer, type == T_QKV ? 8 : b, st, ph);
            PROF(threadIdx.x == 0, 3600 + ti * 4 + 1);
            if (type == T_QKV) {
                if (a + rank * 4 >= 128) qkv_epilogue<true>(acc, sb, layer, ch, a + rank * 4, nq, nd); else qkv_epilogue<false>(acc, sb, layer, ch, a + rank * 4, nq, nd);
                nq++;
            } else {
                const int lane = threadIdx.x & 31, w = threadIdx.x >> 5;
                uint4* dst = op_dst(layer, ch, cc, w, rank) + lane;
                mbar_wait(sb + B_BAR + BB_SF * 8, (nd & 1) ^ 1);
#pragma unroll
                for (int j = 0; j < 16; j++) {
                    const uint4 v = make_uint4(pack2(acc[j * 8], acc[j * 8 + 1]), pack2(acc[j * 8 + 2], acc[j * 8 + 3]), pack2(acc[j * 8 + 4], acc[j * 8 + 5]), pack2(acc[j * 8 + 6], acc[j * 8 + 7]));
                    if (j < 16 - NSB) stg128(dst + j * 32, v, out_pol(T_OP, layer, ch)); else sts128(sb + B_OUT + (w * NSB + j - (16 - NSB)) * 512 + lane * 16, v.x, v.y, v.z, v.w);
                }
                fence_async_smem();
            }
        } else if (type == T_CV) {
            float acc[128];
            conv_task(p, acc, sb, ch, a + rank, layer, b, cc, dry, st, ph, nd);
        } else {
            fin_task(p, ch, a + rank * cc, cc, b, dry);
        }
        if (type != T_FIN) {
            __syncwarp();
            if ((threadIdx.x & 31) == 0) mbar_arrive(sb + B_BAR + (BB_DONE + (nd & 1)) * 8);
            nd++;
        }
        PROF(threadIdx.x == 0, 3600 + ti * 4 + 2);
    }
}

constexpr int P_Y = 131072  , P_PRM = P_Y  , P_K6 = P_PRM + 8192  ,
              P_P = P_Y + 40960  , P_U = P_P + 33280  , P_END = P_U + 17408, P_X = 98304  ;
static_assert(P_END <= B_BAR && P_END <= R_BAR, "prologue scratch");
#define KGUN 2
constexpr int KGU = KGUN;
__device__ __forceinline__ void csq(float& r, float& i) { const float t = r * i; r = fmaf(r, r, -(i * i)); i = t + t; }
__device__ __forceinline__ void cpow(float ar, float ph, float p, float& r, float& i) {
    const float e = ex2(ar * p);
    const float u = ph * p, n = fabsf(u) < 4194304.f ? (u + 12582912.f) - 12582912.f : u;
    const float t = (u - n) * 6.283185307179586f;
    r = e * __cosf(t); i = e * __sinf(t);
}
__device__ __forceinline__ void mma_tf32(float* c, float a0, float a1, float a2, float a3, float b0, float b1) {
    asm volatile("mma.sync.aligned.m16n8k8.row.col.f32.tf32.tf32.f32 {%0,%1,%2,%3},{%4,%5,%6,%7},{%8,%9},{%0,%1,%2,%3};"
                 : "+f"(c[0]), "+f"(c[1]), "+f"(c[2]), "+f"(c[3])
                 : "r"(__float_as_uint(a0)), "r"(__float_as_uint(a1)), "r"(__float_as_uint(a2)), "r"(__float_as_uint(a3)), "r"(__float_as_uint(b0)), "r"(__float_as_uint(b1)));
}

struct ProRegs { uint32_t v[2][4], ldt[2]; };
__device__ __forceinline__ void prologue_load(const ProArgs& a, int b, ProRegs& pr) {
    const int w = threadIdx.x >> 5;
#pragma unroll
    for (int i = 0; i < 2; i++) {
        const int gi = b * 512 + (w & 3) * 128 + ((w >> 2) & 1) * 64 + i * 32 + (threadIdx.x & 31);
        pr.ldt[i] = __ldg((const uint16_t*)a.ldt + b * 4 + (w & 3));
        pr.v[i][0] = __ldg((const uint16_t*)a.lAr + gi); pr.v[i][1] = __ldg((const uint16_t*)a.Ai + gi);
        pr.v[i][2] = __ldg((const uint16_t*)a.Cr + gi); pr.v[i][3] = __ldg((const uint16_t*)a.Ci + gi);
    }
}
__device__ __forceinline__ void prologue(const ProArgs& a, uint32_t sb, int b, int w, const ProRegs& pr) {
    const int tid = threadIdx.x, lane = tid & 31, g = lane >> 2, c = lane & 3;
    const int d0 = b * 4;
    if (w >= 8) {
        const int t2 = tid - 256;
        if (w < 10) {
            const int row = b * 16 + (w - 8) * 8 + g;
            const float2 r = row_stats512((const uint4*)(a.x + (size_t)row * 512) + c, 8, 4);
            const float2 l = ln_finish(r.x * (1.f / 512.f), r.y * (1.f / 512.f));
            if (c == (g >> 1)) asm volatile("st.relaxed.gpu.global.u32 [%0],%1;" ::"l"(g_ln0 + row), "r"(pack2(l.x, l.y)) : "memory");
        }
        PROF(t2 == 0, 3516);
        const int gi = b * 128 + t2;
        if (t2 < 32) acc_init(a.mem0, b * 32 + t2);
        ((uint4*)g_st2)[gi] = make_uint4(~0u, ~0u, ~0u, ~0u);
        if (gi < 9 * 16 * 32) g_cnt[gi] = 0;
        bar_sync(6, 384);
        {
            const int u = b * 3 + (w - 8), blk = u >> 1;
            const uint4* W = w < 11 ? (const uint4*)((blk < 64 ? a.Wq : blk < 128 ? a.Wk : a.Wv) + (size_t)((u & 1) * 256 + c) * 4096 + (blk & 63) * 64) + g
                                    : (const uint4*)a.Wo + (size_t)b * 2048 + lane;
            const int st = w < 11 ? 2048 : 32;
            const uint32_t one = (g & 1) ? 0x3f800000u : 0x00003f80u, selA = (g & 2) ? 0u : one, selB = (g & 2) ? one : 0u;
            float s0[4] = {0, 0, 0, 0}, s1[4] = {0, 0, 0, 0};
#pragma unroll 1
            for (int r = 0; r < 8; r++) {
                uint4 v[8];
#pragma unroll
                for (int i = 0; i < 8; i++) v[i] = __ldg(W + (size_t)(r * 8 + i) * st);
#pragma unroll
                for (int i = 0; i < 8; i++) mma16((i & 1) ? s1 : s0, v[i].x, v[i].y, v[i].z, v[i].w, selA, selB);
            }
            if (c < 2) *(float4*)(g_cs + (w < 11 ? (u & 1) * 12288 + blk * 64 : 24576) + g * 8 + c * 4) = make_float4(s0[0] + s1[0], s0[1] + s1[1], s0[2] + s1[2], s0[3] + s1[3]);
        }
        PROF(t2 == 0, 3517);
        return;
    }
#pragma unroll
    for (int i = 0; i < 2; i++) {
        const float dt = rbf(expf(blo(pr.ldt[i])));
        const float ar = -rbf(expf(blo(pr.v[i][0]))) * dt, ai = blo(pr.v[i][1]) * dt;
        sts128(sb + P_PRM + (w * 64 + i * 32 + lane) * 16, __float_as_uint(ar * 1.4426950408889634f), __float_as_uint(ai * 0.15915494309189535f),
               __float_as_uint(2.f * (blo(pr.v[i][2]) * dt)), __float_as_uint(2.f * (blo(pr.v[i][3]) * dt)));
    }
    if (tid < 64) sts128(sb + P_U + (tid >> 3) * 2176 + (tid & 7) * 16, 0, 0, 0, 0);
    bar_arrive(6, 384);
    __syncwarp();
    PROF(tid == 0, 3510);
    const int ch = w & 3, hf = w >> 2;
    {
        float k0[4] = {0, 0, 0, 0}, k1[4] = {0, 0, 0, 0}, k2[4] = {0, 0, 0, 0}, k3[4] = {0, 0, 0, 0}, k4[4] = {0, 0, 0, 0}, kl = 0;
#pragma unroll KGU
        for (int j = 0; j < 16; j++) {
            const uint4 q = lds128(sb + P_PRM + (w * 64 + j * 4 + c) * 16);
            const float cr = __uint_as_float(q.z), ci = __uint_as_float(q.w);
            float wr[4], wi[4], vr[4], vi[4];
            cpow(__uint_as_float(q.x), __uint_as_float(q.y), (float)g, wr[0], wi[0]);
            cpow(__uint_as_float(q.x), __uint_as_float(q.y), (float)(g + 8), vr[0], vi[0]);
#pragma unroll
            for (int i = 1; i < 4; i++) { wr[i] = wr[i - 1]; wi[i] = wi[i - 1]; csq(wr[i], wi[i]); vr[i] = vr[i - 1]; vi[i] = vi[i - 1]; csq(vr[i], vi[i]); }
            float hr = wr[3], hi = wi[3];
            csq(hr, hi);
            mma_tf32(k0, wr[0], vr[0], wi[0], vi[0], cr * hr - ci * hi, -(cr * hi + ci * hr));
            hr = vr[3]; hi = vi[3]; csq(hr, hi);
            mma_tf32(k1, wr[0], vr[0], wi[0], vi[0], cr * hr - ci * hi, -(cr * hi + ci * hr));
            csq(hr, hi);
            mma_tf32(k2, wr[1], vr[1], wi[1], vi[1], cr * hr - ci * hi, -(cr * hi + ci * hr));
            csq(hr, hi);
            mma_tf32(k3, wr[2], vr[2], wi[2], vi[2], cr * hr - ci * hi, -(cr * hi + ci * hr));
            csq(hr, hi);
            mma_tf32(k4, wr[3], vr[3], wi[3], vi[3], cr * hr - ci * hi, -(cr * hi + ci * hr));
            csq(hr, hi);
            kl += cr * hr - ci * hi;
        }
        kl += __shfl_xor_sync(0xffffffffu, kl, 1); kl += __shfl_xor_sync(0xffffffffu, kl, 2);
        const uint32_t o = sb + P_K6 + (ch * 656 + c * 32 + g) * 4, ol = sb + P_K6 + (ch * 656 + 640) * 4;
#define KST(k, base) sts32(o + (base) * 4, __float_as_uint(k[0])); sts32(o + (base) * 4 + 64, __float_as_uint(k[1])); \
                     sts32(o + (base) * 4 + 32, __float_as_uint(k[2])); sts32(o + (base) * 4 + 96, __float_as_uint(k[3]))
#define KAD(k, base) k[0] += __uint_as_float(lds32(o + (base) * 4)); k[1] += __uint_as_float(lds32(o + (base) * 4 + 64)); \
                     k[2] += __uint_as_float(lds32(o + (base) * 4 + 32)); k[3] += __uint_as_float(lds32(o + (base) * 4 + 96))
        if (hf == 0) {
            bar_sync(2 + ch, 64);
            KAD(k0, 0); KAD(k1, 128); KAD(k2, 256); KAD(k3, 384); KAD(k4, 512);
            kl += __uint_as_float(lds32(ol));
            __syncwarp();
        }
        KST(k0, 0); KST(k1, 128); KST(k2, 256); KST(k3, 384); KST(k4, 512);
        if (lane == 0) sts32(ol, __float_as_uint(kl));
        if (hf == 1) { __syncwarp(); bar_arrive(2 + ch, 64); }
    }
    PROF(tid == 0, 3511);
    {
        uint4 l0, l1;
        int n = 0;
        while (true) {
            l0 = ld_rlx128((const uint4*)g_ln0 + tid * 2); l1 = ld_rlx128((const uint4*)g_ln0 + tid * 2 + 1);
            if (__all_sync(0xffffffffu, l0.x && l0.y && l0.z && l0.w && l1.x && l1.y && l1.z && l1.w)) break;
            if (++n > 2000000) __trap();
        }
        sts128(sb + P_P + tid * 32, l0.x, l0.y, l0.z, l0.w); sts128(sb + P_P + tid * 32 + 16, l1.x, l1.y, l1.z, l1.w);
        bar_sync(8, 384);
        mbar_wait(sb + S_XBAR, 0);
        __syncwarp();
#pragma unroll 2
        for (int i = 0; i < 8; i++) {
            const int t = w * 256 + i * 32 + lane;
            const uint32_t ln = lds32(sb + P_P + t * 4);
            const uint2 x = lds64(sb + P_X + t * 16 + (b & 1) * 8);
            const float m = blo(ln), rs = rcp(bhi(ln));
            const uint32_t u0 = pack2(rbf(blo(x.x) - m) * rs, rbf(bhi(x.x) - m) * rs), u1 = pack2(rbf(blo(x.y) - m) * rs, rbf(bhi(x.y) - m) * rs);
            sts128(sb + P_X + t * 16, x.x, x.y, u0, u1);
            const uint32_t o = sb + P_U + ((t >> 3) & 1) * 2176 + ((t >> 4) + 8) * 16 + (t & 7) * 2;
            asm volatile("st.shared.u16 [%0],%1;" ::"r"(o), "h"((uint16_t)u0) : "memory");
            asm volatile("st.shared.u16 [%0],%1;" ::"r"(o + 4352), "h"((uint16_t)(u0 >> 16)) : "memory");
            asm volatile("st.shared.u16 [%0],%1;" ::"r"(o + 8704), "h"((uint16_t)u1) : "memory");
            asm volatile("st.shared.u16 [%0],%1;" ::"r"(o + 13056), "h"((uint16_t)(u1 >> 16)) : "memory");
        }
    }
    bar_sync(1, 256);
    PROF(tid == 0, 3512);
    if (tid < 64) sts32(sb + P_P + ((tid >> 4) * 2080 + (tid & 15)) * 4, 0);
#pragma unroll 1
    for (int x = tid; x < 2048; x += 512) {
        uint32_t pw[2][4];
#pragma unroll
        for (int h = 0; h < 2; h++) {
            const int y = x + h * 256;
            const int i0 = y <= 256 ? y : 256 + (int)((pack2((float)y, 0.f) & 0xffff) - 0x4380);
            const int i1 = y <= 256 ? max(y - 1, 0) : 256 + (int)((pack2((float)(y - 1), 0.f) & 0xffff) - 0x4380);
#pragma unroll
            for (int k = 0; k < 4; k++) {
                const float lo = __uint_as_float(lds32(sb + P_K6 + k * 2624 + i0 * 4)), hi = __uint_as_float(lds32(sb + P_K6 + k * 2624 + i1 * 4));
                pw[h][k] = pack2(lo, y ? hi : 0.f);
            }
        }
#pragma unroll
        for (int h = 0; h < 2; h++)
#pragma unroll
            for (int k = 0; k < 4; k++) sts32(sb + P_P + (k * 2080 + x + h * 256 + 16) * 4, pw[h][k]);
    }
    fence_async_smem();
    bar_sync(1, 256);
    if (lane < 8) {
        const int k = w >> 1, j = (w & 1) * 8 + lane, d = d0 + k;
        asm volatile("cp.async.bulk.global.shared::cta.bulk_group [%0],[%1],%2;" ::"l"(g_P + (((d >> 5) * 16 + j) * 32 + (d & 31)) * PW),
                     "r"(sb + P_P + (k * 2080 + j * 128) * 4), "r"(PW * 4) : "memory");
        asm volatile("cp.async.bulk.commit_group;" ::: "memory");
    }
    __syncwarp();
    PROF(tid == 0, 3513);
    {
        float acc[16][4];
#pragma unroll
        for (int j = 0; j < 16; j++) acc[j][0] = acc[j][1] = acc[j][2] = acc[j][3] = 0;
#pragma unroll 1
        for (int e = hf * 4; e < hf * 4 + 4; e++) {
            uint32_t B[16][2];
            const uint32_t ua = sb + P_U + ch * 4352 + ((lane >> 3) & 1) * 2176 + (8 + (lane >> 4) * 8 + (lane & 7) - e) * 16;
#pragma unroll
            for (int j = 0; j < 8; j++) { const uint4 v = ldsm4(ua + j * 256); B[2 * j][0] = v.x; B[2 * j][1] = v.y; B[2 * j + 1][0] = v.z; B[2 * j + 1][1] = v.w; }
            const uint32_t pa = sb + P_P + (ch * 2080 + 16 + e * 16 + g - 2 * c) * 4;
#pragma unroll
            for (int d = 0; d < 16; d++) {
                const uint32_t a0 = lds32(pa + d * 512), a1 = lds32(pa + d * 512 + 32), a2 = lds32(pa + d * 512 - 32);
#pragma unroll
                for (int j = d; j < 16; j++) mma16(acc[j], a0, a1, a2, a0, B[j - d][0], B[j - d][1]);
            }
        }
        PROF(tid == 0, 3514);
        const uint32_t o = sb + P_Y + (ch * 2560 + c * 40 + g) * 4;
        if (hf == 0) {
            bar_sync(2 + ch, 64);
#pragma unroll
            for (int j = 0; j < 16; j++) {
                acc[j][0] += __uint_as_float(lds32(o + j * 640)); acc[j][1] += __uint_as_float(lds32(o + j * 640 + 80));
                acc[j][2] += __uint_as_float(lds32(o + j * 640 + 32)); acc[j][3] += __uint_as_float(lds32(o + j * 640 + 112));
            }
        }
#pragma unroll
        for (int j = 0; j < 16; j++) {
            sts32(o + j * 640, __float_as_uint(acc[j][0])); sts32(o + j * 640 + 80, __float_as_uint(acc[j][1]));
            sts32(o + j * 640 + 32, __float_as_uint(acc[j][2])); sts32(o + j * 640 + 112, __float_as_uint(acc[j][3]));
        }
        if (hf == 1) bar_arrive(2 + ch, 64);
    }
    const uint2 dk = __ldg((const uint2*)(a.Dk + d0));
    bar_sync(1, 256);
#pragma unroll 2
    for (int i = 0; i < 8; i++) {
        const int t = i * 256 + tid;
        const uint32_t o = sb + P_Y + (t + 4 * (t >> 4)) * 4;
        const uint4 xu = lds128(sb + P_X + t * 16);
        float y[4];
#pragma unroll
        for (int k = 0; k < 4; k++) y[k] = rbf(__uint_as_float(lds32(o + k * 10240)));
        uint2 r;
        r.x = pack2(blo(xu.x) + rbf(y[0] + rbf(blo(xu.z) * blo(dk.x))), bhi(xu.x) + rbf(y[1] + rbf(bhi(xu.z) * bhi(dk.x))));
        r.y = pack2(blo(xu.y) + rbf(y[2] + rbf(blo(xu.w) * blo(dk.y))), bhi(xu.y) + rbf(y[3] + rbf(bhi(xu.w) * bhi(dk.y))));
        ((uint2*)(g_xA[0] + ((t >> 7) * 8 + (d0 >> 6)) * 1024 + ((t & 127) >> 3) * 64 + ((d0 & 63) >> 3) * 8 + (t & 7)))[(d0 >> 2) & 1] = r;
    }
    PROF(tid == 0, 3515);
    if (lane < 8) asm volatile("cp.async.bulk.wait_group 0;" ::: "memory");
}

__global__ void __cluster_dims__(2, 1, 1) __launch_bounds__(384, 1) main_kernel(const __grid_constant__ Params p) {
    extern __shared__ __align__(1024) uint8_t smem[];
    const uint32_t sb = smem_u32(smem);
    uint32_t rank; asm("mov.u32 %0,%%cluster_ctarank;" : "=r"(rank));
    const int wi = __shfl_sync(0xffffffffu, threadIdx.x >> 5, 0);
    const int cl = blockIdx.x >> 1, wg = wi >> 2;
    const bool rec = p.rec0 >= 0 && cl >= p.rec0 && cl < p.rec0 + 32;
    PROF(threadIdx.x == 0, 3500);
    ProRegs pr;
    prologue_load(p.pa, max((int)blockIdx.x - 4, 0), pr);
    if (rec) rec_init(p, sb, cl - p.rec0, rank); else bulk_init(sb);
    if (threadIdx.x == 352 && p.dopro && cl >= 2) {
        mbar_init(sb + S_XBAR, 1);
        asm volatile("fence.mbarrier_init.release.cluster;" ::: "memory");
        mbar_expect(sb + S_XBAR, 32768);
        for (int j = 0; j < 8; j++) tma2d(sb + P_X + j * 4096, &p.tm[3], ((blockIdx.x - 4) >> 1) * 8, j * 256, sb + S_XBAR);
    }
    if (threadIdx.x == 320) {
        unsigned v = 0;
        if (p.dopro) {
            asm volatile("ld.relaxed.gpu.global.u32 %0,[%1];" : "=r"(v) : "l"(g_gate) : "memory");
            v = (v / (4 * NCL) + 1) * (4 * NCL);
        }
        sts32(sb + S_GATE, v);
    }
    __syncwarp();
    asm volatile("barrier.cluster.arrive.relaxed.aligned;" ::: "memory");
    if (wg == 2) bar_arrive(8, 384);
    if (p.dopro && cl >= 2) prologue(p.pa, sb, blockIdx.x - 4, wi, pr); else if (wg < 2) bar_sync(8, 384);
    asm volatile("barrier.cluster.wait.aligned;" ::: "memory");
    fence_async_smem();
    bar_sync(wg == 2 ? 7 : 1, wg == 2 ? 128 : 256);
    if (p.dopro && (threadIdx.x == 32 || threadIdx.x == 352)) red_release(g_gate, 1);
    if (rec) {
        if (threadIdx.x == 0) {
            rec_fetch(&p.tm[1], sb + R_STK, (cl - p.rec0) * 128, rank * 256, 2, sb + R_BAR + RB_INIT * 8);
            rec_fetch(&p.tm[2], sb + R_STV, (cl - p.rec0) * 128, rank * 256, 2, sb + R_BAR + RB_INIT * 8);
        }
    }
    PROF(threadIdx.x == 0, 3506);
    __syncwarp();
    if (rec) {
        const int head = cl - p.rec0;
        if (wg == 2) {
            reg_dec<RH>();
            const int w = wi & 3;
            if (threadIdx.x == 256) rec_fetch(&p.tm[0], sb + R_STQ, head * 128, rank * 256, 2, sb + R_BAR + RB_INIT * 8);
            __syncwarp();
            wait_cnt_warp(g_gate, lds32(sb + S_GATE));
            __syncthreads();
            cluster_sync();
            if ((p.chains >> (w >> 1)) & 1) rec_attn(p, sb, w >> 1, w & 1, head, rank);
        } else {
            reg_inc<RW0>();
            rec_weights(p, sb, head, rank, wi);
        }
    } else {
        if (wg == 2) {
            reg_dec<40>();
            const int w = wi & 3;
            if (w == 0) bulk_producer(p, sb, cl, rank); else if (w < 3) bulk_stats(p, sb, cl, rank); else bulk_release(p, sb, cl, rank);
        } else { reg_inc<232>(); bulk_consumer(p, sb, cl, rank); }
    }
    __syncwarp();
    cluster_sync();
}

typedef CUresult (*EncFn)(CUtensorMap*, CUtensorMapDataType, cuuint32_t, void*, const cuuint64_t*, const cuuint64_t*, const cuuint32_t*, const cuuint32_t*,
                          CUtensorMapInterleave, CUtensorMapSwizzle, CUtensorMapL2promotion, CUtensorMapFloatOOBfill);
inline uint32_t mk(int type, int layer, int ch, int a, int b, int c) { return type | (layer << 3) | (ch << 4) | (a << 8) | (b << 16) | ((uint32_t)c << 24); }
constexpr int SMEM_BYTES = 232448;

struct Sched {
    Params* P; int n[NCL];
    void clear() { memset(P->task, 0, sizeof(P->task)); memset(n, 0, sizeof(n)); }
    void add(int cl, uint32_t t) { if (n[cl] < MAXT - 1) P->task[cl][n[cl]++] = t; }
};

#define LAG 14
#define TS1 2500
#define TS2 3100
#define REC0 4
#define NS2 6
#define DFN 5000
#define DQN 6300
struct Slot { double s, e; uint32_t w; };
struct Planner {
    Slot sl[NCL][MAXT]; int n[NCL], nc;
    double fit(int i, double r, double d) const {
        double t = r;
        for (int k = 0; k < n[i]; k++) { if (sl[i][k].s >= t + d) break; if (sl[i][k].e > t) t = sl[i][k].e; }
        return t;
    }
    double idle_before(int i, double t) const { double e = 0; for (int k = 0; k < n[i]; k++) if (sl[i][k].e <= t + 1 && sl[i][k].e > e) e = sl[i][k].e; return t - e; }
    void put(int i, double t, double d, uint32_t w) {
        int k = n[i]++;
        while (k > 0 && sl[i][k - 1].s > t) { sl[i][k] = sl[i][k - 1]; k--; }
        sl[i][k] = {t, t + d, w};
    }
    double last_urgent(int i) const { double e = 0; for (int k = 0; k < n[i]; k++) { const uint32_t t = sl[i][k].w & 15; if (t != (T_OP | 8) && t != (T_FIN | 8)) e = sl[i][k].e; } return e; }
    double place(double r, double d, uint32_t w, int lo, bool tight) {
        int bi = -1; double bt = 0, bg = 0;
        for (int i = lo; i < nc; i++) {
            if (n[i] >= MAXT - 2) continue;
            const double t = fit(i, (w & 7) == T_FIN ? fmax(r, last_urgent(i)) : r, d), g = tight ? idle_before(i, t) : -idle_before(i, t);
            if (bi < 0 || t < bt - 1 || (t < bt + 1 && g < bg)) { bi = i; bt = t; bg = g; }
        }
        put(bi, bt, d, w);
        return bt + d;
    }
};
void plan(Params& P) {
    P.rec0 = REC0; P.chains = 3; P.lag = LAG; P.dostats = 1; P.dopro = 1;
    const double DQ = DQN, DKB = 600, DOV = 1000, DH = 520, DHO = 1300, DU = 4300, DF = DFN, HOP = 1600, ODEL = 1000, LEAD = 1500;
    static Planner L;
    int cls[NCL], nc = 0;
    for (int c = REC0 + 32; c < NCL; c++) cls[nc++] = c;
    for (int c = REC0 - 1; c >= 0; c--) cls[nc++] = c;
    for (double grow = 1.0;; grow *= 1.01) {
        memset(L.n, 0, sizeof(L.n)); L.nc = nc;
        double it[100], worst = 1e18, end = 0, cvs[16], cve[16];
        it[0] = DQ + 2 * HOP;
        for (int i = 1; i < 100; i++) it[i] = it[i - 1] + fmax(grow * TS1, (i - 1 >= LAG && i - 1 < 64) ? TS2 : 0);
        const double DO1 = DOV + 8 * DKB, dly = it[4] + ODEL + DO1 + HOP + DU + HOP + DQ + 2 * HOP - it[LAG];
        if (dly > 0) for (int i = LAG; i < 100; i++) it[i] += dly;
        for (int c = 0; c < 16; c++) {
            const double s0 = fmax(it[4 * c + 4] + ODEL, c ? cve[c - 1] : 0);
            for (int i = 0; i < 8; i++) {
                if (c == 0) L.put(i, s0 - 11000, 11000, mk(T_CV, 0, 3, 2 * i, 0, 128));
                L.put(i, s0, DO1, mk(T_OP, 0, c, 8 * i, 8, i));
                L.put(i, s0 + DO1, HOP + DU, mk(T_CV, 0, c, 2 * i, 0, 0));
            }
            cvs[c] = s0 + DO1; cve[c] = cvs[c] + HOP + DU;
        }
        for (int c = 0; c < 16; c++) {
            double e = 0;
            for (int t = 0; t < 24; t++) e = fmax(e, L.place(cve[c] + HOP, DQ, mk(T_QKV, 1, c, t * 8, 4, 0), 0, true));
            worst = fmin(worst, it[LAG + 4 * c] - (c ? LEAD : 0) - HOP - e);
        }
        for (int c = 2; c < 16; c++) {
            double e = 0, r = cve[c - 2] + HOP;
            const int m = c >= HSPLIT ? c / 2 + 1 : c;
            if (m < c) for (int i = 0; i < 8; i++) r = fmax(r, L.place(cve[c - 3] + HOP, DHO + DH * (c - m), mk(T_CV, 1, c, 2 * i, c, m + 1), 8, true));
            for (int i = 0; i < 8; i++) e = fmax(e, L.place(r, DHO + (m < c ? 1500 : 0) + DH * (m - 1), mk(T_CV, 1, c, 2 * i, m, 2), 8, true));
            worst = fmin(worst, cvs[c] - HOP - e);
        }
        for (int c = 0; c < 16; c++) {
            double e = 0;
            for (int t = 0; t < 24; t++) e = fmax(e, L.place(0, DQ, mk(T_QKV, 0, c, t * 8, 4, 0), 0, true));
            worst = fmin(worst, it[4 * c] - (c ? LEAD : 0) - HOP - e);
        }
        for (int cc = 0; cc < 16; cc++) {
            const int c = cc ? cc - 1 : 15, ns = c == 15 ? 16 : c == 14 ? 8 : NS2, nf = c >= 14 ? 8 : 4;
            double e = 0;
            for (int t = 0; t < ns; t++) {
                const int a = t * 64 / ns, b = (t + 1) * 64 / ns - a;
                const double guard = c == 15 ? 9000 : 0;
                e = fmax(e, L.place(it[LAG + 4 * c + 4] + ODEL - guard, DOV + DKB * b + guard, mk(T_OP, 1, c, a, b, t), 0, true));
            }
            for (int t = 0; t < nf; t++) end = fmax(end, L.place(e + HOP, DF, mk(T_FIN, 1, c, t * (32 / nf), ns, 16 / nf), 0, true));
        }
        if (worst >= 0) break;
    }
    for (int lc = 0; lc < 32; lc++) {
        bool used[24] = {};
        for (int pass = 0; pass < 2; pass++)
            for (int i = 0; i < nc; i++)
                for (int k = 0; k < L.n[i]; k++) {
                    uint32_t& w = L.sl[i][k].w;
                    if ((w & 255) != mk(T_QKV, lc & 1, lc >> 1, 0, 0, 0)) continue;
                    int t = i - 8;
                    if (pass == 0) { w |= 0xff00; if (t < 0 || t >= 24 || used[t]) continue; }
                    else { if ((w & 0xff00) != 0xff00) continue; for (t = 0; used[t]; t++) {} }
                    used[t] = true; w = (w & ~0xff00u) | (t * 8) << 8;
                }
    }
    Sched S; S.P = &P; S.clear();
    S.add(0, mk(T_QKV, 1, 15, 124, 4, 128)); S.add(0, mk(T_OP, 1, 15, 0, 4, 128));
    S.add(1, mk(T_CV, 0, 3, 0, 0, 128));
    for (int i = 0; i < nc; i++) {
        bool warm = false;
        for (int k = 0; k < L.n[i]; k++) {
            if (!warm && k + 1 < L.n[i] && (L.sl[i][k + 1].w & 255) == (mk(T_FIN, 1, 15, 0, 0, 0) & 255)) { S.add(cls[i], L.sl[i][k + 1].w | 0x80000000u); warm = true; }
            S.add(cls[i], L.sl[i][k].w);
            if ((L.sl[i][k].w & 7) == T_FIN) warm = true;
        }
    }
}

#define TK0() do {} while (0)
#define TK() do { P.e0 = (P.chains & 1) ? 64 : 0; P.b1 = (P.chains & 2) ? P.lag : 1000; P.nit = (P.chains & 2) ? P.lag + 64 : 64; TK0(); } while (0)
}

extern "C" void kernel_launch(void* const* d_in, const int* in_sizes, int n_in, void* d_out, int out_size) {
    typedef const __nv_bfloat16* BP;
    static EncFn enc = nullptr;
    if (!enc) {
        void* fn = nullptr; cudaDriverEntryPointQueryResult qr;
        cudaGetDriverEntryPoint("cuTensorMapEncodeTiled", &fn, cudaEnableDefault, &qr);
        enc = (EncFn)fn;
        cudaFuncSetAttribute(main_kernel, cudaFuncAttributeMaxDynamicSharedMemorySize, SMEM_BYTES);
    }
    static Params P;
    for (int i = 0; i < 4; i++) {
        const cuuint64_t cols = i < 3 ? 4096 : 512, rows = i < 3 ? 512 : 4096;
        cuuint64_t d2[2] = {cols, rows}, d3[3] = {64, rows, cols / 64}, str[2] = {cols * 2, 128};
        cuuint32_t box[3] = {64, 64, 4}, es[3] = {1, 1, 1};
        enc(&P.tm[i < 3 ? i : 4], CU_TENSOR_MAP_DATA_TYPE_BFLOAT16, 2, d_in[9 + i], d2, str, box, es, CU_TENSOR_MAP_INTERLEAVE_NONE, CU_TENSOR_MAP_SWIZZLE_128B,
                       CU_TENSOR_MAP_L2_PROMOTION_L2_128B, CU_TENSOR_MAP_FLOAT_OOB_FILL_NONE);
        enc(&P.t3[i], CU_TENSOR_MAP_DATA_TYPE_BFLOAT16, 3, d_in[9 + i], d3, str, box, es, CU_TENSOR_MAP_INTERLEAVE_NONE, CU_TENSOR_MAP_SWIZZLE_128B,
            CU_TENSOR_MAP_L2_PROMOTION_L2_128B, CU_TENSOR_MAP_FLOAT_OOB_FILL_NONE);
    }
    {
        cuuint64_t dims[2] = {512, 2048}, str[1] = {1024};
        cuuint32_t box[2] = {8, 256}, es[2] = {1, 1};
        enc(&P.tm[3], CU_TENSOR_MAP_DATA_TYPE_BFLOAT16, 2, d_in[0], dims, str, box, es, CU_TENSOR_MAP_INTERLEAVE_NONE, CU_TENSOR_MAP_SWIZZLE_NONE,
            CU_TENSOR_MAP_L2_PROMOTION_NONE, CU_TENSOR_MAP_FLOAT_OOB_FILL_NONE);
    }
    P.mem0 = (BP)d_in[8]; P.Wo = (BP)d_in[12]; P.Dskip = (BP)d_in[6]; P.out = (__nv_bfloat16*)d_out;
    P.nst[0] = 1; P.nst[1] = 16;
    cudaStream_t s = cudaStreamPerThread;
    P.pa = {(BP)d_in[0], (BP)d_in[1], (BP)d_in[2], (BP)d_in[3], (BP)d_in[4], (BP)d_in[5], (BP)d_in[6], (BP)d_in[9], (BP)d_in[10], (BP)d_in[11], (BP)d_in[12], (BP)d_in[8]};
    static bool planned = false;
    if (!planned) { plan(P); planned = true; }
    TK(); main_kernel<<<2 * NCL, 384, SMEM_BYTES, s>>>(P); TK();
}
```

```cpp
#include <cuda_runtime.h>
#include <cuda_bf16.h>
#include <cuda.h>
#include <stdint.h>
#include <string.h>
#include <math.h>

namespace {

constexpr int NCL = 66;
constexpr int MAXT = 64;
constexpr int OPS1 = 8;
constexpr int MAXSPLIT = 16;
constexpr int HSPLIT = 10;
constexpr int PW = 144;

struct AOps { uint4 x[2][16 * 8 * 1024], o[2][16 * 64 * 1024]; };
__device__ AOps g_A;
#define g_xA g_A.x
#define g_o g_A.o
__device__ float2 g_st[2][16 * 2048];
__device__ float2 g_st2[16 * 16 * 128];
__device__ uint4 g_qkv[2][64 * 64 * 768];
__device__ uint4 g_pp[2][16 * MAXSPLIT * 8192];
__device__ uint4 g_acc[7 * 2048];
__device__ unsigned g_gate[32];
__device__ uint32_t g_P[16 * 16 * 32 * PW];
__device__ uint4 g_u[16 * 16 * 512];
__device__ float4 g_carry[3][16 * 16 * 4 * 256];
__device__ float g_cs[2 * 12288 + 64];
__device__ unsigned g_cnt[9 * 16 * 32];
__device__ uint32_t g_ln0[2048];

enum { C_QKV0 = 0, C_QKV1 = 1, C_O0 = 2, C_O1 = 3, C_OP0 = 4, C_OP1 = 5, C_CV = 6, C_ST = 7, C_H = 8 };
__device__ __forceinline__ unsigned* cnt_ptr(int kind, int chunk) { return g_cnt + (kind * 16 + chunk) * 32; }

enum { T_END = 0, T_QKV = 1, T_OP = 2, T_CV = 3, T_FIN = 4 };
struct ProArgs { const __nv_bfloat16 *x, *lAr, *Ai, *Cr, *Ci, *ldt, *Dk, *Wq, *Wk, *Wv, *Wo, *mem0; };
struct Params {
    CUtensorMap tm[5];
    CUtensorMap t3[2][4];
    CUtensorMap ta[2];
    ProArgs pa;
    int dopro;
    const __nv_bfloat16* mem0;
    const __nv_bfloat16* Wo;
    const __nv_bfloat16* Dskip;
    __nv_bfloat16* out;
    int rec0;
    int chains;
    int lag;
    int b1, e0, nit;
    int zero, gpit;
    int dostats;
    int nst[2];
    uint32_t task[NCL][MAXT];
};

__device__ __forceinline__ uint32_t smem_u32(const void* p) { return (uint32_t)__cvta_generic_to_shared(p); }
__device__ __forceinline__ uint32_t mapa(uint32_t a, uint32_t r) {
    uint32_t o; asm("mapa.shared::cluster.u32 %0,%1,%2;" : "=r"(o) : "r"(a), "r"(r)); return o;
}
__device__ __forceinline__ void mbar_init(uint32_t b, int c) { asm volatile("mbarrier.init.shared::cta.b64 [%0],%1;" ::"r"(b), "r"(c) : "memory"); }
__device__ __forceinline__ void mbar_expect(uint32_t b, int bytes) { asm volatile("mbarrier.arrive.expect_tx.shared::cta.b64 _,[%0],%1;" ::"r"(b), "r"(bytes) : "memory"); }
__device__ __forceinline__ void mbar_arrive(uint32_t b) { asm volatile("mbarrier.arrive.shared::cta.b64 _,[%0];" ::"r"(b) : "memory"); }
__device__ __forceinline__ void mbar_arrive_cluster(uint32_t b) { asm volatile("mbarrier.arrive.shared::cluster.b64 _,[%0];" ::"r"(b) : "memory"); }
__device__ __forceinline__ void mbar_arrive1(uint32_t b) { asm volatile("{.reg .pred p; elect.sync _|p,0xffffffff; @p mbarrier.arrive.shared::cta.b64 _,[%0];}" ::"r"(b) : "memory"); }
__device__ __forceinline__ void mbar_arrive1_cluster(uint32_t b) { asm volatile("{.reg .pred p; elect.sync _|p,0xffffffff; @p mbarrier.arrive.shared::cluster.b64 _,[%0];}" ::"r"(b) : "memory"); }
__device__ __forceinline__ void mbar_wait(uint32_t b, uint32_t ph) {
    asm volatile(
        "{.reg .pred p; .reg .u32 n; mov.u32 n,0;\n"
        "W%=: mbarrier.try_wait.parity.shared::cta.b64 p,[%0],%1;\n"
        "@p bra D%=;\n"
        "add.u32 n,n,1; setp.lt.u32 p,n,2000000; @p bra W%=;\n"
        "trap;\n"
        "D%=: }" ::"r"(b), "r"(ph) : "memory");
}
__device__ __forceinline__ bool wait_lds128(uint32_t b, uint32_t ph, uint32_t a, uint4& v) {
    uint32_t ok;
    asm volatile("{.reg .pred p; mbarrier.try_wait.parity.shared::cta.b64 p,[%5],%6,20000; ld.shared.v4.u32 {%0,%1,%2,%3},[%7]; selp.u32 %4,1,0,p;}"
                 : "=r"(v.x), "=r"(v.y), "=r"(v.z), "=r"(v.w), "=r"(ok) : "r"(b), "r"(ph), "r"(a) : "memory");
    return ok;
}
__device__ __forceinline__ bool wait_lds64(uint32_t b, uint32_t ph, uint32_t a, uint2& v) {
    uint32_t ok;
    asm volatile("{.reg .pred p; mbarrier.try_wait.parity.shared::cta.b64 p,[%3],%4,20000; ld.shared.v2.u32 {%0,%1},[%5]; selp.u32 %2,1,0,p;}"
                 : "=r"(v.x), "=r"(v.y), "=r"(ok) : "r"(b), "r"(ph), "r"(a) : "memory");
    return ok;
}
template <int PH> __device__ __forceinline__ void mbar_wait_c(uint32_t b) {
    asm volatile(
        "{.reg .pred p; .reg .u32 n; mov.u32 n,%2;\n"
        "W%=: mbarrier.try_wait.parity.shared::cta.b64 p,[%0],%1;\n"
        "@p bra D%=;\n"
        "add.u32 n,n,1; setp.lt.u32 p,n,2000000; @p bra W%=;\n"
        "trap;\n"
        "D%=: }" ::"r"(b), "n"(PH), "n"(PH) : "memory");
}
__device__ __forceinline__ void bar_sync(int id, int n) { asm volatile("bar.sync %0,%1;" ::"r"(id), "r"(n) : "memory"); }
__device__ __forceinline__ void bar_arrive(int id, int n) { asm volatile("bar.arrive %0,%1;" ::"r"(id), "r"(n) : "memory"); }
__device__ __forceinline__ void cluster_sync() { asm volatile("barrier.cluster.arrive.relaxed.aligned; barrier.cluster.wait.aligned;" ::: "memory"); }
__device__ __forceinline__ void fence_async() { asm volatile("fence.proxy.async;" ::: "memory"); }
__device__ __forceinline__ void fence_async_smem() { asm volatile("fence.proxy.async.shared::cta;" ::: "memory"); }
#define EFR 1
#define EFW 2
constexpr uint64_t POL_N = 0x1000000000000000ull, POL_F = 0x12F0000000000000ull;
constexpr uint64_t POL_LAST = EFR ? POL_F : POL_N  , POL_LATE = EFW ? POL_F : POL_N  , POL_SOON = EFW > 1 ? POL_F : POL_N;
__device__ __forceinline__ void bulk_g2s(uint32_t dst, const void* src, int bytes, uint32_t bar, uint64_t pol) {
    asm volatile("cp.async.bulk.shared::cluster.global.mbarrier::complete_tx::bytes.L2::cache_hint [%0],[%1],%2,[%3],%4;" ::"r"(dst), "l"(src), "r"(bytes), "r"(bar), "l"(pol) : "memory");
}
__device__ __forceinline__ void bulk_g2s_mc(uint32_t dst, const void* src, int bytes, uint32_t bar, uint64_t pol) {
    asm volatile("cp.async.bulk.shared::cluster.global.mbarrier::complete_tx::bytes.multicast::cluster.L2::cache_hint [%0],[%1],%2,[%3],%4,%5;" ::"r"(dst), "l"(src), "r"(bytes), "r"(bar), "h"((uint16_t)3), "l"(pol) : "memory");
}
__device__ __forceinline__ void bulk_s2s(uint32_t dst, uint32_t src, int bytes, uint32_t bar) {
    asm volatile("cp.async.bulk.shared::cluster.shared::cta.mbarrier::complete_tx::bytes [%0],[%1],%2,[%3];" ::"r"(dst), "r"(src), "r"(bytes), "r"(bar) : "memory");
}
__device__ __forceinline__ bool elect() {
    uint32_t r; asm volatile("{.reg .pred p; elect.sync _|p,0xffffffff; selp.u32 %0,1,0,p;}" : "=r"(r)); return r;
}
__device__ __forceinline__ void stg128(uint4* p, uint4 v, uint64_t pol) {
    asm volatile("st.global.L2::cache_hint.v4.u32 [%0],{%1,%2,%3,%4},%5;" ::"l"(p), "r"(v.x), "r"(v.y), "r"(v.z), "r"(v.w), "l"(pol));
}
__device__ __forceinline__ void stg32(uint32_t* p, uint32_t v, uint64_t pol) { asm volatile("st.global.L2::cache_hint.u32 [%0],%1,%2;" ::"l"(p), "r"(v), "l"(pol)); }
__device__ __forceinline__ uint4 ldcg128_last(const uint4* p) {
    uint4 v; asm volatile("ld.global.cg.L2::cache_hint.v4.u32 {%0,%1,%2,%3},[%4],%5;" : "=r"(v.x), "=r"(v.y), "=r"(v.z), "=r"(v.w) : "l"(p), "l"(POL_LAST) : "memory"); return v;
}
__device__ __forceinline__ void tma2d(uint32_t dst, const CUtensorMap* tm, int x, int y, uint32_t bar) {
    asm volatile("cp.async.bulk.tensor.2d.shared::cluster.global.mbarrier::complete_tx::bytes [%0],[%1,{%2,%3}],[%4];" ::"r"(dst), "l"(tm), "r"(x), "r"(y), "r"(bar) : "memory");
}
__device__ __forceinline__ void tma3d_mc(uint32_t dst, const CUtensorMap* tm, int y, int z, uint32_t bar, uint16_t mask) {
    asm volatile("{.reg .pred p; elect.sync _|p,0xffffffff;\n"
                 "@p cp.async.bulk.tensor.3d.shared::cluster.global.mbarrier::complete_tx::bytes.multicast::cluster [%0],[%1,{0,%2,%3}],[%4],%5;}"
                 ::"r"(dst), "l"(tm), "r"(y), "r"(z), "r"(bar), "h"(mask) : "memory");
}
__device__ __forceinline__ void tma2d_mc(uint32_t dst, const CUtensorMap* tm, int x, int y, uint32_t bar, uint16_t mask, uint64_t pol) {
    asm volatile("{.reg .pred p; elect.sync _|p,0xffffffff;\n"
                 "@p cp.async.bulk.tensor.2d.shared::cluster.global.mbarrier::complete_tx::bytes.multicast::cluster.L2::cache_hint [%0],[%1,{%2,%3}],[%4],%5,%6;}"
                 ::"r"(dst), "l"(tm), "r"(x), "r"(y), "r"(bar), "h"(mask), "l"(pol) : "memory");
}
__device__ __forceinline__ void bulk_g2s1(uint32_t dst, const void* src, int bytes, uint32_t bar, uint64_t pol) {
    asm volatile("{.reg .pred p; elect.sync _|p,0xffffffff;\n"
                 "@p cp.async.bulk.shared::cluster.global.mbarrier::complete_tx::bytes.L2::cache_hint [%0],[%1],%2,[%3],%4;}" ::"r"(dst), "l"(src), "r"(bytes), "r"(bar), "l"(pol) : "memory");
}
__device__ __forceinline__ void mbar_expect1(uint32_t b, int bytes) {
    asm volatile("{.reg .pred p; elect.sync _|p,0xffffffff; @p mbarrier.arrive.expect_tx.shared::cta.b64 _,[%0],%1;}" ::"r"(b), "r"(bytes) : "memory");
}
__device__ __forceinline__ void st_async4(uint32_t a, uint32_t x, uint32_t y, uint32_t z, uint32_t w, uint32_t mb) {
    asm volatile("st.async.shared::cluster.mbarrier::complete_tx::bytes.v4.b32 [%0],{%1,%2,%3,%4},[%5];" ::"r"(a), "r"(x), "r"(y), "r"(z), "r"(w), "r"(mb) : "memory");
}
__device__ __forceinline__ void st_async2(uint32_t a, uint32_t x, uint32_t y, uint32_t mb) {
    asm volatile("st.async.shared::cluster.mbarrier::complete_tx::bytes.v2.b32 [%0],{%1,%2},[%3];" ::"r"(a), "r"(x), "r"(y), "r"(mb) : "memory");
}
#define LDSQ "ld.shared"
__device__ __forceinline__ uint4 lds128(uint32_t a) { uint4 v; asm volatile(LDSQ ".v4.u32 {%0,%1,%2,%3},[%4];" : "=r"(v.x), "=r"(v.y), "=r"(v.z), "=r"(v.w) : "r"(a) : "memory"); return v; }
__device__ __forceinline__ uint2 lds64(uint32_t a) { uint2 v; asm volatile(LDSQ ".v2.u32 {%0,%1},[%2];" : "=r"(v.x), "=r"(v.y) : "r"(a) : "memory"); return v; }
__device__ __forceinline__ uint32_t lds32(uint32_t a) { uint32_t v; asm volatile(LDSQ ".u32 %0,[%1];" : "=r"(v) : "r"(a) : "memory"); return v; }
__device__ __forceinline__ void sts128(uint32_t a, uint32_t x, uint32_t y, uint32_t z, uint32_t w) { asm volatile("st.shared.v4.u32 [%0],{%1,%2,%3,%4};" ::"r"(a), "r"(x), "r"(y), "r"(z), "r"(w) : "memory"); }
__device__ __forceinline__ void sts64(uint32_t a, uint32_t x, uint32_t y) { asm volatile("st.shared.v2.u32 [%0],{%1,%2};" ::"r"(a), "r"(x), "r"(y) : "memory"); }
__device__ __forceinline__ void sts32(uint32_t a, uint32_t x) { asm volatile("st.shared.u32 [%0],%1;" ::"r"(a), "r"(x) : "memory"); }
__device__ __forceinline__ uint4 ldsm4(uint32_t a) { uint4 v; asm volatile("ldmatrix.sync.aligned.m8n8.x4.shared.b16 {%0,%1,%2,%3},[%4];" : "=r"(v.x), "=r"(v.y), "=r"(v.z), "=r"(v.w) : "r"(a) : "memory"); return v; }
__device__ __forceinline__ uint4 ldsm4t(uint32_t a) { uint4 v; asm volatile("ldmatrix.sync.aligned.m8n8.x4.trans.shared.b16 {%0,%1,%2,%3},[%4];" : "=r"(v.x), "=r"(v.y), "=r"(v.z), "=r"(v.w) : "r"(a) : "memory"); return v; }
__device__ __forceinline__ uint32_t movm(uint32_t a) { uint32_t d; asm volatile("movmatrix.sync.aligned.m8n8.trans.b16 %0,%1;" : "=r"(d) : "r"(a)); return d; }
__device__ __forceinline__ uint32_t pack2(float lo, float hi) { uint32_t d; asm("cvt.rn.bf16x2.f32 %0,%1,%2;" : "=r"(d) : "f"(hi), "f"(lo)); return d; }
__device__ __forceinline__ uint32_t hadd2(uint32_t a, uint32_t b) { uint32_t d; asm("add.rn.bf16x2 %0,%1,%2;" : "=r"(d) : "r"(a), "r"(b)); return d; }
__device__ __forceinline__ float blo(uint32_t v) { return __uint_as_float(v << 16); }
__device__ __forceinline__ float bhi(uint32_t v) { return __uint_as_float(v & 0xffff0000u); }
__device__ __forceinline__ float rbf(float x) { return __uint_as_float(pack2(0.f, x)); }
__device__ __forceinline__ float ex2(float x) { float y; asm("ex2.approx.ftz.f32 %0,%1;" : "=f"(y) : "f"(x)); return y; }
__device__ __forceinline__ float rcp(float x) { float y; asm("rcp.approx.ftz.f32 %0,%1;" : "=f"(y) : "f"(x)); return y; }
__device__ __forceinline__ void mma16(float* c, uint32_t a0, uint32_t a1, uint32_t a2, uint32_t a3, uint32_t b0, uint32_t b1) {
    asm volatile("mma.sync.aligned.m16n8k16.row.col.f32.bf16.bf16.f32 {%0,%1,%2,%3},{%4,%5,%6,%7},{%8,%9},{%0,%1,%2,%3};"
                 : "+f"(c[0]), "+f"(c[1]), "+f"(c[2]), "+f"(c[3]) : "r"(a0), "r"(a1), "r"(a2), "r"(a3), "r"(b0), "r"(b1));
}
__device__ __forceinline__ void mma8(float* c, uint32_t a0, uint32_t a1, uint32_t b0) {
    asm volatile("mma.sync.aligned.m16n8k8.row.col.f32.bf16.bf16.f32 {%0,%1,%2,%3},{%4,%5},{%6},{%0,%1,%2,%3};"
                 : "+f"(c[0]), "+f"(c[1]), "+f"(c[2]), "+f"(c[3]) : "r"(a0), "r"(a1), "r"(b0));
}
__device__ __forceinline__ uint4 ld_rlx128(const uint4* p) {
    uint4 v;
    asm volatile("{.reg .b128 t; ld.relaxed.gpu.global.b128 t,[%4]; mov.b128 {%0,%1,%2,%3},t;}" : "=r"(v.x), "=r"(v.y), "=r"(v.z), "=r"(v.w) : "l"(p) : "memory");
    return v;
}
__device__ __forceinline__ void st_rlx128(uint4* p, uint32_t x, uint32_t y, uint32_t z, uint32_t w) {
    asm volatile("{.reg .b128 t; mov.b128 t,{%1,%2,%3,%4}; st.relaxed.gpu.global.b128 [%0],t;}" ::"l"(p), "r"(x), "r"(y), "r"(z), "r"(w) : "memory");
}
__device__ __forceinline__ uint4 ldcg128(const uint4* p) { uint4 v; asm volatile("ld.global.cg.v4.u32 {%0,%1,%2,%3},[%4];" : "=r"(v.x), "=r"(v.y), "=r"(v.z), "=r"(v.w) : "l"(p) : "memory"); return v; }
__device__ __forceinline__ void red_release(unsigned* p, unsigned v) {
    asm volatile("fence.proxy.async; red.relaxed.gpu.global.add.u32 [%0],%1;" ::"l"(p), "r"(v) : "memory");
}
__device__ __forceinline__ void wait_cnt(const unsigned* p, unsigned target) {
    unsigned v; int n = 0;
    while (true) {
        asm volatile("ld.acquire.gpu.global.u32 %0,[%1];" : "=r"(v) : "l"(p) : "memory");
        if (v >= target) break;
        if (++n > 3000000) __trap();
        __nanosleep(40);
    }
}
__device__ __forceinline__ void wait_cnt_warp(const unsigned* p, unsigned target) {
    unsigned v; int n = 0;
    while (true) {
        asm volatile("ld.acquire.gpu.global.u32 %0,[%1];" : "=r"(v) : "l"(p) : "memory");
        if (__all_sync(0xffffffffu, v >= target)) break;
        if (++n > 3000000) __trap();
    }
}
__device__ __forceinline__ uint64_t mkdesc(uint32_t addr, uint32_t lbo, uint32_t sbo, uint32_t sw) {
    return (uint64_t)((addr & 0x3FFFF) >> 4) | ((uint64_t)(lbo >> 4) << 16) | ((uint64_t)(sbo >> 4) << 32) | ((uint64_t)sw << 62);
}
__device__ __forceinline__ void wg_fence() { asm volatile("wgmma.fence.sync.aligned;" ::: "memory"); }
__device__ __forceinline__ void wg_commit() { asm volatile("wgmma.commit_group.sync.aligned;" ::: "memory"); }
template <int N> __device__ __forceinline__ void wg_wait() { asm volatile("wgmma.wait_group.sync.aligned %0;" ::"n"(N) : "memory"); }
#define R8(c, o) "+f"(c[o]), "+f"(c[o + 1]), "+f"(c[o + 2]), "+f"(c[o + 3]), "+f"(c[o + 4]), "+f"(c[o + 5]), "+f"(c[o + 6]), "+f"(c[o + 7])
#define R32(c, o) R8(c, o), R8(c, o + 8), R8(c, o + 16), R8(c, o + 24)
#define S32A "%0,%1,%2,%3,%4,%5,%6,%7,%8,%9,%10,%11,%12,%13,%14,%15,%16,%17,%18,%19,%20,%21,%22,%23,%24,%25,%26,%27,%28,%29,%30,%31"
#define S32B ",%32,%33,%34,%35,%36,%37,%38,%39,%40,%41,%42,%43,%44,%45,%46,%47,%48,%49,%50,%51,%52,%53,%54,%55,%56,%57,%58,%59,%60,%61,%62,%63"
#define S32C ",%64,%65,%66,%67,%68,%69,%70,%71,%72,%73,%74,%75,%76,%77,%78,%79,%80,%81,%82,%83,%84,%85,%86,%87,%88,%89,%90,%91,%92,%93,%94,%95"
#define S32D ",%96,%97,%98,%99,%100,%101,%102,%103,%104,%105,%106,%107,%108,%109,%110,%111,%112,%113,%114,%115,%116,%117,%118,%119,%120,%121,%122,%123,%124,%125,%126,%127"
#define W8(c, o) "=f"(c[o]), "=f"(c[o + 1]), "=f"(c[o + 2]), "=f"(c[o + 3]), "=f"(c[o + 4]), "=f"(c[o + 5]), "=f"(c[o + 6]), "=f"(c[o + 7])
#define W32(c, o) W8(c, o), W8(c, o + 8), W8(c, o + 16), W8(c, o + 24)
template <bool ACC> __device__ __forceinline__ void wgmma256(float* c, uint64_t da, uint64_t db) {
    if (ACC) asm volatile("wgmma.mma_async.sync.aligned.m64n256k16.f32.bf16.bf16 {" S32A S32B S32C S32D "},%128,%129,1,1,1,0,1;"
                          : R32(c, 0), R32(c, 32), R32(c, 64), R32(c, 96) : "l"(da), "l"(db));
    else asm volatile("wgmma.mma_async.sync.aligned.m64n256k16.f32.bf16.bf16 {" S32A S32B S32C S32D "},%128,%129,0,1,1,0,1;"
                      : W32(c, 0), W32(c, 32), W32(c, 64), W32(c, 96) : "l"(da), "l"(db));
}
template <int N> __device__ __forceinline__ void reg_inc() { asm volatile("setmaxnreg.inc.sync.aligned.u32 %0;" ::"n"(N)); }
template <int N> __device__ __forceinline__ void reg_dec() { asm volatile("setmaxnreg.dec.sync.aligned.u32 %0;" ::"n"(N)); }

#define PROF(cond, idx) do {} while (0)
#define CPROF(k) do {} while (0)

constexpr int S_GATE = 232440, S_XBAR = 232432;
constexpr float SC_LOG2E = 0.08838834764831845f * 1.4426950408889634f;

__device__ __forceinline__ float2 ln_finish(float mean, float var) {
    float sd; asm("sqrt.approx.f32 %0,%1;" : "=f"(sd) : "f"(rbf(rbf(var) + 1e-5f)));
    sd = rbf(sd);
    return make_float2(rbf(mean), sd);
}

__device__ __forceinline__ float2 row_stats512(const uint4* src, int s1, int s2) {
    const int g = (threadIdx.x & 31) >> 2;
    uint4 v[16];
#pragma unroll
    for (int i = 0; i < 16; i++) v[i] = ldcg128(src + (i >> 1) * s1 + (i & 1) * s2);
    float a[4] = {0, 0, 0, 0}, q0[4] = {0, 0, 0, 0}, q1[4] = {0, 0, 0, 0};
#pragma unroll
    for (int i = 0; i < 16; i++) {
        mma16(a, v[i].x, v[i].y, v[i].z, v[i].w, 0x3f803f80u, 0x3f803f80u);
        mma8(q0, v[i].x, v[i].y, v[i].x); mma8(q1, v[i].x, v[i].y, v[i].y);
        mma8(q0, v[i].z, v[i].w, v[i].z); mma8(q1, v[i].z, v[i].w, v[i].w);
    }
    const float sum = a[0] + a[2], sq = (g & 1) ? q0[1] + q1[3] : q0[0] + q1[2];
    return make_float2(sum, fmaxf(sq - sum * sum * (1.f / 512.f), 0.f));
}
__device__ __forceinline__ void x1_stats(int rg) {
    const int lane = threadIdx.x & 31, g = lane >> 2, c = lane & 3;
    const float2 r = row_stats512(g_xA[0] + (rg >> 4) * 8192 + (rg & 15) * 64 + c * 8 + g, 1024, 32);
    if (c == (g >> 1)) { g_st[0][rg * 8 + g] = r; g_ln0[rg * 8 + g] = 0; }
    __syncwarp();
    if (lane == 0) red_release(cnt_ptr(C_ST, rg >> 4), 1);
}
__global__ void stats_kernel() { x1_stats(blockIdx.x * 4 + (threadIdx.x >> 5)); }

#define NT 9
#define RH 104
#define RW0 200
#define NPD 5
#define NTO 13
#define DP1 0
#define GPW 0
#define GPJ 0
#define PACE 2
#define STO 1
#define G2I 3
#define VE 4
#define VF 8
constexpr int TILE = 20480;
constexpr int R_WV = 0, R_WO = 65536, R_T = 131072, R_M = R_T + 2 * TILE  , R_LOC = R_M + 8192  ,
              R_REM = R_LOC + 12288  , R_O = R_REM + 24576  , R_SX = R_O + 4096  ,
              R_IL = R_SX + 10240  , R_BAR = 231936, R_Z = R_BAR + 128  , R_STQ = 0, R_STK = 65536, R_STV = 131072;
static_assert(R_IL + 512 <= R_BAR && R_BAR + 256 <= S_XBAR, "smem map");
enum { RB_INIT = 0, RB_T = 2  , RB_V = 4  , RB_QK = 8  , RB_N = 12 };
enum { NB_MF = 1  , NB_LOC = 3  , NB_PAIR = 5  , NB_O = 9  , NB_XG = 11  , NB_W = 13 };
__device__ __forceinline__ uint32_t clk32() { return (uint32_t)clock64(); }

__device__ __forceinline__ char* acc_base() { return (char*)(((size_t)g_acc + 131071) & ~(size_t)131071); }
__device__ __forceinline__ uint32_t acc_slice(uint32_t s6) { return (s6 & 1) * 256 + (s6 >> 1) * 1024; }
__device__ __forceinline__ uint32_t acc_main(uint32_t rank, uint32_t tid) { return acc_slice(rank * 32 + (tid >> 3)) + (tid & 7) * 16; }
__device__ __forceinline__ uint32_t acc_extra(uint32_t rank, uint32_t tid) { return 65536 + acc_slice(((tid >> 5) & 1) + rank * 4 + (tid >> 6) * 8) + (tid & 31) * 4; }
__device__ __forceinline__ uint32_t acc_slot(uint32_t s) { return (s & 1) * 128 + (s & 2) * 256; }
__device__ __forceinline__ void acc_init(const __nv_bfloat16* mem0, int i) {
    const uint32_t tid = i & 255, rank = (i >> 8) & 1, slot = (i >> 9) & 3, X = i >> 11;
    uint32_t v[5] = {0, 0, 0, 0, 0};
    if (slot == 3) {
        const uint16_t* m = (const uint16_t*)mem0 + (tid & 3) * 1024 + rank * 256 + (tid >> 5) * 32 + ((tid >> 2) & 7);
#pragma unroll
        for (int k = 0; k < 4; k++) v[k] = __ldg(m + k * 8) | ((uint32_t)__ldg(m + k * 8 + 512) << 16);
        v[4] = (v[3] >> 16) | 0x42000000u; v[3] = (v[3] & 0xffff) | 0x42000000u;
    }
    *(uint4*)(acc_base() + X * 32768 + acc_slot(slot) + acc_main(rank, tid)) = make_uint4(v[0], v[1], v[2], v[3]);
    *(uint32_t*)(acc_base() + X * 1024 + acc_slot(slot) + acc_extra(rank, tid)) = v[4];
}
__global__ void acc_init_kernel(const __nv_bfloat16* mem0) { acc_init(mem0, blockIdx.x * 256 + threadIdx.x); }

struct RecW { uint32_t am, ae, ah, dp, lp, lpw, vo, sb, bar, zero, ts, tn; };
__device__ __forceinline__ uint32_t vadd(uint32_t a, uint32_t b) { uint32_t d; asm volatile("add.u32 %0,%1,%2;" : "=r"(d) : "r"(a), "r"(b)); return d; }
__device__ __forceinline__ uint32_t vshr(uint32_t a, int n) { uint32_t d; asm volatile("shr.u32 %0,%1,%2;" : "=r"(d) : "r"(a), "r"(n)); return d; }
__device__ __forceinline__ uint64_t gptr(uint32_t lo, uint32_t hi) { uint64_t d; asm("mov.b64 %0,{%1,%2};" : "=l"(d) : "r"(lo), "r"(hi)); return d; }
__device__ __forceinline__ void sfence(uint32_t zero) { asm volatile("{.reg .pred p; setp.ne.u32 p,%0,0; @p exit;}" ::"r"(zero) : "memory"); }
#define SF sfence(k.zero)
#define TS(i) do {} while (0)
#define TSN(i) do {} while (0)
#define TSET(it, slot) do {} while (0)
struct Gat { uint32_t x, y, z, w, e; };
template <int X>
__device__ __forceinline__ void gat_issue(Gat& g, const RecW& k, int s, uint32_t dep) {
    const uint32_t o = acc_slot(s + 3) + dep;
    asm volatile("{.reg .b128 t; ld.relaxed.gpu.global.b128 t,[%5+%7]; mov.b128 {%0,%1,%2,%3},t; ld.relaxed.gpu.global.u32 %4,[%6+%8];}"
                 : "=r"(g.x), "=r"(g.y), "=r"(g.z), "=r"(g.w), "=r"(g.e) : "l"(gptr(k.am + o, k.ah)), "l"(gptr(k.ae + o, k.ah)), "n"(X * 32768), "n"(X * 1024) : "memory");
}
template <int X>
__device__ __forceinline__ bool gat_store(const Gat& g, const RecW& k) {
    uint32_t c;
    asm volatile("prmt.b32 %0,%1,%2,0x7632;" : "=r"(c) : "r"(g.w), "r"(g.e));
    SF;
    asm volatile("{.reg .b32 t; prmt.b32 t,%4,%6,0x5410; stmatrix.sync.aligned.m8n8.x4.trans.shared.b16 [%0+%5],{%1,%2,%3,t};}" ::"r"(k.lpw), "r"(g.x), "r"(g.y), "r"(g.z), "r"(g.w), "n"(R_M + X * 4096), "r"(g.e) : "memory");
    return __all_sync(0xffffffffu, c == 0x42004200u);
}
template <int X>
__device__ __forceinline__ void gat_finish(bool ok, const RecW& k, int s) {
    if (!ok) {
        int n = s;
        while (true) {
            Gat g;
            gat_issue<X>(g, k, n, 0);
            if (gat_store<X>(g, k)) break;
            n += 4;
            if (n > 8000000) __trap();
        }
    }
}
__device__ __forceinline__ uint4 lds128o(uint32_t a, int o) { uint4 v; asm volatile("{.reg .b32 t; add.u32 t,%4,%5; ld.shared.v4.u32 {%0,%1,%2,%3},[t];}" : "=r"(v.x), "=r"(v.y), "=r"(v.z), "=r"(v.w) : "r"(a), "r"(o) : "memory"); return v; }
__device__ __forceinline__ uint4 ldsm4o(uint32_t a, int o) { uint4 v; asm volatile("{.reg .b32 t; add.u32 t,%4,%5; ldmatrix.sync.aligned.m8n8.x4.shared.b16 {%0,%1,%2,%3},[t];}" : "=r"(v.x), "=r"(v.y), "=r"(v.z), "=r"(v.w) : "r"(a), "r"(o) : "memory"); return v; }
#define WLD(base, i) wt[i] = lds128o(k.lpw, (base) + (i) * 4096)
template <int PASS, int X, int NP>
__device__ __forceinline__ void rec_qkv(const RecW& k, int s, const uint32_t (*wq)[4], const uint32_t (*wk)[4], uint4* wt, Gat& g2, int s2) {
    constexpr bool BWD = PASS == 2;
    float aq[4] = {0, 0, 0, 0}, ak[4] = {0, 0, 0, 0}, av[4] = {0, 0, 0, 0};
    constexpr int ma = R_M + X * 4096;
    if (BWD) { TS(1); gat_finish<1>(gat_store<1>(g2, k), k, s); }
    bar_sync(NB_MF + X, 256);
    uint4 mf = ldsm4o(k.lp, ma + (BWD ? 7 : 0) * 512);
    if (BWD) TS(2); else { TS(0); TSN(13); }
#pragma unroll
    for (int ii = 0; ii < 8; ii++) {
        const int i = BWD ? 7 - ii : ii;
        const uint4 m = mf;
        if (ii < 7) mf = ldsm4o(k.lp, ma + (BWD ? i - 1 : i + 1) * 512);
        if (PASS == 1 && ii == G2I) gat_issue<1>(g2, k, s2, 0);
        SF;
#pragma unroll
        for (int hh = 0; hh < 2; hh++) {
            const int h = BWD ? 1 - hh : hh, ks = 2 * i + h;
            const uint32_t b0 = h ? m.z : m.x, b1 = h ? m.w : m.y;
            mma16(aq, wq[ks][0], wq[ks][1], wq[ks][2], wq[ks][3], b0, b1);
            mma16(ak, wk[ks][0], wk[ks][1], wk[ks][2], wk[ks][3], b0, b1);
            SF;
            mma16(av, wt[ks].x, wt[ks].y, wt[ks].z, wt[ks].w, b0, b1);
            SF;
            if (!BWD && ks + NP < 16) WLD(R_WV, ks + NP < 16 ? ks + NP : 0);
            if (BWD && ks >= NT) WLD(R_WV, ks >= NT ? ks - NT : 0);
            SF;
        }
    }
    const uint32_t ra = vadd(k.lpw, k.dp + R_REM + (X * 2 + (s & 1)) * 6144), va = ((vshr(k.lp, 7) & 1) * 48 ^ k.lp ^ (k.vo & 64)) + (k.vo & ~64u);
    const uint32_t x0 = movm(pack2(aq[0], aq[1])), x1 = movm(pack2(aq[2], aq[3])), x2 = movm(pack2(ak[0], ak[1])), x3 = movm(pack2(ak[2], ak[3]));
    SF;
    asm volatile("stmatrix.sync.aligned.m8n8.x2.shared.b16 [%0+%3],{%1,%2};" ::"r"(va), "r"(pack2(av[0], av[1])), "r"(pack2(av[2], av[3])), "n"(R_LOC + X * 6144) : "memory");
    SF;
    if (STO) st_async4(ra, x0, x1, x2, x3, k.bar + X * 16);
    asm volatile("st.shared.v4.u32 [%0+%5],{%1,%2,%3,%4};" ::"r"(k.lpw), "r"(x0), "r"(x1), "r"(x2), "r"(x3), "n"(R_LOC + X * 6144) : "memory");
    bar_arrive(NB_LOC + X, 320);
    if (!STO) st_async4(ra, x0, x1, x2, x3, k.bar + X * 16);
    SF;
    TS(BWD ? 4 : 3);
}
template <bool BWD, int X>
__device__ __forceinline__ void rec_out(const RecW& k, int s, uint4* wt) {
    if (BWD) { WLD(R_WO, 17 - NTO); WLD(R_WO, 16 - NTO); }
    TS(BWD ? 8 : 5);
    bar_sync(NB_O + X, 320);
    float r0[4] = {0, 0, 0, 0}, r1[4] = {0, 0, 0, 0};
    constexpr int oa = R_O + X * 2048;
    uint4 bn = lds128o(k.lp, oa + (BWD ? 3 : 0) * 512);
    TS(BWD ? 9 : 6);
    uint2 il;
    uint64_t pm, pe;
#pragma unroll
    for (int ii = 0; ii < 4; ii++) {
        const int i = BWD ? 3 - ii : ii;
        const uint4 b = bn;
        if (ii < 3) bn = lds128o(k.lp, oa + (BWD ? i - 1 : i + 1) * 512);
        else { asm volatile("ld.shared.v2.u32 {%0,%1},[%2+%3];" : "=r"(il.x), "=r"(il.y) : "r"(k.lp), "n"(R_IL + X * 8) : "memory"); pm = gptr(vadd(k.am, acc_slot(s)), k.ah); pe = gptr(vadd(k.ae, acc_slot(s)), k.ah); }
        SF;
#pragma unroll
        for (int nn = 0; nn < 4; nn++) {
            const int n = BWD ? 3 - nn : nn, f = 4 * i + n, nx = BWD ? f - NTO + 2 : f + NTO - 2;
            mma16((n & 1) ? r1 : r0, wt[f].x, wt[f].y, wt[f].z, wt[f].w, n >> 1 ? b.z : b.x, n >> 1 ? b.w : b.y);
            SF;
            if (ii * 4 + nn >= 2 && nx >= 0 && nx < 16) WLD(R_WO, nx & 15);
            SF;
        }
    }
    const float i0 = __uint_as_float(il.x), i1 = __uint_as_float(il.y);
    asm volatile("red.relaxed.gpu.global.add.noftz.v4.bf16x2 [%0+%5],{%1,%2,%3,%4};" ::"l"(pm),
                 "r"(pack2(r0[0] * i0, r0[1] * i1)), "r"(pack2(r0[2] * i0, r0[3] * i1)), "r"(pack2(r1[0] * i0, r1[1] * i1)), "r"(pack2(r1[2] * i0, 1.f)), "n"(X * 32768) : "memory");
    asm volatile("red.relaxed.gpu.global.add.noftz.bf16x2 [%0+%2],%1;" ::"l"(pe), "r"(pack2(r1[3] * i1, 1.f)), "n"(X * 1024) : "memory");
    bar_arrive(NB_XG + X, 320);
    SF;
    TS(BWD ? 10 : 7);
}
__device__ __forceinline__ uint32_t pause(uint32_t v, int n) {
#pragma unroll
    for (int i = 0; i < n; i++) asm volatile("shfl.sync.bfly.b32 %0,%0,0,0x1f,0xffffffff;" : "+r"(v));
    return v;
}
template <bool DUAL, int X>
__device__ __forceinline__ void rec_step(const RecW& k, int s, int s2, const uint32_t (*wq)[4], const uint32_t (*wk)[4], uint4* wt) {
    constexpr int NP = NPD;
    uint4 wo[16];
    Gat g;
    rec_qkv<DUAL ? 1 : 0, X, NP>(k, s, wq, wk, wt, g, s2);
    if (DUAL) rec_qkv<2, 1, NP>(k, s2, wq, wk, wt, g, s2);
    uint32_t wa = k.lpw;
#pragma unroll
    for (int i = 0; i < NTO; i++) {
        wo[i] = lds128o(wa, R_WO + i * 4096);
        if (i % PACE == PACE - 1) wa = k.lpw + (wo[i].x & k.zero);
        SF;
    }
    rec_out<false, X>(k, s, wo);
    if (DUAL) { rec_out<true, 1>(k, s2, wo); gat_issue<0>(g, k, s + 1, 0); SF; }
#pragma unroll
    for (int i = 0; i < NP; i++) { WLD(R_WV, i); SF; }
    if (!DUAL) gat_issue<X>(g, k, s + 1, pause(wt[NP - 1].x & k.zero, DP1));
    TS(12);
    gat_finish<X>(gat_store<X>(g, k), k, s + 1);
    TS(11);
}

__device__ __forceinline__ void rec_fetch(const CUtensorMap* tm, uint32_t dst, int x, int y, int nx, uint32_t bar) {
#pragma unroll 1
    for (int j = 0; j < 8; j++) tma2d(dst + j * 8192, tm, x + (j / (8 / nx)) * 64, y + (j % (8 / nx)) * 64, bar);
}
__device__ __forceinline__ void rec_weights(const Params& p, uint32_t sb, int head, uint32_t rank, int w) {
    const int lane = threadIdx.x & 31, t = w & 3, WG = w >> 2;
    uint32_t wq[16][4], wk[16][4];
    const uint32_t rowo = (((lane >> 4) << 3) + (lane & 7)) * 128;
    const uint32_t woff = sb + WG * 32768 + rowo + (((2 * t + ((lane >> 3) & 1)) ^ (lane & 7)) << 4);
    const uint32_t qoff = sb + ((w & 1) ? R_STK : R_STQ) + WG * 32768 + rowo + (((2 * (t & 2) + ((lane >> 3) & 1)) ^ (lane & 7)) << 4);
    const uint32_t lw = sb + (lane ^ (lane >> 3)) * 16;
    PROF(threadIdx.x == 0, 3501);
    if (w >= 4 && p.dostats) { wait_cnt_warp(g_gate, lds32(sb + S_GATE)); x1_stats((head * 2 + rank) * 4 + w - 4); }
    PROF(threadIdx.x == 0, 3502);
    mbar_wait(sb + R_BAR + RB_INIT * 8, 0);
    PROF(threadIdx.x == 0, 3503);
#pragma unroll
    for (int ks = 0; ks < 16; ks++) {
        uint4 a = ldsm4t(qoff + ks * 2048), b = ldsm4t((qoff ^ 32) + ks * 2048);
        wq[ks][0] = a.x; wq[ks][1] = a.y; wq[ks][2] = a.z; wq[ks][3] = a.w;
        wk[ks][0] = b.x; wk[ks][1] = b.y; wk[ks][2] = b.z; wk[ks][3] = b.w;
    }
    bar_sync(NB_W, 256);
#pragma unroll 4
    for (int ks = 0; ks < 16; ks++) { const uint4 a = ldsm4t(woff + R_STV + ks * 2048); sts128(lw + w * 512 + R_WV + ks * 4096, a.x, a.y, a.z, a.w); }
    bar_sync(NB_W, 256);
    if (threadIdx.x == 0) {
        mbar_expect(sb + R_BAR + RB_INIT * 8, 65536);
        rec_fetch(&p.tm[4], sb + R_STV, rank * 256, head * 128, 4, sb + R_BAR + RB_INIT * 8);
    }
    __syncwarp();
    mbar_wait(sb + R_BAR + RB_INIT * 8, 1);
#pragma unroll 4
    for (int f = 0; f < 16; f++) {
        const uint4 a = ldsm4t(sb + R_STV + (w >> 1) * 16384 + (f >> 1) * 2048 + rowo + ((((w & 1) * 4 + (f & 1) * 2 + ((lane >> 3) & 1)) ^ (lane & 7)) << 4));
        sts128(lw + w * 512 + R_WO + f * 4096, a.x, a.y, a.z, a.w);
    }
    PROF(threadIdx.x == 0, 3504);
    __syncthreads();
    cluster_sync();
    PROF(threadIdx.x == 0, 3505);
    RecW k;
    k.am = __shfl_sync(0xffffffffu, (uint32_t)(size_t)acc_base() + acc_main(rank, threadIdx.x), lane);
    k.ae = __shfl_sync(0xffffffffu, (uint32_t)(size_t)acc_base() + acc_extra(rank, threadIdx.x), lane);
    k.ah = (uint32_t)((size_t)acc_base() >> 32);
    k.sb = sb; k.zero = p.zero;

    k.dp = mapa(sb, rank ^ 1) - sb;
    k.lp = __shfl_sync(0xffffffffu, lw, lane);
    k.lpw = __shfl_sync(0xffffffffu, lw + w * 512, lane);
    k.vo = 4096 + w * 256 + (w & 1) * 64;
    k.bar = sb + k.dp + R_BAR + (RB_QK + WG) * 8;
    int it = 0;
    uint4 wt[16];
#pragma unroll
    for (int i = 0; i < NPD; i++) WLD(R_WV, i);
    gat_finish<0>(false, k, 0);
#pragma unroll 1
    for (; it < min(p.b1, p.e0); it++) { TSET(it, w == GPW ? 0 : 3); rec_step<false, 0>(k, it, it, wq, wk, wt); }
#pragma unroll 1
    for (; it < p.e0; it++) { TSET(it, w == GPW ? 0 : 3); rec_step<true, 0>(k, it, it - p.b1, wq, wk, wt); }
    if (it < p.nit) gat_finish<1>(false, k, it - p.b1);
#pragma unroll 1
    for (; it < p.nit; it++) { TSET(it, w == GPW ? 0 : 3); rec_step<false, 1>(k, it - p.b1, it - p.b1, wq, wk, wt); }
}

__device__ __forceinline__ void mma16_top(float* c, uint32_t a0, uint32_t a2, uint32_t b0, uint32_t b1) {
    asm volatile("{.reg .b32 j; mma.sync.aligned.m16n8k16.row.col.f32.bf16.bf16.f32 {%0,%1,%2,%3},{%4,j,%5,j},{%6,%7},{%0,%1,%2,%3};}"
                 : "+f"(c[0]), "+f"(c[1]), "+f"(c[2]), "+f"(c[3]) : "r"(a0), "r"(a2), "r"(b0), "r"(b1));
}
__device__ __forceinline__ void rec_load_tile(uint32_t sb, int X, int s, int head, uint32_t rank) {
    const uint32_t bar = sb + R_BAR + (RB_T + X) * 8;
    const uint4* src = g_qkv[X] + (size_t)(s * 32 + head) * 1536;
    mbar_expect1(bar, TILE);
    bulk_g2s1(sb + R_T + X * TILE, src + 512, 16384, bar, POL_LAST);
    bulk_g2s1(sb + R_T + X * TILE + 16384, src + rank * 256, 4096, bar, POL_LAST);
}
__device__ __forceinline__ bool chunk_ready(int X, int s) {
    unsigned v;
    asm volatile("ld.relaxed.gpu.global.u32 %0,[%1];" : "=r"(v) : "l"(cnt_ptr(C_QKV0 + X, s >> 2)) : "memory");
    return __all_sync(0xffffffffu, v >= 384);
}
__device__ __forceinline__ uint4 hadd4(uint4 a, uint4 b) { return make_uint4(hadd2(a.x, b.x), hadd2(a.y, b.y), hadd2(a.z, b.z), hadd2(a.w, b.w)); }
struct RecH { uint32_t lw, lm, lq, lv, lu, sb, zero, ts, tn; };
__device__ __forceinline__ void rec_publish(int X, int s) {
    asm volatile("{.reg .pred p; cp.async.bulk.wait_group 0; elect.sync _|p,0xffffffff; @p red.relaxed.gpu.global.add.u32 [%0],1;}" ::"l"(cnt_ptr(C_O0 + X, s >> 2)) : "memory");
}
__device__ __forceinline__ void rec_mattn(const RecH& k, uint32_t dp, int X, int j, int s, uint4 (*V)[4], uint4* vm) {
    const uint32_t sb = k.sb, to = R_T + X * TILE + j * 2048, lo = R_LOC + X * 6144, ro = R_REM + (X * 2 + (s & 1)) * 6144;
    const uint32_t bar = sb + R_BAR + (X * 2 + j) * 8;
    uint4 K[2][4];
    mbar_wait(sb + R_BAR + (RB_T + X) * 8, s & 1);
    TS(1);
#pragma unroll
    for (int i = 0; i < 8; i++) K[i >> 2][i & 3] = ldsm4(k.lm + (to + (i >> 2) * 1024 + ((i >> 1) & 1) * 4096 + (i & 1) * 512));
    bar_sync(NB_LOC + X, 320);
    uint4 u[4];
#pragma unroll
    for (int i = 0; i < 4; i++) u[i] = ldsm4(k.lm + (lo + j * 2048 + i * 512));
    fence_async_smem();
    asm volatile("{.reg .pred p; elect.sync _|p,0xffffffff; @p cp.async.bulk.shared::cluster.shared::cta.mbarrier::complete_tx::bytes [%0],[%1],1024,[%2];}"
                 ::"r"(sb + dp + ro + 4096 + j * 1024), "r"(sb + lo + 4096 + j * 1024), "r"(bar + dp + RB_V * 8) : "memory");
    TS(2);
    mbar_wait(bar + RB_QK * 8, s & 1);
    TS(3);
    float S[5][4];
#pragma unroll
    for (int i = 0; i < 5; i++) S[i][0] = S[i][1] = S[i][2] = S[i][3] = 0;
    {
        uint4 r[4];
#pragma unroll
        for (int i = 0; i < 4; i++) r[i] = ldsm4(k.lm + (ro + j * 2048 + i * 512));
        SF;
#pragma unroll
        for (int e = 0; e < 2; e++) {
            uint4& km = u[2 * e + 1];
            const uint32_t q0 = hadd2(u[2 * e].x, r[2 * e].x), q1 = hadd2(u[2 * e].y, r[2 * e].y);
            mma16_top(S[0], q0, q1, K[e][0].x, K[e][0].y);
            km.x = hadd2(km.x, r[2 * e + 1].x); km.y = hadd2(km.y, r[2 * e + 1].y);
            SF;
            mma16_top(S[1], q0, q1, K[e][1].x, K[e][1].y);
            const uint32_t q2 = hadd2(u[2 * e].z, r[2 * e].z), q3 = hadd2(u[2 * e].w, r[2 * e].w);
            SF;
            mma16_top(S[2], q0, q1, K[e][2].x, K[e][2].y);
            km.z = hadd2(km.z, r[2 * e + 1].z); km.w = hadd2(km.w, r[2 * e + 1].w);
            SF;
            mma16_top(S[3], q0, q1, K[e][3].x, K[e][3].y);
            mma16_top(S[4], q0, q1, km.x, km.y);
            SF;
#pragma unroll
            for (int i = 0; i < 4; i++) { mma16_top(S[i], q2, q3, K[e][i].z, K[e][i].w); SF; }
            mma16_top(S[4], q2, q3, km.z, km.w);
            SF;
        }
    }
#define VLD(a, b) _Pragma("unroll") for (int i = (a); i < (b); i++) V[i >> 2][i & 3] = ldsm4t((k.lv ^ ((i & 1) * 0x20)) + (to + 8192 + (i >> 2) * 4096 + ((i >> 1) & 1) * 1024))
    VLD(0, VE);
    SF;
    const uint32_t sxr = R_SX + (X * 2 + j) * 2560, sxw = R_SX + (X * 2 + (j ^ 1)) * 2560;
    sts128(k.lw + sxw, __float_as_uint(S[0][0]), __float_as_uint(S[0][1]), __float_as_uint(S[1][0]), __float_as_uint(S[1][1]));
    SF;
    sts128(k.lw + (sxw + 512), __float_as_uint(S[2][0]), __float_as_uint(S[2][1]), __float_as_uint(S[3][0]), __float_as_uint(S[3][1]));
    SF;
    sts64(k.lw + (sxw + 1024), __float_as_uint(S[4][0]), __float_as_uint(S[4][1]));
    TS(4);
    bar_sync(NB_PAIR + X, 64);
    {
        const uint4 a = lds128(k.lw + sxr), b = lds128(k.lw + (sxr + 512));
        const uint2 c = lds64(k.lw + (sxr + 1024));
        SF;
        VLD(VE, VF);
        SF;
        S[0][0] += __uint_as_float(a.x); S[0][1] += __uint_as_float(a.y); S[1][0] += __uint_as_float(a.z); S[1][1] += __uint_as_float(a.w);
        S[2][0] += __uint_as_float(b.x); S[2][1] += __uint_as_float(b.y); S[3][0] += __uint_as_float(b.z); S[3][1] += __uint_as_float(b.w);
        S[4][0] += __uint_as_float(c.x); S[4][1] += __uint_as_float(c.y);
    }
    float m = fmaxf(fmaxf(fmaxf(S[0][0], S[0][1]), fmaxf(S[1][0], S[1][1])), fmaxf(fmaxf(S[2][0], S[2][1]), fmaxf(S[3][0], S[3][1])));
    m = fmaxf(m, fmaxf(S[4][0], S[4][1]));
    m = fmaxf(m, __shfl_xor_sync(0xffffffffu, m, 1));
    const float m2 = __shfl_xor_sync(0xffffffffu, m, 2);
    SF;
    VLD(VF, 8);
    uint32_t ok;
    asm volatile("{.reg .pred p; mbarrier.test_wait.parity.shared::cta.b64 p,[%1],%2; selp.u32 %0,1,0,p;}" : "=r"(ok) : "r"(bar + RB_V * 8), "r"(s & 1) : "memory");
    uint4 vr0 = ldsm4(k.lu + (ro + 4096 + j * 1024)), vr1 = ldsm4(k.lu + (ro + 4608 + j * 1024));
    vm[0] = ldsm4(k.lu + (lo + 4096 + j * 1024)); vm[1] = ldsm4(k.lu + (lo + 4608 + j * 1024));
    SF;
    TS(5);
    m = fmaxf(m, m2) * -SC_LOG2E;
    uint32_t P[5];
#pragma unroll
    for (int i = 0; i < 5; i++) P[i] = pack2(ex2(fmaf(S[i][0], SC_LOG2E, m)), ex2(fmaf(S[i][1], SC_LOG2E, m)));
    float o[4][4], l[4] = {0, 0, 0, 0};
    const uint32_t ONE = 0x3f803f80u;
    mma16_top(l, ONE, ONE, P[0], P[1]);
#pragma unroll
    for (int t = 0; t < 4; t++) { o[t][0] = o[t][1] = o[t][2] = o[t][3] = 0; mma16(o[t], V[0][t].x, V[0][t].y, V[0][t].z, V[0][t].w, P[0], P[1]); }
    mma16_top(l, ONE, ONE, P[2], P[3]);
#pragma unroll
    for (int t = 0; t < 4; t++) mma16(o[t], V[1][t].x, V[1][t].y, V[1][t].z, V[1][t].w, P[2], P[3]);
    if (!__all_sync(0xffffffffu, ok)) {
        mbar_wait(bar + RB_V * 8, s & 1);
        vr0 = ldsm4(k.lu + (ro + 4096 + j * 1024)); vr1 = ldsm4(k.lu + (ro + 4608 + j * 1024));
    }
    TS(6);
    vm[0] = hadd4(vm[0], vr0); vm[1] = hadd4(vm[1], vr1);
    mma8(l, ONE, ONE, P[4]);
    mma8(o[0], vm[0].x, vm[0].y, P[4]); mma8(o[1], vm[0].z, vm[0].w, P[4]); mma8(o[2], vm[1].x, vm[1].y, P[4]); mma8(o[3], vm[1].z, vm[1].w, P[4]);
    if (j == 0) sts64(k.lw + (R_IL + X * 8), __float_as_uint(rcp(l[0])), __float_as_uint(rcp(l[1])));
#pragma unroll
    for (int t = 0; t < 4; t += 2)
        asm volatile("stmatrix.sync.aligned.m8n8.x4.trans.shared.b16 [%0],{%1,%2,%3,%4};" ::"r"(k.lm + (R_O + X * 2048 + j * 1024 + t * 256)),
                     "r"(pack2(o[t][0], o[t][1])), "r"(pack2(o[t][2], o[t][3])), "r"(pack2(o[t + 1][0], o[t + 1][1])), "r"(pack2(o[t + 1][2], o[t + 1][3])) : "memory");
    bar_arrive(NB_O + X, 320);
    TS(7);
#pragma unroll
    for (int e = 0; e < 2; e++) sts128(k.lw + (ro + j * 2048 + e * 1024), u[2 * e + 1].x, u[2 * e + 1].y, u[2 * e + 1].z, u[2 * e + 1].w);
    mbar_expect1(bar + RB_QK * 8, 2048); mbar_expect1(bar + RB_V * 8, 1024);
}
template <int MT>
__device__ __forceinline__ void rec_xattn(const RecH& k, int X, int j, int s, int head, bool early, const uint4 (*V)[4], const uint4* vmm) {
    constexpr int NTL = 3 + 2 * MT;
    const uint32_t sb = k.sb, to = R_T + X * TILE + j * 2048, ro = R_REM + (X * 2 + (s & 1)) * 6144 + j * 2048;
    const uint32_t sxw = R_SX + (X * 2 + j) * 2560, sxr = R_SX + (X * 2 + (j ^ 1)) * 2560;
    float S[NTL][4];
#pragma unroll
    for (int i = 0; i < NTL; i++) S[i][0] = S[i][1] = S[i][2] = S[i][3] = 0;
#pragma unroll
    for (int e = 0; e < 2; e++) {
        const uint4 q0 = ldsm4(k.lq + (to + 16384 + e * 1024)), q1 = ldsm4((k.lq ^ 0x20) + (to + 16384 + e * 1024));
#pragma unroll
        for (int i = 0; i < NTL; i++) {
            const uint4 kk = i ? ldsm4(k.lm + (to + e * 1024 + ((i - 1) >> 1) * 4096 + ((i - 1) & 1) * 512)) : lds128(k.lw + (ro + e * 1024));
            mma16(S[i], q0.x, q0.y, q0.z, q0.w, kk.x, kk.y); mma16(S[i], q1.x, q1.y, q1.z, q1.w, kk.z, kk.w);
        }
    }
#pragma unroll
    for (int i = 0; i < NTL; i++) sts128(k.lw + (sxw + i * 512), __float_as_uint(S[i][0]), __float_as_uint(S[i][1]), __float_as_uint(S[i][2]), __float_as_uint(S[i][3]));
    SF;
    bar_sync(NB_PAIR + X, 64);
    TS(9);
    if (early) rec_load_tile(sb, X, s + 1, head, MT);
#pragma unroll
    for (int i = 0; i < NTL; i++) {
        const uint4 r = lds128(k.lw + (sxr + i * 512));
        S[i][0] += __uint_as_float(r.x); S[i][1] += __uint_as_float(r.y); S[i][2] += __uint_as_float(r.z); S[i][3] += __uint_as_float(r.w);
    }
    const int g = (k.lw >> 6) & 7, c = ((k.lw >> 4) ^ (k.lw >> 7)) & 3;
    const float NEG = -__int_as_float(0x7f800000);
    if (2 * c > g) { S[NTL - 2][0] = NEG; S[NTL - 1][2] = NEG; }
    if (2 * c + 1 > g) { S[NTL - 2][1] = NEG; S[NTL - 1][3] = NEG; }
    float m0 = fmaxf(S[0][0], S[0][1]), m1 = fmaxf(S[0][2], S[0][3]);
#pragma unroll
    for (int i = 1; i < NTL; i++) { if (i < NTL - 1) m0 = fmaxf(m0, fmaxf(S[i][0], S[i][1])); m1 = fmaxf(m1, fmaxf(S[i][2], S[i][3])); }
    m0 = fmaxf(m0, __shfl_xor_sync(0xffffffffu, m0, 1)); m1 = fmaxf(m1, __shfl_xor_sync(0xffffffffu, m1, 1));
    m0 = fmaxf(m0, __shfl_xor_sync(0xffffffffu, m0, 2)); m1 = fmaxf(m1, __shfl_xor_sync(0xffffffffu, m1, 2));
    m0 *= -SC_LOG2E; m1 *= -SC_LOG2E;
    uint32_t P[NTL][2];
#pragma unroll
    for (int i = 0; i < NTL; i++) {
        P[i][0] = i < NTL - 1 ? pack2(ex2(fmaf(S[i][0], SC_LOG2E, m0)), ex2(fmaf(S[i][1], SC_LOG2E, m0))) : 0u;
        P[i][1] = pack2(ex2(fmaf(S[i][2], SC_LOG2E, m1)), ex2(fmaf(S[i][3], SC_LOG2E, m1)));
    }
    float l[4] = {0, 0, 0, 0};
#pragma unroll
    for (int i = 0; i < NTL; i++) mma8(l, P[i][0], P[i][1], 0x3f803f80u);
    const float l0 = rcp(l[0]), l1 = rcp(l[2]);

    const uint32_t st = sb + sxr + c * 128 + g * 16;
#pragma unroll
    for (int e = 0; e < 2; e++) {
        const uint4 vm = vmm[e];
        uint32_t u[2][4];
#pragma unroll
        for (int n = 0; n < 4; n++) {
            float a[4] = {0, 0, 0, 0};
#pragma unroll
            for (int m = 0; m <= MT; m++) {
                const uint4 v = V[m][e * 2 + (n >> 1)];
                mma8(a, P[1 + 2 * m][0], P[1 + 2 * m][1], (n & 1) ? v.y : v.x); mma8(a, P[2 + 2 * m][0], P[2 + 2 * m][1], (n & 1) ? v.w : v.z);
            }
            mma8(a, P[0][0], P[0][1], n == 0 ? vm.x : n == 1 ? vm.y : n == 2 ? vm.z : vm.w);
            u[0][n] = pack2(a[0] * l0, a[1] * l0); u[1][n] = pack2(a[2] * l1, a[3] * l1);
        }
        sts128(st + e * 512, u[0][0], u[0][1], u[0][2], u[0][3]); sts128(st + e * 512 + 1024, u[1][0], u[1][1], u[1][2], u[1][3]);
    }
    TS(10);
}
__device__ __forceinline__ void rec_attn(const Params& p, uint32_t sb, int X, int j, int head, uint32_t rank) {
    const int lane = threadIdx.x & 31;
    RecH k;
    k.lw = __shfl_sync(0xffffffffu, sb + (lane ^ (lane >> 3)) * 16, lane);
    k.lm = __shfl_sync(0xffffffffu, sb + ((lane & 7) * 4 + ((lane >> 3) ^ ((lane & 7) >> 1))) * 16, lane);
    k.lq = __shfl_sync(0xffffffffu, sb + ((lane >> 3) & 1) * 512 + ((lane & 7) * 4 + ((lane >> 4) ^ ((lane & 7) >> 1))) * 16, lane);
    k.lv = __shfl_sync(0xffffffffu, sb + (lane >> 4) * 512 + ((lane & 7) * 4 + (((lane >> 3) & 1) ^ ((lane & 7) >> 1))) * 16, lane);
    k.lu = __shfl_sync(0xffffffffu, sb + ((lane & 6) * 4 + (((lane >> 3) * 2 + (lane & 1)) ^ (lane & 6))) * 16, lane);
    k.sb = sb; k.zero = p.zero;
    const uint32_t dp = mapa(sb, rank ^ 1) - sb;
    char* zp = acc_base() + (j ? X * 32768 + acc_main(rank, head * 8) : X * 1024 + acc_extra(rank, head * 8));
    mbar_expect1(sb + R_BAR + (RB_QK + X * 2 + j) * 8, 2048); mbar_expect1(sb + R_BAR + (RB_V + X * 2 + j) * 8, 1024);
    bool early = j;
#pragma unroll 1
    for (int s = 0; s < 64; s++) {
        TSET(X ? s + p.b1 : s, j == GPJ ? 1 + X : 3);
        TS(0);
        if (!early && !j) { wait_cnt_warp(cnt_ptr(C_QKV0 + X, s >> 2), 384); rec_load_tile(sb, X, s, head, rank); }
        early = !j && s < 63 && ((s & 3) != 3 || chunk_ready(X, s + 1));
        asm volatile("cp.async.bulk.wait_group.read 0;" ::: "memory");
        PROF(lane == 0 && j == 0, X * 64 + s);
        uint4 V[2][4], vm[2];
        rec_mattn(k, dp, X, j, s, V, vm);
        if (s) rec_publish(X, s - 1);
        bar_sync(NB_XG + X, 320);
        TS(8);
        if (rank) rec_xattn<1>(k, X, j, s, head, early, V, vm); else rec_xattn<0>(k, X, j, s, head, early, V, vm);
        fence_async_smem();
        __syncwarp();
        asm volatile("{.reg .pred p; elect.sync _|p,0xffffffff;\n"
                     "@p cp.async.bulk.global.shared::cta.bulk_group.L2::cache_hint [%0],[%1],2048,%2;\n"
                     "@p cp.async.bulk.global.shared::cta.bulk_group [%3],[%4],%5;\n"
                     "cp.async.bulk.commit_group;}"
                     ::"l"(g_o[X] + ((s >> 2) * 64 + head * 2 + j) * 1024 + ((s & 3) * 2 + rank) * 128), "r"(sb + R_SX + (X * 2 + (j ^ 1)) * 2560),
                       "l"((X && s < 40) ? POL_LATE : POL_SOON), "l"(zp + acc_slot(s + 2)), "r"(sb + R_Z), "r"(j ? 128 : 32) : "memory");
    }
    rec_publish(X, 63);
}

__device__ __forceinline__ void rec_init(const Params& p, uint32_t sb, int head, uint32_t rank) {
    const uint32_t b = sb + R_BAR;
    const int i = threadIdx.x - 320;
    if (i >= 0 && i < RB_N) {
        mbar_init(b + i * 8, 1);
        asm volatile("fence.mbarrier_init.release.cluster;" ::: "memory");
    }
    if (i == 0) mbar_expect(b + RB_INIT * 8, 196608);
    if (i >= 0 && i < 32) sts32(sb + R_Z + i * 4, 0);
}

#define NSTGN 8
constexpr int NSTG = NSTGN, STG_B = 24576;
#define CSH 6
#define LAGH 4
#define NSBN 8
constexpr int NSB = NSBN;
constexpr int B_OUT = NSTG * STG_B  , B_UT = B_OUT, B_YT = B_UT + 8192  ,
              B_ST = 229376  , B_BAR = 231936;
static_assert(B_OUT + NSB * 4096 <= B_ST && B_ST + 2048 <= B_BAR && B_YT + 10240 <= B_ST, "smem map");
enum { BB_FULL = 0, BB_EMPTY = 8, BB_STF = 16, BB_STE = 18, BB_SF = 20  , BB_GO = 21, BB_IDLE = 22, BB_DONE = 23  , BB_N = 27 };
enum { NB_C = 11, NB_WG = 12   };

__device__ __forceinline__ void bulk_init(uint32_t sb) {
    const int i = threadIdx.x - 320;
    if (i >= 0 && i < BB_N) {
        mbar_init(sb + B_BAR + i * 8, (i >= BB_EMPTY && i < BB_EMPTY + NSTG) ? 4 : i == BB_STF ? 2 : i == BB_STE ? 8 : i >= BB_DONE ? 4 : 1);
        asm volatile("fence.mbarrier_init.release.cluster;" ::: "memory");
    }
}

struct Task { int type, layer, ch, a, b, c, blk; bool pair, dry; };
__device__ __forceinline__ Task task_of(uint32_t tk, uint32_t rank) {
    Task t;
    t.type = tk & 7; t.layer = (tk >> 3) & 1; t.a = (tk >> 8) & 255; t.b = (tk >> 16) & 255; t.c = (tk >> 24) & 127; t.dry = tk >> 31;
    t.pair = t.type <= T_OP && (t.c & 64);
    t.ch = ((tk >> 4) & 15) + (t.pair ? rank : 0);
    t.blk = t.type == T_QKV ? t.a + (t.pair ? 0 : rank * 4) : 192 + (t.pair ? (t.c >> 2) & 4 : rank * 4);
    return t;
}
__device__ __forceinline__ void bulk_producer(const Params& p, uint32_t sb, int cl, uint32_t rank) {
    int st = 0; uint32_t ph = 1;
    bool gated = false;
#define ACQ(bytes) do { mbar_wait(sb + B_BAR + (BB_EMPTY + st) * 8, ph); mbar_expect1(sb + B_BAR + (BB_FULL + st) * 8, bytes); } while (0)
#define NEXT do { if (++st == NSTG) { st = 0; ph ^= 1; } } while (0)
#pragma unroll 1
    for (int ti = 0; ti < MAXT; ti++) {
        const Task t = task_of(p.task[cl][ti], rank);
        const int layer = t.layer, ch = t.ch;
        if (t.type == T_END) break;
        if (t.type <= T_OP) {
            const bool qkv = t.type == T_QKV, first = qkv && !layer;
            const int rg = qkv ? (layer * 16 + ch) * 128 : 4096 + ((layer * 16 + ch) * 64 + t.a) * 16;
            const int nh = qkv ? 16 : 2 * t.b, row = qkv ? 0 : t.a * 64;
            const unsigned* dep = first ? g_gate : cnt_ptr(qkv ? C_CV : C_O0 + layer, ch);
            const unsigned need = first ? lds32(sb + S_GATE) : qkv ? 16 : 512;
            const uint64_t pol = qkv ? POL_N : POL_LAST;
            const CUtensorMap *tb = &p.t3[t.pair][t.blk >> 6], *ta = &p.ta[t.pair];
            const uint32_t db = sb + 8192 + (t.pair ? rank * 8192 : 0), da = sb + (t.pair ? 0 : rank * 4096);
            const int zb = (t.blk & 63) + (t.pair ? rank * 2 : 0), ya = rg + (t.pair ? 0 : rank * 8);
            const uint16_t mb = t.pair ? 3 : 1 << rank, ma = t.pair ? 1 << rank : 3;
            int h = 0;
            if (!t.dry && !(first && gated)) {
                unsigned v;
                asm volatile("ld.relaxed.gpu.global.u32 %0,[%1];" : "=r"(v) : "l"(dep) : "memory");
                if (!__all_sync(0xffffffffu, v >= need)) {
                    const int pend = min(nh, first ? 4 : NSTG), s0 = st;
#pragma unroll 1
                    for (; h < pend; h++) { ACQ(STG_B); tma3d_mc(db + st * STG_B, tb, row + h * 32, zb, sb + B_BAR + (BB_FULL + st) * 8, mb); NEXT; }
                    wait_cnt_warp(dep, need);
#pragma unroll 1
                    for (int k = 0; k < pend; k++) {
                        const int s2 = s0 + k - (s0 + k >= NSTG ? NSTG : 0);
                        tma2d_mc(da + s2 * STG_B, ta, (k & 1) * 256, ya + (k >> 1) * 16, sb + B_BAR + (BB_FULL + s2) * 8, ma, pol);
                    }
                }
                gated = true;
            }
#pragma unroll 1
            for (; h < nh; h++) {
                ACQ(STG_B);
                tma3d_mc(db + st * STG_B, tb, row + h * 32, zb, sb + B_BAR + (BB_FULL + st) * 8, mb);
                tma2d_mc(da + st * STG_B, ta, (h & 1) * 256, ya + (h >> 1) * 16, sb + B_BAR + (BB_FULL + st) * 8, ma, pol);
                NEXT;
            }
        } else if (t.type == T_CV) {
            const int q = t.a + rank, jhi = layer ? t.b : min(ch, 1), jlo = layer ? t.c : 0;
            if (jhi && !t.dry) wait_cnt_warp(cnt_ptr(C_CV, ch - (layer ? jlo : 1)), 16);
            if (!layer) {
#pragma unroll 1
                for (int i = 0; i < min(ch, 3); i++) {
                    ACQ(16384);
                    if (i && !t.dry) wait_cnt_warp(cnt_ptr(C_H, ch - (i != 1)), ch - (i != 1) >= HSPLIT ? 32 : 16);
                    bulk_g2s1(sb + st * STG_B, g_carry[i] + ((ch - (i != 1)) * 16 + q) * 1024, 16384, sb + B_BAR + (BB_FULL + st) * 8, POL_LAST);
                    NEXT;
                }
            }
#pragma unroll 1
            for (int j = jhi; j >= jlo; j--) {
                ACQ(32 * PW * 4);
                bulk_g2s1(sb + st * STG_B, g_P + (q * 16 + j) * 32 * PW, 32 * PW * 4, sb + B_BAR + (BB_FULL + st) * 8, POL_N);
                NEXT;
                if (j) {
                    ACQ(8192);
                    bulk_g2s1(sb + st * STG_B, g_u + (q * 16 + ch - j) * 512, 8192, sb + B_BAR + (BB_FULL + st) * 8, POL_N);
                    NEXT;
                }
            }
        }
    }
}

__device__ __forceinline__ void bulk_stats(const Params& p, uint32_t sb, int cl, uint32_t rank) {
    const int r0 = threadIdx.x - 288;
    int n = 0;
    bool gated = false;
    for (int ti = 0; ti < MAXT; ti++) {
        const Task t = task_of(p.task[cl][ti], rank);
        const int type = t.type, layer = t.layer, ch = t.ch;
        if (type == T_END) break;
        if (type != T_QKV) continue;
        if (!t.dry) {
            if (!gated) { wait_cnt_warp(g_gate, lds32(sb + S_GATE)); gated = true; }
            wait_cnt_warp(cnt_ptr(layer ? C_CV : C_ST, ch), 16);
        }
        const int np = p.nst[layer];
        const float n0 = 512.f / np, in0 = np * (1.f / 512.f);
        const float4* cp = (const float4*)g_cs + t.blk * 16 + r0;
        float4 cs = __ldcg(cp);
        { const float4 ct = __ldcg(cp + 3072); cs.x += ct.x; cs.y += ct.y; cs.z += ct.z; cs.w += ct.w; }
        const float4* src = (const float4*)(g_st[layer] + ch * 128) + r0;
        const float4 f = __ldcg(src);
        const float m0 = f.x * in0, m1 = f.z * in0;
        float sd0 = 0, sq0 = 0, M0 = f.y, sd1 = 0, sq1 = 0, M1 = f.w;
#pragma unroll 3
        for (int i = 1; i < np; i++) {
            const float4 v = __ldcg(src + i * 1024);
            const float d0 = v.x * in0 - m0, d1 = v.z * in0 - m1;
            sd0 += d0; sq0 += d0 * d0; M0 += v.y; sd1 += d1; sq1 += d1 * d1; M1 += v.w;
        }
        const float b0 = sd0 / np, b1 = sd1 / np;
        const float2 o0 = ln_finish(m0 + b0, (M0 + fmaxf(n0 * (sq0 - np * b0 * b0), 0.f)) * (1.f / 512.f));
        const float2 o1 = ln_finish(m1 + b1, (M1 + fmaxf(n0 * (sq1 - np * b1 * b1), 0.f)) * (1.f / 512.f));
        mbar_wait(sb + B_BAR + BB_STE * 8, (n & 1) ^ 1);
        const uint32_t ca = sb + B_ST + 1024 + (r0 >> 3) * 128 + (r0 & 1) * 64 + ((r0 >> 1) & 3) * 8;
        sts64(ca, __float_as_uint(cs.x), __float_as_uint(cs.y)); sts64(ca + 32, __float_as_uint(cs.z), __float_as_uint(cs.w));
        sts128(sb + B_ST + r0 * 16, __float_as_uint(-o0.x), __float_as_uint(1.f / o0.y), __float_as_uint(-o1.x), __float_as_uint(1.f / o1.y));
        __syncwarp();
        mbar_arrive1(sb + B_BAR + BB_STF * 8);
        n++;
    }
}

__device__ __forceinline__ uint4* qkv_dst(int layer, int ch, int w, int blk);
__device__ __forceinline__ uint4* op_dst(int layer, int ch, int slot, int w, uint32_t rank);
__device__ __forceinline__ uint64_t out_pol(int type, int layer, int ch) { return (type == T_QKV ? (!layer && ch > 1) : (layer && ch < 10)) ? POL_LATE : POL_SOON; }
__device__ __forceinline__ void bulk_release(const Params& p, uint32_t sb, int cl, uint32_t rank) {
    int nd = 0;
    for (int ti = 0; ti < MAXT; ti++) {
        const Task t = task_of(p.task[cl][ti], rank);
        const int type = t.type, layer = t.layer, ch = t.ch;
        if (type == T_END) break;
        if (type == T_FIN || (type == T_OP && (t.c & 32))) continue;
#pragma unroll 1
        for (int w = 0; w < 8; w++) {
            if (!(w & 3)) { mbar_wait(sb + B_BAR + (BB_DONE + (nd & 1) * 2 + (w >> 2)) * 8, (nd >> 1) & 1); fence_async_smem(); }
            const uint4* dst = type == T_QKV ? qkv_dst(layer, ch, w, t.blk) + (8 - NSB / 2) * 32 : op_dst(layer, ch, t.c & 15, w, (t.blk >> 2) & 1) + (16 - NSB) * 32;
            if (NSB && type != T_CV)
                asm volatile("{.reg .pred p; elect.sync _|p,0xffffffff; @p cp.async.bulk.global.shared::cta.bulk_group.L2::cache_hint [%0],[%1],%2,%3;\n"
                             "@p cp.async.bulk.global.shared::cta.bulk_group.L2::cache_hint [%4],[%5],%2,%3;}"
                             ::"l"(dst), "r"(sb + B_OUT + w * NSB * 512), "r"(NSB * 256), "l"(out_pol(type, layer, ch)),
                               "l"(dst + (type == T_QKV ? 1536 : NSB * 16)), "r"(sb + B_OUT + w * NSB * 512 + NSB * 256) : "memory");
        }
        nd++;
        if (elect()) {
            asm volatile("cp.async.bulk.commit_group;" ::: "memory");
            asm volatile("cp.async.bulk.wait_group 0;" ::: "memory");
            mbar_arrive(sb + B_BAR + BB_SF * 8);
            if (!t.dry) red_release(cnt_ptr(type == T_QKV ? C_QKV0 + layer : type == T_OP ? C_OP0 + layer : layer ? C_H : C_CV, ch), type == T_CV ? 1 : 2 * t.b);
            PROF(true, 3600 + ti * 4 + 3);
        }
        __syncwarp();
    }
}

__device__ __forceinline__ void stage_release(uint32_t sb, int w, int st) {
    if (!(w & 2)) mbar_arrive1_cluster(mapa(sb + B_BAR + (BB_EMPTY + st) * 8, w & 1));
}
template <bool ACC>
__device__ __forceinline__ void gemm_run(float* acc, uint32_t sb, int w, int h0, int h1, uint32_t& r0, uint32_t& r1, int& st, uint32_t& ph) {
    const uint64_t da0 = mkdesc(sb + (w >> 2) * 4096, 128, 512, 0), db0 = mkdesc(sb + 8192, 4096, 1024, 1);
    const uint32_t rel0 = mapa(sb + B_BAR + BB_EMPTY * 8, w & 1);
#pragma unroll 1
    for (int h = h0; h < h1; h++) {
        const uint64_t da = da0 + st * (STG_B >> 4), db = db0 + st * (STG_B >> 4);
        mbar_wait(sb + B_BAR + (BB_FULL + st) * 8, ph);
        if (ACC) wg_wait<1>();
        wg_fence();
        wgmma256<ACC>(acc, da, db);
        wgmma256<true>(acc, da + 16, db + 128);
        wg_commit();
        if (ACC) mbar_arrive1_cluster((w == 2 && h == LAGH - 1) ? sb + B_BAR + BB_GO * 8 : r0);
        r0 = r1;
        if (!(w & 2)) r1 = rel0 + st * 8;
        if (++st == NSTG) { st = 0; ph ^= 1; }
    }
}

__device__ __forceinline__ uint4* qkv_dst(int layer, int ch, int w, int blk) {
    return g_qkv[layer] + (size_t)((ch * 4 + (w >> 1)) * 32 + ((blk & 63) >> 1)) * 1536 + (blk >> 6) * 512 + (w & 1) * 256;
}
__device__ __forceinline__ uint4* op_dst(int layer, int ch, int slot, int w, uint32_t rank) {
    return g_pp[layer] + (size_t)(ch * MAXSPLIT + slot) * 8192 + (w * 32 + rank * 16) * 32;
}
__device__ __forceinline__ void qkv_epilogue(const float* acc, const uint4* cs, uint2 s0, uint2 s1, uint32_t sb, int w, int layer, int ch, int blk0) {
    const int lane = threadIdx.x & 31, pos = lane ^ (lane >> 3);
    uint4* dst = qkv_dst(layer, ch, w, blk0) + pos;
    const uint64_t pol = out_pol(T_QKV, layer, ch);
#pragma unroll
    for (int n = 0; n < 16; n++) {
        const int j = (n >> 3) * 4 + ((n >> 2) & 1) + (n & 1) * 2, h = (n >> 1) & 1;
        const float* a = acc + j * 16 + h * 2;
        const float mu = __uint_as_float(h ? s1.x : s0.x), r = __uint_as_float(h ? s1.y : s0.y);
        const uint4 ca = cs[2 * j], cb = cs[2 * j + 1];
        uint4 v;
        v.x = pack2(fmaf(mu, __uint_as_float(ca.x), a[0]) * r, fmaf(mu, __uint_as_float(ca.y), a[1]) * r);
        v.y = pack2(fmaf(mu, __uint_as_float(ca.z), a[4]) * r, fmaf(mu, __uint_as_float(ca.w), a[5]) * r);
        v.z = pack2(fmaf(mu, __uint_as_float(cb.x), a[8]) * r, fmaf(mu, __uint_as_float(cb.y), a[9]) * r);
        v.w = pack2(fmaf(mu, __uint_as_float(cb.z), a[12]) * r, fmaf(mu, __uint_as_float(cb.w), a[13]) * r);
        if ((j & 3) * 2 + h < 8 - NSB / 2) stg128(dst + (j >> 2) * 1536 + ((j & 3) * 2 + h) * 32, v, pol);
        else sts128(sb + B_OUT + (w * NSB + (j >> 2) * (NSB / 2) + (j & 3) * 2 + h - (8 - NSB / 2)) * 512 + pos * 16, v.x, v.y, v.z, v.w);
    }
}

template <int NB>
__device__ __forceinline__ void load_resid(uint32_t* r, int layer, int ch, int w, int cb) {
    const uint32_t* rp = (const uint32_t*)(g_xA[layer] + (ch * 8 + (cb >> 2)) * 1024 + w * 128 + (cb & 3) * 16) + (threadIdx.x & 31);
#pragma unroll
    for (int i = 0; i < NB * 4; i++) r[i] = __ldcg(rp + (i >> 1) * 32 + (i & 1) * 256);
}
template <int NB, int NS>
__device__ __forceinline__ void sum_partials(float* x, const uint32_t* r, int layer, int ch, int w, int cb, int ns) {
    const uint4* src = g_pp[layer] + (size_t)ch * MAXSPLIT * 8192 + (w * 32 + cb) * 32 + (threadIdx.x & 31);
    const int dg = ((threadIdx.x & 31) >> 2) - 2 * (threadIdx.x & 3);
    const uint32_t idm = dg == 0 ? 0x00003f80u : dg == 1 ? 0x3f800000u : 0u;
    uint4 v[NB][NS];
#pragma unroll
    for (int b = 0; b < NB; b++)
#pragma unroll
        for (int s = 0; s < NS; s++) { v[b][s] = make_uint4(0, 0, 0, 0); if (s < ns) v[b][s] = ldcg128_last(src + b * 32 + s * 8192); }
#pragma unroll
    for (int b = 0; b < NB; b++) {
        float* y = x + b * 8;
#pragma unroll
        for (int i = 0; i < 8; i++) y[i] = 0;
#pragma unroll
        for (int s = 0; s < NS; s++) { mma8(y, v[b][s].x, v[b][s].y, idm); mma8(y + 4, v[b][s].z, v[b][s].w, idm); }
#pragma unroll
        for (int i = 0; i < 4; i++) { y[2 * i] = rbf(rbf(y[2 * i]) + blo(r[b * 4 + i])); y[2 * i + 1] = rbf(rbf(y[2 * i + 1]) + bhi(r[b * 4 + i])); }
    }
}

__device__ __forceinline__ float4 row_stats32(const float* x) {
    float a = (x[0] + x[1]) + (x[4] + x[5]) + (x[8] + x[9]) + (x[12] + x[13]);
    float b = (x[2] + x[3]) + (x[6] + x[7]) + (x[10] + x[11]) + (x[14] + x[15]);
    a += __shfl_xor_sync(0xffffffffu, a, 1); b += __shfl_xor_sync(0xffffffffu, b, 1);
    a += __shfl_xor_sync(0xffffffffu, a, 2); b += __shfl_xor_sync(0xffffffffu, b, 2);
    const float ma = a * (1.f / 32.f), mb = b * (1.f / 32.f);
    float qa = 0, qb = 0;
#pragma unroll
    for (int i = 0; i < 4; i++) {
        float d0 = x[4 * i] - ma, d1 = x[4 * i + 1] - ma, d2 = x[4 * i + 2] - mb, d3 = x[4 * i + 3] - mb;
        qa += d0 * d0 + d1 * d1; qb += d2 * d2 + d3 * d3;
    }
    qa += __shfl_xor_sync(0xffffffffu, qa, 1); qb += __shfl_xor_sync(0xffffffffu, qb, 1);
    qa += __shfl_xor_sync(0xffffffffu, qa, 2); qb += __shfl_xor_sync(0xffffffffu, qb, 2);
    return make_float4(a, qa, b, qb);
}

__device__ __forceinline__ void conv_stage(float* Y, uint32_t pbase, uint32_t ubase) {
    const int lane = threadIdx.x & 31, w = threadIdx.x >> 5, g = lane >> 2, c = lane & 3;
#pragma unroll
    for (int cp = 0; cp < 2; cp++) {
        const int chl = w * 4 + cp * 2 + (lane >> 4);
        const uint4 b = ldsm4(ubase + chl * 256 + ((lane >> 3) & 1) * 128 + (((lane & 7) ^ (chl & 7)) << 4));
#pragma unroll
        for (int h = 0; h < 2; h++) {
            const uint32_t pa = pbase + ((w * 4 + cp * 2 + h) * PW + 16 + g - 2 * c) * 4;
            uint32_t lo = lds32(pa - 32);
#pragma unroll
            for (int d = 0; d < 8; d++) {
                const uint32_t a0 = lds32(pa + d * 64), a1 = lds32(pa + d * 64 + 32);
                mma16(Y + ((cp * 2 + h) * 8 + d) * 4, a0, a1, lo, a0, h ? b.z : b.x, h ? b.w : b.y);
                lo = a1;
            }
        }
    }
}

__device__ __forceinline__ void conv_combine(const float* y8, float* cur, float* nxt) {
    const int lane = threadIdx.x & 31, c = lane & 3;
    cur[0] = y8[0]; cur[1] = y8[1] + y8[4]; cur[2] = y8[2]; cur[3] = y8[3] + y8[6];
    nxt[0] = y8[29]; nxt[1] = 0.f; nxt[2] = y8[31]; nxt[3] = 0.f;
#pragma unroll
    for (int e = 1; e < 4; e++) {
        const int src = (lane & ~3) | ((c - e) & 3);
        const float v0 = __shfl_sync(0xffffffffu, y8[8 * e] + y8[8 * e - 3], src), v1 = __shfl_sync(0xffffffffu, y8[8 * e + 1] + y8[8 * e + 4], src);
        const float v2 = __shfl_sync(0xffffffffu, y8[8 * e + 2] + y8[8 * e - 1], src), v3 = __shfl_sync(0xffffffffu, y8[8 * e + 3] + y8[8 * e + 6], src);
        if (c >= e) { cur[0] += v0; cur[1] += v1; cur[2] += v2; cur[3] += v3; }
        else { nxt[0] += v0; nxt[1] += v1; nxt[2] += v2; nxt[3] += v3; }
    }
}

__device__ __forceinline__ void conv_task(const Params& p, float* Y, uint32_t sb, int w, int ch, int q, bool hist, int hhi, int hlo, bool dry, int& st, uint32_t& ph, int nd) {
    const int tid = threadIdx.x, lane = tid & 31, g = lane >> 2, c = lane & 3;
#pragma unroll
    for (int i = 0; i < 128; i++) Y[i] = 0;
    const int jhi = hist ? hhi : min(ch, 1), jlo = hist ? hlo : 1;
    uint32_t rs[8], dk[4];
    if (!hist) {
        load_resid<2>(rs, 0, ch, w, 2 * q);
#pragma unroll
        for (int i = 0; i < 4; i++) dk[i] = __ldg((const uint32_t*)(p.Dskip + q * 32 + i * 8 + 2 * c));
#pragma unroll 1
        for (int i = 0; i < 3 && i < ch; i++) {
            mbar_wait(sb + B_BAR + (BB_FULL + st) * 8, ph);
#pragma unroll
            for (int k = 0; k < 4; k++) {
                const uint4 cr = lds128(sb + st * STG_B + k * 4096 + tid * 16);
                Y[k * 32] += __uint_as_float(cr.x); Y[k * 32 + 1] += __uint_as_float(cr.y); Y[k * 32 + 2] += __uint_as_float(cr.z); Y[k * 32 + 3] += __uint_as_float(cr.w);
            }
            bar_sync(NB_WG + (w >> 2), 128);
            stage_release(sb, w, st);
            if (++st == NSTG) { st = 0; ph ^= 1; }
        }
    }
    for (int j = jhi; j >= jlo; j--) {
        const int s0 = st;
        mbar_wait(sb + B_BAR + (BB_FULL + st) * 8, ph);
        if (++st == NSTG) { st = 0; ph ^= 1; }
        mbar_wait(sb + B_BAR + (BB_FULL + st) * 8, ph);
        conv_stage(Y, sb + s0 * STG_B, sb + st * STG_B);
        bar_sync(NB_WG + (w >> 2), 128);
        stage_release(sb, w, s0); stage_release(sb, w, st);
        if (++st == NSTG) { st = 0; ph ^= 1; }
    }
    mbar_wait(sb + B_BAR + BB_SF * 8, (nd & 1) ^ 1);
    if (hist) {
        if (jhi < ch) wait_cnt_warp(cnt_ptr(C_H, ch), 16);
#pragma unroll
        for (int k = 0; k < 4; k++) {
            float4* d1 = g_carry[1] + ((ch * 16 + q) * 4 + k) * 256 + tid;
            float4* d2 = g_carry[2] + ((ch * 16 + q) * 4 + k) * 256 + tid;
            float4 o1 = make_float4(0, 0, 0, 0), o2 = o1;
            if (jhi < ch) { o1 = __ldcg(d1); o2 = __ldcg(d2); }
            float cur[4], nxt[4];
            conv_combine(Y + k * 32, cur, nxt);
            *d1 = make_float4(cur[0] + o1.x, cur[1] + o1.y, cur[2] + o1.z, cur[3] + o1.w);
            *d2 = make_float4(nxt[0] + o2.x, nxt[1] + o2.y, nxt[2] + o2.z, nxt[3] + o2.w);
        }
        return;
    }
    mbar_wait(sb + B_BAR + (BB_FULL + st) * 8, ph);
    wait_cnt_warp(cnt_ptr(C_OP0, ch), dry ? 0 : 256);
    PROF(tid == 0, 2048 + ch * 8);
    float x[16];
    sum_partials<2, OPS1>(x, rs, 0, ch, w, 2 * q, OPS1);
    if (x[0] == 1.2345e30f) PROF(true, 0);
    PROF(tid == 0, 2048 + ch * 8 + 1);
    float2 ln0, ln1;
    {
        const float4 s = row_stats32(x);
        float2* dst = g_st2 + (ch * 16 + q) * 128 + w * 16 + g;
        if (c == 0 && !dry) asm volatile("st.relaxed.gpu.global.b64 [%0],%1;" ::"l"(dst), "l"(((uint64_t)__float_as_uint(s.y) << 32) | __float_as_uint(s.x)) : "memory");
        if (c == 1 && !dry) asm volatile("st.relaxed.gpu.global.b64 [%0],%1;" ::"l"(dst + 8), "l"(((uint64_t)__float_as_uint(s.w) << 32) | __float_as_uint(s.z)) : "memory");
        const float2* src = g_st2 + (ch * 16 + (lane >> 4) * 8) * 128 + w * 16 + (lane & 15);
        uint64_t v[8];
        int n = 0;
        while (true) {
            bool bad = false;
#pragma unroll
            for (int i = 0; i < 8; i++) asm volatile("ld.relaxed.gpu.global.b64 %0,[%1];" : "=l"(v[i]) : "l"(src + i * 128) : "memory");
#pragma unroll
            for (int i = 0; i < 8; i++) bad = bad || (uint32_t)(v[i] >> 32) == 0xffffffffu;
            if (!__any_sync(0xffffffffu, bad && !dry)) break;
            if (++n > 2000000) __trap();
        }
        float sm = 0;
#pragma unroll
        for (int i = 0; i < 8; i++) sm += __uint_as_float((uint32_t)v[i]);
        sm += __shfl_xor_sync(0xffffffffu, sm, 16);
        const float mean = sm * (1.f / 512.f);
        float M2 = 0;
#pragma unroll
        for (int i = 0; i < 8; i++) { const float d = __uint_as_float((uint32_t)v[i]) * (1.f / 32.f) - mean; M2 += __uint_as_float((uint32_t)(v[i] >> 32)) + 32.f * d * d; }
        M2 += __shfl_xor_sync(0xffffffffu, M2, 16);
        const float2 o = ln_finish(mean, M2 * (1.f / 512.f));
        ln0.x = __shfl_sync(0xffffffffu, o.x, g); ln0.y = __shfl_sync(0xffffffffu, o.y, g);
        ln1.x = __shfl_sync(0xffffffffu, o.x, g + 8); ln1.y = __shfl_sync(0xffffffffu, o.y, g + 8);
    }
    PROF(tid == 0, 2048 + ch * 8 + 2);
    uint32_t u[8];
#pragma unroll
    for (int i = 0; i < 8; i++) {
        const float2 l = (i & 1) ? ln1 : ln0;
        u[i] = pack2(__fdividef(rbf(x[2 * i] - l.x), l.y), __fdividef(rbf(x[2 * i + 1] - l.x), l.y));
        const int chl = (i >> 1) * 8 + g;
        sts32(sb + B_UT + chl * 256 + (i & 1) * 128 + ((w ^ g) << 4) + c * 4, movm(u[i]));
    }
    fence_async_smem();
    bar_sync(NB_C, 256);
    if (w == 0 && ch < 15 && elect()) {
        asm volatile("cp.async.bulk.global.shared::cta.bulk_group [%0],[%1],%2;" ::"l"(g_u + (q * 16 + ch) * 512), "r"(sb + B_UT), "r"(8192) : "memory");
        asm volatile("cp.async.bulk.commit_group;" ::: "memory");
    }
    PROF(tid == 0, 2048 + ch * 8 + 3);
    conv_stage(Y, sb + st * STG_B, sb + B_UT);
    uint32_t yp[4][2];
    {
        float y[4][4];
#pragma unroll
        for (int k = 0; k < 4; k++) {
            float nxt[4];
            conv_combine(Y + k * 32, y[k], nxt);
            g_carry[0][((ch * 16 + q) * 4 + k) * 256 + tid] = make_float4(nxt[0], nxt[1], nxt[2], nxt[3]);
        }
#pragma unroll
        for (int i = 0; i < 4; i++) { yp[i][0] = pack2(y[0][i], y[1][i]); yp[i][1] = pack2(y[2][i], y[3][i]); }
    }
#pragma unroll
    for (int i = 0; i < 4; i++) sts64(sb + B_YT + (16 * (2 * c + (i & 1)) + g + (i >> 1) * 8) * 80 + w * 8, yp[i][0], yp[i][1]);
    bar_sync(NB_C, 256);
    stage_release(sb, w, st);
    if (++st == NSTG) { st = 0; ph ^= 1; }
    PROF(tid == 0, 2048 + ch * 8 + 4);
    uint32_t xo[8];
    uint32_t* dA = (uint32_t*)(g_xA[1] + (ch * 8 + (q >> 1)) * 1024 + (w * 2) * 64 + (q & 1) * 32) + lane;
#pragma unroll
    for (int i = 0; i < 8; i++) {
        const int col = (i >> 1) * 8 + 2 * c;
        const uint32_t yv = lds32(sb + B_YT + (w * 16 + g + (i & 1) * 8) * 80 + col * 2);
        const uint32_t dv = dk[i >> 1];
        x[2 * i] = rbf(x[2 * i] + rbf(blo(yv) + rbf(blo(u[i]) * blo(dv))));
        x[2 * i + 1] = rbf(x[2 * i + 1] + rbf(bhi(yv) + rbf(bhi(u[i]) * bhi(dv))));
        xo[i] = pack2(x[2 * i], x[2 * i + 1]);
        dA[(i >> 1) * 32 + (i & 1) * 256] = xo[i];
    }
    {
        const float4 s = row_stats32(x);
        float2* dst = g_st[1] + q * 2048 + ch * 128 + w * 16 + g;
        if (c == 0) dst[0] = make_float2(s.x, s.y);
        if (c == 1) dst[8] = make_float2(s.z, s.w);
        __syncwarp();
    }
    PROF(tid == 0, 2048 + ch * 8 + 5);
    if (w == 0) asm volatile("cp.async.bulk.wait_group 0;" ::: "memory");
    PROF(tid == 0, 2048 + ch * 8 + 6);
}

__device__ __forceinline__ void out_store(const Params& p, const float* x, int ch, int cb) {
    const int lane = threadIdx.x & 31, w = threadIdx.x >> 5, g = lane >> 2, c = lane & 3;
#pragma unroll
    for (int h = 0; h < 2; h++) {
        const float* y = x + h * 2;
        uint32_t v0 = pack2(y[0], y[1]), v1 = pack2(y[4], y[5]), v2 = pack2(y[8], y[9]), v3 = pack2(y[12], y[13]);
        uint32_t t0 = (c & 1) ? v0 : v1, t1 = (c & 1) ? v2 : v3;
        t0 = __shfl_xor_sync(0xffffffffu, t0, 1); t1 = __shfl_xor_sync(0xffffffffu, t1, 1);
        if (c & 1) { v0 = t0; v2 = t1; } else { v1 = t0; v3 = t1; }
        t0 = (c & 2) ? v0 : v2; t1 = (c & 2) ? v1 : v3;
        t0 = __shfl_xor_sync(0xffffffffu, t0, 2); t1 = __shfl_xor_sync(0xffffffffu, t1, 2);
        if (c & 2) { v0 = t0; v1 = t1; } else { v2 = t0; v3 = t1; }
        stg128((uint4*)(p.out + (size_t)(ch * 128 + w * 16 + g + h * 8) * 512 + cb * 16 + c * 8), make_uint4(v0, v1, v2, v3), POL_LATE);
    }
}
__device__ __forceinline__ void fin_task(const Params& p, int ch, int cb0, int ncb, int ns, bool dry) {
    const int w = threadIdx.x >> 5;
    uint32_t rs[8];
    wait_cnt_warp(cnt_ptr(C_CV, ch), dry ? 0 : 16);
    load_resid<2>(rs, 1, ch, w, cb0);
    wait_cnt_warp(cnt_ptr(C_OP1, ch), dry ? 0 : 256);
    for (int cb = cb0; cb < cb0 + ncb; cb += 2) {
        float x[16];
        if (cb != cb0) load_resid<2>(rs, 1, ch, w, cb);
        sum_partials<2, 16>(x, rs, 1, ch, w, cb, ns);
        out_store(p, x, ch, cb);
    }
}

__device__ __forceinline__ void bulk_consumer(const Params& p, uint32_t sb, int cl, uint32_t rank, int w) {
    int st = 0; uint32_t ph = 0; int nq = 0, nd = 0, ng = 0;
    for (int ti = 0; ti < MAXT; ti++) {
        const Task t = task_of(p.task[cl][ti], rank);
        const int type = t.type, layer = t.layer, ch = t.ch;
        if (type == T_END) break;
        bool staged = type != T_FIN;
        PROF(threadIdx.x == 0, 3600 + ti * 4);
        if (type <= T_OP) {
            const int lane = threadIdx.x & 31, nh = type == T_QKV ? 16 : 2 * t.b;
            float acc[128];
            uint32_t r0 = sb + B_BAR + BB_IDLE * 8, r1 = r0;
            CPROF(0);
            if (w >> 2) mbar_wait(sb + B_BAR + BB_GO * 8, ng & 1);
            ng++;
            CPROF(1);
            gemm_run<false>(acc, sb, w, 0, 1, r0, r1, st, ph);
            gemm_run<true>(acc, sb, w, 1, nh - CSH, r0, r1, st, ph);
            CPROF(2);
            uint4 cs[16]; uint2 s0, s1;
#pragma unroll
            for (int i = 0; i < 16; i++) cs[i] = make_uint4(0, 0, 0, 0);
            s0 = s1 = make_uint2(0, 0);
            if (type == T_QKV) {
                mbar_wait(sb + B_BAR + BB_STF * 8, nq & 1);
                s0 = lds64(sb + B_ST + (w * 16 + (lane >> 2)) * 8); s1 = lds64(sb + B_ST + (w * 16 + (lane >> 2) + 8) * 8);
#pragma unroll
                for (int i = 0; i < 16; i++) cs[i] = lds128(sb + B_ST + 1024 + (i >> 1) * 128 + (lane & 3) * 32 + (i & 1) * 16);
            }
            CPROF(3);
            gemm_run<true>(acc, sb, w, nh - CSH, nh, r0, r1, st, ph);
            CPROF(4);
            if (!(t.c & 32)) mbar_wait(sb + B_BAR + BB_SF * 8, (nd & 1) ^ 1);
            wg_wait<1>();
            mbar_arrive1_cluster(r0);
            wg_wait<0>();
            mbar_arrive1_cluster(r1);
            CPROF(5);
            PROF(threadIdx.x == 128, 3600 + ti * 4 + 1);
            if (type == T_QKV) {
                mbar_arrive1(sb + B_BAR + BB_STE * 8);
                qkv_epilogue(acc, cs, s0, s1, sb, w, layer, ch, t.blk);
                nq++;
            } else if (t.c & 32) {
                staged = false;
#pragma unroll
                for (int j = 0; j < 16; j += 4) {
                    uint32_t rs[16];
                    load_resid<4>(rs, 1, ch, w, (t.blk & 4) * 4 + j);
#pragma unroll
                    for (int i = 0; i < 16; i++) { float* y = acc + j * 8 + 2 * i; y[0] = rbf(y[0]) + blo(rs[i]); y[1] = rbf(y[1]) + bhi(rs[i]); }
                    out_store(p, acc + j * 8, ch, (t.blk & 4) * 4 + j); out_store(p, acc + j * 8 + 16, ch, (t.blk & 4) * 4 + j + 2);
                }
            } else {
                uint4* dst = op_dst(layer, ch, t.c & 15, w, (t.blk >> 2) & 1) + lane;
#pragma unroll
                for (int n = 0; n < 16; n++) {
                    const int j = (n >> 1) + (n & 1) * 8;
                    const uint4 v = make_uint4(pack2(acc[j * 8], acc[j * 8 + 1]), pack2(acc[j * 8 + 2], acc[j * 8 + 3]), pack2(acc[j * 8 + 4], acc[j * 8 + 5]), pack2(acc[j * 8 + 6], acc[j * 8 + 7]));
                    if (j < 16 - NSB) stg128(dst + j * 32, v, out_pol(T_OP, layer, ch)); else sts128(sb + B_OUT + (w * NSB + j - (16 - NSB)) * 512 + lane * 16, v.x, v.y, v.z, v.w);
                }
            }
        } else if (type == T_CV) {
            float acc[128];
            conv_task(p, acc, sb, w, ch, t.a + rank, layer, t.b, t.c, t.dry, st, ph, nd);
        } else {
            fin_task(p, ch, t.a + rank * t.c, t.c, t.b, t.dry);
        }
        if (staged) {
            __syncwarp();
            mbar_arrive1(sb + B_BAR + (BB_DONE + (nd & 1) * 2 + (w >> 2)) * 8);
            nd++;
        }
        CPROF(6);
        PROF(threadIdx.x == 128, 3600 + ti * 4 + 2);
        __syncwarp();
    }
}

constexpr int P_Y = 131072  , P_PRM = P_Y  , P_K6 = P_PRM + 8192  ,
              P_P = P_Y + 40960  , P_U = P_P + 33280  , P_END = P_U + 17408, P_X = 98304  ;
static_assert(P_END <= B_BAR && P_END <= R_BAR, "prologue scratch");
#define KGUN 2
constexpr int KGU = KGUN;
__device__ __forceinline__ void csq(float& r, float& i) { const float t = r * i; r = fmaf(r, r, -(i * i)); i = t + t; }
__device__ __forceinline__ void cpow(float ar, float ph, float p, float& r, float& i) {
    const float e = ex2(ar * p);
    const float u = ph * p, n = fabsf(u) < 4194304.f ? (u + 12582912.f) - 12582912.f : u;
    const float t = (u - n) * 6.283185307179586f;
    r = e * __cosf(t); i = e * __sinf(t);
}
__device__ __forceinline__ void mma_tf32(float* c, float a0, float a1, float a2, float a3, float b0, float b1) {
    asm volatile("mma.sync.aligned.m16n8k8.row.col.f32.tf32.tf32.f32 {%0,%1,%2,%3},{%4,%5,%6,%7},{%8,%9},{%0,%1,%2,%3};"
                 : "+f"(c[0]), "+f"(c[1]), "+f"(c[2]), "+f"(c[3])
                 : "r"(__float_as_uint(a0)), "r"(__float_as_uint(a1)), "r"(__float_as_uint(a2)), "r"(__float_as_uint(a3)), "r"(__float_as_uint(b0)), "r"(__float_as_uint(b1)));
}

struct ProRegs { uint32_t v[2][4], ldt[2]; };
__device__ __forceinline__ void prologue_load(const ProArgs& a, int b, ProRegs& pr) {
    const int w = threadIdx.x >> 5;
#pragma unroll
    for (int i = 0; i < 2; i++) {
        const int gi = b * 512 + (w & 3) * 128 + ((w >> 2) & 1) * 64 + i * 32 + (threadIdx.x & 31);
        pr.ldt[i] = __ldg((const uint16_t*)a.ldt + b * 4 + (w & 3));
        pr.v[i][0] = __ldg((const uint16_t*)a.lAr + gi); pr.v[i][1] = __ldg((const uint16_t*)a.Ai + gi);
        pr.v[i][2] = __ldg((const uint16_t*)a.Cr + gi); pr.v[i][3] = __ldg((const uint16_t*)a.Ci + gi);
    }
}
__device__ __forceinline__ void prologue(const ProArgs& a, uint32_t sb, int b, int w, const ProRegs& pr) {
    const int tid = threadIdx.x, lane = tid & 31, g = lane >> 2, c = lane & 3;
    const int d0 = b * 4;
    if (w >= 8) {
        const int t2 = tid - 256;
        if (w < 10) {
            const int row = b * 16 + (w - 8) * 8 + g;
            const float2 r = row_stats512((const uint4*)(a.x + (size_t)row * 512) + c, 8, 4);
            const float2 l = ln_finish(r.x * (1.f / 512.f), r.y * (1.f / 512.f));
            if (c == (g >> 1)) asm volatile("st.relaxed.gpu.global.u32 [%0],%1;" ::"l"(g_ln0 + row), "r"(pack2(l.x, l.y)) : "memory");
        }
        PROF(t2 == 0, 3516);
        const int gi = b * 128 + t2;
        if (t2 < 32) acc_init(a.mem0, b * 32 + t2);
        ((uint4*)g_st2)[gi] = make_uint4(~0u, ~0u, ~0u, ~0u);
        if (gi < 9 * 16 * 32) g_cnt[gi] = 0;
        bar_sync(6, 384);
        {
            const int u = b * 3 + (w - 8), blk = u >> 1;
            const uint4* W = w < 11 ? (const uint4*)((blk < 64 ? a.Wq : blk < 128 ? a.Wk : a.Wv) + (size_t)((u & 1) * 256 + c) * 4096 + (blk & 63) * 64) + g
                                    : (const uint4*)a.Wo + (size_t)b * 2048 + lane;
            const int st = w < 11 ? 2048 : 32;
            const uint32_t one = (g & 1) ? 0x3f800000u : 0x00003f80u, selA = (g & 2) ? 0u : one, selB = (g & 2) ? one : 0u;
            float s0[4] = {0, 0, 0, 0}, s1[4] = {0, 0, 0, 0};
#pragma unroll 1
            for (int r = 0; r < 8; r++) {
                uint4 v[8];
#pragma unroll
                for (int i = 0; i < 8; i++) v[i] = __ldg(W + (size_t)(r * 8 + i) * st);
#pragma unroll
                for (int i = 0; i < 8; i++) mma16((i & 1) ? s1 : s0, v[i].x, v[i].y, v[i].z, v[i].w, selA, selB);
            }
            if (c < 2) *(float4*)(g_cs + (w < 11 ? (u & 1) * 12288 + blk * 64 : 24576) + g * 8 + c * 4) = make_float4(s0[0] + s1[0], s0[1] + s1[1], s0[2] + s1[2], s0[3] + s1[3]);
        }
        PROF(t2 == 0, 3517);
        return;
    }
#pragma unroll
    for (int i = 0; i < 2; i++) {
        const float dt = rbf(expf(blo(pr.ldt[i])));
        const float ar = -rbf(expf(blo(pr.v[i][0]))) * dt, ai = blo(pr.v[i][1]) * dt;
        sts128(sb + P_PRM + (w * 64 + i * 32 + lane) * 16, __float_as_uint(ar * 1.4426950408889634f), __float_as_uint(ai * 0.15915494309189535f),
               __float_as_uint(2.f * (blo(pr.v[i][2]) * dt)), __float_as_uint(2.f * (blo(pr.v[i][3]) * dt)));
    }
    if (tid < 64) sts128(sb + P_U + (tid >> 3) * 2176 + (tid & 7) * 16, 0, 0, 0, 0);
    bar_arrive(6, 384);
    __syncwarp();
    PROF(tid == 0, 3510);
    const int ch = w & 3, hf = w >> 2;
    {
        float k0[4] = {0, 0, 0, 0}, k1[4] = {0, 0, 0, 0}, k2[4] = {0, 0, 0, 0}, k3[4] = {0, 0, 0, 0}, k4[4] = {0, 0, 0, 0}, kl = 0;
#pragma unroll KGU
        for (int j = 0; j < 16; j++) {
            const uint4 q = lds128(sb + P_PRM + (w * 64 + j * 4 + c) * 16);
            const float cr = __uint_as_float(q.z), ci = __uint_as_float(q.w);
            float wr[4], wi[4], vr[4], vi[4];
            cpow(__uint_as_float(q.x), __uint_as_float(q.y), (float)g, wr[0], wi[0]);
            cpow(__uint_as_float(q.x), __uint_as_float(q.y), (float)(g + 8), vr[0], vi[0]);
#pragma unroll
            for (int i = 1; i < 4; i++) { wr[i] = wr[i - 1]; wi[i] = wi[i - 1]; csq(wr[i], wi[i]); vr[i] = vr[i - 1]; vi[i] = vi[i - 1]; csq(vr[i], vi[i]); }
            float hr = wr[3], hi = wi[3];
            csq(hr, hi);
            mma_tf32(k0, wr[0], vr[0], wi[0], vi[0], cr * hr - ci * hi, -(cr * hi + ci * hr));
            hr = vr[3]; hi = vi[3]; csq(hr, hi);
            mma_tf32(k1, wr[0], vr[0], wi[0], vi[0], cr * hr - ci * hi, -(cr * hi + ci * hr));
            csq(hr, hi);
            mma_tf32(k2, wr[1], vr[1], wi[1], vi[1], cr * hr - ci * hi, -(cr * hi + ci * hr));
            csq(hr, hi);
            mma_tf32(k3, wr[2], vr[2], wi[2], vi[2], cr * hr - ci * hi, -(cr * hi + ci * hr));
            csq(hr, hi);
            mma_tf32(k4, wr[3], vr[3], wi[3], vi[3], cr * hr - ci * hi, -(cr * hi + ci * hr));
            csq(hr, hi);
            kl += cr * hr - ci * hi;
        }
        kl += __shfl_xor_sync(0xffffffffu, kl, 1); kl += __shfl_xor_sync(0xffffffffu, kl, 2);
        const uint32_t o = sb + P_K6 + (ch * 656 + c * 32 + g) * 4, ol = sb + P_K6 + (ch * 656 + 640) * 4;
#define KST(k, base) sts32(o + (base) * 4, __float_as_uint(k[0])); sts32(o + (base) * 4 + 64, __float_as_uint(k[1])); \
                     sts32(o + (base) * 4 + 32, __float_as_uint(k[2])); sts32(o + (base) * 4 + 96, __float_as_uint(k[3]))
#define KAD(k, base) k[0] += __uint_as_float(lds32(o + (base) * 4)); k[1] += __uint_as_float(lds32(o + (base) * 4 + 64)); \
                     k[2] += __uint_as_float(lds32(o + (base) * 4 + 32)); k[3] += __uint_as_float(lds32(o + (base) * 4 + 96))
        if (hf == 0) {
            bar_sync(2 + ch, 64);
            KAD(k0, 0); KAD(k1, 128); KAD(k2, 256); KAD(k3, 384); KAD(k4, 512);
            kl += __uint_as_float(lds32(ol));
            __syncwarp();
        }
        KST(k0, 0); KST(k1, 128); KST(k2, 256); KST(k3, 384); KST(k4, 512);
        if (lane == 0) sts32(ol, __float_as_uint(kl));
        if (hf == 1) { __syncwarp(); bar_arrive(2 + ch, 64); }
    }
    PROF(tid == 0, 3511);
    {
        uint4 l0, l1;
        int n = 0;
        while (true) {
            l0 = ld_rlx128((const uint4*)g_ln0 + tid * 2); l1 = ld_rlx128((const uint4*)g_ln0 + tid * 2 + 1);
            if (__all_sync(0xffffffffu, l0.x && l0.y && l0.z && l0.w && l1.x && l1.y && l1.z && l1.w)) break;
            if (++n > 2000000) __trap();
        }
        sts128(sb + P_P + tid * 32, l0.x, l0.y, l0.z, l0.w); sts128(sb + P_P + tid * 32 + 16, l1.x, l1.y, l1.z, l1.w);
        bar_sync(8, 384);
        mbar_wait(sb + S_XBAR, 0);
        __syncwarp();
#pragma unroll 2
        for (int i = 0; i < 8; i++) {
            const int t = w * 256 + i * 32 + lane;
            const uint32_t ln = lds32(sb + P_P + t * 4);
            const uint2 x = lds64(sb + P_X + t * 16 + (b & 1) * 8);
            const float m = blo(ln), rs = rcp(bhi(ln));
            const uint32_t u0 = pack2(rbf(blo(x.x) - m) * rs, rbf(bhi(x.x) - m) * rs), u1 = pack2(rbf(blo(x.y) - m) * rs, rbf(bhi(x.y) - m) * rs);
            sts128(sb + P_X + t * 16, x.x, x.y, u0, u1);
            const uint32_t o = sb + P_U + ((t >> 3) & 1) * 2176 + ((t >> 4) + 8) * 16 + (t & 7) * 2;
            asm volatile("st.shared.u16 [%0],%1;" ::"r"(o), "h"((uint16_t)u0) : "memory");
            asm volatile("st.shared.u16 [%0],%1;" ::"r"(o + 4352), "h"((uint16_t)(u0 >> 16)) : "memory");
            asm volatile("st.shared.u16 [%0],%1;" ::"r"(o + 8704), "h"((uint16_t)u1) : "memory");
            asm volatile("st.shared.u16 [%0],%1;" ::"r"(o + 13056), "h"((uint16_t)(u1 >> 16)) : "memory");
        }
    }
    bar_sync(1, 256);
    PROF(tid == 0, 3512);
    if (tid < 64) sts32(sb + P_P + ((tid >> 4) * 2080 + (tid & 15)) * 4, 0);
#pragma unroll 1
    for (int x = tid; x < 2048; x += 512) {
        uint32_t pw[2][4];
#pragma unroll
        for (int h = 0; h < 2; h++) {
            const int y = x + h * 256;
            const int i0 = y <= 256 ? y : 256 + (int)((pack2((float)y, 0.f) & 0xffff) - 0x4380);
            const int i1 = y <= 256 ? max(y - 1, 0) : 256 + (int)((pack2((float)(y - 1), 0.f) & 0xffff) - 0x4380);
#pragma unroll
            for (int k = 0; k < 4; k++) {
                const float lo = __uint_as_float(lds32(sb + P_K6 + k * 2624 + i0 * 4)), hi = __uint_as_float(lds32(sb + P_K6 + k * 2624 + i1 * 4));
                pw[h][k] = pack2(lo, y ? hi : 0.f);
            }
        }
#pragma unroll
        for (int h = 0; h < 2; h++)
#pragma unroll
            for (int k = 0; k < 4; k++) sts32(sb + P_P + (k * 2080 + x + h * 256 + 16) * 4, pw[h][k]);
    }
    fence_async_smem();
    bar_sync(1, 256);
    if (lane < 8) {
        const int k = w >> 1, j = (w & 1) * 8 + lane, d = d0 + k;
        asm volatile("cp.async.bulk.global.shared::cta.bulk_group [%0],[%1],%2;" ::"l"(g_P + (((d >> 5) * 16 + j) * 32 + (d & 31)) * PW),
                     "r"(sb + P_P + (k * 2080 + j * 128) * 4), "r"(PW * 4) : "memory");
        asm volatile("cp.async.bulk.commit_group;" ::: "memory");
    }
    __syncwarp();
    PROF(tid == 0, 3513);
    {
        float acc[16][4];
#pragma unroll
        for (int j = 0; j < 16; j++) acc[j][0] = acc[j][1] = acc[j][2] = acc[j][3] = 0;
#pragma unroll 1
        for (int e = hf * 4; e < hf * 4 + 4; e++) {
            uint32_t B[16][2];
            const uint32_t ua = sb + P_U + ch * 4352 + ((lane >> 3) & 1) * 2176 + (8 + (lane >> 4) * 8 + (lane & 7) - e) * 16;
#pragma unroll
            for (int j = 0; j < 8; j++) { const uint4 v = ldsm4(ua + j * 256); B[2 * j][0] = v.x; B[2 * j][1] = v.y; B[2 * j + 1][0] = v.z; B[2 * j + 1][1] = v.w; }
            const uint32_t pa = sb + P_P + (ch * 2080 + 16 + e * 16 + g - 2 * c) * 4;
#pragma unroll
            for (int d = 0; d < 16; d++) {
                const uint32_t a0 = lds32(pa + d * 512), a1 = lds32(pa + d * 512 + 32), a2 = lds32(pa + d * 512 - 32);
#pragma unroll
                for (int j = d; j < 16; j++) mma16(acc[j], a0, a1, a2, a0, B[j - d][0], B[j - d][1]);
            }
        }
        PROF(tid == 0, 3514);
        const uint32_t o = sb + P_Y + (ch * 2560 + c * 40 + g) * 4;
        if (hf == 0) {
            bar_sync(2 + ch, 64);
#pragma unroll
            for (int j = 0; j < 16; j++) {
                acc[j][0] += __uint_as_float(lds32(o + j * 640)); acc[j][1] += __uint_as_float(lds32(o + j * 640 + 80));
                acc[j][2] += __uint_as_float(lds32(o + j * 640 + 32)); acc[j][3] += __uint_as_float(lds32(o + j * 640 + 112));
            }
        }
#pragma unroll
        for (int j = 0; j < 16; j++) {
            sts32(o + j * 640, __float_as_uint(acc[j][0])); sts32(o + j * 640 + 80, __float_as_uint(acc[j][1]));
            sts32(o + j * 640 + 32, __float_as_uint(acc[j][2])); sts32(o + j * 640 + 112, __float_as_uint(acc[j][3]));
        }
        if (hf == 1) bar_arrive(2 + ch, 64);
    }
    const uint2 dk = __ldg((const uint2*)(a.Dk + d0));
    bar_sync(1, 256);
#pragma unroll 2
    for (int i = 0; i < 8; i++) {
        const int t = i * 256 + tid;
        const uint32_t o = sb + P_Y + (t + 4 * (t >> 4)) * 4;
        const uint4 xu = lds128(sb + P_X + t * 16);
        float y[4];
#pragma unroll
        for (int k = 0; k < 4; k++) y[k] = rbf(__uint_as_float(lds32(o + k * 10240)));
        uint2 r;
        r.x = pack2(blo(xu.x) + rbf(y[0] + rbf(blo(xu.z) * blo(dk.x))), bhi(xu.x) + rbf(y[1] + rbf(bhi(xu.z) * bhi(dk.x))));
        r.y = pack2(blo(xu.y) + rbf(y[2] + rbf(blo(xu.w) * blo(dk.y))), bhi(xu.y) + rbf(y[3] + rbf(bhi(xu.w) * bhi(dk.y))));
        ((uint2*)(g_xA[0] + ((t >> 7) * 8 + (d0 >> 6)) * 1024 + ((t & 127) >> 3) * 64 + ((d0 & 63) >> 3) * 8 + (t & 7)))[(d0 >> 2) & 1] = r;
    }
    PROF(tid == 0, 3515);
    if (lane < 8) asm volatile("cp.async.bulk.wait_group 0;" ::: "memory");
}

__global__ void __cluster_dims__(2, 1, 1) __launch_bounds__(384, 1) main_kernel(const __grid_constant__ Params p) {
    extern __shared__ __align__(1024) uint8_t smem[];
    const uint32_t sb = __shfl_sync(0xffffffffu, smem_u32(smem), 0);
    uint32_t rank; asm("mov.u32 %0,%%cluster_ctarank;" : "=r"(rank));
    const int wi = __shfl_sync(0xffffffffu, threadIdx.x >> 5, 0);
    const int cl = blockIdx.x >> 1, wg = wi >> 2;
    const bool rec = p.rec0 >= 0 && cl >= p.rec0 && cl < p.rec0 + 32;
    PROF(threadIdx.x == 0, 3500);
    ProRegs pr;
    prologue_load(p.pa, max((int)blockIdx.x - 4, 0), pr);
    if (rec) rec_init(p, sb, cl - p.rec0, rank); else bulk_init(sb);
    if (threadIdx.x == 352 && p.dopro && cl >= 2) {
        mbar_init(sb + S_XBAR, 1);
        asm volatile("fence.mbarrier_init.release.cluster;" ::: "memory");
        mbar_expect(sb + S_XBAR, 32768);
        for (int j = 0; j < 8; j++) tma2d(sb + P_X + j * 4096, &p.tm[3], ((blockIdx.x - 4) >> 1) * 8, j * 256, sb + S_XBAR);
    }
    if (threadIdx.x == 320) {
        unsigned v = 0;
        if (p.dopro) {
            asm volatile("ld.relaxed.gpu.global.u32 %0,[%1];" : "=r"(v) : "l"(g_gate) : "memory");
            v = (v / (4 * NCL) + 1) * (4 * NCL);
        }
        sts32(sb + S_GATE, v);
    }
    __syncwarp();
    asm volatile("barrier.cluster.arrive.relaxed.aligned;" ::: "memory");
    if (wg == 2) bar_arrive(8, 384);
    if (p.dopro && cl >= 2) prologue(p.pa, sb, blockIdx.x - 4, wi, pr); else if (wg < 2) bar_sync(8, 384);
    asm volatile("barrier.cluster.wait.aligned;" ::: "memory");
    fence_async_smem();
    bar_sync(wg == 2 ? 7 : 1, wg == 2 ? 128 : 256);
    if (p.dopro && (threadIdx.x == 32 || threadIdx.x == 352)) red_release(g_gate, 1);
    if (rec) {
        if (threadIdx.x == 0) {
            rec_fetch(&p.tm[1], sb + R_STK, (cl - p.rec0) * 128, rank * 256, 2, sb + R_BAR + RB_INIT * 8);
            rec_fetch(&p.tm[2], sb + R_STV, (cl - p.rec0) * 128, rank * 256, 2, sb + R_BAR + RB_INIT * 8);
        }
    }
    PROF(threadIdx.x == 0, 3506);
    __syncwarp();
    if (rec) {
        const int head = cl - p.rec0;
        if (wg == 2) {
            reg_dec<RH>();
            const int w = wi & 3;
            if (threadIdx.x == 256) rec_fetch(&p.tm[0], sb + R_STQ, head * 128, rank * 256, 2, sb + R_BAR + RB_INIT * 8);
            __syncwarp();
            wait_cnt_warp(g_gate, lds32(sb + S_GATE));
            __syncthreads();
            cluster_sync();
            if ((p.chains >> (w >> 1)) & 1) rec_attn(p, sb, w >> 1, w & 1, head, rank);
        } else {
            reg_inc<RW0>();
            rec_weights(p, sb, head, rank, wi);
        }
    } else {
        if (wg == 2) {
            reg_dec<40>();
            const int w = wi & 3;
            if (w == 0) bulk_producer(p, sb, cl, rank); else if (w < 3) bulk_stats(p, sb, cl, rank); else bulk_release(p, sb, cl, rank);
        } else { reg_inc<232>(); bulk_consumer(p, sb, cl, rank, wi); }
    }
    __syncwarp();
    cluster_sync();
}

typedef CUresult (*EncFn)(CUtensorMap*, CUtensorMapDataType, cuuint32_t, void*, const cuuint64_t*, const cuuint64_t*, const cuuint32_t*, const cuuint32_t*,
                          CUtensorMapInterleave, CUtensorMapSwizzle, CUtensorMapL2promotion, CUtensorMapFloatOOBfill);
inline uint32_t mk(int type, int layer, int ch, int a, int b, int c) { return type | (layer << 3) | (ch << 4) | (a << 8) | (b << 16) | ((uint32_t)c << 24); }
constexpr int SMEM_BYTES = 232448;

struct Sched {
    Params* P; int n[NCL];
    void clear() { memset(P->task, 0, sizeof(P->task)); memset(n, 0, sizeof(n)); }
    void add(int cl, uint32_t t) { if (n[cl] < MAXT - 1) P->task[cl][n[cl]++] = t; }
};

#define LAG 14
#define TS1 2400
#define TS2 2900
#define REC0 4
#define NS2 8
#define DFN 5000
#define DQN 5600
struct Slot { double s, e; uint32_t w; };
struct Planner {
    Slot sl[NCL][MAXT]; int n[NCL], nc;
    double fit(int i, double r, double d) const {
        double t = r;
        for (int k = 0; k < n[i]; k++) { if (sl[i][k].s >= t + d) break; if (sl[i][k].e > t) t = sl[i][k].e; }
        return t;
    }
    double idle_before(int i, double t) const { double e = 0; for (int k = 0; k < n[i]; k++) if (sl[i][k].e <= t + 1 && sl[i][k].e > e) e = sl[i][k].e; return t - e; }
    void put(int i, double t, double d, uint32_t w) {
        int k = n[i]++;
        while (k > 0 && sl[i][k - 1].s > t) { sl[i][k] = sl[i][k - 1]; k--; }
        sl[i][k] = {t, t + d, w};
    }
    double last_urgent(int i) const { double e = 0; for (int k = 0; k < n[i]; k++) { const uint32_t t = sl[i][k].w & 15; if (t != (T_OP | 8) && t != (T_FIN | 8)) e = sl[i][k].e; } return e; }
    double place(double r, double d, uint32_t w, int lo, bool tight) {
        int bi = -1; double bt = 0, bg = 0;
        for (int i = lo; i < nc; i++) {
            if (n[i] >= MAXT - 2) continue;
            const double t = fit(i, (w & 7) == T_FIN ? fmax(r, last_urgent(i)) : r, d), g = tight ? idle_before(i, t) : -idle_before(i, t);
            if (bi < 0 || t < bt - 1 || (t < bt + 1 && g < bg)) { bi = i; bt = t; bg = g; }
        }
        put(bi, bt, d, w);
        return bt + d;
    }
};
void plan(Params& P) {
    P.rec0 = REC0; P.chains = 3; P.lag = LAG; P.dostats = 1; P.dopro = 1;
    const double DQ = DQN, DKB = 600, DOV = 1000, DH = 520, DHO = 1300, DU = 4300, DF = DFN, HOP = 1600, ODEL = 1000, LEAD = 1500;
    static Planner L;
    int cls[NCL], nc = 0;
    for (int c = REC0 + 32; c < NCL; c++) cls[nc++] = c;
    for (int c = REC0 - 1; c >= 0; c--) cls[nc++] = c;
    for (double grow = 1.0;; grow *= 1.01) {
        memset(L.n, 0, sizeof(L.n)); L.nc = nc;
        double it[100], worst = 1e18, end = 0, cvs[16], cve[16];
        it[0] = DQ + 2 * HOP;
        for (int i = 1; i < 100; i++) it[i] = it[i - 1] + fmax(grow * TS1, (i - 1 >= LAG && i - 1 < 64) ? TS2 : 0);
        const double DO1 = DOV + 8 * DKB, dly = it[4] + ODEL + DO1 + HOP + DU + HOP + DQ + 2 * HOP - it[LAG];
        if (dly > 0) for (int i = LAG; i < 100; i++) it[i] += dly;
        for (int c = 0; c < 16; c++) {
            const double s0 = fmax(it[4 * c + 4] + ODEL, c ? cve[c - 1] : 0);
            for (int i = 0; i < 8; i++) {
                if (c == 0) L.put(i, s0 - 11000, 11000, mk(T_CV, 0, 3, 2 * i, 0, 128));
                L.put(i, s0, DO1, mk(T_OP, 0, c, 8 * i, 8, i));
                L.put(i, s0 + DO1, HOP + DU, mk(T_CV, 0, c, 2 * i, 0, 0));
            }
            cvs[c] = s0 + DO1; cve[c] = cvs[c] + HOP + DU;
        }
        for (int c = 0; c < 16; c++) {
            double e = 0;
            for (int t = 0; t < 24; t++) e = fmax(e, L.place(cve[c] + HOP, DQ, mk(T_QKV, 1, c, t * 8, 4, 0), 0, true));
            worst = fmin(worst, it[LAG + 4 * c] - (c ? LEAD : 0) - HOP - e);
        }
        for (int c = 2; c < 16; c++) {
            double e = 0, r = cve[c - 2] + HOP;
            const int m = c >= HSPLIT ? c / 2 + 1 : c;
            if (m < c) for (int i = 0; i < 8; i++) r = fmax(r, L.place(cve[c - 3] + HOP, DHO + DH * (c - m), mk(T_CV, 1, c, 2 * i, c, m + 1), 8, true));
            for (int i = 0; i < 8; i++) e = fmax(e, L.place(r, DHO + (m < c ? 1500 : 0) + DH * (m - 1), mk(T_CV, 1, c, 2 * i, m, 2), 8, true));
            worst = fmin(worst, cvs[c] - HOP - e);
        }
        for (int c = 0; c < 16; c++) {
            double e = 0;
            for (int t = 0; t < 24; t++) e = fmax(e, L.place(0, DQ, mk(T_QKV, 0, c, t * 8, 4, 0), 0, true));
            worst = fmin(worst, it[4 * c] - (c ? LEAD : 0) - HOP - e);
        }
        for (int cc = 0; cc < 16; cc++) {
            const int c = cc ? cc - 1 : 15, ns = c == 15 ? 16 : c == 14 ? 8 : NS2, nf = c >= 14 ? 8 : 4;
            double e = 0;
            for (int t = 0; t < ns; t++) {
                const int a = t * 64 / ns, b = (t + 1) * 64 / ns - a;
                const double guard = c == 15 ? 9000 : 0;
                e = fmax(e, L.place(it[LAG + 4 * c + 4] + ODEL - guard, DOV + DKB * b + guard, mk(T_OP, 1, c, a, b, t), 0, true));
            }
            for (int t = 0; t < nf; t++) end = fmax(end, L.place(e + HOP, DF, mk(T_FIN, 1, c, t * (32 / nf), ns, 16 / nf), 0, true));
        }
        if (worst >= 0) break;
    }
    for (int lc = 0; lc < 32; lc++) {
        bool used[24] = {};
        for (int pass = 0; pass < 2; pass++)
            for (int i = 0; i < nc; i++)
                for (int k = 0; k < L.n[i]; k++) {
                    uint32_t& w = L.sl[i][k].w;
                    if ((w & 255) != mk(T_QKV, lc & 1, lc >> 1, 0, 0, 0)) continue;
                    int t = i - 8;
                    if (pass == 0) { w |= 0xff00; if (t < 0 || t >= 24 || used[t]) continue; }
                    else { if ((w & 0xff00) != 0xff00) continue; for (t = 0; used[t]; t++) {} }
                    used[t] = true; w = (w & ~0xff00u) | (t * 8) << 8;
                }
    }
    Sched S; S.P = &P; S.clear();
    S.add(0, mk(T_QKV, 1, 15, 124, 4, 128)); S.add(0, mk(T_OP, 1, 15, 0, 4, 128));
    S.add(1, mk(T_CV, 0, 3, 0, 0, 128));
    for (int i = 0; i < nc; i++) {
        bool warm = false;
        for (int k = 0; k < L.n[i]; k++) {
            if (!warm && k + 1 < L.n[i] && (L.sl[i][k + 1].w & 255) == (mk(T_FIN, 1, 15, 0, 0, 0) & 255)) { S.add(cls[i], L.sl[i][k + 1].w | 0x80000000u); warm = true; }
            S.add(cls[i], L.sl[i][k].w);
            if ((L.sl[i][k].w & 7) == T_FIN) warm = true;
        }
    }
}

#define TK0() do {} while (0)
#define TK() do { P.e0 = (P.chains & 1) ? 64 : 0; P.b1 = (P.chains & 2) ? P.lag : 1000; P.nit = (P.chains & 2) ? P.lag + 64 : 64; TK0(); } while (0)
}

extern "C" void kernel_launch(void* const* d_in, const int* in_sizes, int n_in, void* d_out, int out_size) {
    typedef const __nv_bfloat16* BP;
    static EncFn enc = nullptr;
    if (!enc) {
        void* fn = nullptr; cudaDriverEntryPointQueryResult qr;
        cudaGetDriverEntryPoint("cuTensorMapEncodeTiled", &fn, cudaEnableDefault, &qr);
        enc = (EncFn)fn;
        cudaFuncSetAttribute(main_kernel, cudaFuncAttributeMaxDynamicSharedMemorySize, SMEM_BYTES);
    }
    static Params P;
    for (int i = 0; i < 4; i++) {
        const cuuint64_t cols = i < 3 ? 4096 : 512, rows = i < 3 ? 512 : 4096;
        cuuint64_t d2[2] = {cols, rows}, d3[3] = {64, rows, cols / 64}, str[2] = {cols * 2, 128};
        cuuint32_t box[3] = {64, 64, 4}, es[3] = {1, 1, 1};
        enc(&P.tm[i < 3 ? i : 4], CU_TENSOR_MAP_DATA_TYPE_BFLOAT16, 2, d_in[9 + i], d2, str, box, es, CU_TENSOR_MAP_INTERLEAVE_NONE, CU_TENSOR_MAP_SWIZZLE_128B,
                       CU_TENSOR_MAP_L2_PROMOTION_L2_128B, CU_TENSOR_MAP_FLOAT_OOB_FILL_NONE);
        for (int m = 0; m < 2; m++) {
            cuuint32_t box3[3] = {64, 32, m ? 2u : 4u};
            enc(&P.t3[m][i], CU_TENSOR_MAP_DATA_TYPE_BFLOAT16, 3, d_in[9 + i], d3, str, box3, es, CU_TENSOR_MAP_INTERLEAVE_NONE, CU_TENSOR_MAP_SWIZZLE_128B,
                CU_TENSOR_MAP_L2_PROMOTION_L2_128B, CU_TENSOR_MAP_FLOAT_OOB_FILL_NONE);
        }
    }
    {
        cuuint64_t dims[2] = {512, 2048}, str[1] = {1024};
        cuuint32_t box[2] = {8, 256}, es[2] = {1, 1};
        enc(&P.tm[3], CU_TENSOR_MAP_DATA_TYPE_BFLOAT16, 2, d_in[0], dims, str, box, es, CU_TENSOR_MAP_INTERLEAVE_NONE, CU_TENSOR_MAP_SWIZZLE_NONE,
            CU_TENSOR_MAP_L2_PROMOTION_NONE, CU_TENSOR_MAP_FLOAT_OOB_FILL_NONE);
    }
    for (int m = 0; m < 2; m++) {
        void* ga; cudaGetSymbolAddress(&ga, g_A);
        cuuint64_t dims[2] = {512, sizeof(AOps) / 1024}, str[1] = {1024};
        cuuint32_t box[2] = {256, m ? 16u : 8u}, es[2] = {1, 1};
        enc(&P.ta[m], CU_TENSOR_MAP_DATA_TYPE_BFLOAT16, 2, ga, dims, str, box, es, CU_TENSOR_MAP_INTERLEAVE_NONE, CU_TENSOR_MAP_SWIZZLE_NONE,
            CU_TENSOR_MAP_L2_PROMOTION_L2_128B, CU_TENSOR_MAP_FLOAT_OOB_FILL_NONE);
    }
    P.mem0 = (BP)d_in[8]; P.Wo = (BP)d_in[12]; P.Dskip = (BP)d_in[6]; P.out = (__nv_bfloat16*)d_out;
    P.nst[0] = 1; P.nst[1] = 16;
    cudaStream_t s = cudaStreamPerThread;
    P.pa = {(BP)d_in[0], (BP)d_in[1], (BP)d_in[2], (BP)d_in[3], (BP)d_in[4], (BP)d_in[5], (BP)d_in[6], (BP)d_in[9], (BP)d_in[10], (BP)d_in[11], (BP)d_in[12], (BP)d_in[8]};
    static bool planned = false;
    if (!planned) { plan(P); planned = true; }
    TK(); main_kernel<<<2 * NCL, 384, SMEM_BYTES, s>>>(P); TK();
}
```

```cpp
#include <cuda_runtime.h>
#include <cuda_bf16.h>
#include <cuda.h>
#include <stdint.h>
#include <string.h>
#include <math.h>

namespace {

constexpr int NCL = 66;
constexpr int MAXT = 64;
constexpr int OPS1 = 8;
constexpr int MAXSPLIT = 16;
constexpr int HSPLIT = 10;
constexpr int PW = 144;

struct AOps { uint4 x[2][16 * 8 * 1024], o[2][16 * 64 * 1024]; };
__device__ AOps g_A;
#define g_xA g_A.x
#define g_o g_A.o
__device__ float2 g_st[2][16 * 2048];
__device__ float2 g_st2[16 * 16 * 128];
__device__ uint4 g_qkv[2][64 * 64 * 768];
__device__ uint4 g_pp[2][16 * MAXSPLIT * 8192];
__device__ uint4 g_acc[7 * 2048];
__device__ unsigned g_gate[32];
__device__ uint32_t g_P[16 * 16 * 32 * PW];
__device__ uint4 g_u[16 * 16 * 512];
__device__ float4 g_carry[3][16 * 16 * 4 * 256];
__device__ float g_cs[2 * 12288 + 64];
__device__ unsigned g_cnt[9 * 16 * 32];
__device__ uint32_t g_ln0[2048];

enum { C_QKV0 = 0, C_QKV1 = 1, C_O0 = 2, C_O1 = 3, C_OP0 = 4, C_OP1 = 5, C_CV = 6, C_ST = 7, C_H = 8 };
__device__ __forceinline__ unsigned* cnt_ptr(int kind, int chunk) { return g_cnt + (kind * 16 + chunk) * 32; }

enum { T_END = 0, T_QKV = 1, T_OP = 2, T_CV = 3, T_FIN = 4 };
struct ProArgs { const __nv_bfloat16 *x, *lAr, *Ai, *Cr, *Ci, *ldt, *Dk, *Wq, *Wk, *Wv, *Wo, *mem0; };
struct Params {
    CUtensorMap tm[5];
    CUtensorMap t3[2][4];
    CUtensorMap ta[2];
    ProArgs pa;
    int dopro;
    const __nv_bfloat16* mem0;
    const __nv_bfloat16* Wo;
    const __nv_bfloat16* Dskip;
    __nv_bfloat16* out;
    int rec0;
    int chains;
    int lag;
    int b1, e0, nit;
    int zero, gpit;
    int dostats;
    int nst[2];
    uint32_t task[NCL][MAXT];
};

__device__ __forceinline__ uint32_t smem_u32(const void* p) { return (uint32_t)__cvta_generic_to_shared(p); }
__device__ __forceinline__ uint32_t mapa(uint32_t a, uint32_t r) {
    uint32_t o; asm("mapa.shared::cluster.u32 %0,%1,%2;" : "=r"(o) : "r"(a), "r"(r)); return o;
}
__device__ __forceinline__ void mbar_init(uint32_t b, int c) { asm volatile("mbarrier.init.shared::cta.b64 [%0],%1;" ::"r"(b), "r"(c) : "memory"); }
__device__ __forceinline__ void mbar_expect(uint32_t b, int bytes) { asm volatile("mbarrier.arrive.expect_tx.shared::cta.b64 _,[%0],%1;" ::"r"(b), "r"(bytes) : "memory"); }
__device__ __forceinline__ void mbar_arrive(uint32_t b) { asm volatile("mbarrier.arrive.shared::cta.b64 _,[%0];" ::"r"(b) : "memory"); }
__device__ __forceinline__ void mbar_arrive_cluster(uint32_t b) { asm volatile("mbarrier.arrive.shared::cluster.b64 _,[%0];" ::"r"(b) : "memory"); }
__device__ __forceinline__ void mbar_arrive1(uint32_t b) { asm volatile("{.reg .pred p; elect.sync _|p,0xffffffff; @p mbarrier.arrive.shared::cta.b64 _,[%0];}" ::"r"(b) : "memory"); }
__device__ __forceinline__ void mbar_arrive1_cluster(uint32_t b) { asm volatile("{.reg .pred p; elect.sync _|p,0xffffffff; @p mbarrier.arrive.shared::cluster.b64 _,[%0];}" ::"r"(b) : "memory"); }
__device__ __forceinline__ void mbar_wait(uint32_t b, uint32_t ph) {
    asm volatile(
        "{.reg .pred p; .reg .u32 n; mov.u32 n,0;\n"
        "W%=: mbarrier.try_wait.parity.shared::cta.b64 p,[%0],%1;\n"
        "@p bra D%=;\n"
        "add.u32 n,n,1; setp.lt.u32 p,n,2000000; @p bra W%=;\n"
        "trap;\n"
        "D%=: }" ::"r"(b), "r"(ph) : "memory");
}
__device__ __forceinline__ bool wait_lds128(uint32_t b, uint32_t ph, uint32_t a, uint4& v) {
    uint32_t ok;
    asm volatile("{.reg .pred p; mbarrier.try_wait.parity.shared::cta.b64 p,[%5],%6,20000; ld.shared.v4.u32 {%0,%1,%2,%3},[%7]; selp.u32 %4,1,0,p;}"
                 : "=r"(v.x), "=r"(v.y), "=r"(v.z), "=r"(v.w), "=r"(ok) : "r"(b), "r"(ph), "r"(a) : "memory");
    return ok;
}
__device__ __forceinline__ bool wait_lds64(uint32_t b, uint32_t ph, uint32_t a, uint2& v) {
    uint32_t ok;
    asm volatile("{.reg .pred p; mbarrier.try_wait.parity.shared::cta.b64 p,[%3],%4,20000; ld.shared.v2.u32 {%0,%1},[%5]; selp.u32 %2,1,0,p;}"
                 : "=r"(v.x), "=r"(v.y), "=r"(ok) : "r"(b), "r"(ph), "r"(a) : "memory");
    return ok;
}
template <int PH> __device__ __forceinline__ void mbar_wait_c(uint32_t b) {
    asm volatile(
        "{.reg .pred p; .reg .u32 n; mov.u32 n,%2;\n"
        "W%=: mbarrier.try_wait.parity.shared::cta.b64 p,[%0],%1;\n"
        "@p bra D%=;\n"
        "add.u32 n,n,1; setp.lt.u32 p,n,2000000; @p bra W%=;\n"
        "trap;\n"
        "D%=: }" ::"r"(b), "n"(PH), "n"(PH) : "memory");
}
__device__ __forceinline__ void bar_sync(int id, int n) { asm volatile("bar.sync %0,%1;" ::"r"(id), "r"(n) : "memory"); }
__device__ __forceinline__ void bar_arrive(int id, int n) { asm volatile("bar.arrive %0,%1;" ::"r"(id), "r"(n) : "memory"); }
__device__ __forceinline__ void cluster_sync() { asm volatile("barrier.cluster.arrive.relaxed.aligned; barrier.cluster.wait.aligned;" ::: "memory"); }
__device__ __forceinline__ void fence_async() { asm volatile("fence.proxy.async;" ::: "memory"); }
__device__ __forceinline__ void fence_async_smem() { asm volatile("fence.proxy.async.shared::cta;" ::: "memory"); }
#define EFR 1
#define EFW 2
constexpr uint64_t POL_N = 0x1000000000000000ull, POL_F = 0x12F0000000000000ull;
constexpr uint64_t POL_LAST = EFR ? POL_F : POL_N  , POL_LATE = EFW ? POL_F : POL_N  , POL_SOON = EFW > 1 ? POL_F : POL_N;
__device__ __forceinline__ void bulk_g2s(uint32_t dst, const void* src, int bytes, uint32_t bar, uint64_t pol) {
    asm volatile("cp.async.bulk.shared::cluster.global.mbarrier::complete_tx::bytes.L2::cache_hint [%0],[%1],%2,[%3],%4;" ::"r"(dst), "l"(src), "r"(bytes), "r"(bar), "l"(pol) : "memory");
}
__device__ __forceinline__ void bulk_g2s_mc(uint32_t dst, const void* src, int bytes, uint32_t bar, uint64_t pol) {
    asm volatile("cp.async.bulk.shared::cluster.global.mbarrier::complete_tx::bytes.multicast::cluster.L2::cache_hint [%0],[%1],%2,[%3],%4,%5;" ::"r"(dst), "l"(src), "r"(bytes), "r"(bar), "h"((uint16_t)3), "l"(pol) : "memory");
}
__device__ __forceinline__ void bulk_s2s(uint32_t dst, uint32_t src, int bytes, uint32_t bar) {
    asm volatile("cp.async.bulk.shared::cluster.shared::cta.mbarrier::complete_tx::bytes [%0],[%1],%2,[%3];" ::"r"(dst), "r"(src), "r"(bytes), "r"(bar) : "memory");
}
__device__ __forceinline__ bool elect() {
    uint32_t r; asm volatile("{.reg .pred p; elect.sync _|p,0xffffffff; selp.u32 %0,1,0,p;}" : "=r"(r)); return r;
}
__device__ __forceinline__ void stg128(uint4* p, uint4 v, uint64_t pol) {
    asm volatile("st.global.L2::cache_hint.v4.u32 [%0],{%1,%2,%3,%4},%5;" ::"l"(p), "r"(v.x), "r"(v.y), "r"(v.z), "r"(v.w), "l"(pol));
}
__device__ __forceinline__ void stg32(uint32_t* p, uint32_t v, uint64_t pol) { asm volatile("st.global.L2::cache_hint.u32 [%0],%1,%2;" ::"l"(p), "r"(v), "l"(pol)); }
__device__ __forceinline__ uint4 ldcg128_last(const uint4* p) {
    uint4 v; asm volatile("ld.global.cg.L2::cache_hint.v4.u32 {%0,%1,%2,%3},[%4],%5;" : "=r"(v.x), "=r"(v.y), "=r"(v.z), "=r"(v.w) : "l"(p), "l"(POL_LAST) : "memory"); return v;
}
__device__ __forceinline__ void tma2d(uint32_t dst, const CUtensorMap* tm, int x, int y, uint32_t bar) {
    asm volatile("cp.async.bulk.tensor.2d.shared::cluster.global.mbarrier::complete_tx::bytes [%0],[%1,{%2,%3}],[%4];" ::"r"(dst), "l"(tm), "r"(x), "r"(y), "r"(bar) : "memory");
}
__device__ __forceinline__ void tma3d_mc(uint32_t dst, const CUtensorMap* tm, int y, int z, uint32_t bar, uint16_t mask) {
    asm volatile("{.reg .pred p; elect.sync _|p,0xffffffff;\n"
                 "@p cp.async.bulk.tensor.3d.shared::cluster.global.mbarrier::complete_tx::bytes.multicast::cluster [%0],[%1,{0,%2,%3}],[%4],%5;}"
                 ::"r"(dst), "l"(tm), "r"(y), "r"(z), "r"(bar), "h"(mask) : "memory");
}
__device__ __forceinline__ void tma2d_mc(uint32_t dst, const CUtensorMap* tm, int x, int y, uint32_t bar, uint16_t mask, uint64_t pol) {
    asm volatile("{.reg .pred p; elect.sync _|p,0xffffffff;\n"
                 "@p cp.async.bulk.tensor.2d.shared::cluster.global.mbarrier::complete_tx::bytes.multicast::cluster.L2::cache_hint [%0],[%1,{%2,%3}],[%4],%5,%6;}"
                 ::"r"(dst), "l"(tm), "r"(x), "r"(y), "r"(bar), "h"(mask), "l"(pol) : "memory");
}
__device__ __forceinline__ void bulk_g2s1(uint32_t dst, const void* src, int bytes, uint32_t bar, uint64_t pol) {
    asm volatile("{.reg .pred p; elect.sync _|p,0xffffffff;\n"
                 "@p cp.async.bulk.shared::cluster.global.mbarrier::complete_tx::bytes.L2::cache_hint [%0],[%1],%2,[%3],%4;}" ::"r"(dst), "l"(src), "r"(bytes), "r"(bar), "l"(pol) : "memory");
}
__device__ __forceinline__ void mbar_expect1(uint32_t b, int bytes) {
    asm volatile("{.reg .pred p; elect.sync _|p,0xffffffff; @p mbarrier.arrive.expect_tx.shared::cta.b64 _,[%0],%1;}" ::"r"(b), "r"(bytes) : "memory");
}
__device__ __forceinline__ void st_async4(uint32_t a, uint32_t x, uint32_t y, uint32_t z, uint32_t w, uint32_t mb) {
    asm volatile("st.async.shared::cluster.mbarrier::complete_tx::bytes.v4.b32 [%0],{%1,%2,%3,%4},[%5];" ::"r"(a), "r"(x), "r"(y), "r"(z), "r"(w), "r"(mb) : "memory");
}
__device__ __forceinline__ void st_async2(uint32_t a, uint32_t x, uint32_t y, uint32_t mb) {
    asm volatile("st.async.shared::cluster.mbarrier::complete_tx::bytes.v2.b32 [%0],{%1,%2},[%3];" ::"r"(a), "r"(x), "r"(y), "r"(mb) : "memory");
}
#define LDSQ "ld.shared"
__device__ __forceinline__ uint4 lds128(uint32_t a) { uint4 v; asm volatile(LDSQ ".v4.u32 {%0,%1,%2,%3},[%4];" : "=r"(v.x), "=r"(v.y), "=r"(v.z), "=r"(v.w) : "r"(a) : "memory"); return v; }
__device__ __forceinline__ uint2 lds64(uint32_t a) { uint2 v; asm volatile(LDSQ ".v2.u32 {%0,%1},[%2];" : "=r"(v.x), "=r"(v.y) : "r"(a) : "memory"); return v; }
__device__ __forceinline__ uint32_t lds32(uint32_t a) { uint32_t v; asm volatile(LDSQ ".u32 %0,[%1];" : "=r"(v) : "r"(a) : "memory"); return v; }
__device__ __forceinline__ void sts128(uint32_t a, uint32_t x, uint32_t y, uint32_t z, uint32_t w) { asm volatile("st.shared.v4.u32 [%0],{%1,%2,%3,%4};" ::"r"(a), "r"(x), "r"(y), "r"(z), "r"(w) : "memory"); }
__device__ __forceinline__ void sts64(uint32_t a, uint32_t x, uint32_t y) { asm volatile("st.shared.v2.u32 [%0],{%1,%2};" ::"r"(a), "r"(x), "r"(y) : "memory"); }
__device__ __forceinline__ void sts32(uint32_t a, uint32_t x) { asm volatile("st.shared.u32 [%0],%1;" ::"r"(a), "r"(x) : "memory"); }
__device__ __forceinline__ uint4 ldsm4(uint32_t a) { uint4 v; asm volatile("ldmatrix.sync.aligned.m8n8.x4.shared.b16 {%0,%1,%2,%3},[%4];" : "=r"(v.x), "=r"(v.y), "=r"(v.z), "=r"(v.w) : "r"(a) : "memory"); return v; }
__device__ __forceinline__ uint4 ldsm4t(uint32_t a) { uint4 v; asm volatile("ldmatrix.sync.aligned.m8n8.x4.trans.shared.b16 {%0,%1,%2,%3},[%4];" : "=r"(v.x), "=r"(v.y), "=r"(v.z), "=r"(v.w) : "r"(a) : "memory"); return v; }
__device__ __forceinline__ uint32_t movm(uint32_t a) { uint32_t d; asm volatile("movmatrix.sync.aligned.m8n8.trans.b16 %0,%1;" : "=r"(d) : "r"(a)); return d; }
__device__ __forceinline__ uint32_t pack2(float lo, float hi) { uint32_t d; asm("cvt.rn.bf16x2.f32 %0,%1,%2;" : "=r"(d) : "f"(hi), "f"(lo)); return d; }
__device__ __forceinline__ uint32_t hadd2(uint32_t a, uint32_t b) { uint32_t d; asm("add.rn.bf16x2 %0,%1,%2;" : "=r"(d) : "r"(a), "r"(b)); return d; }
__device__ __forceinline__ float blo(uint32_t v) { return __uint_as_float(v << 16); }
__device__ __forceinline__ float bhi(uint32_t v) { return __uint_as_float(v & 0xffff0000u); }
__device__ __forceinline__ float rbf(float x) { return __uint_as_float(pack2(0.f, x)); }
__device__ __forceinline__ float ex2(float x) { float y; asm("ex2.approx.ftz.f32 %0,%1;" : "=f"(y) : "f"(x)); return y; }
__device__ __forceinline__ float rcp(float x) { float y; asm("rcp.approx.ftz.f32 %0,%1;" : "=f"(y) : "f"(x)); return y; }
__device__ __forceinline__ void mma16(float* c, uint32_t a0, uint32_t a1, uint32_t a2, uint32_t a3, uint32_t b0, uint32_t b1) {
    asm volatile("mma.sync.aligned.m16n8k16.row.col.f32.bf16.bf16.f32 {%0,%1,%2,%3},{%4,%5,%6,%7},{%8,%9},{%0,%1,%2,%3};"
                 : "+f"(c[0]), "+f"(c[1]), "+f"(c[2]), "+f"(c[3]) : "r"(a0), "r"(a1), "r"(a2), "r"(a3), "r"(b0), "r"(b1));
}
__device__ __forceinline__ void mma8(float* c, uint32_t a0, uint32_t a1, uint32_t b0) {
    asm volatile("mma.sync.aligned.m16n8k8.row.col.f32.bf16.bf16.f32 {%0,%1,%2,%3},{%4,%5},{%6},{%0,%1,%2,%3};"
                 : "+f"(c[0]), "+f"(c[1]), "+f"(c[2]), "+f"(c[3]) : "r"(a0), "r"(a1), "r"(b0));
}
__device__ __forceinline__ uint4 ld_rlx128(const uint4* p) {
    uint4 v;
    asm volatile("{.reg .b128 t; ld.relaxed.gpu.global.b128 t,[%4]; mov.b128 {%0,%1,%2,%3},t;}" : "=r"(v.x), "=r"(v.y), "=r"(v.z), "=r"(v.w) : "l"(p) : "memory");
    return v;
}
__device__ __forceinline__ void st_rlx128(uint4* p, uint32_t x, uint32_t y, uint32_t z, uint32_t w) {
    asm volatile("{.reg .b128 t; mov.b128 t,{%1,%2,%3,%4}; st.relaxed.gpu.global.b128 [%0],t;}" ::"l"(p), "r"(x), "r"(y), "r"(z), "r"(w) : "memory");
}
__device__ __forceinline__ uint4 ldcg128(const uint4* p) { uint4 v; asm volatile("ld.global.cg.v4.u32 {%0,%1,%2,%3},[%4];" : "=r"(v.x), "=r"(v.y), "=r"(v.z), "=r"(v.w) : "l"(p) : "memory"); return v; }
__device__ __forceinline__ void red_release(unsigned* p, unsigned v) {
    asm volatile("fence.proxy.async; red.relaxed.gpu.global.add.u32 [%0],%1;" ::"l"(p), "r"(v) : "memory");
}
__device__ __forceinline__ void wait_cnt(const unsigned* p, unsigned target) {
    unsigned v; int n = 0;
    while (true) {
        asm volatile("ld.acquire.gpu.global.u32 %0,[%1];" : "=r"(v) : "l"(p) : "memory");
        if (v >= target) break;
        if (++n > 3000000) __trap();
        __nanosleep(40);
    }
}
__device__ __forceinline__ void wait_cnt_warp(const unsigned* p, unsigned target) {
    unsigned v; int n = 0;
    while (true) {
        asm volatile("ld.acquire.gpu.global.u32 %0,[%1];" : "=r"(v) : "l"(p) : "memory");
        if (__all_sync(0xffffffffu, v >= target)) break;
        if (++n > 3000000) __trap();
    }
}
__device__ __forceinline__ uint64_t mkdesc(uint32_t addr, uint32_t lbo, uint32_t sbo, uint32_t sw) {
    return (uint64_t)((addr & 0x3FFFF) >> 4) | ((uint64_t)(lbo >> 4) << 16) | ((uint64_t)(sbo >> 4) << 32) | ((uint64_t)sw << 62);
}
__device__ __forceinline__ void wg_fence() { asm volatile("wgmma.fence.sync.aligned;" ::: "memory"); }
__device__ __forceinline__ void wg_commit() { asm volatile("wgmma.commit_group.sync.aligned;" ::: "memory"); }
template <int N> __device__ __forceinline__ void wg_wait() { asm volatile("wgmma.wait_group.sync.aligned %0;" ::"n"(N) : "memory"); }
#define R8(c, o) "+f"(c[o]), "+f"(c[o + 1]), "+f"(c[o + 2]), "+f"(c[o + 3]), "+f"(c[o + 4]), "+f"(c[o + 5]), "+f"(c[o + 6]), "+f"(c[o + 7])
#define R32(c, o) R8(c, o), R8(c, o + 8), R8(c, o + 16), R8(c, o + 24)
#define S32A "%0,%1,%2,%3,%4,%5,%6,%7,%8,%9,%10,%11,%12,%13,%14,%15,%16,%17,%18,%19,%20,%21,%22,%23,%24,%25,%26,%27,%28,%29,%30,%31"
#define S32B ",%32,%33,%34,%35,%36,%37,%38,%39,%40,%41,%42,%43,%44,%45,%46,%47,%48,%49,%50,%51,%52,%53,%54,%55,%56,%57,%58,%59,%60,%61,%62,%63"
#define S32C ",%64,%65,%66,%67,%68,%69,%70,%71,%72,%73,%74,%75,%76,%77,%78,%79,%80,%81,%82,%83,%84,%85,%86,%87,%88,%89,%90,%91,%92,%93,%94,%95"
#define S32D ",%96,%97,%98,%99,%100,%101,%102,%103,%104,%105,%106,%107,%108,%109,%110,%111,%112,%113,%114,%115,%116,%117,%118,%119,%120,%121,%122,%123,%124,%125,%126,%127"
#define W8(c, o) "=f"(c[o]), "=f"(c[o + 1]), "=f"(c[o + 2]), "=f"(c[o + 3]), "=f"(c[o + 4]), "=f"(c[o + 5]), "=f"(c[o + 6]), "=f"(c[o + 7])
#define W32(c, o) W8(c, o), W8(c, o + 8), W8(c, o + 16), W8(c, o + 24)
template <bool ACC> __device__ __forceinline__ void wgmma256(float* c, uint64_t da, uint64_t db) {
    if (ACC) asm volatile("wgmma.mma_async.sync.aligned.m64n256k16.f32.bf16.bf16 {" S32A S32B S32C S32D "},%128,%129,1,1,1,0,1;"
                          : R32(c, 0), R32(c, 32), R32(c, 64), R32(c, 96) : "l"(da), "l"(db));
    else asm volatile("wgmma.mma_async.sync.aligned.m64n256k16.f32.bf16.bf16 {" S32A S32B S32C S32D "},%128,%129,0,1,1,0,1;"
                      : W32(c, 0), W32(c, 32), W32(c, 64), W32(c, 96) : "l"(da), "l"(db));
}
template <int N> __device__ __forceinline__ void reg_inc() { asm volatile("setmaxnreg.inc.sync.aligned.u32 %0;" ::"n"(N)); }
template <int N> __device__ __forceinline__ void reg_dec() { asm volatile("setmaxnreg.dec.sync.aligned.u32 %0;" ::"n"(N)); }

#define PROF(cond, idx) do {} while (0)
#define CPROF(k) do {} while (0)

constexpr int S_GATE = 232440, S_TAG = 232444, S_XBAR = 232432;
constexpr float SC_LOG2E = 0.08838834764831845f * 1.4426950408889634f;

__device__ __forceinline__ float2 ln_finish(float mean, float var) {
    float sd; asm("sqrt.approx.f32 %0,%1;" : "=f"(sd) : "f"(rbf(rbf(var) + 1e-5f)));
    sd = rbf(sd);
    return make_float2(rbf(mean), sd);
}

__device__ __forceinline__ float2 row_stats512(const uint4* src, int s1, int s2) {
    const int g = (threadIdx.x & 31) >> 2;
    uint4 v[16];
#pragma unroll
    for (int i = 0; i < 16; i++) v[i] = ldcg128(src + (i >> 1) * s1 + (i & 1) * s2);
    float a[4] = {0, 0, 0, 0}, q0[4] = {0, 0, 0, 0}, q1[4] = {0, 0, 0, 0};
#pragma unroll
    for (int i = 0; i < 16; i++) {
        mma16(a, v[i].x, v[i].y, v[i].z, v[i].w, 0x3f803f80u, 0x3f803f80u);
        mma8(q0, v[i].x, v[i].y, v[i].x); mma8(q1, v[i].x, v[i].y, v[i].y);
        mma8(q0, v[i].z, v[i].w, v[i].z); mma8(q1, v[i].z, v[i].w, v[i].w);
    }
    const float sum = a[0] + a[2], sq = (g & 1) ? q0[1] + q1[3] : q0[0] + q1[2];
    return make_float2(sum, fmaxf(sq - sum * sum * (1.f / 512.f), 0.f));
}
__device__ __forceinline__ void x1_stats(int rg) {
    const int lane = threadIdx.x & 31, g = lane >> 2, c = lane & 3;
    const float2 r = row_stats512(g_xA[0] + (rg >> 4) * 8192 + (rg & 15) * 64 + c * 8 + g, 1024, 32);
    if (c == (g >> 1)) { g_st[0][rg * 8 + g] = r; g_ln0[rg * 8 + g] = 0; }
    __syncwarp();
    if (lane == 0) red_release(cnt_ptr(C_ST, rg >> 4), 1);
}
__global__ void stats_kernel() { x1_stats(blockIdx.x * 4 + (threadIdx.x >> 5)); }

#define NT 9
#define RH 104
#define RW0 200
#define NPD 5
#define NTO 13
#define DP1 0
#define GPW 0
#define GPJ 0
#define PACE 2
#define BKA 0
#define GSE 0
#define EARLY 0
#define STO 1
#define G2I 3
#define VE 4
#define VF 8
constexpr int TILE = 20480;
constexpr int R_WV = 0, R_WO = 65536, R_T = 131072, R_M = R_T + 2 * TILE  , R_LOC = R_M + 8192  ,
              R_REM = R_LOC + 12288  , R_O = R_REM + 24576  , R_SX = R_O + 4096  ,
              R_IL = R_SX + 10240  , R_BAR = 231936, R_Z = R_BAR + 128  , R_STQ = 0, R_STK = 65536, R_STV = 131072;
static_assert(R_IL + 512 <= R_BAR && R_BAR + 256 <= S_XBAR, "smem map");
enum { RB_INIT = 0, RB_T = 2  , RB_V = 4  , RB_QK = 8  , RB_N = 12 };
enum { NB_MF = 1  , NB_LOC = 3  , NB_PAIR = 5  , NB_O = 9  , NB_XG = 11  , NB_W = 13 };
__device__ __forceinline__ uint32_t clk32() { return (uint32_t)clock64(); }

__device__ __forceinline__ char* acc_base() { return (char*)(((size_t)g_acc + 131071) & ~(size_t)131071); }
__device__ __forceinline__ uint32_t acc_slice(uint32_t s6) { return (s6 & 1) * 256 + (s6 >> 1) * 1024; }
__device__ __forceinline__ uint32_t acc_main(uint32_t rank, uint32_t tid) { return acc_slice(rank * 32 + (tid >> 3)) + (tid & 7) * 16; }
__device__ __forceinline__ uint32_t acc_extra(uint32_t rank, uint32_t tid) { return 65536 + acc_slice(((tid >> 5) & 1) + rank * 4 + (tid >> 6) * 8) + (tid & 31) * 4; }
__device__ __forceinline__ uint32_t acc_slot(uint32_t s) { return (s & 1) * 128 + (s & 2) * 256; }
__device__ __forceinline__ void acc_init(const __nv_bfloat16* mem0, int i) {
    const uint32_t tid = i & 255, rank = (i >> 8) & 1, slot = (i >> 9) & 3, X = i >> 11;
    uint32_t v[5] = {0, 0, 0, 0, 0};
    if (slot == 3) {
        const uint16_t* m = (const uint16_t*)mem0 + (tid & 3) * 1024 + rank * 256 + (tid >> 5) * 32 + ((tid >> 2) & 7);
#pragma unroll
        for (int k = 0; k < 4; k++) v[k] = __ldg(m + k * 8) | ((uint32_t)__ldg(m + k * 8 + 512) << 16);
        v[4] = (v[3] >> 16) | 0x42000000u; v[3] = (v[3] & 0xffff) | 0x42000000u;
    }
    *(uint4*)(acc_base() + X * 32768 + acc_slot(slot) + acc_main(rank, tid)) = make_uint4(v[0], v[1], v[2], v[3]);
    *(uint32_t*)(acc_base() + X * 1024 + acc_slot(slot) + acc_extra(rank, tid)) = v[4];
}
__global__ void acc_init_kernel(const __nv_bfloat16* mem0) { acc_init(mem0, blockIdx.x * 256 + threadIdx.x); }

struct RecW { uint32_t am, ae, ah, dp, lp, lpw, vo, sb, bar, zero, ts, tn; };
__device__ __forceinline__ uint32_t vadd(uint32_t a, uint32_t b) { uint32_t d; asm volatile("add.u32 %0,%1,%2;" : "=r"(d) : "r"(a), "r"(b)); return d; }
__device__ __forceinline__ uint32_t vshr(uint32_t a, int n) { uint32_t d; asm volatile("shr.u32 %0,%1,%2;" : "=r"(d) : "r"(a), "r"(n)); return d; }
__device__ __forceinline__ uint64_t gptr(uint32_t lo, uint32_t hi) { uint64_t d; asm("mov.b64 %0,{%1,%2};" : "=l"(d) : "r"(lo), "r"(hi)); return d; }
__device__ __forceinline__ void sfence(uint32_t zero) { asm volatile("{.reg .pred p; setp.ne.u32 p,%0,0; @p exit;}" ::"r"(zero) : "memory"); }
#define SF sfence(k.zero)
#define TS(i) do {} while (0)
#define TSN(i) do {} while (0)
#define TSET(it, slot) do {} while (0)
struct Gat { uint32_t x, y, z, w, e; };
template <int X>
__device__ __forceinline__ void gat_issue(Gat& g, const RecW& k, int s, uint32_t dep) {
    const uint32_t o = acc_slot(s + 3) + dep;
    asm volatile("{.reg .b128 t; ld.relaxed.gpu.global.b128 t,[%5+%7]; mov.b128 {%0,%1,%2,%3},t; ld.relaxed.gpu.global.u32 %4,[%6+%8];}"
                 : "=r"(g.x), "=r"(g.y), "=r"(g.z), "=r"(g.w), "=r"(g.e) : "l"(gptr(k.am + o, k.ah)), "l"(gptr(k.ae + o, k.ah)), "n"(X * 32768), "n"(X * 1024) : "memory");
}
template <int X>
__device__ __forceinline__ bool gat_store(const Gat& g, const RecW& k) {
    uint32_t c;
    asm volatile("prmt.b32 %0,%1,%2,0x7632;" : "=r"(c) : "r"(g.w), "r"(g.e));
    SF;
    asm volatile("{.reg .b32 t; prmt.b32 t,%4,%6,0x5410; stmatrix.sync.aligned.m8n8.x4.trans.shared.b16 [%0+%5],{%1,%2,%3,t};}" ::"r"(k.lpw), "r"(g.x), "r"(g.y), "r"(g.z), "r"(g.w), "n"(R_M + X * 4096), "r"(g.e) : "memory");
    return __all_sync(0xffffffffu, c == 0x42004200u);
}
template <int X>
__device__ __forceinline__ void gat_finish(bool ok, const RecW& k, int s) {
    if (!ok) {
        int n = s;
        while (true) {
            Gat g;
            gat_issue<X>(g, k, n, 0);
            if (gat_store<X>(g, k)) break;
            n += 4;
            if (n > 8000000) __trap();
        }
    }
}
__device__ __forceinline__ uint4 lds128o(uint32_t a, int o) { uint4 v; asm volatile("{.reg .b32 t; add.u32 t,%4,%5; ld.shared.v4.u32 {%0,%1,%2,%3},[t];}" : "=r"(v.x), "=r"(v.y), "=r"(v.z), "=r"(v.w) : "r"(a), "r"(o) : "memory"); return v; }
__device__ __forceinline__ uint4 ldsm4o(uint32_t a, int o) { uint4 v; asm volatile("{.reg .b32 t; add.u32 t,%4,%5; ldmatrix.sync.aligned.m8n8.x4.shared.b16 {%0,%1,%2,%3},[t];}" : "=r"(v.x), "=r"(v.y), "=r"(v.z), "=r"(v.w) : "r"(a), "r"(o) : "memory"); return v; }
#define WLD(base, i) wt[i] = lds128o(k.lpw, (base) + (i) * 4096)
template <int PASS, int X, int NP>
__device__ __forceinline__ void rec_qkv(const RecW& k, int s, const uint32_t (*wq)[4], const uint32_t (*wk)[4], uint4* wt, Gat& g2, int s2, bool& ok2) {
    constexpr bool BWD = PASS == 2, DIRECT = !(BKA && PASS == 1);
    float aq[4] = {0, 0, 0, 0}, ak[4] = {0, 0, 0, 0}, av[4] = {0, 0, 0, 0};
    constexpr int ma = R_M + X * 4096;
    if (BWD) { TS(1); gat_finish<1>(GSE ? ok2 : gat_store<1>(g2, k), k, s); }
    bar_sync(NB_MF + X, 256);
    uint4 mf = ldsm4o(k.lp, ma + (BWD ? 7 : 0) * 512);
    if (BWD) TS(2); else { TS(0); TSN(13); }
#pragma unroll
    for (int ii = 0; ii < 8; ii++) {
        const int i = BWD ? 7 - ii : ii;
        const uint4 m = mf;
        if (ii < 7) mf = ldsm4o(k.lp, ma + (BWD ? i - 1 : i + 1) * 512);
        if (PASS == 1 && ii == G2I) gat_issue<1>(g2, k, s2, 0);
        SF;
#pragma unroll
        for (int hh = 0; hh < 2; hh++) {
            const int h = BWD ? 1 - hh : hh, ks = 2 * i + h;
            const uint32_t b0 = h ? m.z : m.x, b1 = h ? m.w : m.y;
            mma16(aq, wq[ks][0], wq[ks][1], wq[ks][2], wq[ks][3], b0, b1);
            mma16(ak, wk[ks][0], wk[ks][1], wk[ks][2], wk[ks][3], b0, b1);
            SF;
            mma16(av, wt[ks].x, wt[ks].y, wt[ks].z, wt[ks].w, b0, b1);
            SF;
            if (!BWD && ks + NP < 16) WLD(R_WV, ks + NP < 16 ? ks + NP : 0);
            if (BWD && ks >= NT) WLD(R_WV, ks >= NT ? ks - NT : 0);
            SF;
        }
    }
    if (PASS == 1 && GSE) { ok2 = gat_store<1>(g2, k); SF; }
    const uint32_t ra = vadd(k.lpw, k.dp + R_REM + (X * 2 + (s & 1)) * 6144), va = ((vshr(k.lp, 7) & 1) * 48 ^ k.lp ^ (k.vo & 64)) + (k.vo & ~64u);
    const uint32_t x0 = movm(pack2(aq[0], aq[1])), x1 = movm(pack2(aq[2], aq[3])), x2 = movm(pack2(ak[0], ak[1])), x3 = movm(pack2(ak[2], ak[3]));
    SF;
    asm volatile("stmatrix.sync.aligned.m8n8.x2.shared.b16 [%0+%3],{%1,%2};" ::"r"(va), "r"(pack2(av[0], av[1])), "r"(pack2(av[2], av[3])), "n"(R_LOC + X * 6144) : "memory");
    SF;
    if (STO && DIRECT) st_async4(ra, x0, x1, x2, x3, k.bar + X * 16);
    asm volatile("st.shared.v4.u32 [%0+%5],{%1,%2,%3,%4};" ::"r"(k.lpw), "r"(x0), "r"(x1), "r"(x2), "r"(x3), "n"(R_LOC + X * 6144) : "memory");
    bar_arrive(NB_LOC + X, 320);
    if (!STO && DIRECT) st_async4(ra, x0, x1, x2, x3, k.bar + X * 16);
    SF;
    TS(BWD ? 4 : 3);
}
template <bool BWD, int X>
__device__ __forceinline__ void rec_out(const RecW& k, int s, uint4* wt, Gat& g, int s1) {
    if (BWD) { WLD(R_WO, 17 - NTO); WLD(R_WO, 16 - NTO); }
    TS(BWD ? 8 : 5);
    bar_sync(NB_O + X, 320);
    float r0[4] = {0, 0, 0, 0}, r1[4] = {0, 0, 0, 0};
    constexpr int oa = R_O + X * 2048;
    uint4 bn = lds128o(k.lp, oa + (BWD ? 3 : 0) * 512);
    TS(BWD ? 9 : 6);
    uint2 il;
    uint64_t pm, pe;
#pragma unroll
    for (int ii = 0; ii < 4; ii++) {
        const int i = BWD ? 3 - ii : ii;
        const uint4 b = bn;
        if (ii < 3) bn = lds128o(k.lp, oa + (BWD ? i - 1 : i + 1) * 512);
        else { asm volatile("ld.shared.v2.u32 {%0,%1},[%2+%3];" : "=r"(il.x), "=r"(il.y) : "r"(k.lp), "n"(R_IL + X * 8) : "memory"); pm = gptr(vadd(k.am, acc_slot(s)), k.ah); pe = gptr(vadd(k.ae, acc_slot(s)), k.ah); }
        SF;
        if (BWD && EARLY == ii + 1) { gat_issue<0>(g, k, s1 + 1, 0); SF; }
#pragma unroll
        for (int nn = 0; nn < 4; nn++) {
            const int n = BWD ? 3 - nn : nn, f = 4 * i + n, nx = BWD ? f - NTO + 2 : f + NTO - 2;
            mma16((n & 1) ? r1 : r0, wt[f].x, wt[f].y, wt[f].z, wt[f].w, n >> 1 ? b.z : b.x, n >> 1 ? b.w : b.y);
            SF;
            if (ii * 4 + nn >= 2 && nx >= 0 && nx < 16) WLD(R_WO, nx & 15);
            SF;
        }
    }
    const float i0 = __uint_as_float(il.x), i1 = __uint_as_float(il.y);
    asm volatile("red.relaxed.gpu.global.add.noftz.v4.bf16x2 [%0+%5],{%1,%2,%3,%4};" ::"l"(pm),
                 "r"(pack2(r0[0] * i0, r0[1] * i1)), "r"(pack2(r0[2] * i0, r0[3] * i1)), "r"(pack2(r1[0] * i0, r1[1] * i1)), "r"(pack2(r1[2] * i0, 1.f)), "n"(X * 32768) : "memory");
    asm volatile("red.relaxed.gpu.global.add.noftz.bf16x2 [%0+%2],%1;" ::"l"(pe), "r"(pack2(r1[3] * i1, 1.f)), "n"(X * 1024) : "memory");
    bar_arrive(NB_XG + X, 320);
    SF;
    TS(BWD ? 10 : 7);
}
__device__ __forceinline__ uint32_t pause(uint32_t v, int n) {
#pragma unroll
    for (int i = 0; i < n; i++) asm volatile("shfl.sync.bfly.b32 %0,%0,0,0x1f,0xffffffff;" : "+r"(v));
    return v;
}
template <bool DUAL, int X>
__device__ __forceinline__ void rec_step(const RecW& k, int s, int s2, const uint32_t (*wq)[4], const uint32_t (*wk)[4], uint4* wt) {
    constexpr int NP = NPD;
    uint4 wo[16];
    Gat g;
    bool ok2;
    rec_qkv<DUAL ? 1 : 0, X, NP>(k, s, wq, wk, wt, g, s2, ok2);
    if (DUAL) rec_qkv<2, 1, NP>(k, s2, wq, wk, wt, g, s2, ok2);
    uint32_t wa = k.lpw;
#pragma unroll
    for (int i = 0; i < NTO; i++) {
        wo[i] = lds128o(wa, R_WO + i * 4096);
        if (i % PACE == PACE - 1) wa = k.lpw + (wo[i].x & k.zero);
        SF;
    }
    rec_out<false, X>(k, s, wo, g, s);
    if (DUAL) { rec_out<true, 1>(k, s2, wo, g, s); if (!EARLY) gat_issue<0>(g, k, s + 1, 0); SF; }
#pragma unroll
    for (int i = 0; i < NP; i++) { WLD(R_WV, i); SF; }
    if (!DUAL) gat_issue<X>(g, k, s + 1, pause(wt[NP - 1].x & k.zero, DP1));
    TS(12);
    gat_finish<X>(gat_store<X>(g, k), k, s + 1);
    TS(11);
}

__device__ __forceinline__ void rec_fetch(const CUtensorMap* tm, uint32_t dst, int x, int y, int nx, uint32_t bar) {
#pragma unroll 1
    for (int j = 0; j < 8; j++) tma2d(dst + j * 8192, tm, x + (j / (8 / nx)) * 64, y + (j % (8 / nx)) * 64, bar);
}
__device__ __forceinline__ void rec_weights(const Params& p, uint32_t sb, int head, uint32_t rank, int w) {
    const int lane = threadIdx.x & 31, t = w & 3, WG = w >> 2;
    uint32_t wq[16][4], wk[16][4];
    const uint32_t rowo = (((lane >> 4) << 3) + (lane & 7)) * 128;
    const uint32_t woff = sb + WG * 32768 + rowo + (((2 * t + ((lane >> 3) & 1)) ^ (lane & 7)) << 4);
    const uint32_t qoff = sb + ((w & 1) ? R_STK : R_STQ) + WG * 32768 + rowo + (((2 * (t & 2) + ((lane >> 3) & 1)) ^ (lane & 7)) << 4);
    const uint32_t lw = sb + (lane ^ (lane >> 3)) * 16;
    PROF(threadIdx.x == 0, 3501);
    if (w >= 4 && p.dostats) { wait_cnt_warp(g_gate, lds32(sb + S_GATE)); x1_stats((head * 2 + rank) * 4 + w - 4); }
    PROF(threadIdx.x == 0, 3502);
    mbar_wait(sb + R_BAR + RB_INIT * 8, 0);
    PROF(threadIdx.x == 0, 3503);
#pragma unroll
    for (int ks = 0; ks < 16; ks++) {
        uint4 a = ldsm4t(qoff + ks * 2048), b = ldsm4t((qoff ^ 32) + ks * 2048);
        wq[ks][0] = a.x; wq[ks][1] = a.y; wq[ks][2] = a.z; wq[ks][3] = a.w;
        wk[ks][0] = b.x; wk[ks][1] = b.y; wk[ks][2] = b.z; wk[ks][3] = b.w;
    }
    bar_sync(NB_W, 256);
#pragma unroll 4
    for (int ks = 0; ks < 16; ks++) { const uint4 a = ldsm4t(woff + R_STV + ks * 2048); sts128(lw + w * 512 + R_WV + ks * 4096, a.x, a.y, a.z, a.w); }
    bar_sync(NB_W, 256);
    if (threadIdx.x == 0) {
        mbar_expect(sb + R_BAR + RB_INIT * 8, 65536);
        rec_fetch(&p.tm[4], sb + R_STV, rank * 256, head * 128, 4, sb + R_BAR + RB_INIT * 8);
    }
    __syncwarp();
    mbar_wait(sb + R_BAR + RB_INIT * 8, 1);
#pragma unroll 4
    for (int f = 0; f < 16; f++) {
        const uint4 a = ldsm4t(sb + R_STV + (w >> 1) * 16384 + (f >> 1) * 2048 + rowo + ((((w & 1) * 4 + (f & 1) * 2 + ((lane >> 3) & 1)) ^ (lane & 7)) << 4));
        sts128(lw + w * 512 + R_WO + f * 4096, a.x, a.y, a.z, a.w);
    }
    PROF(threadIdx.x == 0, 3504);
    __syncthreads();
    cluster_sync();
    PROF(threadIdx.x == 0, 3505);
    RecW k;
    k.am = __shfl_sync(0xffffffffu, (uint32_t)(size_t)acc_base() + acc_main(rank, threadIdx.x), lane);
    k.ae = __shfl_sync(0xffffffffu, (uint32_t)(size_t)acc_base() + acc_extra(rank, threadIdx.x), lane);
    k.ah = (uint32_t)((size_t)acc_base() >> 32);
    k.sb = sb; k.zero = p.zero;

    k.dp = mapa(sb, rank ^ 1) - sb;
    k.lp = __shfl_sync(0xffffffffu, lw, lane);
    k.lpw = __shfl_sync(0xffffffffu, lw + w * 512, lane);
    k.vo = 4096 + w * 256 + (w & 1) * 64;
    k.bar = sb + k.dp + R_BAR + (RB_QK + WG) * 8;
    int it = 0;
    uint4 wt[16];
#pragma unroll
    for (int i = 0; i < NPD; i++) WLD(R_WV, i);
    gat_finish<0>(false, k, 0);
#pragma unroll 1
    for (; it < min(p.b1, p.e0); it++) { TSET(it, w == GPW ? 0 : 3); rec_step<false, 0>(k, it, it, wq, wk, wt); }
#pragma unroll 1
    for (; it < p.e0; it++) { TSET(it, w == GPW ? 0 : 3); rec_step<true, 0>(k, it, it - p.b1, wq, wk, wt); }
    if (it < p.nit) gat_finish<1>(false, k, it - p.b1);
#pragma unroll 1
    for (; it < p.nit; it++) { TSET(it, w == GPW ? 0 : 3); rec_step<false, 1>(k, it - p.b1, it - p.b1, wq, wk, wt); }
}

__device__ __forceinline__ void mma16_top(float* c, uint32_t a0, uint32_t a2, uint32_t b0, uint32_t b1) {
    asm volatile("{.reg .b32 j; mma.sync.aligned.m16n8k16.row.col.f32.bf16.bf16.f32 {%0,%1,%2,%3},{%4,j,%5,j},{%6,%7},{%0,%1,%2,%3};}"
                 : "+f"(c[0]), "+f"(c[1]), "+f"(c[2]), "+f"(c[3]) : "r"(a0), "r"(a2), "r"(b0), "r"(b1));
}
__device__ __forceinline__ void rec_load_tile(uint32_t sb, int X, int s, int head, uint32_t rank) {
    const uint32_t bar = sb + R_BAR + (RB_T + X) * 8;
    const uint4* src = g_qkv[X] + (size_t)(s * 32 + head) * 1536;
    mbar_expect1(bar, TILE);
    bulk_g2s1(sb + R_T + X * TILE, src + 512, 16384, bar, POL_LAST);
    bulk_g2s1(sb + R_T + X * TILE + 16384, src + rank * 256, 4096, bar, POL_LAST);
}
__device__ __forceinline__ bool chunk_ready(int X, int s) {
    unsigned v;
    asm volatile("ld.relaxed.gpu.global.u32 %0,[%1];" : "=r"(v) : "l"(cnt_ptr(C_QKV0 + X, s >> 2)) : "memory");
    return __all_sync(0xffffffffu, v >= 384);
}
__device__ __forceinline__ uint4 hadd4(uint4 a, uint4 b) { return make_uint4(hadd2(a.x, b.x), hadd2(a.y, b.y), hadd2(a.z, b.z), hadd2(a.w, b.w)); }
struct RecH { uint32_t lw, lm, lq, lv, lu, sb, zero, ts, tn; };
__device__ __forceinline__ void rec_publish(int X, int s) {
    asm volatile("{.reg .pred p; cp.async.bulk.wait_group 0; elect.sync _|p,0xffffffff; @p red.relaxed.gpu.global.add.u32 [%0],1;}" ::"l"(cnt_ptr(C_O0 + X, s >> 2)) : "memory");
}
__device__ __forceinline__ void rec_mattn(const RecH& k, uint32_t dp, int X, int j, int s, bool qk, uint4 (*V)[4], uint4* vm) {
    const uint32_t sb = k.sb, to = R_T + X * TILE + j * 2048, lo = R_LOC + X * 6144, ro = R_REM + (X * 2 + (s & 1)) * 6144;
    const uint32_t bar = sb + R_BAR + (X * 2 + j) * 8;
    uint4 K[2][4];
    mbar_wait(sb + R_BAR + (RB_T + X) * 8, s & 1);
    TS(1);
#pragma unroll
    for (int i = 0; i < 8; i++) K[i >> 2][i & 3] = ldsm4(k.lm + (to + (i >> 2) * 1024 + ((i >> 1) & 1) * 4096 + (i & 1) * 512));
    bar_sync(NB_LOC + X, 320);
    fence_async_smem();
    if (qk) asm volatile("{.reg .pred p; elect.sync _|p,0xffffffff; @p cp.async.bulk.shared::cluster.shared::cta.mbarrier::complete_tx::bytes [%0],[%1],2048,[%2];}"
                         ::"r"(sb + dp + ro + j * 2048), "r"(sb + lo + j * 2048), "r"(bar + dp + RB_QK * 8) : "memory");
    asm volatile("{.reg .pred p; elect.sync _|p,0xffffffff; @p cp.async.bulk.shared::cluster.shared::cta.mbarrier::complete_tx::bytes [%0],[%1],1024,[%2];}"
                 ::"r"(sb + dp + ro + 4096 + j * 1024), "r"(sb + lo + 4096 + j * 1024), "r"(bar + dp + RB_V * 8) : "memory");
    uint4 u[4];
#pragma unroll
    for (int i = 0; i < 4; i++) u[i] = ldsm4(k.lm + (lo + j * 2048 + i * 512));
    TS(2);
    mbar_wait(bar + RB_QK * 8, s & 1);
    TS(3);
    float S[5][4];
#pragma unroll
    for (int i = 0; i < 5; i++) S[i][0] = S[i][1] = S[i][2] = S[i][3] = 0;
    {
        uint4 r[4];
#pragma unroll
        for (int i = 0; i < 4; i++) r[i] = ldsm4(k.lm + (ro + j * 2048 + i * 512));
        SF;
#pragma unroll
        for (int e = 0; e < 2; e++) {
            uint4& km = u[2 * e + 1];
            const uint32_t q0 = hadd2(u[2 * e].x, r[2 * e].x), q1 = hadd2(u[2 * e].y, r[2 * e].y);
            mma16_top(S[0], q0, q1, K[e][0].x, K[e][0].y);
            km.x = hadd2(km.x, r[2 * e + 1].x); km.y = hadd2(km.y, r[2 * e + 1].y);
            SF;
            mma16_top(S[1], q0, q1, K[e][1].x, K[e][1].y);
            const uint32_t q2 = hadd2(u[2 * e].z, r[2 * e].z), q3 = hadd2(u[2 * e].w, r[2 * e].w);
            SF;
            mma16_top(S[2], q0, q1, K[e][2].x, K[e][2].y);
            km.z = hadd2(km.z, r[2 * e + 1].z); km.w = hadd2(km.w, r[2 * e + 1].w);
            SF;
            mma16_top(S[3], q0, q1, K[e][3].x, K[e][3].y);
            mma16_top(S[4], q0, q1, km.x, km.y);
            SF;
#pragma unroll
            for (int i = 0; i < 4; i++) { mma16_top(S[i], q2, q3, K[e][i].z, K[e][i].w); SF; }
            mma16_top(S[4], q2, q3, km.z, km.w);
            SF;
        }
    }
#define VLD(a, b) _Pragma("unroll") for (int i = (a); i < (b); i++) V[i >> 2][i & 3] = ldsm4t((k.lv ^ ((i & 1) * 0x20)) + (to + 8192 + (i >> 2) * 4096 + ((i >> 1) & 1) * 1024))
    VLD(0, VE);
    SF;
    const uint32_t sxr = R_SX + (X * 2 + j) * 2560, sxw = R_SX + (X * 2 + (j ^ 1)) * 2560;
    sts128(k.lw + sxw, __float_as_uint(S[0][0]), __float_as_uint(S[0][1]), __float_as_uint(S[1][0]), __float_as_uint(S[1][1]));
    SF;
    sts128(k.lw + (sxw + 512), __float_as_uint(S[2][0]), __float_as_uint(S[2][1]), __float_as_uint(S[3][0]), __float_as_uint(S[3][1]));
    SF;
    sts64(k.lw + (sxw + 1024), __float_as_uint(S[4][0]), __float_as_uint(S[4][1]));
    TS(4);
    bar_sync(NB_PAIR + X, 64);
    {
        const uint4 a = lds128(k.lw + sxr), b = lds128(k.lw + (sxr + 512));
        const uint2 c = lds64(k.lw + (sxr + 1024));
        SF;
        VLD(VE, VF);
        SF;
        S[0][0] += __uint_as_float(a.x); S[0][1] += __uint_as_float(a.y); S[1][0] += __uint_as_float(a.z); S[1][1] += __uint_as_float(a.w);
        S[2][0] += __uint_as_float(b.x); S[2][1] += __uint_as_float(b.y); S[3][0] += __uint_as_float(b.z); S[3][1] += __uint_as_float(b.w);
        S[4][0] += __uint_as_float(c.x); S[4][1] += __uint_as_float(c.y);
    }
    float m = fmaxf(fmaxf(fmaxf(S[0][0], S[0][1]), fmaxf(S[1][0], S[1][1])), fmaxf(fmaxf(S[2][0], S[2][1]), fmaxf(S[3][0], S[3][1])));
    m = fmaxf(m, fmaxf(S[4][0], S[4][1]));
    m = fmaxf(m, __shfl_xor_sync(0xffffffffu, m, 1));
    const float m2 = __shfl_xor_sync(0xffffffffu, m, 2);
    SF;
    VLD(VF, 8);
    uint32_t ok;
    asm volatile("{.reg .pred p; mbarrier.test_wait.parity.shared::cta.b64 p,[%1],%2; selp.u32 %0,1,0,p;}" : "=r"(ok) : "r"(bar + RB_V * 8), "r"(s & 1) : "memory");
    uint4 vr0 = ldsm4(k.lu + (ro + 4096 + j * 1024)), vr1 = ldsm4(k.lu + (ro + 4608 + j * 1024));
    vm[0] = ldsm4(k.lu + (lo + 4096 + j * 1024)); vm[1] = ldsm4(k.lu + (lo + 4608 + j * 1024));
    SF;
    TS(5);
    m = fmaxf(m, m2) * -SC_LOG2E;
    uint32_t P[5];
#pragma unroll
    for (int i = 0; i < 5; i++) P[i] = pack2(ex2(fmaf(S[i][0], SC_LOG2E, m)), ex2(fmaf(S[i][1], SC_LOG2E, m)));
    float o[4][4], l[4] = {0, 0, 0, 0};
    const uint32_t ONE = 0x3f803f80u;
    mma16_top(l, ONE, ONE, P[0], P[1]);
#pragma unroll
    for (int t = 0; t < 4; t++) { o[t][0] = o[t][1] = o[t][2] = o[t][3] = 0; mma16(o[t], V[0][t].x, V[0][t].y, V[0][t].z, V[0][t].w, P[0], P[1]); }
    mma16_top(l, ONE, ONE, P[2], P[3]);
#pragma unroll
    for (int t = 0; t < 4; t++) mma16(o[t], V[1][t].x, V[1][t].y, V[1][t].z, V[1][t].w, P[2], P[3]);
    if (!__all_sync(0xffffffffu, ok)) {
        mbar_wait(bar + RB_V * 8, s & 1);
        vr0 = ldsm4(k.lu + (ro + 4096 + j * 1024)); vr1 = ldsm4(k.lu + (ro + 4608 + j * 1024));
    }
    TS(6);
    vm[0] = hadd4(vm[0], vr0); vm[1] = hadd4(vm[1], vr1);
    mma8(l, ONE, ONE, P[4]);
    mma8(o[0], vm[0].x, vm[0].y, P[4]); mma8(o[1], vm[0].z, vm[0].w, P[4]); mma8(o[2], vm[1].x, vm[1].y, P[4]); mma8(o[3], vm[1].z, vm[1].w, P[4]);
    if (j == 0) sts64(k.lw + (R_IL + X * 8), __float_as_uint(rcp(l[0])), __float_as_uint(rcp(l[1])));
#pragma unroll
    for (int t = 0; t < 4; t += 2)
        asm volatile("stmatrix.sync.aligned.m8n8.x4.trans.shared.b16 [%0],{%1,%2,%3,%4};" ::"r"(k.lm + (R_O + X * 2048 + j * 1024 + t * 256)),
                     "r"(pack2(o[t][0], o[t][1])), "r"(pack2(o[t][2], o[t][3])), "r"(pack2(o[t + 1][0], o[t + 1][1])), "r"(pack2(o[t + 1][2], o[t + 1][3])) : "memory");
    bar_arrive(NB_O + X, 320);
    TS(7);
#pragma unroll
    for (int e = 0; e < 2; e++) sts128(k.lw + (ro + j * 2048 + e * 1024), u[2 * e + 1].x, u[2 * e + 1].y, u[2 * e + 1].z, u[2 * e + 1].w);
    mbar_expect1(bar + RB_QK * 8, 2048); mbar_expect1(bar + RB_V * 8, 1024);
}
template <int MT>
__device__ __forceinline__ void rec_xattn(const RecH& k, int X, int j, int s, int head, bool early, const uint4 (*V)[4], const uint4* vmm) {
    constexpr int NTL = 3 + 2 * MT;
    const uint32_t sb = k.sb, to = R_T + X * TILE + j * 2048, ro = R_REM + (X * 2 + (s & 1)) * 6144 + j * 2048;
    const uint32_t sxw = R_SX + (X * 2 + j) * 2560, sxr = R_SX + (X * 2 + (j ^ 1)) * 2560;
    float S[NTL][4];
#pragma unroll
    for (int i = 0; i < NTL; i++) S[i][0] = S[i][1] = S[i][2] = S[i][3] = 0;
#pragma unroll
    for (int e = 0; e < 2; e++) {
        const uint4 q0 = ldsm4(k.lq + (to + 16384 + e * 1024)), q1 = ldsm4((k.lq ^ 0x20) + (to + 16384 + e * 1024));
#pragma unroll
        for (int i = 0; i < NTL; i++) {
            const uint4 kk = i ? ldsm4(k.lm + (to + e * 1024 + ((i - 1) >> 1) * 4096 + ((i - 1) & 1) * 512)) : lds128(k.lw + (ro + e * 1024));
            mma16(S[i], q0.x, q0.y, q0.z, q0.w, kk.x, kk.y); mma16(S[i], q1.x, q1.y, q1.z, q1.w, kk.z, kk.w);
        }
    }
#pragma unroll
    for (int i = 0; i < NTL; i++) sts128(k.lw + (sxw + i * 512), __float_as_uint(S[i][0]), __float_as_uint(S[i][1]), __float_as_uint(S[i][2]), __float_as_uint(S[i][3]));
    SF;
    bar_sync(NB_PAIR + X, 64);
    TS(9);
    if (early) rec_load_tile(sb, X, s + 1, head, MT);
#pragma unroll
    for (int i = 0; i < NTL; i++) {
        const uint4 r = lds128(k.lw + (sxr + i * 512));
        S[i][0] += __uint_as_float(r.x); S[i][1] += __uint_as_float(r.y); S[i][2] += __uint_as_float(r.z); S[i][3] += __uint_as_float(r.w);
    }
    const int g = (k.lw >> 6) & 7, c = ((k.lw >> 4) ^ (k.lw >> 7)) & 3;
    const float NEG = -__int_as_float(0x7f800000);
    if (2 * c > g) { S[NTL - 2][0] = NEG; S[NTL - 1][2] = NEG; }
    if (2 * c + 1 > g) { S[NTL - 2][1] = NEG; S[NTL - 1][3] = NEG; }
    float m0 = fmaxf(S[0][0], S[0][1]), m1 = fmaxf(S[0][2], S[0][3]);
#pragma unroll
    for (int i = 1; i < NTL; i++) { if (i < NTL - 1) m0 = fmaxf(m0, fmaxf(S[i][0], S[i][1])); m1 = fmaxf(m1, fmaxf(S[i][2], S[i][3])); }
    m0 = fmaxf(m0, __shfl_xor_sync(0xffffffffu, m0, 1)); m1 = fmaxf(m1, __shfl_xor_sync(0xffffffffu, m1, 1));
    m0 = fmaxf(m0, __shfl_xor_sync(0xffffffffu, m0, 2)); m1 = fmaxf(m1, __shfl_xor_sync(0xffffffffu, m1, 2));
    m0 *= -SC_LOG2E; m1 *= -SC_LOG2E;
    uint32_t P[NTL][2];
#pragma unroll
    for (int i = 0; i < NTL; i++) {
        P[i][0] = i < NTL - 1 ? pack2(ex2(fmaf(S[i][0], SC_LOG2E, m0)), ex2(fmaf(S[i][1], SC_LOG2E, m0))) : 0u;
        P[i][1] = pack2(ex2(fmaf(S[i][2], SC_LOG2E, m1)), ex2(fmaf(S[i][3], SC_LOG2E, m1)));
    }
    float l[4] = {0, 0, 0, 0};
#pragma unroll
    for (int i = 0; i < NTL; i++) mma8(l, P[i][0], P[i][1], 0x3f803f80u);
    const float l0 = rcp(l[0]), l1 = rcp(l[2]);

    const uint32_t st = sb + sxr + c * 128 + g * 16;
#pragma unroll
    for (int e = 0; e < 2; e++) {
        const uint4 vm = vmm[e];
        uint32_t u[2][4];
#pragma unroll
        for (int n = 0; n < 4; n++) {
            float a[4] = {0, 0, 0, 0};
#pragma unroll
            for (int m = 0; m <= MT; m++) {
                const uint4 v = V[m][e * 2 + (n >> 1)];
                mma8(a, P[1 + 2 * m][0], P[1 + 2 * m][1], (n & 1) ? v.y : v.x); mma8(a, P[2 + 2 * m][0], P[2 + 2 * m][1], (n & 1) ? v.w : v.z);
            }
            mma8(a, P[0][0], P[0][1], n == 0 ? vm.x : n == 1 ? vm.y : n == 2 ? vm.z : vm.w);
            u[0][n] = pack2(a[0] * l0, a[1] * l0); u[1][n] = pack2(a[2] * l1, a[3] * l1);
        }
        sts128(st + e * 512, u[0][0], u[0][1], u[0][2], u[0][3]); sts128(st + e * 512 + 1024, u[1][0], u[1][1], u[1][2], u[1][3]);
    }
    TS(10);
}
__device__ __forceinline__ void rec_attn(const Params& p, uint32_t sb, int X, int j, int head, uint32_t rank) {
    const int lane = threadIdx.x & 31;
    RecH k;
    k.lw = __shfl_sync(0xffffffffu, sb + (lane ^ (lane >> 3)) * 16, lane);
    k.lm = __shfl_sync(0xffffffffu, sb + ((lane & 7) * 4 + ((lane >> 3) ^ ((lane & 7) >> 1))) * 16, lane);
    k.lq = __shfl_sync(0xffffffffu, sb + ((lane >> 3) & 1) * 512 + ((lane & 7) * 4 + ((lane >> 4) ^ ((lane & 7) >> 1))) * 16, lane);
    k.lv = __shfl_sync(0xffffffffu, sb + (lane >> 4) * 512 + ((lane & 7) * 4 + (((lane >> 3) & 1) ^ ((lane & 7) >> 1))) * 16, lane);
    k.lu = __shfl_sync(0xffffffffu, sb + ((lane & 6) * 4 + (((lane >> 3) * 2 + (lane & 1)) ^ (lane & 6))) * 16, lane);
    k.sb = sb; k.zero = p.zero;
    const uint32_t dp = mapa(sb, rank ^ 1) - sb;
    char* zp = acc_base() + (j ? X * 32768 + acc_main(rank, head * 8) : X * 1024 + acc_extra(rank, head * 8));
    mbar_expect1(sb + R_BAR + (RB_QK + X * 2 + j) * 8, 2048); mbar_expect1(sb + R_BAR + (RB_V + X * 2 + j) * 8, 1024);
    bool early = j;
#pragma unroll 1
    for (int s = 0; s < 64; s++) {
        TSET(X ? s + p.b1 : s, j == GPJ ? 1 + X : 3);
        TS(0);
        if (!early && !j) { wait_cnt_warp(cnt_ptr(C_QKV0 + X, s >> 2), 384); rec_load_tile(sb, X, s, head, rank); }
        early = !j && s < 63 && ((s & 3) != 3 || chunk_ready(X, s + 1));
        asm volatile("cp.async.bulk.wait_group.read 0;" ::: "memory");
        PROF(lane == 0 && j == 0, X * 64 + s);
        uint4 V[2][4], vm[2];
        rec_mattn(k, dp, X, j, s, BKA && !X && s >= p.b1, V, vm);
        if (s) rec_publish(X, s - 1);
        bar_sync(NB_XG + X, 320);
        TS(8);
        if (rank) rec_xattn<1>(k, X, j, s, head, early, V, vm); else rec_xattn<0>(k, X, j, s, head, early, V, vm);
        fence_async_smem();
        __syncwarp();
        asm volatile("{.reg .pred p; elect.sync _|p,0xffffffff;\n"
                     "@p cp.async.bulk.global.shared::cta.bulk_group.L2::cache_hint [%0],[%1],2048,%2;\n"
                     "@p cp.async.bulk.global.shared::cta.bulk_group [%3],[%4],%5;\n"
                     "cp.async.bulk.commit_group;}"
                     ::"l"(g_o[X] + ((s >> 2) * 64 + head * 2 + j) * 1024 + ((s & 3) * 2 + rank) * 128), "r"(sb + R_SX + (X * 2 + (j ^ 1)) * 2560),
                       "l"((X && s < 40) ? POL_LATE : POL_SOON), "l"(zp + acc_slot(s + 2)), "r"(sb + R_Z), "r"(j ? 128 : 32) : "memory");
    }
    rec_publish(X, 63);
}

__device__ __forceinline__ void rec_init(const Params& p, uint32_t sb, int head, uint32_t rank) {
    const uint32_t b = sb + R_BAR;
    const int i = threadIdx.x - 320;
    if (i >= 0 && i < RB_N) {
        mbar_init(b + i * 8, 1);
        asm volatile("fence.mbarrier_init.release.cluster;" ::: "memory");
    }
    if (i == 0) mbar_expect(b + RB_INIT * 8, 196608);
    if (i >= 0 && i < 32) sts32(sb + R_Z + i * 4, 0);
}

#define NSTGN 8
constexpr int NSTG = NSTGN, STG_B = 24576;
#define CSH 6
#define LAGH 4
#define NSBN 8
constexpr int NSB = NSBN;
constexpr int B_OUT = NSTG * STG_B  , B_UT = B_OUT, B_YT = B_UT + 8192  ,
              B_ST = 229376  , B_BAR = 231936;
static_assert(B_OUT + NSB * 4096 <= B_ST && B_ST + 2048 <= B_BAR && B_YT + 10240 <= B_ST, "smem map");
enum { BB_FULL = 0, BB_EMPTY = 8, BB_STF = 16, BB_STE = 18, BB_SF = 20  , BB_GO = 21, BB_IDLE = 22, BB_DONE = 23  , BB_N = 27 };
enum { NB_C = 11, NB_WG = 12   };

__device__ __forceinline__ void bulk_init(uint32_t sb) {
    const int i = threadIdx.x - 320;
    if (i >= 0 && i < BB_N) {
        mbar_init(sb + B_BAR + i * 8, (i >= BB_EMPTY && i < BB_EMPTY + NSTG) ? 4 : i == BB_STF ? 2 : i == BB_STE ? 8 : i >= BB_DONE ? 4 : 1);
        asm volatile("fence.mbarrier_init.release.cluster;" ::: "memory");
    }
}

struct Task { int type, layer, ch, a, b, c, blk; bool pair, dry; };
__device__ __forceinline__ Task task_of(uint32_t tk, uint32_t rank) {
    Task t;
    t.type = tk & 7; t.layer = (tk >> 3) & 1; t.a = (tk >> 8) & 255; t.b = (tk >> 16) & 255; t.c = (tk >> 24) & 127; t.dry = tk >> 31;
    t.pair = t.type <= T_OP && (t.c & 64);
    t.ch = ((tk >> 4) & 15) + (t.pair ? rank : 0);
    t.blk = t.type == T_QKV ? t.a + (t.pair ? 0 : rank * 4) : 192 + (t.pair ? (t.c >> 2) & 4 : rank * 4);
    return t;
}
__device__ __forceinline__ void bulk_producer(const Params& p, uint32_t sb, int cl, uint32_t rank) {
    int st = 0; uint32_t ph = 1;
    bool gated = false;
#define ACQ(bytes) do { mbar_wait(sb + B_BAR + (BB_EMPTY + st) * 8, ph); mbar_expect1(sb + B_BAR + (BB_FULL + st) * 8, bytes); } while (0)
#define NEXT do { if (++st == NSTG) { st = 0; ph ^= 1; } } while (0)
#pragma unroll 1
    for (int ti = 0; ti < MAXT; ti++) {
        const Task t = task_of(p.task[cl][ti], rank);
        const int layer = t.layer, ch = t.ch;
        if (t.type == T_END) break;
        if (t.type <= T_OP) {
            const bool qkv = t.type == T_QKV, first = qkv && !layer;
            const int rg = qkv ? (layer * 16 + ch) * 128 : 4096 + ((layer * 16 + ch) * 64 + t.a) * 16;
            const int nh = qkv ? 16 : 2 * t.b, row = qkv ? 0 : t.a * 64;
            const unsigned* dep = first ? g_gate : cnt_ptr(qkv ? C_CV : C_O0 + layer, ch);
            const unsigned need = first ? lds32(sb + S_GATE) : qkv ? 16 : 512;
            const uint64_t pol = qkv ? POL_N : POL_LAST;
            const CUtensorMap *tb = &p.t3[t.pair][t.blk >> 6], *ta = &p.ta[t.pair];
            const uint32_t db = sb + 8192 + (t.pair ? rank * 8192 : 0), da = sb + (t.pair ? 0 : rank * 4096);
            const int zb = (t.blk & 63) + (t.pair ? rank * 2 : 0), ya = rg + (t.pair ? 0 : rank * 8);
            const uint16_t mb = t.pair ? 3 : 1 << rank, ma = t.pair ? 1 << rank : 3;
            int h = 0;
            if (!t.dry && !(first && gated)) {
                unsigned v;
                asm volatile("ld.relaxed.gpu.global.u32 %0,[%1];" : "=r"(v) : "l"(dep) : "memory");
                if (!__all_sync(0xffffffffu, v >= need)) {
                    const int pend = min(nh, first ? 4 : NSTG), s0 = st;
#pragma unroll 1
                    for (; h < pend; h++) { ACQ(STG_B); tma3d_mc(db + st * STG_B, tb, row + h * 32, zb, sb + B_BAR + (BB_FULL + st) * 8, mb); NEXT; }
                    wait_cnt_warp(dep, need);
#pragma unroll 1
                    for (int k = 0; k < pend; k++) {
                        const int s2 = s0 + k - (s0 + k >= NSTG ? NSTG : 0);
                        tma2d_mc(da + s2 * STG_B, ta, (k & 1) * 256, ya + (k >> 1) * 16, sb + B_BAR + (BB_FULL + s2) * 8, ma, pol);
                    }
                }
                gated = true;
            }
#pragma unroll 1
            for (; h < nh; h++) {
                ACQ(STG_B);
                tma3d_mc(db + st * STG_B, tb, row + h * 32, zb, sb + B_BAR + (BB_FULL + st) * 8, mb);
                tma2d_mc(da + st * STG_B, ta, (h & 1) * 256, ya + (h >> 1) * 16, sb + B_BAR + (BB_FULL + st) * 8, ma, pol);
                NEXT;
            }
        } else if (t.type == T_CV) {
            const int q = t.a + rank, jhi = layer ? t.b : min(ch, 1), jlo = layer ? t.c : 0;
            if (jhi && !t.dry) wait_cnt_warp(cnt_ptr(C_CV, ch - (layer ? jlo : 1)), 16);
            if (!layer) {
#pragma unroll 1
                for (int i = 0; i < min(ch, 3); i++) {
                    ACQ(16384);
                    if (i && !t.dry) wait_cnt_warp(cnt_ptr(C_H, ch - (i != 1)), ch - (i != 1) >= HSPLIT ? 32 : 16);
                    bulk_g2s1(sb + st * STG_B, g_carry[i] + ((ch - (i != 1)) * 16 + q) * 1024, 16384, sb + B_BAR + (BB_FULL + st) * 8, POL_LAST);
                    NEXT;
                }
            }
#pragma unroll 1
            for (int j = jhi; j >= jlo; j--) {
                ACQ(32 * PW * 4);
                bulk_g2s1(sb + st * STG_B, g_P + (q * 16 + j) * 32 * PW, 32 * PW * 4, sb + B_BAR + (BB_FULL + st) * 8, POL_N);
                NEXT;
                if (j) {
                    ACQ(8192);
                    bulk_g2s1(sb + st * STG_B, g_u + (q * 16 + ch - j) * 512, 8192, sb + B_BAR + (BB_FULL + st) * 8, POL_N);
                    NEXT;
                }
            }
        }
    }
}

__device__ __forceinline__ void bulk_stats(const Params& p, uint32_t sb, int cl, uint32_t rank) {
    const int r0 = threadIdx.x - 288;
    int n = 0;
    bool gated = false;
    for (int ti = 0; ti < MAXT; ti++) {
        const Task t = task_of(p.task[cl][ti], rank);
        const int type = t.type, layer = t.layer, ch = t.ch;
        if (type == T_END) break;
        if (type != T_QKV) continue;
        if (!t.dry) {
            if (!gated) { wait_cnt_warp(g_gate, lds32(sb + S_GATE)); gated = true; }
            wait_cnt_warp(cnt_ptr(layer ? C_CV : C_ST, ch), 16);
        }
        const int np = p.nst[layer];
        const float n0 = 512.f / np, in0 = np * (1.f / 512.f);
        const float4* cp = (const float4*)g_cs + t.blk * 16 + r0;
        float4 cs = __ldcg(cp);
        { const float4 ct = __ldcg(cp + 3072); cs.x += ct.x; cs.y += ct.y; cs.z += ct.z; cs.w += ct.w; }
        const float4* src = (const float4*)(g_st[layer] + ch * 128) + r0;
        const float4 f = __ldcg(src);
        const float m0 = f.x * in0, m1 = f.z * in0;
        float sd0 = 0, sq0 = 0, M0 = f.y, sd1 = 0, sq1 = 0, M1 = f.w;
#pragma unroll 3
        for (int i = 1; i < np; i++) {
            const float4 v = __ldcg(src + i * 1024);
            const float d0 = v.x * in0 - m0, d1 = v.z * in0 - m1;
            sd0 += d0; sq0 += d0 * d0; M0 += v.y; sd1 += d1; sq1 += d1 * d1; M1 += v.w;
        }
        const float b0 = sd0 / np, b1 = sd1 / np;
        const float2 o0 = ln_finish(m0 + b0, (M0 + fmaxf(n0 * (sq0 - np * b0 * b0), 0.f)) * (1.f / 512.f));
        const float2 o1 = ln_finish(m1 + b1, (M1 + fmaxf(n0 * (sq1 - np * b1 * b1), 0.f)) * (1.f / 512.f));
        mbar_wait(sb + B_BAR + BB_STE * 8, (n & 1) ^ 1);
        const uint32_t ca = sb + B_ST + 1024 + (r0 >> 3) * 128 + (r0 & 1) * 64 + ((r0 >> 1) & 3) * 8;
        sts64(ca, __float_as_uint(cs.x), __float_as_uint(cs.y)); sts64(ca + 32, __float_as_uint(cs.z), __float_as_uint(cs.w));
        sts128(sb + B_ST + r0 * 16, __float_as_uint(-o0.x), __float_as_uint(1.f / o0.y), __float_as_uint(-o1.x), __float_as_uint(1.f / o1.y));
        __syncwarp();
        mbar_arrive1(sb + B_BAR + BB_STF * 8);
        n++;
    }
}

__device__ __forceinline__ uint4* qkv_dst(int layer, int ch, int w, int blk);
__device__ __forceinline__ uint4* op_dst(int layer, int ch, int slot, int w, uint32_t rank);
__device__ __forceinline__ uint64_t out_pol(int type, int layer, int ch) { return (type == T_QKV ? (!layer && ch > 1) : (layer && ch < 10)) ? POL_LATE : POL_SOON; }
__device__ __forceinline__ void bulk_release(const Params& p, uint32_t sb, int cl, uint32_t rank) {
    int nd = 0;
    for (int ti = 0; ti < MAXT; ti++) {
        const Task t = task_of(p.task[cl][ti], rank);
        const int type = t.type, layer = t.layer, ch = t.ch;
        if (type == T_END) break;
        if (type == T_FIN || (type == T_OP && ((t.c & 32) || !layer))) continue;
#pragma unroll 1
        for (int w = 0; w < 8; w++) {
            if (!(w & 3)) { mbar_wait(sb + B_BAR + (BB_DONE + (nd & 1) * 2 + (w >> 2)) * 8, (nd >> 1) & 1); fence_async_smem(); }
            const uint4* dst = type == T_QKV ? qkv_dst(layer, ch, w, t.blk) + (8 - NSB / 2) * 32 : op_dst(layer, ch, t.c & 15, w, (t.blk >> 2) & 1) + (16 - NSB) * 32;
            if (NSB && type != T_CV)
                asm volatile("{.reg .pred p; elect.sync _|p,0xffffffff; @p cp.async.bulk.global.shared::cta.bulk_group.L2::cache_hint [%0],[%1],%2,%3;\n"
                             "@p cp.async.bulk.global.shared::cta.bulk_group.L2::cache_hint [%4],[%5],%2,%3;}"
                             ::"l"(dst), "r"(sb + B_OUT + w * NSB * 512), "r"(NSB * 256), "l"(out_pol(type, layer, ch)),
                               "l"(dst + (type == T_QKV ? 1536 : NSB * 16)), "r"(sb + B_OUT + w * NSB * 512 + NSB * 256) : "memory");
        }
        nd++;
        if (elect()) {
            asm volatile("cp.async.bulk.commit_group;" ::: "memory");
            asm volatile("cp.async.bulk.wait_group 0;" ::: "memory");
            mbar_arrive(sb + B_BAR + BB_SF * 8);
            if (!t.dry) red_release(cnt_ptr(type == T_QKV ? C_QKV0 + layer : type == T_OP ? C_OP0 + layer : layer ? C_H : C_CV, ch), type == T_CV ? 1 : 2 * t.b);
            PROF(true, 3600 + ti * 4 + 3);
        }
        __syncwarp();
    }
}

__device__ __forceinline__ void stage_release(uint32_t sb, int w, int st) {
    if (!(w & 2)) mbar_arrive1_cluster(mapa(sb + B_BAR + (BB_EMPTY + st) * 8, w & 1));
}
template <bool ACC>
__device__ __forceinline__ void gemm_run(float* acc, uint32_t sb, int w, int h0, int h1, uint32_t& r0, uint32_t& r1, int& st, uint32_t& ph) {
    const uint64_t da0 = mkdesc(sb + (w >> 2) * 4096, 128, 512, 0), db0 = mkdesc(sb + 8192, 4096, 1024, 1);
    const uint32_t rel0 = mapa(sb + B_BAR + BB_EMPTY * 8, w & 1);
#pragma unroll 1
    for (int h = h0; h < h1; h++) {
        const uint64_t da = da0 + st * (STG_B >> 4), db = db0 + st * (STG_B >> 4);
        mbar_wait(sb + B_BAR + (BB_FULL + st) * 8, ph);
        if (ACC) wg_wait<1>();
        wg_fence();
        wgmma256<ACC>(acc, da, db);
        wgmma256<true>(acc, da + 16, db + 128);
        wg_commit();
        if (ACC) mbar_arrive1_cluster((w == 2 && h == LAGH - 1) ? sb + B_BAR + BB_GO * 8 : r0);
        r0 = r1;
        if (!(w & 2)) r1 = rel0 + st * 8;
        if (++st == NSTG) { st = 0; ph ^= 1; }
    }
}

__device__ __forceinline__ uint4* qkv_dst(int layer, int ch, int w, int blk) {
    return g_qkv[layer] + (size_t)((ch * 4 + (w >> 1)) * 32 + ((blk & 63) >> 1)) * 1536 + (blk >> 6) * 512 + (w & 1) * 256;
}
__device__ __forceinline__ uint4* op_dst(int layer, int ch, int slot, int w, uint32_t rank) {
    return g_pp[layer] + (size_t)(ch * MAXSPLIT + slot) * 8192 + (w * 32 + rank * 16) * 32;
}
__device__ __forceinline__ void qkv_epilogue(const float* acc, const uint4* cs, uint2 s0, uint2 s1, uint32_t sb, int w, int layer, int ch, int blk0) {
    const int lane = threadIdx.x & 31, pos = lane ^ (lane >> 3);
    uint4* dst = qkv_dst(layer, ch, w, blk0) + pos;
    const uint64_t pol = out_pol(T_QKV, layer, ch);
#pragma unroll
    for (int n = 0; n < 16; n++) {
        const int j = (n >> 3) * 4 + ((n >> 2) & 1) + (n & 1) * 2, h = (n >> 1) & 1;
        const float* a = acc + j * 16 + h * 2;
        const float mu = __uint_as_float(h ? s1.x : s0.x), r = __uint_as_float(h ? s1.y : s0.y);
        const uint4 ca = cs[2 * j], cb = cs[2 * j + 1];
        uint4 v;
        v.x = pack2(fmaf(mu, __uint_as_float(ca.x), a[0]) * r, fmaf(mu, __uint_as_float(ca.y), a[1]) * r);
        v.y = pack2(fmaf(mu, __uint_as_float(ca.z), a[4]) * r, fmaf(mu, __uint_as_float(ca.w), a[5]) * r);
        v.z = pack2(fmaf(mu, __uint_as_float(cb.x), a[8]) * r, fmaf(mu, __uint_as_float(cb.y), a[9]) * r);
        v.w = pack2(fmaf(mu, __uint_as_float(cb.z), a[12]) * r, fmaf(mu, __uint_as_float(cb.w), a[13]) * r);
        if ((j & 3) * 2 + h < 8 - NSB / 2) stg128(dst + (j >> 2) * 1536 + ((j & 3) * 2 + h) * 32, v, pol);
        else sts128(sb + B_OUT + (w * NSB + (j >> 2) * (NSB / 2) + (j & 3) * 2 + h - (8 - NSB / 2)) * 512 + pos * 16, v.x, v.y, v.z, v.w);
    }
}

template <int NB>
__device__ __forceinline__ void load_resid(uint32_t* r, int layer, int ch, int w, int cb) {
    const uint32_t* rp = (const uint32_t*)(g_xA[layer] + (ch * 8 + (cb >> 2)) * 1024 + w * 128 + (cb & 3) * 16) + (threadIdx.x & 31);
#pragma unroll
    for (int i = 0; i < NB * 4; i++) r[i] = __ldcg(rp + (i >> 1) * 32 + (i & 1) * 256);
}
template <int NB, int NS>
__device__ __forceinline__ void sum_partials(float* x, const uint32_t* r, int layer, int ch, int w, int cb, int ns, uint32_t tag) {
    const uint4* src = g_pp[layer] + (size_t)ch * MAXSPLIT * 8192 + (w * 32 + cb) * 32 + (threadIdx.x & 31);
    const int dg = ((threadIdx.x & 31) >> 2) - 2 * (threadIdx.x & 3);
    const uint32_t idm = dg == 0 ? 0x00003f80u : dg == 1 ? 0x3f800000u : 0u;
    uint4 v[NB][NS];
#pragma unroll
    for (int i = 0; i < NB * NS; i++) v[i / NS][i % NS] = make_uint4(i % NS < ns ? ~tag : tag & 1, 0, 0, 0);
    int n = 0;
    while (true) {
#pragma unroll
        for (int i = 0; i < NB * NS; i++) {
            uint4& u = v[i / NS][i % NS];
            asm volatile("{.reg .pred p; .reg .b128 t; setp.ne.u32 p,%5,0; mov.b128 t,{%0,%1,%2,%3}; @p ld.relaxed.gpu.global.L2::cache_hint.b128 t,[%4],%6; mov.b128 {%0,%1,%2,%3},t;}"
                         : "+r"(u.x), "+r"(u.y), "+r"(u.z), "+r"(u.w) : "l"(src + (i / NS) * 32 + (i % NS) * 8192), "r"((u.x ^ tag) & 1), "l"(POL_LAST) : "memory");
        }
        uint32_t bad = 0;
#pragma unroll
        for (int i = 0; i < NB * NS; i++) bad |= v[i / NS][i % NS].x ^ tag;
        if (__all_sync(0xffffffffu, !(bad & 1) || tag > 1)) break;
        if (++n > 1000000) __trap();
    }
#pragma unroll
    for (int b = 0; b < NB; b++) {
        float* y = x + b * 8;
#pragma unroll
        for (int i = 0; i < 8; i++) y[i] = 0;
#pragma unroll
        for (int s = 0; s < NS; s++) { mma8(y, v[b][s].x, v[b][s].y, idm); mma8(y + 4, v[b][s].z, v[b][s].w, idm); }
#pragma unroll
        for (int i = 0; i < 4; i++) { y[2 * i] = rbf(rbf(y[2 * i]) + blo(r[b * 4 + i])); y[2 * i + 1] = rbf(rbf(y[2 * i + 1]) + bhi(r[b * 4 + i])); }
    }
}

__device__ __forceinline__ float4 row_stats32(const float* x) {
    float a = (x[0] + x[1]) + (x[4] + x[5]) + (x[8] + x[9]) + (x[12] + x[13]);
    float b = (x[2] + x[3]) + (x[6] + x[7]) + (x[10] + x[11]) + (x[14] + x[15]);
    a += __shfl_xor_sync(0xffffffffu, a, 1); b += __shfl_xor_sync(0xffffffffu, b, 1);
    a += __shfl_xor_sync(0xffffffffu, a, 2); b += __shfl_xor_sync(0xffffffffu, b, 2);
    const float ma = a * (1.f / 32.f), mb = b * (1.f / 32.f);
    float qa = 0, qb = 0;
#pragma unroll
    for (int i = 0; i < 4; i++) {
        float d0 = x[4 * i] - ma, d1 = x[4 * i + 1] - ma, d2 = x[4 * i + 2] - mb, d3 = x[4 * i + 3] - mb;
        qa += d0 * d0 + d1 * d1; qb += d2 * d2 + d3 * d3;
    }
    qa += __shfl_xor_sync(0xffffffffu, qa, 1); qb += __shfl_xor_sync(0xffffffffu, qb, 1);
    qa += __shfl_xor_sync(0xffffffffu, qa, 2); qb += __shfl_xor_sync(0xffffffffu, qb, 2);
    return make_float4(a, qa, b, qb);
}

__device__ __forceinline__ void conv_stage(float* Y, uint32_t pbase, uint32_t ubase) {
    const int lane = threadIdx.x & 31, w = threadIdx.x >> 5, g = lane >> 2, c = lane & 3;
#pragma unroll
    for (int cp = 0; cp < 2; cp++) {
        const int chl = w * 4 + cp * 2 + (lane >> 4);
        const uint4 b = ldsm4(ubase + chl * 256 + ((lane >> 3) & 1) * 128 + (((lane & 7) ^ (chl & 7)) << 4));
#pragma unroll
        for (int h = 0; h < 2; h++) {
            const uint32_t pa = pbase + ((w * 4 + cp * 2 + h) * PW + 16 + g - 2 * c) * 4;
            uint32_t lo = lds32(pa - 32);
#pragma unroll
            for (int d = 0; d < 8; d++) {
                const uint32_t a0 = lds32(pa + d * 64), a1 = lds32(pa + d * 64 + 32);
                mma16(Y + ((cp * 2 + h) * 8 + d) * 4, a0, a1, lo, a0, h ? b.z : b.x, h ? b.w : b.y);
                lo = a1;
            }
        }
    }
}

__device__ __forceinline__ void conv_combine(const float* y8, float* cur, float* nxt) {
    const int lane = threadIdx.x & 31, c = lane & 3;
    cur[0] = y8[0]; cur[1] = y8[1] + y8[4]; cur[2] = y8[2]; cur[3] = y8[3] + y8[6];
    nxt[0] = y8[29]; nxt[1] = 0.f; nxt[2] = y8[31]; nxt[3] = 0.f;
#pragma unroll
    for (int e = 1; e < 4; e++) {
        const int src = (lane & ~3) | ((c - e) & 3);
        const float v0 = __shfl_sync(0xffffffffu, y8[8 * e] + y8[8 * e - 3], src), v1 = __shfl_sync(0xffffffffu, y8[8 * e + 1] + y8[8 * e + 4], src);
        const float v2 = __shfl_sync(0xffffffffu, y8[8 * e + 2] + y8[8 * e - 1], src), v3 = __shfl_sync(0xffffffffu, y8[8 * e + 3] + y8[8 * e + 6], src);
        if (c >= e) { cur[0] += v0; cur[1] += v1; cur[2] += v2; cur[3] += v3; }
        else { nxt[0] += v0; nxt[1] += v1; nxt[2] += v2; nxt[3] += v3; }
    }
}

__device__ __forceinline__ void conv_task(const Params& p, float* Y, uint32_t sb, int w, int ch, int q, bool hist, int hhi, int hlo, bool dry, int& st, uint32_t& ph, int nd) {
    const int tid = threadIdx.x, lane = tid & 31, g = lane >> 2, c = lane & 3;
    const int jhi = hist ? hhi : min(ch, 1), jlo = hist ? hlo : 1;
    uint32_t dk[4];
    float x[16];
#pragma unroll
    for (int i = 0; i < 16; i++) x[i] = 0;
    if (!hist) {
        uint32_t rs[8];
        PROF(tid == 128, 2048 + ch * 8);
        load_resid<2>(rs, 0, ch, w, 2 * q);
        sum_partials<2, OPS1>(x, rs, 0, ch, w, 2 * q, OPS1, dry ? 2 : lds32(sb + S_TAG));
        const float4 s = row_stats32(x);
        float2* dst = g_st2 + (ch * 16 + q) * 128 + w * 16 + g + c * 8;
        asm volatile("{.reg .pred p; setp.ne.u32 p,%2,0; @p st.relaxed.gpu.global.b64 [%0],%1;}" ::"l"(dst),
                     "l"(((uint64_t)__float_as_uint(c ? s.w : s.y) << 32) | __float_as_uint(c ? s.z : s.x)), "r"((uint32_t)(c < 2 && !dry)) : "memory");
        PROF(tid == 128, 2048 + ch * 8 + 1);
    }
#pragma unroll
    for (int i = 0; i < 128; i++) Y[i] = 0;
    if (!hist) {
#pragma unroll
        for (int i = 0; i < 4; i++) dk[i] = __ldg((const uint32_t*)(p.Dskip + q * 32 + i * 8 + 2 * c));
#pragma unroll 1
        for (int i = 0; i < 3 && i < ch; i++) {
            mbar_wait(sb + B_BAR + (BB_FULL + st) * 8, ph);
#pragma unroll
            for (int k = 0; k < 4; k++) {
                const uint4 cr = lds128(sb + st * STG_B + k * 4096 + tid * 16);
                Y[k * 32] += __uint_as_float(cr.x); Y[k * 32 + 1] += __uint_as_float(cr.y); Y[k * 32 + 2] += __uint_as_float(cr.z); Y[k * 32 + 3] += __uint_as_float(cr.w);
            }
            bar_sync(NB_WG + (w >> 2), 128);
            stage_release(sb, w, st);
            if (++st == NSTG) { st = 0; ph ^= 1; }
        }
    }
    for (int j = jhi; j >= jlo; j--) {
        const int s0 = st;
        mbar_wait(sb + B_BAR + (BB_FULL + st) * 8, ph);
        if (++st == NSTG) { st = 0; ph ^= 1; }
        mbar_wait(sb + B_BAR + (BB_FULL + st) * 8, ph);
        conv_stage(Y, sb + s0 * STG_B, sb + st * STG_B);
        bar_sync(NB_WG + (w >> 2), 128);
        stage_release(sb, w, s0); stage_release(sb, w, st);
        if (++st == NSTG) { st = 0; ph ^= 1; }
    }
    mbar_wait(sb + B_BAR + BB_SF * 8, (nd & 1) ^ 1);
    if (hist) {
        if (jhi < ch) wait_cnt_warp(cnt_ptr(C_H, ch), 16);
#pragma unroll
        for (int k = 0; k < 4; k++) {
            float4* d1 = g_carry[1] + ((ch * 16 + q) * 4 + k) * 256 + tid;
            float4* d2 = g_carry[2] + ((ch * 16 + q) * 4 + k) * 256 + tid;
            float4 o1 = make_float4(0, 0, 0, 0), o2 = o1;
            if (jhi < ch) { o1 = __ldcg(d1); o2 = __ldcg(d2); }
            float cur[4], nxt[4];
            conv_combine(Y + k * 32, cur, nxt);
            *d1 = make_float4(cur[0] + o1.x, cur[1] + o1.y, cur[2] + o1.z, cur[3] + o1.w);
            *d2 = make_float4(nxt[0] + o2.x, nxt[1] + o2.y, nxt[2] + o2.z, nxt[3] + o2.w);
        }
        return;
    }
    PROF(tid == 128, 2048 + ch * 8 + 7);
    float2 ln0, ln1;
    {
        const float2* src = g_st2 + (ch * 16 + (lane >> 4) * 8) * 128 + w * 16 + (lane & 15);
        uint64_t v[8];
        int n = 0;
        while (true) {
            bool bad = false;
#pragma unroll
            for (int i = 0; i < 8; i++) asm volatile("ld.relaxed.gpu.global.b64 %0,[%1];" : "=l"(v[i]) : "l"(src + i * 128) : "memory");
#pragma unroll
            for (int i = 0; i < 8; i++) bad = bad || (uint32_t)(v[i] >> 32) == 0xffffffffu;
            if (!__any_sync(0xffffffffu, bad && !dry)) break;
            if (++n > 2000000) __trap();
        }
        float sm = 0;
#pragma unroll
        for (int i = 0; i < 8; i++) sm += __uint_as_float((uint32_t)v[i]);
        sm += __shfl_xor_sync(0xffffffffu, sm, 16);
        const float mean = sm * (1.f / 512.f);
        float M2 = 0;
#pragma unroll
        for (int i = 0; i < 8; i++) { const float d = __uint_as_float((uint32_t)v[i]) * (1.f / 32.f) - mean; M2 += __uint_as_float((uint32_t)(v[i] >> 32)) + 32.f * d * d; }
        M2 += __shfl_xor_sync(0xffffffffu, M2, 16);
        const float2 o = ln_finish(mean, M2 * (1.f / 512.f));
        ln0.x = __shfl_sync(0xffffffffu, o.x, g); ln0.y = __shfl_sync(0xffffffffu, o.y, g);
        ln1.x = __shfl_sync(0xffffffffu, o.x, g + 8); ln1.y = __shfl_sync(0xffffffffu, o.y, g + 8);
    }
    PROF(tid == 128, 2048 + ch * 8 + 2);
    uint32_t u[8];
#pragma unroll
    for (int i = 0; i < 8; i++) {
        const float2 l = (i & 1) ? ln1 : ln0;
        u[i] = pack2(__fdividef(rbf(x[2 * i] - l.x), l.y), __fdividef(rbf(x[2 * i + 1] - l.x), l.y));
        const int chl = (i >> 1) * 8 + g;
        sts32(sb + B_UT + chl * 256 + (i & 1) * 128 + ((w ^ g) << 4) + c * 4, movm(u[i]));
    }
    fence_async_smem();
    bar_sync(NB_C, 256);
    if (w == 0 && ch < 15 && elect()) {
        asm volatile("cp.async.bulk.global.shared::cta.bulk_group [%0],[%1],%2;" ::"l"(g_u + (q * 16 + ch) * 512), "r"(sb + B_UT), "r"(8192) : "memory");
        asm volatile("cp.async.bulk.commit_group;" ::: "memory");
    }
    mbar_wait(sb + B_BAR + (BB_FULL + st) * 8, ph);
    PROF(tid == 128, 2048 + ch * 8 + 3);
    conv_stage(Y, sb + st * STG_B, sb + B_UT);
    uint32_t yp[4][2];
    {
        float y[4][4];
#pragma unroll
        for (int k = 0; k < 4; k++) {
            float nxt[4];
            conv_combine(Y + k * 32, y[k], nxt);
            g_carry[0][((ch * 16 + q) * 4 + k) * 256 + tid] = make_float4(nxt[0], nxt[1], nxt[2], nxt[3]);
        }
#pragma unroll
        for (int i = 0; i < 4; i++) { yp[i][0] = pack2(y[0][i], y[1][i]); yp[i][1] = pack2(y[2][i], y[3][i]); }
    }
#pragma unroll
    for (int i = 0; i < 4; i++) sts64(sb + B_YT + (16 * (2 * c + (i & 1)) + g + (i >> 1) * 8) * 80 + w * 8, yp[i][0], yp[i][1]);
    bar_sync(NB_C, 256);
    stage_release(sb, w, st);
    if (++st == NSTG) { st = 0; ph ^= 1; }
    PROF(tid == 128, 2048 + ch * 8 + 4);
    uint32_t xo[8];
    uint32_t* dA = (uint32_t*)(g_xA[1] + (ch * 8 + (q >> 1)) * 1024 + (w * 2) * 64 + (q & 1) * 32) + lane;
#pragma unroll
    for (int i = 0; i < 8; i++) {
        const int col = (i >> 1) * 8 + 2 * c;
        const uint32_t yv = lds32(sb + B_YT + (w * 16 + g + (i & 1) * 8) * 80 + col * 2);
        const uint32_t dv = dk[i >> 1];
        x[2 * i] = rbf(x[2 * i] + rbf(blo(yv) + rbf(blo(u[i]) * blo(dv))));
        x[2 * i + 1] = rbf(x[2 * i + 1] + rbf(bhi(yv) + rbf(bhi(u[i]) * bhi(dv))));
        xo[i] = pack2(x[2 * i], x[2 * i + 1]);
        dA[(i >> 1) * 32 + (i & 1) * 256] = xo[i];
    }
    {
        const float4 s = row_stats32(x);
        float2* dst = g_st[1] + q * 2048 + ch * 128 + w * 16 + g;
        if (c == 0) dst[0] = make_float2(s.x, s.y);
        if (c == 1) dst[8] = make_float2(s.z, s.w);
        __syncwarp();
    }
    PROF(tid == 128, 2048 + ch * 8 + 5);
    if (w == 0) asm volatile("cp.async.bulk.wait_group 0;" ::: "memory");
    PROF(tid == 128, 2048 + ch * 8 + 6);
}

__device__ __forceinline__ void out_store(const Params& p, const float* x, int ch, int cb) {
    const int lane = threadIdx.x & 31, w = threadIdx.x >> 5, g = lane >> 2, c = lane & 3;
#pragma unroll
    for (int h = 0; h < 2; h++) {
        const float* y = x + h * 2;
        uint32_t v0 = pack2(y[0], y[1]), v1 = pack2(y[4], y[5]), v2 = pack2(y[8], y[9]), v3 = pack2(y[12], y[13]);
        uint32_t t0 = (c & 1) ? v0 : v1, t1 = (c & 1) ? v2 : v3;
        t0 = __shfl_xor_sync(0xffffffffu, t0, 1); t1 = __shfl_xor_sync(0xffffffffu, t1, 1);
        if (c & 1) { v0 = t0; v2 = t1; } else { v1 = t0; v3 = t1; }
        t0 = (c & 2) ? v0 : v2; t1 = (c & 2) ? v1 : v3;
        t0 = __shfl_xor_sync(0xffffffffu, t0, 2); t1 = __shfl_xor_sync(0xffffffffu, t1, 2);
        if (c & 2) { v0 = t0; v1 = t1; } else { v2 = t0; v3 = t1; }
        stg128((uint4*)(p.out + (size_t)(ch * 128 + w * 16 + g + h * 8) * 512 + cb * 16 + c * 8), make_uint4(v0, v1, v2, v3), POL_LATE);
    }
}
__device__ __forceinline__ void fin_task(const Params& p, int ch, int cb0, int ncb, int ns, bool dry) {
    const int w = threadIdx.x >> 5;
    uint32_t rs[8];
    wait_cnt_warp(cnt_ptr(C_CV, ch), dry ? 0 : 16);
    load_resid<2>(rs, 1, ch, w, cb0);
    wait_cnt_warp(cnt_ptr(C_OP1, ch), dry ? 0 : 256);
    for (int cb = cb0; cb < cb0 + ncb; cb += 2) {
        float x[16];
        if (cb != cb0) load_resid<2>(rs, 1, ch, w, cb);
        sum_partials<2, 16>(x, rs, 1, ch, w, cb, ns, 2);
        out_store(p, x, ch, cb);
    }
}

__device__ __forceinline__ void bulk_consumer(const Params& p, uint32_t sb, int cl, uint32_t rank, int w) {
    int st = 0; uint32_t ph = 0; int nq = 0, nd = 0, ng = 0;
    for (int ti = 0; ti < MAXT; ti++) {
        const Task t = task_of(p.task[cl][ti], rank);
        const int type = t.type, layer = t.layer, ch = t.ch;
        if (type == T_END) break;
        bool staged = type != T_FIN;
        PROF(threadIdx.x == 0, 3600 + ti * 4);
        if (type <= T_OP) {
            const int lane = threadIdx.x & 31, nh = type == T_QKV ? 16 : 2 * t.b;
            float acc[128];
            uint32_t r0 = sb + B_BAR + BB_IDLE * 8, r1 = r0;
            CPROF(0);
            if (w >> 2) mbar_wait(sb + B_BAR + BB_GO * 8, ng & 1);
            ng++;
            CPROF(1);
            gemm_run<false>(acc, sb, w, 0, 1, r0, r1, st, ph);
            gemm_run<true>(acc, sb, w, 1, nh - CSH, r0, r1, st, ph);
            CPROF(2);
            uint4 cs[16]; uint2 s0, s1;
#pragma unroll
            for (int i = 0; i < 16; i++) cs[i] = make_uint4(0, 0, 0, 0);
            s0 = s1 = make_uint2(0, 0);
            if (type == T_QKV) {
                mbar_wait(sb + B_BAR + BB_STF * 8, nq & 1);
                s0 = lds64(sb + B_ST + (w * 16 + (lane >> 2)) * 8); s1 = lds64(sb + B_ST + (w * 16 + (lane >> 2) + 8) * 8);
#pragma unroll
                for (int i = 0; i < 16; i++) cs[i] = lds128(sb + B_ST + 1024 + (i >> 1) * 128 + (lane & 3) * 32 + (i & 1) * 16);
            }
            CPROF(3);
            gemm_run<true>(acc, sb, w, nh - CSH, nh, r0, r1, st, ph);
            CPROF(4);
            if (!(t.c & 32)) mbar_wait(sb + B_BAR + BB_SF * 8, (nd & 1) ^ 1);
            wg_wait<1>();
            mbar_arrive1_cluster(r0);
            wg_wait<0>();
            mbar_arrive1_cluster(r1);
            CPROF(5);
            PROF(threadIdx.x == 128, 3600 + ti * 4 + 1);
            if (type == T_QKV) {
                mbar_arrive1(sb + B_BAR + BB_STE * 8);
                qkv_epilogue(acc, cs, s0, s1, sb, w, layer, ch, t.blk);
                nq++;
            } else if (t.c & 32) {
                staged = false;
#pragma unroll
                for (int j = 0; j < 16; j += 4) {
                    uint32_t rs[16];
                    load_resid<4>(rs, 1, ch, w, (t.blk & 4) * 4 + j);
#pragma unroll
                    for (int i = 0; i < 16; i++) { float* y = acc + j * 8 + 2 * i; y[0] = rbf(y[0]) + blo(rs[i]); y[1] = rbf(y[1]) + bhi(rs[i]); }
                    out_store(p, acc + j * 8, ch, (t.blk & 4) * 4 + j); out_store(p, acc + j * 8 + 16, ch, (t.blk & 4) * 4 + j + 2);
                }
            } else if (!layer) {
                staged = false;
                uint4* dst = op_dst(0, ch, t.c & 15, w, (t.blk >> 2) & 1) + lane;
                const uint32_t tag = lds32(sb + S_TAG);
#pragma unroll
                for (int j = 0; j < 16; j++)
                    asm volatile("{.reg .b128 t; mov.b128 t,{%1,%2,%3,%4}; st.relaxed.gpu.global.L2::cache_hint.b128 [%0],t,%5;}" ::"l"(dst + j * 32), "r"((pack2(acc[j * 8], acc[j * 8 + 1]) & ~1u) | tag),
                                 "r"(pack2(acc[j * 8 + 2], acc[j * 8 + 3])), "r"(pack2(acc[j * 8 + 4], acc[j * 8 + 5])), "r"(pack2(acc[j * 8 + 6], acc[j * 8 + 7])), "l"(POL_SOON) : "memory");
            } else {
                uint4* dst = op_dst(layer, ch, t.c & 15, w, (t.blk >> 2) & 1) + lane;
#pragma unroll
                for (int n = 0; n < 16; n++) {
                    const int j = (n >> 1) + (n & 1) * 8;
                    const uint4 v = make_uint4(pack2(acc[j * 8], acc[j * 8 + 1]), pack2(acc[j * 8 + 2], acc[j * 8 + 3]), pack2(acc[j * 8 + 4], acc[j * 8 + 5]), pack2(acc[j * 8 + 6], acc[j * 8 + 7]));
                    if (j < 16 - NSB) stg128(dst + j * 32, v, out_pol(T_OP, layer, ch)); else sts128(sb + B_OUT + (w * NSB + j - (16 - NSB)) * 512 + lane * 16, v.x, v.y, v.z, v.w);
                }
            }
        } else if (type == T_CV) {
            float acc[128];
            conv_task(p, acc, sb, w, ch, t.a + rank, layer, t.b, t.c, t.dry, st, ph, nd);
        } else {
            fin_task(p, ch, t.a + rank * t.c, t.c, t.b, t.dry);
        }
        if (staged) {
            __syncwarp();
            mbar_arrive1(sb + B_BAR + (BB_DONE + (nd & 1) * 2 + (w >> 2)) * 8);
            nd++;
        }
        CPROF(6);
        PROF(threadIdx.x == 128, 3600 + ti * 4 + 2);
        __syncwarp();
    }
}

constexpr int P_Y = 131072  , P_PRM = P_Y  , P_K6 = P_PRM + 8192  ,
              P_P = P_Y + 40960  , P_U = P_P + 33280  , P_END = P_U + 17408, P_X = 98304  ;
static_assert(P_END <= B_BAR && P_END <= R_BAR, "prologue scratch");
#define KGUN 2
constexpr int KGU = KGUN;
__device__ __forceinline__ void csq(float& r, float& i) { const float t = r * i; r = fmaf(r, r, -(i * i)); i = t + t; }
__device__ __forceinline__ void cpow(float ar, float ph, float p, float& r, float& i) {
    const float e = ex2(ar * p);
    const float u = ph * p, n = fabsf(u) < 4194304.f ? (u + 12582912.f) - 12582912.f : u;
    const float t = (u - n) * 6.283185307179586f;
    r = e * __cosf(t); i = e * __sinf(t);
}
__device__ __forceinline__ void mma_tf32(float* c, float a0, float a1, float a2, float a3, float b0, float b1) {
    asm volatile("mma.sync.aligned.m16n8k8.row.col.f32.tf32.tf32.f32 {%0,%1,%2,%3},{%4,%5,%6,%7},{%8,%9},{%0,%1,%2,%3};"
                 : "+f"(c[0]), "+f"(c[1]), "+f"(c[2]), "+f"(c[3])
                 : "r"(__float_as_uint(a0)), "r"(__float_as_uint(a1)), "r"(__float_as_uint(a2)), "r"(__float_as_uint(a3)), "r"(__float_as_uint(b0)), "r"(__float_as_uint(b1)));
}

struct ProRegs { uint32_t v[2][4], ldt[2]; };
__device__ __forceinline__ void prologue_load(const ProArgs& a, int b, ProRegs& pr) {
    const int w = threadIdx.x >> 5;
#pragma unroll
    for (int i = 0; i < 2; i++) {
        const int gi = b * 512 + (w & 3) * 128 + ((w >> 2) & 1) * 64 + i * 32 + (threadIdx.x & 31);
        pr.ldt[i] = __ldg((const uint16_t*)a.ldt + b * 4 + (w & 3));
        pr.v[i][0] = __ldg((const uint16_t*)a.lAr + gi); pr.v[i][1] = __ldg((const uint16_t*)a.Ai + gi);
        pr.v[i][2] = __ldg((const uint16_t*)a.Cr + gi); pr.v[i][3] = __ldg((const uint16_t*)a.Ci + gi);
    }
}
__device__ __forceinline__ void prologue(const ProArgs& a, uint32_t sb, int b, int w, const ProRegs& pr) {
    const int tid = threadIdx.x, lane = tid & 31, g = lane >> 2, c = lane & 3;
    const int d0 = b * 4;
    if (w >= 8) {
        const int t2 = tid - 256;
        if (w < 10) {
            const int row = b * 16 + (w - 8) * 8 + g;
            const float2 r = row_stats512((const uint4*)(a.x + (size_t)row * 512) + c, 8, 4);
            const float2 l = ln_finish(r.x * (1.f / 512.f), r.y * (1.f / 512.f));
            if (c == (g >> 1)) asm volatile("st.relaxed.gpu.global.u32 [%0],%1;" ::"l"(g_ln0 + row), "r"(pack2(l.x, l.y)) : "memory");
        }
        PROF(t2 == 0, 3516);
        const int gi = b * 128 + t2;
        if (t2 < 32) acc_init(a.mem0, b * 32 + t2);
        ((uint4*)g_st2)[gi] = make_uint4(~0u, ~0u, ~0u, ~0u);
        if (gi < 9 * 16 * 32) g_cnt[gi] = 0;
        bar_sync(6, 384);
        {
            const int u = b * 3 + (w - 8), blk = u >> 1;
            const uint4* W = w < 11 ? (const uint4*)((blk < 64 ? a.Wq : blk < 128 ? a.Wk : a.Wv) + (size_t)((u & 1) * 256 + c) * 4096 + (blk & 63) * 64) + g
                                    : (const uint4*)a.Wo + (size_t)b * 2048 + lane;
            const int st = w < 11 ? 2048 : 32;
            const uint32_t one = (g & 1) ? 0x3f800000u : 0x00003f80u, selA = (g & 2) ? 0u : one, selB = (g & 2) ? one : 0u;
            float s0[4] = {0, 0, 0, 0}, s1[4] = {0, 0, 0, 0};
#pragma unroll 1
            for (int r = 0; r < 8; r++) {
                uint4 v[8];
#pragma unroll
                for (int i = 0; i < 8; i++) v[i] = __ldg(W + (size_t)(r * 8 + i) * st);
#pragma unroll
                for (int i = 0; i < 8; i++) mma16((i & 1) ? s1 : s0, v[i].x, v[i].y, v[i].z, v[i].w, selA, selB);
            }
            if (c < 2) *(float4*)(g_cs + (w < 11 ? (u & 1) * 12288 + blk * 64 : 24576) + g * 8 + c * 4) = make_float4(s0[0] + s1[0], s0[1] + s1[1], s0[2] + s1[2], s0[3] + s1[3]);
        }
        PROF(t2 == 0, 3517);
        return;
    }
#pragma unroll
    for (int i = 0; i < 2; i++) {
        const float dt = rbf(expf(blo(pr.ldt[i])));
        const float ar = -rbf(expf(blo(pr.v[i][0]))) * dt, ai = blo(pr.v[i][1]) * dt;
        sts128(sb + P_PRM + (w * 64 + i * 32 + lane) * 16, __float_as_uint(ar * 1.4426950408889634f), __float_as_uint(ai * 0.15915494309189535f),
               __float_as_uint(2.f * (blo(pr.v[i][2]) * dt)), __float_as_uint(2.f * (blo(pr.v[i][3]) * dt)));
    }
    if (tid < 64) sts128(sb + P_U + (tid >> 3) * 2176 + (tid & 7) * 16, 0, 0, 0, 0);
    bar_arrive(6, 384);
    __syncwarp();
    PROF(tid == 0, 3510);
    const int ch = w & 3, hf = w >> 2;
    {
        float k0[4] = {0, 0, 0, 0}, k1[4] = {0, 0, 0, 0}, k2[4] = {0, 0, 0, 0}, k3[4] = {0, 0, 0, 0}, k4[4] = {0, 0, 0, 0}, kl = 0;
#pragma unroll KGU
        for (int j = 0; j < 16; j++) {
            const uint4 q = lds128(sb + P_PRM + (w * 64 + j * 4 + c) * 16);
            const float cr = __uint_as_float(q.z), ci = __uint_as_float(q.w);
            float wr[4], wi[4], vr[4], vi[4];
            cpow(__uint_as_float(q.x), __uint_as_float(q.y), (float)g, wr[0], wi[0]);
            cpow(__uint_as_float(q.x), __uint_as_float(q.y), (float)(g + 8), vr[0], vi[0]);
#pragma unroll
            for (int i = 1; i < 4; i++) { wr[i] = wr[i - 1]; wi[i] = wi[i - 1]; csq(wr[i], wi[i]); vr[i] = vr[i - 1]; vi[i] = vi[i - 1]; csq(vr[i], vi[i]); }
            float hr = wr[3], hi = wi[3];
            csq(hr, hi);
            mma_tf32(k0, wr[0], vr[0], wi[0], vi[0], cr * hr - ci * hi, -(cr * hi + ci * hr));
            hr = vr[3]; hi = vi[3]; csq(hr, hi);
            mma_tf32(k1, wr[0], vr[0], wi[0], vi[0], cr * hr - ci * hi, -(cr * hi + ci * hr));
            csq(hr, hi);
            mma_tf32(k2, wr[1], vr[1], wi[1], vi[1], cr * hr - ci * hi, -(cr * hi + ci * hr));
            csq(hr, hi);
            mma_tf32(k3, wr[2], vr[2], wi[2], vi[2], cr * hr - ci * hi, -(cr * hi + ci * hr));
            csq(hr, hi);
            mma_tf32(k4, wr[3], vr[3], wi[3], vi[3], cr * hr - ci * hi, -(cr * hi + ci * hr));
            csq(hr, hi);
            kl += cr * hr - ci * hi;
        }
        kl += __shfl_xor_sync(0xffffffffu, kl, 1); kl += __shfl_xor_sync(0xffffffffu, kl, 2);
        const uint32_t o = sb + P_K6 + (ch * 656 + c * 32 + g) * 4, ol = sb + P_K6 + (ch * 656 + 640) * 4;
#define KST(k, base) sts32(o + (base) * 4, __float_as_uint(k[0])); sts32(o + (base) * 4 + 64, __float_as_uint(k[1])); \
                     sts32(o + (base) * 4 + 32, __float_as_uint(k[2])); sts32(o + (base) * 4 + 96, __float_as_uint(k[3]))
#define KAD(k, base) k[0] += __uint_as_float(lds32(o + (base) * 4)); k[1] += __uint_as_float(lds32(o + (base) * 4 + 64)); \
                     k[2] += __uint_as_float(lds32(o + (base) * 4 + 32)); k[3] += __uint_as_float(lds32(o + (base) * 4 + 96))
        if (hf == 0) {
            bar_sync(2 + ch, 64);
            KAD(k0, 0); KAD(k1, 128); KAD(k2, 256); KAD(k3, 384); KAD(k4, 512);
            kl += __uint_as_float(lds32(ol));
            __syncwarp();
        }
        KST(k0, 0); KST(k1, 128); KST(k2, 256); KST(k3, 384); KST(k4, 512);
        if (lane == 0) sts32(ol, __float_as_uint(kl));
        if (hf == 1) { __syncwarp(); bar_arrive(2 + ch, 64); }
    }
    PROF(tid == 0, 3511);
    {
        uint4 l0, l1;
        int n = 0;
        while (true) {
            l0 = ld_rlx128((const uint4*)g_ln0 + tid * 2); l1 = ld_rlx128((const uint4*)g_ln0 + tid * 2 + 1);
            if (__all_sync(0xffffffffu, l0.x && l0.y && l0.z && l0.w && l1.x && l1.y && l1.z && l1.w)) break;
            if (++n > 2000000) __trap();
        }
        sts128(sb + P_P + tid * 32, l0.x, l0.y, l0.z, l0.w); sts128(sb + P_P + tid * 32 + 16, l1.x, l1.y, l1.z, l1.w);
        bar_sync(8, 384);
        mbar_wait(sb + S_XBAR, 0);
        __syncwarp();
#pragma unroll 2
        for (int i = 0; i < 8; i++) {
            const int t = w * 256 + i * 32 + lane;
            const uint32_t ln = lds32(sb + P_P + t * 4);
            const uint2 x = lds64(sb + P_X + t * 16 + (b & 1) * 8);
            const float m = blo(ln), rs = rcp(bhi(ln));
            const uint32_t u0 = pack2(rbf(blo(x.x) - m) * rs, rbf(bhi(x.x) - m) * rs), u1 = pack2(rbf(blo(x.y) - m) * rs, rbf(bhi(x.y) - m) * rs);
            sts128(sb + P_X + t * 16, x.x, x.y, u0, u1);
            const uint32_t o = sb + P_U + ((t >> 3) & 1) * 2176 + ((t >> 4) + 8) * 16 + (t & 7) * 2;
            asm volatile("st.shared.u16 [%0],%1;" ::"r"(o), "h"((uint16_t)u0) : "memory");
            asm volatile("st.shared.u16 [%0],%1;" ::"r"(o + 4352), "h"((uint16_t)(u0 >> 16)) : "memory");
            asm volatile("st.shared.u16 [%0],%1;" ::"r"(o + 8704), "h"((uint16_t)u1) : "memory");
            asm volatile("st.shared.u16 [%0],%1;" ::"r"(o + 13056), "h"((uint16_t)(u1 >> 16)) : "memory");
        }
    }
    bar_sync(1, 256);
    PROF(tid == 0, 3512);
    if (tid < 64) sts32(sb + P_P + ((tid >> 4) * 2080 + (tid & 15)) * 4, 0);
#pragma unroll 1
    for (int x = tid; x < 2048; x += 512) {
        uint32_t pw[2][4];
#pragma unroll
        for (int h = 0; h < 2; h++) {
            const int y = x + h * 256;
            const int i0 = y <= 256 ? y : 256 + (int)((pack2((float)y, 0.f) & 0xffff) - 0x4380);
            const int i1 = y <= 256 ? max(y - 1, 0) : 256 + (int)((pack2((float)(y - 1), 0.f) & 0xffff) - 0x4380);
#pragma unroll
            for (int k = 0; k < 4; k++) {
                const float lo = __uint_as_float(lds32(sb + P_K6 + k * 2624 + i0 * 4)), hi = __uint_as_float(lds32(sb + P_K6 + k * 2624 + i1 * 4));
                pw[h][k] = pack2(lo, y ? hi : 0.f);
            }
        }
#pragma unroll
        for (int h = 0; h < 2; h++)
#pragma unroll
            for (int k = 0; k < 4; k++) sts32(sb + P_P + (k * 2080 + x + h * 256 + 16) * 4, pw[h][k]);
    }
    fence_async_smem();
    bar_sync(1, 256);
    if (lane < 8) {
        const int k = w >> 1, j = (w & 1) * 8 + lane, d = d0 + k;
        asm volatile("cp.async.bulk.global.shared::cta.bulk_group [%0],[%1],%2;" ::"l"(g_P + (((d >> 5) * 16 + j) * 32 + (d & 31)) * PW),
                     "r"(sb + P_P + (k * 2080 + j * 128) * 4), "r"(PW * 4) : "memory");
        asm volatile("cp.async.bulk.commit_group;" ::: "memory");
    }
    __syncwarp();
    PROF(tid == 0, 3513);
    {
        float acc[16][4];
#pragma unroll
        for (int j = 0; j < 16; j++) acc[j][0] = acc[j][1] = acc[j][2] = acc[j][3] = 0;
#pragma unroll 1
        for (int e = hf * 4; e < hf * 4 + 4; e++) {
            uint32_t B[16][2];
            const uint32_t ua = sb + P_U + ch * 4352 + ((lane >> 3) & 1) * 2176 + (8 + (lane >> 4) * 8 + (lane & 7) - e) * 16;
#pragma unroll
            for (int j = 0; j < 8; j++) { const uint4 v = ldsm4(ua + j * 256); B[2 * j][0] = v.x; B[2 * j][1] = v.y; B[2 * j + 1][0] = v.z; B[2 * j + 1][1] = v.w; }
            const uint32_t pa = sb + P_P + (ch * 2080 + 16 + e * 16 + g - 2 * c) * 4;
#pragma unroll
            for (int d = 0; d < 16; d++) {
                const uint32_t a0 = lds32(pa + d * 512), a1 = lds32(pa + d * 512 + 32), a2 = lds32(pa + d * 512 - 32);
#pragma unroll
                for (int j = d; j < 16; j++) mma16(acc[j], a0, a1, a2, a0, B[j - d][0], B[j - d][1]);
            }
        }
        PROF(tid == 0, 3514);
        const uint32_t o = sb + P_Y + (ch * 2560 + c * 40 + g) * 4;
        if (hf == 0) {
            bar_sync(2 + ch, 64);
#pragma unroll
            for (int j = 0; j < 16; j++) {
                acc[j][0] += __uint_as_float(lds32(o + j * 640)); acc[j][1] += __uint_as_float(lds32(o + j * 640 + 80));
                acc[j][2] += __uint_as_float(lds32(o + j * 640 + 32)); acc[j][3] += __uint_as_float(lds32(o + j * 640 + 112));
            }
        }
#pragma unroll
        for (int j = 0; j < 16; j++) {
            sts32(o + j * 640, __float_as_uint(acc[j][0])); sts32(o + j * 640 + 80, __float_as_uint(acc[j][1]));
            sts32(o + j * 640 + 32, __float_as_uint(acc[j][2])); sts32(o + j * 640 + 112, __float_as_uint(acc[j][3]));
        }
        if (hf == 1) bar_arrive(2 + ch, 64);
    }
    const uint2 dk = __ldg((const uint2*)(a.Dk + d0));
    bar_sync(1, 256);
#pragma unroll 2
    for (int i = 0; i < 8; i++) {
        const int t = i * 256 + tid;
        const uint32_t o = sb + P_Y + (t + 4 * (t >> 4)) * 4;
        const uint4 xu = lds128(sb + P_X + t * 16);
        float y[4];
#pragma unroll
        for (int k = 0; k < 4; k++) y[k] = rbf(__uint_as_float(lds32(o + k * 10240)));
        uint2 r;
        r.x = pack2(blo(xu.x) + rbf(y[0] + rbf(blo(xu.z) * blo(dk.x))), bhi(xu.x) + rbf(y[1] + rbf(bhi(xu.z) * bhi(dk.x))));
        r.y = pack2(blo(xu.y) + rbf(y[2] + rbf(blo(xu.w) * blo(dk.y))), bhi(xu.y) + rbf(y[3] + rbf(bhi(xu.w) * bhi(dk.y))));
        ((uint2*)(g_xA[0] + ((t >> 7) * 8 + (d0 >> 6)) * 1024 + ((t & 127) >> 3) * 64 + ((d0 & 63) >> 3) * 8 + (t & 7)))[(d0 >> 2) & 1] = r;
    }
    PROF(tid == 0, 3515);
    if (lane < 8) asm volatile("cp.async.bulk.wait_group 0;" ::: "memory");
}

__global__ void __cluster_dims__(2, 1, 1) __launch_bounds__(384, 1) main_kernel(const __grid_constant__ Params p) {
    extern __shared__ __align__(1024) uint8_t smem[];
    const uint32_t sb = __shfl_sync(0xffffffffu, smem_u32(smem), 0);
    uint32_t rank; asm("mov.u32 %0,%%cluster_ctarank;" : "=r"(rank));
    const int wi = __shfl_sync(0xffffffffu, threadIdx.x >> 5, 0);
    const int cl = blockIdx.x >> 1, wg = wi >> 2;
    const bool rec = p.rec0 >= 0 && cl >= p.rec0 && cl < p.rec0 + 32;
    PROF(threadIdx.x == 0, 3500);
    ProRegs pr;
    prologue_load(p.pa, max((int)blockIdx.x - 4, 0), pr);
    if (rec) rec_init(p, sb, cl - p.rec0, rank); else bulk_init(sb);
    if (threadIdx.x == 352 && p.dopro && cl >= 2) {
        mbar_init(sb + S_XBAR, 1);
        asm volatile("fence.mbarrier_init.release.cluster;" ::: "memory");
        mbar_expect(sb + S_XBAR, 32768);
        for (int j = 0; j < 8; j++) tma2d(sb + P_X + j * 4096, &p.tm[3], ((blockIdx.x - 4) >> 1) * 8, j * 256, sb + S_XBAR);
    }
    if (threadIdx.x == 320) {
        unsigned v;
        asm volatile("ld.relaxed.gpu.global.u32 %0,[%1];" : "=r"(v) : "l"(g_gate) : "memory");
        v = v / (4 * NCL) + p.dopro;
        sts64(sb + S_GATE, v * (4 * NCL), v & 1);
    }
    __syncwarp();
    asm volatile("barrier.cluster.arrive.relaxed.aligned;" ::: "memory");
    if (wg == 2) bar_arrive(8, 384);
    if (p.dopro && cl >= 2) prologue(p.pa, sb, blockIdx.x - 4, wi, pr); else if (wg < 2) bar_sync(8, 384);
    asm volatile("barrier.cluster.wait.aligned;" ::: "memory");
    fence_async_smem();
    bar_sync(wg == 2 ? 7 : 1, wg == 2 ? 128 : 256);
    if (p.dopro && (threadIdx.x == 32 || threadIdx.x == 352)) red_release(g_gate, 1);
    if (rec) {
        if (threadIdx.x == 0) {
            rec_fetch(&p.tm[1], sb + R_STK, (cl - p.rec0) * 128, rank * 256, 2, sb + R_BAR + RB_INIT * 8);
            rec_fetch(&p.tm[2], sb + R_STV, (cl - p.rec0) * 128, rank * 256, 2, sb + R_BAR + RB_INIT * 8);
        }
    }
    PROF(threadIdx.x == 0, 3506);
    __syncwarp();
    if (rec) {
        const int head = cl - p.rec0;
        if (wg == 2) {
            reg_dec<RH>();
            const int w = wi & 3;
            if (threadIdx.x == 256) rec_fetch(&p.tm[0], sb + R_STQ, head * 128, rank * 256, 2, sb + R_BAR + RB_INIT * 8);
            __syncwarp();
            wait_cnt_warp(g_gate, lds32(sb + S_GATE));
            __syncthreads();
            cluster_sync();
            if ((p.chains >> (w >> 1)) & 1) rec_attn(p, sb, w >> 1, w & 1, head, rank);
        } else {
            reg_inc<RW0>();
            rec_weights(p, sb, head, rank, wi);
        }
    } else {
        if (wg == 2) {
            reg_dec<40>();
            const int w = wi & 3;
            if (w == 0) bulk_producer(p, sb, cl, rank); else if (w < 3) bulk_stats(p, sb, cl, rank); else bulk_release(p, sb, cl, rank);
        } else { reg_inc<232>(); bulk_consumer(p, sb, cl, rank, wi); }
    }
    __syncwarp();
    cluster_sync();
}

typedef CUresult (*EncFn)(CUtensorMap*, CUtensorMapDataType, cuuint32_t, void*, const cuuint64_t*, const cuuint64_t*, const cuuint32_t*, const cuuint32_t*,
                          CUtensorMapInterleave, CUtensorMapSwizzle, CUtensorMapL2promotion, CUtensorMapFloatOOBfill);
inline uint32_t mk(int type, int layer, int ch, int a, int b, int c) { return type | (layer << 3) | (ch << 4) | (a << 8) | (b << 16) | ((uint32_t)c << 24); }
constexpr int SMEM_BYTES = 232448;

struct Sched {
    Params* P; int n[NCL];
    void clear() { memset(P->task, 0, sizeof(P->task)); memset(n, 0, sizeof(n)); }
    void add(int cl, uint32_t t) { if (n[cl] < MAXT - 1) P->task[cl][n[cl]++] = t; }
};

#define LAG 13
#define TS1 2400
#define TS2 2900
#define REC0 4
#define NS2 8
#define DFN 5000
#define DQN 5600
struct Slot { double s, e; uint32_t w; };
struct Planner {
    Slot sl[NCL][MAXT]; int n[NCL], nc;
    double fit(int i, double r, double d) const {
        double t = r;
        for (int k = 0; k < n[i]; k++) { if (sl[i][k].s >= t + d) break; if (sl[i][k].e > t) t = sl[i][k].e; }
        return t;
    }
    double idle_before(int i, double t) const { double e = 0; for (int k = 0; k < n[i]; k++) if (sl[i][k].e <= t + 1 && sl[i][k].e > e) e = sl[i][k].e; return t - e; }
    void put(int i, double t, double d, uint32_t w) {
        int k = n[i]++;
        while (k > 0 && sl[i][k - 1].s > t) { sl[i][k] = sl[i][k - 1]; k--; }
        sl[i][k] = {t, t + d, w};
    }
    double last_urgent(int i) const { double e = 0; for (int k = 0; k < n[i]; k++) { const uint32_t t = sl[i][k].w & 15; if (t != (T_OP | 8) && t != (T_FIN | 8)) e = sl[i][k].e; } return e; }
    double place(double r, double d, uint32_t w, int lo, bool tight) {
        int bi = -1; double bt = 0, bg = 0;
        for (int i = lo; i < nc; i++) {
            if (n[i] >= MAXT - 2) continue;
            const double t = fit(i, (w & 7) == T_FIN ? fmax(r, last_urgent(i)) : r, d), g = tight ? idle_before(i, t) : -idle_before(i, t);
            if (bi < 0 || t < bt - 1 || (t < bt + 1 && g < bg)) { bi = i; bt = t; bg = g; }
        }
        put(bi, bt, d, w);
        return bt + d;
    }
};
void plan(Params& P) {
    P.rec0 = REC0; P.chains = 3; P.lag = LAG; P.dostats = 1; P.dopro = 1;
    const double DQ = DQN, DKB = 600, DOV = 1000, DH = 520, DHO = 1300, DU = 4300, DF = DFN, HOP = 1600, ODEL = 1000, LEAD = 1500;
    static Planner L;
    int cls[NCL], nc = 0;
    for (int c = REC0 + 32; c < NCL; c++) cls[nc++] = c;
    for (int c = REC0 - 1; c >= 0; c--) cls[nc++] = c;
    for (double grow = 1.0;; grow *= 1.01) {
        memset(L.n, 0, sizeof(L.n)); L.nc = nc;
        double it[100], worst = 1e18, end = 0, cvs[16], cve[16];
        it[0] = DQ + 2 * HOP;
        for (int i = 1; i < 100; i++) it[i] = it[i - 1] + fmax(grow * TS1, (i - 1 >= LAG && i - 1 < 64) ? TS2 : 0);
        const double DO1 = DOV + 8 * DKB, dly = it[4] + ODEL + DO1 + HOP + DU + HOP + DQ + 2 * HOP - it[LAG];
        if (dly > 0) for (int i = LAG; i < 100; i++) it[i] += dly;
        for (int c = 0; c < 16; c++) {
            const double s0 = fmax(it[4 * c + 4] + ODEL, c ? cve[c - 1] : 0);
            for (int i = 0; i < 8; i++) {
                if (c == 0) L.put(i, s0 - 11000, 11000, mk(T_CV, 0, 3, 2 * i, 0, 128));
                L.put(i, s0, DO1, mk(T_OP, 0, c, 8 * i, 8, i));
                L.put(i, s0 + DO1, HOP + DU, mk(T_CV, 0, c, 2 * i, 0, 0));
            }
            cvs[c] = s0 + DO1; cve[c] = cvs[c] + HOP + DU;
        }
        for (int c = 0; c < 16; c++) {
            double e = 0;
            for (int t = 0; t < 24; t++) e = fmax(e, L.place(cve[c] + HOP, DQ, mk(T_QKV, 1, c, t * 8, 4, 0), 0, true));
            worst = fmin(worst, it[LAG + 4 * c] - (c ? LEAD : 0) - HOP - e);
        }
        for (int c = 2; c < 16; c++) {
            double e = 0, r = cve[c - 2] + HOP;
            const int m = c >= HSPLIT ? c / 2 + 1 : c;
            if (m < c) for (int i = 0; i < 8; i++) r = fmax(r, L.place(cve[c - 3] + HOP, DHO + DH * (c - m), mk(T_CV, 1, c, 2 * i, c, m + 1), 8, true));
            for (int i = 0; i < 8; i++) e = fmax(e, L.place(r, DHO + (m < c ? 1500 : 0) + DH * (m - 1), mk(T_CV, 1, c, 2 * i, m, 2), 8, true));
            worst = fmin(worst, cvs[c] - HOP - e);
        }
        for (int c = 0; c < 16; c++) {
            double e = 0;
            for (int t = 0; t < 24; t++) e = fmax(e, L.place(0, DQ, mk(T_QKV, 0, c, t * 8, 4, 0), 0, true));
            worst = fmin(worst, it[4 * c] - (c ? LEAD : 0) - HOP - e);
        }
        for (int cc = 0; cc < 16; cc++) {
            const int c = cc ? cc - 1 : 15, ns = c == 15 ? 16 : c == 14 ? 8 : NS2, nf = c >= 14 ? 8 : 4;
            double e = 0;
            for (int t = 0; t < ns; t++) {
                const int a = t * 64 / ns, b = (t + 1) * 64 / ns - a;
                const double guard = c == 15 ? 9000 : 0;
                e = fmax(e, L.place(it[LAG + 4 * c + 4] + ODEL - guard, DOV + DKB * b + guard, mk(T_OP, 1, c, a, b, t), 0, true));
            }
            for (int t = 0; t < nf; t++) end = fmax(end, L.place(e + HOP, DF, mk(T_FIN, 1, c, t * (32 / nf), ns, 16 / nf), 0, true));
        }
        if (worst >= 0) break;
    }
    for (int lc = 0; lc < 32; lc++) {
        bool used[24] = {};
        for (int pass = 0; pass < 2; pass++)
            for (int i = 0; i < nc; i++)
                for (int k = 0; k < L.n[i]; k++) {
                    uint32_t& w = L.sl[i][k].w;
                    if ((w & 255) != mk(T_QKV, lc & 1, lc >> 1, 0, 0, 0)) continue;
                    int t = i - 8;
                    if (pass == 0) { w |= 0xff00; if (t < 0 || t >= 24 || used[t]) continue; }
                    else { if ((w & 0xff00) != 0xff00) continue; for (t = 0; used[t]; t++) {} }
                    used[t] = true; w = (w & ~0xff00u) | (t * 8) << 8;
                }
    }
    Sched S; S.P = &P; S.clear();
    S.add(0, mk(T_QKV, 1, 15, 124, 4, 128)); S.add(0, mk(T_OP, 1, 15, 0, 4, 128));
    S.add(1, mk(T_CV, 0, 3, 0, 0, 128));
    for (int i = 0; i < nc; i++) {
        bool warm = false;
        for (int k = 0; k < L.n[i]; k++) {
            if (!warm && k + 1 < L.n[i] && (L.sl[i][k + 1].w & 255) == (mk(T_FIN, 1, 15, 0, 0, 0) & 255)) { S.add(cls[i], L.sl[i][k + 1].w | 0x80000000u); warm = true; }
            S.add(cls[i], L.sl[i][k].w);
            if ((L.sl[i][k].w & 7) == T_FIN) warm = true;
        }
    }
}

#define TK0() do {} while (0)
#define TK() do { P.e0 = (P.chains & 1) ? 64 : 0; P.b1 = (P.chains & 2) ? P.lag : 1000; P.nit = (P.chains & 2) ? P.lag + 64 : 64; TK0(); } while (0)
}

extern "C" void kernel_launch(void* const* d_in, const int* in_sizes, int n_in, void* d_out, int out_size) {
    typedef const __nv_bfloat16* BP;
    static EncFn enc = nullptr;
    if (!enc) {
        void* fn = nullptr; cudaDriverEntryPointQueryResult qr;
        cudaGetDriverEntryPoint("cuTensorMapEncodeTiled", &fn, cudaEnableDefault, &qr);
        enc = (EncFn)fn;
        cudaFuncSetAttribute(main_kernel, cudaFuncAttributeMaxDynamicSharedMemorySize, SMEM_BYTES);
    }
    static Params P;
    for (int i = 0; i < 4; i++) {
        const cuuint64_t cols = i < 3 ? 4096 : 512, rows = i < 3 ? 512 : 4096;
        cuuint64_t d2[2] = {cols, rows}, d3[3] = {64, rows, cols / 64}, str[2] = {cols * 2, 128};
        cuuint32_t box[3] = {64, 64, 4}, es[3] = {1, 1, 1};
        enc(&P.tm[i < 3 ? i : 4], CU_TENSOR_MAP_DATA_TYPE_BFLOAT16, 2, d_in[9 + i], d2, str, box, es, CU_TENSOR_MAP_INTERLEAVE_NONE, CU_TENSOR_MAP_SWIZZLE_128B,
                       CU_TENSOR_MAP_L2_PROMOTION_L2_128B, CU_TENSOR_MAP_FLOAT_OOB_FILL_NONE);
        for (int m = 0; m < 2; m++) {
            cuuint32_t box3[3] = {64, 32, m ? 2u : 4u};
            enc(&P.t3[m][i], CU_TENSOR_MAP_DATA_TYPE_BFLOAT16, 3, d_in[9 + i], d3, str, box3, es, CU_TENSOR_MAP_INTERLEAVE_NONE, CU_TENSOR_MAP_SWIZZLE_128B,
                CU_TENSOR_MAP_L2_PROMOTION_L2_128B, CU_TENSOR_MAP_FLOAT_OOB_FILL_NONE);
        }
    }
    {
        cuuint64_t dims[2] = {512, 2048}, str[1] = {1024};
        cuuint32_t box[2] = {8, 256}, es[2] = {1, 1};
        enc(&P.tm[3], CU_TENSOR_MAP_DATA_TYPE_BFLOAT16, 2, d_in[0], dims, str, box, es, CU_TENSOR_MAP_INTERLEAVE_NONE, CU_TENSOR_MAP_SWIZZLE_NONE,
            CU_TENSOR_MAP_L2_PROMOTION_NONE, CU_TENSOR_MAP_FLOAT_OOB_FILL_NONE);
    }
    for (int m = 0; m < 2; m++) {
        void* ga; cudaGetSymbolAddress(&ga, g_A);
        cuuint64_t dims[2] = {512, sizeof(AOps) / 1024}, str[1] = {1024};
        cuuint32_t box[2] = {256, m ? 16u : 8u}, es[2] = {1, 1};
        enc(&P.ta[m], CU_TENSOR_MAP_DATA_TYPE_BFLOAT16, 2, ga, dims, str, box, es, CU_TENSOR_MAP_INTERLEAVE_NONE, CU_TENSOR_MAP_SWIZZLE_NONE,
            CU_TENSOR_MAP_L2_PROMOTION_L2_128B, CU_TENSOR_MAP_FLOAT_OOB_FILL_NONE);
    }
    P.mem0 = (BP)d_in[8]; P.Wo = (BP)d_in[12]; P.Dskip = (BP)d_in[6]; P.out = (__nv_bfloat16*)d_out;
    P.nst[0] = 1; P.nst[1] = 16;
    cudaStream_t s = cudaStreamPerThread;
    P.pa = {(BP)d_in[0], (BP)d_in[1], (BP)d_in[2], (BP)d_in[3], (BP)d_in[4], (BP)d_in[5], (BP)d_in[6], (BP)d_in[9], (BP)d_in[10], (BP)d_in[11], (BP)d_in[12], (BP)d_in[8]};
    static bool planned = false;
    if (!planned) { plan(P); planned = true; }
    TK(); main_kernel<<<2 * NCL, 384, SMEM_BYTES, s>>>(P); TK();
}
```

```cpp
#include <cuda_runtime.h>
#include <cuda_bf16.h>
#include <cuda.h>
#include <stdint.h>
#include <string.h>
#include <math.h>

namespace {

constexpr int NCL = 66;
constexpr int MAXT = 64;
#define OPS1N 8
constexpr int OPS1 = OPS1N;
constexpr int MAXSPLIT = 16;
constexpr int PW = 144;

struct AOps { uint4 x[2][16 * 8 * 1024], o[2][16 * 64 * 1024]; };
__device__ AOps g_A;
#define g_xA g_A.x
#define g_o g_A.o
__device__ float2 g_st[2][16 * 2048];
__device__ float2 g_st2[16 * 16 * 128];
__device__ uint4 g_qkv[2][64 * 64 * 768];
__device__ uint4 g_pp[2][16 * MAXSPLIT * 8192];
__device__ uint4 g_acc[7 * 2048];
__device__ unsigned g_gate[32];
__device__ uint32_t g_P[16 * 16 * 32 * PW];
__device__ uint4 g_u[16 * 16 * 512];
__device__ float4 g_carry[2][17 * 16 * 4 * 256];
__device__ float g_cs[2 * 12288 + 64];
__device__ unsigned g_cnt[9 * 16 * 32];
__device__ uint32_t g_ln0[2048];

enum { C_QKV0 = 0, C_QKV1 = 1, C_O0 = 2, C_O1 = 3, C_U = 4, C_OP1 = 5, C_CV = 6, C_ST = 7, C_H = 8 };
__device__ __forceinline__ unsigned* cnt_ptr(int kind, int chunk) { return g_cnt + (kind * 16 + chunk) * 32; }

enum { T_END = 0, T_QKV = 1, T_OP = 2, T_CV = 3, T_FIN = 4 };
struct ProArgs { const __nv_bfloat16 *x, *lAr, *Ai, *Cr, *Ci, *ldt, *Dk, *Wq, *Wk, *Wv, *Wo, *mem0; };
struct Params {
    CUtensorMap tm[5];
    CUtensorMap t3[2][4];
    CUtensorMap ta[2];
    ProArgs pa;
    int dopro;
    const __nv_bfloat16* mem0;
    const __nv_bfloat16* Wo;
    const __nv_bfloat16* Dskip;
    __nv_bfloat16* out;
    int rec0;
    int chains;
    int lag;
    int b1, e0, nit;
    int zero, gpit;
    int dostats;
    int nst[2];
    uint32_t task[NCL][MAXT];
};

__device__ __forceinline__ uint32_t smem_u32(const void* p) { return (uint32_t)__cvta_generic_to_shared(p); }
__device__ __forceinline__ uint32_t mapa(uint32_t a, uint32_t r) {
    uint32_t o; asm("mapa.shared::cluster.u32 %0,%1,%2;" : "=r"(o) : "r"(a), "r"(r)); return o;
}
__device__ __forceinline__ void mbar_init(uint32_t b, int c) { asm volatile("mbarrier.init.shared::cta.b64 [%0],%1;" ::"r"(b), "r"(c) : "memory"); }
__device__ __forceinline__ void mbar_expect(uint32_t b, int bytes) { asm volatile("mbarrier.arrive.expect_tx.shared::cta.b64 _,[%0],%1;" ::"r"(b), "r"(bytes) : "memory"); }
__device__ __forceinline__ void mbar_arrive(uint32_t b) { asm volatile("mbarrier.arrive.shared::cta.b64 _,[%0];" ::"r"(b) : "memory"); }
__device__ __forceinline__ void mbar_arrive_cluster(uint32_t b) { asm volatile("mbarrier.arrive.shared::cluster.b64 _,[%0];" ::"r"(b) : "memory"); }
__device__ __forceinline__ void mbar_arrive1(uint32_t b) { asm volatile("{.reg .pred p; elect.sync _|p,0xffffffff; @p mbarrier.arrive.shared::cta.b64 _,[%0];}" ::"r"(b) : "memory"); }
__device__ __forceinline__ void mbar_arrive1_cluster(uint32_t b) { asm volatile("{.reg .pred p; elect.sync _|p,0xffffffff; @p mbarrier.arrive.shared::cluster.b64 _,[%0];}" ::"r"(b) : "memory"); }
__device__ __forceinline__ void mbar_wait(uint32_t b, uint32_t ph) {
    asm volatile(
        "{.reg .pred p; .reg .u32 n; mov.u32 n,0;\n"
        "W%=: mbarrier.try_wait.parity.shared::cta.b64 p,[%0],%1;\n"
        "@p bra D%=;\n"
        "add.u32 n,n,1; setp.lt.u32 p,n,2000000; @p bra W%=;\n"
        "trap;\n"
        "D%=: }" ::"r"(b), "r"(ph) : "memory");
}
__device__ __forceinline__ bool mbar_test(uint32_t b, uint32_t ph) {
    uint32_t ok;
    asm volatile("{.reg .pred p; mbarrier.test_wait.parity.shared::cta.b64 p,[%1],%2; selp.u32 %0,1,0,p;}" : "=r"(ok) : "r"(b), "r"(ph) : "memory");
    return ok;
}
__device__ __forceinline__ bool wait_lds128(uint32_t b, uint32_t ph, uint32_t a, uint4& v) {
    uint32_t ok;
    asm volatile("{.reg .pred p; mbarrier.try_wait.parity.shared::cta.b64 p,[%5],%6,20000; ld.shared.v4.u32 {%0,%1,%2,%3},[%7]; selp.u32 %4,1,0,p;}"
                 : "=r"(v.x), "=r"(v.y), "=r"(v.z), "=r"(v.w), "=r"(ok) : "r"(b), "r"(ph), "r"(a) : "memory");
    return ok;
}
__device__ __forceinline__ bool wait_lds64(uint32_t b, uint32_t ph, uint32_t a, uint2& v) {
    uint32_t ok;
    asm volatile("{.reg .pred p; mbarrier.try_wait.parity.shared::cta.b64 p,[%3],%4,20000; ld.shared.v2.u32 {%0,%1},[%5]; selp.u32 %2,1,0,p;}"
                 : "=r"(v.x), "=r"(v.y), "=r"(ok) : "r"(b), "r"(ph), "r"(a) : "memory");
    return ok;
}
template <int PH> __device__ __forceinline__ void mbar_wait_c(uint32_t b) {
    asm volatile(
        "{.reg .pred p; .reg .u32 n; mov.u32 n,%2;\n"
        "W%=: mbarrier.try_wait.parity.shared::cta.b64 p,[%0],%1;\n"
        "@p bra D%=;\n"
        "add.u32 n,n,1; setp.lt.u32 p,n,2000000; @p bra W%=;\n"
        "trap;\n"
        "D%=: }" ::"r"(b), "n"(PH), "n"(PH) : "memory");
}
__device__ __forceinline__ void bar_sync(int id, int n) { asm volatile("bar.sync %0,%1;" ::"r"(id), "r"(n) : "memory"); }
__device__ __forceinline__ void bar_arrive(int id, int n) { asm volatile("bar.arrive %0,%1;" ::"r"(id), "r"(n) : "memory"); }
__device__ __forceinline__ void cluster_sync() { asm volatile("barrier.cluster.arrive.relaxed.aligned; barrier.cluster.wait.aligned;" ::: "memory"); }
__device__ __forceinline__ void fence_async() { asm volatile("fence.proxy.async;" ::: "memory"); }
__device__ __forceinline__ void fence_async_smem() { asm volatile("fence.proxy.async.shared::cta;" ::: "memory"); }
#define EFR 1
#define EFW 2
constexpr uint64_t POL_N = 0x1000000000000000ull, POL_F = 0x12F0000000000000ull;
constexpr uint64_t POL_LAST = EFR ? POL_F : POL_N  , POL_LATE = EFW ? POL_F : POL_N  , POL_SOON = EFW > 1 ? POL_F : POL_N;
__device__ __forceinline__ void bulk_g2s(uint32_t dst, const void* src, int bytes, uint32_t bar, uint64_t pol) {
    asm volatile("cp.async.bulk.shared::cluster.global.mbarrier::complete_tx::bytes.L2::cache_hint [%0],[%1],%2,[%3],%4;" ::"r"(dst), "l"(src), "r"(bytes), "r"(bar), "l"(pol) : "memory");
}
__device__ __forceinline__ void bulk_g2s_mc(uint32_t dst, const void* src, int bytes, uint32_t bar, uint64_t pol) {
    asm volatile("cp.async.bulk.shared::cluster.global.mbarrier::complete_tx::bytes.multicast::cluster.L2::cache_hint [%0],[%1],%2,[%3],%4,%5;" ::"r"(dst), "l"(src), "r"(bytes), "r"(bar), "h"((uint16_t)3), "l"(pol) : "memory");
}
__device__ __forceinline__ void bulk_s2s(uint32_t dst, uint32_t src, int bytes, uint32_t bar) {
    asm volatile("cp.async.bulk.shared::cluster.shared::cta.mbarrier::complete_tx::bytes [%0],[%1],%2,[%3];" ::"r"(dst), "r"(src), "r"(bytes), "r"(bar) : "memory");
}
__device__ __forceinline__ bool elect() {
    uint32_t r; asm volatile("{.reg .pred p; elect.sync _|p,0xffffffff; selp.u32 %0,1,0,p;}" : "=r"(r)); return r;
}
__device__ __forceinline__ void stg128(uint4* p, uint4 v, uint64_t pol) {
    asm volatile("st.global.L2::cache_hint.v4.u32 [%0],{%1,%2,%3,%4},%5;" ::"l"(p), "r"(v.x), "r"(v.y), "r"(v.z), "r"(v.w), "l"(pol));
}
__device__ __forceinline__ void stg32(uint32_t* p, uint32_t v, uint64_t pol) { asm volatile("st.global.L2::cache_hint.u32 [%0],%1,%2;" ::"l"(p), "r"(v), "l"(pol)); }
__device__ __forceinline__ uint4 ldcg128_last(const uint4* p) {
    uint4 v; asm volatile("ld.global.cg.L2::cache_hint.v4.u32 {%0,%1,%2,%3},[%4],%5;" : "=r"(v.x), "=r"(v.y), "=r"(v.z), "=r"(v.w) : "l"(p), "l"(POL_LAST) : "memory"); return v;
}
__device__ __forceinline__ void tma2d(uint32_t dst, const CUtensorMap* tm, int x, int y, uint32_t bar) {
    asm volatile("cp.async.bulk.tensor.2d.shared::cluster.global.mbarrier::complete_tx::bytes [%0],[%1,{%2,%3}],[%4];" ::"r"(dst), "l"(tm), "r"(x), "r"(y), "r"(bar) : "memory");
}
__device__ __forceinline__ void tma3d_mc(uint32_t dst, const CUtensorMap* tm, int y, int z, uint32_t bar, uint16_t mask) {
    asm volatile("{.reg .pred p; elect.sync _|p,0xffffffff;\n"
                 "@p cp.async.bulk.tensor.3d.shared::cluster.global.mbarrier::complete_tx::bytes.multicast::cluster [%0],[%1,{0,%2,%3}],[%4],%5;}"
                 ::"r"(dst), "l"(tm), "r"(y), "r"(z), "r"(bar), "h"(mask) : "memory");
}
__device__ __forceinline__ void tma2d_mc(uint32_t dst, const CUtensorMap* tm, int x, int y, uint32_t bar, uint16_t mask, uint64_t pol) {
    asm volatile("{.reg .pred p; elect.sync _|p,0xffffffff;\n"
                 "@p cp.async.bulk.tensor.2d.shared::cluster.global.mbarrier::complete_tx::bytes.multicast::cluster.L2::cache_hint [%0],[%1,{%2,%3}],[%4],%5,%6;}"
                 ::"r"(dst), "l"(tm), "r"(x), "r"(y), "r"(bar), "h"(mask), "l"(pol) : "memory");
}
__device__ __forceinline__ void bulk_g2s1(uint32_t dst, const void* src, int bytes, uint32_t bar, uint64_t pol) {
    asm volatile("{.reg .pred p; elect.sync _|p,0xffffffff;\n"
                 "@p cp.async.bulk.shared::cluster.global.mbarrier::complete_tx::bytes.L2::cache_hint [%0],[%1],%2,[%3],%4;}" ::"r"(dst), "l"(src), "r"(bytes), "r"(bar), "l"(pol) : "memory");
}
__device__ __forceinline__ void mbar_expect1(uint32_t b, int bytes) {
    asm volatile("{.reg .pred p; elect.sync _|p,0xffffffff; @p mbarrier.arrive.expect_tx.shared::cta.b64 _,[%0],%1;}" ::"r"(b), "r"(bytes) : "memory");
}
__device__ __forceinline__ void st_async4(uint32_t a, uint32_t x, uint32_t y, uint32_t z, uint32_t w, uint32_t mb) {
    asm volatile("st.async.shared::cluster.mbarrier::complete_tx::bytes.v4.b32 [%0],{%1,%2,%3,%4},[%5];" ::"r"(a), "r"(x), "r"(y), "r"(z), "r"(w), "r"(mb) : "memory");
}
__device__ __forceinline__ void st_async2(uint32_t a, uint32_t x, uint32_t y, uint32_t mb) {
    asm volatile("st.async.shared::cluster.mbarrier::complete_tx::bytes.v2.b32 [%0],{%1,%2},[%3];" ::"r"(a), "r"(x), "r"(y), "r"(mb) : "memory");
}
#define LDSQ "ld.shared"
__device__ __forceinline__ uint4 lds128(uint32_t a) { uint4 v; asm volatile(LDSQ ".v4.u32 {%0,%1,%2,%3},[%4];" : "=r"(v.x), "=r"(v.y), "=r"(v.z), "=r"(v.w) : "r"(a) : "memory"); return v; }
__device__ __forceinline__ uint2 lds64(uint32_t a) { uint2 v; asm volatile(LDSQ ".v2.u32 {%0,%1},[%2];" : "=r"(v.x), "=r"(v.y) : "r"(a) : "memory"); return v; }
__device__ __forceinline__ uint32_t lds32(uint32_t a) { uint32_t v; asm volatile(LDSQ ".u32 %0,[%1];" : "=r"(v) : "r"(a) : "memory"); return v; }
__device__ __forceinline__ void sts128(uint32_t a, uint32_t x, uint32_t y, uint32_t z, uint32_t w) { asm volatile("st.shared.v4.u32 [%0],{%1,%2,%3,%4};" ::"r"(a), "r"(x), "r"(y), "r"(z), "r"(w) : "memory"); }
__device__ __forceinline__ void sts64(uint32_t a, uint32_t x, uint32_t y) { asm volatile("st.shared.v2.u32 [%0],{%1,%2};" ::"r"(a), "r"(x), "r"(y) : "memory"); }
__device__ __forceinline__ void sts32(uint32_t a, uint32_t x) { asm volatile("st.shared.u32 [%0],%1;" ::"r"(a), "r"(x) : "memory"); }
__device__ __forceinline__ uint4 ldsm4(uint32_t a) { uint4 v; asm volatile("ldmatrix.sync.aligned.m8n8.x4.shared.b16 {%0,%1,%2,%3},[%4];" : "=r"(v.x), "=r"(v.y), "=r"(v.z), "=r"(v.w) : "r"(a) : "memory"); return v; }
__device__ __forceinline__ uint4 ldsm4t(uint32_t a) { uint4 v; asm volatile("ldmatrix.sync.aligned.m8n8.x4.trans.shared.b16 {%0,%1,%2,%3},[%4];" : "=r"(v.x), "=r"(v.y), "=r"(v.z), "=r"(v.w) : "r"(a) : "memory"); return v; }
__device__ __forceinline__ uint32_t movm(uint32_t a) { uint32_t d; asm volatile("movmatrix.sync.aligned.m8n8.trans.b16 %0,%1;" : "=r"(d) : "r"(a)); return d; }
__device__ __forceinline__ uint32_t pack2(float lo, float hi) { uint32_t d; asm("cvt.rn.bf16x2.f32 %0,%1,%2;" : "=r"(d) : "f"(hi), "f"(lo)); return d; }
__device__ __forceinline__ uint32_t hadd2(uint32_t a, uint32_t b) { uint32_t d; asm("add.rn.bf16x2 %0,%1,%2;" : "=r"(d) : "r"(a), "r"(b)); return d; }
__device__ __forceinline__ float blo(uint32_t v) { return __uint_as_float(v << 16); }
__device__ __forceinline__ float bhi(uint32_t v) { return __uint_as_float(v & 0xffff0000u); }
__device__ __forceinline__ float rbf(float x) { return __uint_as_float(pack2(0.f, x)); }
__device__ __forceinline__ float ex2(float x) { float y; asm("ex2.approx.ftz.f32 %0,%1;" : "=f"(y) : "f"(x)); return y; }
__device__ __forceinline__ float rcp(float x) { float y; asm("rcp.approx.ftz.f32 %0,%1;" : "=f"(y) : "f"(x)); return y; }
__device__ __forceinline__ void mma16(float* c, uint32_t a0, uint32_t a1, uint32_t a2, uint32_t a3, uint32_t b0, uint32_t b1) {
    asm volatile("mma.sync.aligned.m16n8k16.row.col.f32.bf16.bf16.f32 {%0,%1,%2,%3},{%4,%5,%6,%7},{%8,%9},{%0,%1,%2,%3};"
                 : "+f"(c[0]), "+f"(c[1]), "+f"(c[2]), "+f"(c[3]) : "r"(a0), "r"(a1), "r"(a2), "r"(a3), "r"(b0), "r"(b1));
}
__device__ __forceinline__ void mma8(float* c, uint32_t a0, uint32_t a1, uint32_t b0) {
    asm volatile("mma.sync.aligned.m16n8k8.row.col.f32.bf16.bf16.f32 {%0,%1,%2,%3},{%4,%5},{%6},{%0,%1,%2,%3};"
                 : "+f"(c[0]), "+f"(c[1]), "+f"(c[2]), "+f"(c[3]) : "r"(a0), "r"(a1), "r"(b0));
}
__device__ __forceinline__ uint4 ld_rlx128(const uint4* p) {
    uint4 v;
    asm volatile("{.reg .b128 t; ld.relaxed.gpu.global.b128 t,[%4]; mov.b128 {%0,%1,%2,%3},t;}" : "=r"(v.x), "=r"(v.y), "=r"(v.z), "=r"(v.w) : "l"(p) : "memory");
    return v;
}
__device__ __forceinline__ void st_rlx128(uint4* p, uint32_t x, uint32_t y, uint32_t z, uint32_t w) {
    asm volatile("{.reg .b128 t; mov.b128 t,{%1,%2,%3,%4}; st.relaxed.gpu.global.b128 [%0],t;}" ::"l"(p), "r"(x), "r"(y), "r"(z), "r"(w) : "memory");
}
__device__ __forceinline__ uint4 ldcg128(const uint4* p) { uint4 v; asm volatile("ld.global.cg.v4.u32 {%0,%1,%2,%3},[%4];" : "=r"(v.x), "=r"(v.y), "=r"(v.z), "=r"(v.w) : "l"(p) : "memory"); return v; }
__device__ __forceinline__ void red_release(unsigned* p, unsigned v) {
    asm volatile("fence.proxy.async; red.relaxed.gpu.global.add.u32 [%0],%1;" ::"l"(p), "r"(v) : "memory");
}
__device__ __forceinline__ void wait_cnt(const unsigned* p, unsigned target) {
    unsigned v; int n = 0;
    while (true) {
        asm volatile("ld.acquire.gpu.global.u32 %0,[%1];" : "=r"(v) : "l"(p) : "memory");
        if (v >= target) break;
        if (++n > 3000000) __trap();
        __nanosleep(40);
    }
}
__device__ __forceinline__ void wait_cnt_warp(const unsigned* p, unsigned target) {
    unsigned v; int n = 0;
    while (true) {
        asm volatile("ld.acquire.gpu.global.u32 %0,[%1];" : "=r"(v) : "l"(p) : "memory");
        if (__all_sync(0xffffffffu, v >= target)) break;
        if (++n > 3000000) __trap();
    }
}
__device__ __forceinline__ uint64_t mkdesc(uint32_t addr, uint32_t lbo, uint32_t sbo, uint32_t sw) {
    return (uint64_t)((addr & 0x3FFFF) >> 4) | ((uint64_t)(lbo >> 4) << 16) | ((uint64_t)(sbo >> 4) << 32) | ((uint64_t)sw << 62);
}
__device__ __forceinline__ void wg_fence() { asm volatile("wgmma.fence.sync.aligned;" ::: "memory"); }
__device__ __forceinline__ void wg_commit() { asm volatile("wgmma.commit_group.sync.aligned;" ::: "memory"); }
template <int N> __device__ __forceinline__ void wg_wait() { asm volatile("wgmma.wait_group.sync.aligned %0;" ::"n"(N) : "memory"); }
#define R8(c, o) "+f"(c[o]), "+f"(c[o + 1]), "+f"(c[o + 2]), "+f"(c[o + 3]), "+f"(c[o + 4]), "+f"(c[o + 5]), "+f"(c[o + 6]), "+f"(c[o + 7])
#define R32(c, o) R8(c, o), R8(c, o + 8), R8(c, o + 16), R8(c, o + 24)
#define S32A "%0,%1,%2,%3,%4,%5,%6,%7,%8,%9,%10,%11,%12,%13,%14,%15,%16,%17,%18,%19,%20,%21,%22,%23,%24,%25,%26,%27,%28,%29,%30,%31"
#define S32B ",%32,%33,%34,%35,%36,%37,%38,%39,%40,%41,%42,%43,%44,%45,%46,%47,%48,%49,%50,%51,%52,%53,%54,%55,%56,%57,%58,%59,%60,%61,%62,%63"
#define S32C ",%64,%65,%66,%67,%68,%69,%70,%71,%72,%73,%74,%75,%76,%77,%78,%79,%80,%81,%82,%83,%84,%85,%86,%87,%88,%89,%90,%91,%92,%93,%94,%95"
#define S32D ",%96,%97,%98,%99,%100,%101,%102,%103,%104,%105,%106,%107,%108,%109,%110,%111,%112,%113,%114,%115,%116,%117,%118,%119,%120,%121,%122,%123,%124,%125,%126,%127"
#define W8(c, o) "=f"(c[o]), "=f"(c[o + 1]), "=f"(c[o + 2]), "=f"(c[o + 3]), "=f"(c[o + 4]), "=f"(c[o + 5]), "=f"(c[o + 6]), "=f"(c[o + 7])
#define W32(c, o) W8(c, o), W8(c, o + 8), W8(c, o + 16), W8(c, o + 24)
template <bool ACC> __device__ __forceinline__ void wgmma256(float* c, uint64_t da, uint64_t db) {
    if (ACC) asm volatile("wgmma.mma_async.sync.aligned.m64n256k16.f32.bf16.bf16 {" S32A S32B S32C S32D "},%128,%129,1,1,1,0,1;"
                          : R32(c, 0), R32(c, 32), R32(c, 64), R32(c, 96) : "l"(da), "l"(db));
    else asm volatile("wgmma.mma_async.sync.aligned.m64n256k16.f32.bf16.bf16 {" S32A S32B S32C S32D "},%128,%129,0,1,1,0,1;"
                      : W32(c, 0), W32(c, 32), W32(c, 64), W32(c, 96) : "l"(da), "l"(db));
}
template <bool ACC> __device__ __forceinline__ void wgmma128r(float* c, const uint4& a, uint64_t db) {
    if (ACC) asm volatile("wgmma.mma_async.sync.aligned.m64n128k16.f32.bf16.bf16 {" S32A S32B "},{%64,%65,%66,%67},%68,1,1,1,1;"
                          : R32(c, 0), R32(c, 32) : "r"(a.x), "r"(a.y), "r"(a.z), "r"(a.w), "l"(db));
    else asm volatile("wgmma.mma_async.sync.aligned.m64n128k16.f32.bf16.bf16 {" S32A S32B "},{%64,%65,%66,%67},%68,0,1,1,1;"
                      : W32(c, 0), W32(c, 32) : "r"(a.x), "r"(a.y), "r"(a.z), "r"(a.w), "l"(db));
}
template <int N> __device__ __forceinline__ void reg_inc() { asm volatile("setmaxnreg.inc.sync.aligned.u32 %0;" ::"n"(N)); }
template <int N> __device__ __forceinline__ void reg_dec() { asm volatile("setmaxnreg.dec.sync.aligned.u32 %0;" ::"n"(N)); }

#define PROF(cond, idx) do {} while (0)
#define CPROF(k) do {} while (0)

constexpr int S_GATE = 232440, S_TAG = 232444, S_XBAR = 232432;
constexpr float SC_LOG2E = 0.08838834764831845f * 1.4426950408889634f;

__device__ __forceinline__ float2 ln_finish(float mean, float var) {
    float sd; asm("sqrt.approx.f32 %0,%1;" : "=f"(sd) : "f"(rbf(rbf(var) + 1e-5f)));
    sd = rbf(sd);
    return make_float2(rbf(mean), sd);
}

__device__ __forceinline__ float2 row_stats512(const uint4* src, int s1, int s2) {
    const int g = (threadIdx.x & 31) >> 2;
    uint4 v[16];
#pragma unroll
    for (int i = 0; i < 16; i++) v[i] = ldcg128(src + (i >> 1) * s1 + (i & 1) * s2);
    float a[4] = {0, 0, 0, 0}, q0[4] = {0, 0, 0, 0}, q1[4] = {0, 0, 0, 0};
#pragma unroll
    for (int i = 0; i < 16; i++) {
        mma16(a, v[i].x, v[i].y, v[i].z, v[i].w, 0x3f803f80u, 0x3f803f80u);
        mma8(q0, v[i].x, v[i].y, v[i].x); mma8(q1, v[i].x, v[i].y, v[i].y);
        mma8(q0, v[i].z, v[i].w, v[i].z); mma8(q1, v[i].z, v[i].w, v[i].w);
    }
    const float sum = a[0] + a[2], sq = (g & 1) ? q0[1] + q1[3] : q0[0] + q1[2];
    return make_float2(sum, fmaxf(sq - sum * sum * (1.f / 512.f), 0.f));
}
__device__ __forceinline__ void x1_stats(int rg) {
    const int lane = threadIdx.x & 31, g = lane >> 2, c = lane & 3;
    const float2 r = row_stats512(g_xA[0] + (rg >> 4) * 8192 + (rg & 15) * 64 + c * 8 + g, 1024, 32);
    if (c == (g >> 1)) { g_st[0][(rg >> 4) * 2048 + (rg & 15) * 8 + g] = r; g_ln0[rg * 8 + g] = 0; }
    __syncwarp();
    if (lane == 0) red_release(cnt_ptr(C_ST, rg >> 4), 1);
}
__global__ void stats_kernel() { x1_stats(blockIdx.x * 4 + (threadIdx.x >> 5)); }

#define NT 9
#define RH 104
#define RW0 200
#define NPD 5
#define NTO 13
#define DP1 0
#define GPW 0
#define GPJ 0
#define PACE 2
#define BKA 0
#define GSE 0
#define EARLY 0
#define STO 1
#define G2I 3
#define VE 4
#define VF 8
constexpr int TILE = 20480;
constexpr int R_WV = 0, R_WO = 65536, R_T = 131072, R_M = R_T + 2 * TILE  , R_LOC = R_M + 8192  ,
              R_REM = R_LOC + 12288  , R_O = R_REM + 24576  , R_SX = R_O + 4096  ,
              R_IL = R_SX + 10240  , R_BAR = 231936, R_Z = R_BAR + 128  , R_STQ = 0, R_STK = 65536, R_STV = 131072;
static_assert(R_IL + 512 <= R_BAR && R_BAR + 256 <= S_XBAR, "smem map");
enum { RB_INIT = 0, RB_T = 2  , RB_V = 4  , RB_QK = 8  , RB_N = 12 };
enum { NB_MF = 1  , NB_LOC = 3  , NB_PAIR = 5  , NB_O = 9  , NB_XG = 11  , NB_W = 13 };
__device__ __forceinline__ uint32_t clk32() { return (uint32_t)clock64(); }

__device__ __forceinline__ char* acc_base() { return (char*)(((size_t)g_acc + 131071) & ~(size_t)131071); }
__device__ __forceinline__ uint32_t acc_slice(uint32_t s6) { return (s6 & 1) * 256 + (s6 >> 1) * 1024; }
__device__ __forceinline__ uint32_t acc_main(uint32_t rank, uint32_t tid) { return acc_slice(rank * 32 + (tid >> 3)) + (tid & 7) * 16; }
__device__ __forceinline__ uint32_t acc_extra(uint32_t rank, uint32_t tid) { return 65536 + acc_slice(((tid >> 5) & 1) + rank * 4 + (tid >> 6) * 8) + (tid & 31) * 4; }
__device__ __forceinline__ uint32_t acc_slot(uint32_t s) { return (s & 1) * 128 + (s & 2) * 256; }
__device__ __forceinline__ void acc_init(const __nv_bfloat16* mem0, int i) {
    const uint32_t tid = i & 255, rank = (i >> 8) & 1, slot = (i >> 9) & 3, X = i >> 11;
    uint32_t v[5] = {0, 0, 0, 0, 0};
    if (slot == 3) {
        const uint16_t* m = (const uint16_t*)mem0 + (tid & 3) * 1024 + rank * 256 + (tid >> 5) * 32 + ((tid >> 2) & 7);
#pragma unroll
        for (int k = 0; k < 4; k++) v[k] = __ldg(m + k * 8) | ((uint32_t)__ldg(m + k * 8 + 512) << 16);
        v[4] = (v[3] >> 16) | 0x42000000u; v[3] = (v[3] & 0xffff) | 0x42000000u;
    }
    *(uint4*)(acc_base() + X * 32768 + acc_slot(slot) + acc_main(rank, tid)) = make_uint4(v[0], v[1], v[2], v[3]);
    *(uint32_t*)(acc_base() + X * 1024 + acc_slot(slot) + acc_extra(rank, tid)) = v[4];
}
__global__ void acc_init_kernel(const __nv_bfloat16* mem0) { acc_init(mem0, blockIdx.x * 256 + threadIdx.x); }

struct RecW { uint32_t am, ae, ah, dp, lp, lpw, vo, sb, bar, zero, ts, tn; };
__device__ __forceinline__ uint32_t vadd(uint32_t a, uint32_t b) { uint32_t d; asm volatile("add.u32 %0,%1,%2;" : "=r"(d) : "r"(a), "r"(b)); return d; }
__device__ __forceinline__ uint32_t vshr(uint32_t a, int n) { uint32_t d; asm volatile("shr.u32 %0,%1,%2;" : "=r"(d) : "r"(a), "r"(n)); return d; }
__device__ __forceinline__ uint64_t gptr(uint32_t lo, uint32_t hi) { uint64_t d; asm("mov.b64 %0,{%1,%2};" : "=l"(d) : "r"(lo), "r"(hi)); return d; }
__device__ __forceinline__ void sfence(uint32_t zero) { asm volatile("{.reg .pred p; setp.ne.u32 p,%0,0; @p exit;}" ::"r"(zero) : "memory"); }
#define SF sfence(k.zero)
#define TS(i) do {} while (0)
#define TSN(i) do {} while (0)
#define TSET(it, slot) do {} while (0)
struct Gat { uint32_t x, y, z, w, e; };
template <int X>
__device__ __forceinline__ void gat_issue(Gat& g, const RecW& k, int s, uint32_t dep) {
    const uint32_t o = acc_slot(s + 3) + dep;
    asm volatile("{.reg .b128 t; ld.relaxed.gpu.global.b128 t,[%5+%7]; mov.b128 {%0,%1,%2,%3},t; ld.relaxed.gpu.global.u32 %4,[%6+%8];}"
                 : "=r"(g.x), "=r"(g.y), "=r"(g.z), "=r"(g.w), "=r"(g.e) : "l"(gptr(k.am + o, k.ah)), "l"(gptr(k.ae + o, k.ah)), "n"(X * 32768), "n"(X * 1024) : "memory");
}
template <int X>
__device__ __forceinline__ bool gat_store(const Gat& g, const RecW& k) {
    uint32_t c;
    asm volatile("prmt.b32 %0,%1,%2,0x7632;" : "=r"(c) : "r"(g.w), "r"(g.e));
    SF;
    asm volatile("{.reg .b32 t; prmt.b32 t,%4,%6,0x5410; stmatrix.sync.aligned.m8n8.x4.trans.shared.b16 [%0+%5],{%1,%2,%3,t};}" ::"r"(k.lpw), "r"(g.x), "r"(g.y), "r"(g.z), "r"(g.w), "n"(R_M + X * 4096), "r"(g.e) : "memory");
    return __all_sync(0xffffffffu, c == 0x42004200u);
}
template <int X>
__device__ __forceinline__ void gat_finish(bool ok, const RecW& k, int s) {
    if (!ok) {
        int n = s;
        while (true) {
            Gat g;
            gat_issue<X>(g, k, n, 0);
            if (gat_store<X>(g, k)) break;
            n += 4;
            if (n > 8000000) __trap();
        }
    }
}
__device__ __forceinline__ uint4 lds128o(uint32_t a, int o) { uint4 v; asm volatile("{.reg .b32 t; add.u32 t,%4,%5; ld.shared.v4.u32 {%0,%1,%2,%3},[t];}" : "=r"(v.x), "=r"(v.y), "=r"(v.z), "=r"(v.w) : "r"(a), "r"(o) : "memory"); return v; }
__device__ __forceinline__ uint4 ldsm4o(uint32_t a, int o) { uint4 v; asm volatile("{.reg .b32 t; add.u32 t,%4,%5; ldmatrix.sync.aligned.m8n8.x4.shared.b16 {%0,%1,%2,%3},[t];}" : "=r"(v.x), "=r"(v.y), "=r"(v.z), "=r"(v.w) : "r"(a), "r"(o) : "memory"); return v; }
#define WLD(base, i) wt[i] = lds128o(k.lpw, (base) + (i) * 4096)
template <int PASS, int X, int NP>
__device__ __forceinline__ void rec_qkv(const RecW& k, int s, const uint32_t (*wq)[4], const uint32_t (*wk)[4], uint4* wt, Gat& g2, int s2, bool& ok2) {
    constexpr bool BWD = PASS == 2, DIRECT = !(BKA && PASS == 1);
    float aq[4] = {0, 0, 0, 0}, ak[4] = {0, 0, 0, 0}, av[4] = {0, 0, 0, 0};
    constexpr int ma = R_M + X * 4096;
    if (BWD) { TS(1); gat_finish<1>(GSE ? ok2 : gat_store<1>(g2, k), k, s); }
    bar_sync(NB_MF + X, 256);
    uint4 mf = ldsm4o(k.lp, ma + (BWD ? 7 : 0) * 512);
    if (BWD) TS(2); else { TS(0); TSN(13); }
#pragma unroll
    for (int ii = 0; ii < 8; ii++) {
        const int i = BWD ? 7 - ii : ii;
        const uint4 m = mf;
        if (ii < 7) mf = ldsm4o(k.lp, ma + (BWD ? i - 1 : i + 1) * 512);
        if (PASS == 1 && ii == G2I) gat_issue<1>(g2, k, s2, 0);
        SF;
#pragma unroll
        for (int hh = 0; hh < 2; hh++) {
            const int h = BWD ? 1 - hh : hh, ks = 2 * i + h;
            const uint32_t b0 = h ? m.z : m.x, b1 = h ? m.w : m.y;
            mma16(aq, wq[ks][0], wq[ks][1], wq[ks][2], wq[ks][3], b0, b1);
            mma16(ak, wk[ks][0], wk[ks][1], wk[ks][2], wk[ks][3], b0, b1);
            SF;
            mma16(av, wt[ks].x, wt[ks].y, wt[ks].z, wt[ks].w, b0, b1);
            SF;
            if (!BWD && ks + NP < 16) WLD(R_WV, ks + NP < 16 ? ks + NP : 0);
            if (BWD && ks >= NT) WLD(R_WV, ks >= NT ? ks - NT : 0);
            SF;
        }
    }
    if (PASS == 1 && GSE) { ok2 = gat_store<1>(g2, k); SF; }
    const uint32_t ra = vadd(k.lpw, k.dp + R_REM + (X * 2 + (s & 1)) * 6144), va = ((vshr(k.lp, 7) & 1) * 48 ^ k.lp ^ (k.vo & 64)) + (k.vo & ~64u);
    const uint32_t x0 = movm(pack2(aq[0], aq[1])), x1 = movm(pack2(aq[2], aq[3])), x2 = movm(pack2(ak[0], ak[1])), x3 = movm(pack2(ak[2], ak[3]));
    SF;
    asm volatile("stmatrix.sync.aligned.m8n8.x2.shared.b16 [%0+%3],{%1,%2};" ::"r"(va), "r"(pack2(av[0], av[1])), "r"(pack2(av[2], av[3])), "n"(R_LOC + X * 6144) : "memory");
    SF;
    if (STO && DIRECT) st_async4(ra, x0, x1, x2, x3, k.bar + X * 16);
    asm volatile("st.shared.v4.u32 [%0+%5],{%1,%2,%3,%4};" ::"r"(k.lpw), "r"(x0), "r"(x1), "r"(x2), "r"(x3), "n"(R_LOC + X * 6144) : "memory");
    bar_arrive(NB_LOC + X, 320);
    if (!STO && DIRECT) st_async4(ra, x0, x1, x2, x3, k.bar + X * 16);
    SF;
    TS(BWD ? 4 : 3);
}
template <bool BWD, int X>
__device__ __forceinline__ void rec_out(const RecW& k, int s, uint4* wt, Gat& g, int s1) {
    if (BWD) { WLD(R_WO, 17 - NTO); WLD(R_WO, 16 - NTO); }
    TS(BWD ? 8 : 5);
    bar_sync(NB_O + X, 320);
    float r0[4] = {0, 0, 0, 0}, r1[4] = {0, 0, 0, 0};
    constexpr int oa = R_O + X * 2048;
    uint4 bn = lds128o(k.lp, oa + (BWD ? 3 : 0) * 512);
    TS(BWD ? 9 : 6);
    uint2 il;
    uint64_t pm, pe;
#pragma unroll
    for (int ii = 0; ii < 4; ii++) {
        const int i = BWD ? 3 - ii : ii;
        const uint4 b = bn;
        if (ii < 3) bn = lds128o(k.lp, oa + (BWD ? i - 1 : i + 1) * 512);
        else { asm volatile("ld.shared.v2.u32 {%0,%1},[%2+%3];" : "=r"(il.x), "=r"(il.y) : "r"(k.lp), "n"(R_IL + X * 8) : "memory"); pm = gptr(vadd(k.am, acc_slot(s)), k.ah); pe = gptr(vadd(k.ae, acc_slot(s)), k.ah); }
        SF;
        if (BWD && EARLY == ii + 1) { gat_issue<0>(g, k, s1 + 1, 0); SF; }
#pragma unroll
        for (int nn = 0; nn < 4; nn++) {
            const int n = BWD ? 3 - nn : nn, f = 4 * i + n, nx = BWD ? f - NTO + 2 : f + NTO - 2;
            mma16((n & 1) ? r1 : r0, wt[f].x, wt[f].y, wt[f].z, wt[f].w, n >> 1 ? b.z : b.x, n >> 1 ? b.w : b.y);
            SF;
            if (ii * 4 + nn >= 2 && nx >= 0 && nx < 16) WLD(R_WO, nx & 15);
            SF;
        }
    }
    const float i0 = __uint_as_float(il.x), i1 = __uint_as_float(il.y);
    asm volatile("red.relaxed.gpu.global.add.noftz.v4.bf16x2 [%0+%5],{%1,%2,%3,%4};" ::"l"(pm),
                 "r"(pack2(r0[0] * i0, r0[1] * i1)), "r"(pack2(r0[2] * i0, r0[3] * i1)), "r"(pack2(r1[0] * i0, r1[1] * i1)), "r"(pack2(r1[2] * i0, 1.f)), "n"(X * 32768) : "memory");
    asm volatile("red.relaxed.gpu.global.add.noftz.bf16x2 [%0+%2],%1;" ::"l"(pe), "r"(pack2(r1[3] * i1, 1.f)), "n"(X * 1024) : "memory");
    bar_arrive(NB_XG + X, 320);
    SF;
    TS(BWD ? 10 : 7);
}
__device__ __forceinline__ uint32_t pause(uint32_t v, int n) {
#pragma unroll
    for (int i = 0; i < n; i++) asm volatile("shfl.sync.bfly.b32 %0,%0,0,0x1f,0xffffffff;" : "+r"(v));
    return v;
}
template <bool DUAL, int X>
__device__ __forceinline__ void rec_step(const RecW& k, int s, int s2, const uint32_t (*wq)[4], const uint32_t (*wk)[4], uint4* wt) {
    constexpr int NP = NPD;
    uint4 wo[16];
    Gat g;
    bool ok2;
    rec_qkv<DUAL ? 1 : 0, X, NP>(k, s, wq, wk, wt, g, s2, ok2);
    if (DUAL) rec_qkv<2, 1, NP>(k, s2, wq, wk, wt, g, s2, ok2);
    uint32_t wa = k.lpw;
#pragma unroll
    for (int i = 0; i < NTO; i++) {
        wo[i] = lds128o(wa, R_WO + i * 4096);
        if (i % PACE == PACE - 1) wa = k.lpw + (wo[i].x & k.zero);
        SF;
    }
    rec_out<false, X>(k, s, wo, g, s);
    if (DUAL) { rec_out<true, 1>(k, s2, wo, g, s); if (!EARLY) gat_issue<0>(g, k, s + 1, 0); SF; }
#pragma unroll
    for (int i = 0; i < NP; i++) { WLD(R_WV, i); SF; }
    if (!DUAL) gat_issue<X>(g, k, s + 1, pause(wt[NP - 1].x & k.zero, DP1));
    TS(12);
    gat_finish<X>(gat_store<X>(g, k), k, s + 1);
    TS(11);
}

__device__ __forceinline__ void rec_fetch(const CUtensorMap* tm, uint32_t dst, int x, int y, int nx, uint32_t bar) {
#pragma unroll 1
    for (int j = 0; j < 8; j++) tma2d(dst + j * 8192, tm, x + (j / (8 / nx)) * 64, y + (j % (8 / nx)) * 64, bar);
}
__device__ __forceinline__ void rec_weights(const Params& p, uint32_t sb, int head, uint32_t rank, int w) {
    const int lane = threadIdx.x & 31, t = w & 3, WG = w >> 2;
    uint32_t wq[16][4], wk[16][4];
    const uint32_t rowo = (((lane >> 4) << 3) + (lane & 7)) * 128;
    const uint32_t woff = sb + WG * 32768 + rowo + (((2 * t + ((lane >> 3) & 1)) ^ (lane & 7)) << 4);
    const uint32_t qoff = sb + ((w & 1) ? R_STK : R_STQ) + WG * 32768 + rowo + (((2 * (t & 2) + ((lane >> 3) & 1)) ^ (lane & 7)) << 4);
    const uint32_t lw = sb + (lane ^ (lane >> 3)) * 16;
    PROF(threadIdx.x == 0, 3501);
    if (w >= 4 && p.dostats) { wait_cnt_warp(g_gate, lds32(sb + S_GATE)); x1_stats((head * 2 + rank) * 4 + w - 4); }
    PROF(threadIdx.x == 0, 3502);
    mbar_wait(sb + R_BAR + RB_INIT * 8, 0);
    PROF(threadIdx.x == 0, 3503);
#pragma unroll
    for (int ks = 0; ks < 16; ks++) {
        uint4 a = ldsm4t(qoff + ks * 2048), b = ldsm4t((qoff ^ 32) + ks * 2048);
        wq[ks][0] = a.x; wq[ks][1] = a.y; wq[ks][2] = a.z; wq[ks][3] = a.w;
        wk[ks][0] = b.x; wk[ks][1] = b.y; wk[ks][2] = b.z; wk[ks][3] = b.w;
    }
    bar_sync(NB_W, 256);
#pragma unroll 4
    for (int ks = 0; ks < 16; ks++) { const uint4 a = ldsm4t(woff + R_STV + ks * 2048); sts128(lw + w * 512 + R_WV + ks * 4096, a.x, a.y, a.z, a.w); }
    bar_sync(NB_W, 256);
    if (threadIdx.x == 0) {
        mbar_expect(sb + R_BAR + RB_INIT * 8, 65536);
        rec_fetch(&p.tm[4], sb + R_STV, rank * 256, head * 128, 4, sb + R_BAR + RB_INIT * 8);
    }
    __syncwarp();
    mbar_wait(sb + R_BAR + RB_INIT * 8, 1);
#pragma unroll 4
    for (int f = 0; f < 16; f++) {
        const uint4 a = ldsm4t(sb + R_STV + (w >> 1) * 16384 + (f >> 1) * 2048 + rowo + ((((w & 1) * 4 + (f & 1) * 2 + ((lane >> 3) & 1)) ^ (lane & 7)) << 4));
        sts128(lw + w * 512 + R_WO + f * 4096, a.x, a.y, a.z, a.w);
    }
    PROF(threadIdx.x == 0, 3504);
    __syncthreads();
    cluster_sync();
    PROF(threadIdx.x == 0, 3505);
    RecW k;
    k.am = __shfl_sync(0xffffffffu, (uint32_t)(size_t)acc_base() + acc_main(rank, threadIdx.x), lane);
    k.ae = __shfl_sync(0xffffffffu, (uint32_t)(size_t)acc_base() + acc_extra(rank, threadIdx.x), lane);
    k.ah = (uint32_t)((size_t)acc_base() >> 32);
    k.sb = sb; k.zero = p.zero;

    k.dp = mapa(sb, rank ^ 1) - sb;
    k.lp = __shfl_sync(0xffffffffu, lw, lane);
    k.lpw = __shfl_sync(0xffffffffu, lw + w * 512, lane);
    k.vo = 4096 + w * 256 + (w & 1) * 64;
    k.bar = sb + k.dp + R_BAR + (RB_QK + WG) * 8;
    int it = 0;
    uint4 wt[16];
#pragma unroll
    for (int i = 0; i < NPD; i++) WLD(R_WV, i);
    gat_finish<0>(false, k, 0);
#pragma unroll 1
    for (; it < min(p.b1, p.e0); it++) { TSET(it, w == GPW ? 0 : 3); rec_step<false, 0>(k, it, it, wq, wk, wt); }
#pragma unroll 1
    for (; it < p.e0; it++) { TSET(it, w == GPW ? 0 : 3); rec_step<true, 0>(k, it, it - p.b1, wq, wk, wt); }
    if (it < p.nit) gat_finish<1>(false, k, it - p.b1);
#pragma unroll 1
    for (; it < p.nit; it++) { TSET(it, w == GPW ? 0 : 3); rec_step<false, 1>(k, it - p.b1, it - p.b1, wq, wk, wt); }
}

__device__ __forceinline__ void mma16_top(float* c, uint32_t a0, uint32_t a2, uint32_t b0, uint32_t b1) {
    asm volatile("{.reg .b32 j; mma.sync.aligned.m16n8k16.row.col.f32.bf16.bf16.f32 {%0,%1,%2,%3},{%4,j,%5,j},{%6,%7},{%0,%1,%2,%3};}"
                 : "+f"(c[0]), "+f"(c[1]), "+f"(c[2]), "+f"(c[3]) : "r"(a0), "r"(a2), "r"(b0), "r"(b1));
}
__device__ __forceinline__ void rec_load_tile(uint32_t sb, int X, int s, int head, uint32_t rank) {
    const uint32_t bar = sb + R_BAR + (RB_T + X) * 8;
    const uint4* src = g_qkv[X] + (size_t)(s * 32 + head) * 1536;
    mbar_expect1(bar, TILE);
    bulk_g2s1(sb + R_T + X * TILE, src + 512, 16384, bar, POL_LAST);
    bulk_g2s1(sb + R_T + X * TILE + 16384, src + rank * 256, 4096, bar, POL_LAST);
}
__device__ __forceinline__ bool chunk_ready(int X, int s) {
    unsigned v;
    asm volatile("ld.relaxed.gpu.global.u32 %0,[%1];" : "=r"(v) : "l"(cnt_ptr(C_QKV0 + X, s >> 2)) : "memory");
    return __all_sync(0xffffffffu, v >= 384);
}
__device__ __forceinline__ uint4 hadd4(uint4 a, uint4 b) { return make_uint4(hadd2(a.x, b.x), hadd2(a.y, b.y), hadd2(a.z, b.z), hadd2(a.w, b.w)); }
struct RecH { uint32_t lw, lm, lq, lv, lu, sb, zero, ts, tn; };
__device__ __forceinline__ void rec_publish(int X, int s) {
    asm volatile("{.reg .pred p; cp.async.bulk.wait_group 0; elect.sync _|p,0xffffffff; @p red.relaxed.gpu.global.add.u32 [%0],4;}" ::"l"(cnt_ptr(C_O0 + X, s >> 2)) : "memory");
}
__device__ __forceinline__ void rec_mattn(const RecH& k, uint32_t dp, int X, int j, int s, bool qk, uint4 (*V)[4], uint4* vm) {
    const uint32_t sb = k.sb, to = R_T + X * TILE + j * 2048, lo = R_LOC + X * 6144, ro = R_REM + (X * 2 + (s & 1)) * 6144;
    const uint32_t bar = sb + R_BAR + (X * 2 + j) * 8;
    uint4 K[2][4];
    mbar_wait(sb + R_BAR + (RB_T + X) * 8, s & 1);
    TS(1);
#pragma unroll
    for (int i = 0; i < 8; i++) K[i >> 2][i & 3] = ldsm4(k.lm + (to + (i >> 2) * 1024 + ((i >> 1) & 1) * 4096 + (i & 1) * 512));
    asm volatile("cp.async.bulk.wait_group 0;" ::: "memory");
    bar_sync(NB_LOC + X, 320);
    fence_async_smem();
    if (qk) asm volatile("{.reg .pred p; elect.sync _|p,0xffffffff; @p cp.async.bulk.shared::cluster.shared::cta.mbarrier::complete_tx::bytes [%0],[%1],2048,[%2];}"
                         ::"r"(sb + dp + ro + j * 2048), "r"(sb + lo + j * 2048), "r"(bar + dp + RB_QK * 8) : "memory");
    asm volatile("{.reg .pred p; elect.sync _|p,0xffffffff; @p cp.async.bulk.shared::cluster.shared::cta.mbarrier::complete_tx::bytes [%0],[%1],1024,[%2];}"
                 ::"r"(sb + dp + ro + 4096 + j * 1024), "r"(sb + lo + 4096 + j * 1024), "r"(bar + dp + RB_V * 8) : "memory");
    uint4 u[4];
#pragma unroll
    for (int i = 0; i < 4; i++) u[i] = ldsm4(k.lm + (lo + j * 2048 + i * 512));
    TS(2);
    mbar_wait(bar + RB_QK * 8, s & 1);
    TS(3);
    float S[5][4];
#pragma unroll
    for (int i = 0; i < 5; i++) S[i][0] = S[i][1] = S[i][2] = S[i][3] = 0;
    {
        uint4 r[4];
#pragma unroll
        for (int i = 0; i < 4; i++) r[i] = ldsm4(k.lm + (ro + j * 2048 + i * 512));
        SF;
#pragma unroll
        for (int e = 0; e < 2; e++) {
            uint4& km = u[2 * e + 1];
            const uint32_t q0 = hadd2(u[2 * e].x, r[2 * e].x), q1 = hadd2(u[2 * e].y, r[2 * e].y);
            mma16_top(S[0], q0, q1, K[e][0].x, K[e][0].y);
            km.x = hadd2(km.x, r[2 * e + 1].x); km.y = hadd2(km.y, r[2 * e + 1].y);
            SF;
            mma16_top(S[1], q0, q1, K[e][1].x, K[e][1].y);
            const uint32_t q2 = hadd2(u[2 * e].z, r[2 * e].z), q3 = hadd2(u[2 * e].w, r[2 * e].w);
            SF;
            mma16_top(S[2], q0, q1, K[e][2].x, K[e][2].y);
            km.z = hadd2(km.z, r[2 * e + 1].z); km.w = hadd2(km.w, r[2 * e + 1].w);
            SF;
            mma16_top(S[3], q0, q1, K[e][3].x, K[e][3].y);
            mma16_top(S[4], q0, q1, km.x, km.y);
            SF;
#pragma unroll
            for (int i = 0; i < 4; i++) { mma16_top(S[i], q2, q3, K[e][i].z, K[e][i].w); SF; }
            mma16_top(S[4], q2, q3, km.z, km.w);
            SF;
        }
    }
#define VLD(a, b) _Pragma("unroll") for (int i = (a); i < (b); i++) V[i >> 2][i & 3] = ldsm4t((k.lv ^ ((i & 1) * 0x20)) + (to + 8192 + (i >> 2) * 4096 + ((i >> 1) & 1) * 1024))
    VLD(0, VE);
    SF;
    const uint32_t sxr = R_SX + (X * 2 + j) * 2560, sxw = R_SX + (X * 2 + (j ^ 1)) * 2560;
    sts128(k.lw + sxw, __float_as_uint(S[0][0]), __float_as_uint(S[0][1]), __float_as_uint(S[1][0]), __float_as_uint(S[1][1]));
    SF;
    sts128(k.lw + (sxw + 512), __float_as_uint(S[2][0]), __float_as_uint(S[2][1]), __float_as_uint(S[3][0]), __float_as_uint(S[3][1]));
    SF;
    sts64(k.lw + (sxw + 1024), __float_as_uint(S[4][0]), __float_as_uint(S[4][1]));
    TS(4);
    bar_sync(NB_PAIR + X, 64);
    {
        const uint4 a = lds128(k.lw + sxr), b = lds128(k.lw + (sxr + 512));
        const uint2 c = lds64(k.lw + (sxr + 1024));
        SF;
        VLD(VE, VF);
        SF;
        S[0][0] += __uint_as_float(a.x); S[0][1] += __uint_as_float(a.y); S[1][0] += __uint_as_float(a.z); S[1][1] += __uint_as_float(a.w);
        S[2][0] += __uint_as_float(b.x); S[2][1] += __uint_as_float(b.y); S[3][0] += __uint_as_float(b.z); S[3][1] += __uint_as_float(b.w);
        S[4][0] += __uint_as_float(c.x); S[4][1] += __uint_as_float(c.y);
    }
    float m = fmaxf(fmaxf(fmaxf(S[0][0], S[0][1]), fmaxf(S[1][0], S[1][1])), fmaxf(fmaxf(S[2][0], S[2][1]), fmaxf(S[3][0], S[3][1])));
    m = fmaxf(m, fmaxf(S[4][0], S[4][1]));
    m = fmaxf(m, __shfl_xor_sync(0xffffffffu, m, 1));
    const float m2 = __shfl_xor_sync(0xffffffffu, m, 2);
    SF;
    VLD(VF, 8);
    uint32_t ok;
    asm volatile("{.reg .pred p; mbarrier.test_wait.parity.shared::cta.b64 p,[%1],%2; selp.u32 %0,1,0,p;}" : "=r"(ok) : "r"(bar + RB_V * 8), "r"(s & 1) : "memory");
    uint4 vr0 = ldsm4(k.lu + (ro + 4096 + j * 1024)), vr1 = ldsm4(k.lu + (ro + 4608 + j * 1024));
    vm[0] = ldsm4(k.lu + (lo + 4096 + j * 1024)); vm[1] = ldsm4(k.lu + (lo + 4608 + j * 1024));
    SF;
    TS(5);
    m = fmaxf(m, m2) * -SC_LOG2E;
    uint32_t P[5];
#pragma unroll
    for (int i = 0; i < 5; i++) P[i] = pack2(ex2(fmaf(S[i][0], SC_LOG2E, m)), ex2(fmaf(S[i][1], SC_LOG2E, m)));
    float o[4][4], l[4] = {0, 0, 0, 0};
    const uint32_t ONE = 0x3f803f80u;
    mma16_top(l, ONE, ONE, P[0], P[1]);
#pragma unroll
    for (int t = 0; t < 4; t++) { o[t][0] = o[t][1] = o[t][2] = o[t][3] = 0; mma16(o[t], V[0][t].x, V[0][t].y, V[0][t].z, V[0][t].w, P[0], P[1]); }
    mma16_top(l, ONE, ONE, P[2], P[3]);
#pragma unroll
    for (int t = 0; t < 4; t++) mma16(o[t], V[1][t].x, V[1][t].y, V[1][t].z, V[1][t].w, P[2], P[3]);
    if (!__all_sync(0xffffffffu, ok)) {
        mbar_wait(bar + RB_V * 8, s & 1);
        vr0 = ldsm4(k.lu + (ro + 4096 + j * 1024)); vr1 = ldsm4(k.lu + (ro + 4608 + j * 1024));
    }
    TS(6);
    vm[0] = hadd4(vm[0], vr0); vm[1] = hadd4(vm[1], vr1);
    mma8(l, ONE, ONE, P[4]);
    mma8(o[0], vm[0].x, vm[0].y, P[4]); mma8(o[1], vm[0].z, vm[0].w, P[4]); mma8(o[2], vm[1].x, vm[1].y, P[4]); mma8(o[3], vm[1].z, vm[1].w, P[4]);
    if (j == 0) sts64(k.lw + (R_IL + X * 8), __float_as_uint(rcp(l[0])), __float_as_uint(rcp(l[1])));
#pragma unroll
    for (int t = 0; t < 4; t += 2)
        asm volatile("stmatrix.sync.aligned.m8n8.x4.trans.shared.b16 [%0],{%1,%2,%3,%4};" ::"r"(k.lm + (R_O + X * 2048 + j * 1024 + t * 256)),
                     "r"(pack2(o[t][0], o[t][1])), "r"(pack2(o[t][2], o[t][3])), "r"(pack2(o[t + 1][0], o[t + 1][1])), "r"(pack2(o[t + 1][2], o[t + 1][3])) : "memory");
    bar_arrive(NB_O + X, 320);
    TS(7);
#pragma unroll
    for (int e = 0; e < 2; e++) sts128(k.lw + (ro + j * 2048 + e * 1024), u[2 * e + 1].x, u[2 * e + 1].y, u[2 * e + 1].z, u[2 * e + 1].w);
    mbar_expect1(bar + RB_QK * 8, 2048); mbar_expect1(bar + RB_V * 8, 1024);
}
template <int MT>
__device__ __forceinline__ void rec_xattn(const RecH& k, int X, int j, int s, int head, bool early, const uint4 (*V)[4], const uint4* vmm) {
    constexpr int NTL = 3 + 2 * MT;
    const uint32_t sb = k.sb, to = R_T + X * TILE + j * 2048, ro = R_REM + (X * 2 + (s & 1)) * 6144 + j * 2048;
    const uint32_t sxw = R_SX + (X * 2 + j) * 2560, sxr = R_SX + (X * 2 + (j ^ 1)) * 2560;
    float S[NTL][4];
#pragma unroll
    for (int i = 0; i < NTL; i++) S[i][0] = S[i][1] = S[i][2] = S[i][3] = 0;
#pragma unroll
    for (int e = 0; e < 2; e++) {
        const uint4 q0 = ldsm4(k.lq + (to + 16384 + e * 1024)), q1 = ldsm4((k.lq ^ 0x20) + (to + 16384 + e * 1024));
#pragma unroll
        for (int i = 0; i < NTL; i++) {
            const uint4 kk = i ? ldsm4(k.lm + (to + e * 1024 + ((i - 1) >> 1) * 4096 + ((i - 1) & 1) * 512)) : lds128(k.lw + (ro + e * 1024));
            mma16(S[i], q0.x, q0.y, q0.z, q0.w, kk.x, kk.y); mma16(S[i], q1.x, q1.y, q1.z, q1.w, kk.z, kk.w);
        }
    }
#pragma unroll
    for (int i = 0; i < NTL; i++) sts128(k.lw + (sxw + i * 512), __float_as_uint(S[i][0]), __float_as_uint(S[i][1]), __float_as_uint(S[i][2]), __float_as_uint(S[i][3]));
    SF;
    bar_sync(NB_PAIR + X, 64);
    TS(9);
    if (early) rec_load_tile(sb, X, s + 1, head, MT);
#pragma unroll
    for (int i = 0; i < NTL; i++) {
        const uint4 r = lds128(k.lw + (sxr + i * 512));
        S[i][0] += __uint_as_float(r.x); S[i][1] += __uint_as_float(r.y); S[i][2] += __uint_as_float(r.z); S[i][3] += __uint_as_float(r.w);
    }
    const int g = (k.lw >> 6) & 7, c = ((k.lw >> 4) ^ (k.lw >> 7)) & 3;
    const float NEG = -__int_as_float(0x7f800000);
    if (2 * c > g) { S[NTL - 2][0] = NEG; S[NTL - 1][2] = NEG; }
    if (2 * c + 1 > g) { S[NTL - 2][1] = NEG; S[NTL - 1][3] = NEG; }
    float m0 = fmaxf(S[0][0], S[0][1]), m1 = fmaxf(S[0][2], S[0][3]);
#pragma unroll
    for (int i = 1; i < NTL; i++) { if (i < NTL - 1) m0 = fmaxf(m0, fmaxf(S[i][0], S[i][1])); m1 = fmaxf(m1, fmaxf(S[i][2], S[i][3])); }
    m0 = fmaxf(m0, __shfl_xor_sync(0xffffffffu, m0, 1)); m1 = fmaxf(m1, __shfl_xor_sync(0xffffffffu, m1, 1));
    m0 = fmaxf(m0, __shfl_xor_sync(0xffffffffu, m0, 2)); m1 = fmaxf(m1, __shfl_xor_sync(0xffffffffu, m1, 2));
    m0 *= -SC_LOG2E; m1 *= -SC_LOG2E;
    uint32_t P[NTL][2];
#pragma unroll
    for (int i = 0; i < NTL; i++) {
        P[i][0] = i < NTL - 1 ? pack2(ex2(fmaf(S[i][0], SC_LOG2E, m0)), ex2(fmaf(S[i][1], SC_LOG2E, m0))) : 0u;
        P[i][1] = pack2(ex2(fmaf(S[i][2], SC_LOG2E, m1)), ex2(fmaf(S[i][3], SC_LOG2E, m1)));
    }
    float l[4] = {0, 0, 0, 0};
#pragma unroll
    for (int i = 0; i < NTL; i++) mma8(l, P[i][0], P[i][1], 0x3f803f80u);
    const float l0 = rcp(l[0]), l1 = rcp(l[2]);

    const uint32_t st = sb + sxr + c * 128 + g * 16;
#pragma unroll
    for (int e = 0; e < 2; e++) {
        const uint4 vm = vmm[e];
        uint32_t u[2][4];
#pragma unroll
        for (int n = 0; n < 4; n++) {
            float a[4] = {0, 0, 0, 0};
#pragma unroll
            for (int m = 0; m <= MT; m++) {
                const uint4 v = V[m][e * 2 + (n >> 1)];
                mma8(a, P[1 + 2 * m][0], P[1 + 2 * m][1], (n & 1) ? v.y : v.x); mma8(a, P[2 + 2 * m][0], P[2 + 2 * m][1], (n & 1) ? v.w : v.z);
            }
            mma8(a, P[0][0], P[0][1], n == 0 ? vm.x : n == 1 ? vm.y : n == 2 ? vm.z : vm.w);
            u[0][n] = pack2(a[0] * l0, a[1] * l0); u[1][n] = pack2(a[2] * l1, a[3] * l1);
        }
        sts128(st + e * 512, u[0][0], u[0][1], u[0][2], u[0][3]); sts128(st + e * 512 + 1024, u[1][0], u[1][1], u[1][2], u[1][3]);
    }
    TS(10);
}
__device__ __forceinline__ void rec_attn(const Params& p, uint32_t sb, int X, int j, int head, uint32_t rank) {
    const int lane = threadIdx.x & 31;
    RecH k;
    k.lw = __shfl_sync(0xffffffffu, sb + (lane ^ (lane >> 3)) * 16, lane);
    k.lm = __shfl_sync(0xffffffffu, sb + ((lane & 7) * 4 + ((lane >> 3) ^ ((lane & 7) >> 1))) * 16, lane);
    k.lq = __shfl_sync(0xffffffffu, sb + ((lane >> 3) & 1) * 512 + ((lane & 7) * 4 + ((lane >> 4) ^ ((lane & 7) >> 1))) * 16, lane);
    k.lv = __shfl_sync(0xffffffffu, sb + (lane >> 4) * 512 + ((lane & 7) * 4 + (((lane >> 3) & 1) ^ ((lane & 7) >> 1))) * 16, lane);
    k.lu = __shfl_sync(0xffffffffu, sb + ((lane & 6) * 4 + (((lane >> 3) * 2 + (lane & 1)) ^ (lane & 6))) * 16, lane);
    k.sb = sb; k.zero = p.zero;
    const uint32_t dp = mapa(sb, rank ^ 1) - sb;
    char* zp = acc_base() + (j ? X * 32768 + acc_main(rank, head * 8) : X * 1024 + acc_extra(rank, head * 8));
    mbar_expect1(sb + R_BAR + (RB_QK + X * 2 + j) * 8, 2048); mbar_expect1(sb + R_BAR + (RB_V + X * 2 + j) * 8, 1024);
    bool early = j;
#pragma unroll 1
    for (int s = 0; s < 64; s++) {
        TSET(X ? s + p.b1 : s, j == GPJ ? 1 + X : 3);
        TS(0);
        if (!early && !j) { wait_cnt_warp(cnt_ptr(C_QKV0 + X, s >> 2), 384); rec_load_tile(sb, X, s, head, rank); }
        early = !j && s < 63 && ((s & 3) != 3 || chunk_ready(X, s + 1));
        PROF(lane == 0 && j == 0, X * 64 + s);
        uint4 V[2][4], vm[2];
        rec_mattn(k, dp, X, j, s, BKA && !X && s >= p.b1, V, vm);
        bar_sync(NB_XG + X, 320);
        TS(8);
        if (rank) rec_xattn<1>(k, X, j, s, head, early, V, vm); else rec_xattn<0>(k, X, j, s, head, early, V, vm);
        fence_async_smem();
        __syncwarp();
        asm volatile("{.reg .pred p; elect.sync _|p,0xffffffff;\n"
                     "@p cp.async.bulk.global.shared::cta.bulk_group.L2::cache_hint [%0],[%1],2048,%2;\n"
                     "@p cp.async.bulk.global.shared::cta.bulk_group [%3],[%4],%5;\n"
                     "cp.async.bulk.commit_group;}"
                     ::"l"(g_o[X] + ((s >> 2) * 64 + head * 2 + j) * 1024 + ((s & 3) * 2 + rank) * 128), "r"(sb + R_SX + (X * 2 + (j ^ 1)) * 2560),
                       "l"((X && s < 40) ? POL_LATE : POL_SOON), "l"(zp + acc_slot(s + 2)), "r"(sb + R_Z), "r"(j ? 128 : 32) : "memory");
        if ((s & 3) == 3) rec_publish(X, s);
    }
}

__device__ __forceinline__ void rec_init(const Params& p, uint32_t sb, int head, uint32_t rank) {
    const uint32_t b = sb + R_BAR;
    const int i = threadIdx.x - 320;
    if (i >= 0 && i < RB_N) {
        mbar_init(b + i * 8, 1);
        asm volatile("fence.mbarrier_init.release.cluster;" ::: "memory");
    }
    if (i == 0) mbar_expect(b + RB_INIT * 8, 196608);
    if (i >= 0 && i < 32) sts32(sb + R_Z + i * 4, 0);
}

#define NSTGN 8
constexpr int NSTG = NSTGN, STG_B = 24576;
#define LAGQ 1
#define LAGH 4
constexpr int NSB = 8;
constexpr int B_OUT = NSTG * STG_B  , B_UT = B_OUT, B_YT = B_UT + 16384, B_SP = B_YT  ,
              B_ST = 229376  , B_BAR = 231936;
static_assert(B_OUT + NSB * 4096 <= B_ST && B_ST + 2048 <= B_BAR && B_YT + 10240 <= B_ST, "smem map");
enum { BB_FULL = 0, BB_EMPTY = 8, BB_SF = 16  , BB_GO = 18, BB_DONE = 20  , BB_IDLE = 22  , BB_N = 30 };
enum { NB_C = 11, NB_WG = 12   };

__device__ __forceinline__ void bulk_init(uint32_t sb) {
    const int i = threadIdx.x - 320;
    if (i >= 0 && i < BB_N) {
        mbar_init(sb + B_BAR + i * 8, (i >= BB_EMPTY && i < BB_EMPTY + NSTG) ? 4 : i >= BB_DONE ? 4 : 1);
        asm volatile("fence.mbarrier_init.release.cluster;" ::: "memory");
    }
}

struct Task { int type, layer, ch, a, b, c, blk; bool pair, dry; };
__device__ __forceinline__ Task task_of(uint32_t tk, uint32_t rank) {
    Task t;
    t.type = tk & 7; t.layer = (tk >> 3) & 1; t.a = (tk >> 8) & 255; t.b = (tk >> 16) & 255; t.c = (tk >> 24) & 127; t.dry = tk >> 31;
    t.pair = t.type <= T_OP && (t.c & 64);
    t.ch = ((tk >> 4) & 15) + (t.pair ? rank : 0);
    t.blk = t.type == T_QKV ? 2 * (t.a + (t.pair ? 0 : rank * t.b)) : 192 + (t.pair ? (t.c >> 2) & 4 : rank * 4);
    return t;
}
__device__ __forceinline__ void bulk_producer(const Params& p, uint32_t sb, int cl, uint32_t rank) {
    int st = 0; uint32_t ph = 1;
    bool gated = false;
#define ACQ(bytes) do { mbar_wait(sb + B_BAR + (BB_EMPTY + st) * 8, ph); mbar_expect1(sb + B_BAR + (BB_FULL + st) * 8, bytes); } while (0)
#define NEXT do { if (++st == NSTG) { st = 0; ph ^= 1; } } while (0)
#pragma unroll 1
    for (int ti = 0; ti < MAXT; ti++) {
        const Task t = task_of(p.task[cl][ti], rank);
        const int layer = t.layer, ch = t.ch;
        if (t.type == T_END) break;
        if (t.type <= T_OP) {
            const bool qkv = t.type == T_QKV;
            const int rg = qkv ? (layer * 16 + ch) * 128 : 4096 + ((layer * 16 + ch) * 64 + t.a) * 16;
            const int nh = qkv ? 16 : 2 * t.b, row = qkv ? 0 : t.a * 64, bytes = qkv ? 16384 : STG_B;
            const unsigned* dep = cnt_ptr(qkv ? (layer ? C_CV : C_ST) : C_O0 + layer, ch);
            const unsigned need = qkv ? 16 << layer : 512;
            const uint64_t pol = qkv ? POL_N : POL_LAST;
            const CUtensorMap *tb = &p.t3[t.pair || qkv][t.blk >> 6], *ta = &p.ta[t.pair];
            const uint32_t db = sb + 8192 + (t.pair && !qkv ? rank * 8192 : 0), da = sb + (t.pair ? 0 : rank * 4096);
            const int zb = (t.blk & 63) + (t.pair && !qkv ? rank * 2 : 0), ya = rg + (t.pair ? 0 : rank * 8);
            const uint16_t mb = t.pair ? 3 : 1 << rank, ma = t.pair ? 1 << rank : 3;
            const int skip = t.pair && qkv ? rank ^ 1 : 2;
            int pend = qkv ? 2 : 0;
            bool wait = false;
            if (!t.dry) {
                unsigned v = 0;
                if (gated) asm volatile("ld.relaxed.gpu.global.u32 %0,[%1];" : "=r"(v) : "l"(dep) : "memory");
                wait = !__all_sync(0xffffffffu, v >= need);
                if (wait) pend = min(nh, gated ? NSTG : 4);
            }
#pragma unroll 1
            while (qkv && st) { ACQ(0); NEXT; }
            int h = 0;
            const int s0 = st;
#pragma unroll 1
            for (; h < pend; h++) {
                ACQ(bytes + (qkv && h < 2 ? (layer ? 8192 : 1024) : 0));
                if ((h & 1) != skip) tma3d_mc(db + st * STG_B, tb, row + h * 32, zb, sb + B_BAR + (BB_FULL + st) * 8, mb);
                NEXT;
            }
            if (wait) {
                if (!gated) { wait_cnt_warp(g_gate, lds32(sb + S_GATE)); gated = true; }
                wait_cnt_warp(dep, need);
            }
#pragma unroll 1
            for (int k = 0; k < pend; k++) {
                const int s2 = s0 + k - (s0 + k >= NSTG ? NSTG : 0);
                if (qkv && k < 2) bulk_g2s1(sb + s2 * STG_B + 16384, g_st[layer] + ch * 2048 + k * layer * 1024, layer ? 8192 : 1024, sb + B_BAR + (BB_FULL + s2) * 8, POL_N);
                tma2d_mc(da + s2 * STG_B, ta, (k & 1) * 256, ya + (k >> 1) * 16, sb + B_BAR + (BB_FULL + s2) * 8, ma, pol);
            }
#pragma unroll 1
            for (; h < nh; h++) {
                ACQ(bytes);
                if ((h & 1) != skip) tma3d_mc(db + st * STG_B, tb, row + h * 32, zb, sb + B_BAR + (BB_FULL + st) * 8, mb);
                tma2d_mc(da + st * STG_B, ta, (h & 1) * 256, ya + (h >> 1) * 16, sb + B_BAR + (BB_FULL + st) * 8, ma, pol);
                NEXT;
            }
#pragma unroll 1
            for (h = 0; h < 4 && !qkv && !layer; h++) { ACQ(0); NEXT; }
            if (qkv) {
#pragma unroll 1
                for (h = 8; h < 8 * t.b; h++) {
                    const int blk = t.blk + (h >> 3) * 2;
                    ACQ(16384);
                    if (skip != 0) tma3d_mc(sb + st * STG_B, &p.t3[1][blk >> 6], (h & 7) * 64, blk & 63, sb + B_BAR + (BB_FULL + st) * 8, mb);
                    if (skip != 1) tma3d_mc(sb + st * STG_B + 8192, &p.t3[1][blk >> 6], (h & 7) * 64 + 32, blk & 63, sb + B_BAR + (BB_FULL + st) * 8, mb);
                    NEXT;
                }
            }
        } else if (t.type == T_CV) {
            const int q = t.a + rank;
            if (!gated && !t.dry) { wait_cnt_warp(g_gate, lds32(sb + S_GATE)); gated = true; }
            if (layer) {
                wait_cnt_warp(cnt_ptr(C_U, ch - 2), 32);
#pragma unroll 1
                for (int j = ch + 1; j >= 2; j--) {
                    ACQ(16 * PW * 4 + (j > 2 ? 4096 : 0));
                    bulk_g2s1(sb + st * STG_B, g_P + (((q >> 1) * 16 + j) * 2 + (q & 1)) * 16 * PW, 16 * PW * 4, sb + B_BAR + (BB_FULL + st) * 8, POL_N);
                    if (j > 2) bulk_g2s1(sb + st * STG_B + 12288, g_u + (((q >> 1) * 16 + ch + 1 - j) * 2 + (q & 1)) * 256, 4096, sb + B_BAR + (BB_FULL + st) * 8, POL_N);
                    NEXT;
                }
            } else {
#pragma unroll 1
                for (int j = min(ch, 1 + (ch & 1)); j >= 0; j--) {
                    if (j == 0 && ch >= 2) {
                        if (!t.dry) wait_cnt_warp(cnt_ptr(C_H, ch & ~1), 64);
#pragma unroll 1
                        for (int i = 0; i < ((ch & 1) || ch == 2 ? 1 : 2); i++) {
                            ACQ(16384);
                            bulk_g2s1(sb + st * STG_B, g_carry[i] + (ch * 16 + q) * 1024, 16384, sb + B_BAR + (BB_FULL + st) * 8, POL_LAST);
                            NEXT;
                        }
                    }
                    ACQ(32 * PW * 4);
                    bulk_g2s1(sb + st * STG_B, g_P + (q * 16 + j) * 32 * PW, 32 * PW * 4, sb + B_BAR + (BB_FULL + st) * 8, POL_N);
                    NEXT;
                }
            }
        }
    }
}

__device__ __forceinline__ uint4* qkv_dst(int layer, int ch, int w, int blk);
__device__ __forceinline__ uint4* op_dst(int layer, int ch, int slot, int w, uint32_t rank);
__device__ __forceinline__ uint64_t out_pol(int type, int layer, int ch) { return (type == T_QKV ? (!layer && ch > 1) : (layer && ch < 10)) ? POL_LATE : POL_SOON; }
__device__ __forceinline__ void bulk_release(const Params& p, uint32_t sb, int cl, uint32_t rank, int wg) {
    int nd = 0;
    for (int ti = 0; ti < MAXT; ti++) {
        const Task t = task_of(p.task[cl][ti], rank);
        const int type = t.type, layer = t.layer, ch = t.ch;
        if (type == T_END) break;
        if (type == T_FIN || (type == T_OP && (t.c & 32))) continue;
        if (type == T_OP && !layer) {
            mbar_wait(sb + B_BAR + (BB_DONE + wg) * 8, nd & 1);
            nd++;
            const int s0 = __shfl_sync(0xffffffffu, lds32(sb + B_ST + wg * 4), 0) + wg * 2;
            fence_async_smem();
#pragma unroll 1
            for (int w = 0; w < 4; w++)
                asm volatile("{.reg .pred p; elect.sync _|p,0xffffffff; @p cp.async.bulk.global.shared::cta.bulk_group.L2::cache_hint [%0],[%1],8192,%2;}"
                             ::"l"(op_dst(0, ch, t.c & 15, wg * 4 + w, rank)), "r"(sb + ((s0 + (w >> 1)) & (NSTG - 1)) * STG_B + (w & 1) * 8192), "l"(POL_SOON) : "memory");
            mbar_arrive1(sb + B_BAR + (BB_SF + wg) * 8);
            asm volatile("cp.async.bulk.commit_group; cp.async.bulk.wait_group.read 0;" ::: "memory");
#pragma unroll 1
            for (int i = 0; i < 8; i++) mbar_arrive1_cluster(mapa(sb + B_BAR + (BB_EMPTY + ((s0 + (i >> 2)) & (NSTG - 1))) * 8, i & 1));
            continue;
        }
        unsigned* cnt = cnt_ptr(type == T_QKV ? C_QKV0 + layer : type == T_OP ? C_OP1 : layer ? C_H : C_CV, ch);
#pragma unroll 1
        for (int u = 0; u < (type == T_QKV ? t.b : 1); u++) {
            const uint4* dst = type == T_QKV ? qkv_dst(layer, ch, wg * 4, t.blk + 2 * u) : op_dst(1, ch, t.c & 15, wg * 4, (t.blk >> 2) & 1) + 256;
            mbar_wait(sb + B_BAR + (BB_DONE + wg) * 8, nd & 1);
            nd++;
            if (type != T_CV) {
                fence_async_smem();
#pragma unroll
                for (int w = 0; w < 4; w++)
                    asm volatile("{.reg .pred p; elect.sync _|p,0xffffffff; @p cp.async.bulk.global.shared::cta.bulk_group.L2::cache_hint [%0],[%1],4096,%2;}"
                                 ::"l"(dst + (type == T_QKV ? (w >> 1) * 49152 + (w & 1) * 256 : w * 1024)), "r"(sb + B_OUT + (wg * 4 + w) * 4096), "l"(out_pol(type, layer, ch)) : "memory");
                asm volatile("cp.async.bulk.commit_group; cp.async.bulk.wait_group 0;" ::: "memory");
            }
            if (type != T_QKV) fence_async();
            if (!t.dry) asm volatile("{.reg .pred p; elect.sync _|p,0xffffffff; @p red.relaxed.gpu.global.add.u32 [%0],%1;}" ::"l"(cnt), "r"(type == T_QKV ? 2 : type == T_OP ? t.b : 1) : "memory");
            if (type == T_CV && !layer && !t.dry) {
                asm volatile("{.reg .pred p; elect.sync _|p,0xffffffff; @p cp.async.bulk.global.shared::cta.bulk_group [%0],[%1],4096;\n"
                             "cp.async.bulk.commit_group; cp.async.bulk.wait_group 0; @p red.relaxed.gpu.global.add.u32 [%2],1;}"
                             ::"l"(g_u + ((t.a + rank) * 16 + ch) * 512 + wg * 256), "r"(sb + B_UT + (ch & 1) * 8192 + wg * 4096), "l"(cnt_ptr(C_U, ch)) : "memory");
            }
            mbar_arrive1(sb + B_BAR + (BB_SF + wg) * 8);
        }
        PROF(wg && (threadIdx.x & 31) == 0, 3600 + ti * 4 + 3);
    }
}

__device__ __forceinline__ void stage_release(uint32_t sb, int w, int st) {
    if (!(w & 2)) mbar_arrive1_cluster(mapa(sb + B_BAR + (BB_EMPTY + st) * 8, w & 1));
}
template <bool ACC>
__device__ __forceinline__ void gemm_run(float* acc, uint32_t sb, int w, int h0, int h1, uint32_t& r0, uint32_t& r1, int& st, uint32_t& ph) {
    const uint64_t da0 = mkdesc(sb + (w >> 2) * 4096, 128, 512, 0), db0 = mkdesc(sb + 8192, 4096, 1024, 1);
    const uint32_t rel0 = mapa(sb + B_BAR + BB_EMPTY * 8, w & 1);
#pragma unroll 1
    for (int h = h0; h < h1; h++) {
        const uint64_t da = da0 + st * (STG_B >> 4), db = db0 + st * (STG_B >> 4);
        mbar_wait(sb + B_BAR + (BB_FULL + st) * 8, ph);
        if (ACC) wg_wait<1>();
        wg_fence();
        wgmma256<ACC>(acc, da, db);
        wgmma256<true>(acc, da + 16, db + 128);
        wg_commit();
        if (ACC) mbar_arrive1_cluster((w == 2 && h == LAGH - 1) ? sb + B_BAR + BB_GO * 8 : r0);
        r0 = r1;
        if (!(w & 2)) r1 = rel0 + st * 8;
        if (++st == NSTG) { st = 0; ph ^= 1; }
    }
}

__device__ __forceinline__ uint4* qkv_dst(int layer, int ch, int w, int blk) {
    return g_qkv[layer] + (size_t)((ch * 4 + (w >> 1)) * 32 + ((blk & 63) >> 1)) * 1536 + (blk >> 6) * 512 + (w & 1) * 256;
}
__device__ __forceinline__ uint4* op_dst(int layer, int ch, int slot, int w, uint32_t rank) {
    return g_pp[layer] + (size_t)(ch * MAXSPLIT + slot) * 8192 + (w * 32 + rank * 16) * 32;
}
__device__ __forceinline__ uint32_t ln2(uint32_t x, uint32_t m, uint32_t rh, uint32_t rl) {
    uint32_t d; asm volatile("{.reg .b32 t,u; sub.rn.bf16x2 t,%1,%2; mul.rn.bf16x2 u,t,%4; fma.rn.bf16x2 %0,t,%3,u;}" : "=r"(d) : "r"(x), "r"(m), "r"(rh), "r"(rl)); return d;
}
__device__ __forceinline__ void qkv_task(uint32_t sb, int w, int layer, int nu, int ng, int& nd, uint32_t& ph) {
    static_assert(NSTG == 8, "ring");
    const int lane = threadIdx.x & 31;
    const uint64_t db0 = mkdesc(sb, 4096, 1024, 1);
    const uint32_t rel = (w & 2) ? sb + B_BAR + BB_IDLE * 8 : mapa(sb + B_BAR + BB_EMPTY * 8, w & 1), full = sb + B_BAR + BB_FULL * 8;
    const uint32_t la = sb + w * 1024 + ((lane >> 3) & 1) * 512 + (lane >> 4) * 128 + (lane & 7) * 16, lo = sb + B_OUT + w * 4096 + (lane ^ (lane >> 3)) * 16;
    uint32_t m0, m1, h0, h1, l0, l1;
    uint4 A[32];
    {
        mbar_wait(full, ph);
        mbar_wait(full + 8, ph);
        const uint32_t sa = sb + (lane >> 4) * STG_B + 16384 + (w * 16 + (lane & 15)) * 8;
        uint2 v = lds64(sa);
        float sm = __uint_as_float(v.x), M2 = __uint_as_float(v.y);
        if (layer) {
            float e[8];
            e[0] = sm;
#pragma unroll
            for (int i = 1; i < 8; i++) { v = lds64(sa + i * 1024); e[i] = __uint_as_float(v.x); sm += e[i]; M2 += __uint_as_float(v.y); }
            sm += __shfl_xor_sync(0xffffffffu, sm, 16);
#pragma unroll
            for (int i = 0; i < 8; i++) { const float d = e[i] * (1.f / 32.f) - sm * (1.f / 512.f); M2 += 32.f * d * d; }
            M2 += __shfl_xor_sync(0xffffffffu, M2, 16);
        }
        A[0] = ldsm4(la); A[1] = ldsm4(la + 256);
        const float2 o = ln_finish(sm * (1.f / 512.f), M2 * (1.f / 512.f));
        const float r = rcp(o.y), rh = rbf(r);
        const uint32_t mm = pack2(o.x, o.x), hl = pack2(r - rh, rh);
        m0 = __shfl_sync(0xffffffffu, mm, lane >> 2); m1 = __shfl_sync(0xffffffffu, mm, (lane >> 2) + 8);
        l0 = __shfl_sync(0xffffffffu, hl, lane >> 2); l1 = __shfl_sync(0xffffffffu, hl, (lane >> 2) + 8);
        h0 = __byte_perm(l0, 0, 0x3232); h1 = __byte_perm(l1, 0, 0x3232); l0 = __byte_perm(l0, 0, 0x1010); l1 = __byte_perm(l1, 0, 0x1010);
    }
    float acc[64];
#define QNRM(i) A[i] = make_uint4(ln2(A[i].x, m0, h0, l0), ln2(A[i].y, m1, h1, l1), ln2(A[i].z, m0, h0, l0), ln2(A[i].w, m1, h1, l1))
    if (w >> 2) mbar_wait(sb + B_BAR + BB_GO * 8, ~ng & 1);
#pragma unroll
    for (int h = 0; h < 16; h++) {
        const uint64_t db = db0 + ((h & 7) * (STG_B >> 4) + 512);
        if (h < 15) { A[(2 * h + 2) & 31] = ldsm4(la + ((h + 1) & 7) * STG_B); A[(2 * h + 3) & 31] = ldsm4(la + ((h + 1) & 7) * STG_B + 256); }
        const bool ok = h >= 14 || mbar_test(full + ((h + 2) & 7) * 8, ph ^ ((h + 2) >> 3));
        QNRM(2 * h); QNRM(2 * h + 1);
        if (h) wg_wait<1>();
        wg_fence();
        if (h) wgmma128r<true>(acc, A[2 * h], db); else wgmma128r<false>(acc, A[0], db);
        wgmma128r<true>(acc, A[2 * h + 1], db + 128);
        wg_commit();
        if (h >= 2) mbar_arrive1_cluster(rel + ((h - 2) & 7) * 8);
        if (h == LAGQ - 1 && w == 2) mbar_arrive1(sb + B_BAR + BB_GO * 8);
        if (!ok) mbar_wait(full + ((h + 2) & 7) * 8, ph ^ ((h + 2) >> 3));
    }
#pragma unroll 1
    for (int u = 1;; u++) {
        mbar_wait(sb + B_BAR + (BB_SF + (w >> 2)) * 8, (nd & 1) ^ 1);
        if (u < nu) mbar_wait(full, ph);
        wg_wait<1>();
        mbar_arrive1_cluster(rel + 48);
        wg_wait<0>();
        mbar_arrive1_cluster(rel + 56);
        uint4 o[8];
#pragma unroll
        for (int n = 0; n < 8; n++) {
            const float* a = acc + (n >> 1) * 16 + (n & 1) * 2;
            o[n] = make_uint4(pack2(a[0], a[1]), pack2(a[4], a[5]), pack2(a[8], a[9]), pack2(a[12], a[13]));
            sts128(lo + n * 512, o[n].x, o[n].y, o[n].z, o[n].w);
        }
        __syncwarp();
        mbar_arrive1(sb + B_BAR + (BB_DONE + (w >> 2)) * 8);
        nd++;
        if (u == nu) break;
#pragma unroll
        for (int h = 0; h < 8; h++) {
            const uint64_t db = db0 + h * (STG_B >> 4);
            if (h) { mbar_wait(full + h * 8, ph); wg_wait<1>(); }
            wg_fence();
            if (h) wgmma128r<true>(acc, A[4 * h], db); else wgmma128r<false>(acc, A[0], db);
            wgmma128r<true>(acc, A[4 * h + 1], db + 128);
            wgmma128r<true>(acc, A[4 * h + 2], db + 512);
            wgmma128r<true>(acc, A[4 * h + 3], db + 640);
            wg_commit();
            if (h >= 2) mbar_arrive1_cluster(rel + (h - 2) * 8);
        }
        ph ^= 1;
    }
}

template <int NB>
__device__ __forceinline__ void load_resid(uint32_t* r, int layer, int ch, int w, int cb) {
    const uint32_t* rp = (const uint32_t*)(g_xA[layer] + (ch * 8 + (cb >> 2)) * 1024 + w * 128 + (cb & 3) * 16) + (threadIdx.x & 31);
#pragma unroll
    for (int i = 0; i < NB * 4; i++) r[i] = __ldcg(rp + (i >> 1) * 32 + (i & 1) * 256);
}
template <int NS>
__device__ __forceinline__ void part_load(uint4* v, int layer, int ch, int w, int cb, int ns) {
    const uint4* src = g_pp[layer] + (size_t)ch * MAXSPLIT * 8192 + (w * 32 + cb) * 32 + (threadIdx.x & 31);
#pragma unroll
    for (int i = 0; i < 2 * NS; i++) {
        asm volatile("{.reg .pred p; .reg .b128 t; setp.gt.s32 p,%6,0; mov.b128 t,{0,0,0,0}; @p ld.relaxed.gpu.global.L2::cache_hint.b128 t,[%4],%5; mov.b128 {%0,%1,%2,%3},t;}"
                     : "=r"(v[i].x), "=r"(v[i].y), "=r"(v[i].z), "=r"(v[i].w) : "l"(src + (i / NS) * 32 + (i % NS) * 8192), "l"(POL_LAST), "r"(ns - i % NS) : "memory");
    }
}
template <int NS>
__device__ __forceinline__ void part_sum(float* x, const uint4* v, const uint32_t* r) {
    const int dg = ((threadIdx.x & 31) >> 2) - 2 * (threadIdx.x & 3);
    const uint32_t idm = dg == 0 ? 0x00003f80u : dg == 1 ? 0x3f800000u : 0u;
#pragma unroll
    for (int b = 0; b < 2; b++) {
        float* y = x + b * 8;
#pragma unroll
        for (int i = 0; i < 8; i++) y[i] = 0;
#pragma unroll
        for (int s = 0; s < NS; s++) { mma8(y, v[b * NS + s].x, v[b * NS + s].y, idm); mma8(y + 4, v[b * NS + s].z, v[b * NS + s].w, idm); }
#pragma unroll
        for (int i = 0; i < 4; i++) { y[2 * i] = rbf(rbf(y[2 * i]) + blo(r[b * 4 + i])); y[2 * i + 1] = rbf(rbf(y[2 * i + 1]) + bhi(r[b * 4 + i])); }
    }
}

__device__ __forceinline__ float4 row_stats32(const float* x) {
    float a = (x[0] + x[1]) + (x[4] + x[5]) + (x[8] + x[9]) + (x[12] + x[13]);
    float b = (x[2] + x[3]) + (x[6] + x[7]) + (x[10] + x[11]) + (x[14] + x[15]);
    a += __shfl_xor_sync(0xffffffffu, a, 1); b += __shfl_xor_sync(0xffffffffu, b, 1);
    a += __shfl_xor_sync(0xffffffffu, a, 2); b += __shfl_xor_sync(0xffffffffu, b, 2);
    const float ma = a * (1.f / 32.f), mb = b * (1.f / 32.f);
    float qa = 0, qb = 0;
#pragma unroll
    for (int i = 0; i < 4; i++) {
        float d0 = x[4 * i] - ma, d1 = x[4 * i + 1] - ma, d2 = x[4 * i + 2] - mb, d3 = x[4 * i + 3] - mb;
        qa += d0 * d0 + d1 * d1; qb += d2 * d2 + d3 * d3;
    }
    qa += __shfl_xor_sync(0xffffffffu, qa, 1); qb += __shfl_xor_sync(0xffffffffu, qb, 1);
    qa += __shfl_xor_sync(0xffffffffu, qa, 2); qb += __shfl_xor_sync(0xffffffffu, qb, 2);
    return make_float4(a, qa, b, qb);
}

__device__ __forceinline__ void conv_stage(float* Y, uint32_t pbase, uint32_t ubase) {
    const int lane = threadIdx.x & 31, w = threadIdx.x >> 5, g = lane >> 2, c = lane & 3;
#pragma unroll
    for (int cp = 0; cp < 2; cp++) {
        const int chl = w * 4 + cp * 2 + (lane >> 4);
        const uint4 b = ldsm4(ubase + chl * 256 + ((lane >> 3) & 1) * 128 + (((lane & 7) ^ (chl & 7)) << 4));
#pragma unroll
        for (int h = 0; h < 2; h++) {
            const uint32_t pa = pbase + ((w * 4 + cp * 2 + h) * PW + 16 + g - 2 * c) * 4;
            uint32_t lo = lds32(pa - 32);
#pragma unroll
            for (int d = 0; d < 8; d++) {
                const uint32_t a0 = lds32(pa + d * 64), a1 = lds32(pa + d * 64 + 32);
                mma16(Y + ((cp * 2 + h) * 8 + d) * 4, a0, a1, lo, a0, h ? b.z : b.x, h ? b.w : b.y);
                lo = a1;
            }
        }
    }
}

__device__ __forceinline__ void conv_combine(const float* y8, float* cur, float* nxt) {
    const int lane = threadIdx.x & 31, c = lane & 3;
    cur[0] = y8[0]; cur[1] = y8[1] + y8[4]; cur[2] = y8[2]; cur[3] = y8[3] + y8[6];
    nxt[0] = y8[29]; nxt[1] = 0.f; nxt[2] = y8[31]; nxt[3] = 0.f;
#pragma unroll
    for (int e = 1; e < 4; e++) {
        const int src = (lane & ~3) | ((c - e) & 3);
        const float v0 = __shfl_sync(0xffffffffu, y8[8 * e] + y8[8 * e - 3], src), v1 = __shfl_sync(0xffffffffu, y8[8 * e + 1] + y8[8 * e + 4], src);
        const float v2 = __shfl_sync(0xffffffffu, y8[8 * e + 2] + y8[8 * e - 1], src), v3 = __shfl_sync(0xffffffffu, y8[8 * e + 3] + y8[8 * e + 6], src);
        if (c >= e) { cur[0] += v0; cur[1] += v1; cur[2] += v2; cur[3] += v3; }
        else { nxt[0] += v0; nxt[1] += v1; nxt[2] += v2; nxt[3] += v3; }
    }
}

__device__ __forceinline__ void hist_task(float* Y, uint32_t sb, int w, int ch, int q, int& st, uint32_t& ph, int nd) {
    const int lane = threadIdx.x & 31, chl = w * 2 + (lane >> 4);
    const uint32_t ua = sb + 12288 + chl * 256 + ((lane >> 3) & 1) * 128 + (((lane & 7) ^ (chl & 7)) << 4);
    const uint32_t pa = sb + (w * 2 * PW + 16 + (lane >> 2) - 2 * (lane & 3)) * 4;
#pragma unroll
    for (int i = 0; i < 128; i++) Y[i] = 0;
    uint4 b1 = make_uint4(0, 0, 0, 0);
#pragma unroll 1
    for (int j = ch + 1; j >= 2; j--) {
        const uint4 b0 = b1;
        mbar_wait(sb + B_BAR + (BB_FULL + st) * 8, ph);
        b1 = ldsm4(ua + st * STG_B);
        if (j == 2) b1 = make_uint4(0, 0, 0, 0);
#pragma unroll
        for (int h = 0; h < 2; h++) {
            const uint32_t o = pa + st * STG_B + h * PW * 4;
            uint32_t lo = lds32(o - 32);
#pragma unroll
            for (int d = 0; d < 8; d++) {
                const uint32_t a0 = lds32(o + d * 64), a1 = lds32(o + d * 64 + 32);
                mma16(Y + (h * 16 + d) * 4, a0, a1, lo, a0, h ? b0.z : b0.x, h ? b0.w : b0.y);
                mma16(Y + (h * 16 + 8 + d) * 4, a0, a1, lo, a0, h ? b1.z : b1.x, h ? b1.w : b1.y);
                lo = a1;
            }
        }
        bar_sync(NB_WG + (w >> 2), 128);
        stage_release(sb, w, st);
        if (++st == NSTG) { st = 0; ph ^= 1; }
    }
    mbar_wait(sb + B_BAR + (BB_SF + (w >> 2)) * 8, (nd & 1) ^ 1);
#pragma unroll
    for (int h = 0; h < 2; h++) {
        const int o = ((ch * 16 + (q >> 1)) * 4 + (w & 1) * 2 + h) * 256 + ((q & 1) * 4 + (w >> 1)) * 32 + lane;
        float c0[4], n0[4], c1[4], n1[4];
        conv_combine(Y + h * 64, c0, n0); conv_combine(Y + h * 64 + 32, c1, n1);
        g_carry[0][o] = make_float4(c0[0], c0[1], c0[2], c0[3]);
        g_carry[0][o + 16384] = make_float4(c1[0] + n0[0], c1[1] + n0[1], c1[2] + n0[2], c1[3] + n0[3]);
        g_carry[1][o + 32768] = make_float4(n1[0], n1[1], n1[2], n1[3]);
    }
}

__device__ __forceinline__ void conv_task(const Params& p, float* Y, uint32_t sb, int w, int ch, int q, bool dry, int& st, uint32_t& ph, int nd) {
    const int tid = threadIdx.x, lane = tid & 31, g = lane >> 2, c = lane & 3;
    uint32_t dk[4];
    int sr = st;
    float x[16];
    uint32_t rs[8];
    load_resid<2>(rs, 0, ch, w, 2 * q);
    PROF(tid == 128, 2048 + ch * 8);
#pragma unroll
    for (int i = 0; i < 128; i++) Y[i] = 0;
#pragma unroll 1
    for (int j = min(ch, 1 + (ch & 1)); j >= 1; j--) {
        mbar_wait(sb + B_BAR + (BB_FULL + st) * 8, ph);
        conv_stage(Y, sb + st * STG_B, sb + B_UT + ((ch - j) & 1) * 8192);
        if (++st == NSTG) { st = 0; ph ^= 1; }
    }
    PROF(tid == 128, 2048 + ch * 8 + 7);
    {
        const uint32_t tag = lds32(sb + S_TAG);
        uint4 v[2 * OPS1];
        int n = 0;
        while (true) {
            part_load<OPS1>(v, 0, ch, w, 2 * q, OPS1);
            uint32_t bad = 0;
#pragma unroll
            for (int i = 0; i < 2 * OPS1; i++) bad |= v[i].x ^ tag;
            if (__all_sync(0xffffffffu, !(bad & 1) || dry)) break;
            if (++n > 1000000) __trap();
        }
        part_sum<OPS1>(x, v, rs);
        const float4 s = row_stats32(x);
        float2* dst = g_st2 + (ch * 16 + q) * 128 + w * 16 + g + c * 8;
        asm volatile("{.reg .pred p; setp.ne.u32 p,%2,0; @p st.relaxed.gpu.global.b64 [%0],%1;}" ::"l"(dst),
                     "l"(((uint64_t)__float_as_uint(c ? s.w : s.y) << 32) | __float_as_uint(c ? s.z : s.x)), "r"((uint32_t)(c < 2 && !dry)) : "memory");
        PROF(tid == 128, 2048 + ch * 8 + 1);
    }
#pragma unroll
    for (int i = 0; i < 4; i++) asm volatile("ld.global.nc.u32 %0,[%1];" : "=r"(dk[i]) : "l"(p.Dskip + q * 32 + i * 8 + 2 * c));
#pragma unroll 1
    for (int i = 0; i < min(ch, (ch & 1) ? 2 : 3); i++) {
        if (i) mbar_wait(sb + B_BAR + (BB_FULL + st) * 8, ph);
        const uint32_t ca = sb + (i ? st * STG_B : B_SP) + tid * 16;
#pragma unroll
        for (int k = 0; k < 4; k++) {
            const uint4 cr = lds128(ca + k * 4096);
            Y[k * 32] += __uint_as_float(cr.x); Y[k * 32 + 1] += __uint_as_float(cr.y); Y[k * 32 + 2] += __uint_as_float(cr.z); Y[k * 32 + 3] += __uint_as_float(cr.w);
        }
        if (i && ++st == NSTG) { st = 0; ph ^= 1; }
    }
    bar_sync(NB_C, 256);
#pragma unroll 1
    for (; sr != st; sr = (sr + 1) & (NSTG - 1)) stage_release(sb, w, sr);
    const uint32_t ut = sb + B_UT + (ch & 1) * 8192;
    mbar_wait(sb + B_BAR + (BB_SF + (w >> 2)) * 8, (nd & 1) ^ 1);
    mbar_wait(sb + B_BAR + (BB_SF + 1 - (w >> 2)) * 8, (nd & 1) ^ 1);
    float2 ln0, ln1;
    {
        const float2* src = g_st2 + (ch * 16 + (lane >> 4) * 8) * 128 + w * 16 + (lane & 15);
        uint64_t v[8];
        int n = 0;
        while (true) {
            bool bad = false;
#pragma unroll
            for (int i = 0; i < 8; i++) asm volatile("ld.relaxed.gpu.global.b64 %0,[%1];" : "=l"(v[i]) : "l"(src + i * 128) : "memory");
#pragma unroll
            for (int i = 0; i < 8; i++) bad = bad || (uint32_t)(v[i] >> 32) == 0xffffffffu;
            if (!__any_sync(0xffffffffu, bad && !dry)) break;
            if (++n > 2000000) __trap();
        }
        float sm = 0;
#pragma unroll
        for (int i = 0; i < 8; i++) sm += __uint_as_float((uint32_t)v[i]);
        sm += __shfl_xor_sync(0xffffffffu, sm, 16);
        const float mean = sm * (1.f / 512.f);
        float M2 = 0;
#pragma unroll
        for (int i = 0; i < 8; i++) { const float d = __uint_as_float((uint32_t)v[i]) * (1.f / 32.f) - mean; M2 += __uint_as_float((uint32_t)(v[i] >> 32)) + 32.f * d * d; }
        M2 += __shfl_xor_sync(0xffffffffu, M2, 16);
        const float2 o = ln_finish(mean, M2 * (1.f / 512.f));
        ln0.x = __shfl_sync(0xffffffffu, o.x, g); ln0.y = __shfl_sync(0xffffffffu, o.y, g);
        ln1.x = __shfl_sync(0xffffffffu, o.x, g + 8); ln1.y = __shfl_sync(0xffffffffu, o.y, g + 8);
    }
    PROF(tid == 128, 2048 + ch * 8 + 2);
    uint32_t u[8];
#pragma unroll
    for (int i = 0; i < 8; i++) {
        const float2 l = (i & 1) ? ln1 : ln0;
        u[i] = pack2(__fdividef(rbf(x[2 * i] - l.x), l.y), __fdividef(rbf(x[2 * i + 1] - l.x), l.y));
        const int chl = (i >> 1) * 8 + g;
        sts32(ut + chl * 256 + (i & 1) * 128 + ((w ^ g) << 4) + c * 4, movm(u[i]));
    }
    bar_sync(NB_C, 256);
    mbar_wait(sb + B_BAR + (BB_FULL + st) * 8, ph);
    PROF(tid == 128, 2048 + ch * 8 + 3);
    conv_stage(Y, sb + st * STG_B, ut);
    uint32_t yp[4][2];
    float nxt[4][4];
    {
        float y[4][4];
#pragma unroll
        for (int k = 0; k < 4; k++) conv_combine(Y + k * 32, y[k], nxt[k]);
#pragma unroll
        for (int i = 0; i < 4; i++) { yp[i][0] = pack2(y[0][i], y[1][i]); yp[i][1] = pack2(y[2][i], y[3][i]); }
    }
#pragma unroll
    for (int i = 0; i < 4; i++) sts64(sb + B_YT + (16 * (2 * c + (i & 1)) + g + (i >> 1) * 8) * 80 + w * 8, yp[i][0], yp[i][1]);
    bar_sync(NB_C, 256);
    stage_release(sb, w, st);
    if (++st == NSTG) { st = 0; ph ^= 1; }
    PROF(tid == 128, 2048 + ch * 8 + 4);
    uint32_t xo[8];
    uint32_t* dA = (uint32_t*)(g_xA[1] + (ch * 8 + (q >> 1)) * 1024 + (w * 2) * 64 + (q & 1) * 32) + lane;
#pragma unroll
    for (int i = 0; i < 8; i++) {
        const int col = (i >> 1) * 8 + 2 * c;
        const uint32_t yv = lds32(sb + B_YT + (w * 16 + g + (i & 1) * 8) * 80 + col * 2);
        const uint32_t dv = dk[i >> 1];
        x[2 * i] = rbf(x[2 * i] + rbf(blo(yv) + rbf(blo(u[i]) * blo(dv))));
        x[2 * i + 1] = rbf(x[2 * i + 1] + rbf(bhi(yv) + rbf(bhi(u[i]) * bhi(dv))));
        xo[i] = pack2(x[2 * i], x[2 * i + 1]);
        dA[(i >> 1) * 32 + (i & 1) * 256] = xo[i];
    }
    {
        const float4 s = row_stats32(x);
        float2* dst = g_st[1] + (ch * 16 + q) * 128 + w * 16 + g;
        if (c == 0) dst[0] = make_float2(s.x, s.y);
        if (c == 1) dst[8] = make_float2(s.z, s.w);
        __syncwarp();
    }
    PROF(tid == 128, 2048 + ch * 8 + 5);
    mbar_arrive1(sb + B_BAR + (BB_DONE + (w >> 2)) * 8);
    bar_sync(NB_C, 256);
#pragma unroll
    for (int k = 0; k < 4; k++) sts128(sb + B_SP + k * 4096 + tid * 16, __float_as_uint(nxt[k][0]), __float_as_uint(nxt[k][1]), __float_as_uint(nxt[k][2]), __float_as_uint(nxt[k][3]));
    PROF(tid == 128, 2048 + ch * 8 + 6);
}

__device__ __forceinline__ void out_store(const Params& p, const float* x, int ch, int cb) {
    const int lane = threadIdx.x & 31, w = threadIdx.x >> 5, g = lane >> 2, c = lane & 3;
#pragma unroll
    for (int h = 0; h < 2; h++) {
        const float* y = x + h * 2;
        uint32_t v0 = pack2(y[0], y[1]), v1 = pack2(y[4], y[5]), v2 = pack2(y[8], y[9]), v3 = pack2(y[12], y[13]);
        uint32_t t0 = (c & 1) ? v0 : v1, t1 = (c & 1) ? v2 : v3;
        t0 = __shfl_xor_sync(0xffffffffu, t0, 1); t1 = __shfl_xor_sync(0xffffffffu, t1, 1);
        if (c & 1) { v0 = t0; v2 = t1; } else { v1 = t0; v3 = t1; }
        t0 = (c & 2) ? v0 : v2; t1 = (c & 2) ? v1 : v3;
        t0 = __shfl_xor_sync(0xffffffffu, t0, 2); t1 = __shfl_xor_sync(0xffffffffu, t1, 2);
        if (c & 2) { v0 = t0; v1 = t1; } else { v2 = t0; v3 = t1; }
        stg128((uint4*)(p.out + (size_t)(ch * 128 + w * 16 + g + h * 8) * 512 + cb * 16 + c * 8), make_uint4(v0, v1, v2, v3), POL_LATE);
    }
}
__device__ __forceinline__ void fin_task(const Params& p, int ch, int cb0, int ncb, int ns, bool dry) {
    const int w = threadIdx.x >> 5;
    uint32_t rs[8];
    wait_cnt_warp(cnt_ptr(C_CV, ch), dry ? 0 : 32);
    load_resid<2>(rs, 1, ch, w, cb0);
    wait_cnt_warp(cnt_ptr(C_OP1, ch), dry ? 0 : 256);
    for (int cb = cb0; cb < cb0 + ncb; cb += 2) {
        float x[16];
        if (cb != cb0) load_resid<2>(rs, 1, ch, w, cb);
        uint4 v[32];
        part_load<16>(v, 1, ch, w, cb, ns);
        part_sum<16>(x, v, rs);
        out_store(p, x, ch, cb);
    }
}

__device__ __forceinline__ void bulk_consumer(const Params& p, uint32_t sb, int cl, uint32_t rank, int w) {
    int st = 0; uint32_t ph = 0; int nd = 0, ng = 0;
    for (int ti = 0; ti < MAXT; ti++) {
        const Task t = task_of(p.task[cl][ti], rank);
        const int type = t.type, layer = t.layer, ch = t.ch;
        if (type == T_END) break;
        bool staged = type != T_FIN;
        PROF(threadIdx.x == 0, 3600 + ti * 4);
        if (type <= T_OP) {
            CPROF(0);
            if ((w >> 2) && type == T_OP) mbar_wait(sb + B_BAR + BB_GO * 8, ng & 1);
            ng++;
            CPROF(1);
        }
        if (type == T_QKV) {
            staged = false;
            #pragma unroll 1
            while (st) {
                if (!(w & 3)) { mbar_wait(sb + B_BAR + (BB_FULL + st) * 8, ph); stage_release(sb, 0, st); stage_release(sb, 1, st); }
                if (++st == NSTG) { st = 0; ph ^= 1; }
            }
            qkv_task(sb, w, layer, t.b, ng, nd, ph);
            PROF(threadIdx.x == 128, 3600 + ti * 4 + 1);
        } else if (type == T_OP) {
            const int lane = threadIdx.x & 31;
            float acc[128];
            uint32_t r0 = sb + B_BAR + BB_IDLE * 8, r1 = r0;
            gemm_run<false>(acc, sb, w, 0, 1, r0, r1, st, ph);
            gemm_run<true>(acc, sb, w, 1, 2 * t.b, r0, r1, st, ph);
            mbar_wait(sb + B_BAR + (BB_SF + (w >> 2)) * 8, (nd & 1) ^ 1);
            wg_wait<1>();
            mbar_arrive1_cluster(r0);
            wg_wait<0>();
            mbar_arrive1_cluster(r1);
            PROF(threadIdx.x == 128, 3600 + ti * 4 + 1);
            if (t.c & 32) {
                staged = false;
#pragma unroll
                for (int j = 0; j < 16; j += 4) {
                    uint32_t rs[16];
                    load_resid<4>(rs, 1, ch, w, (t.blk & 4) * 4 + j);
#pragma unroll
                    for (int i = 0; i < 16; i++) { float* y = acc + j * 8 + 2 * i; y[0] = rbf(y[0]) + blo(rs[i]); y[1] = rbf(y[1]) + bhi(rs[i]); }
                    out_store(p, acc + j * 8, ch, (t.blk & 4) * 4 + j); out_store(p, acc + j * 8 + 16, ch, (t.blk & 4) * 4 + j + 2);
                }
            } else if (!layer) {
                const int s2 = st + (w >> 1);
                const uint32_t tag = lds32(sb + S_TAG), o = sb + (s2 & (NSTG - 1)) * STG_B + (w & 1) * 8192 + lane * 16;
                mbar_wait(sb + B_BAR + (BB_FULL + (s2 & (NSTG - 1))) * 8, ph ^ (s2 >= NSTG));
#pragma unroll
                for (int j = 0; j < 16; j++)
                    sts128(o + j * 512, (pack2(acc[j * 8], acc[j * 8 + 1]) & ~1u) | tag, pack2(acc[j * 8 + 2], acc[j * 8 + 3]), pack2(acc[j * 8 + 4], acc[j * 8 + 5]), pack2(acc[j * 8 + 6], acc[j * 8 + 7]));
                sts32(sb + B_ST + (w >> 2) * 4, st);
                st += 4;
                if (st >= NSTG) { st -= NSTG; ph ^= 1; }
            } else {
                uint4* dst = op_dst(layer, ch, t.c & 15, w, (t.blk >> 2) & 1) + lane;
#pragma unroll
                for (int n = 0; n < 16; n++) {
                    const int j = (n >> 1) + (n & 1) * 8;
                    const uint4 v = make_uint4(pack2(acc[j * 8], acc[j * 8 + 1]), pack2(acc[j * 8 + 2], acc[j * 8 + 3]), pack2(acc[j * 8 + 4], acc[j * 8 + 5]), pack2(acc[j * 8 + 6], acc[j * 8 + 7]));
                    if (j < 16 - NSB) stg128(dst + j * 32, v, out_pol(T_OP, layer, ch)); else sts128(sb + B_OUT + (w * NSB + j - (16 - NSB)) * 512 + lane * 16, v.x, v.y, v.z, v.w);
                }
            }
        } else if (type == T_CV) {
            float acc[128];
            if (layer) hist_task(acc, sb, w, ch, t.a + rank, st, ph, nd);
            else { conv_task(p, acc, sb, w, ch, t.a + rank, t.dry, st, ph, nd); staged = false; nd++; }
        } else {
            fin_task(p, ch, t.a + rank * t.c, t.c, t.b, t.dry);
        }
        if (staged) {
            __syncwarp();
            mbar_arrive1(sb + B_BAR + (BB_DONE + (w >> 2)) * 8);
            nd++;
        }
        CPROF(6);
        PROF(threadIdx.x == 128, 3600 + ti * 4 + 2);
        __syncwarp();
    }
}

constexpr int P_Y = 131072  , P_PRM = P_Y  , P_K6 = P_PRM + 8192  ,
              P_P = P_Y + 40960  , P_U = P_P + 33280  , P_END = P_U + 17408, P_X = 98304  ;
static_assert(P_END <= B_BAR && P_END <= R_BAR, "prologue scratch");
#define KGUN 2
constexpr int KGU = KGUN;
__device__ __forceinline__ void csq(float& r, float& i) { const float t = r * i; r = fmaf(r, r, -(i * i)); i = t + t; }
__device__ __forceinline__ void cpow(float ar, float ph, float p, float& r, float& i) {
    const float e = ex2(ar * p);
    const float u = ph * p, n = fabsf(u) < 4194304.f ? (u + 12582912.f) - 12582912.f : u;
    const float t = (u - n) * 6.283185307179586f;
    r = e * __cosf(t); i = e * __sinf(t);
}
__device__ __forceinline__ void mma_tf32(float* c, float a0, float a1, float a2, float a3, float b0, float b1) {
    asm volatile("mma.sync.aligned.m16n8k8.row.col.f32.tf32.tf32.f32 {%0,%1,%2,%3},{%4,%5,%6,%7},{%8,%9},{%0,%1,%2,%3};"
                 : "+f"(c[0]), "+f"(c[1]), "+f"(c[2]), "+f"(c[3])
                 : "r"(__float_as_uint(a0)), "r"(__float_as_uint(a1)), "r"(__float_as_uint(a2)), "r"(__float_as_uint(a3)), "r"(__float_as_uint(b0)), "r"(__float_as_uint(b1)));
}

struct ProRegs { uint32_t v[2][4], ldt[2]; };
__device__ __forceinline__ void prologue_load(const ProArgs& a, int b, ProRegs& pr) {
    const int w = threadIdx.x >> 5;
#pragma unroll
    for (int i = 0; i < 2; i++) {
        const int gi = b * 512 + (w & 3) * 128 + ((w >> 2) & 1) * 64 + i * 32 + (threadIdx.x & 31);
        pr.ldt[i] = __ldg((const uint16_t*)a.ldt + b * 4 + (w & 3));
        pr.v[i][0] = __ldg((const uint16_t*)a.lAr + gi); pr.v[i][1] = __ldg((const uint16_t*)a.Ai + gi);
        pr.v[i][2] = __ldg((const uint16_t*)a.Cr + gi); pr.v[i][3] = __ldg((const uint16_t*)a.Ci + gi);
    }
}
__device__ __forceinline__ void prologue(const ProArgs& a, uint32_t sb, int b, int w, const ProRegs& pr) {
    const int tid = threadIdx.x, lane = tid & 31, g = lane >> 2, c = lane & 3;
    const int d0 = b * 4;
    if (w >= 8) {
        const int t2 = tid - 256;
        if (w < 10) {
            const int row = b * 16 + (w - 8) * 8 + g;
            const float2 r = row_stats512((const uint4*)(a.x + (size_t)row * 512) + c, 8, 4);
            const float2 l = ln_finish(r.x * (1.f / 512.f), r.y * (1.f / 512.f));
            if (c == (g >> 1)) asm volatile("st.relaxed.gpu.global.u32 [%0],%1;" ::"l"(g_ln0 + row), "r"(pack2(l.x, l.y)) : "memory");
        }
        PROF(t2 == 0, 3516);
        const int gi = b * 128 + t2;
        if (t2 < 32) acc_init(a.mem0, b * 32 + t2);
        ((uint4*)g_st2)[gi] = make_uint4(~0u, ~0u, ~0u, ~0u);
        if (gi < 9 * 16 * 32) g_cnt[gi] = 0;
        bar_sync(6, 384);
        {
            const int u = b * 3 + (w - 8), blk = u >> 1;
            const uint4* W = w < 11 ? (const uint4*)((blk < 64 ? a.Wq : blk < 128 ? a.Wk : a.Wv) + (size_t)((u & 1) * 256 + c) * 4096 + (blk & 63) * 64) + g
                                    : (const uint4*)a.Wo + (size_t)b * 2048 + lane;
            const int st = w < 11 ? 2048 : 32;
            const uint32_t one = (g & 1) ? 0x3f800000u : 0x00003f80u, selA = (g & 2) ? 0u : one, selB = (g & 2) ? one : 0u;
            float s0[4] = {0, 0, 0, 0}, s1[4] = {0, 0, 0, 0};
#pragma unroll 1
            for (int r = 0; r < 8; r++) {
                uint4 v[8];
#pragma unroll
                for (int i = 0; i < 8; i++) v[i] = __ldg(W + (size_t)(r * 8 + i) * st);
#pragma unroll
                for (int i = 0; i < 8; i++) mma16((i & 1) ? s1 : s0, v[i].x, v[i].y, v[i].z, v[i].w, selA, selB);
            }
            if (c < 2) *(float4*)(g_cs + (w < 11 ? (u & 1) * 12288 + blk * 64 : 24576) + g * 8 + c * 4) = make_float4(s0[0] + s1[0], s0[1] + s1[1], s0[2] + s1[2], s0[3] + s1[3]);
        }
        PROF(t2 == 0, 3517);
        return;
    }
#pragma unroll
    for (int i = 0; i < 2; i++) {
        const float dt = rbf(expf(blo(pr.ldt[i])));
        const float ar = -rbf(expf(blo(pr.v[i][0]))) * dt, ai = blo(pr.v[i][1]) * dt;
        sts128(sb + P_PRM + (w * 64 + i * 32 + lane) * 16, __float_as_uint(ar * 1.4426950408889634f), __float_as_uint(ai * 0.15915494309189535f),
               __float_as_uint(2.f * (blo(pr.v[i][2]) * dt)), __float_as_uint(2.f * (blo(pr.v[i][3]) * dt)));
    }
    if (tid < 64) sts128(sb + P_U + (tid >> 3) * 2176 + (tid & 7) * 16, 0, 0, 0, 0);
    bar_arrive(6, 384);
    __syncwarp();
    PROF(tid == 0, 3510);
    const int ch = w & 3, hf = w >> 2;
    {
        float k0[4] = {0, 0, 0, 0}, k1[4] = {0, 0, 0, 0}, k2[4] = {0, 0, 0, 0}, k3[4] = {0, 0, 0, 0}, k4[4] = {0, 0, 0, 0}, kl = 0;
#pragma unroll KGU
        for (int j = 0; j < 16; j++) {
            const uint4 q = lds128(sb + P_PRM + (w * 64 + j * 4 + c) * 16);
            const float cr = __uint_as_float(q.z), ci = __uint_as_float(q.w);
            float wr[4], wi[4], vr[4], vi[4];
            cpow(__uint_as_float(q.x), __uint_as_float(q.y), (float)g, wr[0], wi[0]);
            cpow(__uint_as_float(q.x), __uint_as_float(q.y), (float)(g + 8), vr[0], vi[0]);
#pragma unroll
            for (int i = 1; i < 4; i++) { wr[i] = wr[i - 1]; wi[i] = wi[i - 1]; csq(wr[i], wi[i]); vr[i] = vr[i - 1]; vi[i] = vi[i - 1]; csq(vr[i], vi[i]); }
            float hr = wr[3], hi = wi[3];
            csq(hr, hi);
            mma_tf32(k0, wr[0], vr[0], wi[0], vi[0], cr * hr - ci * hi, -(cr * hi + ci * hr));
            hr = vr[3]; hi = vi[3]; csq(hr, hi);
            mma_tf32(k1, wr[0], vr[0], wi[0], vi[0], cr * hr - ci * hi, -(cr * hi + ci * hr));
            csq(hr, hi);
            mma_tf32(k2, wr[1], vr[1], wi[1], vi[1], cr * hr - ci * hi, -(cr * hi + ci * hr));
            csq(hr, hi);
            mma_tf32(k3, wr[2], vr[2], wi[2], vi[2], cr * hr - ci * hi, -(cr * hi + ci * hr));
            csq(hr, hi);
            mma_tf32(k4, wr[3], vr[3], wi[3], vi[3], cr * hr - ci * hi, -(cr * hi + ci * hr));
            csq(hr, hi);
            kl += cr * hr - ci * hi;
        }
        kl += __shfl_xor_sync(0xffffffffu, kl, 1); kl += __shfl_xor_sync(0xffffffffu, kl, 2);
        const uint32_t o = sb + P_K6 + (ch * 656 + c * 32 + g) * 4, ol = sb + P_K6 + (ch * 656 + 640) * 4;
#define KST(k, base) sts32(o + (base) * 4, __float_as_uint(k[0])); sts32(o + (base) * 4 + 64, __float_as_uint(k[1])); \
                     sts32(o + (base) * 4 + 32, __float_as_uint(k[2])); sts32(o + (base) * 4 + 96, __float_as_uint(k[3]))
#define KAD(k, base) k[0] += __uint_as_float(lds32(o + (base) * 4)); k[1] += __uint_as_float(lds32(o + (base) * 4 + 64)); \
                     k[2] += __uint_as_float(lds32(o + (base) * 4 + 32)); k[3] += __uint_as_float(lds32(o + (base) * 4 + 96))
        if (hf == 0) {
            bar_sync(2 + ch, 64);
            KAD(k0, 0); KAD(k1, 128); KAD(k2, 256); KAD(k3, 384); KAD(k4, 512);
            kl += __uint_as_float(lds32(ol));
            __syncwarp();
        }
        KST(k0, 0); KST(k1, 128); KST(k2, 256); KST(k3, 384); KST(k4, 512);
        if (lane == 0) sts32(ol, __float_as_uint(kl));
        if (hf == 1) { __syncwarp(); bar_arrive(2 + ch, 64); }
    }
    PROF(tid == 0, 3511);
    {
        uint4 l0, l1;
        int n = 0;
        while (true) {
            l0 = ld_rlx128((const uint4*)g_ln0 + tid * 2); l1 = ld_rlx128((const uint4*)g_ln0 + tid * 2 + 1);
            if (__all_sync(0xffffffffu, l0.x && l0.y && l0.z && l0.w && l1.x && l1.y && l1.z && l1.w)) break;
            if (++n > 2000000) __trap();
        }
        sts128(sb + P_P + tid * 32, l0.x, l0.y, l0.z, l0.w); sts128(sb + P_P + tid * 32 + 16, l1.x, l1.y, l1.z, l1.w);
        bar_sync(8, 384);
        mbar_wait(sb + S_XBAR, 0);
        __syncwarp();
#pragma unroll 2
        for (int i = 0; i < 8; i++) {
            const int t = w * 256 + i * 32 + lane;
            const uint32_t ln = lds32(sb + P_P + t * 4);
            const uint2 x = lds64(sb + P_X + t * 16 + (b & 1) * 8);
            const float m = blo(ln), rs = rcp(bhi(ln));
            const uint32_t u0 = pack2(rbf(blo(x.x) - m) * rs, rbf(bhi(x.x) - m) * rs), u1 = pack2(rbf(blo(x.y) - m) * rs, rbf(bhi(x.y) - m) * rs);
            sts128(sb + P_X + t * 16, x.x, x.y, u0, u1);
            const uint32_t o = sb + P_U + ((t >> 3) & 1) * 2176 + ((t >> 4) + 8) * 16 + (t & 7) * 2;
            asm volatile("st.shared.u16 [%0],%1;" ::"r"(o), "h"((uint16_t)u0) : "memory");
            asm volatile("st.shared.u16 [%0],%1;" ::"r"(o + 4352), "h"((uint16_t)(u0 >> 16)) : "memory");
            asm volatile("st.shared.u16 [%0],%1;" ::"r"(o + 8704), "h"((uint16_t)u1) : "memory");
            asm volatile("st.shared.u16 [%0],%1;" ::"r"(o + 13056), "h"((uint16_t)(u1 >> 16)) : "memory");
        }
    }
    bar_sync(1, 256);
    PROF(tid == 0, 3512);
    if (tid < 64) sts32(sb + P_P + ((tid >> 4) * 2080 + (tid & 15)) * 4, 0);
#pragma unroll 1
    for (int x = tid; x < 2048; x += 512) {
        uint32_t pw[2][4];
#pragma unroll
        for (int h = 0; h < 2; h++) {
            const int y = x + h * 256;
            const int i0 = y <= 256 ? y : 256 + (int)((pack2((float)y, 0.f) & 0xffff) - 0x4380);
            const int i1 = y <= 256 ? max(y - 1, 0) : 256 + (int)((pack2((float)(y - 1), 0.f) & 0xffff) - 0x4380);
#pragma unroll
            for (int k = 0; k < 4; k++) {
                const float lo = __uint_as_float(lds32(sb + P_K6 + k * 2624 + i0 * 4)), hi = __uint_as_float(lds32(sb + P_K6 + k * 2624 + i1 * 4));
                pw[h][k] = pack2(lo, y ? hi : 0.f);
            }
        }
#pragma unroll
        for (int h = 0; h < 2; h++)
#pragma unroll
            for (int k = 0; k < 4; k++) sts32(sb + P_P + (k * 2080 + x + h * 256 + 16) * 4, pw[h][k]);
    }
    fence_async_smem();
    bar_sync(1, 256);
    if (lane < 8) {
        const int k = w >> 1, j = (w & 1) * 8 + lane, d = d0 + k;
        asm volatile("cp.async.bulk.global.shared::cta.bulk_group [%0],[%1],%2;" ::"l"(g_P + (((d >> 5) * 16 + j) * 32 + (d & 31)) * PW),
                     "r"(sb + P_P + (k * 2080 + j * 128) * 4), "r"(PW * 4) : "memory");
        asm volatile("cp.async.bulk.commit_group;" ::: "memory");
    }
    __syncwarp();
    PROF(tid == 0, 3513);
    {
        float acc[16][4];
#pragma unroll
        for (int j = 0; j < 16; j++) acc[j][0] = acc[j][1] = acc[j][2] = acc[j][3] = 0;
#pragma unroll 1
        for (int e = hf * 4; e < hf * 4 + 4; e++) {
            uint32_t B[16][2];
            const uint32_t ua = sb + P_U + ch * 4352 + ((lane >> 3) & 1) * 2176 + (8 + (lane >> 4) * 8 + (lane & 7) - e) * 16;
#pragma unroll
            for (int j = 0; j < 8; j++) { const uint4 v = ldsm4(ua + j * 256); B[2 * j][0] = v.x; B[2 * j][1] = v.y; B[2 * j + 1][0] = v.z; B[2 * j + 1][1] = v.w; }
            const uint32_t pa = sb + P_P + (ch * 2080 + 16 + e * 16 + g - 2 * c) * 4;
#pragma unroll
            for (int d = 0; d < 16; d++) {
                const uint32_t a0 = lds32(pa + d * 512), a1 = lds32(pa + d * 512 + 32), a2 = lds32(pa + d * 512 - 32);
#pragma unroll
                for (int j = d; j < 16; j++) mma16(acc[j], a0, a1, a2, a0, B[j - d][0], B[j - d][1]);
            }
        }
        PROF(tid == 0, 3514);
        const uint32_t o = sb + P_Y + (ch * 2560 + c * 40 + g) * 4;
        if (hf == 0) {
            bar_sync(2 + ch, 64);
#pragma unroll
            for (int j = 0; j < 16; j++) {
                acc[j][0] += __uint_as_float(lds32(o + j * 640)); acc[j][1] += __uint_as_float(lds32(o + j * 640 + 80));
                acc[j][2] += __uint_as_float(lds32(o + j * 640 + 32)); acc[j][3] += __uint_as_float(lds32(o + j * 640 + 112));
            }
        }
#pragma unroll
        for (int j = 0; j < 16; j++) {
            sts32(o + j * 640, __float_as_uint(acc[j][0])); sts32(o + j * 640 + 80, __float_as_uint(acc[j][1]));
            sts32(o + j * 640 + 32, __float_as_uint(acc[j][2])); sts32(o + j * 640 + 112, __float_as_uint(acc[j][3]));
        }
        if (hf == 1) bar_arrive(2 + ch, 64);
    }
    const uint2 dk = __ldg((const uint2*)(a.Dk + d0));
    bar_sync(1, 256);
#pragma unroll 2
    for (int i = 0; i < 8; i++) {
        const int t = i * 256 + tid;
        const uint32_t o = sb + P_Y + (t + 4 * (t >> 4)) * 4;
        const uint4 xu = lds128(sb + P_X + t * 16);
        float y[4];
#pragma unroll
        for (int k = 0; k < 4; k++) y[k] = rbf(__uint_as_float(lds32(o + k * 10240)));
        uint2 r;
        r.x = pack2(blo(xu.x) + rbf(y[0] + rbf(blo(xu.z) * blo(dk.x))), bhi(xu.x) + rbf(y[1] + rbf(bhi(xu.z) * bhi(dk.x))));
        r.y = pack2(blo(xu.y) + rbf(y[2] + rbf(blo(xu.w) * blo(dk.y))), bhi(xu.y) + rbf(y[3] + rbf(bhi(xu.w) * bhi(dk.y))));
        ((uint2*)(g_xA[0] + ((t >> 7) * 8 + (d0 >> 6)) * 1024 + ((t & 127) >> 3) * 64 + ((d0 & 63) >> 3) * 8 + (t & 7)))[(d0 >> 2) & 1] = r;
    }
    PROF(tid == 0, 3515);
    if (lane < 8) asm volatile("cp.async.bulk.wait_group 0;" ::: "memory");
}

__global__ void __cluster_dims__(2, 1, 1) __launch_bounds__(384, 1) main_kernel(const __grid_constant__ Params p) {
    extern __shared__ __align__(1024) uint8_t smem[];
    const uint32_t sb = __shfl_sync(0xffffffffu, smem_u32(smem), 0);
    uint32_t rank; asm("mov.u32 %0,%%cluster_ctarank;" : "=r"(rank));
    const int wi = __shfl_sync(0xffffffffu, threadIdx.x >> 5, 0);
    const int cl = blockIdx.x >> 1, wg = wi >> 2;
    const bool rec = p.rec0 >= 0 && cl >= p.rec0 && cl < p.rec0 + 32;
    PROF(threadIdx.x == 0, 3500);
    ProRegs pr;
    prologue_load(p.pa, max((int)blockIdx.x - 4, 0), pr);
    if (rec) rec_init(p, sb, cl - p.rec0, rank); else bulk_init(sb);
    if (threadIdx.x == 352 && p.dopro && cl >= 2) {
        mbar_init(sb + S_XBAR, 1);
        asm volatile("fence.mbarrier_init.release.cluster;" ::: "memory");
        mbar_expect(sb + S_XBAR, 32768);
        for (int j = 0; j < 8; j++) tma2d(sb + P_X + j * 4096, &p.tm[3], ((blockIdx.x - 4) >> 1) * 8, j * 256, sb + S_XBAR);
    }
    if (threadIdx.x == 320) {
        unsigned v;
        asm volatile("ld.relaxed.gpu.global.u32 %0,[%1];" : "=r"(v) : "l"(g_gate) : "memory");
        v = v / (4 * NCL) + p.dopro;
        sts64(sb + S_GATE, v * (4 * NCL), v & 1);
    }
    __syncwarp();
    asm volatile("barrier.cluster.arrive.relaxed.aligned;" ::: "memory");
    if (wg == 2) bar_arrive(8, 384);
    if (p.dopro && cl >= 2) prologue(p.pa, sb, blockIdx.x - 4, wi, pr); else if (wg < 2) bar_sync(8, 384);
    asm volatile("barrier.cluster.wait.aligned;" ::: "memory");
    fence_async_smem();
    bar_sync(wg == 2 ? 7 : 1, wg == 2 ? 128 : 256);
    if (p.dopro && (threadIdx.x == 32 || threadIdx.x == 352)) red_release(g_gate, 1);
    if (rec) {
        if (threadIdx.x == 0) {
            rec_fetch(&p.tm[1], sb + R_STK, (cl - p.rec0) * 128, rank * 256, 2, sb + R_BAR + RB_INIT * 8);
            rec_fetch(&p.tm[2], sb + R_STV, (cl - p.rec0) * 128, rank * 256, 2, sb + R_BAR + RB_INIT * 8);
        }
    }
    PROF(threadIdx.x == 0, 3506);
    __syncwarp();
    if (rec) {
        const int head = cl - p.rec0;
        if (wg == 2) {
            reg_dec<RH>();
            const int w = wi & 3;
            if (threadIdx.x == 256) rec_fetch(&p.tm[0], sb + R_STQ, head * 128, rank * 256, 2, sb + R_BAR + RB_INIT * 8);
            __syncwarp();
            wait_cnt_warp(g_gate, lds32(sb + S_GATE));
            __syncthreads();
            cluster_sync();
            if ((p.chains >> (w >> 1)) & 1) rec_attn(p, sb, w >> 1, w & 1, head, rank);
        } else {
            reg_inc<RW0>();
            rec_weights(p, sb, head, rank, wi);
        }
    } else {
        if (wg == 2) {
            reg_dec<40>();
            const int w = wi & 3;
            if (w == 0) bulk_producer(p, sb, cl, rank); else if (w >= 2) bulk_release(p, sb, cl, rank, w - 2);
        } else { reg_inc<232>(); bulk_consumer(p, sb, cl, rank, wi); }
    }
    __syncwarp();
    cluster_sync();
}

typedef CUresult (*EncFn)(CUtensorMap*, CUtensorMapDataType, cuuint32_t, void*, const cuuint64_t*, const cuuint64_t*, const cuuint32_t*, const cuuint32_t*,
                          CUtensorMapInterleave, CUtensorMapSwizzle, CUtensorMapL2promotion, CUtensorMapFloatOOBfill);
inline uint32_t mk(int type, int layer, int ch, int a, int b, int c) { return type | (layer << 3) | (ch << 4) | (a << 8) | (b << 16) | ((uint32_t)c << 24); }
constexpr int SMEM_BYTES = 232448;

struct Sched {
    Params* P; int n[NCL];
    void clear() { memset(P->task, 0, sizeof(P->task)); memset(n, 0, sizeof(n)); }
    void add(int cl, uint32_t t) { if (n[cl] < MAXT - 1) P->task[cl][n[cl]++] = t; }
};

#define LAG 13
#define TS1 2400
#define TS2 2950
#define REC0 4
#define DQU 2450
#define DQO 1400
#define DHN 380
#define PUBN 600
#define DUN 5400
#define NQ1 4
#define FAST0 1
#define FAST1 14
#define MARG 1000
struct Plan { uint32_t w[NCL][MAXT]; int n[NCL]; double end, rec; };
void simulate(Plan& L, int nc, int n0, int nlong, int nuns, int ns2, int nhg, double hs) {
    const double INF = 1e18, DKB = 600, DOV = 700, DH = DHN, DHO = 1100, DF = 2200, DFB = 200, POLL = 450, FILL = 500, PUB = PUBN;
    enum { Q0, O0, Q1, HB, O1, FI, NK };
    struct Grp { int n, left; double done; } G[NK][16];
    double fr[NCL], it[100] = {}, cv[16];
    int ns[16], last[2][NCL], uc = 0, nit = 0;
    memset(L.n, 0, sizeof(L.n)); L.end = 0;
    auto fast = [&](int c) { return c < FAST0 || c >= FAST1; };
    for (int c = 0; c < 16; c++) {
        ns[c] = c < nuns ? 1 : c == 15 ? 16 : c == 14 ? 8 : ns2;
        const int cnt[NK] = {c < 2 ? 48 : (c & 1) ? 0 : 96, OPS1, c == 15 ? 24 : fast(c) ? 16 : 48 / NQ1, c >= 2 && !(c & 1) ? 16 : 0, ns[c], ns[c] == 1 ? 0 : c >= 14 ? 8 : 4};
        for (int k = 0; k < NK; k++) G[k][c] = {cnt[k], cnt[k], 0};
        cv[c] = INF;
    }
    for (int i = 0; i < nc; i++) { fr[i] = 0; last[0][i] = last[1][i] = -1; }
    auto fin = [&](int k, int c) { if ((k == Q0 && c >= 2) || k == HB) c &= ~1; return G[k][c].left ? INF : G[k][c].done; };
    auto len = [&](int i) { return (i >= LAG && i < 64) ? (double)TS2 : (double)TS1; };
    auto end_it = [&](int i) { return i < nit ? it[i] + len(i) : INF; };
    auto nominal = [&](int i) { if (i < nit) return it[i]; double t = nit ? it[nit - 1] : 11000 - TS1; for (int j = nit - 1; j < i; j++) t += len(j); return t; };
    auto put = [&](int i, uint32_t w) { if (L.n[i] < MAXT - 4) L.w[i][L.n[i]++] = w; else L.end = INF; };
    auto rel = [&](int k, int c) {
        switch (k) {
            case Q0: return 0.0;
            case O0: return end_it(4 * c + 3) + PUB + POLL;
            case Q1: return cv[c] + POLL;
            case HB: return cv[c - 2] + 600 + POLL;
            case O1: return end_it(LAG + 4 * c + 3) + PUB + POLL;
            default: return fin(O1, c) + POLL;
        }
    };
    auto dur = [&](int k, int c) {
        switch (k) {
            case Q0: return DQO + (c < 2 ? 2.0 : 1.0) * DQU;
            case O0: return ((63 + OPS1) / OPS1) * DKB + 800;
            case HB: return DHO + DH * c;
            case Q1: return DQO + 48.0 / G[Q1][c].n * DQU;
            case O1: return DOV + DKB * 64 / ns[c] + (ns[c] == 1 ? 1500 : 0);
            default: return DF + DFB * ns[c] * (c >= 14 ? 0.5 : 1);
        }
    };
    auto o0_est = [&](int c) {
        double t = uc ? cv[uc - 1] - 900 : 0;
        for (int j = uc; j < c; j++) t = fmax(t, nominal(4 * j + 4) + PUB + POLL + FILL) + dur(O0, j) + DUN;
        return fmax(t, nominal(4 * c + 4) + PUB + POLL);
    };
    auto cv_est = [&](int c) { return c < uc ? cv[c] : o0_est(c) + FILL + dur(O0, c) + DUN + 900; };
    auto first = [&](int k, int c) { return k == O0 || c == 15 ? 0 : OPS1; };
    while (true) {
        while (nit < 64 + LAG) {
            double t = nit ? end_it(nit - 1) : 0;
            if (nit < 64) t = fmax(t, fin(Q0, nit >> 2) + POLL);
            if (nit >= LAG) t = fmax(t, fin(Q1, (nit - LAG) >> 2) + (nit < 64 ? 0 : POLL));
            if (t >= INF) break;
            it[nit++] = t;
        }
        int i = -1;
        for (int j = 0; j < nc; j++) if (fr[j] < INF && (i < 0 || fr[j] < fr[i])) i = j;
        if (i < 0) break;
        const double t = fr[i];
        double lim = INF;
        if (i < 8 && last[0][i] == uc) {
            if (G[O0][uc].left || fin(HB, uc) >= INF) { fr[i] = t + 200; continue; }
            const double e = fmax(G[O0][uc].done, fin(HB, uc) - 2000) + DUN;
            for (int j = 0; j < 8; j++) { put(j, mk(T_CV, 0, uc, 2 * j, 0, 0)); fr[j] = e; }
            cv[uc++] = e + 900;
            continue;
        }
        const bool hg = (unsigned)(i - OPS1 - 48 / NQ1) < (unsigned)nhg;
        double hlim = INF;
        for (int c = 2; c < 16 && hg; c++) if (G[HB][c].left) { hlim = cv_est(c - 2) + hs; break; }
        int mine[2] = {-1, -1};
        for (int k = 0; k < 2; k++)
            for (int c = last[k][i] + 1; c < 16 && mine[k] < 0; c++) if ((unsigned)(i - first(O0 + k, c)) < (unsigned)G[O0 + k][c].n) mine[k] = c;
        if (mine[0] >= 0) lim = o0_est(mine[0]) - (i < 8 && !uc ? 8500 : 0);
        else if (mine[1] >= 0) lim = cv_est(mine[1]) + POLL;
        else if (i < 16 && G[O1][15].left) lim = fmin(lim, nominal(64 + LAG) + PUB);
        int bk = -1, bc = 0; double bd = INF;
        for (int k = 0; k < NK; k++)
            for (int c = 0; c < 16; c++) {
                const bool urgent = k == O0 || k == Q1 || (k == O1 && c == 15);
                if (!G[k][c].left || ((k == O0 || k == Q1) && c != mine[k - O0]) || (k == O1 && ns[c] == 1 && i < nc - nlong) || (k == O1 && c == 15 && i >= 16)) continue;
                if (rel(k, c) > t || (t + dur(k, c) + (k == Q0 && c >= 2 ? DQU : 0) > lim && !urgent)) continue;
                if (i < 8 && uc && uc < 16 && k != O0) continue;
                if ((k == HB && !hg) || (k != HB && !urgent && t + dur(k, c) + (k == Q0 && c >= 2 ? DQU : 0) > hlim)) continue;
                const double dl = urgent || (k == O1 && ns[c] == 1) ? -INF : k == HB ? -INF / 2 : k == Q0 ? nominal(4 * c) - 3000 : 1e9 + c * 2 + (k == O1);
                if (dl < bd) { bd = dl; bk = k; bc = c; }
            }
        if (bk < 0) {
            bool any = i < 8 && uc < 16;
            for (int k = 0; k < NK; k++) for (int c = 0; c < 16; c++) any = any || G[k][c].left;
            fr[i] = any ? t + 200 : INF;
            if (t > 400000) { L.end = INF; return; }
            continue;
        }
        Grp& g = G[bk][bc];
        const int n = g.n - g.left, c = bc;
        int nu = 1;
        double d = dur(bk, c);
        if (bk == Q0) for (nu = c < 2 ? 2 : 1; c >= 2 && nu < g.left && (nu < 2 || (nu < n0 && t + d + DQU < fmin(fmin(lim, hlim), bd - MARG))); nu++) d += DQU;
        if (bk == O0 || bk == Q1) last[bk - O0][i] = c;
        if (bk == O0 && !c && i < 8) put(i, mk(T_CV, 0, 3, 2 * i, 0, 128));
        g.left -= nu;
        const double e = fmax(t, rel(bk, c) + FILL) + (t < 1 ? 4500 : 0) + d;
        fr[i] = e;
        g.done = fmax(g.done, e + (bk == O1 ? 1900 : bk == O0 ? 0 : 1000));
        if (bk == FI || (bk == O1 && ns[c] == 1)) L.end = fmax(L.end, e);
        put(i, bk == Q0 ? (c < 2 ? mk(T_QKV, 0, c, 2 * n, 2, 0) : mk(T_QKV, 0, c, n, nu, 64))
             : bk == O0 ? mk(T_OP, 0, c, i * 64 / OPS1, (i + 1) * 64 / OPS1 - i * 64 / OPS1, i)
             : bk == HB ? mk(T_CV, 1, c, 2 * n, 0, 0)
             : bk == Q1 ? mk(T_QKV, 1, c, (i - first(Q1, c)) * 96 / g.n, 48 / g.n, 0)
             : bk == O1 ? mk(T_OP, 1, c, n * 64 / ns[c], 64 / ns[c], ns[c] == 1 ? 32 : n)
                        : mk(T_FIN, 1, c, n * (32 / g.n), ns[c], 16 / g.n));
    }
    L.rec = end_it(63 + LAG);
}
void plan(Params& P) {
    P.rec0 = REC0; P.chains = 3; P.lag = LAG; P.dostats = 1; P.dopro = 1;
    static Plan L, T;
    int cls[NCL], nc = 0;
    for (int c = REC0 + 32; c < NCL; c++) cls[nc++] = c;
    for (int c = REC0 - 1; c >= 0; c--) cls[nc++] = c;
    L.end = 1e18;
    for (int n0 = 10; n0 >= 4; n0 -= 2)
        for (int nuns = 0; nuns <= 6; nuns += 3)
            for (int ns2 = 8; ns2 >= 4; ns2 -= 4)
                for (int v = 0; v < 4; v++) {
                    const int nhg = (v & 1) ? 6 : 8, hs = (v & 2) ? 4000 : 2000;
                    simulate(T, nc, n0, nuns > 3 ? 2 : 1, nuns, ns2, nhg, hs);
                    if (T.end < L.end) {
                        L = T;
                    }
                }
    Sched S; S.P = &P; S.clear();
    S.add(0, mk(T_QKV, 1, 15, 60, 2, 128)); S.add(0, mk(T_OP, 1, 15, 0, 4, 128));
    S.add(1, mk(T_CV, 0, 3, 0, 0, 128));
    for (int i = 0; i < nc; i++) {
        bool warm = false;
        for (int k = 0; k < L.n[i]; k++) {
            if (!warm && k + 1 < L.n[i] && (L.w[i][k + 1] & 255) == (mk(T_FIN, 1, 15, 0, 0, 0) & 255)) { S.add(cls[i], L.w[i][k + 1] | 0x80000000u); warm = true; }
            S.add(cls[i], L.w[i][k]);
            if ((L.w[i][k] & 7) == T_FIN) warm = true;
        }
    }
}

#define TK0() do {} while (0)
#define TK() do { P.e0 = (P.chains & 1) ? 64 : 0; P.b1 = (P.chains & 2) ? P.lag : 1000; P.nit = (P.chains & 2) ? P.lag + 64 : 64; TK0(); } while (0)
}

extern "C" void kernel_launch(void* const* d_in, const int* in_sizes, int n_in, void* d_out, int out_size) {
    typedef const __nv_bfloat16* BP;
    static EncFn enc = nullptr;
    if (!enc) {
        void* fn = nullptr; cudaDriverEntryPointQueryResult qr;
        cudaGetDriverEntryPoint("cuTensorMapEncodeTiled", &fn, cudaEnableDefault, &qr);
        enc = (EncFn)fn;
        cudaFuncSetAttribute(main_kernel, cudaFuncAttributeMaxDynamicSharedMemorySize, SMEM_BYTES);
    }
    static Params P;
    for (int i = 0; i < 4; i++) {
        const cuuint64_t cols = i < 3 ? 4096 : 512, rows = i < 3 ? 512 : 4096;
        cuuint64_t d2[2] = {cols, rows}, d3[3] = {64, rows, cols / 64}, str[2] = {cols * 2, 128};
        cuuint32_t box[3] = {64, 64, 4}, es[3] = {1, 1, 1};
        enc(&P.tm[i < 3 ? i : 4], CU_TENSOR_MAP_DATA_TYPE_BFLOAT16, 2, d_in[9 + i], d2, str, box, es, CU_TENSOR_MAP_INTERLEAVE_NONE, CU_TENSOR_MAP_SWIZZLE_128B,
                       CU_TENSOR_MAP_L2_PROMOTION_L2_128B, CU_TENSOR_MAP_FLOAT_OOB_FILL_NONE);
        for (int m = 0; m < 2; m++) {
            cuuint32_t box3[3] = {64, 32, m ? 2u : 4u};
            enc(&P.t3[m][i], CU_TENSOR_MAP_DATA_TYPE_BFLOAT16, 3, d_in[9 + i], d3, str, box3, es, CU_TENSOR_MAP_INTERLEAVE_NONE, CU_TENSOR_MAP_SWIZZLE_128B,
                CU_TENSOR_MAP_L2_PROMOTION_L2_128B, CU_TENSOR_MAP_FLOAT_OOB_FILL_NONE);
        }
    }
    {
        cuuint64_t dims[2] = {512, 2048}, str[1] = {1024};
        cuuint32_t box[2] = {8, 256}, es[2] = {1, 1};
        enc(&P.tm[3], CU_TENSOR_MAP_DATA_TYPE_BFLOAT16, 2, d_in[0], dims, str, box, es, CU_TENSOR_MAP_INTERLEAVE_NONE, CU_TENSOR_MAP_SWIZZLE_NONE,
            CU_TENSOR_MAP_L2_PROMOTION_NONE, CU_TENSOR_MAP_FLOAT_OOB_FILL_NONE);
    }
    for (int m = 0; m < 2; m++) {
        void* ga; cudaGetSymbolAddress(&ga, g_A);
        cuuint64_t dims[2] = {512, sizeof(AOps) / 1024}, str[1] = {1024};
        cuuint32_t box[2] = {256, m ? 16u : 8u}, es[2] = {1, 1};
        enc(&P.ta[m], CU_TENSOR_MAP_DATA_TYPE_BFLOAT16, 2, ga, dims, str, box, es, CU_TENSOR_MAP_INTERLEAVE_NONE, CU_TENSOR_MAP_SWIZZLE_NONE,
            CU_TENSOR_MAP_L2_PROMOTION_L2_128B, CU_TENSOR_MAP_FLOAT_OOB_FILL_NONE);
    }
    P.mem0 = (BP)d_in[8]; P.Wo = (BP)d_in[12]; P.Dskip = (BP)d_in[6]; P.out = (__nv_bfloat16*)d_out;
    P.nst[0] = 1; P.nst[1] = 16;
    cudaStream_t s = cudaStreamPerThread;
    P.pa = {(BP)d_in[0], (BP)d_in[1], (BP)d_in[2], (BP)d_in[3], (BP)d_in[4], (BP)d_in[5], (BP)d_in[6], (BP)d_in[9], (BP)d_in[10], (BP)d_in[11], (BP)d_in[12], (BP)d_in[8]};
    static bool planned = false;
    if (!planned) { plan(P); planned = true; }
    TK(); main_kernel<<<2 * NCL, 384, SMEM_BYTES, s>>>(P); TK();
}
```

```cpp
#include <cuda_runtime.h>
#include <cuda_bf16.h>
#include <cuda.h>
#include <stdint.h>
#include <string.h>
#include <math.h>

namespace {

constexpr int NCL = 66;
constexpr int MAXT = 64;
#define PFC 1
#define OPS1N 8
constexpr int OPS1 = OPS1N;
constexpr int MAXSPLIT = 16;
constexpr int PW = 144;

struct AOps { uint4 x[2][16 * 8 * 1024], o[2][16 * 64 * 1024]; };
__device__ AOps g_A;
#define g_xA g_A.x
#define g_o g_A.o
__device__ float2 g_st[2][16 * 2048];
__device__ float2 g_st2[2 * 16 * 128];
__device__ uint4 g_qkv[2][64 * 64 * 768];
__device__ uint4 g_pp[2][16 * MAXSPLIT * 8192];
__device__ uint4 g_acc[7 * 2048];
__device__ unsigned g_gate[32];
__device__ uint32_t g_P[16 * 16 * 32 * PW];
__device__ uint4 g_u[16 * 16 * 512];
__device__ float4 g_carry[2][17 * 16 * 4 * 256];
__device__ unsigned g_cnt[13 * 64];
__device__ uint32_t g_ln0[2048];

enum { C_QKV0 = 0, C_QKV1 = 1, C_O0 = 2, C_O1 = 3, C_U = 4, C_OP1 = 5, C_CV = 6, C_ST = 7, C_H = 8, C_OP0 = 9   };
__device__ __forceinline__ unsigned* cnt_ptr(int kind, int chunk) { return g_cnt + kind * 64 + chunk; }

enum { T_END = 0, T_QKV = 1, T_OP = 2, T_CV = 3, T_FIN = 4 };
struct ProArgs { const __nv_bfloat16 *x, *lAr, *Ai, *Cr, *Ci, *ldt, *Dk, *Wq, *Wk, *Wv, *Wo, *mem0; };
struct Params {
    CUtensorMap tm[5];
    CUtensorMap t3[2][4];
    CUtensorMap ta[2];
    ProArgs pa;
    int dopro;
    const __nv_bfloat16* mem0;
    const __nv_bfloat16* Wo;
    const __nv_bfloat16* Dskip;
    __nv_bfloat16* out;
    int rec0;
    int chains;
    int lag;
    int b1, e0, nit;
    int zero, gpit;
    int dostats;
    uint32_t task[NCL][MAXT];
};

__device__ __forceinline__ uint32_t smem_u32(const void* p) { return (uint32_t)__cvta_generic_to_shared(p); }
__device__ __forceinline__ uint32_t mapa(uint32_t a, uint32_t r) {
    uint32_t o; asm("mapa.shared::cluster.u32 %0,%1,%2;" : "=r"(o) : "r"(a), "r"(r)); return o;
}
__device__ __forceinline__ void mbar_init(uint32_t b, int c) { asm volatile("mbarrier.init.shared::cta.b64 [%0],%1;" ::"r"(b), "r"(c) : "memory"); }
__device__ __forceinline__ void mbar_expect(uint32_t b, int bytes) { asm volatile("mbarrier.arrive.expect_tx.shared::cta.b64 _,[%0],%1;" ::"r"(b), "r"(bytes) : "memory"); }
__device__ __forceinline__ void mbar_arrive(uint32_t b) { asm volatile("mbarrier.arrive.shared::cta.b64 _,[%0];" ::"r"(b) : "memory"); }
__device__ __forceinline__ void mbar_arrive_cluster(uint32_t b) { asm volatile("mbarrier.arrive.shared::cluster.b64 _,[%0];" ::"r"(b) : "memory"); }
__device__ __forceinline__ void mbar_arrive1(uint32_t b) { asm volatile("{.reg .pred p; elect.sync _|p,0xffffffff; @p mbarrier.arrive.shared::cta.b64 _,[%0];}" ::"r"(b) : "memory"); }
__device__ __forceinline__ void mbar_arrive1_cluster(uint32_t b) { asm volatile("{.reg .pred p; elect.sync _|p,0xffffffff; @p mbarrier.arrive.shared::cluster.b64 _,[%0];}" ::"r"(b) : "memory"); }
__device__ __forceinline__ void mbar_wait(uint32_t b, uint32_t ph) {
    asm volatile(
        "{.reg .pred p; .reg .u32 n; mov.u32 n,0;\n"
        "W%=: mbarrier.try_wait.parity.shared::cta.b64 p,[%0],%1;\n"
        "@p bra D%=;\n"
        "add.u32 n,n,1; setp.lt.u32 p,n,2000000; @p bra W%=;\n"
        "trap;\n"
        "D%=: }" ::"r"(b), "r"(ph) : "memory");
}
__device__ __forceinline__ bool mbar_test(uint32_t b, uint32_t ph) {
    uint32_t ok;
    asm volatile("{.reg .pred p; mbarrier.test_wait.parity.shared::cta.b64 p,[%1],%2; selp.u32 %0,1,0,p;}" : "=r"(ok) : "r"(b), "r"(ph) : "memory");
    return ok;
}
__device__ __forceinline__ bool wait_lds128(uint32_t b, uint32_t ph, uint32_t a, uint4& v) {
    uint32_t ok;
    asm volatile("{.reg .pred p; mbarrier.try_wait.parity.shared::cta.b64 p,[%5],%6,20000; ld.shared.v4.u32 {%0,%1,%2,%3},[%7]; selp.u32 %4,1,0,p;}"
                 : "=r"(v.x), "=r"(v.y), "=r"(v.z), "=r"(v.w), "=r"(ok) : "r"(b), "r"(ph), "r"(a) : "memory");
    return ok;
}
__device__ __forceinline__ bool wait_lds64(uint32_t b, uint32_t ph, uint32_t a, uint2& v) {
    uint32_t ok;
    asm volatile("{.reg .pred p; mbarrier.try_wait.parity.shared::cta.b64 p,[%3],%4,20000; ld.shared.v2.u32 {%0,%1},[%5]; selp.u32 %2,1,0,p;}"
                 : "=r"(v.x), "=r"(v.y), "=r"(ok) : "r"(b), "r"(ph), "r"(a) : "memory");
    return ok;
}
template <int PH> __device__ __forceinline__ void mbar_wait_c(uint32_t b) {
    asm volatile(
        "{.reg .pred p; .reg .u32 n; mov.u32 n,%2;\n"
        "W%=: mbarrier.try_wait.parity.shared::cta.b64 p,[%0],%1;\n"
        "@p bra D%=;\n"
        "add.u32 n,n,1; setp.lt.u32 p,n,2000000; @p bra W%=;\n"
        "trap;\n"
        "D%=: }" ::"r"(b), "n"(PH), "n"(PH) : "memory");
}
__device__ __forceinline__ void bar_sync(int id, int n) { asm volatile("bar.sync %0,%1;" ::"r"(id), "r"(n) : "memory"); }
__device__ __forceinline__ void bar_arrive(int id, int n) { asm volatile("bar.arrive %0,%1;" ::"r"(id), "r"(n) : "memory"); }
__device__ __forceinline__ void cluster_sync() { asm volatile("barrier.cluster.arrive.relaxed.aligned; barrier.cluster.wait.aligned;" ::: "memory"); }
__device__ __forceinline__ void fence_async() { asm volatile("fence.proxy.async;" ::: "memory"); }
__device__ __forceinline__ void fence_async_smem() { asm volatile("fence.proxy.async.shared::cta;" ::: "memory"); }
#define EFR 1
#define EFW 2
constexpr uint64_t POL_N = 0x1000000000000000ull, POL_F = 0x12F0000000000000ull;
constexpr uint64_t POL_LAST = EFR ? POL_F : POL_N  , POL_LATE = EFW ? POL_F : POL_N  , POL_SOON = EFW > 1 ? POL_F : POL_N;
__device__ __forceinline__ void bulk_g2s(uint32_t dst, const void* src, int bytes, uint32_t bar, uint64_t pol) {
    asm volatile("cp.async.bulk.shared::cluster.global.mbarrier::complete_tx::bytes.L2::cache_hint [%0],[%1],%2,[%3],%4;" ::"r"(dst), "l"(src), "r"(bytes), "r"(bar), "l"(pol) : "memory");
}
__device__ __forceinline__ void bulk_g2s_mc(uint32_t dst, const void* src, int bytes, uint32_t bar, uint64_t pol) {
    asm volatile("cp.async.bulk.shared::cluster.global.mbarrier::complete_tx::bytes.multicast::cluster.L2::cache_hint [%0],[%1],%2,[%3],%4,%5;" ::"r"(dst), "l"(src), "r"(bytes), "r"(bar), "h"((uint16_t)3), "l"(pol) : "memory");
}
__device__ __forceinline__ void bulk_s2s(uint32_t dst, uint32_t src, int bytes, uint32_t bar) {
    asm volatile("cp.async.bulk.shared::cluster.shared::cta.mbarrier::complete_tx::bytes [%0],[%1],%2,[%3];" ::"r"(dst), "r"(src), "r"(bytes), "r"(bar) : "memory");
}
__device__ __forceinline__ bool elect() {
    uint32_t r; asm volatile("{.reg .pred p; elect.sync _|p,0xffffffff; selp.u32 %0,1,0,p;}" : "=r"(r)); return r;
}
__device__ __forceinline__ void stg128(uint4* p, uint4 v, uint64_t pol) {
    asm volatile("st.global.L2::cache_hint.v4.u32 [%0],{%1,%2,%3,%4},%5;" ::"l"(p), "r"(v.x), "r"(v.y), "r"(v.z), "r"(v.w), "l"(pol));
}
__device__ __forceinline__ void stg32(uint32_t* p, uint32_t v, uint64_t pol) { asm volatile("st.global.L2::cache_hint.u32 [%0],%1,%2;" ::"l"(p), "r"(v), "l"(pol)); }
__device__ __forceinline__ uint4 ldcg128_last(const uint4* p) {
    uint4 v; asm volatile("ld.global.cg.L2::cache_hint.v4.u32 {%0,%1,%2,%3},[%4],%5;" : "=r"(v.x), "=r"(v.y), "=r"(v.z), "=r"(v.w) : "l"(p), "l"(POL_LAST) : "memory"); return v;
}
__device__ __forceinline__ void tma2d(uint32_t dst, const CUtensorMap* tm, int x, int y, uint32_t bar) {
    asm volatile("cp.async.bulk.tensor.2d.shared::cluster.global.mbarrier::complete_tx::bytes [%0],[%1,{%2,%3}],[%4];" ::"r"(dst), "l"(tm), "r"(x), "r"(y), "r"(bar) : "memory");
}
__device__ __forceinline__ void tma3d_mc(uint32_t dst, const CUtensorMap* tm, int y, int z, uint32_t bar, uint16_t mask) {
    asm volatile("{.reg .pred p; elect.sync _|p,0xffffffff;\n"
                 "@p cp.async.bulk.tensor.3d.shared::cluster.global.mbarrier::complete_tx::bytes.multicast::cluster [%0],[%1,{0,%2,%3}],[%4],%5;}"
                 ::"r"(dst), "l"(tm), "r"(y), "r"(z), "r"(bar), "h"(mask) : "memory");
}
__device__ __forceinline__ void tma2d_mc(uint32_t dst, const CUtensorMap* tm, int x, int y, uint32_t bar, uint16_t mask, uint64_t pol) {
    asm volatile("{.reg .pred p; elect.sync _|p,0xffffffff;\n"
                 "@p cp.async.bulk.tensor.2d.shared::cluster.global.mbarrier::complete_tx::bytes.multicast::cluster.L2::cache_hint [%0],[%1,{%2,%3}],[%4],%5,%6;}"
                 ::"r"(dst), "l"(tm), "r"(x), "r"(y), "r"(bar), "h"(mask), "l"(pol) : "memory");
}
__device__ __forceinline__ void bulk_g2s1(uint32_t dst, const void* src, int bytes, uint32_t bar, uint64_t pol) {
    asm volatile("{.reg .pred p; elect.sync _|p,0xffffffff;\n"
                 "@p cp.async.bulk.shared::cluster.global.mbarrier::complete_tx::bytes.L2::cache_hint [%0],[%1],%2,[%3],%4;}" ::"r"(dst), "l"(src), "r"(bytes), "r"(bar), "l"(pol) : "memory");
}
__device__ __forceinline__ void mbar_expect1(uint32_t b, int bytes) {
    asm volatile("{.reg .pred p; elect.sync _|p,0xffffffff; @p mbarrier.arrive.expect_tx.shared::cta.b64 _,[%0],%1;}" ::"r"(b), "r"(bytes) : "memory");
}
__device__ __forceinline__ void st_async4(uint32_t a, uint32_t x, uint32_t y, uint32_t z, uint32_t w, uint32_t mb) {
    asm volatile("st.async.shared::cluster.mbarrier::complete_tx::bytes.v4.b32 [%0],{%1,%2,%3,%4},[%5];" ::"r"(a), "r"(x), "r"(y), "r"(z), "r"(w), "r"(mb) : "memory");
}
__device__ __forceinline__ void st_async2(uint32_t a, uint32_t x, uint32_t y, uint32_t mb) {
    asm volatile("st.async.shared::cluster.mbarrier::complete_tx::bytes.v2.b32 [%0],{%1,%2},[%3];" ::"r"(a), "r"(x), "r"(y), "r"(mb) : "memory");
}
#define LDSQ "ld.shared"
__device__ __forceinline__ uint4 lds128(uint32_t a) { uint4 v; asm volatile(LDSQ ".v4.u32 {%0,%1,%2,%3},[%4];" : "=r"(v.x), "=r"(v.y), "=r"(v.z), "=r"(v.w) : "r"(a) : "memory"); return v; }
__device__ __forceinline__ uint2 lds64(uint32_t a) { uint2 v; asm volatile(LDSQ ".v2.u32 {%0,%1},[%2];" : "=r"(v.x), "=r"(v.y) : "r"(a) : "memory"); return v; }
__device__ __forceinline__ uint32_t lds32(uint32_t a) { uint32_t v; asm volatile(LDSQ ".u32 %0,[%1];" : "=r"(v) : "r"(a) : "memory"); return v; }
__device__ __forceinline__ void sts128(uint32_t a, uint32_t x, uint32_t y, uint32_t z, uint32_t w) { asm volatile("st.shared.v4.u32 [%0],{%1,%2,%3,%4};" ::"r"(a), "r"(x), "r"(y), "r"(z), "r"(w) : "memory"); }
__device__ __forceinline__ void sts64(uint32_t a, uint32_t x, uint32_t y) { asm volatile("st.shared.v2.u32 [%0],{%1,%2};" ::"r"(a), "r"(x), "r"(y) : "memory"); }
__device__ __forceinline__ void sts32(uint32_t a, uint32_t x) { asm volatile("st.shared.u32 [%0],%1;" ::"r"(a), "r"(x) : "memory"); }
__device__ __forceinline__ uint4 ldsm4(uint32_t a) { uint4 v; asm volatile("ldmatrix.sync.aligned.m8n8.x4.shared.b16 {%0,%1,%2,%3},[%4];" : "=r"(v.x), "=r"(v.y), "=r"(v.z), "=r"(v.w) : "r"(a) : "memory"); return v; }
__device__ __forceinline__ uint4 ldsm4t(uint32_t a) { uint4 v; asm volatile("ldmatrix.sync.aligned.m8n8.x4.trans.shared.b16 {%0,%1,%2,%3},[%4];" : "=r"(v.x), "=r"(v.y), "=r"(v.z), "=r"(v.w) : "r"(a) : "memory"); return v; }
__device__ __forceinline__ uint32_t movm(uint32_t a) { uint32_t d; asm volatile("movmatrix.sync.aligned.m8n8.trans.b16 %0,%1;" : "=r"(d) : "r"(a)); return d; }
__device__ __forceinline__ uint32_t pack2(float lo, float hi) { uint32_t d; asm("cvt.rn.bf16x2.f32 %0,%1,%2;" : "=r"(d) : "f"(hi), "f"(lo)); return d; }
__device__ __forceinline__ uint32_t hadd2(uint32_t a, uint32_t b) { uint32_t d; asm("add.rn.bf16x2 %0,%1,%2;" : "=r"(d) : "r"(a), "r"(b)); return d; }
__device__ __forceinline__ float blo(uint32_t v) { return __uint_as_float(v << 16); }
__device__ __forceinline__ float bhi(uint32_t v) { return __uint_as_float(v & 0xffff0000u); }
__device__ __forceinline__ float rbf(float x) { return __uint_as_float(pack2(0.f, x)); }
__device__ __forceinline__ float ex2(float x) { float y; asm("ex2.approx.ftz.f32 %0,%1;" : "=f"(y) : "f"(x)); return y; }
__device__ __forceinline__ float rcp(float x) { float y; asm("rcp.approx.ftz.f32 %0,%1;" : "=f"(y) : "f"(x)); return y; }
__device__ __forceinline__ void mma16(float* c, uint32_t a0, uint32_t a1, uint32_t a2, uint32_t a3, uint32_t b0, uint32_t b1) {
    asm volatile("mma.sync.aligned.m16n8k16.row.col.f32.bf16.bf16.f32 {%0,%1,%2,%3},{%4,%5,%6,%7},{%8,%9},{%0,%1,%2,%3};"
                 : "+f"(c[0]), "+f"(c[1]), "+f"(c[2]), "+f"(c[3]) : "r"(a0), "r"(a1), "r"(a2), "r"(a3), "r"(b0), "r"(b1));
}
__device__ __forceinline__ void mma8(float* c, uint32_t a0, uint32_t a1, uint32_t b0) {
    asm volatile("mma.sync.aligned.m16n8k8.row.col.f32.bf16.bf16.f32 {%0,%1,%2,%3},{%4,%5},{%6},{%0,%1,%2,%3};"
                 : "+f"(c[0]), "+f"(c[1]), "+f"(c[2]), "+f"(c[3]) : "r"(a0), "r"(a1), "r"(b0));
}
__device__ __forceinline__ uint4 ld_rlx128(const uint4* p) {
    uint4 v;
    asm volatile("{.reg .b128 t; ld.relaxed.gpu.global.b128 t,[%4]; mov.b128 {%0,%1,%2,%3},t;}" : "=r"(v.x), "=r"(v.y), "=r"(v.z), "=r"(v.w) : "l"(p) : "memory");
    return v;
}
__device__ __forceinline__ void st_rlx128(uint4* p, uint32_t x, uint32_t y, uint32_t z, uint32_t w) {
    asm volatile("{.reg .b128 t; mov.b128 t,{%1,%2,%3,%4}; st.relaxed.gpu.global.b128 [%0],t;}" ::"l"(p), "r"(x), "r"(y), "r"(z), "r"(w) : "memory");
}
__device__ __forceinline__ uint4 ldcg128(const uint4* p) { uint4 v; asm volatile("ld.global.cg.v4.u32 {%0,%1,%2,%3},[%4];" : "=r"(v.x), "=r"(v.y), "=r"(v.z), "=r"(v.w) : "l"(p) : "memory"); return v; }
__device__ __forceinline__ void red_release(unsigned* p, unsigned v) {
    asm volatile("fence.proxy.async; red.relaxed.gpu.global.add.u32 [%0],%1;" ::"l"(p), "r"(v) : "memory");
}
__device__ __forceinline__ void wait_cnt(const unsigned* p, unsigned target) {
    unsigned v; int n = 0;
    while (true) {
        asm volatile("ld.acquire.gpu.global.u32 %0,[%1];" : "=r"(v) : "l"(p) : "memory");
        if (v >= target) break;
        if (++n > 3000000) __trap();
        __nanosleep(40);
    }
}
__device__ __forceinline__ void wait_cnt_warp(const unsigned* p, unsigned target) {
    unsigned v; int n = 0;
    while (true) {
        asm volatile("ld.acquire.gpu.global.u32 %0,[%1];" : "=r"(v) : "l"(p) : "memory");
        if (__all_sync(0xffffffffu, v >= target)) break;
        if (++n > 3000000) __trap();
    }
}
__device__ __forceinline__ uint64_t mkdesc(uint32_t addr, uint32_t lbo, uint32_t sbo, uint32_t sw) {
    return (uint64_t)((addr & 0x3FFFF) >> 4) | ((uint64_t)(lbo >> 4) << 16) | ((uint64_t)(sbo >> 4) << 32) | ((uint64_t)sw << 62);
}
__device__ __forceinline__ void wg_fence() { asm volatile("wgmma.fence.sync.aligned;" ::: "memory"); }
__device__ __forceinline__ void wg_commit() { asm volatile("wgmma.commit_group.sync.aligned;" ::: "memory"); }
template <int N> __device__ __forceinline__ void wg_wait() { asm volatile("wgmma.wait_group.sync.aligned %0;" ::"n"(N) : "memory"); }
#define R8(c, o) "+f"(c[o]), "+f"(c[o + 1]), "+f"(c[o + 2]), "+f"(c[o + 3]), "+f"(c[o + 4]), "+f"(c[o + 5]), "+f"(c[o + 6]), "+f"(c[o + 7])
#define R32(c, o) R8(c, o), R8(c, o + 8), R8(c, o + 16), R8(c, o + 24)
#define S32A "%0,%1,%2,%3,%4,%5,%6,%7,%8,%9,%10,%11,%12,%13,%14,%15,%16,%17,%18,%19,%20,%21,%22,%23,%24,%25,%26,%27,%28,%29,%30,%31"
#define S32B ",%32,%33,%34,%35,%36,%37,%38,%39,%40,%41,%42,%43,%44,%45,%46,%47,%48,%49,%50,%51,%52,%53,%54,%55,%56,%57,%58,%59,%60,%61,%62,%63"
#define S32C ",%64,%65,%66,%67,%68,%69,%70,%71,%72,%73,%74,%75,%76,%77,%78,%79,%80,%81,%82,%83,%84,%85,%86,%87,%88,%89,%90,%91,%92,%93,%94,%95"
#define S32D ",%96,%97,%98,%99,%100,%101,%102,%103,%104,%105,%106,%107,%108,%109,%110,%111,%112,%113,%114,%115,%116,%117,%118,%119,%120,%121,%122,%123,%124,%125,%126,%127"
#define W8(c, o) "=f"(c[o]), "=f"(c[o + 1]), "=f"(c[o + 2]), "=f"(c[o + 3]), "=f"(c[o + 4]), "=f"(c[o + 5]), "=f"(c[o + 6]), "=f"(c[o + 7])
#define W32(c, o) W8(c, o), W8(c, o + 8), W8(c, o + 16), W8(c, o + 24)
template <bool ACC> __device__ __forceinline__ void wgmma256(float* c, uint64_t da, uint64_t db) {
    if (ACC) asm volatile("wgmma.mma_async.sync.aligned.m64n256k16.f32.bf16.bf16 {" S32A S32B S32C S32D "},%128,%129,1,1,1,0,1;"
                          : R32(c, 0), R32(c, 32), R32(c, 64), R32(c, 96) : "l"(da), "l"(db));
    else asm volatile("wgmma.mma_async.sync.aligned.m64n256k16.f32.bf16.bf16 {" S32A S32B S32C S32D "},%128,%129,0,1,1,0,1;"
                      : W32(c, 0), W32(c, 32), W32(c, 64), W32(c, 96) : "l"(da), "l"(db));
}
template <bool ACC> __device__ __forceinline__ void wgmma128r(float* c, const uint4& a, uint64_t db) {
    if (ACC) asm volatile("wgmma.mma_async.sync.aligned.m64n128k16.f32.bf16.bf16 {" S32A S32B "},{%64,%65,%66,%67},%68,1,1,1,1;"
                          : R32(c, 0), R32(c, 32) : "r"(a.x), "r"(a.y), "r"(a.z), "r"(a.w), "l"(db));
    else asm volatile("wgmma.mma_async.sync.aligned.m64n128k16.f32.bf16.bf16 {" S32A S32B "},{%64,%65,%66,%67},%68,0,1,1,1;"
                      : W32(c, 0), W32(c, 32) : "r"(a.x), "r"(a.y), "r"(a.z), "r"(a.w), "l"(db));
}
template <int N> __device__ __forceinline__ void reg_inc() { asm volatile("setmaxnreg.inc.sync.aligned.u32 %0;" ::"n"(N)); }
template <int N> __device__ __forceinline__ void reg_dec() { asm volatile("setmaxnreg.dec.sync.aligned.u32 %0;" ::"n"(N)); }

#define PROF(cond, idx) do {} while (0)
#define CPROF(k) do {} while (0)

constexpr int S_GATE = 232440, S_TAG = 232444, S_XBAR = 232432;
constexpr float SC_LOG2E = 0.08838834764831845f * 1.4426950408889634f;

__device__ __forceinline__ float2 ln_finish(float mean, float var) {
    float sd; asm("sqrt.approx.f32 %0,%1;" : "=f"(sd) : "f"(rbf(rbf(var) + 1e-5f)));
    sd = rbf(sd);
    return make_float2(rbf(mean), sd);
}

__device__ __forceinline__ float2 row_stats512(const uint4* src, int s1, int s2) {
    const int g = (threadIdx.x & 31) >> 2;
    uint4 v[16];
#pragma unroll
    for (int i = 0; i < 16; i++) v[i] = ldcg128(src + (i >> 1) * s1 + (i & 1) * s2);
    float a[4] = {0, 0, 0, 0}, q0[4] = {0, 0, 0, 0}, q1[4] = {0, 0, 0, 0};
#pragma unroll
    for (int i = 0; i < 16; i++) {
        mma16(a, v[i].x, v[i].y, v[i].z, v[i].w, 0x3f803f80u, 0x3f803f80u);
        mma8(q0, v[i].x, v[i].y, v[i].x); mma8(q1, v[i].x, v[i].y, v[i].y);
        mma8(q0, v[i].z, v[i].w, v[i].z); mma8(q1, v[i].z, v[i].w, v[i].w);
    }
    const float sum = a[0] + a[2], sq = (g & 1) ? q0[1] + q1[3] : q0[0] + q1[2];
    return make_float2(sum, sq);
}
__device__ __forceinline__ void x1_stats(int rg, int tag) {
    const int lane = threadIdx.x & 31, g = lane >> 2, c = lane & 3;
    const float2 r = row_stats512(g_xA[0] + (rg >> 4) * 8192 + (rg & 15) * 64 + c * 8 + g, 1024, 32);
    if (c == (g >> 1)) { g_st[0][(rg >> 4) * 2048 + (rg < 32 ? 2 : tag) * 128 + (rg & 15) * 8 + g] = r; g_ln0[rg * 8 + g] = 0; }
    __syncwarp();
    if (lane == 0) red_release(cnt_ptr(C_ST, rg >> 4), 1);
}
__global__ void stats_kernel() { x1_stats(blockIdx.x * 4 + (threadIdx.x >> 5), (g_gate[0] / (4 * NCL)) & 1); }

#define NT 9
#define RH 104
#define RW0 200
#define NPD 5
#define NTO 13
#define DP1 0
#define GPW 0
#define GPJ 0
#define PACE 2
#define BKA 0
#define GSE 0
#define EARLY 4
#define PFD 0
#define PFB 0
#define STO 1
#define G2I 3
#define VE 4
#define VF 8
constexpr int TILE = 20480;
constexpr int R_WV = 0, R_WO = 65536, R_T = 131072, R_M = R_T + 2 * TILE  , R_LOC = R_M + 8192  ,
              R_REM = R_LOC + 12288  , R_O = R_REM + 24576  , R_SX = R_O + 4096  ,
              R_IL = R_SX + 10240  , R_BAR = 231936, R_Z = R_BAR + 128  , R_STQ = 0, R_STK = 65536, R_STV = 131072;
static_assert(R_IL + 512 <= R_BAR && R_BAR + 256 <= S_XBAR, "smem map");
enum { RB_INIT = 0, RB_T = 2  , RB_V = 4  , RB_QK = 8  , RB_N = 12 };
enum { NB_MF = 1  , NB_LOC = 3  , NB_PAIR = 5  , NB_O = 9  , NB_XG = 11  , NB_W = 13 };
__device__ __forceinline__ uint32_t clk32() { return (uint32_t)clock64(); }

__device__ __forceinline__ char* acc_base() { return (char*)(((size_t)g_acc + 131071) & ~(size_t)131071); }
__device__ __forceinline__ uint32_t acc_slice(uint32_t s6) { return (s6 & 1) * 256 + (s6 >> 1) * 1024; }
__device__ __forceinline__ uint32_t acc_main(uint32_t rank, uint32_t tid) { return acc_slice(rank * 32 + (tid >> 3)) + (tid & 7) * 16; }
__device__ __forceinline__ uint32_t acc_extra(uint32_t rank, uint32_t tid) { return 65536 + acc_slice(((tid >> 5) & 1) + rank * 4 + (tid >> 6) * 8) + (tid & 31) * 4; }
__device__ __forceinline__ uint32_t acc_slot(uint32_t s) { return (s & 1) * 128 + (s & 2) * 256; }
__device__ __forceinline__ void acc_init(const __nv_bfloat16* mem0, int i) {
    const uint32_t tid = i & 255, rank = (i >> 8) & 1, slot = (i >> 9) & 3, X = i >> 11;
    uint32_t v[5] = {0, 0, 0, 0, 0};
    if (slot == 3) {
        const uint16_t* m = (const uint16_t*)mem0 + (tid & 3) * 1024 + rank * 256 + (tid >> 5) * 32 + ((tid >> 2) & 7);
#pragma unroll
        for (int k = 0; k < 4; k++) v[k] = __ldg(m + k * 8) | ((uint32_t)__ldg(m + k * 8 + 512) << 16);
        v[4] = (v[3] >> 16) | 0x42000000u; v[3] = (v[3] & 0xffff) | 0x42000000u;
    }
    *(uint4*)(acc_base() + X * 32768 + acc_slot(slot) + acc_main(rank, tid)) = make_uint4(v[0], v[1], v[2], v[3]);
    *(uint32_t*)(acc_base() + X * 1024 + acc_slot(slot) + acc_extra(rank, tid)) = v[4];
}
__global__ void acc_init_kernel(const __nv_bfloat16* mem0) { acc_init(mem0, blockIdx.x * 256 + threadIdx.x); }

struct RecW { uint32_t am, ae, ah, dp, lp, lpw, vo, sb, bar, zero, ts, tn; };
__device__ __forceinline__ uint32_t vadd(uint32_t a, uint32_t b) { uint32_t d; asm volatile("add.u32 %0,%1,%2;" : "=r"(d) : "r"(a), "r"(b)); return d; }
__device__ __forceinline__ uint32_t vshr(uint32_t a, int n) { uint32_t d; asm volatile("shr.u32 %0,%1,%2;" : "=r"(d) : "r"(a), "r"(n)); return d; }
__device__ __forceinline__ uint64_t gptr(uint32_t lo, uint32_t hi) { uint64_t d; asm("mov.b64 %0,{%1,%2};" : "=l"(d) : "r"(lo), "r"(hi)); return d; }
__device__ __forceinline__ void sfence(uint32_t zero) { asm volatile("{.reg .pred p; setp.ne.u32 p,%0,0; @p exit;}" ::"r"(zero) : "memory"); }
#define SF sfence(k.zero)
#define TS(i) do {} while (0)
#define TSN(i) do {} while (0)
#define TSET(it, slot) do {} while (0)
struct Gat { uint32_t x, y, z, w, e; };
template <int X>
__device__ __forceinline__ void gat_issue(Gat& g, const RecW& k, int s, uint32_t dep) {
    const uint32_t o = acc_slot(s + 3) + dep;
    asm volatile("{.reg .b128 t; ld.relaxed.gpu.global.b128 t,[%5+%7]; mov.b128 {%0,%1,%2,%3},t; ld.relaxed.gpu.global.u32 %4,[%6+%8];}"
                 : "=r"(g.x), "=r"(g.y), "=r"(g.z), "=r"(g.w), "=r"(g.e) : "l"(gptr(k.am + o, k.ah)), "l"(gptr(k.ae + o, k.ah)), "n"(X * 32768), "n"(X * 1024) : "memory");
}
template <int X>
__device__ __forceinline__ bool gat_store(const Gat& g, const RecW& k) {
    uint32_t c;
    asm volatile("prmt.b32 %0,%1,%2,0x7632;" : "=r"(c) : "r"(g.w), "r"(g.e));
    SF;
    asm volatile("{.reg .b32 t; prmt.b32 t,%4,%6,0x5410; stmatrix.sync.aligned.m8n8.x4.trans.shared.b16 [%0+%5],{%1,%2,%3,t};}" ::"r"(k.lpw), "r"(g.x), "r"(g.y), "r"(g.z), "r"(g.w), "n"(R_M + X * 4096), "r"(g.e) : "memory");
    return __all_sync(0xffffffffu, c == 0x42004200u);
}
template <int X>
__device__ __forceinline__ void gat_finish(bool ok, const RecW& k, int s) {
    if (!ok) {
        int n = s;
        while (true) {
            Gat g;
            gat_issue<X>(g, k, n, 0);
            if (gat_store<X>(g, k)) break;
            n += 4;
            if (n > 8000000) __trap();
        }
    }
}
__device__ __forceinline__ uint4 lds128o(uint32_t a, int o) { uint4 v; asm volatile("{.reg .b32 t; add.u32 t,%4,%5; ld.shared.v4.u32 {%0,%1,%2,%3},[t];}" : "=r"(v.x), "=r"(v.y), "=r"(v.z), "=r"(v.w) : "r"(a), "r"(o) : "memory"); return v; }
__device__ __forceinline__ uint4 ldsm4o(uint32_t a, int o) { uint4 v; asm volatile("{.reg .b32 t; add.u32 t,%4,%5; ldmatrix.sync.aligned.m8n8.x4.shared.b16 {%0,%1,%2,%3},[t];}" : "=r"(v.x), "=r"(v.y), "=r"(v.z), "=r"(v.w) : "r"(a), "r"(o) : "memory"); return v; }
#define WLD(base, i) wt[i] = lds128o(k.lpw, (base) + (i) * 4096)
template <int PASS, int X, int NP>
__device__ __forceinline__ void rec_qkv(const RecW& k, int s, const uint32_t (*wq)[4], const uint32_t (*wk)[4], uint4* wt, Gat& g2, int s2, bool& ok2) {
    constexpr bool BWD = PASS == 2, DIRECT = !(BKA && PASS == 1);
    float aq[4] = {0, 0, 0, 0}, ak[4] = {0, 0, 0, 0}, av[4] = {0, 0, 0, 0};
    constexpr int ma = R_M + X * 4096;
    if (BWD) { TS(1); gat_finish<1>(GSE ? ok2 : gat_store<1>(g2, k), k, s); }
    bar_sync(NB_MF + X, 256);
    uint4 mf = ldsm4o(k.lp, ma + (BWD ? 7 : 0) * 512);
    if (BWD) TS(2); else { TS(0); TSN(13); }
#pragma unroll
    for (int ii = 0; ii < 8; ii++) {
        const int i = BWD ? 7 - ii : ii;
        const uint4 m = mf;
        if (ii < 7) mf = ldsm4o(k.lp, ma + (BWD ? i - 1 : i + 1) * 512);
        if (PASS == 1 && ii == G2I) gat_issue<1>(g2, k, s2, 0);
        SF;
#pragma unroll
        for (int hh = 0; hh < 2; hh++) {
            const int h = BWD ? 1 - hh : hh, ks = 2 * i + h;
            const uint32_t b0 = h ? m.z : m.x, b1 = h ? m.w : m.y;
            mma16(aq, wq[ks][0], wq[ks][1], wq[ks][2], wq[ks][3], b0, b1);
            mma16(ak, wk[ks][0], wk[ks][1], wk[ks][2], wk[ks][3], b0, b1);
            SF;
            mma16(av, wt[ks].x, wt[ks].y, wt[ks].z, wt[ks].w, b0, b1);
            SF;
            if (!BWD && ks + NP < 16) WLD(R_WV, ks + NP < 16 ? ks + NP : 0);
            if (BWD && ks >= NT) WLD(R_WV, ks >= NT ? ks - NT : 0);
            SF;
        }
    }
    if (PASS == 1 && GSE) { ok2 = gat_store<1>(g2, k); SF; }
    const uint32_t ra = vadd(k.lpw, k.dp + R_REM + (X * 2 + (s & 1)) * 6144), va = ((vshr(k.lp, 7) & 1) * 48 ^ k.lp ^ (k.vo & 64)) + (k.vo & ~64u);
    const uint32_t x0 = movm(pack2(aq[0], aq[1])), x1 = movm(pack2(aq[2], aq[3])), x2 = movm(pack2(ak[0], ak[1])), x3 = movm(pack2(ak[2], ak[3]));
    SF;
    asm volatile("stmatrix.sync.aligned.m8n8.x2.shared.b16 [%0+%3],{%1,%2};" ::"r"(va), "r"(pack2(av[0], av[1])), "r"(pack2(av[2], av[3])), "n"(R_LOC + X * 6144) : "memory");
    SF;
    if (STO && DIRECT) st_async4(ra, x0, x1, x2, x3, k.bar + X * 16);
    asm volatile("st.shared.v4.u32 [%0+%5],{%1,%2,%3,%4};" ::"r"(k.lpw), "r"(x0), "r"(x1), "r"(x2), "r"(x3), "n"(R_LOC + X * 6144) : "memory");
    bar_arrive(NB_LOC + X, 320);
    if (!STO && DIRECT) st_async4(ra, x0, x1, x2, x3, k.bar + X * 16);
    SF;
    TS(BWD ? 4 : 3);
}
template <bool BWD, int X>
__device__ __forceinline__ void rec_out(const RecW& k, int s, uint4* wt, Gat& g, int s1) {
    if (BWD) { WLD(R_WO, 17 - NTO); WLD(R_WO, 16 - NTO); }
    TS(BWD ? 8 : 5);
    bar_sync(NB_O + X, 320);
    float r0[4] = {0, 0, 0, 0}, r1[4] = {0, 0, 0, 0};
    constexpr int oa = R_O + X * 2048;
    uint4 bn = lds128o(k.lp, oa + (BWD ? 3 : 0) * 512);
    TS(BWD ? 9 : 6);
    uint2 il;
    uint64_t pm, pe;
#pragma unroll
    for (int ii = 0; ii < 4; ii++) {
        const int i = BWD ? 3 - ii : ii;
        const uint4 b = bn;
        if (ii < 3) bn = lds128o(k.lp, oa + (BWD ? i - 1 : i + 1) * 512);
        else { asm volatile("ld.shared.v2.u32 {%0,%1},[%2+%3];" : "=r"(il.x), "=r"(il.y) : "r"(k.lp), "n"(R_IL + X * 8) : "memory"); pm = gptr(vadd(k.am, acc_slot(s)), k.ah); pe = gptr(vadd(k.ae, acc_slot(s)), k.ah); }
        SF;
        if (BWD && EARLY == ii + 1) { gat_issue<0>(g, k, s1 + 1, 0); SF; }
#pragma unroll
        for (int nn = 0; nn < 4; nn++) {
            const int n = BWD ? 3 - nn : nn, f = 4 * i + n, nx = BWD ? f - NTO + 2 : f + NTO - 2;
            mma16((n & 1) ? r1 : r0, wt[f].x, wt[f].y, wt[f].z, wt[f].w, n >> 1 ? b.z : b.x, n >> 1 ? b.w : b.y);
            SF;
            if (ii * 4 + nn >= 2 && nx >= 0 && nx < 16) WLD(R_WO, nx & 15);
            SF;
        }
    }
    const float i0 = __uint_as_float(il.x), i1 = __uint_as_float(il.y);
    asm volatile("red.relaxed.gpu.global.add.noftz.v4.bf16x2 [%0+%5],{%1,%2,%3,%4};" ::"l"(pm),
                 "r"(pack2(r0[0] * i0, r0[1] * i1)), "r"(pack2(r0[2] * i0, r0[3] * i1)), "r"(pack2(r1[0] * i0, r1[1] * i1)), "r"(pack2(r1[2] * i0, 1.f)), "n"(X * 32768) : "memory");
    asm volatile("red.relaxed.gpu.global.add.noftz.bf16x2 [%0+%2],%1;" ::"l"(pe), "r"(pack2(r1[3] * i1, 1.f)), "n"(X * 1024) : "memory");
    bar_arrive(NB_XG + X, 320);
    SF;
    TS(BWD ? 10 : 7);
}
__device__ __forceinline__ uint32_t pause(uint32_t v, int n) {
#pragma unroll
    for (int i = 0; i < n; i++) asm volatile("shfl.sync.bfly.b32 %0,%0,0,0x1f,0xffffffff;" : "+r"(v));
    return v;
}
template <bool DUAL, int X>
__device__ __forceinline__ void rec_step(const RecW& k, int s, int s2, const uint32_t (*wq)[4], const uint32_t (*wk)[4], uint4* wt) {
    constexpr int NP = NPD;
    uint4 wo[16];
    Gat g;
    bool ok2;
    rec_qkv<DUAL ? 1 : 0, X, NP>(k, s, wq, wk, wt, g, s2, ok2);
    if (DUAL) rec_qkv<2, 1, NP>(k, s2, wq, wk, wt, g, s2, ok2);
    uint32_t wa = k.lpw;
#pragma unroll
    for (int i = 0; i < NTO; i++) {
        wo[i] = lds128o(wa, R_WO + i * 4096);
        if (i % PACE == PACE - 1) wa = k.lpw + (wo[i].x & k.zero);
        SF;
    }
    rec_out<false, X>(k, s, wo, g, s);
    if (DUAL) { rec_out<true, 1>(k, s2, wo, g, s); if (!EARLY) gat_issue<0>(g, k, s + 1, 0); SF; }
#pragma unroll
    for (int i = 0; i < NP; i++) { WLD(R_WV, i); SF; }
    if (!DUAL) gat_issue<X>(g, k, s + 1, pause(wt[NP - 1].x & k.zero, DP1));
    TS(12);
    gat_finish<X>(gat_store<X>(g, k), k, s + 1);
    TS(11);
}

__device__ __forceinline__ void rec_fetch(const CUtensorMap* tm, uint32_t dst, int x, int y, int nx, uint32_t bar) {
#pragma unroll 1
    for (int j = 0; j < 8; j++) tma2d(dst + j * 8192, tm, x + (j / (8 / nx)) * 64, y + (j % (8 / nx)) * 64, bar);
}
__device__ __forceinline__ void rec_weights(const Params& p, uint32_t sb, int head, uint32_t rank, int w) {
    const int lane = threadIdx.x & 31, t = w & 3, WG = w >> 2;
    uint32_t wq[16][4], wk[16][4];
    const uint32_t rowo = (((lane >> 4) << 3) + (lane & 7)) * 128;
    const uint32_t woff = sb + WG * 32768 + rowo + (((2 * t + ((lane >> 3) & 1)) ^ (lane & 7)) << 4);
    const uint32_t qoff = sb + ((w & 1) ? R_STK : R_STQ) + WG * 32768 + rowo + (((2 * (t & 2) + ((lane >> 3) & 1)) ^ (lane & 7)) << 4);
    const uint32_t lw = sb + (lane ^ (lane >> 3)) * 16;
    PROF(threadIdx.x == 0, 3501);
    PROF(threadIdx.x == 0, 3502);
    mbar_wait(sb + R_BAR + RB_INIT * 8, 0);
    PROF(threadIdx.x == 0, 3503);
#pragma unroll
    for (int ks = 0; ks < 16; ks++) {
        uint4 a = ldsm4t(qoff + ks * 2048), b = ldsm4t((qoff ^ 32) + ks * 2048);
        wq[ks][0] = a.x; wq[ks][1] = a.y; wq[ks][2] = a.z; wq[ks][3] = a.w;
        wk[ks][0] = b.x; wk[ks][1] = b.y; wk[ks][2] = b.z; wk[ks][3] = b.w;
    }
    bar_sync(NB_W, 256);
#pragma unroll 4
    for (int ks = 0; ks < 16; ks++) { const uint4 a = ldsm4t(woff + R_STV + ks * 2048); sts128(lw + w * 512 + R_WV + ks * 4096, a.x, a.y, a.z, a.w); }
    bar_sync(NB_W, 256);
    if (threadIdx.x == 0) {
        mbar_expect(sb + R_BAR + RB_INIT * 8, 65536);
        rec_fetch(&p.tm[4], sb + R_STV, rank * 256, head * 128, 4, sb + R_BAR + RB_INIT * 8);
    }
    __syncwarp();
    mbar_wait(sb + R_BAR + RB_INIT * 8, 1);
#pragma unroll 4
    for (int f = 0; f < 16; f++) {
        const uint4 a = ldsm4t(sb + R_STV + (w >> 1) * 16384 + (f >> 1) * 2048 + rowo + ((((w & 1) * 4 + (f & 1) * 2 + ((lane >> 3) & 1)) ^ (lane & 7)) << 4));
        sts128(lw + w * 512 + R_WO + f * 4096, a.x, a.y, a.z, a.w);
    }
    PROF(threadIdx.x == 0, 3504);
    __syncthreads();
    cluster_sync();
    PROF(threadIdx.x == 0, 3505);
    RecW k;
    k.am = __shfl_sync(0xffffffffu, (uint32_t)(size_t)acc_base() + acc_main(rank, threadIdx.x), lane);
    k.ae = __shfl_sync(0xffffffffu, (uint32_t)(size_t)acc_base() + acc_extra(rank, threadIdx.x), lane);
    k.ah = (uint32_t)((size_t)acc_base() >> 32);
    k.sb = sb; k.zero = p.zero;

    k.dp = mapa(sb, rank ^ 1) - sb;
    k.lp = __shfl_sync(0xffffffffu, lw, lane);
    k.lpw = __shfl_sync(0xffffffffu, lw + w * 512, lane);
    k.vo = 4096 + w * 256 + (w & 1) * 64;
    k.bar = sb + k.dp + R_BAR + (RB_QK + WG) * 8;
    int it = 0;
    uint4 wt[16];
#pragma unroll
    for (int i = 0; i < NPD; i++) WLD(R_WV, i);
    gat_finish<0>(false, k, 0);
#pragma unroll 1
    for (; it < min(p.b1, p.e0); it++) { TSET(it, w == GPW ? 0 : 3); rec_step<false, 0>(k, it, it, wq, wk, wt); }
#pragma unroll 1
    for (; it < p.e0; it++) { TSET(it, w == GPW ? 0 : 3); rec_step<true, 0>(k, it, it - p.b1, wq, wk, wt); }
    if (it < p.nit) gat_finish<1>(false, k, it - p.b1);
#pragma unroll 1
    for (; it < p.nit; it++) { TSET(it, w == GPW ? 0 : 3); rec_step<false, 1>(k, it - p.b1, it - p.b1, wq, wk, wt); }
}

__device__ __forceinline__ void mma16_top(float* c, uint32_t a0, uint32_t a2, uint32_t b0, uint32_t b1) {
    asm volatile("{.reg .b32 j; mma.sync.aligned.m16n8k16.row.col.f32.bf16.bf16.f32 {%0,%1,%2,%3},{%4,j,%5,j},{%6,%7},{%0,%1,%2,%3};}"
                 : "+f"(c[0]), "+f"(c[1]), "+f"(c[2]), "+f"(c[3]) : "r"(a0), "r"(a2), "r"(b0), "r"(b1));
}
__device__ __forceinline__ void rec_load_tile(uint32_t sb, int X, int s, int head, uint32_t rank) {
    const uint32_t bar = sb + R_BAR + (RB_T + X) * 8;
    const uint4* src = g_qkv[X] + (size_t)(s * 32 + head) * 1536;
    mbar_expect1(bar, TILE);
    bulk_g2s1(sb + R_T + X * TILE, src + 512, 16384, bar, POL_LAST);
    bulk_g2s1(sb + R_T + X * TILE + 16384, src + rank * 256, 4096, bar, POL_LAST);
}
__device__ __forceinline__ bool chunk_ready(int X, int s) {
    unsigned v;
    asm volatile("ld.relaxed.gpu.global.u32 %0,[%1];" : "=r"(v) : "l"(cnt_ptr(C_QKV0 + X, s >> 2)) : "memory");
    return __all_sync(0xffffffffu, v >= 384);
}
__device__ __forceinline__ uint4 hadd4(uint4 a, uint4 b) { return make_uint4(hadd2(a.x, b.x), hadd2(a.y, b.y), hadd2(a.z, b.z), hadd2(a.w, b.w)); }
struct RecH { uint32_t lw, lm, lq, lv, lu, sb, zero, ts, tn; };
__device__ __forceinline__ void rec_publish(int X, int s) {
    asm volatile("{.reg .pred p; cp.async.bulk.wait_group 0; elect.sync _|p,0xffffffff; @p red.relaxed.gpu.global.add.u32 [%0],4;}" ::"l"(cnt_ptr(C_O0 + X, s >> 2)) : "memory");
}
__device__ __forceinline__ void rec_mattn(const RecH& k, uint32_t dp, int X, int j, int s, bool qk, uint4 (*V)[4], uint4* vm) {
    const uint32_t sb = k.sb, to = R_T + X * TILE + j * 2048, lo = R_LOC + X * 6144, ro = R_REM + (X * 2 + (s & 1)) * 6144;
    const uint32_t bar = sb + R_BAR + (X * 2 + j) * 8;
    uint4 K[2][4];
    mbar_wait(sb + R_BAR + (RB_T + X) * 8, s & 1);
    TS(1);
#pragma unroll
    for (int i = 0; i < 8; i++) K[i >> 2][i & 3] = ldsm4(k.lm + (to + (i >> 2) * 1024 + ((i >> 1) & 1) * 4096 + (i & 1) * 512));
    asm volatile("cp.async.bulk.wait_group 0;" ::: "memory");
    bar_sync(NB_LOC + X, 320);
    fence_async_smem();
    if (qk) asm volatile("{.reg .pred p; elect.sync _|p,0xffffffff; @p cp.async.bulk.shared::cluster.shared::cta.mbarrier::complete_tx::bytes [%0],[%1],2048,[%2];}"
                         ::"r"(sb + dp + ro + j * 2048), "r"(sb + lo + j * 2048), "r"(bar + dp + RB_QK * 8) : "memory");
    asm volatile("{.reg .pred p; elect.sync _|p,0xffffffff; @p cp.async.bulk.shared::cluster.shared::cta.mbarrier::complete_tx::bytes [%0],[%1],1024,[%2];}"
                 ::"r"(sb + dp + ro + 4096 + j * 1024), "r"(sb + lo + 4096 + j * 1024), "r"(bar + dp + RB_V * 8) : "memory");
    uint4 u[4];
#pragma unroll
    for (int i = 0; i < 4; i++) u[i] = ldsm4(k.lm + (lo + j * 2048 + i * 512));
    TS(2);
    mbar_wait(bar + RB_QK * 8, s & 1);
    TS(3);
    float S[5][4];
#pragma unroll
    for (int i = 0; i < 5; i++) S[i][0] = S[i][1] = S[i][2] = S[i][3] = 0;
    {
        uint4 r[4];
#pragma unroll
        for (int i = 0; i < 4; i++) r[i] = ldsm4(k.lm + (ro + j * 2048 + i * 512));
        SF;
#pragma unroll
        for (int e = 0; e < 2; e++) {
            uint4& km = u[2 * e + 1];
            const uint32_t q0 = hadd2(u[2 * e].x, r[2 * e].x), q1 = hadd2(u[2 * e].y, r[2 * e].y);
            mma16_top(S[0], q0, q1, K[e][0].x, K[e][0].y);
            km.x = hadd2(km.x, r[2 * e + 1].x); km.y = hadd2(km.y, r[2 * e + 1].y);
            SF;
            mma16_top(S[1], q0, q1, K[e][1].x, K[e][1].y);
            const uint32_t q2 = hadd2(u[2 * e].z, r[2 * e].z), q3 = hadd2(u[2 * e].w, r[2 * e].w);
            SF;
            mma16_top(S[2], q0, q1, K[e][2].x, K[e][2].y);
            km.z = hadd2(km.z, r[2 * e + 1].z); km.w = hadd2(km.w, r[2 * e + 1].w);
            SF;
            mma16_top(S[3], q0, q1, K[e][3].x, K[e][3].y);
            mma16_top(S[4], q0, q1, km.x, km.y);
            SF;
#pragma unroll
            for (int i = 0; i < 4; i++) { mma16_top(S[i], q2, q3, K[e][i].z, K[e][i].w); SF; }
            mma16_top(S[4], q2, q3, km.z, km.w);
            SF;
        }
    }
#define VLD(a, b) _Pragma("unroll") for (int i = (a); i < (b); i++) V[i >> 2][i & 3] = ldsm4t((k.lv ^ ((i & 1) * 0x20)) + (to + 8192 + (i >> 2) * 4096 + ((i >> 1) & 1) * 1024))
    VLD(0, VE);
    SF;
    const uint32_t sxr = R_SX + (X * 2 + j) * 2560, sxw = R_SX + (X * 2 + (j ^ 1)) * 2560;
    sts128(k.lw + sxw, __float_as_uint(S[0][0]), __float_as_uint(S[0][1]), __float_as_uint(S[1][0]), __float_as_uint(S[1][1]));
    SF;
    sts128(k.lw + (sxw + 512), __float_as_uint(S[2][0]), __float_as_uint(S[2][1]), __float_as_uint(S[3][0]), __float_as_uint(S[3][1]));
    SF;
    sts64(k.lw + (sxw + 1024), __float_as_uint(S[4][0]), __float_as_uint(S[4][1]));
    TS(4);
    bar_sync(NB_PAIR + X, 64);
    {
        const uint4 a = lds128(k.lw + sxr), b = lds128(k.lw + (sxr + 512));
        const uint2 c = lds64(k.lw + (sxr + 1024));
        SF;
        VLD(VE, VF);
        SF;
        S[0][0] += __uint_as_float(a.x); S[0][1] += __uint_as_float(a.y); S[1][0] += __uint_as_float(a.z); S[1][1] += __uint_as_float(a.w);
        S[2][0] += __uint_as_float(b.x); S[2][1] += __uint_as_float(b.y); S[3][0] += __uint_as_float(b.z); S[3][1] += __uint_as_float(b.w);
        S[4][0] += __uint_as_float(c.x); S[4][1] += __uint_as_float(c.y);
    }
    float m = fmaxf(fmaxf(fmaxf(S[0][0], S[0][1]), fmaxf(S[1][0], S[1][1])), fmaxf(fmaxf(S[2][0], S[2][1]), fmaxf(S[3][0], S[3][1])));
    m = fmaxf(m, fmaxf(S[4][0], S[4][1]));
    m = fmaxf(m, __shfl_xor_sync(0xffffffffu, m, 1));
    const float m2 = __shfl_xor_sync(0xffffffffu, m, 2);
    SF;
    VLD(VF, 8);
    uint32_t ok;
    asm volatile("{.reg .pred p; mbarrier.test_wait.parity.shared::cta.b64 p,[%1],%2; selp.u32 %0,1,0,p;}" : "=r"(ok) : "r"(bar + RB_V * 8), "r"(s & 1) : "memory");
    uint4 vr0 = ldsm4(k.lu + (ro + 4096 + j * 1024)), vr1 = ldsm4(k.lu + (ro + 4608 + j * 1024));
    vm[0] = ldsm4(k.lu + (lo + 4096 + j * 1024)); vm[1] = ldsm4(k.lu + (lo + 4608 + j * 1024));
    SF;
    TS(5);
    m = fmaxf(m, m2) * -SC_LOG2E;
    uint32_t P[5];
#pragma unroll
    for (int i = 0; i < 5; i++) P[i] = pack2(ex2(fmaf(S[i][0], SC_LOG2E, m)), ex2(fmaf(S[i][1], SC_LOG2E, m)));
    float o[4][4], l[4] = {0, 0, 0, 0};
    const uint32_t ONE = 0x3f803f80u;
    mma16_top(l, ONE, ONE, P[0], P[1]);
#pragma unroll
    for (int t = 0; t < 4; t++) { o[t][0] = o[t][1] = o[t][2] = o[t][3] = 0; mma16(o[t], V[0][t].x, V[0][t].y, V[0][t].z, V[0][t].w, P[0], P[1]); }
    mma16_top(l, ONE, ONE, P[2], P[3]);
#pragma unroll
    for (int t = 0; t < 4; t++) mma16(o[t], V[1][t].x, V[1][t].y, V[1][t].z, V[1][t].w, P[2], P[3]);
    if (!__all_sync(0xffffffffu, ok)) {
        mbar_wait(bar + RB_V * 8, s & 1);
        vr0 = ldsm4(k.lu + (ro + 4096 + j * 1024)); vr1 = ldsm4(k.lu + (ro + 4608 + j * 1024));
    }
    TS(6);
    vm[0] = hadd4(vm[0], vr0); vm[1] = hadd4(vm[1], vr1);
    mma8(l, ONE, ONE, P[4]);
    mma8(o[0], vm[0].x, vm[0].y, P[4]); mma8(o[1], vm[0].z, vm[0].w, P[4]); mma8(o[2], vm[1].x, vm[1].y, P[4]); mma8(o[3], vm[1].z, vm[1].w, P[4]);
    if (j == 0) sts64(k.lw + (R_IL + X * 8), __float_as_uint(rcp(l[0])), __float_as_uint(rcp(l[1])));
#pragma unroll
    for (int t = 0; t < 4; t += 2)
        asm volatile("stmatrix.sync.aligned.m8n8.x4.trans.shared.b16 [%0],{%1,%2,%3,%4};" ::"r"(k.lm + (R_O + X * 2048 + j * 1024 + t * 256)),
                     "r"(pack2(o[t][0], o[t][1])), "r"(pack2(o[t][2], o[t][3])), "r"(pack2(o[t + 1][0], o[t + 1][1])), "r"(pack2(o[t + 1][2], o[t + 1][3])) : "memory");
    bar_arrive(NB_O + X, 320);
    PROF(k.lw == sb && j == 0, X * 64 + s);
    TS(7);
#pragma unroll
    for (int e = 0; e < 2; e++) sts128(k.lw + (ro + j * 2048 + e * 1024), u[2 * e + 1].x, u[2 * e + 1].y, u[2 * e + 1].z, u[2 * e + 1].w);
    mbar_expect1(bar + RB_QK * 8, 2048); mbar_expect1(bar + RB_V * 8, 1024);
}
template <int MT>
__device__ __forceinline__ void rec_xattn(const RecH& k, int X, int j, int s, int head, bool early, const uint4 (*V)[4], const uint4* vmm) {
    constexpr int NTL = 3 + 2 * MT;
    const uint32_t sb = k.sb, to = R_T + X * TILE + j * 2048, ro = R_REM + (X * 2 + (s & 1)) * 6144 + j * 2048;
    const uint32_t sxw = R_SX + (X * 2 + j) * 2560, sxr = R_SX + (X * 2 + (j ^ 1)) * 2560;
    float S[NTL][4];
#pragma unroll
    for (int i = 0; i < NTL; i++) S[i][0] = S[i][1] = S[i][2] = S[i][3] = 0;
#pragma unroll
    for (int e = 0; e < 2; e++) {
        const uint4 q0 = ldsm4(k.lq + (to + 16384 + e * 1024)), q1 = ldsm4((k.lq ^ 0x20) + (to + 16384 + e * 1024));
#pragma unroll
        for (int i = 0; i < NTL; i++) {
            const uint4 kk = i ? ldsm4(k.lm + (to + e * 1024 + ((i - 1) >> 1) * 4096 + ((i - 1) & 1) * 512)) : lds128(k.lw + (ro + e * 1024));
            mma16(S[i], q0.x, q0.y, q0.z, q0.w, kk.x, kk.y); mma16(S[i], q1.x, q1.y, q1.z, q1.w, kk.z, kk.w);
        }
    }
#pragma unroll
    for (int i = 0; i < NTL; i++) sts128(k.lw + (sxw + i * 512), __float_as_uint(S[i][0]), __float_as_uint(S[i][1]), __float_as_uint(S[i][2]), __float_as_uint(S[i][3]));
    SF;
    bar_sync(NB_PAIR + X, 64);
    TS(9);
    if (early) rec_load_tile(sb, X, s + 1, head, MT);
#pragma unroll
    for (int i = 0; i < NTL; i++) {
        const uint4 r = lds128(k.lw + (sxr + i * 512));
        S[i][0] += __uint_as_float(r.x); S[i][1] += __uint_as_float(r.y); S[i][2] += __uint_as_float(r.z); S[i][3] += __uint_as_float(r.w);
    }
    const int g = (k.lw >> 6) & 7, c = ((k.lw >> 4) ^ (k.lw >> 7)) & 3;
    const float NEG = -__int_as_float(0x7f800000);
    if (2 * c > g) { S[NTL - 2][0] = NEG; S[NTL - 1][2] = NEG; }
    if (2 * c + 1 > g) { S[NTL - 2][1] = NEG; S[NTL - 1][3] = NEG; }
    float m0 = fmaxf(S[0][0], S[0][1]), m1 = fmaxf(S[0][2], S[0][3]);
#pragma unroll
    for (int i = 1; i < NTL; i++) { if (i < NTL - 1) m0 = fmaxf(m0, fmaxf(S[i][0], S[i][1])); m1 = fmaxf(m1, fmaxf(S[i][2], S[i][3])); }
    m0 = fmaxf(m0, __shfl_xor_sync(0xffffffffu, m0, 1)); m1 = fmaxf(m1, __shfl_xor_sync(0xffffffffu, m1, 1));
    m0 = fmaxf(m0, __shfl_xor_sync(0xffffffffu, m0, 2)); m1 = fmaxf(m1, __shfl_xor_sync(0xffffffffu, m1, 2));
    m0 *= -SC_LOG2E; m1 *= -SC_LOG2E;
    uint32_t P[NTL][2];
#pragma unroll
    for (int i = 0; i < NTL; i++) {
        P[i][0] = i < NTL - 1 ? pack2(ex2(fmaf(S[i][0], SC_LOG2E, m0)), ex2(fmaf(S[i][1], SC_LOG2E, m0))) : 0u;
        P[i][1] = pack2(ex2(fmaf(S[i][2], SC_LOG2E, m1)), ex2(fmaf(S[i][3], SC_LOG2E, m1)));
    }
    float l[4] = {0, 0, 0, 0};
#pragma unroll
    for (int i = 0; i < NTL; i++) mma8(l, P[i][0], P[i][1], 0x3f803f80u);
    const float l0 = rcp(l[0]), l1 = rcp(l[2]);

    const uint32_t st = sb + sxr + c * 128 + g * 16;
#pragma unroll
    for (int e = 0; e < 2; e++) {
        const uint4 vm = vmm[e];
        uint32_t u[2][4];
#pragma unroll
        for (int n = 0; n < 4; n++) {
            float a[4] = {0, 0, 0, 0};
#pragma unroll
            for (int m = 0; m <= MT; m++) {
                const uint4 v = V[m][e * 2 + (n >> 1)];
                mma8(a, P[1 + 2 * m][0], P[1 + 2 * m][1], (n & 1) ? v.y : v.x); mma8(a, P[2 + 2 * m][0], P[2 + 2 * m][1], (n & 1) ? v.w : v.z);
            }
            mma8(a, P[0][0], P[0][1], n == 0 ? vm.x : n == 1 ? vm.y : n == 2 ? vm.z : vm.w);
            u[0][n] = pack2(a[0] * l0, a[1] * l0); u[1][n] = pack2(a[2] * l1, a[3] * l1);
        }
        sts128(st + e * 512, u[0][0], u[0][1], u[0][2], u[0][3]); sts128(st + e * 512 + 1024, u[1][0], u[1][1], u[1][2], u[1][3]);
    }
    TS(10);
}
__device__ __forceinline__ void rec_attn(const Params& p, uint32_t sb, int X, int j, int head, uint32_t rank) {
    const int lane = threadIdx.x & 31;
    RecH k;
    k.lw = __shfl_sync(0xffffffffu, sb + (lane ^ (lane >> 3)) * 16, lane);
    k.lm = __shfl_sync(0xffffffffu, sb + ((lane & 7) * 4 + ((lane >> 3) ^ ((lane & 7) >> 1))) * 16, lane);
    k.lq = __shfl_sync(0xffffffffu, sb + ((lane >> 3) & 1) * 512 + ((lane & 7) * 4 + ((lane >> 4) ^ ((lane & 7) >> 1))) * 16, lane);
    k.lv = __shfl_sync(0xffffffffu, sb + (lane >> 4) * 512 + ((lane & 7) * 4 + (((lane >> 3) & 1) ^ ((lane & 7) >> 1))) * 16, lane);
    k.lu = __shfl_sync(0xffffffffu, sb + ((lane & 6) * 4 + (((lane >> 3) * 2 + (lane & 1)) ^ (lane & 6))) * 16, lane);
    k.sb = sb; k.zero = p.zero;
    const uint32_t dp = mapa(sb, rank ^ 1) - sb;
    char* zp = acc_base() + (j ? X * 32768 + acc_main(rank, head * 8) : X * 1024 + acc_extra(rank, head * 8));
    mbar_expect1(sb + R_BAR + (RB_QK + X * 2 + j) * 8, 2048); mbar_expect1(sb + R_BAR + (RB_V + X * 2 + j) * 8, 1024);
    bool early = j;
    int rc = -1;
#pragma unroll 1
    for (int s = 0; s < 64; s++) {
        TSET(X ? s + p.b1 : s, j == GPJ ? 1 + X : 3);
        TS(0);
        if (!early && !j) { wait_cnt_warp(cnt_ptr(C_QKV0 + X, s >> 2), 384); rec_load_tile(sb, X, s, head, rank); }
        if (PFD && j && s + PFD < 64 && (PFB || !X)) {
            if (rc < (s + PFD) >> 2 && chunk_ready(X, s + PFD)) rc = (s + PFD) >> 2;
            if (rc == (s + PFD) >> 2)
                asm volatile("{.reg .pred p; elect.sync _|p,0xffffffff; @p cp.async.bulk.prefetch.L2.global [%0],12288;}" ::"l"(g_qkv[X] + (size_t)((s + PFD) * 32 + head) * 1536 + rank * 768) : "memory");
        }
        early = !j && s < 63 && ((s & 3) != 3 || chunk_ready(X, s + 1));
        uint4 V[2][4], vm[2];
        rec_mattn(k, dp, X, j, s, BKA && !X && s >= p.b1, V, vm);
        bar_sync(NB_XG + X, 320);
        TS(8);
        if (rank) rec_xattn<1>(k, X, j, s, head, early, V, vm); else rec_xattn<0>(k, X, j, s, head, early, V, vm);
        fence_async_smem();
        __syncwarp();
        asm volatile("{.reg .pred p; elect.sync _|p,0xffffffff;\n"
                     "@p cp.async.bulk.global.shared::cta.bulk_group.L2::cache_hint [%0],[%1],2048,%2;\n"
                     "@p cp.async.bulk.global.shared::cta.bulk_group [%3],[%4],%5;\n"
                     "cp.async.bulk.commit_group;}"
                     ::"l"(g_o[X] + ((s >> 2) * 64 + head * 2 + j) * 1024 + ((s & 3) * 2 + rank) * 128), "r"(sb + R_SX + (X * 2 + (j ^ 1)) * 2560),
                       "l"((X && s < 40) ? POL_LATE : POL_SOON), "l"(zp + acc_slot(s + 2)), "r"(sb + R_Z), "r"(j ? 128 : 32) : "memory");
        if ((s & 3) == 3) rec_publish(X, s);
    }
}

__device__ __forceinline__ void rec_init(const Params& p, uint32_t sb, int head, uint32_t rank) {
    const uint32_t b = sb + R_BAR;
    const int i = threadIdx.x - 320;
    if (i >= 0 && i < RB_N) {
        mbar_init(b + i * 8, 1);
        asm volatile("fence.mbarrier_init.release.cluster;" ::: "memory");
    }
    if (i == 0) mbar_expect(b + RB_INIT * 8, 196608);
    if (i >= 0 && i < 32) sts32(sb + R_Z + i * 4, 0);
}

#define NSTGN 8
constexpr int NSTG = NSTGN, STG_B = 24576;
#define LAGQ 1
#define LAGH 3
constexpr int NSB = 8;
constexpr int B_OUT = NSTG * STG_B  , B_UT = B_OUT, B_YT = B_UT + 16384, B_SP = B_YT  ,
              B_ST = 229376  , B_BAR = 231936;
static_assert(B_OUT + NSB * 4096 <= B_ST && B_ST + 2048 <= B_BAR && B_YT + 10240 <= B_ST, "smem map");
enum { BB_FULL = 0, BB_EMPTY = 8, BB_SF = 16  , BB_GO = 18, BB_DONE = 20  , BB_IDLE = 22  , BB_N = 30 };
enum { NB_C = 11, NB_WG = 12   };

__device__ __forceinline__ void bulk_init(uint32_t sb) {
    const int i = threadIdx.x - 320;
    if (i >= 0 && i < BB_N) {
        mbar_init(sb + B_BAR + i * 8, (i >= BB_EMPTY && i < BB_EMPTY + NSTG) ? 4 : i >= BB_DONE ? 4 : 1);
        asm volatile("fence.mbarrier_init.release.cluster;" ::: "memory");
    }
}

struct Task { int type, layer, ch, a, b, c, blk; bool pair, dry; };
__device__ __forceinline__ Task task_of(uint32_t tk, uint32_t rank) {
    Task t;
    t.type = tk & 7; t.layer = (tk >> 3) & 1; t.a = (tk >> 8) & 255; t.b = (tk >> 16) & 255; t.c = (tk >> 24) & 127; t.dry = tk >> 31;
    t.pair = t.type <= T_OP && (t.c & 64);
    t.ch = ((tk >> 4) & 15) + (t.pair ? rank : 0);
    t.blk = t.type == T_QKV ? 2 * (t.a + (t.pair ? 0 : rank * t.b)) : 192 + (t.pair ? (t.c >> 2) & 4 : rank * 4);
    return t;
}
__device__ __forceinline__ void bulk_producer(const Params& p, uint32_t sb, int cl, uint32_t rank) {
    int st = 0; uint32_t ph = 1;
    const int tag = __shfl_sync(0xffffffffu, lds32(sb + S_TAG), 0);
    bool gated = false;
#define ACQ(bytes) do { mbar_wait(sb + B_BAR + (BB_EMPTY + st) * 8, ph); mbar_expect1(sb + B_BAR + (BB_FULL + st) * 8, bytes); } while (0)
#define NEXT do { if (++st == NSTG) { st = 0; ph ^= 1; } } while (0)
#pragma unroll 1
    for (int ti = 0; ti < MAXT; ti++) {
        const Task t = task_of(p.task[cl][ti], rank);
        const int layer = t.layer, ch = t.ch;
        if (t.type == T_END) break;
        if (t.type <= T_OP) {
            const bool qkv = t.type == T_QKV;
            const int rg = qkv ? (layer * 16 + ch) * 128 : 4096 + ((layer * 16 + ch) * 64 + t.a) * 16;
            const int nh = qkv ? 16 : 2 * t.b, row = qkv ? 0 : t.a * 64, bytes = qkv ? 16384 : STG_B;
            const unsigned* dep = cnt_ptr(qkv ? (layer ? C_CV : C_ST) : C_O0 + layer, ch);
            const unsigned need = qkv ? (layer ? 32 : ch < 2 ? 0 : 16) : 512;
            const uint64_t pol = qkv ? POL_N : POL_LAST;
            const CUtensorMap *tb = &p.t3[t.pair || qkv][t.blk >> 6], *ta = &p.ta[t.pair];
            const uint32_t db = sb + 8192 + (t.pair && !qkv ? rank * 8192 : 0), da = sb + (t.pair ? 0 : rank * 4096);
            const int zb = (t.blk & 63) + (t.pair && !qkv ? rank * 2 : 0), ya = rg + (t.pair ? 0 : rank * 8);
            const uint16_t mb = t.pair ? 3 : 1 << rank, ma = t.pair ? 1 << rank : 3;
            const int skip = t.pair && qkv ? rank ^ 1 : 2;
            int pend = qkv ? 2 : 0;
            bool wait = false;
            if (!t.dry) {
                unsigned v = 0;
                if (gated) asm volatile("ld.relaxed.gpu.global.u32 %0,[%1];" : "=r"(v) : "l"(dep) : "memory");
                wait = !gated || !__all_sync(0xffffffffu, v >= need);
                if (wait) pend = min(nh, gated ? NSTG : 4);
            }
            if (PFC && !qkv && !layer && (t.c & 15) < 8) {
                const int q = (t.c & 15) * 2 + rank;
                asm volatile("{.reg .pred p; elect.sync _|p,0xffffffff; @p cp.async.bulk.prefetch.L2.global [%0],8192; @p cp.async.bulk.prefetch.L2.global [%1],%2;}"
                             ::"l"(g_xA[0] + (ch * 16 + q) * 512), "l"(g_P + q * 16 * 32 * PW), "r"((2 + (ch & 1)) * 32 * PW * 4) : "memory");
            }
#pragma unroll 1
            while (qkv && st) { ACQ(0); NEXT; }
            int h = 0;
            const int s0 = st;
#pragma unroll 1
            for (; h < pend; h++) {
                ACQ(bytes + (qkv && h < 2 ? (layer ? 8192 : 1024) : 0));
                if ((h & 1) != skip) tma3d_mc(db + st * STG_B, tb, row + h * 32, zb, sb + B_BAR + (BB_FULL + st) * 8, mb);
                NEXT;
            }
            if (wait) {
                if (!gated) { wait_cnt_warp(g_gate, lds32(sb + S_GATE)); gated = true; }
                if (need) wait_cnt_warp(dep, need);
            }
#pragma unroll 1
            for (int k = 0; k < pend; k++) {
                const int s2 = s0 + k - (s0 + k >= NSTG ? NSTG : 0);
                if (qkv && k < 2) bulk_g2s1(sb + s2 * STG_B + 16384, g_st[layer] + ch * 2048 + (layer ? k * 1024 : tag * 128), layer ? 8192 : 1024, sb + B_BAR + (BB_FULL + s2) * 8, POL_N);
                tma2d_mc(da + s2 * STG_B, ta, (k & 1) * 256, ya + (k >> 1) * 16, sb + B_BAR + (BB_FULL + s2) * 8, ma, pol);
            }
#pragma unroll 1
            for (; h < nh; h++) {
                ACQ(bytes);
                if ((h & 1) != skip) tma3d_mc(db + st * STG_B, tb, row + h * 32, zb, sb + B_BAR + (BB_FULL + st) * 8, mb);
                tma2d_mc(da + st * STG_B, ta, (h & 1) * 256, ya + (h >> 1) * 16, sb + B_BAR + (BB_FULL + st) * 8, ma, pol);
                NEXT;
            }
#pragma unroll 1
            for (h = 0; h < 4 && !qkv && !layer; h++) { ACQ(0); NEXT; }
            if (qkv) {
#pragma unroll 1
                for (h = 8; h < 8 * t.b; h++) {
                    const int blk = t.blk + (h >> 3) * 2;
                    ACQ(16384);
                    if (skip != 0) tma3d_mc(sb + st * STG_B, &p.t3[1][blk >> 6], (h & 7) * 64, blk & 63, sb + B_BAR + (BB_FULL + st) * 8, mb);
                    if (skip != 1) tma3d_mc(sb + st * STG_B + 8192, &p.t3[1][blk >> 6], (h & 7) * 64 + 32, blk & 63, sb + B_BAR + (BB_FULL + st) * 8, mb);
                    NEXT;
                }
            }
        } else if (t.type == T_CV) {
            const int q = t.a + rank;
            if (!gated && !t.dry) { wait_cnt_warp(g_gate, lds32(sb + S_GATE)); gated = true; }
            if (layer) {
                wait_cnt_warp(cnt_ptr(C_U, ch - 2), 32);
#pragma unroll 1
                for (int j = ch + 1; j >= 2; j--) {
                    ACQ(16 * PW * 4 + (j > 2 ? 4096 : 0));
                    bulk_g2s1(sb + st * STG_B, g_P + (((q >> 1) * 16 + j) * 2 + (q & 1)) * 16 * PW, 16 * PW * 4, sb + B_BAR + (BB_FULL + st) * 8, POL_N);
                    if (j > 2) bulk_g2s1(sb + st * STG_B + 12288, g_u + (((q >> 1) * 16 + ch + 1 - j) * 2 + (q & 1)) * 256, 4096, sb + B_BAR + (BB_FULL + st) * 8, POL_N);
                    NEXT;
                }
            } else {
#pragma unroll 1
                for (int j = min(ch, 1 + (ch & 1)); j >= 0; j--) {
                    if (j == 0 && ch >= 2) {
                        if (!t.dry) wait_cnt_warp(cnt_ptr(C_H, ch & ~1), 64);
#pragma unroll 1
                        for (int i = 0; i < ((ch & 1) || ch == 2 ? 1 : 2); i++) {
                            ACQ(16384);
                            bulk_g2s1(sb + st * STG_B, g_carry[i] + (ch * 16 + q) * 1024, 16384, sb + B_BAR + (BB_FULL + st) * 8, POL_LAST);
                            NEXT;
                        }
                    }
                    ACQ(32 * PW * 4);
                    bulk_g2s1(sb + st * STG_B, g_P + (q * 16 + j) * 32 * PW, 32 * PW * 4, sb + B_BAR + (BB_FULL + st) * 8, POL_N);
                    NEXT;
                }
            }
        }
    }
}

__device__ __forceinline__ uint4* qkv_dst(int layer, int ch, int w, int blk);
__device__ __forceinline__ uint4* op_dst(int layer, int ch, int slot, int w, uint32_t rank);
__device__ __forceinline__ uint64_t out_pol(int type, int layer, int ch) { return (type == T_QKV ? (!layer && ch > 1) : (layer && ch < 10)) ? POL_LATE : POL_SOON; }
__device__ __forceinline__ void bulk_release(const Params& p, uint32_t sb, int cl, uint32_t rank, int wg) {
    int nd = 0;
    for (int ti = 0; ti < MAXT; ti++) {
        const Task t = task_of(p.task[cl][ti], rank);
        const int type = t.type, layer = t.layer, ch = t.ch;
        if (type == T_END) break;
        if (type == T_FIN || (type == T_OP && (t.c & 32))) continue;
        if (type == T_OP && !layer) {
            mbar_wait(sb + B_BAR + (BB_DONE + wg) * 8, nd & 1);
            nd++;
            const int s0 = __shfl_sync(0xffffffffu, lds32(sb + B_ST + wg * 4), 0) + wg * 2;
            fence_async_smem();
#pragma unroll 1
            for (int w = 0; w < 4; w++)
                asm volatile("{.reg .pred p; elect.sync _|p,0xffffffff; @p cp.async.bulk.global.shared::cta.bulk_group.L2::cache_hint [%0],[%1],8192,%2;}"
                             ::"l"(op_dst(0, ch, t.c & 15, wg * 4 + w, rank)), "r"(sb + ((s0 + (w >> 1)) & (NSTG - 1)) * STG_B + (w & 1) * 8192), "l"(POL_SOON) : "memory");
            mbar_arrive1(sb + B_BAR + (BB_SF + wg) * 8);
            asm volatile("{.reg .pred p; cp.async.bulk.commit_group; cp.async.bulk.wait_group 0; elect.sync _|p,0xffffffff; @p red.relaxed.gpu.global.add.u32 [%0],1;}"
                         ::"l"(cnt_ptr(C_OP0 + rank * 2 + wg, ch)) : "memory");
#pragma unroll 1
            for (int i = 0; i < 8; i++) mbar_arrive1_cluster(mapa(sb + B_BAR + (BB_EMPTY + ((s0 + (i >> 2)) & (NSTG - 1))) * 8, i & 1));
            continue;
        }
        unsigned* cnt = cnt_ptr(type == T_QKV ? C_QKV0 + layer : type == T_OP ? C_OP1 : layer ? C_H : C_CV, ch);
#pragma unroll 1
        for (int u = 0; u < (type == T_QKV ? t.b : 1); u++) {
            const uint4* dst = type == T_QKV ? qkv_dst(layer, ch, wg * 4, t.blk + 2 * u) : op_dst(1, ch, t.c & 15, wg * 4, (t.blk >> 2) & 1) + 256;
            mbar_wait(sb + B_BAR + (BB_DONE + wg) * 8, nd & 1);
            nd++;
            if (type != T_CV) {
                fence_async_smem();
#pragma unroll
                for (int w = 0; w < 4; w++)
                    asm volatile("{.reg .pred p; elect.sync _|p,0xffffffff; @p cp.async.bulk.global.shared::cta.bulk_group.L2::cache_hint [%0],[%1],4096,%2;}"
                                 ::"l"(dst + (type == T_QKV ? (w >> 1) * 49152 + (w & 1) * 256 : w * 1024)), "r"(sb + B_OUT + (wg * 4 + w) * 4096), "l"(out_pol(type, layer, ch)) : "memory");
                asm volatile("cp.async.bulk.commit_group; cp.async.bulk.wait_group 0;" ::: "memory");
            }
            if (type != T_QKV) fence_async();
            if (!t.dry) asm volatile("{.reg .pred p; elect.sync _|p,0xffffffff; @p red.relaxed.gpu.global.add.u32 [%0],%1;}" ::"l"(cnt), "r"(type == T_QKV ? 2 : type == T_OP ? t.b : 1) : "memory");
            if (type == T_CV && !layer && !t.dry) {
                asm volatile("{.reg .pred p; elect.sync _|p,0xffffffff; @p cp.async.bulk.global.shared::cta.bulk_group [%0],[%1],4096;\n"
                             "cp.async.bulk.commit_group; cp.async.bulk.wait_group 0; @p red.relaxed.gpu.global.add.u32 [%2],1;}"
                             ::"l"(g_u + ((t.a + rank) * 16 + ch) * 512 + wg * 256), "r"(sb + B_UT + (ch & 1) * 8192 + wg * 4096), "l"(cnt_ptr(C_U, ch)) : "memory");
            }
            mbar_arrive1(sb + B_BAR + (BB_SF + wg) * 8);
        }
        PROF(wg && (threadIdx.x & 31) == 0, 3600 + ti * 4 + 3);
    }
}

__device__ __forceinline__ void stage_release(uint32_t sb, int w, int st) {
    if (!(w & 2)) mbar_arrive1_cluster(mapa(sb + B_BAR + (BB_EMPTY + st) * 8, w & 1));
}
template <bool ACC>
__device__ __forceinline__ void gemm_run(float* acc, uint32_t sb, int w, int h0, int h1, uint32_t& r0, uint32_t& r1, int& st, uint32_t& ph) {
    const uint64_t da0 = mkdesc(sb + (w >> 2) * 4096, 128, 512, 0), db0 = mkdesc(sb + 8192, 4096, 1024, 1);
    const uint32_t rel0 = mapa(sb + B_BAR + BB_EMPTY * 8, w & 1);
#pragma unroll 1
    for (int h = h0; h < h1; h++) {
        const uint64_t da = da0 + st * (STG_B >> 4), db = db0 + st * (STG_B >> 4);
        mbar_wait(sb + B_BAR + (BB_FULL + st) * 8, ph);
        if (ACC) wg_wait<1>();
        wg_fence();
        wgmma256<ACC>(acc, da, db);
        wgmma256<true>(acc, da + 16, db + 128);
        wg_commit();
        if (ACC) mbar_arrive1_cluster((w == 2 && h == LAGH - 1) ? sb + B_BAR + BB_GO * 8 : r0);
        r0 = r1;
        if (!(w & 2)) r1 = rel0 + st * 8;
        if (++st == NSTG) { st = 0; ph ^= 1; }
    }
}

__device__ __forceinline__ uint4* qkv_dst(int layer, int ch, int w, int blk) {
    return g_qkv[layer] + (size_t)((ch * 4 + (w >> 1)) * 32 + ((blk & 63) >> 1)) * 1536 + (blk >> 6) * 512 + (w & 1) * 256;
}
__device__ __forceinline__ uint4* op_dst(int layer, int ch, int slot, int w, uint32_t rank) {
    return g_pp[layer] + (size_t)(ch * MAXSPLIT + slot) * 8192 + (w * 32 + rank * 16) * 32;
}
__device__ __forceinline__ uint32_t ln2(uint32_t x, uint32_t m, uint32_t rh, uint32_t rl) {
    uint32_t d; asm volatile("{.reg .b32 t,u; sub.rn.bf16x2 t,%1,%2; mul.rn.bf16x2 u,t,%4; fma.rn.bf16x2 %0,t,%3,u;}" : "=r"(d) : "r"(x), "r"(m), "r"(rh), "r"(rl)); return d;
}
__device__ __forceinline__ void qkv_task(uint32_t sb, int w, int layer, int nu, int ng, int& nd, uint32_t& ph) {
    static_assert(NSTG == 8, "ring");
    const int lane = threadIdx.x & 31;
    const uint64_t db0 = mkdesc(sb, 4096, 1024, 1);
    const uint32_t rel = (w & 2) ? sb + B_BAR + BB_IDLE * 8 : mapa(sb + B_BAR + BB_EMPTY * 8, w & 1), full = sb + B_BAR + BB_FULL * 8;
    const uint32_t la = sb + w * 1024 + ((lane >> 3) & 1) * 512 + (lane >> 4) * 128 + (lane & 7) * 16, lo = sb + B_OUT + w * 4096 + (lane ^ (lane >> 3)) * 16;
    uint32_t m0, m1, h0, h1, l0, l1;
    uint4 A[32];
    {
        mbar_wait(full, ph);
        mbar_wait(full + 8, ph);
        const uint32_t sa = sb + (lane >> 4) * STG_B + 16384 + (w * 16 + (lane & 15)) * 8;
        uint2 v = lds64(sa);
        float sm = __uint_as_float(v.x), M2 = __uint_as_float(v.y);
        if (layer) {
            float e[8];
            e[0] = sm;
#pragma unroll
            for (int i = 1; i < 8; i++) { v = lds64(sa + i * 1024); e[i] = __uint_as_float(v.x); sm += e[i]; M2 += __uint_as_float(v.y); }
            sm += __shfl_xor_sync(0xffffffffu, sm, 16);
#pragma unroll
            for (int i = 0; i < 8; i++) { const float d = e[i] * (1.f / 32.f) - sm * (1.f / 512.f); M2 += 32.f * d * d; }
            M2 += __shfl_xor_sync(0xffffffffu, M2, 16);
        } else M2 = fmaxf(M2 - sm * sm * (1.f / 512.f), 0.f);
        A[0] = ldsm4(la); A[1] = ldsm4(la + 256);
        const float2 o = ln_finish(sm * (1.f / 512.f), M2 * (1.f / 512.f));
        const float r = rcp(o.y), rh = rbf(r);
        const uint32_t mm = pack2(o.x, o.x), hl = pack2(r - rh, rh);
        m0 = __shfl_sync(0xffffffffu, mm, lane >> 2); m1 = __shfl_sync(0xffffffffu, mm, (lane >> 2) + 8);
        l0 = __shfl_sync(0xffffffffu, hl, lane >> 2); l1 = __shfl_sync(0xffffffffu, hl, (lane >> 2) + 8);
        h0 = __byte_perm(l0, 0, 0x3232); h1 = __byte_perm(l1, 0, 0x3232); l0 = __byte_perm(l0, 0, 0x1010); l1 = __byte_perm(l1, 0, 0x1010);
    }
    float acc[64];
#define QNRM(i) A[i] = make_uint4(ln2(A[i].x, m0, h0, l0), ln2(A[i].y, m1, h1, l1), ln2(A[i].z, m0, h0, l0), ln2(A[i].w, m1, h1, l1))
    if (w >> 2) mbar_wait(sb + B_BAR + BB_GO * 8, ~ng & 1);
#pragma unroll
    for (int h = 0; h < 16; h++) {
        const uint64_t db = db0 + ((h & 7) * (STG_B >> 4) + 512);
        if (h < 15) { A[(2 * h + 2) & 31] = ldsm4(la + ((h + 1) & 7) * STG_B); A[(2 * h + 3) & 31] = ldsm4(la + ((h + 1) & 7) * STG_B + 256); }
        const bool ok = h >= 14 || mbar_test(full + ((h + 2) & 7) * 8, ph ^ ((h + 2) >> 3));
        QNRM(2 * h); QNRM(2 * h + 1);
        if (h) wg_wait<1>();
        wg_fence();
        if (h) wgmma128r<true>(acc, A[2 * h], db); else wgmma128r<false>(acc, A[0], db);
        wgmma128r<true>(acc, A[2 * h + 1], db + 128);
        wg_commit();
        if (h >= 2) mbar_arrive1_cluster(rel + ((h - 2) & 7) * 8);
        if (h == LAGQ - 1 && w == 2) mbar_arrive1(sb + B_BAR + BB_GO * 8);
        if (!ok) mbar_wait(full + ((h + 2) & 7) * 8, ph ^ ((h + 2) >> 3));
    }
#pragma unroll 1
    for (int u = 1;; u++) {
        mbar_wait(sb + B_BAR + (BB_SF + (w >> 2)) * 8, (nd & 1) ^ 1);
        if (u < nu) mbar_wait(full, ph);
        wg_wait<1>();
        mbar_arrive1_cluster(rel + 48);
        wg_wait<0>();
        mbar_arrive1_cluster(rel + 56);
        uint4 o[8];
#pragma unroll
        for (int n = 0; n < 8; n++) {
            const float* a = acc + (n >> 1) * 16 + (n & 1) * 2;
            o[n] = make_uint4(pack2(a[0], a[1]), pack2(a[4], a[5]), pack2(a[8], a[9]), pack2(a[12], a[13]));
            sts128(lo + n * 512, o[n].x, o[n].y, o[n].z, o[n].w);
        }
        __syncwarp();
        mbar_arrive1(sb + B_BAR + (BB_DONE + (w >> 2)) * 8);
        nd++;
        if (u == nu) break;
#pragma unroll
        for (int h = 0; h < 8; h++) {
            const uint64_t db = db0 + h * (STG_B >> 4);
            if (h) { mbar_wait(full + h * 8, ph); wg_wait<1>(); }
            wg_fence();
            if (h) wgmma128r<true>(acc, A[4 * h], db); else wgmma128r<false>(acc, A[0], db);
            wgmma128r<true>(acc, A[4 * h + 1], db + 128);
            wgmma128r<true>(acc, A[4 * h + 2], db + 512);
            wgmma128r<true>(acc, A[4 * h + 3], db + 640);
            wg_commit();
            if (h >= 2) mbar_arrive1_cluster(rel + (h - 2) * 8);
        }
        ph ^= 1;
    }
}

template <int NB>
__device__ __forceinline__ void load_resid(uint32_t* r, int layer, int ch, int w, int cb) {
    const uint32_t* rp = (const uint32_t*)(g_xA[layer] + (ch * 8 + (cb >> 2)) * 1024 + w * 128 + (cb & 3) * 16) + (threadIdx.x & 31);
#pragma unroll
    for (int i = 0; i < NB * 4; i++) r[i] = __ldcg(rp + (i >> 1) * 32 + (i & 1) * 256);
}
template <int NS>
__device__ __forceinline__ void part_load(uint4* v, int layer, int ch, int w, int cb, int ns) {
    const uint4* src = g_pp[layer] + (size_t)ch * MAXSPLIT * 8192 + (w * 32 + cb) * 32 + (threadIdx.x & 31);
#pragma unroll
    for (int i = 0; i < 2 * NS; i++) {
        asm volatile("{.reg .pred p; .reg .b128 t; setp.gt.s32 p,%6,0; mov.b128 t,{0,0,0,0}; @p ld.relaxed.gpu.global.L2::cache_hint.b128 t,[%4],%5; mov.b128 {%0,%1,%2,%3},t;}"
                     : "=r"(v[i].x), "=r"(v[i].y), "=r"(v[i].z), "=r"(v[i].w) : "l"(src + (i / NS) * 32 + (i % NS) * 8192), "l"(POL_LAST), "r"(ns - i % NS) : "memory");
    }
}
template <int NS>
__device__ __forceinline__ void part_sum(float* x, const uint4* v, const uint32_t* r) {
    const int dg = ((threadIdx.x & 31) >> 2) - 2 * (threadIdx.x & 3);
    const uint32_t idm = dg == 0 ? 0x00003f80u : dg == 1 ? 0x3f800000u : 0u;
#pragma unroll
    for (int b = 0; b < 2; b++) {
        float* y = x + b * 8;
#pragma unroll
        for (int i = 0; i < 8; i++) y[i] = 0;
#pragma unroll
        for (int s = 0; s < NS; s++) { mma8(y, v[b * NS + s].x, v[b * NS + s].y, idm); mma8(y + 4, v[b * NS + s].z, v[b * NS + s].w, idm); }
#pragma unroll
        for (int i = 0; i < 4; i++) { y[2 * i] = rbf(rbf(y[2 * i]) + blo(r[b * 4 + i])); y[2 * i + 1] = rbf(rbf(y[2 * i + 1]) + bhi(r[b * 4 + i])); }
    }
}

__device__ __forceinline__ float4 row_stats32(const float* x) {
    float a = (x[0] + x[1]) + (x[4] + x[5]) + (x[8] + x[9]) + (x[12] + x[13]);
    float b = (x[2] + x[3]) + (x[6] + x[7]) + (x[10] + x[11]) + (x[14] + x[15]);
    a += __shfl_xor_sync(0xffffffffu, a, 1); b += __shfl_xor_sync(0xffffffffu, b, 1);
    a += __shfl_xor_sync(0xffffffffu, a, 2); b += __shfl_xor_sync(0xffffffffu, b, 2);
    const float ma = a * (1.f / 32.f), mb = b * (1.f / 32.f);
    float qa = 0, qb = 0;
#pragma unroll
    for (int i = 0; i < 4; i++) {
        float d0 = x[4 * i] - ma, d1 = x[4 * i + 1] - ma, d2 = x[4 * i + 2] - mb, d3 = x[4 * i + 3] - mb;
        qa += d0 * d0 + d1 * d1; qb += d2 * d2 + d3 * d3;
    }
    qa += __shfl_xor_sync(0xffffffffu, qa, 1); qb += __shfl_xor_sync(0xffffffffu, qb, 1);
    qa += __shfl_xor_sync(0xffffffffu, qa, 2); qb += __shfl_xor_sync(0xffffffffu, qb, 2);
    return make_float4(a, qa, b, qb);
}

__device__ __forceinline__ void conv_stage(float* Y, uint32_t pbase, uint32_t ubase) {
    const int lane = threadIdx.x & 31, w = threadIdx.x >> 5, g = lane >> 2, c = lane & 3;
#pragma unroll
    for (int cp = 0; cp < 2; cp++) {
        const int chl = w * 4 + cp * 2 + (lane >> 4);
        const uint4 b = ldsm4(ubase + chl * 256 + ((lane >> 3) & 1) * 128 + (((lane & 7) ^ (chl & 7)) << 4));
#pragma unroll
        for (int h = 0; h < 2; h++) {
            const uint32_t pa = pbase + ((w * 4 + cp * 2 + h) * PW + 16 + g - 2 * c) * 4;
            uint32_t lo = lds32(pa - 32);
#pragma unroll
            for (int d = 0; d < 8; d++) {
                const uint32_t a0 = lds32(pa + d * 64), a1 = lds32(pa + d * 64 + 32);
                mma16(Y + ((cp * 2 + h) * 8 + d) * 4, a0, a1, lo, a0, h ? b.z : b.x, h ? b.w : b.y);
                lo = a1;
            }
        }
    }
}

__device__ __forceinline__ void conv_combine(const float* y8, float* cur, float* nxt) {
    const int lane = threadIdx.x & 31, c = lane & 3;
    cur[0] = y8[0]; cur[1] = y8[1] + y8[4]; cur[2] = y8[2]; cur[3] = y8[3] + y8[6];
    nxt[0] = y8[29]; nxt[1] = 0.f; nxt[2] = y8[31]; nxt[3] = 0.f;
#pragma unroll
    for (int e = 1; e < 4; e++) {
        const int src = (lane & ~3) | ((c - e) & 3);
        const float v0 = __shfl_sync(0xffffffffu, y8[8 * e] + y8[8 * e - 3], src), v1 = __shfl_sync(0xffffffffu, y8[8 * e + 1] + y8[8 * e + 4], src);
        const float v2 = __shfl_sync(0xffffffffu, y8[8 * e + 2] + y8[8 * e - 1], src), v3 = __shfl_sync(0xffffffffu, y8[8 * e + 3] + y8[8 * e + 6], src);
        if (c >= e) { cur[0] += v0; cur[1] += v1; cur[2] += v2; cur[3] += v3; }
        else { nxt[0] += v0; nxt[1] += v1; nxt[2] += v2; nxt[3] += v3; }
    }
}

__device__ __forceinline__ void hist_task(float* Y, uint32_t sb, int w, int ch, int q, int& st, uint32_t& ph, int nd) {
    const int lane = threadIdx.x & 31, chl = w * 2 + (lane >> 4);
    const uint32_t ua = sb + 12288 + chl * 256 + ((lane >> 3) & 1) * 128 + (((lane & 7) ^ (chl & 7)) << 4);
    const uint32_t pa = sb + (w * 2 * PW + 16 + (lane >> 2) - 2 * (lane & 3)) * 4;
#pragma unroll
    for (int i = 0; i < 128; i++) Y[i] = 0;
    uint4 b1 = make_uint4(0, 0, 0, 0);
#pragma unroll 1
    for (int j = ch + 1; j >= 2; j--) {
        const uint4 b0 = b1;
        mbar_wait(sb + B_BAR + (BB_FULL + st) * 8, ph);
        b1 = ldsm4(ua + st * STG_B);
        if (j == 2) b1 = make_uint4(0, 0, 0, 0);
#pragma unroll
        for (int h = 0; h < 2; h++) {
            const uint32_t o = pa + st * STG_B + h * PW * 4;
            uint32_t lo = lds32(o - 32);
#pragma unroll
            for (int d = 0; d < 8; d++) {
                const uint32_t a0 = lds32(o + d * 64), a1 = lds32(o + d * 64 + 32);
                mma16(Y + (h * 16 + d) * 4, a0, a1, lo, a0, h ? b0.z : b0.x, h ? b0.w : b0.y);
                mma16(Y + (h * 16 + 8 + d) * 4, a0, a1, lo, a0, h ? b1.z : b1.x, h ? b1.w : b1.y);
                lo = a1;
            }
        }
        bar_sync(NB_WG + (w >> 2), 128);
        stage_release(sb, w, st);
        if (++st == NSTG) { st = 0; ph ^= 1; }
    }
    mbar_wait(sb + B_BAR + (BB_SF + (w >> 2)) * 8, (nd & 1) ^ 1);
#pragma unroll
    for (int h = 0; h < 2; h++) {
        const int o = ((ch * 16 + (q >> 1)) * 4 + (w & 1) * 2 + h) * 256 + ((q & 1) * 4 + (w >> 1)) * 32 + lane;
        float c0[4], n0[4], c1[4], n1[4];
        conv_combine(Y + h * 64, c0, n0); conv_combine(Y + h * 64 + 32, c1, n1);
        g_carry[0][o] = make_float4(c0[0], c0[1], c0[2], c0[3]);
        g_carry[0][o + 16384] = make_float4(c1[0] + n0[0], c1[1] + n0[1], c1[2] + n0[2], c1[3] + n0[3]);
        g_carry[1][o + 32768] = make_float4(n1[0], n1[1], n1[2], n1[3]);
    }
}

__device__ __forceinline__ void conv_task(const Params& p, float* Y, uint32_t sb, int w, int ch, int q, bool dry, int& st, uint32_t& ph, int nd) {
    const int tid = threadIdx.x, lane = tid & 31, g = lane >> 2, c = lane & 3;
    uint32_t dk[4];
    const uint32_t sg = (~ch & 2) << 30;
    int sr = st;
    float x[16];
    uint32_t rs[8];
    load_resid<2>(rs, 0, ch, w, 2 * q);
    PROF(tid == 128, 2048 + ch * 8);
#pragma unroll
    for (int i = 0; i < 128; i++) Y[i] = 0;
#pragma unroll 1
    for (int j = min(ch, 1 + (ch & 1)); j >= 1; j--) {
        mbar_wait(sb + B_BAR + (BB_FULL + st) * 8, ph);
        conv_stage(Y, sb + st * STG_B, sb + B_UT + ((ch - j) & 1) * 8192);
        if (++st == NSTG) { st = 0; ph ^= 1; }
    }
    PROF(tid == 128, 2048 + ch * 8 + 7);
    {
        uint4 v[2 * OPS1];
        wait_cnt_warp(cnt_ptr(C_OP0 + (q >> 3) * 2 + (w >> 2), ch), dry ? 0 : OPS1);
        part_load<OPS1>(v, 0, ch, w, 2 * q, OPS1);
        part_sum<OPS1>(x, v, rs);
        const float4 s = row_stats32(x);
        float2* dst = g_st2 + ((ch & 1) * 16 + q) * 128 + w * 16 + g + c * 8;
        asm volatile("{.reg .pred p; setp.ne.u32 p,%2,0; @p st.relaxed.gpu.global.b64 [%0],%1;}" ::"l"(dst),
                     "l"(((uint64_t)((__float_as_uint(c ? s.w : s.y) & 0x7fffffffu) | sg) << 32) | __float_as_uint(c ? s.z : s.x)), "r"((uint32_t)(c < 2 && !dry)) : "memory");
        PROF(tid == 128, 2048 + ch * 8 + 1);
    }
#pragma unroll
    for (int i = 0; i < 4; i++) asm volatile("ld.global.nc.u32 %0,[%1];" : "=r"(dk[i]) : "l"(p.Dskip + q * 32 + i * 8 + 2 * c));
#pragma unroll 1
    for (int i = 0; i < min(ch, (ch & 1) ? 2 : 3); i++) {
        if (i) mbar_wait(sb + B_BAR + (BB_FULL + st) * 8, ph);
        const uint32_t ca = sb + (i ? st * STG_B : B_SP) + tid * 16;
#pragma unroll
        for (int k = 0; k < 4; k++) {
            const uint4 cr = lds128(ca + k * 4096);
            Y[k * 32] += __uint_as_float(cr.x); Y[k * 32 + 1] += __uint_as_float(cr.y); Y[k * 32 + 2] += __uint_as_float(cr.z); Y[k * 32 + 3] += __uint_as_float(cr.w);
        }
        if (i && ++st == NSTG) { st = 0; ph ^= 1; }
    }
    bar_sync(NB_C, 256);
#pragma unroll 1
    for (; sr != st; sr = (sr + 1) & (NSTG - 1)) stage_release(sb, w, sr);
    const uint32_t ut = sb + B_UT + (ch & 1) * 8192;
    mbar_wait(sb + B_BAR + (BB_SF + (w >> 2)) * 8, (nd & 1) ^ 1);
    mbar_wait(sb + B_BAR + (BB_SF + 1 - (w >> 2)) * 8, (nd & 1) ^ 1);
    float2 ln0, ln1;
    {
        const float2* src = g_st2 + ((ch & 1) * 16 + (lane >> 4) * 8) * 128 + w * 16 + (lane & 15);
        uint64_t v[8];
        int n = 0;
#pragma unroll
        for (int i = 0; i < 8; i++) v[i] = (uint64_t)~sg << 32;
        while (true) {
            bool bad = false;
#pragma unroll
            for (int i = 0; i < 8; i++) asm volatile("{.reg .pred p; setp.lt.s32 p,%2,0; @p ld.relaxed.gpu.global.b64 %0,[%1];}" : "+l"(v[i]) : "l"(src + i * 128), "r"((uint32_t)(v[i] >> 32) ^ sg) : "memory");
#pragma unroll
            for (int i = 0; i < 8; i++) bad = bad || (int)((uint32_t)(v[i] >> 32) ^ sg) < 0;
            if (!__any_sync(0xffffffffu, bad && !dry)) break;
            if (++n > 2000000) __trap();
        }
        float sm = 0;
#pragma unroll
        for (int i = 0; i < 8; i++) sm += __uint_as_float((uint32_t)v[i]);
        sm += __shfl_xor_sync(0xffffffffu, sm, 16);
        const float mean = sm * (1.f / 512.f);
        float M2 = 0;
#pragma unroll
        for (int i = 0; i < 8; i++) { const float d = __uint_as_float((uint32_t)v[i]) * (1.f / 32.f) - mean; M2 += fabsf(__uint_as_float((uint32_t)(v[i] >> 32))) + 32.f * d * d; }
        M2 += __shfl_xor_sync(0xffffffffu, M2, 16);
        const float2 o = ln_finish(mean, M2 * (1.f / 512.f));
        ln0.x = __shfl_sync(0xffffffffu, o.x, g); ln0.y = __shfl_sync(0xffffffffu, o.y, g);
        ln1.x = __shfl_sync(0xffffffffu, o.x, g + 8); ln1.y = __shfl_sync(0xffffffffu, o.y, g + 8);
    }
    PROF(tid == 128, 2048 + ch * 8 + 2);
    uint32_t u[8];
#pragma unroll
    for (int i = 0; i < 8; i++) {
        const float2 l = (i & 1) ? ln1 : ln0;
        u[i] = pack2(__fdividef(rbf(x[2 * i] - l.x), l.y), __fdividef(rbf(x[2 * i + 1] - l.x), l.y));
        const int chl = (i >> 1) * 8 + g;
        sts32(ut + chl * 256 + (i & 1) * 128 + ((w ^ g) << 4) + c * 4, movm(u[i]));
    }
    bar_sync(NB_C, 256);
    mbar_wait(sb + B_BAR + (BB_FULL + st) * 8, ph);
    PROF(tid == 128, 2048 + ch * 8 + 3);
    conv_stage(Y, sb + st * STG_B, ut);
    uint32_t yp[4][2];
    float nxt[4][4];
    {
        float y[4][4];
#pragma unroll
        for (int k = 0; k < 4; k++) conv_combine(Y + k * 32, y[k], nxt[k]);
#pragma unroll
        for (int i = 0; i < 4; i++) { yp[i][0] = pack2(y[0][i], y[1][i]); yp[i][1] = pack2(y[2][i], y[3][i]); }
    }
#pragma unroll
    for (int i = 0; i < 4; i++) sts64(sb + B_YT + (16 * (2 * c + (i & 1)) + g + (i >> 1) * 8) * 80 + w * 8, yp[i][0], yp[i][1]);
    bar_sync(NB_C, 256);
    stage_release(sb, w, st);
    if (++st == NSTG) { st = 0; ph ^= 1; }
    PROF(tid == 128, 2048 + ch * 8 + 4);
    uint32_t xo[8];
    uint32_t* dA = (uint32_t*)(g_xA[1] + (ch * 8 + (q >> 1)) * 1024 + (w * 2) * 64 + (q & 1) * 32) + lane;
#pragma unroll
    for (int i = 0; i < 8; i++) {
        const int col = (i >> 1) * 8 + 2 * c;
        const uint32_t yv = lds32(sb + B_YT + (w * 16 + g + (i & 1) * 8) * 80 + col * 2);
        const uint32_t dv = dk[i >> 1];
        x[2 * i] = rbf(x[2 * i] + rbf(blo(yv) + rbf(blo(u[i]) * blo(dv))));
        x[2 * i + 1] = rbf(x[2 * i + 1] + rbf(bhi(yv) + rbf(bhi(u[i]) * bhi(dv))));
        xo[i] = pack2(x[2 * i], x[2 * i + 1]);
        dA[(i >> 1) * 32 + (i & 1) * 256] = xo[i];
    }
    {
        const float4 s = row_stats32(x);
        float2* dst = g_st[1] + (ch * 16 + q) * 128 + w * 16 + g;
        if (c == 0) dst[0] = make_float2(s.x, s.y);
        if (c == 1) dst[8] = make_float2(s.z, s.w);
        __syncwarp();
    }
    PROF(tid == 128, 2048 + ch * 8 + 5);
    mbar_arrive1(sb + B_BAR + (BB_DONE + (w >> 2)) * 8);
    bar_sync(NB_C, 256);
#pragma unroll
    for (int k = 0; k < 4; k++) sts128(sb + B_SP + k * 4096 + tid * 16, __float_as_uint(nxt[k][0]), __float_as_uint(nxt[k][1]), __float_as_uint(nxt[k][2]), __float_as_uint(nxt[k][3]));
    PROF(tid == 128, 2048 + ch * 8 + 6);
}

__device__ __forceinline__ void out_store(const Params& p, const float* x, int ch, int cb) {
    const int lane = threadIdx.x & 31, w = threadIdx.x >> 5, g = lane >> 2, c = lane & 3;
#pragma unroll
    for (int h = 0; h < 2; h++) {
        const float* y = x + h * 2;
        uint32_t v0 = pack2(y[0], y[1]), v1 = pack2(y[4], y[5]), v2 = pack2(y[8], y[9]), v3 = pack2(y[12], y[13]);
        uint32_t t0 = (c & 1) ? v0 : v1, t1 = (c & 1) ? v2 : v3;
        t0 = __shfl_xor_sync(0xffffffffu, t0, 1); t1 = __shfl_xor_sync(0xffffffffu, t1, 1);
        if (c & 1) { v0 = t0; v2 = t1; } else { v1 = t0; v3 = t1; }
        t0 = (c & 2) ? v0 : v2; t1 = (c & 2) ? v1 : v3;
        t0 = __shfl_xor_sync(0xffffffffu, t0, 2); t1 = __shfl_xor_sync(0xffffffffu, t1, 2);
        if (c & 2) { v0 = t0; v1 = t1; } else { v2 = t0; v3 = t1; }
        stg128((uint4*)(p.out + (size_t)(ch * 128 + w * 16 + g + h * 8) * 512 + cb * 16 + c * 8), make_uint4(v0, v1, v2, v3), POL_LATE);
    }
}
__device__ __forceinline__ void fin_task(const Params& p, int ch, int cb0, int ncb, int ns, bool dry) {
    const int w = threadIdx.x >> 5;
    uint32_t rs[8];
    wait_cnt_warp(cnt_ptr(C_CV, ch), dry ? 0 : 32);
    load_resid<2>(rs, 1, ch, w, cb0);
    wait_cnt_warp(cnt_ptr(C_OP1, ch), dry ? 0 : 256);
    for (int cb = cb0; cb < cb0 + ncb; cb += 2) {
        float x[16];
        if (cb != cb0) load_resid<2>(rs, 1, ch, w, cb);
        uint4 v[32];
        part_load<16>(v, 1, ch, w, cb, ns);
        part_sum<16>(x, v, rs);
        out_store(p, x, ch, cb);
    }
}

__device__ __forceinline__ void bulk_consumer(const Params& p, uint32_t sb, int cl, uint32_t rank, int w) {
    int st = 0; uint32_t ph = 0; int nd = 0, ng = 0;
    for (int ti = 0; ti < MAXT; ti++) {
        const Task t = task_of(p.task[cl][ti], rank);
        const int type = t.type, layer = t.layer, ch = t.ch;
        if (type == T_END) break;
        bool staged = type != T_FIN;
        PROF(threadIdx.x == 0, 3600 + ti * 4);
        if (type <= T_OP) {
            CPROF(0);
            if ((w >> 2) && type == T_OP) mbar_wait(sb + B_BAR + BB_GO * 8, ng & 1);
            ng++;
            CPROF(1);
        }
        if (type == T_QKV) {
            staged = false;
            #pragma unroll 1
            while (st) {
                if (!(w & 3)) { mbar_wait(sb + B_BAR + (BB_FULL + st) * 8, ph); stage_release(sb, 0, st); stage_release(sb, 1, st); }
                if (++st == NSTG) { st = 0; ph ^= 1; }
            }
            qkv_task(sb, w, layer, t.b, ng, nd, ph);
            PROF(threadIdx.x == 128, 3600 + ti * 4 + 1);
        } else if (type == T_OP) {
            const int lane = threadIdx.x & 31;
            float acc[128];
            uint32_t r0 = sb + B_BAR + BB_IDLE * 8, r1 = r0;
            gemm_run<false>(acc, sb, w, 0, 1, r0, r1, st, ph);
            gemm_run<true>(acc, sb, w, 1, 2 * t.b, r0, r1, st, ph);
            mbar_wait(sb + B_BAR + (BB_SF + (w >> 2)) * 8, (nd & 1) ^ 1);
            wg_wait<1>();
            mbar_arrive1_cluster(r0);
            wg_wait<0>();
            mbar_arrive1_cluster(r1);
            PROF(threadIdx.x == 128, 3600 + ti * 4 + 1);
            if (t.c & 32) {
                staged = false;
#pragma unroll
                for (int j = 0; j < 16; j += 4) {
                    uint32_t rs[16];
                    load_resid<4>(rs, 1, ch, w, (t.blk & 4) * 4 + j);
#pragma unroll
                    for (int i = 0; i < 16; i++) { float* y = acc + j * 8 + 2 * i; y[0] = rbf(y[0]) + blo(rs[i]); y[1] = rbf(y[1]) + bhi(rs[i]); }
                    out_store(p, acc + j * 8, ch, (t.blk & 4) * 4 + j); out_store(p, acc + j * 8 + 16, ch, (t.blk & 4) * 4 + j + 2);
                }
            } else if (!layer) {
                const int s2 = st + (w >> 1);
                const uint32_t o = sb + (s2 & (NSTG - 1)) * STG_B + (w & 1) * 8192 + lane * 16;
                mbar_wait(sb + B_BAR + (BB_FULL + (s2 & (NSTG - 1))) * 8, ph ^ (s2 >= NSTG));
#pragma unroll
                for (int j = 0; j < 16; j++)
                    sts128(o + j * 512, pack2(acc[j * 8], acc[j * 8 + 1]), pack2(acc[j * 8 + 2], acc[j * 8 + 3]), pack2(acc[j * 8 + 4], acc[j * 8 + 5]), pack2(acc[j * 8 + 6], acc[j * 8 + 7]));
                sts32(sb + B_ST + (w >> 2) * 4, st);
                st += 4;
                if (st >= NSTG) { st -= NSTG; ph ^= 1; }
            } else {
                uint4* dst = op_dst(layer, ch, t.c & 15, w, (t.blk >> 2) & 1) + lane;
#pragma unroll
                for (int n = 0; n < 16; n++) {
                    const int j = (n >> 1) + (n & 1) * 8;
                    const uint4 v = make_uint4(pack2(acc[j * 8], acc[j * 8 + 1]), pack2(acc[j * 8 + 2], acc[j * 8 + 3]), pack2(acc[j * 8 + 4], acc[j * 8 + 5]), pack2(acc[j * 8 + 6], acc[j * 8 + 7]));
                    if (j < 16 - NSB) stg128(dst + j * 32, v, out_pol(T_OP, layer, ch)); else sts128(sb + B_OUT + (w * NSB + j - (16 - NSB)) * 512 + lane * 16, v.x, v.y, v.z, v.w);
                }
            }
        } else if (type == T_CV) {
            float acc[128];
            if (layer) hist_task(acc, sb, w, ch, t.a + rank, st, ph, nd);
            else { conv_task(p, acc, sb, w, ch, t.a + rank, t.dry, st, ph, nd); staged = false; nd++; }
        } else {
            fin_task(p, ch, t.a + rank * t.c, t.c, t.b, t.dry);
        }
        if (staged) {
            __syncwarp();
            mbar_arrive1(sb + B_BAR + (BB_DONE + (w >> 2)) * 8);
            nd++;
        }
        CPROF(6);
        PROF(threadIdx.x == 128, 3600 + ti * 4 + 2);
        __syncwarp();
    }
}

constexpr int P_Y = 131072  , P_PRM = P_Y  , P_K6 = P_PRM + 8192  ,
              P_P = P_Y + 40960  , P_U = P_P + 33280  , P_END = P_U + 17408, P_X = 98304  ;
static_assert(P_END <= B_BAR && P_END <= R_BAR, "prologue scratch");
#define KGUN 2
constexpr int KGU = KGUN;
__device__ __forceinline__ void csq(float& r, float& i) { const float t = r * i; r = fmaf(r, r, -(i * i)); i = t + t; }
__device__ __forceinline__ void cpow(float ar, float ph, float p, float& r, float& i) {
    const float e = ex2(ar * p);
    const float u = ph * p, n = fabsf(u) < 4194304.f ? (u + 12582912.f) - 12582912.f : u;
    const float t = (u - n) * 6.283185307179586f;
    r = e * __cosf(t); i = e * __sinf(t);
}
__device__ __forceinline__ void mma_tf32(float* c, float a0, float a1, float a2, float a3, float b0, float b1) {
    asm volatile("mma.sync.aligned.m16n8k8.row.col.f32.tf32.tf32.f32 {%0,%1,%2,%3},{%4,%5,%6,%7},{%8,%9},{%0,%1,%2,%3};"
                 : "+f"(c[0]), "+f"(c[1]), "+f"(c[2]), "+f"(c[3])
                 : "r"(__float_as_uint(a0)), "r"(__float_as_uint(a1)), "r"(__float_as_uint(a2)), "r"(__float_as_uint(a3)), "r"(__float_as_uint(b0)), "r"(__float_as_uint(b1)));
}

struct ProRegs { uint32_t v[2][4], ldt[2]; };
__device__ __forceinline__ void prologue_load(const ProArgs& a, int b, ProRegs& pr) {
    const int w = threadIdx.x >> 5;
#pragma unroll
    for (int i = 0; i < 2; i++) {
        const int gi = b * 512 + (w & 3) * 128 + ((w >> 2) & 1) * 64 + i * 32 + (threadIdx.x & 31);
        pr.ldt[i] = __ldg((const uint16_t*)a.ldt + b * 4 + (w & 3));
        pr.v[i][0] = __ldg((const uint16_t*)a.lAr + gi); pr.v[i][1] = __ldg((const uint16_t*)a.Ai + gi);
        pr.v[i][2] = __ldg((const uint16_t*)a.Cr + gi); pr.v[i][3] = __ldg((const uint16_t*)a.Ci + gi);
    }
}
__device__ __forceinline__ void prologue(const ProArgs& a, uint32_t sb, int b, int w, const ProRegs& pr) {
    const int tid = threadIdx.x, lane = tid & 31, g = lane >> 2, c = lane & 3;
    const int d0 = b * 4;
    if (w >= 8) {
        const int t2 = tid - 256;
        if (w < 10) {
            const int row = b * 16 + (w - 8) * 8 + g;
            const float2 r = row_stats512((const uint4*)(a.x + (size_t)row * 512) + c, 8, 4);
            const float2 l = ln_finish(r.x * (1.f / 512.f), fmaxf(r.y - r.x * r.x * (1.f / 512.f), 0.f) * (1.f / 512.f));
            if (c == (g >> 1)) asm volatile("st.relaxed.gpu.global.u32 [%0],%1;" ::"l"(g_ln0 + row), "r"(pack2(l.x, l.y)) : "memory");
        }
        PROF(t2 == 0, 3516);
        const int gi = b * 128 + t2;
        if (t2 < 32) acc_init(a.mem0, b * 32 + t2);
        if (t2 >= 112) ((uint4*)g_st2)[b * 16 + t2 - 112] = make_uint4(0, 0, 0, 0);
        if (gi < 13 * 64) g_cnt[gi] = 0;
        bar_sync(6, 384);
        if (gi < 256) g_st[0][(gi >> 7) * 2048 + (lds32(sb + S_TAG) ^ 1) * 128 + (gi & 127)] = make_float2(0.f, 0.f);
        asm volatile("{.reg .pred p; elect.sync _|p,0xffffffff; @p cp.async.bulk.prefetch.L2.global [%0],32768;}"
                     ::"l"((w == 8 ? a.Wq : w == 9 ? a.Wk : w == 10 ? a.Wv : a.Wo) + (size_t)b * 16384) : "memory");
        mbar_wait(sb + S_XBAR, 0);
#pragma unroll 1
        for (int h = 0; h < 2; h++) {
            uint32_t l[8];
            int n = 0;
            while (true) {
                bool ok = true;
#pragma unroll
                for (int i = 0; i < 8; i++) asm volatile("ld.relaxed.gpu.global.u32 %0,[%1];" : "=r"(l[i]) : "l"(g_ln0 + h * 1024 + i * 128 + t2) : "memory");
#pragma unroll
                for (int i = 0; i < 8; i++) ok = ok && l[i];
                if (__all_sync(0xffffffffu, ok)) break;
                if (++n > 2000000) __trap();
            }
#pragma unroll
            for (int i = 0; i < 8; i++) {
                const int t = h * 1024 + i * 128 + t2;
                const uint2 x = lds64(sb + P_X + t * 16 + (b & 1) * 8);
                const float m = blo(l[i]), rs = rcp(bhi(l[i]));
                const uint32_t u0 = pack2(rbf(blo(x.x) - m) * rs, rbf(bhi(x.x) - m) * rs), u1 = pack2(rbf(blo(x.y) - m) * rs, rbf(bhi(x.y) - m) * rs);
                sts128(sb + P_X + t * 16, x.x, x.y, u0, u1);
                const uint32_t o = sb + P_U + ((t >> 3) & 1) * 2176 + ((t >> 4) + 8) * 16 + (t & 7) * 2;
                asm volatile("st.shared.u16 [%0],%1;" ::"r"(o), "h"((uint16_t)u0) : "memory");
                asm volatile("st.shared.u16 [%0],%1;" ::"r"(o + 4352), "h"((uint16_t)(u0 >> 16)) : "memory");
                asm volatile("st.shared.u16 [%0],%1;" ::"r"(o + 8704), "h"((uint16_t)u1) : "memory");
                asm volatile("st.shared.u16 [%0],%1;" ::"r"(o + 13056), "h"((uint16_t)(u1 >> 16)) : "memory");
            }
        }
        PROF(t2 == 0, 3517);
        bar_sync(9, 384);
        fence_async_smem();
#pragma unroll 1
        for (int j = 0; j < 16; j++) {
            const int d = d0 + w - 8;
            asm volatile("{.reg .pred p; elect.sync _|p,0xffffffff; @p cp.async.bulk.global.shared::cta.bulk_group [%0],[%1],%2;}" ::"l"(g_P + (((d >> 5) * 16 + j) * 32 + (d & 31)) * PW),
                         "r"(sb + P_P + ((w - 8) * 2080 + j * 128) * 4), "r"(PW * 4) : "memory");
        }
        asm volatile("cp.async.bulk.commit_group; cp.async.bulk.wait_group 0;" ::: "memory");
        bar_arrive(10, 384);
        return;
    }
#pragma unroll
    for (int i = 0; i < 2; i++) {
        const float dt = rbf(expf(blo(pr.ldt[i])));
        const float ar = -rbf(expf(blo(pr.v[i][0]))) * dt, ai = blo(pr.v[i][1]) * dt;
        sts128(sb + P_PRM + (w * 64 + i * 32 + lane) * 16, __float_as_uint(ar * 1.4426950408889634f), __float_as_uint(ai * 0.15915494309189535f),
               __float_as_uint(2.f * (blo(pr.v[i][2]) * dt)), __float_as_uint(2.f * (blo(pr.v[i][3]) * dt)));
    }
    if (tid < 64) sts128(sb + P_U + (tid >> 3) * 2176 + (tid & 7) * 16, 0, 0, 0, 0);
    bar_arrive(6, 384);
    __syncwarp();
    PROF(tid == 0, 3510);
    const int ch = w & 3, hf = w >> 2;
    {
        float k0[4] = {0, 0, 0, 0}, k1[4] = {0, 0, 0, 0}, k2[4] = {0, 0, 0, 0}, k3[4] = {0, 0, 0, 0}, k4[4] = {0, 0, 0, 0}, kl = 0;
#pragma unroll KGU
        for (int j = 0; j < 16; j++) {
            const uint4 q = lds128(sb + P_PRM + (w * 64 + j * 4 + c) * 16);
            const float cr = __uint_as_float(q.z), ci = __uint_as_float(q.w);
            float wr[4], wi[4], vr[4], vi[4];
            cpow(__uint_as_float(q.x), __uint_as_float(q.y), (float)g, wr[0], wi[0]);
            cpow(__uint_as_float(q.x), __uint_as_float(q.y), (float)(g + 8), vr[0], vi[0]);
#pragma unroll
            for (int i = 1; i < 4; i++) { wr[i] = wr[i - 1]; wi[i] = wi[i - 1]; csq(wr[i], wi[i]); vr[i] = vr[i - 1]; vi[i] = vi[i - 1]; csq(vr[i], vi[i]); }
            float hr = wr[3], hi = wi[3];
            csq(hr, hi);
            mma_tf32(k0, wr[0], vr[0], wi[0], vi[0], cr * hr - ci * hi, -(cr * hi + ci * hr));
            hr = vr[3]; hi = vi[3]; csq(hr, hi);
            mma_tf32(k1, wr[0], vr[0], wi[0], vi[0], cr * hr - ci * hi, -(cr * hi + ci * hr));
            csq(hr, hi);
            mma_tf32(k2, wr[1], vr[1], wi[1], vi[1], cr * hr - ci * hi, -(cr * hi + ci * hr));
            csq(hr, hi);
            mma_tf32(k3, wr[2], vr[2], wi[2], vi[2], cr * hr - ci * hi, -(cr * hi + ci * hr));
            csq(hr, hi);
            mma_tf32(k4, wr[3], vr[3], wi[3], vi[3], cr * hr - ci * hi, -(cr * hi + ci * hr));
            csq(hr, hi);
            kl += cr * hr - ci * hi;
        }
        kl += __shfl_xor_sync(0xffffffffu, kl, 1); kl += __shfl_xor_sync(0xffffffffu, kl, 2);
        const uint32_t o = sb + P_K6 + (ch * 656 + c * 32 + g) * 4, ol = sb + P_K6 + (ch * 656 + 640) * 4;
#define KST(k, base) sts32(o + (base) * 4, __float_as_uint(k[0])); sts32(o + (base) * 4 + 64, __float_as_uint(k[1])); \
                     sts32(o + (base) * 4 + 32, __float_as_uint(k[2])); sts32(o + (base) * 4 + 96, __float_as_uint(k[3]))
#define KAD(k, base) k[0] += __uint_as_float(lds32(o + (base) * 4)); k[1] += __uint_as_float(lds32(o + (base) * 4 + 64)); \
                     k[2] += __uint_as_float(lds32(o + (base) * 4 + 32)); k[3] += __uint_as_float(lds32(o + (base) * 4 + 96))
        if (hf == 0) {
            bar_sync(2 + ch, 64);
            KAD(k0, 0); KAD(k1, 128); KAD(k2, 256); KAD(k3, 384); KAD(k4, 512);
            kl += __uint_as_float(lds32(ol));
            __syncwarp();
        }
        KST(k0, 0); KST(k1, 128); KST(k2, 256); KST(k3, 384); KST(k4, 512);
        if (lane == 0) sts32(ol, __float_as_uint(kl));
        if (hf == 1) { __syncwarp(); bar_arrive(2 + ch, 64); }
    }
    PROF(tid == 0, 3511);
    bar_sync(8, 384);
    PROF(tid == 0, 3512);
    if (tid < 64) sts32(sb + P_P + ((tid >> 4) * 2080 + (tid & 15)) * 4, 0);
#pragma unroll 1
    for (int x = tid; x < 2048; x += 512) {
        uint32_t pw[2][4];
#pragma unroll
        for (int h = 0; h < 2; h++) {
            const int y = x + h * 256;
            const int i0 = y <= 256 ? y : 256 + (int)((pack2((float)y, 0.f) & 0xffff) - 0x4380);
            const int i1 = y <= 256 ? max(y - 1, 0) : 256 + (int)((pack2((float)(y - 1), 0.f) & 0xffff) - 0x4380);
#pragma unroll
            for (int k = 0; k < 4; k++) {
                const float lo = __uint_as_float(lds32(sb + P_K6 + k * 2624 + i0 * 4)), hi = __uint_as_float(lds32(sb + P_K6 + k * 2624 + i1 * 4));
                pw[h][k] = pack2(lo, y ? hi : 0.f);
            }
        }
#pragma unroll
        for (int h = 0; h < 2; h++)
#pragma unroll
            for (int k = 0; k < 4; k++) sts32(sb + P_P + (k * 2080 + x + h * 256 + 16) * 4, pw[h][k]);
    }
    bar_sync(9, 384);
    PROF(tid == 0, 3513);
    {
        float acc[16][4];
#pragma unroll
        for (int j = 0; j < 16; j++) acc[j][0] = acc[j][1] = acc[j][2] = acc[j][3] = 0;
#pragma unroll 1
        for (int e = hf * 4; e < hf * 4 + 4; e++) {
            uint32_t B[16][2];
            const uint32_t ua = sb + P_U + ch * 4352 + ((lane >> 3) & 1) * 2176 + (8 + (lane >> 4) * 8 + (lane & 7) - e) * 16;
#pragma unroll
            for (int j = 0; j < 8; j++) { const uint4 v = ldsm4(ua + j * 256); B[2 * j][0] = v.x; B[2 * j][1] = v.y; B[2 * j + 1][0] = v.z; B[2 * j + 1][1] = v.w; }
            const uint32_t pa = sb + P_P + (ch * 2080 + 16 + e * 16 + g - 2 * c) * 4;
#pragma unroll
            for (int d = 0; d < 16; d++) {
                const uint32_t a0 = lds32(pa + d * 512), a1 = lds32(pa + d * 512 + 32), a2 = lds32(pa + d * 512 - 32);
#pragma unroll
                for (int j = d; j < 16; j++) mma16(acc[j], a0, a1, a2, a0, B[j - d][0], B[j - d][1]);
            }
        }
        PROF(tid == 0, 3514);
        const uint32_t o = sb + P_Y + (ch * 2560 + c * 40 + g) * 4;
#pragma unroll
        for (int j = 0; j < 8; j++) {
#pragma unroll
            for (int i = 0; i < 4; i++) { const float lo = acc[j][i], hi = acc[j + 8][i]; acc[j][i] = hf ? hi : lo; sts32(o + (j + 8 - hf * 8) * 640 + (i & 1) * 80 + (i >> 1) * 32, __float_as_uint(hf ? lo : hi)); }
        }
        bar_sync(2 + ch, 64);
#pragma unroll
        for (int j = 0; j < 8; j++) {
#pragma unroll
            for (int i = 0; i < 4; i++) acc[j][i] += __uint_as_float(lds32(o + (j + hf * 8) * 640 + (i & 1) * 80 + (i >> 1) * 32));
        }
#pragma unroll
        for (int j = 0; j < 8; j++) {
#pragma unroll
            for (int i = 0; i < 4; i++) sts32(o + (j + hf * 8) * 640 + (i & 1) * 80 + (i >> 1) * 32, __float_as_uint(acc[j][i]));
        }
    }
    const uint2 dk = __ldg((const uint2*)(a.Dk + d0));
    bar_sync(1, 256);
#pragma unroll 2
    for (int i = 0; i < 8; i++) {
        const int t = i * 256 + tid;
        const uint32_t o = sb + P_Y + (t + 4 * (t >> 4)) * 4;
        const uint4 xu = lds128(sb + P_X + t * 16);
        float y[4];
#pragma unroll
        for (int k = 0; k < 4; k++) y[k] = rbf(__uint_as_float(lds32(o + k * 10240)));
        uint2 r;
        r.x = pack2(blo(xu.x) + rbf(y[0] + rbf(blo(xu.z) * blo(dk.x))), bhi(xu.x) + rbf(y[1] + rbf(bhi(xu.z) * bhi(dk.x))));
        r.y = pack2(blo(xu.y) + rbf(y[2] + rbf(blo(xu.w) * blo(dk.y))), bhi(xu.y) + rbf(y[3] + rbf(bhi(xu.w) * bhi(dk.y))));
        ((uint2*)(g_xA[0] + ((t >> 7) * 8 + (d0 >> 6)) * 1024 + ((t & 127) >> 3) * 64 + ((d0 & 63) >> 3) * 8 + (t & 7)))[(d0 >> 2) & 1] = r;
        if (i == 0) {
            const float e0 = blo(r.x), e1 = bhi(r.x), e2 = blo(r.y), e3 = bhi(r.y);
            asm volatile("red.relaxed.gpu.global.add.v2.f32 [%0],{%1,%2};" ::"l"(g_st[0] + (t >> 7) * 2048 + lds32(sb + S_TAG) * 128 + (t & 127)),
                         "f"((e0 + e1) + (e2 + e3)), "f"((e0 * e0 + e1 * e1) + (e2 * e2 + e3 * e3)) : "memory");
        }
    }
    PROF(tid == 0, 3515);
    bar_sync(10, 384);
}

__global__ void __cluster_dims__(2, 1, 1) __launch_bounds__(384, 1) main_kernel(const __grid_constant__ Params p) {
    extern __shared__ __align__(1024) uint8_t smem[];
    const uint32_t sb = __shfl_sync(0xffffffffu, smem_u32(smem), 0);
    uint32_t rank; asm("mov.u32 %0,%%cluster_ctarank;" : "=r"(rank));
    const int wi = __shfl_sync(0xffffffffu, threadIdx.x >> 5, 0);
    const int cl = blockIdx.x >> 1, wg = wi >> 2;
    const bool rec = p.rec0 >= 0 && cl >= p.rec0 && cl < p.rec0 + 32;
    PROF(threadIdx.x == 0, 3500);
    ProRegs pr;
    prologue_load(p.pa, max((int)blockIdx.x - 4, 0), pr);
    if (rec) rec_init(p, sb, cl - p.rec0, rank); else bulk_init(sb);
    if (threadIdx.x == 352 && p.dopro && cl >= 2) {
        mbar_init(sb + S_XBAR, 1);
        asm volatile("fence.mbarrier_init.release.cluster;" ::: "memory");
        mbar_expect(sb + S_XBAR, 32768);
        for (int j = 0; j < 8; j++) tma2d(sb + P_X + j * 4096, &p.tm[3], ((blockIdx.x - 4) >> 1) * 8, j * 256, sb + S_XBAR);
    }
    if (threadIdx.x == 320) {
        unsigned v;
        asm volatile("ld.relaxed.gpu.global.u32 %0,[%1];" : "=r"(v) : "l"(g_gate) : "memory");
        v = v / (4 * NCL) + p.dopro;
        sts64(sb + S_GATE, v * (4 * NCL), v & 1);
    }
    __syncwarp();
    asm volatile("barrier.cluster.arrive.relaxed.aligned;" ::: "memory");
    if (wg == 2) bar_arrive(8, 384);
    if (p.dopro && cl >= 2) prologue(p.pa, sb, blockIdx.x - 4, wi, pr); else if (wg < 2) bar_sync(8, 384);
    asm volatile("barrier.cluster.wait.aligned;" ::: "memory");
    fence_async_smem();
    bar_sync(wg == 2 ? 7 : 1, wg == 2 ? 128 : 256);
    if (p.dopro && (threadIdx.x == 32 || threadIdx.x == 352)) red_release(g_gate, 1);
    if (rec) {
        if (threadIdx.x == 0) {
            rec_fetch(&p.tm[1], sb + R_STK, (cl - p.rec0) * 128, rank * 256, 2, sb + R_BAR + RB_INIT * 8);
            rec_fetch(&p.tm[2], sb + R_STV, (cl - p.rec0) * 128, rank * 256, 2, sb + R_BAR + RB_INIT * 8);
        }
    }
    PROF(threadIdx.x == 0, 3506);
    __syncwarp();
    if (rec) {
        const int head = cl - p.rec0;
        if (wg == 2) {
            reg_dec<RH>();
            const int w = wi & 3;
            if (threadIdx.x == 256) rec_fetch(&p.tm[0], sb + R_STQ, head * 128, rank * 256, 2, sb + R_BAR + RB_INIT * 8);
            __syncwarp();
            wait_cnt_warp(g_gate, lds32(sb + S_GATE));
            if (p.dostats) x1_stats((head * 2 + rank) * 4 + w, lds32(sb + S_TAG));
            __syncthreads();
            cluster_sync();
            if ((p.chains >> (w >> 1)) & 1) rec_attn(p, sb, w >> 1, w & 1, head, rank);
        } else {
            reg_inc<RW0>();
            rec_weights(p, sb, head, rank, wi);
        }
    } else {
        if (wg == 2) {
            reg_dec<40>();
            const int w = wi & 3;
            if (w == 0) bulk_producer(p, sb, cl, rank); else if (w >= 2) bulk_release(p, sb, cl, rank, w - 2);
        } else { reg_inc<232>(); bulk_consumer(p, sb, cl, rank, wi); }
    }
    __syncwarp();
    cluster_sync();
}

typedef CUresult (*EncFn)(CUtensorMap*, CUtensorMapDataType, cuuint32_t, void*, const cuuint64_t*, const cuuint64_t*, const cuuint32_t*, const cuuint32_t*,
                          CUtensorMapInterleave, CUtensorMapSwizzle, CUtensorMapL2promotion, CUtensorMapFloatOOBfill);
inline uint32_t mk(int type, int layer, int ch, int a, int b, int c) { return type | (layer << 3) | (ch << 4) | (a << 8) | (b << 16) | ((uint32_t)c << 24); }
constexpr int SMEM_BYTES = 232448;

struct Sched {
    Params* P; int n[NCL];
    void clear() { memset(P->task, 0, sizeof(P->task)); memset(n, 0, sizeof(n)); }
    void add(int cl, uint32_t t) { if (n[cl] < MAXT - 1) P->task[cl][n[cl]++] = t; }
};

#define LAG 13
#define TS1 2400
#define TS2 2950
#define REC0 4
#define DQU 2450
#define DQO 1400
#define DHN 380
#define PUBN 600
#define DUN 5400
#define NQ1 4
#define FAST0 1
#define FAST1 14
#define MARG 1000
struct Plan { uint32_t w[NCL][MAXT]; int n[NCL]; double end, rec; };
void simulate(Plan& L, int nc, int n0, int nlong, int nuns, int ns2, int nhg, double hs) {
    const double INF = 1e18, DKB = 600, DOV = 700, DH = DHN, DHO = 1100, DF = 2200, DFB = 200, POLL = 450, FILL = 500, PUB = PUBN;
    enum { Q0, O0, Q1, HB, O1, FI, NK };
    struct Grp { int n, left; double done; } G[NK][16];
    double fr[NCL], it[100] = {}, cv[16];
    int ns[16], last[2][NCL], uc = 0, nit = 0;
    memset(L.n, 0, sizeof(L.n)); L.end = 0;
    auto fast = [&](int c) { return c < FAST0 || c >= FAST1; };
    for (int c = 0; c < 16; c++) {
        ns[c] = c < nuns ? 1 : c == 15 ? 16 : c == 14 ? 8 : ns2;
        const int cnt[NK] = {c < 2 ? 48 : (c & 1) ? 0 : 96, OPS1, c == 15 ? 24 : fast(c) ? 16 : 48 / NQ1, c >= 2 && !(c & 1) ? 16 : 0, ns[c], ns[c] == 1 ? 0 : c >= 14 ? 8 : 4};
        for (int k = 0; k < NK; k++) G[k][c] = {cnt[k], cnt[k], 0};
        cv[c] = INF;
    }
    for (int i = 0; i < nc; i++) { fr[i] = 0; last[0][i] = last[1][i] = -1; }
    auto fin = [&](int k, int c) { if ((k == Q0 && c >= 2) || k == HB) c &= ~1; return G[k][c].left ? INF : G[k][c].done; };
    auto len = [&](int i) { return (i >= LAG && i < 64) ? (double)TS2 : (double)TS1; };
    auto end_it = [&](int i) { return i < nit ? it[i] + len(i) : INF; };
    auto nominal = [&](int i) { if (i < nit) return it[i]; double t = nit ? it[nit - 1] : 11000 - TS1; for (int j = nit - 1; j < i; j++) t += len(j); return t; };
    auto put = [&](int i, uint32_t w) { if (L.n[i] < MAXT - 4) L.w[i][L.n[i]++] = w; else L.end = INF; };
    auto rel = [&](int k, int c) {
        switch (k) {
            case Q0: return 0.0;
            case O0: return end_it(4 * c + 3) + PUB + POLL;
            case Q1: return cv[c] + POLL;
            case HB: return cv[c - 2] + 600 + POLL;
            case O1: return end_it(LAG + 4 * c + 3) + PUB + POLL;
            default: return fin(O1, c) + POLL;
        }
    };
    auto dur = [&](int k, int c) {
        switch (k) {
            case Q0: return DQO + (c < 2 ? 2.0 : 1.0) * DQU;
            case O0: return ((63 + OPS1) / OPS1) * DKB + 800;
            case HB: return DHO + DH * c;
            case Q1: return DQO + 48.0 / G[Q1][c].n * DQU;
            case O1: return DOV + DKB * 64 / ns[c] + (ns[c] == 1 ? 1500 : 0);
            default: return DF + DFB * ns[c] * (c >= 14 ? 0.5 : 1);
        }
    };
    auto o0_est = [&](int c) {
        double t = uc ? cv[uc - 1] - 900 : 0;
        for (int j = uc; j < c; j++) t = fmax(t, nominal(4 * j + 4) + PUB + POLL + FILL) + dur(O0, j) + DUN;
        return fmax(t, nominal(4 * c + 4) + PUB + POLL);
    };
    auto cv_est = [&](int c) { return c < uc ? cv[c] : o0_est(c) + FILL + dur(O0, c) + DUN + 900; };
    auto first = [&](int k, int c) { return k == O0 || c == 15 ? 0 : OPS1; };
    while (true) {
        while (nit < 64 + LAG) {
            double t = nit ? end_it(nit - 1) : 0;
            if (nit < 64) t = fmax(t, fin(Q0, nit >> 2) + POLL);
            if (nit >= LAG) t = fmax(t, fin(Q1, (nit - LAG) >> 2) + (nit < 64 ? 0 : POLL));
            if (t >= INF) break;
            it[nit++] = t;
        }
        int i = -1;
        for (int j = 0; j < nc; j++) if (fr[j] < INF && (i < 0 || fr[j] < fr[i])) i = j;
        if (i < 0) break;
        const double t = fr[i];
        double lim = INF;
        if (i < 8 && last[0][i] == uc) {
            if (G[O0][uc].left || fin(HB, uc) >= INF) { fr[i] = t + 200; continue; }
            const double e = fmax(G[O0][uc].done, fin(HB, uc) - 2000) + DUN;
            for (int j = 0; j < 8; j++) { put(j, mk(T_CV, 0, uc, 2 * j, 0, 0)); fr[j] = e; }
            cv[uc++] = e + 900;
            continue;
        }
        const bool hg = (unsigned)(i - OPS1 - 48 / NQ1) < (unsigned)nhg;
        double hlim = INF;
        for (int c = 2; c < 16 && hg; c++) if (G[HB][c].left) { hlim = cv_est(c - 2) + hs; break; }
        int mine[2] = {-1, -1};
        for (int k = 0; k < 2; k++)
            for (int c = last[k][i] + 1; c < 16 && mine[k] < 0; c++) if ((unsigned)(i - first(O0 + k, c)) < (unsigned)G[O0 + k][c].n) mine[k] = c;
        if (mine[0] >= 0) lim = o0_est(mine[0]) - (i < 8 && !uc ? 8500 : 0);
        else if (mine[1] >= 0) lim = cv_est(mine[1]) + POLL;
        else if (i < 16 && G[O1][15].left) lim = fmin(lim, nominal(64 + LAG) + PUB);
        int bk = -1, bc = 0; double bd = INF;
        for (int k = 0; k < NK; k++)
            for (int c = 0; c < 16; c++) {
                const bool urgent = k == O0 || k == Q1 || (k == O1 && c == 15);
                if (!G[k][c].left || ((k == O0 || k == Q1) && c != mine[k - O0]) || (k == O1 && ns[c] == 1 && i < nc - nlong) || (k == O1 && c == 15 && i >= 16)) continue;
                if (rel(k, c) > t || (t + dur(k, c) + (k == Q0 && c >= 2 ? DQU : 0) > lim && !urgent)) continue;
                if (i < 8 && uc && uc < 16 && k != O0) continue;
                if ((k == HB && !hg) || (k != HB && !urgent && t + dur(k, c) + (k == Q0 && c >= 2 ? DQU : 0) > hlim)) continue;
                const double dl = urgent || (k == O1 && ns[c] == 1) ? -INF : k == HB ? -INF / 2 : k == Q0 ? nominal(4 * c) - 3000 : 1e9 + c * 2 + (k == O1);
                if (dl < bd) { bd = dl; bk = k; bc = c; }
            }
        if (bk < 0) {
            bool any = i < 8 && uc < 16;
            for (int k = 0; k < NK; k++) for (int c = 0; c < 16; c++) any = any || G[k][c].left;
            fr[i] = any ? t + 200 : INF;
            if (t > 400000) { L.end = INF; return; }
            continue;
        }
        Grp& g = G[bk][bc];
        const int n = g.n - g.left, c = bc;
        int nu = 1;
        double d = dur(bk, c);
        if (bk == Q0) for (nu = c < 2 ? 2 : 1; c >= 2 && nu < g.left && (nu < 2 || (nu < n0 && t + d + DQU < fmin(fmin(lim, hlim), bd - MARG))); nu++) d += DQU;
        if (bk == O0 || bk == Q1) last[bk - O0][i] = c;
        if (bk == O0 && !c && i < 8) put(i, mk(T_CV, 0, 3, 2 * i, 0, 128));
        g.left -= nu;
        const double e = fmax(t, rel(bk, c) + FILL) + (t < 1 ? 4500 : 0) + d;
        fr[i] = e;
        g.done = fmax(g.done, e + (bk == O1 ? 1900 : bk == O0 ? 0 : 1000));
        if (bk == FI || (bk == O1 && ns[c] == 1)) L.end = fmax(L.end, e);
        put(i, bk == Q0 ? (c < 2 ? mk(T_QKV, 0, c, 2 * n, 2, 0) : mk(T_QKV, 0, c, n, nu, 64))
             : bk == O0 ? mk(T_OP, 0, c, i * 64 / OPS1, (i + 1) * 64 / OPS1 - i * 64 / OPS1, i)
             : bk == HB ? mk(T_CV, 1, c, 2 * n, 0, 0)
             : bk == Q1 ? mk(T_QKV, 1, c, (i - first(Q1, c)) * 96 / g.n, 48 / g.n, 0)
             : bk == O1 ? mk(T_OP, 1, c, n * 64 / ns[c], 64 / ns[c], ns[c] == 1 ? 32 : n)
                        : mk(T_FIN, 1, c, n * (32 / g.n), ns[c], 16 / g.n));
    }
    L.rec = end_it(63 + LAG);
}
void plan(Params& P) {
    P.rec0 = REC0; P.chains = 3; P.lag = LAG; P.dostats = 1; P.dopro = 1;
    static Plan L, T;
    int cls[NCL], nc = 0;
    for (int c = REC0 + 32; c < NCL; c++) cls[nc++] = c;
    for (int c = REC0 - 1; c >= 0; c--) cls[nc++] = c;
    L.end = 1e18;
    for (int n0 = 10; n0 >= 4; n0 -= 2)
        for (int nuns = 0; nuns <= 6; nuns += 3)
            for (int ns2 = 8; ns2 >= 4; ns2 -= 4)
                for (int v = 0; v < 4; v++) {
                    const int nhg = (v & 1) ? 6 : 8, hs = (v & 2) ? 4000 : 2000;
                    simulate(T, nc, n0, nuns > 3 ? 2 : 1, nuns, ns2, nhg, hs);
                    if (T.end < L.end) {
                        L = T;
                    }
                }
    Sched S; S.P = &P; S.clear();
    S.add(0, mk(T_QKV, 1, 15, 60, 2, 128)); S.add(0, mk(T_OP, 1, 15, 0, 4, 128));
    S.add(1, mk(T_CV, 0, 3, 0, 0, 128));
    for (int i = 0; i < nc; i++) {
        bool warm = false;
        for (int k = 0; k < L.n[i]; k++) {
            if (!warm && k + 1 < L.n[i] && (L.w[i][k + 1] & 255) == (mk(T_FIN, 1, 15, 0, 0, 0) & 255)) { S.add(cls[i], L.w[i][k + 1] | 0x80000000u); warm = true; }
            S.add(cls[i], L.w[i][k]);
            if ((L.w[i][k] & 7) == T_FIN) warm = true;
        }
    }
}

#define TK0() do {} while (0)
#define TK() do { P.e0 = (P.chains & 1) ? 64 : 0; P.b1 = (P.chains & 2) ? P.lag : 1000; P.nit = (P.chains & 2) ? P.lag + 64 : 64; TK0(); } while (0)
}

extern "C" void kernel_launch(void* const* d_in, const int* in_sizes, int n_in, void* d_out, int out_size) {
    typedef const __nv_bfloat16* BP;
    static EncFn enc = nullptr;
    if (!enc) {
        void* fn = nullptr; cudaDriverEntryPointQueryResult qr;
        cudaGetDriverEntryPoint("cuTensorMapEncodeTiled", &fn, cudaEnableDefault, &qr);
        enc = (EncFn)fn;
        cudaFuncSetAttribute(main_kernel, cudaFuncAttributeMaxDynamicSharedMemorySize, SMEM_BYTES);
    }
    static Params P;
    for (int i = 0; i < 4; i++) {
        const cuuint64_t cols = i < 3 ? 4096 : 512, rows = i < 3 ? 512 : 4096;
        cuuint64_t d2[2] = {cols, rows}, d3[3] = {64, rows, cols / 64}, str[2] = {cols * 2, 128};
        cuuint32_t box[3] = {64, 64, 4}, es[3] = {1, 1, 1};
        enc(&P.tm[i < 3 ? i : 4], CU_TENSOR_MAP_DATA_TYPE_BFLOAT16, 2, d_in[9 + i], d2, str, box, es, CU_TENSOR_MAP_INTERLEAVE_NONE, CU_TENSOR_MAP_SWIZZLE_128B,
                       CU_TENSOR_MAP_L2_PROMOTION_L2_128B, CU_TENSOR_MAP_FLOAT_OOB_FILL_NONE);
        for (int m = 0; m < 2; m++) {
            cuuint32_t box3[3] = {64, 32, m ? 2u : 4u};
            enc(&P.t3[m][i], CU_TENSOR_MAP_DATA_TYPE_BFLOAT16, 3, d_in[9 + i], d3, str, box3, es, CU_TENSOR_MAP_INTERLEAVE_NONE, CU_TENSOR_MAP_SWIZZLE_128B,
                CU_TENSOR_MAP_L2_PROMOTION_L2_128B, CU_TENSOR_MAP_FLOAT_OOB_FILL_NONE);
        }
    }
    {
        cuuint64_t dims[2] = {512, 2048}, str[1] = {1024};
        cuuint32_t box[2] = {8, 256}, es[2] = {1, 1};
        enc(&P.tm[3], CU_TENSOR_MAP_DATA_TYPE_BFLOAT16, 2, d_in[0], dims, str, box, es, CU_TENSOR_MAP_INTERLEAVE_NONE, CU_TENSOR_MAP_SWIZZLE_NONE,
            CU_TENSOR_MAP_L2_PROMOTION_NONE, CU_TENSOR_MAP_FLOAT_OOB_FILL_NONE);
    }
    for (int m = 0; m < 2; m++) {
        void* ga; cudaGetSymbolAddress(&ga, g_A);
        cuuint64_t dims[2] = {512, sizeof(AOps) / 1024}, str[1] = {1024};
        cuuint32_t box[2] = {256, m ? 16u : 8u}, es[2] = {1, 1};
        enc(&P.ta[m], CU_TENSOR_MAP_DATA_TYPE_BFLOAT16, 2, ga, dims, str, box, es, CU_TENSOR_MAP_INTERLEAVE_NONE, CU_TENSOR_MAP_SWIZZLE_NONE,
            CU_TENSOR_MAP_L2_PROMOTION_L2_128B, CU_TENSOR_MAP_FLOAT_OOB_FILL_NONE);
    }
    P.mem0 = (BP)d_in[8]; P.Wo = (BP)d_in[12]; P.Dskip = (BP)d_in[6]; P.out = (__nv_bfloat16*)d_out;
    cudaStream_t s = cudaStreamPerThread;
    P.pa = {(BP)d_in[0], (BP)d_in[1], (BP)d_in[2], (BP)d_in[3], (BP)d_in[4], (BP)d_in[5], (BP)d_in[6], (BP)d_in[9], (BP)d_in[10], (BP)d_in[11], (BP)d_in[12], (BP)d_in[8]};
    static bool planned = false;
    if (!planned) { plan(P); planned = true; }
    TK(); main_kernel<<<2 * NCL, 384, SMEM_BYTES, s>>>(P); TK();
}
```

```cpp
#include <cuda_runtime.h>
#include <cuda_bf16.h>
#include <cuda.h>
#include <stdint.h>
#include <string.h>
#include <math.h>

namespace {

constexpr int NCL = 66;
constexpr int MAXT = 64;
#define PFC 1
#define OPS1N 8
constexpr int OPS1 = OPS1N;
constexpr int MAXSPLIT = 16;
constexpr int PW = 144;

struct AOps { uint4 x[2][16 * 8 * 1024], o[2][16 * 64 * 1024]; };
__device__ AOps g_A;
#define g_xA g_A.x
#define g_o g_A.o
__device__ float2 g_st[2][16 * 2048];
__device__ float2 g_st2[2 * 16 * 128];
__device__ uint4 g_qkv[2][64 * 64 * 768];
__device__ uint4 g_pp[2][16 * MAXSPLIT * 8192];
__device__ uint4 g_acc[7 * 2048];
__device__ unsigned g_gate[32];
__device__ uint32_t g_P[16 * 16 * 32 * PW];
__device__ uint4 g_u[16 * 16 * 512];
__device__ float4 g_carry[2][17 * 16 * 4 * 256];
__device__ unsigned g_cnt[13 * 64];
__device__ uint32_t g_ln0[2048];

enum { C_QKV0 = 0, C_QKV1 = 1  , C_O0 = 2, C_O1 = 3, C_U = 4, C_OP1 = 5, C_CV = 6, C_ST = 7, C_H = 8, C_OP0 = 9   };
__device__ __forceinline__ unsigned* cnt_ptr(int kind, int chunk) { return g_cnt + kind * 64 + chunk; }

enum { T_END = 0, T_QKV = 1, T_OP = 2, T_CV = 3, T_FIN = 4 };
struct ProArgs { const __nv_bfloat16 *x, *lAr, *Ai, *Cr, *Ci, *ldt, *Dk, *Wq, *Wk, *Wv, *Wo, *mem0; };
struct Params {
    CUtensorMap tm[5];
    CUtensorMap t3[2][4];
    CUtensorMap ta[2];
    ProArgs pa;
    int dopro;
    const __nv_bfloat16* mem0;
    const __nv_bfloat16* Wo;
    const __nv_bfloat16* Dskip;
    __nv_bfloat16* out;
    int rec0;
    int chains;
    int lag;
    int b1, e0, nit;
    int zero, gpit;
    int dostats;
    uint32_t task[NCL][MAXT];
};

__device__ __forceinline__ uint32_t smem_u32(const void* p) { return (uint32_t)__cvta_generic_to_shared(p); }
__device__ __forceinline__ uint32_t mapa(uint32_t a, uint32_t r) {
    uint32_t o; asm("mapa.shared::cluster.u32 %0,%1,%2;" : "=r"(o) : "r"(a), "r"(r)); return o;
}
__device__ __forceinline__ void mbar_init(uint32_t b, int c) { asm volatile("mbarrier.init.shared::cta.b64 [%0],%1;" ::"r"(b), "r"(c) : "memory"); }
__device__ __forceinline__ void mbar_expect(uint32_t b, int bytes) { asm volatile("mbarrier.arrive.expect_tx.shared::cta.b64 _,[%0],%1;" ::"r"(b), "r"(bytes) : "memory"); }
__device__ __forceinline__ void mbar_arrive(uint32_t b) { asm volatile("mbarrier.arrive.shared::cta.b64 _,[%0];" ::"r"(b) : "memory"); }
__device__ __forceinline__ void mbar_arrive_cluster(uint32_t b) { asm volatile("mbarrier.arrive.shared::cluster.b64 _,[%0];" ::"r"(b) : "memory"); }
__device__ __forceinline__ void mbar_arrive1(uint32_t b) { asm volatile("{.reg .pred p; elect.sync _|p,0xffffffff; @p mbarrier.arrive.shared::cta.b64 _,[%0];}" ::"r"(b) : "memory"); }
__device__ __forceinline__ void mbar_arrive1_cluster(uint32_t b) { asm volatile("{.reg .pred p; elect.sync _|p,0xffffffff; @p mbarrier.arrive.shared::cluster.b64 _,[%0];}" ::"r"(b) : "memory"); }
__device__ __forceinline__ void mbar_wait(uint32_t b, uint32_t ph) {
    asm volatile(
        "{.reg .pred p; .reg .u32 n; mov.u32 n,0;\n"
        "W%=: mbarrier.try_wait.parity.shared::cta.b64 p,[%0],%1;\n"
        "@p bra D%=;\n"
        "add.u32 n,n,1; setp.lt.u32 p,n,2000000; @p bra W%=;\n"
        "trap;\n"
        "D%=: }" ::"r"(b), "r"(ph) : "memory");
}
__device__ __forceinline__ bool mbar_test(uint32_t b, uint32_t ph) {
    uint32_t ok;
    asm volatile("{.reg .pred p; mbarrier.test_wait.parity.shared::cta.b64 p,[%1],%2; selp.u32 %0,1,0,p;}" : "=r"(ok) : "r"(b), "r"(ph) : "memory");
    return ok;
}
__device__ __forceinline__ bool wait_lds128(uint32_t b, uint32_t ph, uint32_t a, uint4& v) {
    uint32_t ok;
    asm volatile("{.reg .pred p; mbarrier.try_wait.parity.shared::cta.b64 p,[%5],%6,20000; ld.shared.v4.u32 {%0,%1,%2,%3},[%7]; selp.u32 %4,1,0,p;}"
                 : "=r"(v.x), "=r"(v.y), "=r"(v.z), "=r"(v.w), "=r"(ok) : "r"(b), "r"(ph), "r"(a) : "memory");
    return ok;
}
__device__ __forceinline__ bool wait_lds64(uint32_t b, uint32_t ph, uint32_t a, uint2& v) {
    uint32_t ok;
    asm volatile("{.reg .pred p; mbarrier.try_wait.parity.shared::cta.b64 p,[%3],%4,20000; ld.shared.v2.u32 {%0,%1},[%5]; selp.u32 %2,1,0,p;}"
                 : "=r"(v.x), "=r"(v.y), "=r"(ok) : "r"(b), "r"(ph), "r"(a) : "memory");
    return ok;
}
template <int PH> __device__ __forceinline__ void mbar_wait_c(uint32_t b) {
    asm volatile(
        "{.reg .pred p; .reg .u32 n; mov.u32 n,%2;\n"
        "W%=: mbarrier.try_wait.parity.shared::cta.b64 p,[%0],%1;\n"
        "@p bra D%=;\n"
        "add.u32 n,n,1; setp.lt.u32 p,n,2000000; @p bra W%=;\n"
        "trap;\n"
        "D%=: }" ::"r"(b), "n"(PH), "n"(PH) : "memory");
}
__device__ __forceinline__ void bar_sync(int id, int n) { asm volatile("bar.sync %0,%1;" ::"r"(id), "r"(n) : "memory"); }
__device__ __forceinline__ void bar_arrive(int id, int n) { asm volatile("bar.arrive %0,%1;" ::"r"(id), "r"(n) : "memory"); }
__device__ __forceinline__ void cluster_sync() { asm volatile("barrier.cluster.arrive.relaxed.aligned; barrier.cluster.wait.aligned;" ::: "memory"); }
__device__ __forceinline__ void fence_async() { asm volatile("fence.proxy.async;" ::: "memory"); }
__device__ __forceinline__ void fence_async_smem() { asm volatile("fence.proxy.async.shared::cta;" ::: "memory"); }
#define EFR 1
#define EFW 2
constexpr uint64_t POL_N = 0x1000000000000000ull, POL_F = 0x12F0000000000000ull;
constexpr uint64_t POL_LAST = EFR ? POL_F : POL_N  , POL_LATE = EFW ? POL_F : POL_N  , POL_SOON = EFW > 1 ? POL_F : POL_N;
__device__ __forceinline__ void bulk_g2s(uint32_t dst, const void* src, int bytes, uint32_t bar, uint64_t pol) {
    asm volatile("cp.async.bulk.shared::cluster.global.mbarrier::complete_tx::bytes.L2::cache_hint [%0],[%1],%2,[%3],%4;" ::"r"(dst), "l"(src), "r"(bytes), "r"(bar), "l"(pol) : "memory");
}
__device__ __forceinline__ void bulk_g2s_mc(uint32_t dst, const void* src, int bytes, uint32_t bar, uint64_t pol) {
    asm volatile("cp.async.bulk.shared::cluster.global.mbarrier::complete_tx::bytes.multicast::cluster.L2::cache_hint [%0],[%1],%2,[%3],%4,%5;" ::"r"(dst), "l"(src), "r"(bytes), "r"(bar), "h"((uint16_t)3), "l"(pol) : "memory");
}
__device__ __forceinline__ void bulk_s2s(uint32_t dst, uint32_t src, int bytes, uint32_t bar) {
    asm volatile("cp.async.bulk.shared::cluster.shared::cta.mbarrier::complete_tx::bytes [%0],[%1],%2,[%3];" ::"r"(dst), "r"(src), "r"(bytes), "r"(bar) : "memory");
}
__device__ __forceinline__ bool elect() {
    uint32_t r; asm volatile("{.reg .pred p; elect.sync _|p,0xffffffff; selp.u32 %0,1,0,p;}" : "=r"(r)); return r;
}
__device__ __forceinline__ void stg128(uint4* p, uint4 v, uint64_t pol) {
    asm volatile("st.global.L2::cache_hint.v4.u32 [%0],{%1,%2,%3,%4},%5;" ::"l"(p), "r"(v.x), "r"(v.y), "r"(v.z), "r"(v.w), "l"(pol));
}
__device__ __forceinline__ void stg32(uint32_t* p, uint32_t v, uint64_t pol) { asm volatile("st.global.L2::cache_hint.u32 [%0],%1,%2;" ::"l"(p), "r"(v), "l"(pol)); }
__device__ __forceinline__ uint4 ldcg128_last(const uint4* p) {
    uint4 v; asm volatile("ld.global.cg.L2::cache_hint.v4.u32 {%0,%1,%2,%3},[%4],%5;" : "=r"(v.x), "=r"(v.y), "=r"(v.z), "=r"(v.w) : "l"(p), "l"(POL_LAST) : "memory"); return v;
}
__device__ __forceinline__ void tma2d(uint32_t dst, const CUtensorMap* tm, int x, int y, uint32_t bar) {
    asm volatile("cp.async.bulk.tensor.2d.shared::cluster.global.mbarrier::complete_tx::bytes [%0],[%1,{%2,%3}],[%4];" ::"r"(dst), "l"(tm), "r"(x), "r"(y), "r"(bar) : "memory");
}
__device__ __forceinline__ void tma3d_mc(uint32_t dst, const CUtensorMap* tm, int y, int z, uint32_t bar, uint16_t mask) {
    asm volatile("{.reg .pred p; elect.sync _|p,0xffffffff;\n"
                 "@p cp.async.bulk.tensor.3d.shared::cluster.global.mbarrier::complete_tx::bytes.multicast::cluster [%0],[%1,{0,%2,%3}],[%4],%5;}"
                 ::"r"(dst), "l"(tm), "r"(y), "r"(z), "r"(bar), "h"(mask) : "memory");
}
__device__ __forceinline__ void tma2d_mc(uint32_t dst, const CUtensorMap* tm, int x, int y, uint32_t bar, uint16_t mask, uint64_t pol) {
    asm volatile("{.reg .pred p; elect.sync _|p,0xffffffff;\n"
                 "@p cp.async.bulk.tensor.2d.shared::cluster.global.mbarrier::complete_tx::bytes.multicast::cluster.L2::cache_hint [%0],[%1,{%2,%3}],[%4],%5,%6;}"
                 ::"r"(dst), "l"(tm), "r"(x), "r"(y), "r"(bar), "h"(mask), "l"(pol) : "memory");
}
__device__ __forceinline__ void bulk_g2s1(uint32_t dst, const void* src, int bytes, uint32_t bar, uint64_t pol) {
    asm volatile("{.reg .pred p; elect.sync _|p,0xffffffff;\n"
                 "@p cp.async.bulk.shared::cluster.global.mbarrier::complete_tx::bytes.L2::cache_hint [%0],[%1],%2,[%3],%4;}" ::"r"(dst), "l"(src), "r"(bytes), "r"(bar), "l"(pol) : "memory");
}
__device__ __forceinline__ void mbar_expect1(uint32_t b, int bytes) {
    asm volatile("{.reg .pred p; elect.sync _|p,0xffffffff; @p mbarrier.arrive.expect_tx.shared::cta.b64 _,[%0],%1;}" ::"r"(b), "r"(bytes) : "memory");
}
__device__ __forceinline__ void st_async4(uint32_t a, uint32_t x, uint32_t y, uint32_t z, uint32_t w, uint32_t mb) {
    asm volatile("st.async.shared::cluster.mbarrier::complete_tx::bytes.v4.b32 [%0],{%1,%2,%3,%4},[%5];" ::"r"(a), "r"(x), "r"(y), "r"(z), "r"(w), "r"(mb) : "memory");
}
__device__ __forceinline__ void st_async2(uint32_t a, uint32_t x, uint32_t y, uint32_t mb) {
    asm volatile("st.async.shared::cluster.mbarrier::complete_tx::bytes.v2.b32 [%0],{%1,%2},[%3];" ::"r"(a), "r"(x), "r"(y), "r"(mb) : "memory");
}
#define LDSQ "ld.shared"
__device__ __forceinline__ uint4 lds128(uint32_t a) { uint4 v; asm volatile(LDSQ ".v4.u32 {%0,%1,%2,%3},[%4];" : "=r"(v.x), "=r"(v.y), "=r"(v.z), "=r"(v.w) : "r"(a) : "memory"); return v; }
__device__ __forceinline__ uint2 lds64(uint32_t a) { uint2 v; asm volatile(LDSQ ".v2.u32 {%0,%1},[%2];" : "=r"(v.x), "=r"(v.y) : "r"(a) : "memory"); return v; }
__device__ __forceinline__ uint32_t lds32(uint32_t a) { uint32_t v; asm volatile(LDSQ ".u32 %0,[%1];" : "=r"(v) : "r"(a) : "memory"); return v; }
__device__ __forceinline__ void sts128(uint32_t a, uint32_t x, uint32_t y, uint32_t z, uint32_t w) { asm volatile("st.shared.v4.u32 [%0],{%1,%2,%3,%4};" ::"r"(a), "r"(x), "r"(y), "r"(z), "r"(w) : "memory"); }
__device__ __forceinline__ void sts64(uint32_t a, uint32_t x, uint32_t y) { asm volatile("st.shared.v2.u32 [%0],{%1,%2};" ::"r"(a), "r"(x), "r"(y) : "memory"); }
__device__ __forceinline__ void sts32(uint32_t a, uint32_t x) { asm volatile("st.shared.u32 [%0],%1;" ::"r"(a), "r"(x) : "memory"); }
__device__ __forceinline__ uint4 ldsm4(uint32_t a) { uint4 v; asm volatile("ldmatrix.sync.aligned.m8n8.x4.shared.b16 {%0,%1,%2,%3},[%4];" : "=r"(v.x), "=r"(v.y), "=r"(v.z), "=r"(v.w) : "r"(a) : "memory"); return v; }
__device__ __forceinline__ uint4 ldsm4t(uint32_t a) { uint4 v; asm volatile("ldmatrix.sync.aligned.m8n8.x4.trans.shared.b16 {%0,%1,%2,%3},[%4];" : "=r"(v.x), "=r"(v.y), "=r"(v.z), "=r"(v.w) : "r"(a) : "memory"); return v; }
__device__ __forceinline__ uint32_t movm(uint32_t a) { uint32_t d; asm volatile("movmatrix.sync.aligned.m8n8.trans.b16 %0,%1;" : "=r"(d) : "r"(a)); return d; }
__device__ __forceinline__ uint32_t pack2(float lo, float hi) { uint32_t d; asm("cvt.rn.bf16x2.f32 %0,%1,%2;" : "=r"(d) : "f"(hi), "f"(lo)); return d; }
__device__ __forceinline__ uint32_t hadd2(uint32_t a, uint32_t b) { uint32_t d; asm("add.rn.bf16x2 %0,%1,%2;" : "=r"(d) : "r"(a), "r"(b)); return d; }
__device__ __forceinline__ float blo(uint32_t v) { return __uint_as_float(v << 16); }
__device__ __forceinline__ float bhi(uint32_t v) { return __uint_as_float(v & 0xffff0000u); }
__device__ __forceinline__ float rbf(float x) { return __uint_as_float(pack2(0.f, x)); }
__device__ __forceinline__ float ex2(float x) { float y; asm("ex2.approx.ftz.f32 %0,%1;" : "=f"(y) : "f"(x)); return y; }
__device__ __forceinline__ float rcp(float x) { float y; asm("rcp.approx.ftz.f32 %0,%1;" : "=f"(y) : "f"(x)); return y; }
__device__ __forceinline__ void mma16(float* c, uint32_t a0, uint32_t a1, uint32_t a2, uint32_t a3, uint32_t b0, uint32_t b1) {
    asm volatile("mma.sync.aligned.m16n8k16.row.col.f32.bf16.bf16.f32 {%0,%1,%2,%3},{%4,%5,%6,%7},{%8,%9},{%0,%1,%2,%3};"
                 : "+f"(c[0]), "+f"(c[1]), "+f"(c[2]), "+f"(c[3]) : "r"(a0), "r"(a1), "r"(a2), "r"(a3), "r"(b0), "r"(b1));
}
__device__ __forceinline__ void mma8(float* c, uint32_t a0, uint32_t a1, uint32_t b0) {
    asm volatile("mma.sync.aligned.m16n8k8.row.col.f32.bf16.bf16.f32 {%0,%1,%2,%3},{%4,%5},{%6},{%0,%1,%2,%3};"
                 : "+f"(c[0]), "+f"(c[1]), "+f"(c[2]), "+f"(c[3]) : "r"(a0), "r"(a1), "r"(b0));
}
__device__ __forceinline__ uint4 ld_rlx128(const uint4* p) {
    uint4 v;
    asm volatile("{.reg .b128 t; ld.relaxed.gpu.global.b128 t,[%4]; mov.b128 {%0,%1,%2,%3},t;}" : "=r"(v.x), "=r"(v.y), "=r"(v.z), "=r"(v.w) : "l"(p) : "memory");
    return v;
}
__device__ __forceinline__ void st_rlx128(uint4* p, uint32_t x, uint32_t y, uint32_t z, uint32_t w) {
    asm volatile("{.reg .b128 t; mov.b128 t,{%1,%2,%3,%4}; st.relaxed.gpu.global.b128 [%0],t;}" ::"l"(p), "r"(x), "r"(y), "r"(z), "r"(w) : "memory");
}
__device__ __forceinline__ uint4 ldcg128(const uint4* p) { uint4 v; asm volatile("ld.global.cg.v4.u32 {%0,%1,%2,%3},[%4];" : "=r"(v.x), "=r"(v.y), "=r"(v.z), "=r"(v.w) : "l"(p) : "memory"); return v; }
__device__ __forceinline__ void red_release(unsigned* p, unsigned v) {
    asm volatile("fence.proxy.async; red.relaxed.gpu.global.add.u32 [%0],%1;" ::"l"(p), "r"(v) : "memory");
}
__device__ __forceinline__ void wait_cnt(const unsigned* p, unsigned target) {
    unsigned v; int n = 0;
    while (true) {
        asm volatile("ld.acquire.gpu.global.u32 %0,[%1];" : "=r"(v) : "l"(p) : "memory");
        if (v >= target) break;
        if (++n > 3000000) __trap();
        __nanosleep(40);
    }
}
__device__ __forceinline__ void wait_cnt_warp(const unsigned* p, unsigned target) {
    unsigned v; int n = 0;
    while (true) {
        asm volatile("ld.acquire.gpu.global.u32 %0,[%1];" : "=r"(v) : "l"(p) : "memory");
        if (__all_sync(0xffffffffu, v >= target)) break;
        if (++n > 3000000) __trap();
    }
}
__device__ __forceinline__ uint64_t mkdesc(uint32_t addr, uint32_t lbo, uint32_t sbo, uint32_t sw) {
    return (uint64_t)((addr & 0x3FFFF) >> 4) | ((uint64_t)(lbo >> 4) << 16) | ((uint64_t)(sbo >> 4) << 32) | ((uint64_t)sw << 62);
}
__device__ __forceinline__ void wg_fence() { asm volatile("wgmma.fence.sync.aligned;" ::: "memory"); }
__device__ __forceinline__ void wg_commit() { asm volatile("wgmma.commit_group.sync.aligned;" ::: "memory"); }
template <int N> __device__ __forceinline__ void wg_wait() { asm volatile("wgmma.wait_group.sync.aligned %0;" ::"n"(N) : "memory"); }
#define R8(c, o) "+f"(c[o]), "+f"(c[o + 1]), "+f"(c[o + 2]), "+f"(c[o + 3]), "+f"(c[o + 4]), "+f"(c[o + 5]), "+f"(c[o + 6]), "+f"(c[o + 7])
#define R32(c, o) R8(c, o), R8(c, o + 8), R8(c, o + 16), R8(c, o + 24)
#define S32A "%0,%1,%2,%3,%4,%5,%6,%7,%8,%9,%10,%11,%12,%13,%14,%15,%16,%17,%18,%19,%20,%21,%22,%23,%24,%25,%26,%27,%28,%29,%30,%31"
#define S32B ",%32,%33,%34,%35,%36,%37,%38,%39,%40,%41,%42,%43,%44,%45,%46,%47,%48,%49,%50,%51,%52,%53,%54,%55,%56,%57,%58,%59,%60,%61,%62,%63"
#define S32C ",%64,%65,%66,%67,%68,%69,%70,%71,%72,%73,%74,%75,%76,%77,%78,%79,%80,%81,%82,%83,%84,%85,%86,%87,%88,%89,%90,%91,%92,%93,%94,%95"
#define S32D ",%96,%97,%98,%99,%100,%101,%102,%103,%104,%105,%106,%107,%108,%109,%110,%111,%112,%113,%114,%115,%116,%117,%118,%119,%120,%121,%122,%123,%124,%125,%126,%127"
#define W8(c, o) "=f"(c[o]), "=f"(c[o + 1]), "=f"(c[o + 2]), "=f"(c[o + 3]), "=f"(c[o + 4]), "=f"(c[o + 5]), "=f"(c[o + 6]), "=f"(c[o + 7])
#define W32(c, o) W8(c, o), W8(c, o + 8), W8(c, o + 16), W8(c, o + 24)
template <bool ACC> __device__ __forceinline__ void wgmma256(float* c, uint64_t da, uint64_t db) {
    if (ACC) asm volatile("wgmma.mma_async.sync.aligned.m64n256k16.f32.bf16.bf16 {" S32A S32B S32C S32D "},%128,%129,1,1,1,0,1;"
                          : R32(c, 0), R32(c, 32), R32(c, 64), R32(c, 96) : "l"(da), "l"(db));
    else asm volatile("wgmma.mma_async.sync.aligned.m64n256k16.f32.bf16.bf16 {" S32A S32B S32C S32D "},%128,%129,0,1,1,0,1;"
                      : W32(c, 0), W32(c, 32), W32(c, 64), W32(c, 96) : "l"(da), "l"(db));
}
template <bool ACC> __device__ __forceinline__ void wgmma128r(float* c, const uint4& a, uint64_t db) {
    if (ACC) asm volatile("wgmma.mma_async.sync.aligned.m64n128k16.f32.bf16.bf16 {" S32A S32B "},{%64,%65,%66,%67},%68,1,1,1,1;"
                          : R32(c, 0), R32(c, 32) : "r"(a.x), "r"(a.y), "r"(a.z), "r"(a.w), "l"(db));
    else asm volatile("wgmma.mma_async.sync.aligned.m64n128k16.f32.bf16.bf16 {" S32A S32B "},{%64,%65,%66,%67},%68,0,1,1,1;"
                      : W32(c, 0), W32(c, 32) : "r"(a.x), "r"(a.y), "r"(a.z), "r"(a.w), "l"(db));
}
template <int N> __device__ __forceinline__ void reg_inc() { asm volatile("setmaxnreg.inc.sync.aligned.u32 %0;" ::"n"(N)); }
template <int N> __device__ __forceinline__ void reg_dec() { asm volatile("setmaxnreg.dec.sync.aligned.u32 %0;" ::"n"(N)); }

#define PROF(cond, idx) do {} while (0)
#define CPROF(k) do {} while (0)

constexpr int S_GATE = 232440, S_TAG = 232444, S_XBAR = 232432;
constexpr float SC_LOG2E = 0.08838834764831845f * 1.4426950408889634f;

__device__ __forceinline__ float2 ln_finish(float mean, float var) {
    float sd; asm("sqrt.approx.f32 %0,%1;" : "=f"(sd) : "f"(rbf(rbf(var) + 1e-5f)));
    sd = rbf(sd);
    return make_float2(rbf(mean), sd);
}

__device__ __forceinline__ float2 row_stats512(const uint4* src, int s1, int s2) {
    const int g = (threadIdx.x & 31) >> 2;
    uint4 v[16];
#pragma unroll
    for (int i = 0; i < 16; i++) v[i] = ldcg128(src + (i >> 1) * s1 + (i & 1) * s2);
    float a[4] = {0, 0, 0, 0}, q0[4] = {0, 0, 0, 0}, q1[4] = {0, 0, 0, 0};
#pragma unroll
    for (int i = 0; i < 16; i++) {
        mma16(a, v[i].x, v[i].y, v[i].z, v[i].w, 0x3f803f80u, 0x3f803f80u);
        mma8(q0, v[i].x, v[i].y, v[i].x); mma8(q1, v[i].x, v[i].y, v[i].y);
        mma8(q0, v[i].z, v[i].w, v[i].z); mma8(q1, v[i].z, v[i].w, v[i].w);
    }
    const float sum = a[0] + a[2], sq = (g & 1) ? q0[1] + q1[3] : q0[0] + q1[2];
    return make_float2(sum, sq);
}
__device__ __forceinline__ void x1_stats(int rg, int tag) {
    const int lane = threadIdx.x & 31, g = lane >> 2, c = lane & 3;
    const float2 r = row_stats512(g_xA[0] + (rg >> 4) * 8192 + (rg & 15) * 64 + c * 8 + g, 1024, 32);
    if (c == (g >> 1)) { g_st[0][(rg >> 4) * 2048 + (rg < 32 ? 2 : tag) * 128 + (rg & 15) * 8 + g] = r; g_ln0[rg * 8 + g] = 0; }
    __syncwarp();
    if (lane == 0) red_release(cnt_ptr(C_ST, rg >> 4), 1);
}
__global__ void stats_kernel() { x1_stats(blockIdx.x * 4 + (threadIdx.x >> 5), (g_gate[0] / (4 * NCL)) & 1); }

#define NT 9
#define RH 104
#define RW0 200
#define NPD 9
#define NTO 13
#define DP1 6
#define GPW 0
#define GPJ 0
#define PACE 2
#define BKA 0
#define GSE 4
#define EARLY 4
#define PFD 0
#define PFB 0
#define G2S 7
#define STO 1
#define G2I 2
#define VE 4
#define VF 8
constexpr int TILE = 20480;
constexpr int R_WV = 0, R_WO = 65536, R_T = 131072, R_M = R_T + 2 * TILE  , R_LOC = R_M + 8192  ,
              R_REM = R_LOC + 12288  , R_O = R_REM + 24576  , R_SX = R_O + 4096  ,
              R_IL = R_SX + 10240  , R_BAR = 231936, R_Z = R_BAR + 128  , R_STQ = 0, R_STK = 65536, R_STV = 131072;
static_assert(R_IL + 512 <= R_BAR && R_BAR + 256 <= S_XBAR, "smem map");
enum { RB_INIT = 0, RB_MB = 1, RB_V = 4  , RB_QK = 8  , RB_T = 12  , RB_N = 16 };
enum { NB_MF = 1  , NB_LOC = 3  , NB_PAIR = 5  , NB_O = 9  , NB_XG = 11  , NB_W = 13 };
__device__ __forceinline__ uint32_t clk32() { return (uint32_t)clock64(); }

__device__ __forceinline__ char* acc_base() { return (char*)(((size_t)g_acc + 131071) & ~(size_t)131071); }
__device__ __forceinline__ uint32_t acc_slice(uint32_t s6) { return (s6 & 1) * 256 + (s6 >> 1) * 1024; }
__device__ __forceinline__ uint32_t acc_main(uint32_t rank, uint32_t tid) { return acc_slice(rank * 32 + (tid >> 3)) + (tid & 7) * 16; }
__device__ __forceinline__ uint32_t acc_extra(uint32_t rank, uint32_t tid) { return 65536 + acc_slice(((tid >> 5) & 1) + rank * 4 + (tid >> 6) * 8) + (tid & 31) * 4; }
__device__ __forceinline__ uint32_t acc_slot(uint32_t s) { return (s & 1) * 128 + (s & 2) * 256; }
__device__ __forceinline__ void acc_init(const __nv_bfloat16* mem0, int i) {
    const uint32_t tid = i & 255, rank = (i >> 8) & 1, slot = (i >> 9) & 3, X = i >> 11;
    uint32_t v[5] = {0, 0, 0, 0, 0};
    if (slot == 3) {
        const uint16_t* m = (const uint16_t*)mem0 + (tid & 3) * 1024 + rank * 256 + (tid >> 5) * 32 + ((tid >> 2) & 7);
#pragma unroll
        for (int k = 0; k < 4; k++) v[k] = __ldg(m + k * 8) | ((uint32_t)__ldg(m + k * 8 + 512) << 16);
        v[4] = (v[3] >> 16) | 0x42000000u; v[3] = (v[3] & 0xffff) | 0x42000000u;
    }
    *(uint4*)(acc_base() + X * 32768 + acc_slot(slot) + acc_main(rank, tid)) = make_uint4(v[0], v[1], v[2], v[3]);
    *(uint32_t*)(acc_base() + X * 1024 + acc_slot(slot) + acc_extra(rank, tid)) = v[4];
}
__global__ void acc_init_kernel(const __nv_bfloat16* mem0) { acc_init(mem0, blockIdx.x * 256 + threadIdx.x); }

struct RecW { uint32_t am, ae, ah, dp, lp, lpw, vo, sb, bar, zero, ts, tn; };
__device__ __forceinline__ uint32_t vadd(uint32_t a, uint32_t b) { uint32_t d; asm volatile("add.u32 %0,%1,%2;" : "=r"(d) : "r"(a), "r"(b)); return d; }
__device__ __forceinline__ uint32_t vshr(uint32_t a, int n) { uint32_t d; asm volatile("shr.u32 %0,%1,%2;" : "=r"(d) : "r"(a), "r"(n)); return d; }
__device__ __forceinline__ uint64_t gptr(uint32_t lo, uint32_t hi) { uint64_t d; asm("mov.b64 %0,{%1,%2};" : "=l"(d) : "r"(lo), "r"(hi)); return d; }
__device__ __forceinline__ void sfence(uint32_t zero) { asm volatile("{.reg .pred p; setp.ne.u32 p,%0,0; @p exit;}" ::"r"(zero) : "memory"); }
#define SF sfence(k.zero)
#define TS(i) do {} while (0)
#define TSN(i) do {} while (0)
#define TSET(it, slot) do {} while (0)
struct Gat { uint32_t x, y, z, w, e; };
template <int X>
__device__ __forceinline__ void gat_issue(Gat& g, const RecW& k, int s, uint32_t dep) {
    const uint32_t o = acc_slot(s + 3) + dep;
    asm volatile("{.reg .b128 t; ld.relaxed.gpu.global.b128 t,[%5+%7]; mov.b128 {%0,%1,%2,%3},t; ld.relaxed.gpu.global.u32 %4,[%6+%8];}"
                 : "=r"(g.x), "=r"(g.y), "=r"(g.z), "=r"(g.w), "=r"(g.e) : "l"(gptr(k.am + o, k.ah)), "l"(gptr(k.ae + o, k.ah)), "n"(X * 32768), "n"(X * 1024) : "memory");
}
template <int X>
__device__ __forceinline__ bool gat_store(const Gat& g, const RecW& k) {
    uint32_t c;
    asm volatile("prmt.b32 %0,%1,%2,0x7632;" : "=r"(c) : "r"(g.w), "r"(g.e));
    SF;
    asm volatile("{.reg .b32 t; prmt.b32 t,%4,%6,0x5410; stmatrix.sync.aligned.m8n8.x4.trans.shared.b16 [%0+%5],{%1,%2,%3,t};}" ::"r"(k.lpw), "r"(g.x), "r"(g.y), "r"(g.z), "r"(g.w), "n"(R_M + X * 4096), "r"(g.e) : "memory");
    return __all_sync(0xffffffffu, c == 0x42004200u);
}
template <int X>
__device__ __forceinline__ void gat_finish(bool ok, const RecW& k, int s) {
    if (!ok) {
        int n = s;
        while (true) {
            Gat g;
            gat_issue<X>(g, k, n, 0);
            if (gat_store<X>(g, k)) break;
            n += 4;
            if (n > 8000000) __trap();
        }
    }
}
__device__ __forceinline__ uint4 lds128o(uint32_t a, int o) { uint4 v; asm volatile("{.reg .b32 t; add.u32 t,%4,%5; ld.shared.v4.u32 {%0,%1,%2,%3},[t];}" : "=r"(v.x), "=r"(v.y), "=r"(v.z), "=r"(v.w) : "r"(a), "r"(o) : "memory"); return v; }
__device__ __forceinline__ uint4 ldsm4o(uint32_t a, int o) { uint4 v; asm volatile("{.reg .b32 t; add.u32 t,%4,%5; ldmatrix.sync.aligned.m8n8.x4.shared.b16 {%0,%1,%2,%3},[t];}" : "=r"(v.x), "=r"(v.y), "=r"(v.z), "=r"(v.w) : "r"(a), "r"(o) : "memory"); return v; }
__device__ __forceinline__ uint4 ldsm4to(uint32_t a, int o) { uint4 v; asm volatile("{.reg .b32 t; add.u32 t,%4,%5; ldmatrix.sync.aligned.m8n8.x4.trans.shared.b16 {%0,%1,%2,%3},[t];}" : "=r"(v.x), "=r"(v.y), "=r"(v.z), "=r"(v.w) : "r"(a), "r"(o) : "memory"); return v; }
__device__ __forceinline__ uint2 lds64o(uint32_t a, int o) { uint2 v; asm volatile("{.reg .b32 t; add.u32 t,%2,%3; ld.shared.v2.u32 {%0,%1},[t];}" : "=r"(v.x), "=r"(v.y) : "r"(a), "r"(o) : "memory"); return v; }
__device__ __forceinline__ void sts128o(uint32_t a, int o, uint32_t x, uint32_t y, uint32_t z, uint32_t w) { asm volatile("{.reg .b32 t; add.u32 t,%0,%5; st.shared.v4.u32 [t],{%1,%2,%3,%4};}" ::"r"(a), "r"(x), "r"(y), "r"(z), "r"(w), "r"(o) : "memory"); }
__device__ __forceinline__ void sts64o(uint32_t a, int o, uint32_t x, uint32_t y) { asm volatile("{.reg .b32 t; add.u32 t,%0,%3; st.shared.v2.u32 [t],{%1,%2};}" ::"r"(a), "r"(x), "r"(y), "r"(o) : "memory"); }
__device__ __forceinline__ uint32_t vxor(uint32_t a, uint32_t b) { uint32_t d; asm volatile("xor.b32 %0,%1,%2;" : "=r"(d) : "r"(a), "r"(b)); return d; }
#define WLD(base, i) wt[i] = lds128o(k.lpw, (base) + (i) * 4096)
template <int PASS, int X, int NP>
__device__ __forceinline__ void rec_qkv(const RecW& k, int s, const uint32_t (*wq)[4], const uint32_t (*wk)[4], uint4* wt, Gat& g2, int s2, bool& ok2, uint4& mf) {
    constexpr bool BWD = PASS == 2, DIRECT = !(BKA && PASS == 1);
    float aq[4] = {0, 0, 0, 0}, ak[4] = {0, 0, 0, 0}, av[4] = {0, 0, 0, 0};
    constexpr int ma = R_M + X * 4096;
    if (BWD && GSE == 4) { TS(1); mbar_wait(k.sb + R_BAR + RB_MB * 8, s & 1); mf = ldsm4o(k.lp, ma + 7 * 512); TS(2); }
    if (!BWD || GSE < 2) {
        if (BWD) { TS(1); gat_finish<1>(GSE ? ok2 : gat_store<1>(g2, k), k, s); }
        bar_sync(NB_MF + X, 256);
        mf = ldsm4o(k.lp, ma + (BWD ? 7 : 0) * 512);
        if (BWD) TS(2); else { TS(0); TSN(13); }
    }
#pragma unroll
    for (int ii = 0; ii < 8; ii++) {
        const int i = BWD ? 7 - ii : ii;
        const uint4 m = mf;
        if (ii < 7) mf = ldsm4o(k.lp, ma + (BWD ? i - 1 : i + 1) * 512);
        if (PASS == 1 && ii == G2I) gat_issue<1>(g2, k, s2, 0);
        if (PASS == 1 && GSE == 2 && ii == 7) { TS(1); gat_finish<1>(gat_store<1>(g2, k), k, s2); }
        if (PASS == 1 && GSE == 4 && ii == G2S) { gat_finish<1>(gat_store<1>(g2, k), k, s2); mbar_arrive1(k.sb + R_BAR + RB_MB * 8); }
        SF;
#pragma unroll
        for (int hh = 0; hh < 2; hh++) {
            const int h = BWD ? 1 - hh : hh, ks = 2 * i + h;
            const uint32_t b0 = h ? m.z : m.x, b1 = h ? m.w : m.y;
            mma16(aq, wq[ks][0], wq[ks][1], wq[ks][2], wq[ks][3], b0, b1);
            mma16(ak, wk[ks][0], wk[ks][1], wk[ks][2], wk[ks][3], b0, b1);
            SF;
            mma16(av, wt[ks].x, wt[ks].y, wt[ks].z, wt[ks].w, b0, b1);
            SF;
            if (!BWD && ks + NP < 16) WLD(R_WV, ks + NP < 16 ? ks + NP : 0);
            if (BWD && ks >= NT) WLD(R_WV, ks >= NT ? ks - NT : 0);
            SF;
        }
    }
    if (PASS == 1 && GSE == 1) { ok2 = gat_store<1>(g2, k); SF; }
    if (PASS == 1 && GSE == 3) { TS(1); gat_finish<1>(gat_store<1>(g2, k), k, s2); }
    if (PASS == 1 && (GSE == 2 || GSE == 3)) { bar_sync(NB_MF + 1, 256); mf = ldsm4o(k.lp, ma + 4096 + 7 * 512); TS(2); SF; }
    const uint32_t ra = vadd(k.lpw, k.dp + R_REM + (X * 2 + (s & 1)) * 6144), va = ((vshr(k.lp, 7) & 1) * 48 ^ k.lp ^ (k.vo & 64)) + (k.vo & ~64u);
    const uint32_t x0 = movm(pack2(aq[0], aq[1])), x1 = movm(pack2(aq[2], aq[3])), x2 = movm(pack2(ak[0], ak[1])), x3 = movm(pack2(ak[2], ak[3]));
    SF;
    asm volatile("stmatrix.sync.aligned.m8n8.x2.shared.b16 [%0+%3],{%1,%2};" ::"r"(va), "r"(pack2(av[0], av[1])), "r"(pack2(av[2], av[3])), "n"(R_LOC + X * 6144) : "memory");
    SF;
    if (STO && DIRECT) st_async4(ra, x0, x1, x2, x3, k.bar + X * 16);
    asm volatile("st.shared.v4.u32 [%0+%5],{%1,%2,%3,%4};" ::"r"(k.lpw), "r"(x0), "r"(x1), "r"(x2), "r"(x3), "n"(R_LOC + X * 6144) : "memory");
    bar_arrive(NB_LOC + X, 320);
    if (!STO && DIRECT) st_async4(ra, x0, x1, x2, x3, k.bar + X * 16);
    SF;
    TS(BWD ? 4 : 3);
}
template <bool BWD, int X>
__device__ __forceinline__ void rec_out(const RecW& k, int s, uint4* wt, Gat& g, int s1) {
    if (BWD) { WLD(R_WO, 17 - NTO); WLD(R_WO, 16 - NTO); }
    TS(BWD ? 8 : 5);
    bar_sync(NB_O + X, 320);
    float r0[4] = {0, 0, 0, 0}, r1[4] = {0, 0, 0, 0};
    constexpr int oa = R_O + X * 2048;
    uint4 bn = lds128o(k.lp, oa + (BWD ? 3 : 0) * 512);
    TS(BWD ? 9 : 6);
    uint2 il;
    uint64_t pm, pe;
#pragma unroll
    for (int ii = 0; ii < 4; ii++) {
        const int i = BWD ? 3 - ii : ii;
        const uint4 b = bn;
        if (ii < 3) bn = lds128o(k.lp, oa + (BWD ? i - 1 : i + 1) * 512);
        else { asm volatile("ld.shared.v2.u32 {%0,%1},[%2+%3];" : "=r"(il.x), "=r"(il.y) : "r"((vshr(k.ae, 2) & 3) * 8 + k.sb), "n"(R_IL + X * 32) : "memory"); pm = gptr(vadd(k.am, acc_slot(s)), k.ah); pe = gptr(vadd(k.ae, acc_slot(s)), k.ah); }
        SF;
        if (BWD && EARLY == ii + 1) { gat_issue<0>(g, k, s1 + 1, 0); SF; }
#pragma unroll
        for (int nn = 0; nn < 4; nn++) {
            const int n = BWD ? 3 - nn : nn, f = 4 * i + n, nx = BWD ? f - NTO + 2 : f + NTO - 2;
            mma16((n & 1) ? r1 : r0, wt[f].x, wt[f].y, wt[f].z, wt[f].w, n >> 1 ? b.z : b.x, n >> 1 ? b.w : b.y);
            SF;
            if (ii * 4 + nn >= 2 && nx >= 0 && nx < 16) WLD(R_WO, nx & 15);
            SF;
        }
    }
    const float i0 = __uint_as_float(il.x), i1 = __uint_as_float(il.y);
    asm volatile("red.relaxed.gpu.global.add.noftz.v4.bf16x2 [%0+%5],{%1,%2,%3,%4};" ::"l"(pm),
                 "r"(pack2(r0[0] * i0, r0[1] * i1)), "r"(pack2(r0[2] * i0, r0[3] * i1)), "r"(pack2(r1[0] * i0, r1[1] * i1)), "r"(pack2(r1[2] * i0, 1.f)), "n"(X * 32768) : "memory");
    asm volatile("red.relaxed.gpu.global.add.noftz.bf16x2 [%0+%2],%1;" ::"l"(pe), "r"(pack2(r1[3] * i1, 1.f)), "n"(X * 1024) : "memory");
    bar_arrive(NB_XG + X, 320);
    SF;
    TS(BWD ? 10 : 7);
}
__device__ __forceinline__ uint32_t pause(uint32_t v, int n) {
#pragma unroll
    for (int i = 0; i < n; i++) asm volatile("shfl.sync.bfly.b32 %0,%0,0,0x1f,0xffffffff;" : "+r"(v));
    return v;
}
template <bool DUAL, int X>
__device__ __forceinline__ void rec_step(const RecW& k, int s, int s2, const uint32_t (*wq)[4], const uint32_t (*wk)[4], uint4* wt) {
    constexpr int NP = NPD;
    uint4 wo[16];
    Gat g;
    bool ok2;
    uint4 mf;
    rec_qkv<DUAL ? 1 : 0, X, NP>(k, s, wq, wk, wt, g, s2, ok2, mf);
    if (DUAL) rec_qkv<2, 1, NP>(k, s2, wq, wk, wt, g, s2, ok2, mf);
    uint32_t wa = k.lpw;
#pragma unroll
    for (int i = 0; i < NTO; i++) {
        wo[i] = lds128o(wa, R_WO + i * 4096);
        if (i % PACE == PACE - 1) wa = k.lpw + (wo[i].x & k.zero);
        SF;
    }
    rec_out<false, X>(k, s, wo, g, s);
    if (DUAL) { rec_out<true, 1>(k, s2, wo, g, s); if (!EARLY) gat_issue<0>(g, k, s + 1, 0); SF; }
#pragma unroll
    for (int i = 0; i < NP; i++) { WLD(R_WV, i); SF; }
    if (!DUAL) gat_issue<X>(g, k, s + 1, pause(wt[NP - 1].x & k.zero, DP1));
    TS(12);
    gat_finish<X>(gat_store<X>(g, k), k, s + 1);
    TS(11);
}

__device__ __forceinline__ void rec_fetch(const CUtensorMap* tm, uint32_t dst, int x, int y, int nx, uint32_t bar) {
#pragma unroll 1
    for (int j = 0; j < 8; j++) tma2d(dst + j * 8192, tm, x + (j / (8 / nx)) * 64, y + (j % (8 / nx)) * 64, bar);
}
__device__ __forceinline__ void rec_weights(const Params& p, uint32_t sb, int head, uint32_t rank, int w) {
    const int lane = threadIdx.x & 31, t = w & 3, WG = w >> 2;
    uint32_t wq[16][4], wk[16][4];
    const uint32_t rowo = (((lane >> 4) << 3) + (lane & 7)) * 128;
    const uint32_t woff = sb + WG * 32768 + rowo + (((2 * t + ((lane >> 3) & 1)) ^ (lane & 7)) << 4);
    const uint32_t qoff = sb + ((w & 1) ? R_STK : R_STQ) + WG * 32768 + rowo + (((2 * (t & 2) + ((lane >> 3) & 1)) ^ (lane & 7)) << 4);
    const uint32_t lw = sb + (lane ^ (lane >> 3)) * 16;
    PROF(threadIdx.x == 0, 3501);
    PROF(threadIdx.x == 0, 3502);
    mbar_wait(sb + R_BAR + RB_INIT * 8, 0);
    PROF(threadIdx.x == 0, 3503);
#pragma unroll
    for (int ks = 0; ks < 16; ks++) {
        uint4 a = ldsm4t(qoff + ks * 2048), b = ldsm4t((qoff ^ 32) + ks * 2048);
        wq[ks][0] = a.x; wq[ks][1] = a.y; wq[ks][2] = a.z; wq[ks][3] = a.w;
        wk[ks][0] = b.x; wk[ks][1] = b.y; wk[ks][2] = b.z; wk[ks][3] = b.w;
    }
    bar_sync(NB_W, 256);
#pragma unroll 4
    for (int ks = 0; ks < 16; ks++) { const uint4 a = ldsm4t(woff + R_STV + ks * 2048); sts128(lw + w * 512 + R_WV + ks * 4096, a.x, a.y, a.z, a.w); }
    bar_sync(NB_W, 256);
    if (threadIdx.x == 0) {
        mbar_expect(sb + R_BAR + RB_INIT * 8, 65536);
        rec_fetch(&p.tm[4], sb + R_STV, rank * 256, head * 128, 4, sb + R_BAR + RB_INIT * 8);
    }
    __syncwarp();
    mbar_wait(sb + R_BAR + RB_INIT * 8, 1);
#pragma unroll 4
    for (int f = 0; f < 16; f++) {
        const uint4 a = ldsm4t(sb + R_STV + (w >> 1) * 16384 + (f >> 1) * 2048 + rowo + ((((w & 1) * 4 + (f & 1) * 2 + ((lane >> 3) & 1)) ^ (lane & 7)) << 4));
        sts128(lw + w * 512 + R_WO + f * 4096, a.x, a.y, a.z, a.w);
    }
    PROF(threadIdx.x == 0, 3504);
    __syncthreads();
    cluster_sync();
    PROF(threadIdx.x == 0, 3505);
    RecW k;
    k.am = __shfl_sync(0xffffffffu, (uint32_t)(size_t)acc_base() + acc_main(rank, threadIdx.x), lane);
    k.ae = __shfl_sync(0xffffffffu, (uint32_t)(size_t)acc_base() + acc_extra(rank, threadIdx.x), lane);
    k.ah = (uint32_t)((size_t)acc_base() >> 32);
    k.sb = sb; k.zero = p.zero;

    k.dp = mapa(sb, rank ^ 1) - sb;
    k.lp = __shfl_sync(0xffffffffu, lw, lane);
    k.lpw = __shfl_sync(0xffffffffu, lw + w * 512, lane);
    k.vo = 4096 + w * 256 + (w & 1) * 64;
    k.bar = sb + k.dp + R_BAR + (RB_QK + WG) * 8;
    int it = 0;
    uint4 wt[16];
#pragma unroll
    for (int i = 0; i < NPD; i++) WLD(R_WV, i);
    gat_finish<0>(false, k, 0);
#pragma unroll 1
    for (; it < min(p.b1, p.e0); it++) { TSET(it, w == GPW ? 0 : 3); rec_step<false, 0>(k, it, it, wq, wk, wt); }
#pragma unroll 1
    for (; it < p.e0; it++) { TSET(it, w == GPW ? 0 : 3); rec_step<true, 0>(k, it, it - p.b1, wq, wk, wt); }
    if (it < p.nit) gat_finish<1>(false, k, it - p.b1);
#pragma unroll 1
    for (; it < p.nit; it++) { TSET(it, w == GPW ? 0 : 3); rec_step<false, 1>(k, it - p.b1, it - p.b1, wq, wk, wt); }
}

__device__ __forceinline__ void mma16_top(float* c, uint32_t a0, uint32_t a2, uint32_t b0, uint32_t b1) {
    asm volatile("{.reg .b32 j; mma.sync.aligned.m16n8k16.row.col.f32.bf16.bf16.f32 {%0,%1,%2,%3},{%4,j,%5,j},{%6,%7},{%0,%1,%2,%3};}"
                 : "+f"(c[0]), "+f"(c[1]), "+f"(c[2]), "+f"(c[3]) : "r"(a0), "r"(a2), "r"(b0), "r"(b1));
}
__device__ __forceinline__ void rec_load_tile(uint32_t sb, int X, int j, int s, int head, uint32_t rank) {
    const uint32_t bar = sb + R_BAR + (RB_T + X * 2 + j) * 8;
    mbar_expect1(bar, j ? 4096 : 16384);
    bulk_g2s1(sb + R_T + X * TILE + j * 16384, g_qkv[X] + (size_t)(s * 32 + head) * 1536 + (j ? rank * 256 : 512), j ? 4096 : 16384, bar, POL_LAST);
}
__device__ __forceinline__ bool chunk_ready(int X, int j, int s) {
    unsigned v;
    asm volatile("ld.relaxed.gpu.global.u32 %0,[%1];" : "=r"(v) : "l"(cnt_ptr(C_QKV0 + X, (s >> 2) + j * 16)) : "memory");
    return __all_sync(0xffffffffu, v >= (256 >> j));
}
__device__ __forceinline__ uint4 hadd4(uint4 a, uint4 b) { return make_uint4(hadd2(a.x, b.x), hadd2(a.y, b.y), hadd2(a.z, b.z), hadd2(a.w, b.w)); }
struct RecH { uint32_t lw, lm, lq, lv, lu, sa, sp, sb, zero, ts, tn; };
__device__ __forceinline__ void rec_publish(int X, int s) {
    asm volatile("{.reg .pred p; cp.async.bulk.wait_group 0; elect.sync _|p,0xffffffff; @p red.relaxed.gpu.global.add.u32 [%0],4;}" ::"l"(cnt_ptr(C_O0 + X, s >> 2)) : "memory");
}
__device__ __forceinline__ void rec_mattn(const RecH& k, uint32_t dp, int X, int j, int s, bool qk, uint4 (*V)[4], uint4* vm) {
    const uint32_t sb = k.sb, to = R_T + X * TILE + j * 2048, lo = R_LOC + X * 6144, ro = R_REM + (X * 2 + (s & 1)) * 6144;
    const uint32_t bar = sb + R_BAR + (X * 2 + j) * 8;
    uint4 K[2][4];
    mbar_wait(sb + R_BAR + (RB_T + X * 2) * 8, s & 1);
    TS(1);
#pragma unroll
    for (int i = 0; i < 8; i++) K[i >> 2][i & 3] = ldsm4o(k.lm, (to + (i >> 2) * 1024 + ((i >> 1) & 1) * 4096 + (i & 1) * 512));
    asm volatile("cp.async.bulk.wait_group 0;" ::: "memory");
    bar_sync(NB_LOC + X, 320);
    fence_async_smem();
    if (qk) asm volatile("{.reg .pred p; elect.sync _|p,0xffffffff; @p cp.async.bulk.shared::cluster.shared::cta.mbarrier::complete_tx::bytes [%0],[%1],2048,[%2];}"
                         ::"r"(sb + dp + ro + j * 2048), "r"(sb + lo + j * 2048), "r"(bar + dp + RB_QK * 8) : "memory");
    asm volatile("{.reg .pred p; elect.sync _|p,0xffffffff; @p cp.async.bulk.shared::cluster.shared::cta.mbarrier::complete_tx::bytes [%0],[%1],1024,[%2];}"
                 ::"r"(sb + dp + ro + 4096 + j * 1024), "r"(sb + lo + 4096 + j * 1024), "r"(bar + dp + RB_V * 8) : "memory");
    uint4 u[4];
#pragma unroll
    for (int i = 0; i < 4; i++) u[i] = ldsm4o(k.lm, (lo + j * 2048 + i * 512));
    TS(2);
    mbar_wait(bar + RB_QK * 8, s & 1);
    TS(3);
    float S[5][4];
#pragma unroll
    for (int i = 0; i < 5; i++) S[i][0] = S[i][1] = S[i][2] = S[i][3] = 0;
    {
        uint4 r[4];
#pragma unroll
        for (int i = 0; i < 4; i++) r[i] = ldsm4o(k.lm, (ro + j * 2048 + i * 512));
        SF;
#pragma unroll
        for (int e = 0; e < 2; e++) {
            uint4& km = u[2 * e + 1];
            const uint32_t q0 = hadd2(u[2 * e].x, r[2 * e].x), q1 = hadd2(u[2 * e].y, r[2 * e].y);
            mma16_top(S[0], q0, q1, K[e][0].x, K[e][0].y);
            km.x = hadd2(km.x, r[2 * e + 1].x); km.y = hadd2(km.y, r[2 * e + 1].y);
            SF;
            mma16_top(S[1], q0, q1, K[e][1].x, K[e][1].y);
            const uint32_t q2 = hadd2(u[2 * e].z, r[2 * e].z), q3 = hadd2(u[2 * e].w, r[2 * e].w);
            SF;
            mma16_top(S[2], q0, q1, K[e][2].x, K[e][2].y);
            km.z = hadd2(km.z, r[2 * e + 1].z); km.w = hadd2(km.w, r[2 * e + 1].w);
            SF;
            mma16_top(S[3], q0, q1, K[e][3].x, K[e][3].y);
            mma16_top(S[4], q0, q1, km.x, km.y);
            SF;
#pragma unroll
            for (int i = 0; i < 4; i++) {
                mma16_top(S[i], q2, q3, K[e][i].z, K[e][i].w); SF;
            }
            mma16_top(S[4], q2, q3, km.z, km.w);
            SF;
        }
    }
#define VLD(a, b) _Pragma("unroll") for (int i = (a); i < (b); i++) V[i >> 2][i & 3] = ldsm4to((i & 1) ? lv2 : k.lv, (to + 8192 + (i >> 2) * 4096 + ((i >> 1) & 1) * 1024))
    const uint32_t lv2 = vxor(k.lv, 0x20), lh = vshr(k.lw, 1);
    VLD(0, VE);
    SF;
    const uint32_t sxr = k.sa, sxw = k.sp;
    sts128o(k.lw, sxw, __float_as_uint(S[0][0]), __float_as_uint(S[0][1]), __float_as_uint(S[1][0]), __float_as_uint(S[1][1]));
    SF;
    sts128o(k.lw, (sxw + 512), __float_as_uint(S[2][0]), __float_as_uint(S[2][1]), __float_as_uint(S[3][0]), __float_as_uint(S[3][1]));
    SF;
    sts64o(lh, (sb / 2 + sxw + 1024), __float_as_uint(S[4][0]), __float_as_uint(S[4][1]));
    TS(4);
    bar_sync(NB_PAIR + X, 64);
    {
        const uint4 a = lds128o(k.lw, sxr), b = lds128o(k.lw, (sxr + 512));
        const uint2 c = lds64o(lh, (sb / 2 + sxr + 1024));
        SF;
        VLD(VE, VF);
        SF;
        S[0][0] += __uint_as_float(a.x); S[0][1] += __uint_as_float(a.y); S[1][0] += __uint_as_float(a.z); S[1][1] += __uint_as_float(a.w);
        S[2][0] += __uint_as_float(b.x); S[2][1] += __uint_as_float(b.y); S[3][0] += __uint_as_float(b.z); S[3][1] += __uint_as_float(b.w);
        S[4][0] += __uint_as_float(c.x); S[4][1] += __uint_as_float(c.y);
    }
    float m = fmaxf(fmaxf(fmaxf(S[0][0], S[0][1]), fmaxf(S[1][0], S[1][1])), fmaxf(fmaxf(S[2][0], S[2][1]), fmaxf(S[3][0], S[3][1])));
    m = fmaxf(m, fmaxf(S[4][0], S[4][1]));
    m = fmaxf(m, __shfl_xor_sync(0xffffffffu, m, 1));
    const float m2 = __shfl_xor_sync(0xffffffffu, m, 2);
    SF;
    VLD(VF, 8);
    uint32_t ok;
    asm volatile("{.reg .pred p; mbarrier.test_wait.parity.shared::cta.b64 p,[%1],%2; selp.u32 %0,1,0,p;}" : "=r"(ok) : "r"(bar + RB_V * 8), "r"(s & 1) : "memory");
    uint4 vr0 = ldsm4o(k.lu, (ro + 4096 + j * 1024)), vr1 = ldsm4o(k.lu, (ro + 4608 + j * 1024));
    vm[0] = ldsm4o(k.lu, (lo + 4096 + j * 1024)); vm[1] = ldsm4o(k.lu, (lo + 4608 + j * 1024));
    SF;
    TS(5);
    m = fmaxf(m, m2) * -SC_LOG2E;
    uint32_t P[5];
#pragma unroll
    for (int i = 0; i < 5; i++) P[i] = pack2(ex2(fmaf(S[i][0], SC_LOG2E, m)), ex2(fmaf(S[i][1], SC_LOG2E, m)));
    float o[4][4], l[4] = {0, 0, 0, 0};
    const uint32_t ONE = 0x3f803f80u;
    mma16_top(l, ONE, ONE, P[0], P[1]);
#pragma unroll
    for (int t = 0; t < 4; t++) { o[t][0] = o[t][1] = o[t][2] = o[t][3] = 0; mma16(o[t], V[0][t].x, V[0][t].y, V[0][t].z, V[0][t].w, P[0], P[1]); }
    mma16_top(l, ONE, ONE, P[2], P[3]);
#pragma unroll
    for (int t = 0; t < 4; t++) mma16(o[t], V[1][t].x, V[1][t].y, V[1][t].z, V[1][t].w, P[2], P[3]);
    if (!__all_sync(0xffffffffu, ok)) {
        mbar_wait(bar + RB_V * 8, s & 1);
        vr0 = ldsm4o(k.lu, (ro + 4096 + j * 1024)); vr1 = ldsm4o(k.lu, (ro + 4608 + j * 1024));
    }
    TS(6);
    vm[0] = hadd4(vm[0], vr0); vm[1] = hadd4(vm[1], vr1);
    mma8(l, ONE, ONE, P[4]);
    mma8(o[0], vm[0].x, vm[0].y, P[4]); mma8(o[1], vm[0].z, vm[0].w, P[4]); mma8(o[2], vm[1].x, vm[1].y, P[4]); mma8(o[3], vm[1].z, vm[1].w, P[4]);
    asm volatile("{.reg .pred p; .reg .b32 t; setp.lt.u32 p,%0,%3; add.u32 t,%0,%4; @p st.shared.v2.f32 [t],{%1,%2};}" ::"r"(lh), "f"(rcp(l[0])), "f"(rcp(l[1])), "r"(j ? 0 : sb / 2 + 32), "r"(sb / 2 + R_IL + X * 32) : "memory");
#pragma unroll
    for (int t = 0; t < 4; t += 2)
        asm volatile("{.reg .b32 t; add.u32 t,%0,%5; stmatrix.sync.aligned.m8n8.x4.trans.shared.b16 [t],{%1,%2,%3,%4};}" ::"r"(k.lm),
                     "r"(pack2(o[t][0], o[t][1])), "r"(pack2(o[t][2], o[t][3])), "r"(pack2(o[t + 1][0], o[t + 1][1])), "r"(pack2(o[t + 1][2], o[t + 1][3])), "r"(R_O + X * 2048 + j * 1024 + t * 256) : "memory");
    bar_arrive(NB_O + X, 320);
    PROF(k.lw == sb && j == 0, X * 64 + s);
    TS(7);
#pragma unroll
    for (int e = 0; e < 2; e++) sts128o(k.lw, (ro + j * 2048 + e * 1024), u[2 * e + 1].x, u[2 * e + 1].y, u[2 * e + 1].z, u[2 * e + 1].w);
    mbar_expect1(bar + RB_QK * 8, 2048); mbar_expect1(bar + RB_V * 8, 1024);
}
template <int MT>
__device__ __forceinline__ void rec_xattn(const RecH& k, int X, int j, int s, int head, bool early, const uint4 (*V)[4], const uint4* vmm) {
    constexpr int NTL = 3 + 2 * MT;
    const uint32_t sb = k.sb, to = R_T + X * TILE + j * 2048, ro = R_REM + (X * 2 + (s & 1)) * 6144 + j * 2048;
    const uint32_t sxw = k.sa, sxr = k.sp;
    const uint32_t lq2 = vxor(k.lq, 0x20);
    float S[NTL][4];
#pragma unroll
    for (int i = 0; i < NTL; i++) S[i][0] = S[i][1] = S[i][2] = S[i][3] = 0;
#pragma unroll
    for (int e = 0; e < 2; e++) {
        const uint4 q0 = ldsm4o(k.lq, (to + 16384 + e * 1024)), q1 = ldsm4o(lq2, (to + 16384 + e * 1024));
#pragma unroll
        for (int i = 0; i < NTL; i++) {
            const uint4 kk = i ? ldsm4o(k.lm, (to + e * 1024 + ((i - 1) >> 1) * 4096 + ((i - 1) & 1) * 512)) : lds128o(k.lw, (ro + e * 1024));
            mma16(S[i], q0.x, q0.y, q0.z, q0.w, kk.x, kk.y); mma16(S[i], q1.x, q1.y, q1.z, q1.w, kk.z, kk.w);
        }
    }
#pragma unroll
    for (int i = 0; i < NTL; i++) sts128o(k.lw, (sxw + i * 512), __float_as_uint(S[i][0]), __float_as_uint(S[i][1]), __float_as_uint(S[i][2]), __float_as_uint(S[i][3]));
    SF;
    bar_sync(NB_PAIR + 2 + X, 64);
    TS(9);
    if (early) rec_load_tile(sb, X, j, s + 1, head, MT);
#pragma unroll
    for (int i = 0; i < NTL; i++) {
        const uint4 r = lds128o(k.lw, (sxr + i * 512));
        S[i][0] += __uint_as_float(r.x); S[i][1] += __uint_as_float(r.y); S[i][2] += __uint_as_float(r.z); S[i][3] += __uint_as_float(r.w);
    }
    const int g = vshr(k.lw, 6) & 7, c = (vshr(k.lw, 4) ^ (g >> 1)) & 3;
    const float NEG = -__int_as_float(0x7f800000);
    if (2 * c > g) { S[NTL - 2][0] = NEG; S[NTL - 1][2] = NEG; }
    if (2 * c + 1 > g) { S[NTL - 2][1] = NEG; S[NTL - 1][3] = NEG; }
    float m0 = fmaxf(S[0][0], S[0][1]), m1 = fmaxf(S[0][2], S[0][3]);
#pragma unroll
    for (int i = 1; i < NTL; i++) { if (i < NTL - 1) m0 = fmaxf(m0, fmaxf(S[i][0], S[i][1])); m1 = fmaxf(m1, fmaxf(S[i][2], S[i][3])); }
    m0 = fmaxf(m0, __shfl_xor_sync(0xffffffffu, m0, 1)); m1 = fmaxf(m1, __shfl_xor_sync(0xffffffffu, m1, 1));
    m0 = fmaxf(m0, __shfl_xor_sync(0xffffffffu, m0, 2)); m1 = fmaxf(m1, __shfl_xor_sync(0xffffffffu, m1, 2));
    m0 *= -SC_LOG2E; m1 *= -SC_LOG2E;
    uint32_t P[NTL][2];
#pragma unroll
    for (int i = 0; i < NTL; i++) {
        P[i][0] = i < NTL - 1 ? pack2(ex2(fmaf(S[i][0], SC_LOG2E, m0)), ex2(fmaf(S[i][1], SC_LOG2E, m0))) : 0u;
        P[i][1] = pack2(ex2(fmaf(S[i][2], SC_LOG2E, m1)), ex2(fmaf(S[i][3], SC_LOG2E, m1)));
    }
    float l[4] = {0, 0, 0, 0};
#pragma unroll
    for (int i = 0; i < NTL; i++) mma8(l, P[i][0], P[i][1], 0x3f803f80u);
    const float l0 = rcp(l[0]), l1 = rcp(l[2]);

#pragma unroll
    for (int e = 0; e < 2; e++) {
        const uint4 vm = vmm[e];
        uint32_t u[2][4];
#pragma unroll
        for (int n = 0; n < 4; n++) {
            float a[4] = {0, 0, 0, 0};
#pragma unroll
            for (int m = 0; m <= MT; m++) {
                const uint4 v = V[m][e * 2 + (n >> 1)];
                mma8(a, P[1 + 2 * m][0], P[1 + 2 * m][1], (n & 1) ? v.y : v.x); mma8(a, P[2 + 2 * m][0], P[2 + 2 * m][1], (n & 1) ? v.w : v.z);
            }
            mma8(a, P[0][0], P[0][1], n == 0 ? vm.x : n == 1 ? vm.y : n == 2 ? vm.z : vm.w);
            u[0][n] = pack2(a[0] * l0, a[1] * l0); u[1][n] = pack2(a[2] * l1, a[3] * l1);
        }
        sts128o(k.lw, sxr + e * 512, u[0][0], u[0][1], u[0][2], u[0][3]); sts128o(k.lw, sxr + e * 512 + 1024, u[1][0], u[1][1], u[1][2], u[1][3]);
    }
    TS(10);
}
__device__ __forceinline__ void rec_attn(const Params& p, uint32_t sb, int X, int j, int head, uint32_t rank) {
    const int lane = threadIdx.x & 31;
    RecH k;
    k.lw = __shfl_sync(0xffffffffu, sb + (lane ^ (lane >> 3)) * 16, lane);
    k.lm = __shfl_sync(0xffffffffu, sb + ((lane & 7) * 4 + ((lane >> 3) ^ ((lane & 7) >> 1))) * 16, lane);
    k.lq = __shfl_sync(0xffffffffu, sb + ((lane >> 3) & 1) * 512 + ((lane & 7) * 4 + ((lane >> 4) ^ ((lane & 7) >> 1))) * 16, lane);
    k.lv = __shfl_sync(0xffffffffu, sb + (lane >> 4) * 512 + ((lane & 7) * 4 + (((lane >> 3) & 1) ^ ((lane & 7) >> 1))) * 16, lane);
    k.lu = __shfl_sync(0xffffffffu, sb + ((lane & 6) * 4 + (((lane >> 3) * 2 + (lane & 1)) ^ (lane & 6))) * 16, lane);
    k.sa = __shfl_sync(0xffffffffu, R_SX + (X * 2 + j) * 2560, 0); k.sp = __shfl_sync(0xffffffffu, R_SX + (X * 2 + (j ^ 1)) * 2560, 0);
    k.sb = sb; k.zero = p.zero;
    const uint32_t dp = mapa(sb, rank ^ 1) - sb;
    char* zp = acc_base() + (j ? X * 32768 + acc_main(rank, head * 8) : X * 1024 + acc_extra(rank, head * 8));
    mbar_expect1(sb + R_BAR + (RB_QK + X * 2 + j) * 8, 2048); mbar_expect1(sb + R_BAR + (RB_V + X * 2 + j) * 8, 1024);
    bool early = false;
#pragma unroll 1
    for (int s = 0; s < 64; s++) {
        TSET(X ? s + p.b1 : s, j == GPJ ? 1 + X : 3);
        TS(0);
        if (!early) {
            if (!j) wait_cnt_warp(cnt_ptr(C_QKV0 + X, s >> 2), 256);
            early = !j || chunk_ready(X, 1, s);
            if (early) rec_load_tile(sb, X, j, s, head, rank);
        }
        const bool nxt = s < 63 && ((s & 3) != 3 || chunk_ready(X, j, s + 1));
        if (PFD && nxt && early && (PFB || !X))
            asm volatile("{.reg .pred p; elect.sync _|p,0xffffffff; @p cp.async.bulk.prefetch.L2.global.L2::cache_hint [%0],%1,%2;}"
                         ::"l"(g_qkv[X] + (size_t)((s + 1) * 32 + head) * 1536 + (j ? rank * 256 : 512 + rank * 512)), "r"(j ? 4096 : 8192), "l"(POL_LAST) : "memory");
        uint4 V[2][4], vm[2];
        rec_mattn(k, dp, X, j, s, BKA && !X && s >= p.b1, V, vm);
        if (!early) { wait_cnt_warp(cnt_ptr(C_QKV0 + X, (s >> 2) + 16), 128); rec_load_tile(sb, X, 1, s, head, rank); }
        early = nxt;
        mbar_wait(sb + R_BAR + (RB_T + X * 2 + 1) * 8, s & 1);
        bar_sync(NB_XG + X, 320);
        TS(8);
        if (rank) rec_xattn<1>(k, X, j, s, head, early, V, vm); else rec_xattn<0>(k, X, j, s, head, early, V, vm);
        fence_async_smem();
        __syncwarp();
        asm volatile("{.reg .pred p; elect.sync _|p,0xffffffff;\n"
                     "@p cp.async.bulk.global.shared::cta.bulk_group.L2::cache_hint [%0],[%1],2048,%2;\n"
                     "@p cp.async.bulk.global.shared::cta.bulk_group [%3],[%4],%5;\n"
                     "cp.async.bulk.commit_group;}"
                     ::"l"(g_o[X] + ((s >> 2) * 64 + head * 2 + j) * 1024 + ((s & 3) * 2 + rank) * 128), "r"(sb + k.sp),
                       "l"((X && s < 40) ? POL_LATE : POL_SOON), "l"(zp + acc_slot(s + 2)), "r"(sb + R_Z), "r"(j ? 128 : 32) : "memory");
        if ((s & 3) == 3) rec_publish(X, s);
    }
}

__device__ __forceinline__ void rec_init(const Params& p, uint32_t sb, int head, uint32_t rank) {
    const uint32_t b = sb + R_BAR;
    const int i = threadIdx.x - 320;
    if (i >= 0 && i < RB_N) {
        mbar_init(b + i * 8, i == RB_MB ? 8 : 1);
        asm volatile("fence.mbarrier_init.release.cluster;" ::: "memory");
    }
    if (i == 0) mbar_expect(b + RB_INIT * 8, 196608);
    if (i >= 0 && i < 32) sts32(sb + R_Z + i * 4, 0);
}

#define NSTGN 8
constexpr int NSTG = NSTGN, STG_B = 24576;
#define LAGQ 1
#define LAGH 3
constexpr int NSB = 8;
constexpr int B_OUT = NSTG * STG_B  , B_UT = B_OUT, B_YT = B_UT + 16384, B_SP = B_YT  ,
              B_ST = 229376  , B_BAR = 231936;
static_assert(B_OUT + NSB * 4096 <= B_ST && B_ST + 2048 <= B_BAR && B_YT + 10240 <= B_ST, "smem map");
enum { BB_FULL = 0, BB_EMPTY = 8, BB_SF = 16  , BB_GO = 18, BB_DONE = 20  , BB_IDLE = 22  , BB_N = 30 };
enum { NB_C = 11, NB_WG = 12   };

__device__ __forceinline__ void bulk_init(uint32_t sb) {
    const int i = threadIdx.x - 320;
    if (i >= 0 && i < BB_N) {
        mbar_init(sb + B_BAR + i * 8, (i >= BB_EMPTY && i < BB_EMPTY + NSTG) ? 4 : i >= BB_DONE ? 4 : 1);
        asm volatile("fence.mbarrier_init.release.cluster;" ::: "memory");
    }
}

struct Task { int type, layer, ch, a, b, c, blk; bool pair, dry; };
__device__ __forceinline__ Task task_of(uint32_t tk, uint32_t rank) {
    Task t;
    t.type = tk & 7; t.layer = (tk >> 3) & 1; t.a = (tk >> 8) & 255; t.b = (tk >> 16) & 255; t.c = (tk >> 24) & 127; t.dry = tk >> 31;
    t.pair = t.type <= T_OP && (t.c & 64);
    t.ch = ((tk >> 4) & 15) + (t.pair ? rank : 0);
    t.blk = t.type == T_QKV ? t.a + (t.pair ? 0 : rank) : 192 + (t.pair ? (t.c >> 2) & 4 : rank * 4);
    return t;
}
__device__ __forceinline__ int qkv_blk(const Task& t, int u) {
    const int v = t.blk + (t.pair ? 1 : 2 * t.c) * u;
    return 2 * (v < 64 ? v + 32 : v - 64);
}
__device__ __forceinline__ void bulk_producer(const Params& p, uint32_t sb, int cl, uint32_t rank) {
    int st = 0; uint32_t ph = 1;
    const int tag = __shfl_sync(0xffffffffu, lds32(sb + S_TAG), 0);
    bool gated = false;
#define ACQ(bytes) do { mbar_wait(sb + B_BAR + (BB_EMPTY + st) * 8, ph); mbar_expect1(sb + B_BAR + (BB_FULL + st) * 8, bytes); } while (0)
#define NEXT do { if (++st == NSTG) { st = 0; ph ^= 1; } } while (0)
#pragma unroll 1
    for (int ti = 0; ti < MAXT; ti++) {
        const Task t = task_of(p.task[cl][ti], rank);
        const int layer = t.layer, ch = t.ch;
        if (t.type == T_END) break;
        if (t.type <= T_OP) {
            const bool qkv = t.type == T_QKV;
            const int rg = qkv ? (layer * 16 + ch) * 128 : 4096 + ((layer * 16 + ch) * 64 + t.a) * 16;
            const int nh = qkv ? 16 : 2 * t.b, row = qkv ? 0 : t.a * 64, bytes = qkv ? 16384 : STG_B;
            const unsigned* dep = cnt_ptr(qkv ? (layer ? C_CV : C_ST) : C_O0 + layer, ch);
            const unsigned need = qkv ? (layer ? 32 : ch < 2 ? 0 : 16) : 512;
            const uint64_t pol = qkv ? POL_N : POL_LAST;
            const int blk0 = qkv ? qkv_blk(t, 0) : t.blk;
            const CUtensorMap *tb = &p.t3[t.pair || qkv][blk0 >> 6], *ta = &p.ta[t.pair];
            const uint32_t db = sb + 8192 + (t.pair && !qkv ? rank * 8192 : 0), da = sb + (t.pair ? 0 : rank * 4096);
            const int zb = (blk0 & 63) + (t.pair && !qkv ? rank * 2 : 0), ya = rg + (t.pair ? 0 : rank * 8);
            const uint16_t mb = t.pair ? 3 : 1 << rank, ma = t.pair ? 1 << rank : 3;
            const int skip = t.pair && qkv ? rank ^ 1 : 2;
            int pend = qkv ? 2 : 0;
            bool wait = false;
            if (!t.dry) {
                unsigned v = 0;
                if (gated) asm volatile("ld.relaxed.gpu.global.u32 %0,[%1];" : "=r"(v) : "l"(dep) : "memory");
                wait = !gated || !__all_sync(0xffffffffu, v >= need);
                if (wait) pend = min(nh, gated ? NSTG : 4);
            }
            if (PFC && !qkv && !layer && (t.c & 15) < 8) {
                const int q = (t.c & 15) * 2 + rank;
                asm volatile("{.reg .pred p; elect.sync _|p,0xffffffff; @p cp.async.bulk.prefetch.L2.global [%0],8192; @p cp.async.bulk.prefetch.L2.global [%1],%2;}"
                             ::"l"(g_xA[0] + (ch * 16 + q) * 512), "l"(g_P + q * 16 * 32 * PW), "r"((2 + (ch & 1)) * 32 * PW * 4) : "memory");
            }
#pragma unroll 1
            while (qkv && st) { ACQ(0); NEXT; }
            int h = 0;
            const int s0 = st;
#pragma unroll 1
            for (; h < pend; h++) {
                ACQ(bytes + (qkv && h < 2 ? (layer ? 8192 : 1024) : 0));
                if ((h & 1) != skip) tma3d_mc(db + st * STG_B, tb, row + h * 32, zb, sb + B_BAR + (BB_FULL + st) * 8, mb);
                NEXT;
            }
            if (wait) {
                if (!gated) { wait_cnt_warp(g_gate, lds32(sb + S_GATE)); gated = true; }
                if (need) wait_cnt_warp(dep, need);
            }
#pragma unroll 1
            for (int k = 0; k < pend; k++) {
                const int s2 = s0 + k - (s0 + k >= NSTG ? NSTG : 0);
                if (qkv && k < 2) bulk_g2s1(sb + s2 * STG_B + 16384, g_st[layer] + ch * 2048 + (layer ? k * 1024 : tag * 128), layer ? 8192 : 1024, sb + B_BAR + (BB_FULL + s2) * 8, POL_N);
                tma2d_mc(da + s2 * STG_B, ta, (k & 1) * 256, ya + (k >> 1) * 16, sb + B_BAR + (BB_FULL + s2) * 8, ma, pol);
            }
#pragma unroll 1
            for (; h < nh; h++) {
                ACQ(bytes);
                if ((h & 1) != skip) tma3d_mc(db + st * STG_B, tb, row + h * 32, zb, sb + B_BAR + (BB_FULL + st) * 8, mb);
                tma2d_mc(da + st * STG_B, ta, (h & 1) * 256, ya + (h >> 1) * 16, sb + B_BAR + (BB_FULL + st) * 8, ma, pol);
                NEXT;
            }
#pragma unroll 1
            for (h = 0; h < 4 && !qkv && !layer; h++) { ACQ(0); NEXT; }
            if (qkv) {
#pragma unroll 1
                for (h = 8; h < 8 * t.b; h++) {
                    const int blk = qkv_blk(t, h >> 3);
                    ACQ(16384);
                    if (skip != 0) tma3d_mc(sb + st * STG_B, &p.t3[1][blk >> 6], (h & 7) * 64, blk & 63, sb + B_BAR + (BB_FULL + st) * 8, mb);
                    if (skip != 1) tma3d_mc(sb + st * STG_B + 8192, &p.t3[1][blk >> 6], (h & 7) * 64 + 32, blk & 63, sb + B_BAR + (BB_FULL + st) * 8, mb);
                    NEXT;
                }
            }
        } else if (t.type == T_CV) {
            const int q = t.a + rank;
            if (!gated && !t.dry) { wait_cnt_warp(g_gate, lds32(sb + S_GATE)); gated = true; }
            if (layer) {
                wait_cnt_warp(cnt_ptr(C_U, ch - 2), 32);
#pragma unroll 1
                for (int j = ch + 1; j >= 2; j--) {
                    ACQ(16 * PW * 4 + (j > 2 ? 4096 : 0));
                    bulk_g2s1(sb + st * STG_B, g_P + (((q >> 1) * 16 + j) * 2 + (q & 1)) * 16 * PW, 16 * PW * 4, sb + B_BAR + (BB_FULL + st) * 8, POL_N);
                    if (j > 2) bulk_g2s1(sb + st * STG_B + 12288, g_u + (((q >> 1) * 16 + ch + 1 - j) * 2 + (q & 1)) * 256, 4096, sb + B_BAR + (BB_FULL + st) * 8, POL_N);
                    NEXT;
                }
            } else {
#pragma unroll 1
                for (int j = min(ch, 1 + (ch & 1)); j >= 0; j--) {
                    if (j == 0 && ch >= 2) {
                        if (!t.dry) wait_cnt_warp(cnt_ptr(C_H, ch & ~1), 64);
#pragma unroll 1
                        for (int i = 0; i < ((ch & 1) || ch == 2 ? 1 : 2); i++) {
                            ACQ(16384);
                            bulk_g2s1(sb + st * STG_B, g_carry[i] + (ch * 16 + q) * 1024, 16384, sb + B_BAR + (BB_FULL + st) * 8, POL_LAST);
                            NEXT;
                        }
                    }
                    ACQ(32 * PW * 4);
                    bulk_g2s1(sb + st * STG_B, g_P + (q * 16 + j) * 32 * PW, 32 * PW * 4, sb + B_BAR + (BB_FULL + st) * 8, POL_N);
                    NEXT;
                }
            }
        }
    }
}

__device__ __forceinline__ uint4* qkv_dst(int layer, int ch, int w, int blk);
__device__ __forceinline__ uint4* op_dst(int layer, int ch, int slot, int w, uint32_t rank);
__device__ __forceinline__ uint64_t out_pol(int type, int layer, int ch) { return (type == T_QKV ? (!layer && ch > 1) : (layer && ch < 10)) ? POL_LATE : POL_SOON; }
__device__ __forceinline__ void bulk_release(const Params& p, uint32_t sb, int cl, uint32_t rank, int wg) {
    int nd = 0;
    for (int ti = 0; ti < MAXT; ti++) {
        const Task t = task_of(p.task[cl][ti], rank);
        const int type = t.type, layer = t.layer, ch = t.ch;
        if (type == T_END) break;
        if (type == T_FIN || (type == T_OP && (t.c & 32))) continue;
        if (type == T_OP && !layer) {
            mbar_wait(sb + B_BAR + (BB_DONE + wg) * 8, nd & 1);
            nd++;
            const int s0 = __shfl_sync(0xffffffffu, lds32(sb + B_ST + wg * 4), 0) + wg * 2;
            fence_async_smem();
#pragma unroll 1
            for (int w = 0; w < 4; w++)
                asm volatile("{.reg .pred p; elect.sync _|p,0xffffffff; @p cp.async.bulk.global.shared::cta.bulk_group.L2::cache_hint [%0],[%1],8192,%2;}"
                             ::"l"(op_dst(0, ch, t.c & 15, wg * 4 + w, rank)), "r"(sb + ((s0 + (w >> 1)) & (NSTG - 1)) * STG_B + (w & 1) * 8192), "l"(POL_SOON) : "memory");
            mbar_arrive1(sb + B_BAR + (BB_SF + wg) * 8);
            asm volatile("{.reg .pred p; cp.async.bulk.commit_group; cp.async.bulk.wait_group 0; elect.sync _|p,0xffffffff; @p red.relaxed.gpu.global.add.u32 [%0],1;}"
                         ::"l"(cnt_ptr(C_OP0 + rank * 2 + wg, ch)) : "memory");
#pragma unroll 1
            for (int i = 0; i < 8; i++) mbar_arrive1_cluster(mapa(sb + B_BAR + (BB_EMPTY + ((s0 + (i >> 2)) & (NSTG - 1))) * 8, i & 1));
            continue;
        }
#pragma unroll 1
        for (int u = 0; u < (type == T_QKV ? t.b : 1); u++) {
            const int blk = qkv_blk(t, u);
            unsigned* cnt = cnt_ptr(type == T_QKV ? C_QKV0 + layer : type == T_OP ? C_OP1 : layer ? C_H : C_CV, ch + (type == T_QKV && blk < 64 ? 16 : 0));
            const uint4* dst = type == T_QKV ? qkv_dst(layer, ch, wg * 4, blk) : op_dst(1, ch, t.c & 15, wg * 4, (t.blk >> 2) & 1) + 256;
            mbar_wait(sb + B_BAR + (BB_DONE + wg) * 8, nd & 1);
            nd++;
            if (type != T_CV) {
                fence_async_smem();
#pragma unroll
                for (int w = 0; w < 4; w++)
                    asm volatile("{.reg .pred p; elect.sync _|p,0xffffffff; @p cp.async.bulk.global.shared::cta.bulk_group.L2::cache_hint [%0],[%1],4096,%2;}"
                                 ::"l"(dst + (type == T_QKV ? (w >> 1) * 49152 + (w & 1) * 256 : w * 1024)), "r"(sb + B_OUT + (wg * 4 + w) * 4096), "l"(out_pol(type, layer, ch)) : "memory");
                asm volatile("cp.async.bulk.commit_group; cp.async.bulk.wait_group 0;" ::: "memory");
            }
            if (type != T_QKV) fence_async();
            if (!t.dry) asm volatile("{.reg .pred p; elect.sync _|p,0xffffffff; @p red.relaxed.gpu.global.add.u32 [%0],%1;}" ::"l"(cnt), "r"(type == T_QKV ? 2 : type == T_OP ? t.b : 1) : "memory");
            if (type == T_CV && !layer && !t.dry) {
                asm volatile("{.reg .pred p; elect.sync _|p,0xffffffff; @p cp.async.bulk.global.shared::cta.bulk_group [%0],[%1],4096;\n"
                             "cp.async.bulk.commit_group; cp.async.bulk.wait_group 0; @p red.relaxed.gpu.global.add.u32 [%2],1;}"
                             ::"l"(g_u + ((t.a + rank) * 16 + ch) * 512 + wg * 256), "r"(sb + B_UT + (ch & 1) * 8192 + wg * 4096), "l"(cnt_ptr(C_U, ch)) : "memory");
            }
            mbar_arrive1(sb + B_BAR + (BB_SF + wg) * 8);
        }
        PROF(wg && (threadIdx.x & 31) == 0, 3600 + ti * 4 + 3);
    }
}

__device__ __forceinline__ void stage_release(uint32_t sb, int w, int st) {
    if (!(w & 2)) mbar_arrive1_cluster(mapa(sb + B_BAR + (BB_EMPTY + st) * 8, w & 1));
}
template <bool ACC>
__device__ __forceinline__ void gemm_run(float* acc, uint32_t sb, int w, int h0, int h1, uint32_t& r0, uint32_t& r1, int& st, uint32_t& ph) {
    const uint64_t da0 = mkdesc(sb + (w >> 2) * 4096, 16, 512, 2), db0 = mkdesc(sb + 8192, 4096, 1024, 1);
    const uint32_t rel0 = mapa(sb + B_BAR + BB_EMPTY * 8, w & 1);
#pragma unroll 1
    for (int h = h0; h < h1; h++) {
        const uint64_t da = da0 + st * (STG_B >> 4), db = db0 + st * (STG_B >> 4);
        mbar_wait(sb + B_BAR + (BB_FULL + st) * 8, ph);
        if (ACC) wg_wait<1>();
        wg_fence();
        wgmma256<ACC>(acc, da, db);
        wgmma256<true>(acc, da + 2, db + 128);
        wg_commit();
        if (ACC) mbar_arrive1_cluster((w == 2 && h == LAGH - 1) ? sb + B_BAR + BB_GO * 8 : r0);
        r0 = r1;
        if (!(w & 2)) r1 = rel0 + st * 8;
        if (++st == NSTG) { st = 0; ph ^= 1; }
    }
}

__device__ __forceinline__ uint4* qkv_dst(int layer, int ch, int w, int blk) {
    return g_qkv[layer] + (size_t)((ch * 4 + (w >> 1)) * 32 + ((blk & 63) >> 1)) * 1536 + (blk >> 6) * 512 + (w & 1) * 256;
}
__device__ __forceinline__ uint4* op_dst(int layer, int ch, int slot, int w, uint32_t rank) {
    return g_pp[layer] + (size_t)(ch * MAXSPLIT + slot) * 8192 + (w * 32 + rank * 16) * 32;
}
__device__ __forceinline__ uint32_t ln2(uint32_t x, uint32_t m, uint32_t rh, uint32_t rl) {
    uint32_t d; asm volatile("{.reg .b32 t,u; sub.rn.bf16x2 t,%1,%2; mul.rn.bf16x2 u,t,%4; fma.rn.bf16x2 %0,t,%3,u;}" : "=r"(d) : "r"(x), "r"(m), "r"(rh), "r"(rl)); return d;
}
__device__ __forceinline__ void qkv_task(uint32_t sb, int w, int layer, int nu, int ng, int& nd, uint32_t& ph) {
    static_assert(NSTG == 8, "ring");
    const int lane = threadIdx.x & 31;
    const uint64_t db0 = mkdesc(sb, 4096, 1024, 1);
    const uint32_t rel = (w & 2) ? sb + B_BAR + BB_IDLE * 8 : mapa(sb + B_BAR + BB_EMPTY * 8, w & 1), full = sb + B_BAR + BB_FULL * 8;
    const uint32_t la = sb + w * 1024 + ((lane >> 3) & 1) * 512 + (lane >> 4) * 128 + (lane & 7) * 16, lo = sb + B_OUT + w * 4096 + (lane ^ (lane >> 3)) * 16;
    uint32_t m0, m1, h0, h1, l0, l1;
    uint4 A[32];
    {
        mbar_wait(full, ph);
        mbar_wait(full + 8, ph);
        const uint32_t sa = sb + (lane >> 4) * STG_B + 16384 + (w * 16 + (lane & 15)) * 8;
        uint2 v = lds64(sa);
        float sm = __uint_as_float(v.x), M2 = __uint_as_float(v.y);
        if (layer) {
            float e[8];
            e[0] = sm;
#pragma unroll
            for (int i = 1; i < 8; i++) { v = lds64(sa + i * 1024); e[i] = __uint_as_float(v.x); sm += e[i]; M2 += __uint_as_float(v.y); }
            sm += __shfl_xor_sync(0xffffffffu, sm, 16);
#pragma unroll
            for (int i = 0; i < 8; i++) { const float d = e[i] * (1.f / 32.f) - sm * (1.f / 512.f); M2 += 32.f * d * d; }
            M2 += __shfl_xor_sync(0xffffffffu, M2, 16);
        } else M2 = fmaxf(M2 - sm * sm * (1.f / 512.f), 0.f);
        A[0] = ldsm4(la); A[1] = ldsm4(la + 256);
        const float2 o = ln_finish(sm * (1.f / 512.f), M2 * (1.f / 512.f));
        const float r = rcp(o.y), rh = rbf(r);
        const uint32_t mm = pack2(o.x, o.x), hl = pack2(r - rh, rh);
        m0 = __shfl_sync(0xffffffffu, mm, lane >> 2); m1 = __shfl_sync(0xffffffffu, mm, (lane >> 2) + 8);
        l0 = __shfl_sync(0xffffffffu, hl, lane >> 2); l1 = __shfl_sync(0xffffffffu, hl, (lane >> 2) + 8);
        h0 = __byte_perm(l0, 0, 0x3232); h1 = __byte_perm(l1, 0, 0x3232); l0 = __byte_perm(l0, 0, 0x1010); l1 = __byte_perm(l1, 0, 0x1010);
    }
    float acc[64];
#define QNRM(i) A[i] = make_uint4(ln2(A[i].x, m0, h0, l0), ln2(A[i].y, m1, h1, l1), ln2(A[i].z, m0, h0, l0), ln2(A[i].w, m1, h1, l1))
    if (w >> 2) mbar_wait(sb + B_BAR + BB_GO * 8, ~ng & 1);
#pragma unroll
    for (int h = 0; h < 16; h++) {
        const uint64_t db = db0 + ((h & 7) * (STG_B >> 4) + 512);
        if (h < 15) { A[(2 * h + 2) & 31] = ldsm4(la + ((h + 1) & 7) * STG_B); A[(2 * h + 3) & 31] = ldsm4(la + ((h + 1) & 7) * STG_B + 256); }
        const bool ok = h >= 14 || mbar_test(full + ((h + 2) & 7) * 8, ph ^ ((h + 2) >> 3));
        QNRM(2 * h); QNRM(2 * h + 1);
        if (h) wg_wait<1>();
        wg_fence();
        if (h) wgmma128r<true>(acc, A[2 * h], db); else wgmma128r<false>(acc, A[0], db);
        wgmma128r<true>(acc, A[2 * h + 1], db + 128);
        wg_commit();
        if (h >= 2) mbar_arrive1_cluster(rel + ((h - 2) & 7) * 8);
        if (h == LAGQ - 1 && w == 2) mbar_arrive1(sb + B_BAR + BB_GO * 8);
        if (!ok) mbar_wait(full + ((h + 2) & 7) * 8, ph ^ ((h + 2) >> 3));
    }
#pragma unroll 1
    for (int u = 1;; u++) {
        mbar_wait(sb + B_BAR + (BB_SF + (w >> 2)) * 8, (nd & 1) ^ 1);
        if (u < nu) mbar_wait(full, ph);
        wg_wait<1>();
        mbar_arrive1_cluster(rel + 48);
        wg_wait<0>();
        mbar_arrive1_cluster(rel + 56);
        uint4 o[8];
#pragma unroll
        for (int n = 0; n < 8; n++) {
            const float* a = acc + (n >> 1) * 16 + (n & 1) * 2;
            o[n] = make_uint4(pack2(a[0], a[1]), pack2(a[4], a[5]), pack2(a[8], a[9]), pack2(a[12], a[13]));
            sts128(lo + n * 512, o[n].x, o[n].y, o[n].z, o[n].w);
        }
        __syncwarp();
        mbar_arrive1(sb + B_BAR + (BB_DONE + (w >> 2)) * 8);
        nd++;
        if (u == nu) break;
#pragma unroll
        for (int h = 0; h < 8; h++) {
            const uint64_t db = db0 + h * (STG_B >> 4);
            if (h) { mbar_wait(full + h * 8, ph); wg_wait<1>(); }
            wg_fence();
            if (h) wgmma128r<true>(acc, A[4 * h], db); else wgmma128r<false>(acc, A[0], db);
            wgmma128r<true>(acc, A[4 * h + 1], db + 128);
            wgmma128r<true>(acc, A[4 * h + 2], db + 512);
            wgmma128r<true>(acc, A[4 * h + 3], db + 640);
            wg_commit();
            if (h >= 2) mbar_arrive1_cluster(rel + (h - 2) * 8);
        }
        ph ^= 1;
    }
}

template <int NB>
__device__ __forceinline__ void load_resid(uint32_t* r, int layer, int ch, int w, int cb) {
    const uint32_t* rp = (const uint32_t*)(g_xA[layer] + (ch * 8 + (cb >> 2)) * 1024 + w * 128 + (cb & 3) * 16) + (threadIdx.x & 31);
#pragma unroll
    for (int i = 0; i < NB * 4; i++) r[i] = __ldcg(rp + (i >> 1) * 32 + (i & 1) * 256);
}
template <int NS>
__device__ __forceinline__ void part_load(uint4* v, int layer, int ch, int w, int cb, int ns) {
    const uint4* src = g_pp[layer] + (size_t)ch * MAXSPLIT * 8192 + (w * 32 + cb) * 32 + (threadIdx.x & 31);
#pragma unroll
    for (int i = 0; i < 2 * NS; i++) {
        asm volatile("{.reg .pred p; .reg .b128 t; setp.gt.s32 p,%6,0; mov.b128 t,{0,0,0,0}; @p ld.relaxed.gpu.global.L2::cache_hint.b128 t,[%4],%5; mov.b128 {%0,%1,%2,%3},t;}"
                     : "=r"(v[i].x), "=r"(v[i].y), "=r"(v[i].z), "=r"(v[i].w) : "l"(src + (i / NS) * 32 + (i % NS) * 8192), "l"(POL_LAST), "r"(ns - i % NS) : "memory");
    }
}
template <int NS>
__device__ __forceinline__ void part_sum(float* x, const uint4* v, const uint32_t* r) {
    const int dg = ((threadIdx.x & 31) >> 2) - 2 * (threadIdx.x & 3);
    const uint32_t idm = dg == 0 ? 0x00003f80u : dg == 1 ? 0x3f800000u : 0u;
#pragma unroll
    for (int b = 0; b < 2; b++) {
        float* y = x + b * 8;
#pragma unroll
        for (int i = 0; i < 8; i++) y[i] = 0;
#pragma unroll
        for (int s = 0; s < NS; s++) { mma8(y, v[b * NS + s].x, v[b * NS + s].y, idm); mma8(y + 4, v[b * NS + s].z, v[b * NS + s].w, idm); }
#pragma unroll
        for (int i = 0; i < 4; i++) { y[2 * i] = rbf(rbf(y[2 * i]) + blo(r[b * 4 + i])); y[2 * i + 1] = rbf(rbf(y[2 * i + 1]) + bhi(r[b * 4 + i])); }
    }
}

__device__ __forceinline__ float4 row_stats32(const float* x) {
    float a = (x[0] + x[1]) + (x[4] + x[5]) + (x[8] + x[9]) + (x[12] + x[13]);
    float b = (x[2] + x[3]) + (x[6] + x[7]) + (x[10] + x[11]) + (x[14] + x[15]);
    a += __shfl_xor_sync(0xffffffffu, a, 1); b += __shfl_xor_sync(0xffffffffu, b, 1);
    a += __shfl_xor_sync(0xffffffffu, a, 2); b += __shfl_xor_sync(0xffffffffu, b, 2);
    const float ma = a * (1.f / 32.f), mb = b * (1.f / 32.f);
    float qa = 0, qb = 0;
#pragma unroll
    for (int i = 0; i < 4; i++) {
        float d0 = x[4 * i] - ma, d1 = x[4 * i + 1] - ma, d2 = x[4 * i + 2] - mb, d3 = x[4 * i + 3] - mb;
        qa += d0 * d0 + d1 * d1; qb += d2 * d2 + d3 * d3;
    }
    qa += __shfl_xor_sync(0xffffffffu, qa, 1); qb += __shfl_xor_sync(0xffffffffu, qb, 1);
    qa += __shfl_xor_sync(0xffffffffu, qa, 2); qb += __shfl_xor_sync(0xffffffffu, qb, 2);
    return make_float4(a, qa, b, qb);
}

__device__ __forceinline__ void conv_stage(float* Y, uint32_t pbase, uint32_t ubase) {
    const int lane = threadIdx.x & 31, w = threadIdx.x >> 5, g = lane >> 2, c = lane & 3;
#pragma unroll
    for (int cp = 0; cp < 2; cp++) {
        const int chl = w * 4 + cp * 2 + (lane >> 4);
        const uint4 b = ldsm4(ubase + chl * 256 + ((lane >> 3) & 1) * 128 + (((lane & 7) ^ (chl & 7)) << 4));
#pragma unroll
        for (int h = 0; h < 2; h++) {
            const uint32_t pa = pbase + ((w * 4 + cp * 2 + h) * PW + 16 + g - 2 * c) * 4;
            uint32_t lo = lds32(pa - 32);
#pragma unroll
            for (int d = 0; d < 8; d++) {
                const uint32_t a0 = lds32(pa + d * 64), a1 = lds32(pa + d * 64 + 32);
                mma16(Y + ((cp * 2 + h) * 8 + d) * 4, a0, a1, lo, a0, h ? b.z : b.x, h ? b.w : b.y);
                lo = a1;
            }
        }
    }
}

__device__ __forceinline__ void conv_combine(const float* y8, float* cur, float* nxt) {
    const int lane = threadIdx.x & 31, c = lane & 3;
    cur[0] = y8[0]; cur[1] = y8[1] + y8[4]; cur[2] = y8[2]; cur[3] = y8[3] + y8[6];
    nxt[0] = y8[29]; nxt[1] = 0.f; nxt[2] = y8[31]; nxt[3] = 0.f;
#pragma unroll
    for (int e = 1; e < 4; e++) {
        const int src = (lane & ~3) | ((c - e) & 3);
        const float v0 = __shfl_sync(0xffffffffu, y8[8 * e] + y8[8 * e - 3], src), v1 = __shfl_sync(0xffffffffu, y8[8 * e + 1] + y8[8 * e + 4], src);
        const float v2 = __shfl_sync(0xffffffffu, y8[8 * e + 2] + y8[8 * e - 1], src), v3 = __shfl_sync(0xffffffffu, y8[8 * e + 3] + y8[8 * e + 6], src);
        if (c >= e) { cur[0] += v0; cur[1] += v1; cur[2] += v2; cur[3] += v3; }
        else { nxt[0] += v0; nxt[1] += v1; nxt[2] += v2; nxt[3] += v3; }
    }
}

__device__ __forceinline__ void hist_task(float* Y, uint32_t sb, int w, int ch, int q, int& st, uint32_t& ph, int nd) {
    const int lane = threadIdx.x & 31, chl = w * 2 + (lane >> 4);
    const uint32_t ua = sb + 12288 + chl * 256 + ((lane >> 3) & 1) * 128 + (((lane & 7) ^ (chl & 7)) << 4);
    const uint32_t pa = sb + (w * 2 * PW + 16 + (lane >> 2) - 2 * (lane & 3)) * 4;
#pragma unroll
    for (int i = 0; i < 128; i++) Y[i] = 0;
    uint4 b1 = make_uint4(0, 0, 0, 0);
#pragma unroll 1
    for (int j = ch + 1; j >= 2; j--) {
        const uint4 b0 = b1;
        mbar_wait(sb + B_BAR + (BB_FULL + st) * 8, ph);
        b1 = ldsm4(ua + st * STG_B);
        if (j == 2) b1 = make_uint4(0, 0, 0, 0);
#pragma unroll
        for (int h = 0; h < 2; h++) {
            const uint32_t o = pa + st * STG_B + h * PW * 4;
            uint32_t lo = lds32(o - 32);
#pragma unroll
            for (int d = 0; d < 8; d++) {
                const uint32_t a0 = lds32(o + d * 64), a1 = lds32(o + d * 64 + 32);
                mma16(Y + (h * 16 + d) * 4, a0, a1, lo, a0, h ? b0.z : b0.x, h ? b0.w : b0.y);
                mma16(Y + (h * 16 + 8 + d) * 4, a0, a1, lo, a0, h ? b1.z : b1.x, h ? b1.w : b1.y);
                lo = a1;
            }
        }
        bar_sync(NB_WG + (w >> 2), 128);
        stage_release(sb, w, st);
        if (++st == NSTG) { st = 0; ph ^= 1; }
    }
    mbar_wait(sb + B_BAR + (BB_SF + (w >> 2)) * 8, (nd & 1) ^ 1);
#pragma unroll
    for (int h = 0; h < 2; h++) {
        const int o = ((ch * 16 + (q >> 1)) * 4 + (w & 1) * 2 + h) * 256 + ((q & 1) * 4 + (w >> 1)) * 32 + lane;
        float c0[4], n0[4], c1[4], n1[4];
        conv_combine(Y + h * 64, c0, n0); conv_combine(Y + h * 64 + 32, c1, n1);
        g_carry[0][o] = make_float4(c0[0], c0[1], c0[2], c0[3]);
        g_carry[0][o + 16384] = make_float4(c1[0] + n0[0], c1[1] + n0[1], c1[2] + n0[2], c1[3] + n0[3]);
        g_carry[1][o + 32768] = make_float4(n1[0], n1[1], n1[2], n1[3]);
    }
}

__device__ __forceinline__ void conv_task(const Params& p, float* Y, uint32_t sb, int w, int ch, int q, bool dry, int& st, uint32_t& ph, int nd) {
    const int tid = threadIdx.x, lane = tid & 31, g = lane >> 2, c = lane & 3;
    uint32_t dk[4];
    const uint32_t sg = (~ch & 2) << 30;
    int sr = st;
    float x[16];
    uint32_t rs[8];
    load_resid<2>(rs, 0, ch, w, 2 * q);
    PROF(tid == 128, 2048 + ch * 8);
#pragma unroll
    for (int i = 0; i < 128; i++) Y[i] = 0;
#pragma unroll 1
    for (int j = min(ch, 1 + (ch & 1)); j >= 1; j--) {
        mbar_wait(sb + B_BAR + (BB_FULL + st) * 8, ph);
        conv_stage(Y, sb + st * STG_B, sb + B_UT + ((ch - j) & 1) * 8192);
        if (++st == NSTG) { st = 0; ph ^= 1; }
    }
    PROF(tid == 128, 2048 + ch * 8 + 7);
    {
        uint4 v[2 * OPS1];
        wait_cnt_warp(cnt_ptr(C_OP0 + (q >> 3) * 2 + (w >> 2), ch), dry ? 0 : OPS1);
        part_load<OPS1>(v, 0, ch, w, 2 * q, OPS1);
        part_sum<OPS1>(x, v, rs);
        const float4 s = row_stats32(x);
        float2* dst = g_st2 + ((ch & 1) * 16 + q) * 128 + w * 16 + g + c * 8;
        asm volatile("{.reg .pred p; setp.ne.u32 p,%2,0; @p st.relaxed.gpu.global.b64 [%0],%1;}" ::"l"(dst),
                     "l"(((uint64_t)((__float_as_uint(c ? s.w : s.y) & 0x7fffffffu) | sg) << 32) | __float_as_uint(c ? s.z : s.x)), "r"((uint32_t)(c < 2 && !dry)) : "memory");
        PROF(tid == 128, 2048 + ch * 8 + 1);
    }
#pragma unroll
    for (int i = 0; i < 4; i++) asm volatile("ld.global.nc.u32 %0,[%1];" : "=r"(dk[i]) : "l"(p.Dskip + q * 32 + i * 8 + 2 * c));
#pragma unroll 1
    for (int i = 0; i < min(ch, (ch & 1) ? 2 : 3); i++) {
        if (i) mbar_wait(sb + B_BAR + (BB_FULL + st) * 8, ph);
        const uint32_t ca = sb + (i ? st * STG_B : B_SP) + tid * 16;
#pragma unroll
        for (int k = 0; k < 4; k++) {
            const uint4 cr = lds128(ca + k * 4096);
            Y[k * 32] += __uint_as_float(cr.x); Y[k * 32 + 1] += __uint_as_float(cr.y); Y[k * 32 + 2] += __uint_as_float(cr.z); Y[k * 32 + 3] += __uint_as_float(cr.w);
        }
        if (i && ++st == NSTG) { st = 0; ph ^= 1; }
    }
    bar_sync(NB_C, 256);
#pragma unroll 1
    for (; sr != st; sr = (sr + 1) & (NSTG - 1)) stage_release(sb, w, sr);
    const uint32_t ut = sb + B_UT + (ch & 1) * 8192;
    mbar_wait(sb + B_BAR + (BB_SF + (w >> 2)) * 8, (nd & 1) ^ 1);
    mbar_wait(sb + B_BAR + (BB_SF + 1 - (w >> 2)) * 8, (nd & 1) ^ 1);
    float2 ln0, ln1;
    {
        const float2* src = g_st2 + ((ch & 1) * 16 + (lane >> 4) * 8) * 128 + w * 16 + (lane & 15);
        uint64_t v[8];
        int n = 0;
#pragma unroll
        for (int i = 0; i < 8; i++) v[i] = (uint64_t)~sg << 32;
        while (true) {
            bool bad = false;
#pragma unroll
            for (int i = 0; i < 8; i++) asm volatile("{.reg .pred p; setp.lt.s32 p,%2,0; @p ld.relaxed.gpu.global.b64 %0,[%1];}" : "+l"(v[i]) : "l"(src + i * 128), "r"((uint32_t)(v[i] >> 32) ^ sg) : "memory");
#pragma unroll
            for (int i = 0; i < 8; i++) bad = bad || (int)((uint32_t)(v[i] >> 32) ^ sg) < 0;
            if (!__any_sync(0xffffffffu, bad && !dry)) break;
            if (++n > 2000000) __trap();
        }
        float sm = 0;
#pragma unroll
        for (int i = 0; i < 8; i++) sm += __uint_as_float((uint32_t)v[i]);
        sm += __shfl_xor_sync(0xffffffffu, sm, 16);
        const float mean = sm * (1.f / 512.f);
        float M2 = 0;
#pragma unroll
        for (int i = 0; i < 8; i++) { const float d = __uint_as_float((uint32_t)v[i]) * (1.f / 32.f) - mean; M2 += fabsf(__uint_as_float((uint32_t)(v[i] >> 32))) + 32.f * d * d; }
        M2 += __shfl_xor_sync(0xffffffffu, M2, 16);
        const float2 o = ln_finish(mean, M2 * (1.f / 512.f));
        ln0.x = __shfl_sync(0xffffffffu, o.x, g); ln0.y = __shfl_sync(0xffffffffu, o.y, g);
        ln1.x = __shfl_sync(0xffffffffu, o.x, g + 8); ln1.y = __shfl_sync(0xffffffffu, o.y, g + 8);
    }
    PROF(tid == 128, 2048 + ch * 8 + 2);
    uint32_t u[8];
#pragma unroll
    for (int i = 0; i < 8; i++) {
        const float2 l = (i & 1) ? ln1 : ln0;
        u[i] = pack2(__fdividef(rbf(x[2 * i] - l.x), l.y), __fdividef(rbf(x[2 * i + 1] - l.x), l.y));
        const int chl = (i >> 1) * 8 + g;
        sts32(ut + chl * 256 + (i & 1) * 128 + ((w ^ g) << 4) + c * 4, movm(u[i]));
    }
    bar_sync(NB_C, 256);
    mbar_wait(sb + B_BAR + (BB_FULL + st) * 8, ph);
    PROF(tid == 128, 2048 + ch * 8 + 3);
    conv_stage(Y, sb + st * STG_B, ut);
    uint32_t yp[4][2];
    float nxt[4][4];
    {
        float y[4][4];
#pragma unroll
        for (int k = 0; k < 4; k++) conv_combine(Y + k * 32, y[k], nxt[k]);
#pragma unroll
        for (int i = 0; i < 4; i++) { yp[i][0] = pack2(y[0][i], y[1][i]); yp[i][1] = pack2(y[2][i], y[3][i]); }
    }
#pragma unroll
    for (int i = 0; i < 4; i++) sts64(sb + B_YT + (16 * (2 * c + (i & 1)) + g + (i >> 1) * 8) * 80 + w * 8, yp[i][0], yp[i][1]);
    bar_sync(NB_C, 256);
    stage_release(sb, w, st);
    if (++st == NSTG) { st = 0; ph ^= 1; }
    PROF(tid == 128, 2048 + ch * 8 + 4);
    uint32_t xo[8];
    uint32_t* dA = (uint32_t*)(g_xA[1] + (ch * 8 + (q >> 1)) * 1024 + (w * 2) * 64 + (q & 1) * 32) + lane;
#pragma unroll
    for (int i = 0; i < 8; i++) {
        const int col = (i >> 1) * 8 + 2 * c;
        const uint32_t yv = lds32(sb + B_YT + (w * 16 + g + (i & 1) * 8) * 80 + col * 2);
        const uint32_t dv = dk[i >> 1];
        x[2 * i] = rbf(x[2 * i] + rbf(blo(yv) + rbf(blo(u[i]) * blo(dv))));
        x[2 * i + 1] = rbf(x[2 * i + 1] + rbf(bhi(yv) + rbf(bhi(u[i]) * bhi(dv))));
        xo[i] = pack2(x[2 * i], x[2 * i + 1]);
        dA[(i >> 1) * 32 + (i & 1) * 256] = xo[i];
    }
    {
        const float4 s = row_stats32(x);
        float2* dst = g_st[1] + (ch * 16 + q) * 128 + w * 16 + g;
        if (c == 0) dst[0] = make_float2(s.x, s.y);
        if (c == 1) dst[8] = make_float2(s.z, s.w);
        __syncwarp();
    }
    PROF(tid == 128, 2048 + ch * 8 + 5);
    mbar_arrive1(sb + B_BAR + (BB_DONE + (w >> 2)) * 8);
    bar_sync(NB_C, 256);
#pragma unroll
    for (int k = 0; k < 4; k++) sts128(sb + B_SP + k * 4096 + tid * 16, __float_as_uint(nxt[k][0]), __float_as_uint(nxt[k][1]), __float_as_uint(nxt[k][2]), __float_as_uint(nxt[k][3]));
    PROF(tid == 128, 2048 + ch * 8 + 6);
}

__device__ __forceinline__ void out_store(const Params& p, const float* x, int ch, int cb) {
    const int lane = threadIdx.x & 31, w = threadIdx.x >> 5, g = lane >> 2, c = lane & 3;
#pragma unroll
    for (int h = 0; h < 2; h++) {
        const float* y = x + h * 2;
        uint32_t v0 = pack2(y[0], y[1]), v1 = pack2(y[4], y[5]), v2 = pack2(y[8], y[9]), v3 = pack2(y[12], y[13]);
        uint32_t t0 = (c & 1) ? v0 : v1, t1 = (c & 1) ? v2 : v3;
        t0 = __shfl_xor_sync(0xffffffffu, t0, 1); t1 = __shfl_xor_sync(0xffffffffu, t1, 1);
        if (c & 1) { v0 = t0; v2 = t1; } else { v1 = t0; v3 = t1; }
        t0 = (c & 2) ? v0 : v2; t1 = (c & 2) ? v1 : v3;
        t0 = __shfl_xor_sync(0xffffffffu, t0, 2); t1 = __shfl_xor_sync(0xffffffffu, t1, 2);
        if (c & 2) { v0 = t0; v1 = t1; } else { v2 = t0; v3 = t1; }
        stg128((uint4*)(p.out + (size_t)(ch * 128 + w * 16 + g + h * 8) * 512 + cb * 16 + c * 8), make_uint4(v0, v1, v2, v3), POL_LATE);
    }
}
__device__ __forceinline__ void fin_task(const Params& p, int ch, int cb0, int ncb, int ns, bool dry) {
    const int w = threadIdx.x >> 5;
    uint32_t rs[8];
    wait_cnt_warp(cnt_ptr(C_CV, ch), dry ? 0 : 32);
    load_resid<2>(rs, 1, ch, w, cb0);
    wait_cnt_warp(cnt_ptr(C_OP1, ch), dry ? 0 : 256);
    for (int cb = cb0; cb < cb0 + ncb; cb += 2) {
        float x[16];
        if (cb != cb0) load_resid<2>(rs, 1, ch, w, cb);
        uint4 v[32];
        part_load<16>(v, 1, ch, w, cb, ns);
        part_sum<16>(x, v, rs);
        out_store(p, x, ch, cb);
    }
}

__device__ __forceinline__ void bulk_consumer(const Params& p, uint32_t sb, int cl, uint32_t rank, int w) {
    int st = 0; uint32_t ph = 0; int nd = 0, ng = 0;
    for (int ti = 0; ti < MAXT; ti++) {
        const Task t = task_of(p.task[cl][ti], rank);
        const int type = t.type, layer = t.layer, ch = t.ch;
        if (type == T_END) break;
        bool staged = type != T_FIN;
        PROF(threadIdx.x == 0, 3600 + ti * 4);
        if (type <= T_OP) {
            CPROF(0);
            if ((w >> 2) && type == T_OP) mbar_wait(sb + B_BAR + BB_GO * 8, ng & 1);
            ng++;
            CPROF(1);
        }
        if (type == T_QKV) {
            staged = false;
            #pragma unroll 1
            while (st) {
                if (!(w & 3)) { mbar_wait(sb + B_BAR + (BB_FULL + st) * 8, ph); stage_release(sb, 0, st); stage_release(sb, 1, st); }
                if (++st == NSTG) { st = 0; ph ^= 1; }
            }
            qkv_task(sb, w, layer, t.b, ng, nd, ph);
            PROF(threadIdx.x == 128, 3600 + ti * 4 + 1);
        } else if (type == T_OP) {
            const int lane = threadIdx.x & 31;
            float acc[128];
            uint32_t r0 = sb + B_BAR + BB_IDLE * 8, r1 = r0;
            gemm_run<false>(acc, sb, w, 0, 1, r0, r1, st, ph);
            gemm_run<true>(acc, sb, w, 1, 2 * t.b, r0, r1, st, ph);
            mbar_wait(sb + B_BAR + (BB_SF + (w >> 2)) * 8, (nd & 1) ^ 1);
            wg_wait<1>();
            mbar_arrive1_cluster(r0);
            wg_wait<0>();
            mbar_arrive1_cluster(r1);
            PROF(threadIdx.x == 128, 3600 + ti * 4 + 1);
            if (t.c & 32) {
                staged = false;
#pragma unroll
                for (int j = 0; j < 16; j += 4) {
                    uint32_t rs[16];
                    load_resid<4>(rs, 1, ch, w, (t.blk & 4) * 4 + j);
#pragma unroll
                    for (int i = 0; i < 16; i++) { float* y = acc + j * 8 + 2 * i; y[0] = rbf(y[0]) + blo(rs[i]); y[1] = rbf(y[1]) + bhi(rs[i]); }
                    out_store(p, acc + j * 8, ch, (t.blk & 4) * 4 + j); out_store(p, acc + j * 8 + 16, ch, (t.blk & 4) * 4 + j + 2);
                }
            } else if (!layer) {
                const int s2 = st + (w >> 1);
                const uint32_t o = sb + (s2 & (NSTG - 1)) * STG_B + (w & 1) * 8192 + lane * 16;
                mbar_wait(sb + B_BAR + (BB_FULL + (s2 & (NSTG - 1))) * 8, ph ^ (s2 >= NSTG));
#pragma unroll
                for (int j = 0; j < 16; j++)
                    sts128(o + j * 512, pack2(acc[j * 8], acc[j * 8 + 1]), pack2(acc[j * 8 + 2], acc[j * 8 + 3]), pack2(acc[j * 8 + 4], acc[j * 8 + 5]), pack2(acc[j * 8 + 6], acc[j * 8 + 7]));
                sts32(sb + B_ST + (w >> 2) * 4, st);
                st += 4;
                if (st >= NSTG) { st -= NSTG; ph ^= 1; }
            } else {
                uint4* dst = op_dst(layer, ch, t.c & 15, w, (t.blk >> 2) & 1) + lane;
#pragma unroll
                for (int n = 0; n < 16; n++) {
                    const int j = (n >> 1) + (n & 1) * 8;
                    const uint4 v = make_uint4(pack2(acc[j * 8], acc[j * 8 + 1]), pack2(acc[j * 8 + 2], acc[j * 8 + 3]), pack2(acc[j * 8 + 4], acc[j * 8 + 5]), pack2(acc[j * 8 + 6], acc[j * 8 + 7]));
                    if (j < 16 - NSB) stg128(dst + j * 32, v, out_pol(T_OP, layer, ch)); else sts128(sb + B_OUT + (w * NSB + j - (16 - NSB)) * 512 + lane * 16, v.x, v.y, v.z, v.w);
                }
            }
        } else if (type == T_CV) {
            float acc[128];
            if (layer) hist_task(acc, sb, w, ch, t.a + rank, st, ph, nd);
            else { conv_task(p, acc, sb, w, ch, t.a + rank, t.dry, st, ph, nd); staged = false; nd++; }
        } else {
            fin_task(p, ch, t.a + rank * t.c, t.c, t.b, t.dry);
        }
        if (staged) {
            __syncwarp();
            mbar_arrive1(sb + B_BAR + (BB_DONE + (w >> 2)) * 8);
            nd++;
        }
        CPROF(6);
        PROF(threadIdx.x == 128, 3600 + ti * 4 + 2);
        __syncwarp();
    }
}

constexpr int P_Y = 131072  , P_PRM = P_Y  , P_K6 = P_PRM + 8192  ,
              P_P = P_Y + 40960  , P_U = P_P + 33280  , P_END = P_U + 17408, P_X = 98304  ;
static_assert(P_END <= B_BAR && P_END <= R_BAR, "prologue scratch");
#define KGUN 2
constexpr int KGU = KGUN;
__device__ __forceinline__ void csq(float& r, float& i) { const float t = r * i; r = fmaf(r, r, -(i * i)); i = t + t; }
__device__ __forceinline__ void cpow(float ar, float ph, float p, float& r, float& i) {
    const float e = ex2(ar * p);
    const float u = ph * p, n = fabsf(u) < 4194304.f ? (u + 12582912.f) - 12582912.f : u;
    const float t = (u - n) * 6.283185307179586f;
    r = e * __cosf(t); i = e * __sinf(t);
}
__device__ __forceinline__ void mma_tf32(float* c, float a0, float a1, float a2, float a3, float b0, float b1) {
    asm volatile("mma.sync.aligned.m16n8k8.row.col.f32.tf32.tf32.f32 {%0,%1,%2,%3},{%4,%5,%6,%7},{%8,%9},{%0,%1,%2,%3};"
                 : "+f"(c[0]), "+f"(c[1]), "+f"(c[2]), "+f"(c[3])
                 : "r"(__float_as_uint(a0)), "r"(__float_as_uint(a1)), "r"(__float_as_uint(a2)), "r"(__float_as_uint(a3)), "r"(__float_as_uint(b0)), "r"(__float_as_uint(b1)));
}

struct ProRegs { uint32_t v[2][4], ldt[2]; };
__device__ __forceinline__ void prologue_load(const ProArgs& a, int b, ProRegs& pr) {
    const int w = threadIdx.x >> 5;
#pragma unroll
    for (int i = 0; i < 2; i++) {
        const int gi = b * 512 + (w & 3) * 128 + ((w >> 2) & 1) * 64 + i * 32 + (threadIdx.x & 31);
        pr.ldt[i] = __ldg((const uint16_t*)a.ldt + b * 4 + (w & 3));
        pr.v[i][0] = __ldg((const uint16_t*)a.lAr + gi); pr.v[i][1] = __ldg((const uint16_t*)a.Ai + gi);
        pr.v[i][2] = __ldg((const uint16_t*)a.Cr + gi); pr.v[i][3] = __ldg((const uint16_t*)a.Ci + gi);
    }
}
__device__ __forceinline__ void prologue(const ProArgs& a, uint32_t sb, int b, int w, const ProRegs& pr) {
    const int tid = threadIdx.x, lane = tid & 31, g = lane >> 2, c = lane & 3;
    const int d0 = b * 4;
    if (w >= 8) {
        const int t2 = tid - 256;
        if (w < 10) {
            const int row = b * 16 + (w - 8) * 8 + g;
            const float2 r = row_stats512((const uint4*)(a.x + (size_t)row * 512) + c, 8, 4);
            const float2 l = ln_finish(r.x * (1.f / 512.f), fmaxf(r.y - r.x * r.x * (1.f / 512.f), 0.f) * (1.f / 512.f));
            if (c == (g >> 1)) asm volatile("st.relaxed.gpu.global.u32 [%0],%1;" ::"l"(g_ln0 + row), "r"(pack2(l.x, l.y)) : "memory");
        }
        PROF(t2 == 0, 3516);
        const int gi = b * 128 + t2;
        if (t2 < 32) acc_init(a.mem0, b * 32 + t2);
        if (t2 >= 112) ((uint4*)g_st2)[b * 16 + t2 - 112] = make_uint4(0, 0, 0, 0);
        if (gi < 13 * 64) g_cnt[gi] = 0;
        bar_sync(6, 384);
        if (gi < 256) g_st[0][(gi >> 7) * 2048 + (lds32(sb + S_TAG) ^ 1) * 128 + (gi & 127)] = make_float2(0.f, 0.f);
        asm volatile("{.reg .pred p; elect.sync _|p,0xffffffff; @p cp.async.bulk.prefetch.L2.global [%0],32768;}"
                     ::"l"((w == 8 ? a.Wq : w == 9 ? a.Wk : w == 10 ? a.Wv : a.Wo) + (size_t)b * 16384) : "memory");
        mbar_wait(sb + S_XBAR, 0);
#pragma unroll 1
        for (int h = 0; h < 2; h++) {
            uint32_t l[8];
            int n = 0;
            while (true) {
                bool ok = true;
#pragma unroll
                for (int i = 0; i < 8; i++) asm volatile("ld.relaxed.gpu.global.u32 %0,[%1];" : "=r"(l[i]) : "l"(g_ln0 + h * 1024 + i * 128 + t2) : "memory");
#pragma unroll
                for (int i = 0; i < 8; i++) ok = ok && l[i];
                if (__all_sync(0xffffffffu, ok)) break;
                if (++n > 2000000) __trap();
            }
#pragma unroll
            for (int i = 0; i < 8; i++) {
                const int t = h * 1024 + i * 128 + t2;
                const uint2 x = lds64(sb + P_X + t * 16 + (b & 1) * 8);
                const float m = blo(l[i]), rs = rcp(bhi(l[i]));
                const uint32_t u0 = pack2(rbf(blo(x.x) - m) * rs, rbf(bhi(x.x) - m) * rs), u1 = pack2(rbf(blo(x.y) - m) * rs, rbf(bhi(x.y) - m) * rs);
                sts128(sb + P_X + t * 16, x.x, x.y, u0, u1);
                const uint32_t o = sb + P_U + ((t >> 3) & 1) * 2176 + ((t >> 4) + 8) * 16 + (t & 7) * 2;
                asm volatile("st.shared.u16 [%0],%1;" ::"r"(o), "h"((uint16_t)u0) : "memory");
                asm volatile("st.shared.u16 [%0],%1;" ::"r"(o + 4352), "h"((uint16_t)(u0 >> 16)) : "memory");
                asm volatile("st.shared.u16 [%0],%1;" ::"r"(o + 8704), "h"((uint16_t)u1) : "memory");
                asm volatile("st.shared.u16 [%0],%1;" ::"r"(o + 13056), "h"((uint16_t)(u1 >> 16)) : "memory");
            }
        }
        PROF(t2 == 0, 3517);
        bar_sync(9, 384);
        fence_async_smem();
#pragma unroll 1
        for (int j = 0; j < 16; j++) {
            const int d = d0 + w - 8;
            asm volatile("{.reg .pred p; elect.sync _|p,0xffffffff; @p cp.async.bulk.global.shared::cta.bulk_group [%0],[%1],%2;}" ::"l"(g_P + (((d >> 5) * 16 + j) * 32 + (d & 31)) * PW),
                         "r"(sb + P_P + ((w - 8) * 2080 + j * 128) * 4), "r"(PW * 4) : "memory");
        }
        asm volatile("cp.async.bulk.commit_group; cp.async.bulk.wait_group 0;" ::: "memory");
        bar_arrive(10, 384);
        return;
    }
#pragma unroll
    for (int i = 0; i < 2; i++) {
        const float dt = rbf(expf(blo(pr.ldt[i])));
        const float ar = -rbf(expf(blo(pr.v[i][0]))) * dt, ai = blo(pr.v[i][1]) * dt;
        sts128(sb + P_PRM + (w * 64 + i * 32 + lane) * 16, __float_as_uint(ar * 1.4426950408889634f), __float_as_uint(ai * 0.15915494309189535f),
               __float_as_uint(2.f * (blo(pr.v[i][2]) * dt)), __float_as_uint(2.f * (blo(pr.v[i][3]) * dt)));
    }
    if (tid < 64) sts128(sb + P_U + (tid >> 3) * 2176 + (tid & 7) * 16, 0, 0, 0, 0);
    bar_arrive(6, 384);
    __syncwarp();
    PROF(tid == 0, 3510);
    const int ch = w & 3, hf = w >> 2;
    {
        float k0[4] = {0, 0, 0, 0}, k1[4] = {0, 0, 0, 0}, k2[4] = {0, 0, 0, 0}, k3[4] = {0, 0, 0, 0}, k4[4] = {0, 0, 0, 0}, kl = 0;
#pragma unroll KGU
        for (int j = 0; j < 16; j++) {
            const uint4 q = lds128(sb + P_PRM + (w * 64 + j * 4 + c) * 16);
            const float cr = __uint_as_float(q.z), ci = __uint_as_float(q.w);
            float wr[4], wi[4], vr[4], vi[4];
            cpow(__uint_as_float(q.x), __uint_as_float(q.y), (float)g, wr[0], wi[0]);
            cpow(__uint_as_float(q.x), __uint_as_float(q.y), (float)(g + 8), vr[0], vi[0]);
#pragma unroll
            for (int i = 1; i < 4; i++) { wr[i] = wr[i - 1]; wi[i] = wi[i - 1]; csq(wr[i], wi[i]); vr[i] = vr[i - 1]; vi[i] = vi[i - 1]; csq(vr[i], vi[i]); }
            float hr = wr[3], hi = wi[3];
            csq(hr, hi);
            mma_tf32(k0, wr[0], vr[0], wi[0], vi[0], cr * hr - ci * hi, -(cr * hi + ci * hr));
            hr = vr[3]; hi = vi[3]; csq(hr, hi);
            mma_tf32(k1, wr[0], vr[0], wi[0], vi[0], cr * hr - ci * hi, -(cr * hi + ci * hr));
            csq(hr, hi);
            mma_tf32(k2, wr[1], vr[1], wi[1], vi[1], cr * hr - ci * hi, -(cr * hi + ci * hr));
            csq(hr, hi);
            mma_tf32(k3, wr[2], vr[2], wi[2], vi[2], cr * hr - ci * hi, -(cr * hi + ci * hr));
            csq(hr, hi);
            mma_tf32(k4, wr[3], vr[3], wi[3], vi[3], cr * hr - ci * hi, -(cr * hi + ci * hr));
            csq(hr, hi);
            kl += cr * hr - ci * hi;
        }
        kl += __shfl_xor_sync(0xffffffffu, kl, 1); kl += __shfl_xor_sync(0xffffffffu, kl, 2);
        const uint32_t o = sb + P_K6 + (ch * 656 + c * 32 + g) * 4, ol = sb + P_K6 + (ch * 656 + 640) * 4;
#define KST(k, base) sts32(o + (base) * 4, __float_as_uint(k[0])); sts32(o + (base) * 4 + 64, __float_as_uint(k[1])); \
                     sts32(o + (base) * 4 + 32, __float_as_uint(k[2])); sts32(o + (base) * 4 + 96, __float_as_uint(k[3]))
#define KAD(k, base) k[0] += __uint_as_float(lds32(o + (base) * 4)); k[1] += __uint_as_float(lds32(o + (base) * 4 + 64)); \
                     k[2] += __uint_as_float(lds32(o + (base) * 4 + 32)); k[3] += __uint_as_float(lds32(o + (base) * 4 + 96))
        if (hf == 0) {
            bar_sync(2 + ch, 64);
            KAD(k0, 0); KAD(k1, 128); KAD(k2, 256); KAD(k3, 384); KAD(k4, 512);
            kl += __uint_as_float(lds32(ol));
            __syncwarp();
        }
        KST(k0, 0); KST(k1, 128); KST(k2, 256); KST(k3, 384); KST(k4, 512);
        if (lane == 0) sts32(ol, __float_as_uint(kl));
        if (hf == 1) { __syncwarp(); bar_arrive(2 + ch, 64); }
    }
    PROF(tid == 0, 3511);
    bar_sync(8, 384);
    PROF(tid == 0, 3512);
    if (tid < 64) sts32(sb + P_P + ((tid >> 4) * 2080 + (tid & 15)) * 4, 0);
#pragma unroll 1
    for (int x = tid; x < 2048; x += 512) {
        uint32_t pw[2][4];
#pragma unroll
        for (int h = 0; h < 2; h++) {
            const int y = x + h * 256;
            const int i0 = y <= 256 ? y : 256 + (int)((pack2((float)y, 0.f) & 0xffff) - 0x4380);
            const int i1 = y <= 256 ? max(y - 1, 0) : 256 + (int)((pack2((float)(y - 1), 0.f) & 0xffff) - 0x4380);
#pragma unroll
            for (int k = 0; k < 4; k++) {
                const float lo = __uint_as_float(lds32(sb + P_K6 + k * 2624 + i0 * 4)), hi = __uint_as_float(lds32(sb + P_K6 + k * 2624 + i1 * 4));
                pw[h][k] = pack2(lo, y ? hi : 0.f);
            }
        }
#pragma unroll
        for (int h = 0; h < 2; h++)
#pragma unroll
            for (int k = 0; k < 4; k++) sts32(sb + P_P + (k * 2080 + x + h * 256 + 16) * 4, pw[h][k]);
    }
    bar_sync(9, 384);
    PROF(tid == 0, 3513);
    {
        float acc[16][4];
#pragma unroll
        for (int j = 0; j < 16; j++) acc[j][0] = acc[j][1] = acc[j][2] = acc[j][3] = 0;
#pragma unroll 1
        for (int e = hf * 4; e < hf * 4 + 4; e++) {
            uint32_t B[16][2];
            const uint32_t ua = sb + P_U + ch * 4352 + ((lane >> 3) & 1) * 2176 + (8 + (lane >> 4) * 8 + (lane & 7) - e) * 16;
#pragma unroll
            for (int j = 0; j < 8; j++) { const uint4 v = ldsm4(ua + j * 256); B[2 * j][0] = v.x; B[2 * j][1] = v.y; B[2 * j + 1][0] = v.z; B[2 * j + 1][1] = v.w; }
            const uint32_t pa = sb + P_P + (ch * 2080 + 16 + e * 16 + g - 2 * c) * 4;
#pragma unroll
            for (int d = 0; d < 16; d++) {
                const uint32_t a0 = lds32(pa + d * 512), a1 = lds32(pa + d * 512 + 32), a2 = lds32(pa + d * 512 - 32);
#pragma unroll
                for (int j = d; j < 16; j++) mma16(acc[j], a0, a1, a2, a0, B[j - d][0], B[j - d][1]);
            }
        }
        PROF(tid == 0, 3514);
        const uint32_t o = sb + P_Y + (ch * 2560 + c * 40 + g) * 4;
#pragma unroll
        for (int j = 0; j < 8; j++) {
#pragma unroll
            for (int i = 0; i < 4; i++) { const float lo = acc[j][i], hi = acc[j + 8][i]; acc[j][i] = hf ? hi : lo; sts32(o + (j + 8 - hf * 8) * 640 + (i & 1) * 80 + (i >> 1) * 32, __float_as_uint(hf ? lo : hi)); }
        }
        bar_sync(2 + ch, 64);
#pragma unroll
        for (int j = 0; j < 8; j++) {
#pragma unroll
            for (int i = 0; i < 4; i++) acc[j][i] += __uint_as_float(lds32(o + (j + hf * 8) * 640 + (i & 1) * 80 + (i >> 1) * 32));
        }
#pragma unroll
        for (int j = 0; j < 8; j++) {
#pragma unroll
            for (int i = 0; i < 4; i++) sts32(o + (j + hf * 8) * 640 + (i & 1) * 80 + (i >> 1) * 32, __float_as_uint(acc[j][i]));
        }
    }
    const uint2 dk = __ldg((const uint2*)(a.Dk + d0));
    bar_sync(1, 256);
#pragma unroll 2
    for (int i = 0; i < 8; i++) {
        const int t = i * 256 + tid;
        const uint32_t o = sb + P_Y + (t + 4 * (t >> 4)) * 4;
        const uint4 xu = lds128(sb + P_X + t * 16);
        float y[4];
#pragma unroll
        for (int k = 0; k < 4; k++) y[k] = rbf(__uint_as_float(lds32(o + k * 10240)));
        uint2 r;
        r.x = pack2(blo(xu.x) + rbf(y[0] + rbf(blo(xu.z) * blo(dk.x))), bhi(xu.x) + rbf(y[1] + rbf(bhi(xu.z) * bhi(dk.x))));
        r.y = pack2(blo(xu.y) + rbf(y[2] + rbf(blo(xu.w) * blo(dk.y))), bhi(xu.y) + rbf(y[3] + rbf(bhi(xu.w) * bhi(dk.y))));
        ((uint2*)(g_xA[0] + ((t >> 7) * 8 + (d0 >> 6)) * 1024 + ((t & 127) >> 3) * 64 + ((d0 & 63) >> 3) * 8 + (t & 7)))[(d0 >> 2) & 1] = r;
        if (i == 0) {
            const float e0 = blo(r.x), e1 = bhi(r.x), e2 = blo(r.y), e3 = bhi(r.y);
            asm volatile("red.relaxed.gpu.global.add.v2.f32 [%0],{%1,%2};" ::"l"(g_st[0] + (t >> 7) * 2048 + lds32(sb + S_TAG) * 128 + (t & 127)),
                         "f"((e0 + e1) + (e2 + e3)), "f"((e0 * e0 + e1 * e1) + (e2 * e2 + e3 * e3)) : "memory");
        }
    }
    PROF(tid == 0, 3515);
    bar_sync(10, 384);
}

__global__ void __cluster_dims__(2, 1, 1) __launch_bounds__(384, 1) main_kernel(const __grid_constant__ Params p) {
    extern __shared__ __align__(1024) uint8_t smem[];
    const uint32_t sb = __shfl_sync(0xffffffffu, smem_u32(smem), 0);
    uint32_t rank; asm("mov.u32 %0,%%cluster_ctarank;" : "=r"(rank));
    const int wi = __shfl_sync(0xffffffffu, threadIdx.x >> 5, 0);
    const int cl = blockIdx.x >> 1, wg = wi >> 2;
    const bool rec = p.rec0 >= 0 && cl >= p.rec0 && cl < p.rec0 + 32;
    PROF(threadIdx.x == 0, 3500);
    ProRegs pr;
    prologue_load(p.pa, max((int)blockIdx.x - 4, 0), pr);
    if (rec) rec_init(p, sb, cl - p.rec0, rank); else bulk_init(sb);
    if (threadIdx.x == 352 && p.dopro && cl >= 2) {
        mbar_init(sb + S_XBAR, 1);
        asm volatile("fence.mbarrier_init.release.cluster;" ::: "memory");
        mbar_expect(sb + S_XBAR, 32768);
        for (int j = 0; j < 8; j++) tma2d(sb + P_X + j * 4096, &p.tm[3], ((blockIdx.x - 4) >> 1) * 8, j * 256, sb + S_XBAR);
    }
    if (threadIdx.x == 320) {
        unsigned v;
        asm volatile("ld.relaxed.gpu.global.u32 %0,[%1];" : "=r"(v) : "l"(g_gate) : "memory");
        v = v / (4 * NCL) + p.dopro;
        sts64(sb + S_GATE, v * (4 * NCL), v & 1);
    }
    __syncwarp();
    asm volatile("barrier.cluster.arrive.relaxed.aligned;" ::: "memory");
    if (wg == 2) bar_arrive(8, 384);
    if (p.dopro && cl >= 2) prologue(p.pa, sb, blockIdx.x - 4, wi, pr); else if (wg < 2) bar_sync(8, 384);
    asm volatile("barrier.cluster.wait.aligned;" ::: "memory");
    fence_async_smem();
    bar_sync(wg == 2 ? 7 : 1, wg == 2 ? 128 : 256);
    if (p.dopro && (threadIdx.x == 32 || threadIdx.x == 352)) red_release(g_gate, 1);
    if (rec) {
        if (threadIdx.x == 0) {
            rec_fetch(&p.tm[1], sb + R_STK, (cl - p.rec0) * 128, rank * 256, 2, sb + R_BAR + RB_INIT * 8);
            rec_fetch(&p.tm[2], sb + R_STV, (cl - p.rec0) * 128, rank * 256, 2, sb + R_BAR + RB_INIT * 8);
        }
    }
    PROF(threadIdx.x == 0, 3506);
    __syncwarp();
    if (rec) {
        const int head = cl - p.rec0;
        if (wg == 2) {
            reg_dec<RH>();
            const int w = wi & 3;
            if (threadIdx.x == 256) rec_fetch(&p.tm[0], sb + R_STQ, head * 128, rank * 256, 2, sb + R_BAR + RB_INIT * 8);
            __syncwarp();
            wait_cnt_warp(g_gate, lds32(sb + S_GATE));
            if (p.dostats) x1_stats((head * 2 + rank) * 4 + w, lds32(sb + S_TAG));
            __syncthreads();
            cluster_sync();
            if ((p.chains >> (w >> 1)) & 1) rec_attn(p, sb, w >> 1, w & 1, head, rank);
        } else {
            reg_inc<RW0>();
            rec_weights(p, sb, head, rank, wi);
        }
    } else {
        if (wg == 2) {
            reg_dec<40>();
            const int w = wi & 3;
            if (w == 0) bulk_producer(p, sb, cl, rank); else if (w >= 2) bulk_release(p, sb, cl, rank, w - 2);
        } else { reg_inc<232>(); bulk_consumer(p, sb, cl, rank, wi); }
    }
    __syncwarp();
    cluster_sync();
}

typedef CUresult (*EncFn)(CUtensorMap*, CUtensorMapDataType, cuuint32_t, void*, const cuuint64_t*, const cuuint64_t*, const cuuint32_t*, const cuuint32_t*,
                          CUtensorMapInterleave, CUtensorMapSwizzle, CUtensorMapL2promotion, CUtensorMapFloatOOBfill);
inline uint32_t mk(int type, int layer, int ch, int a, int b, int c) { return type | (layer << 3) | (ch << 4) | (a << 8) | (b << 16) | ((uint32_t)c << 24); }
constexpr int SMEM_BYTES = 232448;

struct Sched {
    Params* P; int n[NCL];
    void clear() { memset(P->task, 0, sizeof(P->task)); memset(n, 0, sizeof(n)); }
    void add(int cl, uint32_t t) { if (n[cl] < MAXT - 1) P->task[cl][n[cl]++] = t; }
};

#define LAG 13
#define TS1 2400
#define TS2 2950
#define REC0 4
#define DQU 2450
#define DQO 1400
#define DHN 380
#define PUBN 600
#define DUN 5400
#define NQ1 4
#define FAST0 1
#define FAST1 14
#define MARG 1000
struct Plan { uint32_t w[NCL][MAXT]; int n[NCL]; double end, rec; };
void simulate(Plan& L, int nc, int n0, int nlong, int nuns, int ns2, int nhg, double hs) {
    const double INF = 1e18, DKB = 600, DOV = 700, DH = DHN, DHO = 1100, DF = 2200, DFB = 200, POLL = 450, FILL = 500, PUB = PUBN;
    enum { Q0, O0, Q1, HB, O1, FI, NK };
    struct Grp { int n, left; double done; } G[NK][16];
    double fr[NCL], it[100] = {}, cv[16];
    int ns[16], last[2][NCL], uc = 0, nit = 0;
    memset(L.n, 0, sizeof(L.n)); L.end = 0;
    auto fast = [&](int c) { return c < FAST0 || c >= FAST1; };
    for (int c = 0; c < 16; c++) {
        ns[c] = c < nuns ? 1 : c == 15 ? 16 : c == 14 ? 8 : ns2;
        const int cnt[NK] = {c < 2 ? 48 : (c & 1) ? 0 : 96, OPS1, c == 15 ? 24 : fast(c) ? 16 : 48 / NQ1, c >= 2 && !(c & 1) ? 16 : 0, ns[c], ns[c] == 1 ? 0 : c >= 14 ? 8 : 4};
        for (int k = 0; k < NK; k++) G[k][c] = {cnt[k], cnt[k], 0};
        cv[c] = INF;
    }
    for (int i = 0; i < nc; i++) { fr[i] = 0; last[0][i] = last[1][i] = -1; }
    auto fin = [&](int k, int c) { if ((k == Q0 && c >= 2) || k == HB) c &= ~1; return G[k][c].left ? INF : G[k][c].done; };
    auto len = [&](int i) { return (i >= LAG && i < 64) ? (double)TS2 : (double)TS1; };
    auto end_it = [&](int i) { return i < nit ? it[i] + len(i) : INF; };
    auto nominal = [&](int i) { if (i < nit) return it[i]; double t = nit ? it[nit - 1] : 11000 - TS1; for (int j = nit - 1; j < i; j++) t += len(j); return t; };
    auto put = [&](int i, uint32_t w) { if (L.n[i] < MAXT - 4) L.w[i][L.n[i]++] = w; else L.end = INF; };
    auto rel = [&](int k, int c) {
        switch (k) {
            case Q0: return 0.0;
            case O0: return end_it(4 * c + 3) + PUB + POLL;
            case Q1: return cv[c] + POLL;
            case HB: return cv[c - 2] + 600 + POLL;
            case O1: return end_it(LAG + 4 * c + 3) + PUB + POLL;
            default: return fin(O1, c) + POLL;
        }
    };
    auto dur = [&](int k, int c) {
        switch (k) {
            case Q0: return DQO + (c < 2 ? 2.0 : 1.0) * DQU;
            case O0: return ((63 + OPS1) / OPS1) * DKB + 800;
            case HB: return DHO + DH * c;
            case Q1: return DQO + 48.0 / G[Q1][c].n * DQU;
            case O1: return DOV + DKB * 64 / ns[c] + (ns[c] == 1 ? 1500 : 0);
            default: return DF + DFB * ns[c] * (c >= 14 ? 0.5 : 1);
        }
    };
    auto o0_est = [&](int c) {
        double t = uc ? cv[uc - 1] - 900 : 0;
        for (int j = uc; j < c; j++) t = fmax(t, nominal(4 * j + 4) + PUB + POLL + FILL) + dur(O0, j) + DUN;
        return fmax(t, nominal(4 * c + 4) + PUB + POLL);
    };
    auto cv_est = [&](int c) { return c < uc ? cv[c] : o0_est(c) + FILL + dur(O0, c) + DUN + 900; };
    auto first = [&](int k, int c) { return k == O0 || c == 15 ? 0 : OPS1; };
    while (true) {
        while (nit < 64 + LAG) {
            double t = nit ? end_it(nit - 1) : 0;
            if (nit < 64) t = fmax(t, fin(Q0, nit >> 2) + POLL);
            if (nit >= LAG) t = fmax(t, fin(Q1, (nit - LAG) >> 2) + (nit < 64 ? 0 : POLL));
            if (t >= INF) break;
            it[nit++] = t;
        }
        int i = -1;
        for (int j = 0; j < nc; j++) if (fr[j] < INF && (i < 0 || fr[j] < fr[i])) i = j;
        if (i < 0) break;
        const double t = fr[i];
        double lim = INF;
        if (i < 8 && last[0][i] == uc) {
            if (G[O0][uc].left || fin(HB, uc) >= INF) { fr[i] = t + 200; continue; }
            const double e = fmax(G[O0][uc].done, fin(HB, uc) - 2000) + DUN;
            for (int j = 0; j < 8; j++) { put(j, mk(T_CV, 0, uc, 2 * j, 0, 0)); fr[j] = e; }
            cv[uc++] = e + 900;
            continue;
        }
        const bool hg = (unsigned)(i - OPS1 - 48 / NQ1) < (unsigned)nhg;
        double hlim = INF;
        for (int c = 2; c < 16 && hg; c++) if (G[HB][c].left) { hlim = cv_est(c - 2) + hs; break; }
        int mine[2] = {-1, -1};
        for (int k = 0; k < 2; k++)
            for (int c = last[k][i] + 1; c < 16 && mine[k] < 0; c++) if ((unsigned)(i - first(O0 + k, c)) < (unsigned)G[O0 + k][c].n) mine[k] = c;
        if (mine[0] >= 0) lim = o0_est(mine[0]) - (i < 8 && !uc ? 8500 : 0);
        else if (mine[1] >= 0) lim = cv_est(mine[1]) + POLL;
        else if (i < 16 && G[O1][15].left) lim = fmin(lim, nominal(64 + LAG) + PUB);
        int bk = -1, bc = 0; double bd = INF;
        for (int k = 0; k < NK; k++)
            for (int c = 0; c < 16; c++) {
                const bool urgent = k == O0 || k == Q1 || (k == O1 && c == 15);
                if (!G[k][c].left || ((k == O0 || k == Q1) && c != mine[k - O0]) || (k == O1 && ns[c] == 1 && i < nc - nlong) || (k == O1 && c == 15 && i >= 16)) continue;
                if (rel(k, c) > t || (t + dur(k, c) + (k == Q0 && c >= 2 ? DQU : 0) > lim && !urgent)) continue;
                if (i < 8 && uc && uc < 16 && k != O0) continue;
                if ((k == HB && !hg) || (k != HB && !urgent && t + dur(k, c) + (k == Q0 && c >= 2 ? DQU : 0) > hlim)) continue;
                const double dl = urgent || (k == O1 && ns[c] == 1) ? -INF : k == HB ? -INF / 2 : k == Q0 ? nominal(4 * c) - 3000 : 1e9 + c * 2 + (k == O1);
                if (dl < bd) { bd = dl; bk = k; bc = c; }
            }
        if (bk < 0) {
            bool any = i < 8 && uc < 16;
            for (int k = 0; k < NK; k++) for (int c = 0; c < 16; c++) any = any || G[k][c].left;
            fr[i] = any ? t + 200 : INF;
            if (t > 400000) { L.end = INF; return; }
            continue;
        }
        Grp& g = G[bk][bc];
        const int n = g.n - g.left, c = bc;
        int nu = 1;
        double d = dur(bk, c);
        if (bk == Q0) for (nu = c < 2 ? 2 : 1; c >= 2 && nu < g.left && (nu < 2 || (nu < n0 && t + d + DQU < fmin(fmin(lim, hlim), bd - MARG))); nu++) d += DQU;
        if (bk == Q0 && !c && n >= 32) { nu = 1; d -= DQU; }
        if (bk == O0 || bk == Q1) last[bk - O0][i] = c;
        if (bk == O0 && !c && i < 8) put(i, mk(T_CV, 0, 3, 2 * i, 0, 128));
        g.left -= nu;
        const double e = fmax(t, rel(bk, c) + FILL) + (t < 1 ? 4500 : 0) + d;
        fr[i] = e;
        g.done = fmax(g.done, e + (bk == O1 ? 1900 : bk == O0 ? 0 : (bk == Q1 && g.n < 24) || (bk == Q0 && !c && nu == 2) ? -500 : 1000));
        if (bk == FI || (bk == O1 && ns[c] == 1)) L.end = fmax(L.end, e);
        put(i, bk == Q0 ? (c == 0 ? mk(T_QKV, 0, 0, n < 32 ? n : 2 * n - 32, nu, 32) : c == 1 ? mk(T_QKV, 0, c, n, 2, 24) : mk(T_QKV, 0, c, n, nu, 64))
             : bk == O0 ? mk(T_OP, 0, c, i * 64 / OPS1, (i + 1) * 64 / OPS1 - i * 64 / OPS1, i)
             : bk == HB ? mk(T_CV, 1, c, 2 * n, 0, 0)
             : bk == Q1 ? mk(T_QKV, 1, c, (i - first(Q1, c)) * 2, 48 / g.n, g.n)
             : bk == O1 ? mk(T_OP, 1, c, n * 64 / ns[c], 64 / ns[c], ns[c] == 1 ? 32 : n)
                        : mk(T_FIN, 1, c, n * (32 / g.n), ns[c], 16 / g.n));
    }
    L.rec = end_it(63 + LAG);
}
void plan(Params& P) {
    P.rec0 = REC0; P.chains = 3; P.lag = LAG; P.dostats = 1; P.dopro = 1;
    static Plan L, T;
    int cls[NCL], nc = 0;
    for (int c = REC0 + 32; c < NCL; c++) cls[nc++] = c;
    for (int c = REC0 - 1; c >= 0; c--) cls[nc++] = c;
    L.end = 1e18;
    for (int n0 = 10; n0 >= 4; n0 -= 2)
        for (int nuns = 0; nuns <= 6; nuns += 3)
            for (int ns2 = 8; ns2 >= 4; ns2 -= 4)
                for (int v = 0; v < 4; v++) {
                    const int nhg = (v & 1) ? 6 : 8, hs = (v & 2) ? 4000 : 2000;
                    simulate(T, nc, n0, nuns > 3 ? 2 : 1, nuns, ns2, nhg, hs);
                    if (T.end < L.end) {
                        L = T;
                    }
                }
    Sched S; S.P = &P; S.clear();
    S.add(0, mk(T_QKV, 1, 15, 0, 2, 128 + 24)); S.add(0, mk(T_OP, 1, 15, 0, 4, 128));
    S.add(1, mk(T_CV, 0, 3, 0, 0, 128));
    for (int i = 0; i < nc; i++) {
        bool warm = false;
        for (int k = 0; k < L.n[i]; k++) {
            if (!warm && k + 1 < L.n[i] && (L.w[i][k + 1] & 255) == (mk(T_FIN, 1, 15, 0, 0, 0) & 255)) { S.add(cls[i], L.w[i][k + 1] | 0x80000000u); warm = true; }
            S.add(cls[i], L.w[i][k]);
            if ((L.w[i][k] & 7) == T_FIN) warm = true;
        }
    }
}

#define TK0() do {} while (0)
#define TK() do { P.e0 = (P.chains & 1) ? 64 : 0; P.b1 = (P.chains & 2) ? P.lag : 1000; P.nit = (P.chains & 2) ? P.lag + 64 : 64; TK0(); } while (0)
}

extern "C" void kernel_launch(void* const* d_in, const int* in_sizes, int n_in, void* d_out, int out_size) {
    typedef const __nv_bfloat16* BP;
    static EncFn enc = nullptr;
    if (!enc) {
        void* fn = nullptr; cudaDriverEntryPointQueryResult qr;
        cudaGetDriverEntryPoint("cuTensorMapEncodeTiled", &fn, cudaEnableDefault, &qr);
        enc = (EncFn)fn;
        cudaFuncSetAttribute(main_kernel, cudaFuncAttributeMaxDynamicSharedMemorySize, SMEM_BYTES);
    }
    static Params P;
    for (int i = 0; i < 4; i++) {
        const cuuint64_t cols = i < 3 ? 4096 : 512, rows = i < 3 ? 512 : 4096;
        cuuint64_t d2[2] = {cols, rows}, d3[3] = {64, rows, cols / 64}, str[2] = {cols * 2, 128};
        cuuint32_t box[3] = {64, 64, 4}, es[3] = {1, 1, 1};
        enc(&P.tm[i < 3 ? i : 4], CU_TENSOR_MAP_DATA_TYPE_BFLOAT16, 2, d_in[9 + i], d2, str, box, es, CU_TENSOR_MAP_INTERLEAVE_NONE, CU_TENSOR_MAP_SWIZZLE_128B,
                       CU_TENSOR_MAP_L2_PROMOTION_L2_128B, CU_TENSOR_MAP_FLOAT_OOB_FILL_NONE);
        for (int m = 0; m < 2; m++) {
            cuuint32_t box3[3] = {64, 32, m ? 2u : 4u};
            enc(&P.t3[m][i], CU_TENSOR_MAP_DATA_TYPE_BFLOAT16, 3, d_in[9 + i], d3, str, box3, es, CU_TENSOR_MAP_INTERLEAVE_NONE, CU_TENSOR_MAP_SWIZZLE_128B,
                CU_TENSOR_MAP_L2_PROMOTION_L2_128B, CU_TENSOR_MAP_FLOAT_OOB_FILL_NONE);
        }
    }
    {
        cuuint64_t dims[2] = {512, 2048}, str[1] = {1024};
        cuuint32_t box[2] = {8, 256}, es[2] = {1, 1};
        enc(&P.tm[3], CU_TENSOR_MAP_DATA_TYPE_BFLOAT16, 2, d_in[0], dims, str, box, es, CU_TENSOR_MAP_INTERLEAVE_NONE, CU_TENSOR_MAP_SWIZZLE_NONE,
            CU_TENSOR_MAP_L2_PROMOTION_NONE, CU_TENSOR_MAP_FLOAT_OOB_FILL_NONE);
    }
    for (int m = 0; m < 2; m++) {
        void* ga; cudaGetSymbolAddress(&ga, g_A);
        cuuint64_t dims[2] = {512, sizeof(AOps) / 1024}, str[1] = {1024};
        cuuint32_t box[2] = {256, m ? 16u : 8u}, es[2] = {1, 1};
        enc(&P.ta[m], CU_TENSOR_MAP_DATA_TYPE_BFLOAT16, 2, ga, dims, str, box, es, CU_TENSOR_MAP_INTERLEAVE_NONE, CU_TENSOR_MAP_SWIZZLE_NONE,
            CU_TENSOR_MAP_L2_PROMOTION_L2_128B, CU_TENSOR_MAP_FLOAT_OOB_FILL_NONE);
    }
    P.mem0 = (BP)d_in[8]; P.Wo = (BP)d_in[12]; P.Dskip = (BP)d_in[6]; P.out = (__nv_bfloat16*)d_out;
    cudaStream_t s = cudaStreamPerThread;
    P.pa = {(BP)d_in[0], (BP)d_in[1], (BP)d_in[2], (BP)d_in[3], (BP)d_in[4], (BP)d_in[5], (BP)d_in[6], (BP)d_in[9], (BP)d_in[10], (BP)d_in[11], (BP)d_in[12], (BP)d_in[8]};
    static bool planned = false;
    if (!planned) { plan(P); planned = true; }
    TK(); main_kernel<<<2 * NCL, 384, SMEM_BYTES, s>>>(P); TK();
}
```

```cpp
#include <cuda_runtime.h>
#include <cuda_bf16.h>
#include <cuda.h>
#include <stdint.h>
#include <string.h>
#include <math.h>

namespace {

constexpr int NCL = 66;
constexpr int MAXT = 64;
#define PFC 1
#define OPS1N 10
constexpr int OPS1 = OPS1N;
constexpr int MAXSPLIT = 16;
constexpr int PW = 144;

struct AOps { uint4 x[2][16 * 8 * 1024], o[2][16 * 64 * 1024]; };
__device__ AOps g_A;
#define g_xA g_A.x
#define g_o g_A.o
__device__ float2 g_st[2][16 * 2048];
__device__ float2 g_st2[2 * 16 * 128];
__device__ uint4 g_qkv[2][64 * 64 * 768];
__device__ uint4 g_pp[2][16 * MAXSPLIT * 8192];
__device__ uint4 g_acc[7 * 2048];
__device__ unsigned g_gate[32];
__device__ uint32_t g_P[16 * 16 * 32 * PW];
__device__ uint4 g_u[16 * 16 * 512];
__device__ float4 g_carry[2][17 * 16 * 4 * 256];
__device__ unsigned g_cnt[13 * 64];
__device__ uint32_t g_ln0[2048];

enum { C_QKV0 = 0, C_QKV1 = 1  , C_O0 = 2, C_O1 = 3, C_U = 4, C_OP1 = 5, C_CV = 6, C_ST = 7, C_H = 8, C_OP0 = 9   };
__device__ __forceinline__ unsigned* cnt_ptr(int kind, int chunk) { return g_cnt + kind * 64 + chunk; }

enum { T_END = 0, T_QKV = 1, T_OP = 2, T_CV = 3, T_FIN = 4 };
struct ProArgs { const __nv_bfloat16 *x, *lAr, *Ai, *Cr, *Ci, *ldt, *Dk, *Wq, *Wk, *Wv, *Wo, *mem0; };
struct Params {
    CUtensorMap tm[5];
    CUtensorMap t3[2][4];
    CUtensorMap ta[2];
    ProArgs pa;
    int dopro;
    const __nv_bfloat16* mem0;
    const __nv_bfloat16* Wo;
    const __nv_bfloat16* Dskip;
    __nv_bfloat16* out;
    int rec0;
    int chains;
    int lag;
    int b1, e0, nit;
    int zero, gpit;
    int dostats;
    uint32_t task[NCL][MAXT];
};

__device__ __forceinline__ uint32_t smem_u32(const void* p) { return (uint32_t)__cvta_generic_to_shared(p); }
__device__ __forceinline__ uint32_t mapa(uint32_t a, uint32_t r) {
    uint32_t o; asm("mapa.shared::cluster.u32 %0,%1,%2;" : "=r"(o) : "r"(a), "r"(r)); return o;
}
__device__ __forceinline__ void mbar_init(uint32_t b, int c) { asm volatile("mbarrier.init.shared::cta.b64 [%0],%1;" ::"r"(b), "r"(c) : "memory"); }
__device__ __forceinline__ void mbar_expect(uint32_t b, int bytes) { asm volatile("mbarrier.arrive.expect_tx.shared::cta.b64 _,[%0],%1;" ::"r"(b), "r"(bytes) : "memory"); }
__device__ __forceinline__ void mbar_arrive(uint32_t b) { asm volatile("mbarrier.arrive.shared::cta.b64 _,[%0];" ::"r"(b) : "memory"); }
__device__ __forceinline__ void mbar_arrive_cluster(uint32_t b) { asm volatile("mbarrier.arrive.shared::cluster.b64 _,[%0];" ::"r"(b) : "memory"); }
__device__ __forceinline__ void mbar_arrive1(uint32_t b) { asm volatile("{.reg .pred p; elect.sync _|p,0xffffffff; @p mbarrier.arrive.shared::cta.b64 _,[%0];}" ::"r"(b) : "memory"); }
__device__ __forceinline__ void mbar_arrive1_cluster(uint32_t b) { asm volatile("{.reg .pred p; elect.sync _|p,0xffffffff; @p mbarrier.arrive.shared::cluster.b64 _,[%0];}" ::"r"(b) : "memory"); }
__device__ __forceinline__ void mbar_wait(uint32_t b, uint32_t ph) {
    asm volatile(
        "{.reg .pred p; .reg .u32 n; mov.u32 n,0;\n"
        "W%=: mbarrier.try_wait.parity.shared::cta.b64 p,[%0],%1;\n"
        "@p bra D%=;\n"
        "add.u32 n,n,1; setp.lt.u32 p,n,2000000; @p bra W%=;\n"
        "trap;\n"
        "D%=: }" ::"r"(b), "r"(ph) : "memory");
}
__device__ __forceinline__ bool mbar_test(uint32_t b, uint32_t ph) {
    uint32_t ok;
    asm volatile("{.reg .pred p; mbarrier.test_wait.parity.shared::cta.b64 p,[%1],%2; selp.u32 %0,1,0,p;}" : "=r"(ok) : "r"(b), "r"(ph) : "memory");
    return ok;
}
__device__ __forceinline__ bool wait_lds128(uint32_t b, uint32_t ph, uint32_t a, uint4& v) {
    uint32_t ok;
    asm volatile("{.reg .pred p; mbarrier.try_wait.parity.shared::cta.b64 p,[%5],%6,20000; ld.shared.v4.u32 {%0,%1,%2,%3},[%7]; selp.u32 %4,1,0,p;}"
                 : "=r"(v.x), "=r"(v.y), "=r"(v.z), "=r"(v.w), "=r"(ok) : "r"(b), "r"(ph), "r"(a) : "memory");
    return ok;
}
__device__ __forceinline__ bool wait_lds64(uint32_t b, uint32_t ph, uint32_t a, uint2& v) {
    uint32_t ok;
    asm volatile("{.reg .pred p; mbarrier.try_wait.parity.shared::cta.b64 p,[%3],%4,20000; ld.shared.v2.u32 {%0,%1},[%5]; selp.u32 %2,1,0,p;}"
                 : "=r"(v.x), "=r"(v.y), "=r"(ok) : "r"(b), "r"(ph), "r"(a) : "memory");
    return ok;
}
template <int PH> __device__ __forceinline__ void mbar_wait_c(uint32_t b) {
    asm volatile(
        "{.reg .pred p; .reg .u32 n; mov.u32 n,%2;\n"
        "W%=: mbarrier.try_wait.parity.shared::cta.b64 p,[%0],%1;\n"
        "@p bra D%=;\n"
        "add.u32 n,n,1; setp.lt.u32 p,n,2000000; @p bra W%=;\n"
        "trap;\n"
        "D%=: }" ::"r"(b), "n"(PH), "n"(PH) : "memory");
}
__device__ __forceinline__ void bar_sync(int id, int n) { asm volatile("bar.sync %0,%1;" ::"r"(id), "r"(n) : "memory"); }
__device__ __forceinline__ void bar_arrive(int id, int n) { asm volatile("bar.arrive %0,%1;" ::"r"(id), "r"(n) : "memory"); }
__device__ __forceinline__ void cluster_sync() { asm volatile("barrier.cluster.arrive.relaxed.aligned; barrier.cluster.wait.aligned;" ::: "memory"); }
__device__ __forceinline__ void fence_async() { asm volatile("fence.proxy.async;" ::: "memory"); }
__device__ __forceinline__ void fence_async_smem() { asm volatile("fence.proxy.async.shared::cta;" ::: "memory"); }
#define EFR 1
#define EFW 2
constexpr uint64_t POL_N = 0x1000000000000000ull, POL_F = 0x12F0000000000000ull;
constexpr uint64_t POL_LAST = EFR ? POL_F : POL_N  , POL_LATE = EFW ? POL_F : POL_N  , POL_SOON = EFW > 1 ? POL_F : POL_N;
__device__ __forceinline__ void bulk_g2s(uint32_t dst, const void* src, int bytes, uint32_t bar, uint64_t pol) {
    asm volatile("cp.async.bulk.shared::cluster.global.mbarrier::complete_tx::bytes.L2::cache_hint [%0],[%1],%2,[%3],%4;" ::"r"(dst), "l"(src), "r"(bytes), "r"(bar), "l"(pol) : "memory");
}
__device__ __forceinline__ void bulk_g2s_mc(uint32_t dst, const void* src, int bytes, uint32_t bar, uint64_t pol) {
    asm volatile("cp.async.bulk.shared::cluster.global.mbarrier::complete_tx::bytes.multicast::cluster.L2::cache_hint [%0],[%1],%2,[%3],%4,%5;" ::"r"(dst), "l"(src), "r"(bytes), "r"(bar), "h"((uint16_t)3), "l"(pol) : "memory");
}
__device__ __forceinline__ void bulk_s2s(uint32_t dst, uint32_t src, int bytes, uint32_t bar) {
    asm volatile("cp.async.bulk.shared::cluster.shared::cta.mbarrier::complete_tx::bytes [%0],[%1],%2,[%3];" ::"r"(dst), "r"(src), "r"(bytes), "r"(bar) : "memory");
}
__device__ __forceinline__ bool elect() {
    uint32_t r; asm volatile("{.reg .pred p; elect.sync _|p,0xffffffff; selp.u32 %0,1,0,p;}" : "=r"(r)); return r;
}
__device__ __forceinline__ void stg128(uint4* p, uint4 v, uint64_t pol) {
    asm volatile("st.global.L2::cache_hint.v4.u32 [%0],{%1,%2,%3,%4},%5;" ::"l"(p), "r"(v.x), "r"(v.y), "r"(v.z), "r"(v.w), "l"(pol));
}
__device__ __forceinline__ void stg32(uint32_t* p, uint32_t v, uint64_t pol) { asm volatile("st.global.L2::cache_hint.u32 [%0],%1,%2;" ::"l"(p), "r"(v), "l"(pol)); }
__device__ __forceinline__ uint4 ldcg128_last(const uint4* p) {
    uint4 v; asm volatile("ld.global.cg.L2::cache_hint.v4.u32 {%0,%1,%2,%3},[%4],%5;" : "=r"(v.x), "=r"(v.y), "=r"(v.z), "=r"(v.w) : "l"(p), "l"(POL_LAST) : "memory"); return v;
}
__device__ __forceinline__ void tma2d(uint32_t dst, const CUtensorMap* tm, int x, int y, uint32_t bar) {
    asm volatile("cp.async.bulk.tensor.2d.shared::cluster.global.mbarrier::complete_tx::bytes [%0],[%1,{%2,%3}],[%4];" ::"r"(dst), "l"(tm), "r"(x), "r"(y), "r"(bar) : "memory");
}
__device__ __forceinline__ void tma3d_mc(uint32_t dst, const CUtensorMap* tm, int y, int z, uint32_t bar, uint16_t mask) {
    asm volatile("{.reg .pred p; elect.sync _|p,0xffffffff;\n"
                 "@p cp.async.bulk.tensor.3d.shared::cluster.global.mbarrier::complete_tx::bytes.multicast::cluster [%0],[%1,{0,%2,%3}],[%4],%5;}"
                 ::"r"(dst), "l"(tm), "r"(y), "r"(z), "r"(bar), "h"(mask) : "memory");
}
__device__ __forceinline__ void tma2d_mc(uint32_t dst, const CUtensorMap* tm, int x, int y, uint32_t bar, uint16_t mask, uint64_t pol) {
    asm volatile("{.reg .pred p; elect.sync _|p,0xffffffff;\n"
                 "@p cp.async.bulk.tensor.2d.shared::cluster.global.mbarrier::complete_tx::bytes.multicast::cluster.L2::cache_hint [%0],[%1,{%2,%3}],[%4],%5,%6;}"
                 ::"r"(dst), "l"(tm), "r"(x), "r"(y), "r"(bar), "h"(mask), "l"(pol) : "memory");
}
__device__ __forceinline__ void bulk_g2s1(uint32_t dst, const void* src, int bytes, uint32_t bar, uint64_t pol) {
    asm volatile("{.reg .pred p; elect.sync _|p,0xffffffff;\n"
                 "@p cp.async.bulk.shared::cluster.global.mbarrier::complete_tx::bytes.L2::cache_hint [%0],[%1],%2,[%3],%4;}" ::"r"(dst), "l"(src), "r"(bytes), "r"(bar), "l"(pol) : "memory");
}
__device__ __forceinline__ void mbar_expect1(uint32_t b, int bytes) {
    asm volatile("{.reg .pred p; elect.sync _|p,0xffffffff; @p mbarrier.arrive.expect_tx.shared::cta.b64 _,[%0],%1;}" ::"r"(b), "r"(bytes) : "memory");
}
__device__ __forceinline__ void st_async4(uint32_t a, uint32_t x, uint32_t y, uint32_t z, uint32_t w, uint32_t mb) {
    asm volatile("st.async.shared::cluster.mbarrier::complete_tx::bytes.v4.b32 [%0],{%1,%2,%3,%4},[%5];" ::"r"(a), "r"(x), "r"(y), "r"(z), "r"(w), "r"(mb) : "memory");
}
__device__ __forceinline__ void st_async2(uint32_t a, uint32_t x, uint32_t y, uint32_t mb) {
    asm volatile("st.async.shared::cluster.mbarrier::complete_tx::bytes.v2.b32 [%0],{%1,%2},[%3];" ::"r"(a), "r"(x), "r"(y), "r"(mb) : "memory");
}
#define LDSQ "ld.shared"
__device__ __forceinline__ uint4 lds128(uint32_t a) { uint4 v; asm volatile(LDSQ ".v4.u32 {%0,%1,%2,%3},[%4];" : "=r"(v.x), "=r"(v.y), "=r"(v.z), "=r"(v.w) : "r"(a) : "memory"); return v; }
__device__ __forceinline__ uint2 lds64(uint32_t a) { uint2 v; asm volatile(LDSQ ".v2.u32 {%0,%1},[%2];" : "=r"(v.x), "=r"(v.y) : "r"(a) : "memory"); return v; }
__device__ __forceinline__ uint32_t lds32(uint32_t a) { uint32_t v; asm volatile(LDSQ ".u32 %0,[%1];" : "=r"(v) : "r"(a) : "memory"); return v; }
__device__ __forceinline__ void sts128(uint32_t a, uint32_t x, uint32_t y, uint32_t z, uint32_t w) { asm volatile("st.shared.v4.u32 [%0],{%1,%2,%3,%4};" ::"r"(a), "r"(x), "r"(y), "r"(z), "r"(w) : "memory"); }
__device__ __forceinline__ void sts64(uint32_t a, uint32_t x, uint32_t y) { asm volatile("st.shared.v2.u32 [%0],{%1,%2};" ::"r"(a), "r"(x), "r"(y) : "memory"); }
__device__ __forceinline__ void sts32(uint32_t a, uint32_t x) { asm volatile("st.shared.u32 [%0],%1;" ::"r"(a), "r"(x) : "memory"); }
__device__ __forceinline__ uint4 ldsm4(uint32_t a) { uint4 v; asm volatile("ldmatrix.sync.aligned.m8n8.x4.shared.b16 {%0,%1,%2,%3},[%4];" : "=r"(v.x), "=r"(v.y), "=r"(v.z), "=r"(v.w) : "r"(a) : "memory"); return v; }
__device__ __forceinline__ uint4 ldsm4t(uint32_t a) { uint4 v; asm volatile("ldmatrix.sync.aligned.m8n8.x4.trans.shared.b16 {%0,%1,%2,%3},[%4];" : "=r"(v.x), "=r"(v.y), "=r"(v.z), "=r"(v.w) : "r"(a) : "memory"); return v; }
__device__ __forceinline__ uint32_t movm(uint32_t a) { uint32_t d; asm volatile("movmatrix.sync.aligned.m8n8.trans.b16 %0,%1;" : "=r"(d) : "r"(a)); return d; }
__device__ __forceinline__ uint32_t pack2(float lo, float hi) { uint32_t d; asm("cvt.rn.bf16x2.f32 %0,%1,%2;" : "=r"(d) : "f"(hi), "f"(lo)); return d; }
__device__ __forceinline__ uint32_t hadd2(uint32_t a, uint32_t b) { uint32_t d; asm("add.rn.bf16x2 %0,%1,%2;" : "=r"(d) : "r"(a), "r"(b)); return d; }
__device__ __forceinline__ float blo(uint32_t v) { return __uint_as_float(v << 16); }
__device__ __forceinline__ float bhi(uint32_t v) { return __uint_as_float(v & 0xffff0000u); }
__device__ __forceinline__ float rbf(float x) { return __uint_as_float(pack2(0.f, x)); }
__device__ __forceinline__ float ex2(float x) { float y; asm("ex2.approx.ftz.f32 %0,%1;" : "=f"(y) : "f"(x)); return y; }
__device__ __forceinline__ float rcp(float x) { float y; asm("rcp.approx.ftz.f32 %0,%1;" : "=f"(y) : "f"(x)); return y; }
__device__ __forceinline__ void mma16(float* c, uint32_t a0, uint32_t a1, uint32_t a2, uint32_t a3, uint32_t b0, uint32_t b1) {
    asm volatile("mma.sync.aligned.m16n8k16.row.col.f32.bf16.bf16.f32 {%0,%1,%2,%3},{%4,%5,%6,%7},{%8,%9},{%0,%1,%2,%3};"
                 : "+f"(c[0]), "+f"(c[1]), "+f"(c[2]), "+f"(c[3]) : "r"(a0), "r"(a1), "r"(a2), "r"(a3), "r"(b0), "r"(b1));
}
__device__ __forceinline__ void mma8(float* c, uint32_t a0, uint32_t a1, uint32_t b0) {
    asm volatile("mma.sync.aligned.m16n8k8.row.col.f32.bf16.bf16.f32 {%0,%1,%2,%3},{%4,%5},{%6},{%0,%1,%2,%3};"
                 : "+f"(c[0]), "+f"(c[1]), "+f"(c[2]), "+f"(c[3]) : "r"(a0), "r"(a1), "r"(b0));
}
__device__ __forceinline__ uint4 ld_rlx128(const uint4* p) {
    uint4 v;
    asm volatile("{.reg .b128 t; ld.relaxed.gpu.global.b128 t,[%4]; mov.b128 {%0,%1,%2,%3},t;}" : "=r"(v.x), "=r"(v.y), "=r"(v.z), "=r"(v.w) : "l"(p) : "memory");
    return v;
}
__device__ __forceinline__ void st_rlx128(uint4* p, uint32_t x, uint32_t y, uint32_t z, uint32_t w) {
    asm volatile("{.reg .b128 t; mov.b128 t,{%1,%2,%3,%4}; st.relaxed.gpu.global.b128 [%0],t;}" ::"l"(p), "r"(x), "r"(y), "r"(z), "r"(w) : "memory");
}
__device__ __forceinline__ uint4 ldcg128(const uint4* p) { uint4 v; asm volatile("ld.global.cg.v4.u32 {%0,%1,%2,%3},[%4];" : "=r"(v.x), "=r"(v.y), "=r"(v.z), "=r"(v.w) : "l"(p) : "memory"); return v; }
__device__ __forceinline__ void red_release(unsigned* p, unsigned v) {
    asm volatile("fence.proxy.async; red.relaxed.gpu.global.add.u32 [%0],%1;" ::"l"(p), "r"(v) : "memory");
}
__device__ __forceinline__ void wait_cnt(const unsigned* p, unsigned target) {
    unsigned v; int n = 0;
    while (true) {
        asm volatile("ld.acquire.gpu.global.u32 %0,[%1];" : "=r"(v) : "l"(p) : "memory");
        if (v >= target) break;
        if (++n > 3000000) __trap();
        __nanosleep(40);
    }
}
__device__ __forceinline__ void wait_cnt_warp(const unsigned* p, unsigned target) {
    unsigned v; int n = 0;
    while (true) {
        asm volatile("ld.acquire.gpu.global.u32 %0,[%1];" : "=r"(v) : "l"(p) : "memory");
        if (__all_sync(0xffffffffu, v >= target)) break;
        if (++n > 3000000) __trap();
    }
}
__device__ __forceinline__ uint64_t mkdesc(uint32_t addr, uint32_t lbo, uint32_t sbo, uint32_t sw) {
    return (uint64_t)((addr & 0x3FFFF) >> 4) | ((uint64_t)(lbo >> 4) << 16) | ((uint64_t)(sbo >> 4) << 32) | ((uint64_t)sw << 62);
}
__device__ __forceinline__ void wg_fence() { asm volatile("wgmma.fence.sync.aligned;" ::: "memory"); }
__device__ __forceinline__ void wg_commit() { asm volatile("wgmma.commit_group.sync.aligned;" ::: "memory"); }
template <int N> __device__ __forceinline__ void wg_wait() { asm volatile("wgmma.wait_group.sync.aligned %0;" ::"n"(N) : "memory"); }
#define R8(c, o) "+f"(c[o]), "+f"(c[o + 1]), "+f"(c[o + 2]), "+f"(c[o + 3]), "+f"(c[o + 4]), "+f"(c[o + 5]), "+f"(c[o + 6]), "+f"(c[o + 7])
#define R32(c, o) R8(c, o), R8(c, o + 8), R8(c, o + 16), R8(c, o + 24)
#define S32A "%0,%1,%2,%3,%4,%5,%6,%7,%8,%9,%10,%11,%12,%13,%14,%15,%16,%17,%18,%19,%20,%21,%22,%23,%24,%25,%26,%27,%28,%29,%30,%31"
#define S32B ",%32,%33,%34,%35,%36,%37,%38,%39,%40,%41,%42,%43,%44,%45,%46,%47,%48,%49,%50,%51,%52,%53,%54,%55,%56,%57,%58,%59,%60,%61,%62,%63"
#define S32C ",%64,%65,%66,%67,%68,%69,%70,%71,%72,%73,%74,%75,%76,%77,%78,%79,%80,%81,%82,%83,%84,%85,%86,%87,%88,%89,%90,%91,%92,%93,%94,%95"
#define S32D ",%96,%97,%98,%99,%100,%101,%102,%103,%104,%105,%106,%107,%108,%109,%110,%111,%112,%113,%114,%115,%116,%117,%118,%119,%120,%121,%122,%123,%124,%125,%126,%127"
#define W8(c, o) "=f"(c[o]), "=f"(c[o + 1]), "=f"(c[o + 2]), "=f"(c[o + 3]), "=f"(c[o + 4]), "=f"(c[o + 5]), "=f"(c[o + 6]), "=f"(c[o + 7])
#define W32(c, o) W8(c, o), W8(c, o + 8), W8(c, o + 16), W8(c, o + 24)
template <bool ACC> __device__ __forceinline__ void wgmma256(float* c, uint64_t da, uint64_t db) {
    if (ACC) asm volatile("wgmma.mma_async.sync.aligned.m64n256k16.f32.bf16.bf16 {" S32A S32B S32C S32D "},%128,%129,1,1,1,0,1;"
                          : R32(c, 0), R32(c, 32), R32(c, 64), R32(c, 96) : "l"(da), "l"(db));
    else asm volatile("wgmma.mma_async.sync.aligned.m64n256k16.f32.bf16.bf16 {" S32A S32B S32C S32D "},%128,%129,0,1,1,0,1;"
                      : W32(c, 0), W32(c, 32), W32(c, 64), W32(c, 96) : "l"(da), "l"(db));
}
template <bool ACC> __device__ __forceinline__ void wgmma128r(float* c, const uint4& a, uint64_t db) {
    if (ACC) asm volatile("wgmma.mma_async.sync.aligned.m64n128k16.f32.bf16.bf16 {" S32A S32B "},{%64,%65,%66,%67},%68,1,1,1,1;"
                          : R32(c, 0), R32(c, 32) : "r"(a.x), "r"(a.y), "r"(a.z), "r"(a.w), "l"(db));
    else asm volatile("wgmma.mma_async.sync.aligned.m64n128k16.f32.bf16.bf16 {" S32A S32B "},{%64,%65,%66,%67},%68,0,1,1,1;"
                      : W32(c, 0), W32(c, 32) : "r"(a.x), "r"(a.y), "r"(a.z), "r"(a.w), "l"(db));
}
template <int N> __device__ __forceinline__ void reg_inc() { asm volatile("setmaxnreg.inc.sync.aligned.u32 %0;" ::"n"(N)); }
template <int N> __device__ __forceinline__ void reg_dec() { asm volatile("setmaxnreg.dec.sync.aligned.u32 %0;" ::"n"(N)); }

#define PROF(cond, idx) do {} while (0)
#define CPROF(k) do {} while (0)

constexpr int S_GATE = 232440, S_TAG = 232444, S_XBAR = 232432;
constexpr float SC_LOG2E = 0.08838834764831845f * 1.4426950408889634f;

__device__ __forceinline__ float2 ln_finish(float mean, float var) {
    float sd; asm("sqrt.approx.f32 %0,%1;" : "=f"(sd) : "f"(rbf(rbf(var) + 1e-5f)));
    sd = rbf(sd);
    return make_float2(rbf(mean), sd);
}

__device__ __forceinline__ float2 row_stats512(const uint4* src, int s1, int s2) {
    const int g = (threadIdx.x & 31) >> 2;
    uint4 v[16];
#pragma unroll
    for (int i = 0; i < 16; i++) v[i] = ldcg128(src + (i >> 1) * s1 + (i & 1) * s2);
    float a[4] = {0, 0, 0, 0}, q0[4] = {0, 0, 0, 0}, q1[4] = {0, 0, 0, 0};
#pragma unroll
    for (int i = 0; i < 16; i++) {
        mma16(a, v[i].x, v[i].y, v[i].z, v[i].w, 0x3f803f80u, 0x3f803f80u);
        mma8(q0, v[i].x, v[i].y, v[i].x); mma8(q1, v[i].x, v[i].y, v[i].y);
        mma8(q0, v[i].z, v[i].w, v[i].z); mma8(q1, v[i].z, v[i].w, v[i].w);
    }
    const float sum = a[0] + a[2], sq = (g & 1) ? q0[1] + q1[3] : q0[0] + q1[2];
    return make_float2(sum, sq);
}
__device__ __forceinline__ void x1_stats(int rg, int tag) {
    const int lane = threadIdx.x & 31, g = lane >> 2, c = lane & 3;
    const float2 r = row_stats512(g_xA[0] + (rg >> 4) * 8192 + (rg & 15) * 64 + c * 8 + g, 1024, 32);
    if (c == (g >> 1)) { g_st[0][(rg >> 4) * 2048 + (rg < 32 ? 2 : tag) * 128 + (rg & 15) * 8 + g] = r; g_ln0[rg * 8 + g] = 0; }
    __syncwarp();
    if (lane == 0) red_release(cnt_ptr(C_ST, rg >> 4), 1);
}
__global__ void stats_kernel() { x1_stats(blockIdx.x * 4 + (threadIdx.x >> 5), (g_gate[0] / (4 * NCL)) & 1); }

#define NT 9
#define RH 104
#define RW0 200
#define NPD 9
#define NTO 13
#define DP1 9
#define GPW 0
#define GPJ 0
#define PACE 2
#define BKA 0
#define GSE 4
#define EARLY 4
#define PFD 0
#define PFB 0
#define G2S 7
#define STO 1
#define G2I 2
#define VE 4
#define VF 8
constexpr int TILE = 20480;
constexpr int R_WV = 0, R_WO = 65536, R_T = 131072, R_M = R_T + 2 * TILE  , R_LOC = R_M + 8192  ,
              R_REM = R_LOC + 12288  , R_O = R_REM + 24576  , R_SX = R_O + 4096  ,
              R_IL = R_SX + 10240  , R_BAR = 231936, R_Z = R_BAR + 128  , R_STQ = 0, R_STK = 65536, R_STV = 131072;
static_assert(R_IL + 512 <= R_BAR && R_BAR + 256 <= S_XBAR, "smem map");
enum { RB_INIT = 0, RB_MB = 1, RB_V = 4  , RB_QK = 8  , RB_T = 12  , RB_N = 16 };
enum { NB_MF = 1  , NB_LOC = 3  , NB_PAIR = 5  , NB_O = 9  , NB_XG = 11  , NB_W = 13 };
__device__ __forceinline__ uint32_t clk32() { return (uint32_t)clock64(); }

__device__ __forceinline__ char* acc_base() { return (char*)(((size_t)g_acc + 131071) & ~(size_t)131071); }
__device__ __forceinline__ uint32_t acc_slice(uint32_t s6) { return (s6 & 1) * 256 + (s6 >> 1) * 1024; }
__device__ __forceinline__ uint32_t acc_main(uint32_t rank, uint32_t tid) { return acc_slice(rank * 32 + (tid >> 3)) + (tid & 7) * 16; }
__device__ __forceinline__ uint32_t acc_extra(uint32_t rank, uint32_t tid) { return 65536 + acc_slice(((tid >> 5) & 1) + rank * 4 + (tid >> 6) * 8) + (tid & 31) * 4; }
__device__ __forceinline__ uint32_t acc_slot(uint32_t s) { return (s & 1) * 128 + (s & 2) * 256; }
__device__ __forceinline__ void acc_init(const __nv_bfloat16* mem0, int i) {
    const uint32_t tid = i & 255, rank = (i >> 8) & 1, slot = (i >> 9) & 3, X = i >> 11;
    uint32_t v[5] = {0, 0, 0, 0, 0};
    if (slot == 3) {
        const uint16_t* m = (const uint16_t*)mem0 + (tid & 3) * 1024 + rank * 256 + (tid >> 5) * 32 + ((tid >> 2) & 7);
#pragma unroll
        for (int k = 0; k < 4; k++) v[k] = __ldg(m + k * 8) | ((uint32_t)__ldg(m + k * 8 + 512) << 16);
        v[4] = (v[3] >> 16) | 0x42000000u; v[3] = (v[3] & 0xffff) | 0x42000000u;
    }
    *(uint4*)(acc_base() + X * 32768 + acc_slot(slot) + acc_main(rank, tid)) = make_uint4(v[0], v[1], v[2], v[3]);
    *(uint32_t*)(acc_base() + X * 1024 + acc_slot(slot) + acc_extra(rank, tid)) = v[4];
}
__global__ void acc_init_kernel(const __nv_bfloat16* mem0) { acc_init(mem0, blockIdx.x * 256 + threadIdx.x); }

struct RecW { uint32_t am, ae, ah, dp, lp, lpw, vo, sb, bar, zero, ts, tn; };
__device__ __forceinline__ uint32_t vadd(uint32_t a, uint32_t b) { uint32_t d; asm volatile("add.u32 %0,%1,%2;" : "=r"(d) : "r"(a), "r"(b)); return d; }
__device__ __forceinline__ uint32_t vshr(uint32_t a, int n) { uint32_t d; asm volatile("shr.u32 %0,%1,%2;" : "=r"(d) : "r"(a), "r"(n)); return d; }
__device__ __forceinline__ uint64_t gptr(uint32_t lo, uint32_t hi) { uint64_t d; asm("mov.b64 %0,{%1,%2};" : "=l"(d) : "r"(lo), "r"(hi)); return d; }
__device__ __forceinline__ void sfence(uint32_t zero) { asm volatile("{.reg .pred p; setp.ne.u32 p,%0,0; @p exit;}" ::"r"(zero) : "memory"); }
#define SF sfence(k.zero)
#define TS(i) do {} while (0)
#define TSN(i) do {} while (0)
#define TSET(it, slot) do {} while (0)
struct Gat { uint32_t x, y, z, w, e; };
template <int X>
__device__ __forceinline__ void gat_issue(Gat& g, const RecW& k, int s, uint32_t dep) {
    const uint32_t o = acc_slot(s + 3) + dep;
    asm volatile("{.reg .b128 t; ld.relaxed.gpu.global.b128 t,[%5+%7]; mov.b128 {%0,%1,%2,%3},t; ld.relaxed.gpu.global.u32 %4,[%6+%8];}"
                 : "=r"(g.x), "=r"(g.y), "=r"(g.z), "=r"(g.w), "=r"(g.e) : "l"(gptr(k.am + o, k.ah)), "l"(gptr(k.ae + o, k.ah)), "n"(X * 32768), "n"(X * 1024) : "memory");
}
template <int X>
__device__ __forceinline__ bool gat_store(const Gat& g, const RecW& k) {
    uint32_t c;
    asm volatile("prmt.b32 %0,%1,%2,0x7632;" : "=r"(c) : "r"(g.w), "r"(g.e));
    SF;
    asm volatile("{.reg .b32 t; prmt.b32 t,%4,%6,0x5410; stmatrix.sync.aligned.m8n8.x4.trans.shared.b16 [%0+%5],{%1,%2,%3,t};}" ::"r"(k.lpw), "r"(g.x), "r"(g.y), "r"(g.z), "r"(g.w), "n"(R_M + X * 4096), "r"(g.e) : "memory");
    return __all_sync(0xffffffffu, c == 0x42004200u);
}
template <int X>
__device__ __forceinline__ void gat_finish(bool ok, const RecW& k, int s) {
    if (!ok) {
        int n = s;
        while (true) {
            Gat g;
            gat_issue<X>(g, k, n, 0);
            if (gat_store<X>(g, k)) break;
            n += 4;
            if (n > 8000000) __trap();
        }
    }
}
__device__ __forceinline__ uint4 lds128o(uint32_t a, int o) { uint4 v; asm volatile("{.reg .b32 t; add.u32 t,%4,%5; ld.shared.v4.u32 {%0,%1,%2,%3},[t];}" : "=r"(v.x), "=r"(v.y), "=r"(v.z), "=r"(v.w) : "r"(a), "r"(o) : "memory"); return v; }
__device__ __forceinline__ uint4 ldsm4o(uint32_t a, int o) { uint4 v; asm volatile("{.reg .b32 t; add.u32 t,%4,%5; ldmatrix.sync.aligned.m8n8.x4.shared.b16 {%0,%1,%2,%3},[t];}" : "=r"(v.x), "=r"(v.y), "=r"(v.z), "=r"(v.w) : "r"(a), "r"(o) : "memory"); return v; }
__device__ __forceinline__ uint4 ldsm4to(uint32_t a, int o) { uint4 v; asm volatile("{.reg .b32 t; add.u32 t,%4,%5; ldmatrix.sync.aligned.m8n8.x4.trans.shared.b16 {%0,%1,%2,%3},[t];}" : "=r"(v.x), "=r"(v.y), "=r"(v.z), "=r"(v.w) : "r"(a), "r"(o) : "memory"); return v; }
__device__ __forceinline__ uint2 lds64o(uint32_t a, int o) { uint2 v; asm volatile("{.reg .b32 t; add.u32 t,%2,%3; ld.shared.v2.u32 {%0,%1},[t];}" : "=r"(v.x), "=r"(v.y) : "r"(a), "r"(o) : "memory"); return v; }
__device__ __forceinline__ void sts128o(uint32_t a, int o, uint32_t x, uint32_t y, uint32_t z, uint32_t w) { asm volatile("{.reg .b32 t; add.u32 t,%0,%5; st.shared.v4.u32 [t],{%1,%2,%3,%4};}" ::"r"(a), "r"(x), "r"(y), "r"(z), "r"(w), "r"(o) : "memory"); }
__device__ __forceinline__ void sts64o(uint32_t a, int o, uint32_t x, uint32_t y) { asm volatile("{.reg .b32 t; add.u32 t,%0,%3; st.shared.v2.u32 [t],{%1,%2};}" ::"r"(a), "r"(x), "r"(y), "r"(o) : "memory"); }
__device__ __forceinline__ uint32_t vxor(uint32_t a, uint32_t b) { uint32_t d; asm volatile("xor.b32 %0,%1,%2;" : "=r"(d) : "r"(a), "r"(b)); return d; }
#define WLD(base, i) wt[i] = lds128o(k.lpw, (base) + (i) * 4096)
template <int PASS, int X, int NP>
__device__ __forceinline__ void rec_qkv(const RecW& k, int s, const uint32_t (*wq)[4], const uint32_t (*wk)[4], uint4* wt, Gat& g2, int s2, bool& ok2, uint4& mf) {
    constexpr bool BWD = PASS == 2, DIRECT = !(BKA && PASS == 1);
    float aq[4] = {0, 0, 0, 0}, ak[4] = {0, 0, 0, 0}, av[4] = {0, 0, 0, 0};
    constexpr int ma = R_M + X * 4096;
    if (BWD && GSE == 4) { TS(1); mbar_wait(k.sb + R_BAR + RB_MB * 8, s & 1); mf = ldsm4o(k.lp, ma + 7 * 512); TS(2); }
    if (!BWD || GSE < 2) {
        if (BWD) { TS(1); gat_finish<1>(GSE ? ok2 : gat_store<1>(g2, k), k, s); }
        bar_sync(NB_MF + X, 256);
        mf = ldsm4o(k.lp, ma + (BWD ? 7 : 0) * 512);
        if (BWD) TS(2); else { TS(0); TSN(13); }
    }
#pragma unroll
    for (int ii = 0; ii < 8; ii++) {
        const int i = BWD ? 7 - ii : ii;
        const uint4 m = mf;
        if (ii < 7) mf = ldsm4o(k.lp, ma + (BWD ? i - 1 : i + 1) * 512);
        if (PASS == 1 && ii == G2I) gat_issue<1>(g2, k, s2, 0);
        if (PASS == 1 && GSE == 2 && ii == 7) { TS(1); gat_finish<1>(gat_store<1>(g2, k), k, s2); }
        if (PASS == 1 && GSE == 4 && ii == G2S) { gat_finish<1>(gat_store<1>(g2, k), k, s2); mbar_arrive1(k.sb + R_BAR + RB_MB * 8); }
        SF;
#pragma unroll
        for (int hh = 0; hh < 2; hh++) {
            const int h = BWD ? 1 - hh : hh, ks = 2 * i + h;
            const uint32_t b0 = h ? m.z : m.x, b1 = h ? m.w : m.y;
            mma16(aq, wq[ks][0], wq[ks][1], wq[ks][2], wq[ks][3], b0, b1);
            mma16(ak, wk[ks][0], wk[ks][1], wk[ks][2], wk[ks][3], b0, b1);
            SF;
            mma16(av, wt[ks].x, wt[ks].y, wt[ks].z, wt[ks].w, b0, b1);
            SF;
            if (!BWD && ks + NP < 16) WLD(R_WV, ks + NP < 16 ? ks + NP : 0);
            if (BWD && ks >= NT) WLD(R_WV, ks >= NT ? ks - NT : 0);
            SF;
        }
    }
    if (PASS == 1 && GSE == 1) { ok2 = gat_store<1>(g2, k); SF; }
    if (PASS == 1 && GSE == 3) { TS(1); gat_finish<1>(gat_store<1>(g2, k), k, s2); }
    if (PASS == 1 && (GSE == 2 || GSE == 3)) { bar_sync(NB_MF + 1, 256); mf = ldsm4o(k.lp, ma + 4096 + 7 * 512); TS(2); SF; }
    const uint32_t ra = vadd(k.lpw, k.dp + R_REM + (X * 2 + (s & 1)) * 6144), va = ((vshr(k.lp, 7) & 1) * 48 ^ k.lp ^ (k.vo & 64)) + (k.vo & ~64u);
    const uint32_t x0 = movm(pack2(aq[0], aq[1])), x1 = movm(pack2(aq[2], aq[3])), x2 = movm(pack2(ak[0], ak[1])), x3 = movm(pack2(ak[2], ak[3]));
    SF;
    asm volatile("stmatrix.sync.aligned.m8n8.x2.shared.b16 [%0+%3],{%1,%2};" ::"r"(va), "r"(pack2(av[0], av[1])), "r"(pack2(av[2], av[3])), "n"(R_LOC + X * 6144) : "memory");
    SF;
    if (STO && DIRECT) st_async4(ra, x0, x1, x2, x3, k.bar + X * 16);
    asm volatile("st.shared.v4.u32 [%0+%5],{%1,%2,%3,%4};" ::"r"(k.lpw), "r"(x0), "r"(x1), "r"(x2), "r"(x3), "n"(R_LOC + X * 6144) : "memory");
    bar_arrive(NB_LOC + X, 320);
    if (!STO && DIRECT) st_async4(ra, x0, x1, x2, x3, k.bar + X * 16);
    SF;
    TS(BWD ? 4 : 3);
}
template <bool BWD, int X>
__device__ __forceinline__ void rec_out(const RecW& k, int s, uint4* wt, Gat& g, int s1) {
    if (BWD) { WLD(R_WO, 17 - NTO); WLD(R_WO, 16 - NTO); }
    TS(BWD ? 8 : 5);
    bar_sync(NB_O + X, 320);
    float r0[4] = {0, 0, 0, 0}, r1[4] = {0, 0, 0, 0};
    constexpr int oa = R_O + X * 2048;
    uint4 bn = lds128o(k.lp, oa + (BWD ? 3 : 0) * 512);
    TS(BWD ? 9 : 6);
    uint2 il;
    uint64_t pm, pe;
#pragma unroll
    for (int ii = 0; ii < 4; ii++) {
        const int i = BWD ? 3 - ii : ii;
        const uint4 b = bn;
        if (ii < 3) bn = lds128o(k.lp, oa + (BWD ? i - 1 : i + 1) * 512);
        else { asm volatile("ld.shared.v2.u32 {%0,%1},[%2+%3];" : "=r"(il.x), "=r"(il.y) : "r"((vshr(k.ae, 2) & 3) * 8 + k.sb), "n"(R_IL + X * 32) : "memory"); pm = gptr(vadd(k.am, acc_slot(s)), k.ah); pe = gptr(vadd(k.ae, acc_slot(s)), k.ah); }
        SF;
        if (BWD && EARLY == ii + 1) { gat_issue<0>(g, k, s1 + 1, 0); SF; }
#pragma unroll
        for (int nn = 0; nn < 4; nn++) {
            const int n = BWD ? 3 - nn : nn, f = 4 * i + n, nx = BWD ? f - NTO + 2 : f + NTO - 2;
            mma16((n & 1) ? r1 : r0, wt[f].x, wt[f].y, wt[f].z, wt[f].w, n >> 1 ? b.z : b.x, n >> 1 ? b.w : b.y);
            SF;
            if (ii * 4 + nn >= 2 && nx >= 0 && nx < 16) WLD(R_WO, nx & 15);
            SF;
        }
    }
    const float i0 = __uint_as_float(il.x), i1 = __uint_as_float(il.y);
    asm volatile("red.relaxed.gpu.global.add.noftz.v4.bf16x2 [%0+%5],{%1,%2,%3,%4};" ::"l"(pm),
                 "r"(pack2(r0[0] * i0, r0[1] * i1)), "r"(pack2(r0[2] * i0, r0[3] * i1)), "r"(pack2(r1[0] * i0, r1[1] * i1)), "r"(pack2(r1[2] * i0, 1.f)), "n"(X * 32768) : "memory");
    asm volatile("red.relaxed.gpu.global.add.noftz.bf16x2 [%0+%2],%1;" ::"l"(pe), "r"(pack2(r1[3] * i1, 1.f)), "n"(X * 1024) : "memory");
    bar_arrive(NB_XG + X, 320);
    SF;
    TS(BWD ? 10 : 7);
}
__device__ __forceinline__ uint32_t pause(uint32_t v, int n) {
#pragma unroll
    for (int i = 0; i < n; i++) asm volatile("shfl.sync.bfly.b32 %0,%0,0,0x1f,0xffffffff;" : "+r"(v));
    return v;
}
template <bool DUAL, int X>
__device__ __forceinline__ void rec_step(const RecW& k, int s, int s2, const uint32_t (*wq)[4], const uint32_t (*wk)[4], uint4* wt) {
    constexpr int NP = NPD;
    uint4 wo[16];
    Gat g;
    bool ok2;
    uint4 mf;
    rec_qkv<DUAL ? 1 : 0, X, NP>(k, s, wq, wk, wt, g, s2, ok2, mf);
    if (DUAL) rec_qkv<2, 1, NP>(k, s2, wq, wk, wt, g, s2, ok2, mf);
    uint32_t wa = k.lpw;
#pragma unroll
    for (int i = 0; i < NTO; i++) {
        wo[i] = lds128o(wa, R_WO + i * 4096);
        if (i % PACE == PACE - 1) wa = k.lpw + (wo[i].x & k.zero);
        SF;
    }
    rec_out<false, X>(k, s, wo, g, s);
    if (DUAL) { rec_out<true, 1>(k, s2, wo, g, s); if (!EARLY) gat_issue<0>(g, k, s + 1, 0); SF; }
#pragma unroll
    for (int i = 0; i < NP; i++) { WLD(R_WV, i); SF; }
    if (!DUAL) gat_issue<X>(g, k, s + 1, pause(wt[NP - 1].x & k.zero, DP1));
    TS(12);
    gat_finish<X>(gat_store<X>(g, k), k, s + 1);
    TS(11);
}

__device__ __forceinline__ void rec_fetch(const CUtensorMap* tm, uint32_t dst, int x, int y, int nx, uint32_t bar) {
#pragma unroll 1
    for (int j = 0; j < 8; j++) tma2d(dst + j * 8192, tm, x + (j / (8 / nx)) * 64, y + (j % (8 / nx)) * 64, bar);
}
__device__ __forceinline__ void rec_weights(const Params& p, uint32_t sb, int head, uint32_t rank, int w) {
    const int lane = threadIdx.x & 31, t = w & 3, WG = w >> 2;
    uint32_t wq[16][4], wk[16][4];
    const uint32_t rowo = (((lane >> 4) << 3) + (lane & 7)) * 128;
    const uint32_t woff = sb + WG * 32768 + rowo + (((2 * t + ((lane >> 3) & 1)) ^ (lane & 7)) << 4);
    const uint32_t qoff = sb + ((w & 1) ? R_STK : R_STQ) + WG * 32768 + rowo + (((2 * (t & 2) + ((lane >> 3) & 1)) ^ (lane & 7)) << 4);
    const uint32_t lw = sb + (lane ^ (lane >> 3)) * 16;
    PROF(threadIdx.x == 0, 3501);
    PROF(threadIdx.x == 0, 3502);
    mbar_wait(sb + R_BAR + RB_INIT * 8, 0);
    PROF(threadIdx.x == 0, 3503);
#pragma unroll
    for (int ks = 0; ks < 16; ks++) {
        uint4 a = ldsm4t(qoff + ks * 2048), b = ldsm4t((qoff ^ 32) + ks * 2048);
        wq[ks][0] = a.x; wq[ks][1] = a.y; wq[ks][2] = a.z; wq[ks][3] = a.w;
        wk[ks][0] = b.x; wk[ks][1] = b.y; wk[ks][2] = b.z; wk[ks][3] = b.w;
    }
    bar_sync(NB_W, 256);
#pragma unroll 4
    for (int ks = 0; ks < 16; ks++) { const uint4 a = ldsm4t(woff + R_STV + ks * 2048); sts128(lw + w * 512 + R_WV + ks * 4096, a.x, a.y, a.z, a.w); }
    bar_sync(NB_W, 256);
    if (threadIdx.x == 0) {
        mbar_expect(sb + R_BAR + RB_INIT * 8, 65536);
        rec_fetch(&p.tm[4], sb + R_STV, rank * 256, head * 128, 4, sb + R_BAR + RB_INIT * 8);
    }
    __syncwarp();
    mbar_wait(sb + R_BAR + RB_INIT * 8, 1);
#pragma unroll 4
    for (int f = 0; f < 16; f++) {
        const uint4 a = ldsm4t(sb + R_STV + (w >> 1) * 16384 + (f >> 1) * 2048 + rowo + ((((w & 1) * 4 + (f & 1) * 2 + ((lane >> 3) & 1)) ^ (lane & 7)) << 4));
        sts128(lw + w * 512 + R_WO + f * 4096, a.x, a.y, a.z, a.w);
    }
    PROF(threadIdx.x == 0, 3504);
    __syncthreads();
    cluster_sync();
    PROF(threadIdx.x == 0, 3505);
    RecW k;
    k.am = __shfl_sync(0xffffffffu, (uint32_t)(size_t)acc_base() + acc_main(rank, threadIdx.x), lane);
    k.ae = __shfl_sync(0xffffffffu, (uint32_t)(size_t)acc_base() + acc_extra(rank, threadIdx.x), lane);
    k.ah = (uint32_t)((size_t)acc_base() >> 32);
    k.sb = sb; k.zero = p.zero;

    k.dp = mapa(sb, rank ^ 1) - sb;
    k.lp = __shfl_sync(0xffffffffu, lw, lane);
    k.lpw = __shfl_sync(0xffffffffu, lw + w * 512, lane);
    k.vo = 4096 + w * 256 + (w & 1) * 64;
    k.bar = sb + k.dp + R_BAR + (RB_QK + WG) * 8;
    int it = 0;
    uint4 wt[16];
#pragma unroll
    for (int i = 0; i < NPD; i++) WLD(R_WV, i);
    gat_finish<0>(false, k, 0);
#pragma unroll 1
    for (; it < min(p.b1, p.e0); it++) { TSET(it, w == GPW ? 0 : 3); rec_step<false, 0>(k, it, it, wq, wk, wt); }
#pragma unroll 1
    for (; it < p.e0; it++) { TSET(it, w == GPW ? 0 : 3); rec_step<true, 0>(k, it, it - p.b1, wq, wk, wt); }
    if (it < p.nit) gat_finish<1>(false, k, it - p.b1);
#pragma unroll 1
    for (; it < p.nit; it++) { TSET(it, w == GPW ? 0 : 3); rec_step<false, 1>(k, it - p.b1, it - p.b1, wq, wk, wt); }
}

__device__ __forceinline__ void mma16_top(float* c, uint32_t a0, uint32_t a2, uint32_t b0, uint32_t b1) {
    asm volatile("{.reg .b32 j; mma.sync.aligned.m16n8k16.row.col.f32.bf16.bf16.f32 {%0,%1,%2,%3},{%4,j,%5,j},{%6,%7},{%0,%1,%2,%3};}"
                 : "+f"(c[0]), "+f"(c[1]), "+f"(c[2]), "+f"(c[3]) : "r"(a0), "r"(a2), "r"(b0), "r"(b1));
}
__device__ __forceinline__ void rec_load_tile(uint32_t sb, int X, int j, int s, int head, uint32_t rank) {
    const uint32_t bar = sb + R_BAR + (RB_T + X * 2 + j) * 8;
    mbar_expect1(bar, j ? 4096 : 16384);
    bulk_g2s1(sb + R_T + X * TILE + j * 16384, g_qkv[X] + (size_t)(s * 32 + head) * 1536 + (j ? rank * 256 : 512), j ? 4096 : 16384, bar, POL_LAST);
}
__device__ __forceinline__ bool chunk_ready(int X, int j, int s) {
    unsigned v;
    asm volatile("ld.relaxed.gpu.global.u32 %0,[%1];" : "=r"(v) : "l"(cnt_ptr(C_QKV0 + X, (s >> 2) + j * 16)) : "memory");
    return __all_sync(0xffffffffu, v >= (256 >> j));
}
__device__ __forceinline__ uint4 hadd4(uint4 a, uint4 b) { return make_uint4(hadd2(a.x, b.x), hadd2(a.y, b.y), hadd2(a.z, b.z), hadd2(a.w, b.w)); }
struct RecH { uint32_t lw, lm, lq, lv, lu, sa, sp, sb, zero, ts, tn; };
__device__ __forceinline__ void rec_publish(int X, int s) {
    asm volatile("{.reg .pred p; cp.async.bulk.wait_group 0; elect.sync _|p,0xffffffff; @p red.relaxed.gpu.global.add.u32 [%0],4;}" ::"l"(cnt_ptr(C_O0 + X, s >> 2)) : "memory");
}
__device__ __forceinline__ void rec_mattn(const RecH& k, uint32_t dp, int X, int j, int s, bool qk, uint4 (*V)[4], uint4* vm) {
    const uint32_t sb = k.sb, to = R_T + X * TILE + j * 2048, lo = R_LOC + X * 6144, ro = R_REM + (X * 2 + (s & 1)) * 6144;
    const uint32_t bar = sb + R_BAR + (X * 2 + j) * 8;
    uint4 K[2][4];
    mbar_wait(sb + R_BAR + (RB_T + X * 2) * 8, s & 1);
    TS(1);
#pragma unroll
    for (int i = 0; i < 8; i++) K[i >> 2][i & 3] = ldsm4o(k.lm, (to + (i >> 2) * 1024 + ((i >> 1) & 1) * 4096 + (i & 1) * 512));
    asm volatile("cp.async.bulk.wait_group 0;" ::: "memory");
    bar_sync(NB_LOC + X, 320);
    fence_async_smem();
    if (qk) asm volatile("{.reg .pred p; elect.sync _|p,0xffffffff; @p cp.async.bulk.shared::cluster.shared::cta.mbarrier::complete_tx::bytes [%0],[%1],2048,[%2];}"
                         ::"r"(sb + dp + ro + j * 2048), "r"(sb + lo + j * 2048), "r"(bar + dp + RB_QK * 8) : "memory");
    asm volatile("{.reg .pred p; elect.sync _|p,0xffffffff; @p cp.async.bulk.shared::cluster.shared::cta.mbarrier::complete_tx::bytes [%0],[%1],1024,[%2];}"
                 ::"r"(sb + dp + ro + 4096 + j * 1024), "r"(sb + lo + 4096 + j * 1024), "r"(bar + dp + RB_V * 8) : "memory");
    uint4 u[4];
#pragma unroll
    for (int i = 0; i < 4; i++) u[i] = ldsm4o(k.lm, (lo + j * 2048 + i * 512));
    TS(2);
    mbar_wait(bar + RB_QK * 8, s & 1);
    TS(3);
    float S[5][4];
#pragma unroll
    for (int i = 0; i < 5; i++) S[i][0] = S[i][1] = S[i][2] = S[i][3] = 0;
    {
        uint4 r[4];
#pragma unroll
        for (int i = 0; i < 4; i++) r[i] = ldsm4o(k.lm, (ro + j * 2048 + i * 512));
        SF;
#pragma unroll
        for (int e = 0; e < 2; e++) {
            uint4& km = u[2 * e + 1];
            const uint32_t q0 = hadd2(u[2 * e].x, r[2 * e].x), q1 = hadd2(u[2 * e].y, r[2 * e].y);
            mma16_top(S[0], q0, q1, K[e][0].x, K[e][0].y);
            km.x = hadd2(km.x, r[2 * e + 1].x); km.y = hadd2(km.y, r[2 * e + 1].y);
            SF;
            mma16_top(S[1], q0, q1, K[e][1].x, K[e][1].y);
            const uint32_t q2 = hadd2(u[2 * e].z, r[2 * e].z), q3 = hadd2(u[2 * e].w, r[2 * e].w);
            SF;
            mma16_top(S[2], q0, q1, K[e][2].x, K[e][2].y);
            km.z = hadd2(km.z, r[2 * e + 1].z); km.w = hadd2(km.w, r[2 * e + 1].w);
            SF;
            mma16_top(S[3], q0, q1, K[e][3].x, K[e][3].y);
            mma16_top(S[4], q0, q1, km.x, km.y);
            SF;
#pragma unroll
            for (int i = 0; i < 4; i++) {
                mma16_top(S[i], q2, q3, K[e][i].z, K[e][i].w); SF;
            }
            mma16_top(S[4], q2, q3, km.z, km.w);
            SF;
        }
    }
#define VLD(a, b) _Pragma("unroll") for (int i = (a); i < (b); i++) V[i >> 2][i & 3] = ldsm4to((i & 1) ? lv2 : k.lv, (to + 8192 + (i >> 2) * 4096 + ((i >> 1) & 1) * 1024))
    const uint32_t lv2 = vxor(k.lv, 0x20), lh = vshr(k.lw, 1);
    VLD(0, VE);
    SF;
    const uint32_t sxr = k.sa, sxw = k.sp;
    sts128o(k.lw, sxw, __float_as_uint(S[0][0]), __float_as_uint(S[0][1]), __float_as_uint(S[1][0]), __float_as_uint(S[1][1]));
    SF;
    sts128o(k.lw, (sxw + 512), __float_as_uint(S[2][0]), __float_as_uint(S[2][1]), __float_as_uint(S[3][0]), __float_as_uint(S[3][1]));
    SF;
    sts64o(lh, (sb / 2 + sxw + 1024), __float_as_uint(S[4][0]), __float_as_uint(S[4][1]));
    TS(4);
    bar_sync(NB_PAIR + X, 64);
    {
        const uint4 a = lds128o(k.lw, sxr), b = lds128o(k.lw, (sxr + 512));
        const uint2 c = lds64o(lh, (sb / 2 + sxr + 1024));
        SF;
        VLD(VE, VF);
        SF;
        S[0][0] += __uint_as_float(a.x); S[0][1] += __uint_as_float(a.y); S[1][0] += __uint_as_float(a.z); S[1][1] += __uint_as_float(a.w);
        S[2][0] += __uint_as_float(b.x); S[2][1] += __uint_as_float(b.y); S[3][0] += __uint_as_float(b.z); S[3][1] += __uint_as_float(b.w);
        S[4][0] += __uint_as_float(c.x); S[4][1] += __uint_as_float(c.y);
    }
    float m = fmaxf(fmaxf(fmaxf(S[0][0], S[0][1]), fmaxf(S[1][0], S[1][1])), fmaxf(fmaxf(S[2][0], S[2][1]), fmaxf(S[3][0], S[3][1])));
    m = fmaxf(m, fmaxf(S[4][0], S[4][1]));
    m = fmaxf(m, __shfl_xor_sync(0xffffffffu, m, 1));
    const float m2 = __shfl_xor_sync(0xffffffffu, m, 2);
    SF;
    VLD(VF, 8);
    uint32_t ok;
    asm volatile("{.reg .pred p; mbarrier.test_wait.parity.shared::cta.b64 p,[%1],%2; selp.u32 %0,1,0,p;}" : "=r"(ok) : "r"(bar + RB_V * 8), "r"(s & 1) : "memory");
    uint4 vr0 = ldsm4o(k.lu, (ro + 4096 + j * 1024)), vr1 = ldsm4o(k.lu, (ro + 4608 + j * 1024));
    vm[0] = ldsm4o(k.lu, (lo + 4096 + j * 1024)); vm[1] = ldsm4o(k.lu, (lo + 4608 + j * 1024));
    SF;
    TS(5);
    m = fmaxf(m, m2) * -SC_LOG2E;
    uint32_t P[5];
#pragma unroll
    for (int i = 0; i < 5; i++) P[i] = pack2(ex2(fmaf(S[i][0], SC_LOG2E, m)), ex2(fmaf(S[i][1], SC_LOG2E, m)));
    float o[4][4], l[4] = {0, 0, 0, 0};
    const uint32_t ONE = 0x3f803f80u;
    mma16_top(l, ONE, ONE, P[0], P[1]);
#pragma unroll
    for (int t = 0; t < 4; t++) { o[t][0] = o[t][1] = o[t][2] = o[t][3] = 0; mma16(o[t], V[0][t].x, V[0][t].y, V[0][t].z, V[0][t].w, P[0], P[1]); }
    mma16_top(l, ONE, ONE, P[2], P[3]);
#pragma unroll
    for (int t = 0; t < 4; t++) mma16(o[t], V[1][t].x, V[1][t].y, V[1][t].z, V[1][t].w, P[2], P[3]);
    if (!__all_sync(0xffffffffu, ok)) {
        mbar_wait(bar + RB_V * 8, s & 1);
        vr0 = ldsm4o(k.lu, (ro + 4096 + j * 1024)); vr1 = ldsm4o(k.lu, (ro + 4608 + j * 1024));
    }
    TS(6);
    vm[0] = hadd4(vm[0], vr0); vm[1] = hadd4(vm[1], vr1);
    mma8(l, ONE, ONE, P[4]);
    mma8(o[0], vm[0].x, vm[0].y, P[4]); mma8(o[1], vm[0].z, vm[0].w, P[4]); mma8(o[2], vm[1].x, vm[1].y, P[4]); mma8(o[3], vm[1].z, vm[1].w, P[4]);
    asm volatile("{.reg .pred p; .reg .b32 t; setp.lt.u32 p,%0,%3; add.u32 t,%0,%4; @p st.shared.v2.f32 [t],{%1,%2};}" ::"r"(lh), "f"(rcp(l[0])), "f"(rcp(l[1])), "r"(j ? 0 : sb / 2 + 32), "r"(sb / 2 + R_IL + X * 32) : "memory");
#pragma unroll
    for (int t = 0; t < 4; t += 2)
        asm volatile("{.reg .b32 t; add.u32 t,%0,%5; stmatrix.sync.aligned.m8n8.x4.trans.shared.b16 [t],{%1,%2,%3,%4};}" ::"r"(k.lm),
                     "r"(pack2(o[t][0], o[t][1])), "r"(pack2(o[t][2], o[t][3])), "r"(pack2(o[t + 1][0], o[t + 1][1])), "r"(pack2(o[t + 1][2], o[t + 1][3])), "r"(R_O + X * 2048 + j * 1024 + t * 256) : "memory");
    bar_arrive(NB_O + X, 320);
    PROF(k.lw == sb && j == 0, X * 64 + s);
    TS(7);
#pragma unroll
    for (int e = 0; e < 2; e++) sts128o(k.lw, (ro + j * 2048 + e * 1024), u[2 * e + 1].x, u[2 * e + 1].y, u[2 * e + 1].z, u[2 * e + 1].w);
    mbar_expect1(bar + RB_QK * 8, 2048); mbar_expect1(bar + RB_V * 8, 1024);
}
template <int MT>
__device__ __forceinline__ void rec_xattn(const RecH& k, int X, int j, int s, int head, bool early, const uint4 (*V)[4], const uint4* vmm) {
    constexpr int NTL = 3 + 2 * MT;
    const uint32_t sb = k.sb, to = R_T + X * TILE + j * 2048, ro = R_REM + (X * 2 + (s & 1)) * 6144 + j * 2048;
    const uint32_t sxw = k.sa, sxr = k.sp;
    const uint32_t lq2 = vxor(k.lq, 0x20);
    float S[NTL][4];
#pragma unroll
    for (int i = 0; i < NTL; i++) S[i][0] = S[i][1] = S[i][2] = S[i][3] = 0;
#pragma unroll
    for (int e = 0; e < 2; e++) {
        const uint4 q0 = ldsm4o(k.lq, (to + 16384 + e * 1024)), q1 = ldsm4o(lq2, (to + 16384 + e * 1024));
#pragma unroll
        for (int i = 0; i < NTL; i++) {
            const uint4 kk = i ? ldsm4o(k.lm, (to + e * 1024 + ((i - 1) >> 1) * 4096 + ((i - 1) & 1) * 512)) : lds128o(k.lw, (ro + e * 1024));
            mma16(S[i], q0.x, q0.y, q0.z, q0.w, kk.x, kk.y); mma16(S[i], q1.x, q1.y, q1.z, q1.w, kk.z, kk.w);
        }
    }
#pragma unroll
    for (int i = 0; i < NTL; i++) sts128o(k.lw, (sxw + i * 512), __float_as_uint(S[i][0]), __float_as_uint(S[i][1]), __float_as_uint(S[i][2]), __float_as_uint(S[i][3]));
    SF;
    bar_sync(NB_PAIR + 2 + X, 64);
    TS(9);
    if (early) rec_load_tile(sb, X, j, s + 1, head, MT);
#pragma unroll
    for (int i = 0; i < NTL; i++) {
        const uint4 r = lds128o(k.lw, (sxr + i * 512));
        S[i][0] += __uint_as_float(r.x); S[i][1] += __uint_as_float(r.y); S[i][2] += __uint_as_float(r.z); S[i][3] += __uint_as_float(r.w);
    }
    const int g = vshr(k.lw, 6) & 7, c = (vshr(k.lw, 4) ^ (g >> 1)) & 3;
    const float NEG = -__int_as_float(0x7f800000);
    if (2 * c > g) { S[NTL - 2][0] = NEG; S[NTL - 1][2] = NEG; }
    if (2 * c + 1 > g) { S[NTL - 2][1] = NEG; S[NTL - 1][3] = NEG; }
    float m0 = fmaxf(S[0][0], S[0][1]), m1 = fmaxf(S[0][2], S[0][3]);
#pragma unroll
    for (int i = 1; i < NTL; i++) { if (i < NTL - 1) m0 = fmaxf(m0, fmaxf(S[i][0], S[i][1])); m1 = fmaxf(m1, fmaxf(S[i][2], S[i][3])); }
    m0 = fmaxf(m0, __shfl_xor_sync(0xffffffffu, m0, 1)); m1 = fmaxf(m1, __shfl_xor_sync(0xffffffffu, m1, 1));
    m0 = fmaxf(m0, __shfl_xor_sync(0xffffffffu, m0, 2)); m1 = fmaxf(m1, __shfl_xor_sync(0xffffffffu, m1, 2));
    m0 *= -SC_LOG2E; m1 *= -SC_LOG2E;
    uint32_t P[NTL][2];
#pragma unroll
    for (int i = 0; i < NTL; i++) {
        P[i][0] = i < NTL - 1 ? pack2(ex2(fmaf(S[i][0], SC_LOG2E, m0)), ex2(fmaf(S[i][1], SC_LOG2E, m0))) : 0u;
        P[i][1] = pack2(ex2(fmaf(S[i][2], SC_LOG2E, m1)), ex2(fmaf(S[i][3], SC_LOG2E, m1)));
    }
    float l[4] = {0, 0, 0, 0};
#pragma unroll
    for (int i = 0; i < NTL; i++) mma8(l, P[i][0], P[i][1], 0x3f803f80u);
    const float l0 = rcp(l[0]), l1 = rcp(l[2]);

#pragma unroll
    for (int e = 0; e < 2; e++) {
        const uint4 vm = vmm[e];
        uint32_t u[2][4];
#pragma unroll
        for (int n = 0; n < 4; n++) {
            float a[4] = {0, 0, 0, 0};
#pragma unroll
            for (int m = 0; m <= MT; m++) {
                const uint4 v = V[m][e * 2 + (n >> 1)];
                mma8(a, P[1 + 2 * m][0], P[1 + 2 * m][1], (n & 1) ? v.y : v.x); mma8(a, P[2 + 2 * m][0], P[2 + 2 * m][1], (n & 1) ? v.w : v.z);
            }
            mma8(a, P[0][0], P[0][1], n == 0 ? vm.x : n == 1 ? vm.y : n == 2 ? vm.z : vm.w);
            u[0][n] = pack2(a[0] * l0, a[1] * l0); u[1][n] = pack2(a[2] * l1, a[3] * l1);
        }
        sts128o(k.lw, sxr + e * 512, u[0][0], u[0][1], u[0][2], u[0][3]); sts128o(k.lw, sxr + e * 512 + 1024, u[1][0], u[1][1], u[1][2], u[1][3]);
    }
    TS(10);
}
__device__ __forceinline__ void rec_attn(const Params& p, uint32_t sb, int X, int j, int head, uint32_t rank) {
    const int lane = threadIdx.x & 31;
    RecH k;
    k.lw = __shfl_sync(0xffffffffu, sb + (lane ^ (lane >> 3)) * 16, lane);
    k.lm = __shfl_sync(0xffffffffu, sb + ((lane & 7) * 4 + ((lane >> 3) ^ ((lane & 7) >> 1))) * 16, lane);
    k.lq = __shfl_sync(0xffffffffu, sb + ((lane >> 3) & 1) * 512 + ((lane & 7) * 4 + ((lane >> 4) ^ ((lane & 7) >> 1))) * 16, lane);
    k.lv = __shfl_sync(0xffffffffu, sb + (lane >> 4) * 512 + ((lane & 7) * 4 + (((lane >> 3) & 1) ^ ((lane & 7) >> 1))) * 16, lane);
    k.lu = __shfl_sync(0xffffffffu, sb + ((lane & 6) * 4 + (((lane >> 3) * 2 + (lane & 1)) ^ (lane & 6))) * 16, lane);
    k.sa = __shfl_sync(0xffffffffu, R_SX + (X * 2 + j) * 2560, 0); k.sp = __shfl_sync(0xffffffffu, R_SX + (X * 2 + (j ^ 1)) * 2560, 0);
    k.sb = sb; k.zero = p.zero;
    const uint32_t dp = mapa(sb, rank ^ 1) - sb;
    char* zp = acc_base() + (j ? X * 32768 + acc_main(rank, head * 8) : X * 1024 + acc_extra(rank, head * 8));
    mbar_expect1(sb + R_BAR + (RB_QK + X * 2 + j) * 8, 2048); mbar_expect1(sb + R_BAR + (RB_V + X * 2 + j) * 8, 1024);
    bool early = false;
#pragma unroll 1
    for (int s = 0; s < 64; s++) {
        TSET(X ? s + p.b1 : s, j == GPJ ? 1 + X : 3);
        TS(0);
        if (!early) {
            if (!j) wait_cnt_warp(cnt_ptr(C_QKV0 + X, s >> 2), 256);
            early = !j || chunk_ready(X, 1, s);
            if (early) rec_load_tile(sb, X, j, s, head, rank);
        }
        if (PFD && s < 63 && early && (PFB || !X) && ((s & 3) != 3 || chunk_ready(X, j, s + 1)))
            asm volatile("{.reg .pred p; elect.sync _|p,0xffffffff; @p cp.async.bulk.prefetch.L2.global.L2::cache_hint [%0],%1,%2;}"
                         ::"l"(g_qkv[X] + (size_t)((s + 1) * 32 + head) * 1536 + (j ? rank * 256 : 512 + rank * 512)), "r"(j ? 4096 : 8192), "l"(POL_LAST) : "memory");
        uint4 V[2][4], vm[2];
        rec_mattn(k, dp, X, j, s, BKA && !X && s >= p.b1, V, vm);
        if (!early) { wait_cnt_warp(cnt_ptr(C_QKV0 + X, (s >> 2) + 16), 128); rec_load_tile(sb, X, 1, s, head, rank); }
        early = s < 63 && ((s & 3) != 3 || chunk_ready(X, j, s + 1));
        mbar_wait(sb + R_BAR + (RB_T + X * 2 + 1) * 8, s & 1);
        bar_sync(NB_XG + X, 320);
        TS(8);
        if (rank) rec_xattn<1>(k, X, j, s, head, early, V, vm); else rec_xattn<0>(k, X, j, s, head, early, V, vm);
        fence_async_smem();
        __syncwarp();
        asm volatile("{.reg .pred p; elect.sync _|p,0xffffffff;\n"
                     "@p cp.async.bulk.global.shared::cta.bulk_group.L2::cache_hint [%0],[%1],2048,%2;\n"
                     "@p cp.async.bulk.global.shared::cta.bulk_group [%3],[%4],%5;\n"
                     "cp.async.bulk.commit_group;}"
                     ::"l"(g_o[X] + ((s >> 2) * 64 + head * 2 + j) * 1024 + ((s & 3) * 2 + rank) * 128), "r"(sb + k.sp),
                       "l"((X && s < 40) ? POL_LATE : POL_SOON), "l"(zp + acc_slot(s + 2)), "r"(sb + R_Z), "r"(j ? 128 : 32) : "memory");
        if ((s & 3) == 3) {
            if (!early && s < 63 && chunk_ready(X, j, s + 1)) { rec_load_tile(sb, X, j, s + 1, head, rank); early = true; }
            rec_publish(X, s);
        }
    }
}

__device__ __forceinline__ void rec_init(const Params& p, uint32_t sb, int head, uint32_t rank) {
    const uint32_t b = sb + R_BAR;
    const int i = threadIdx.x - 320;
    if (i >= 0 && i < RB_N) {
        mbar_init(b + i * 8, i == RB_MB ? 8 : 1);
        asm volatile("fence.mbarrier_init.release.cluster;" ::: "memory");
    }
    if (i == 0) mbar_expect(b + RB_INIT * 8, 196608);
    if (i >= 0 && i < 32) sts32(sb + R_Z + i * 4, 0);
}

#define NSTGN 8
constexpr int NSTG = NSTGN, STG_B = 24576;
#define LAGQ 1
#define LAGH 3
constexpr int NSB = 8;
constexpr int B_OUT = NSTG * STG_B  , B_UT = B_OUT, B_YT = B_UT + 16384, B_SP = B_YT  ,
              B_ST = 229376  , B_BAR = 231936;
static_assert(B_OUT + NSB * 4096 <= B_ST && B_ST + 2048 <= B_BAR && B_YT + 10240 <= B_ST, "smem map");
enum { BB_FULL = 0, BB_EMPTY = 8, BB_SF = 16  , BB_GO = 18, BB_DONE = 20  , BB_IDLE = 22  , BB_N = 30 };
enum { NB_C = 11, NB_WG = 12   };

__device__ __forceinline__ void bulk_init(uint32_t sb) {
    const int i = threadIdx.x - 320;
    if (i >= 0 && i < BB_N) {
        mbar_init(sb + B_BAR + i * 8, (i >= BB_EMPTY && i < BB_EMPTY + NSTG) ? 4 : i >= BB_DONE ? 4 : 1);
        asm volatile("fence.mbarrier_init.release.cluster;" ::: "memory");
    }
}

struct Task { int type, layer, ch, a, b, c, blk; bool pair, dry; };
__device__ __forceinline__ Task task_of(uint32_t tk, uint32_t rank) {
    Task t;
    t.type = tk & 7; t.layer = (tk >> 3) & 1; t.a = (tk >> 8) & 255; t.b = (tk >> 16) & 255; t.c = (tk >> 24) & 127; t.dry = tk >> 31;
    t.pair = t.type <= T_OP && (t.c & 64);
    t.ch = ((tk >> 4) & 15) + (t.pair ? rank : 0);
    t.blk = t.type == T_QKV ? t.a + (t.pair ? 0 : rank) : 192 + (t.pair ? (t.c >> 2) & 4 : rank * 4);
    return t;
}
__device__ __forceinline__ int qkv_blk(const Task& t, int u) {
    const int v = t.blk + (t.pair ? 1 : 2 * t.c) * u;
    return 2 * (v < 64 ? v + 32 : v - 64);
}
__device__ __forceinline__ void bulk_producer(const Params& p, uint32_t sb, int cl, uint32_t rank) {
    int st = 0; uint32_t ph = 1;
    const int tag = __shfl_sync(0xffffffffu, lds32(sb + S_TAG), 0);
    bool gated = false;
#define ACQ(bytes) do { mbar_wait(sb + B_BAR + (BB_EMPTY + st) * 8, ph); mbar_expect1(sb + B_BAR + (BB_FULL + st) * 8, bytes); } while (0)
#define NEXT do { if (++st == NSTG) { st = 0; ph ^= 1; } } while (0)
#pragma unroll 1
    for (int ti = 0; ti < MAXT; ti++) {
        const Task t = task_of(p.task[cl][ti], rank);
        const int layer = t.layer, ch = t.ch;
        if (t.type == T_END) break;
        if (t.type <= T_OP) {
            const bool qkv = t.type == T_QKV;
            const int rg = qkv ? (layer * 16 + ch) * 128 : 4096 + ((layer * 16 + ch) * 64 + t.a) * 16;
            const int nh = qkv ? 16 : 2 * t.b, row = qkv ? 0 : t.a * 64, bytes = qkv ? 16384 : STG_B;
            const unsigned* dep = cnt_ptr(qkv ? (layer ? C_CV : C_ST) : C_O0 + layer, ch);
            const unsigned need = qkv ? (layer ? 32 : ch < 2 ? 0 : 16) : 512;
            const uint64_t pol = qkv ? POL_N : POL_LAST;
            const int blk0 = qkv ? qkv_blk(t, 0) : t.blk;
            const CUtensorMap *tb = &p.t3[t.pair || qkv][blk0 >> 6], *ta = &p.ta[t.pair];
            const uint32_t db = sb + 8192 + (t.pair && !qkv ? rank * 8192 : 0), da = sb + (t.pair ? 0 : rank * 4096);
            const int zb = (blk0 & 63) + (t.pair && !qkv ? rank * 2 : 0), ya = rg + (t.pair ? 0 : rank * 8);
            const uint16_t mb = t.pair ? 3 : 1 << rank, ma = t.pair ? 1 << rank : 3;
            const int skip = t.pair && qkv ? rank ^ 1 : 2;
            int pend = qkv ? 2 : 0;
            bool wait = false;
            if (!t.dry) {
                unsigned v = 0;
                if (gated) asm volatile("ld.relaxed.gpu.global.u32 %0,[%1];" : "=r"(v) : "l"(dep) : "memory");
                wait = !gated || !__all_sync(0xffffffffu, v >= need);
                if (wait) pend = min(nh, gated ? NSTG : 4);
            }
            if (PFC && !qkv && !layer && (t.c & 15) < 8) {
                const int q = (t.c & 15) * 2 + rank;
                asm volatile("{.reg .pred p; elect.sync _|p,0xffffffff; @p cp.async.bulk.prefetch.L2.global [%0],8192; @p cp.async.bulk.prefetch.L2.global [%1],%2;}"
                             ::"l"(g_xA[0] + (ch * 16 + q) * 512), "l"(g_P + q * 16 * 32 * PW), "r"((2 + (ch & 1)) * 32 * PW * 4) : "memory");
            }
#pragma unroll 1
            while (qkv && st) { ACQ(0); NEXT; }
            int h = 0;
            const int s0 = st;
#pragma unroll 1
            for (; h < pend; h++) {
                ACQ(bytes + (qkv && h < 2 ? (layer ? 8192 : 1024) : 0));
                if ((h & 1) != skip) tma3d_mc(db + st * STG_B, tb, row + h * 32, zb, sb + B_BAR + (BB_FULL + st) * 8, mb);
                NEXT;
            }
            if (wait) {
                if (!gated) { wait_cnt_warp(g_gate, lds32(sb + S_GATE)); gated = true; }
                if (need) wait_cnt_warp(dep, need);
            }
#pragma unroll 1
            for (int k = 0; k < pend; k++) {
                const int s2 = s0 + k - (s0 + k >= NSTG ? NSTG : 0);
                if (qkv && k < 2) bulk_g2s1(sb + s2 * STG_B + 16384, g_st[layer] + ch * 2048 + (layer ? k * 1024 : tag * 128), layer ? 8192 : 1024, sb + B_BAR + (BB_FULL + s2) * 8, POL_N);
                tma2d_mc(da + s2 * STG_B, ta, (k & 1) * 256, ya + (k >> 1) * 16, sb + B_BAR + (BB_FULL + s2) * 8, ma, pol);
            }
#pragma unroll 1
            for (; h < nh; h++) {
                ACQ(bytes);
                if ((h & 1) != skip) tma3d_mc(db + st * STG_B, tb, row + h * 32, zb, sb + B_BAR + (BB_FULL + st) * 8, mb);
                tma2d_mc(da + st * STG_B, ta, (h & 1) * 256, ya + (h >> 1) * 16, sb + B_BAR + (BB_FULL + st) * 8, ma, pol);
                NEXT;
            }
#pragma unroll 1
            for (h = 0; h < 4 && !qkv && !layer; h++) { ACQ(0); NEXT; }
            if (qkv) {
#pragma unroll 1
                for (h = 8; h < 8 * t.b; h++) {
                    const int blk = qkv_blk(t, h >> 3);
                    ACQ(16384);
                    if (skip != 0) tma3d_mc(sb + st * STG_B, &p.t3[1][blk >> 6], (h & 7) * 64, blk & 63, sb + B_BAR + (BB_FULL + st) * 8, mb);
                    if (skip != 1) tma3d_mc(sb + st * STG_B + 8192, &p.t3[1][blk >> 6], (h & 7) * 64 + 32, blk & 63, sb + B_BAR + (BB_FULL + st) * 8, mb);
                    NEXT;
                }
            }
        } else if (t.type == T_CV) {
            const int q = t.a + rank;
            if (!gated && !t.dry) { wait_cnt_warp(g_gate, lds32(sb + S_GATE)); gated = true; }
            if (layer) {
                wait_cnt_warp(cnt_ptr(C_U, ch - 2), 32);
#pragma unroll 1
                for (int j = ch + 1; j >= 2; j--) {
                    ACQ(16 * PW * 4 + (j > 2 ? 4096 : 0));
                    bulk_g2s1(sb + st * STG_B, g_P + (((q >> 1) * 16 + j) * 2 + (q & 1)) * 16 * PW, 16 * PW * 4, sb + B_BAR + (BB_FULL + st) * 8, POL_N);
                    if (j > 2) bulk_g2s1(sb + st * STG_B + 12288, g_u + (((q >> 1) * 16 + ch + 1 - j) * 2 + (q & 1)) * 256, 4096, sb + B_BAR + (BB_FULL + st) * 8, POL_N);
                    NEXT;
                }
            } else {
#pragma unroll 1
                for (int j = min(ch, 1 + (ch & 1)); j >= 0; j--) {
                    if (j == 0 && ch >= 2) {
                        if (!t.dry) wait_cnt_warp(cnt_ptr(C_H, ch & ~1), 64);
#pragma unroll 1
                        for (int i = 0; i < ((ch & 1) || ch == 2 ? 1 : 2); i++) {
                            ACQ(16384);
                            bulk_g2s1(sb + st * STG_B, g_carry[i] + (ch * 16 + q) * 1024, 16384, sb + B_BAR + (BB_FULL + st) * 8, POL_LAST);
                            NEXT;
                        }
                    }
                    ACQ(32 * PW * 4);
                    bulk_g2s1(sb + st * STG_B, g_P + (q * 16 + j) * 32 * PW, 32 * PW * 4, sb + B_BAR + (BB_FULL + st) * 8, POL_N);
                    NEXT;
                }
            }
        }
    }
}

__device__ __forceinline__ uint4* qkv_dst(int layer, int ch, int w, int blk);
__device__ __forceinline__ uint4* op_dst(int layer, int ch, int slot, int w, uint32_t rank);
__device__ __forceinline__ uint64_t out_pol(int type, int layer, int ch) { return (type == T_QKV ? (!layer && ch > 1) : (layer && ch < 10)) ? POL_LATE : POL_SOON; }
__device__ __forceinline__ void bulk_release(const Params& p, uint32_t sb, int cl, uint32_t rank, int wg) {
    int nd = 0;
    for (int ti = 0; ti < MAXT; ti++) {
        const Task t = task_of(p.task[cl][ti], rank);
        const int type = t.type, layer = t.layer, ch = t.ch;
        if (type == T_END) break;
        if (type == T_FIN || (type == T_OP && (t.c & 32))) continue;
        if (type == T_OP && !layer) {
            mbar_wait(sb + B_BAR + (BB_DONE + wg) * 8, nd & 1);
            nd++;
            const int s0 = __shfl_sync(0xffffffffu, lds32(sb + B_ST + wg * 4), 0) + wg * 2;
            fence_async_smem();
#pragma unroll 1
            for (int w = 0; w < 4; w++)
                asm volatile("{.reg .pred p; elect.sync _|p,0xffffffff; @p cp.async.bulk.global.shared::cta.bulk_group.L2::cache_hint [%0],[%1],8192,%2; cp.async.bulk.commit_group;}"
                             ::"l"(op_dst(0, ch, t.c & 15, wg * 4 + w, rank)), "r"(sb + ((s0 + (w >> 1)) & (NSTG - 1)) * STG_B + (w & 1) * 8192), "l"(POL_SOON) : "memory");
            mbar_arrive1(sb + B_BAR + (BB_SF + wg) * 8);
            asm volatile("{.reg .pred p; elect.sync _|p,0xffffffff;\n"
                         "cp.async.bulk.wait_group 3; @p red.relaxed.gpu.global.add.u32 [%0],1; cp.async.bulk.wait_group 2; @p red.relaxed.gpu.global.add.u32 [%0+64],1;\n"
                         "cp.async.bulk.wait_group 1; @p red.relaxed.gpu.global.add.u32 [%0+128],1; cp.async.bulk.wait_group 0; @p red.relaxed.gpu.global.add.u32 [%0+192],1;}"
                         ::"l"(cnt_ptr(C_OP0 + rank * 2 + wg, ch)) : "memory");
#pragma unroll 1
            for (int i = 0; i < 8; i++) mbar_arrive1_cluster(mapa(sb + B_BAR + (BB_EMPTY + ((s0 + (i >> 2)) & (NSTG - 1))) * 8, i & 1));
            continue;
        }
#pragma unroll 1
        for (int u = 0; u < (type == T_QKV ? t.b : 1); u++) {
            const int blk = qkv_blk(t, u);
            unsigned* cnt = cnt_ptr(type == T_QKV ? C_QKV0 + layer : type == T_OP ? C_OP1 : layer ? C_H : C_CV, ch + (type == T_QKV && blk < 64 ? 16 : 0));
            const uint4* dst = type == T_QKV ? qkv_dst(layer, ch, wg * 4, blk) : op_dst(1, ch, t.c & 15, wg * 4, (t.blk >> 2) & 1) + 256;
            mbar_wait(sb + B_BAR + (BB_DONE + wg) * 8, nd & 1);
            nd++;
            if (type != T_CV) {
                fence_async_smem();
#pragma unroll
                for (int w = 0; w < 4; w++)
                    asm volatile("{.reg .pred p; elect.sync _|p,0xffffffff; @p cp.async.bulk.global.shared::cta.bulk_group.L2::cache_hint [%0],[%1],4096,%2;}"
                                 ::"l"(dst + (type == T_QKV ? (w >> 1) * 49152 + (w & 1) * 256 : w * 1024)), "r"(sb + B_OUT + (wg * 4 + w) * 4096), "l"(out_pol(type, layer, ch)) : "memory");
                asm volatile("cp.async.bulk.commit_group; cp.async.bulk.wait_group 0;" ::: "memory");
            }
            if (type != T_QKV) fence_async();
            if (!t.dry) asm volatile("{.reg .pred p; elect.sync _|p,0xffffffff; @p red.relaxed.gpu.global.add.u32 [%0],%1;}" ::"l"(cnt), "r"(type == T_QKV ? 2 : type == T_OP ? t.b : 1) : "memory");
            if (type == T_CV && !layer && !t.dry) {
                asm volatile("{.reg .pred p; elect.sync _|p,0xffffffff; @p cp.async.bulk.global.shared::cta.bulk_group [%0],[%1],4096;\n"
                             "cp.async.bulk.commit_group; cp.async.bulk.wait_group 0; @p red.relaxed.gpu.global.add.u32 [%2],1;}"
                             ::"l"(g_u + ((t.a + rank) * 16 + ch) * 512 + wg * 256), "r"(sb + B_UT + (ch & 1) * 8192 + wg * 4096), "l"(cnt_ptr(C_U, ch)) : "memory");
            }
            mbar_arrive1(sb + B_BAR + (BB_SF + wg) * 8);
        }
        PROF(wg && (threadIdx.x & 31) == 0, 3600 + ti * 4 + 3);
    }
}

__device__ __forceinline__ void stage_release(uint32_t sb, int w, int st) {
    if (!(w & 2)) mbar_arrive1_cluster(mapa(sb + B_BAR + (BB_EMPTY + st) * 8, w & 1));
}
template <bool ACC>
__device__ __forceinline__ void gemm_run(float* acc, uint32_t sb, int w, int h0, int h1, uint32_t& r0, uint32_t& r1, int& st, uint32_t& ph) {
    const uint64_t da0 = mkdesc(sb + (w >> 2) * 4096, 16, 512, 2), db0 = mkdesc(sb + 8192, 4096, 1024, 1);
    const uint32_t rel0 = mapa(sb + B_BAR + BB_EMPTY * 8, w & 1);
#pragma unroll 1
    for (int h = h0; h < h1; h++) {
        const uint64_t da = da0 + st * (STG_B >> 4), db = db0 + st * (STG_B >> 4);
        mbar_wait(sb + B_BAR + (BB_FULL + st) * 8, ph);
        if (ACC) wg_wait<1>();
        wg_fence();
        wgmma256<ACC>(acc, da, db);
        wgmma256<true>(acc, da + 2, db + 128);
        wg_commit();
        if (ACC) mbar_arrive1_cluster((w == 2 && h == LAGH - 1) ? sb + B_BAR + BB_GO * 8 : r0);
        r0 = r1;
        if (!(w & 2)) r1 = rel0 + st * 8;
        if (++st == NSTG) { st = 0; ph ^= 1; }
    }
}

__device__ __forceinline__ uint4* qkv_dst(int layer, int ch, int w, int blk) {
    return g_qkv[layer] + (size_t)((ch * 4 + (w >> 1)) * 32 + ((blk & 63) >> 1)) * 1536 + (blk >> 6) * 512 + (w & 1) * 256;
}
__device__ __forceinline__ uint4* op_dst(int layer, int ch, int slot, int w, uint32_t rank) {
    return g_pp[layer] + (size_t)(ch * MAXSPLIT + slot) * 8192 + (w * 32 + rank * 16) * 32;
}
__device__ __forceinline__ uint32_t ln2(uint32_t x, uint32_t m, uint32_t rh, uint32_t rl) {
    uint32_t d; asm volatile("{.reg .b32 t,u; sub.rn.bf16x2 t,%1,%2; mul.rn.bf16x2 u,t,%4; fma.rn.bf16x2 %0,t,%3,u;}" : "=r"(d) : "r"(x), "r"(m), "r"(rh), "r"(rl)); return d;
}
__device__ __forceinline__ void qkv_task(uint32_t sb, int w, int layer, int nu, int ng, int& nd, uint32_t& ph) {
    static_assert(NSTG == 8, "ring");
    const int lane = threadIdx.x & 31;
    const uint64_t db0 = mkdesc(sb, 4096, 1024, 1);
    const uint32_t rel = (w & 2) ? sb + B_BAR + BB_IDLE * 8 : mapa(sb + B_BAR + BB_EMPTY * 8, w & 1), full = sb + B_BAR + BB_FULL * 8;
    const uint32_t la = sb + w * 1024 + ((lane >> 3) & 1) * 512 + (lane >> 4) * 128 + (lane & 7) * 16, lo = sb + B_OUT + w * 4096 + (lane ^ (lane >> 3)) * 16;
    uint32_t m0, m1, h0, h1, l0, l1;
    uint4 A[32];
    {
        mbar_wait(full, ph);
        mbar_wait(full + 8, ph);
        const uint32_t sa = sb + (lane >> 4) * STG_B + 16384 + (w * 16 + (lane & 15)) * 8;
        uint2 v = lds64(sa);
        float sm = __uint_as_float(v.x), M2 = __uint_as_float(v.y);
        if (layer) {
            float e[8];
            e[0] = sm;
#pragma unroll
            for (int i = 1; i < 8; i++) { v = lds64(sa + i * 1024); e[i] = __uint_as_float(v.x); sm += e[i]; M2 += __uint_as_float(v.y); }
            sm += __shfl_xor_sync(0xffffffffu, sm, 16);
#pragma unroll
            for (int i = 0; i < 8; i++) { const float d = e[i] * (1.f / 32.f) - sm * (1.f / 512.f); M2 += 32.f * d * d; }
            M2 += __shfl_xor_sync(0xffffffffu, M2, 16);
        } else M2 = fmaxf(M2 - sm * sm * (1.f / 512.f), 0.f);
        A[0] = ldsm4(la); A[1] = ldsm4(la + 256);
        const float2 o = ln_finish(sm * (1.f / 512.f), M2 * (1.f / 512.f));
        const float r = rcp(o.y), rh = rbf(r);
        const uint32_t mm = pack2(o.x, o.x), hl = pack2(r - rh, rh);
        m0 = __shfl_sync(0xffffffffu, mm, lane >> 2); m1 = __shfl_sync(0xffffffffu, mm, (lane >> 2) + 8);
        l0 = __shfl_sync(0xffffffffu, hl, lane >> 2); l1 = __shfl_sync(0xffffffffu, hl, (lane >> 2) + 8);
        h0 = __byte_perm(l0, 0, 0x3232); h1 = __byte_perm(l1, 0, 0x3232); l0 = __byte_perm(l0, 0, 0x1010); l1 = __byte_perm(l1, 0, 0x1010);
    }
    float acc[64];
#define QNRM(i) A[i] = make_uint4(ln2(A[i].x, m0, h0, l0), ln2(A[i].y, m1, h1, l1), ln2(A[i].z, m0, h0, l0), ln2(A[i].w, m1, h1, l1))
    if (w >> 2) mbar_wait(sb + B_BAR + BB_GO * 8, ~ng & 1);
#pragma unroll
    for (int h = 0; h < 16; h++) {
        const uint64_t db = db0 + ((h & 7) * (STG_B >> 4) + 512);
        if (h < 15) { A[(2 * h + 2) & 31] = ldsm4(la + ((h + 1) & 7) * STG_B); A[(2 * h + 3) & 31] = ldsm4(la + ((h + 1) & 7) * STG_B + 256); }
        const bool ok = h >= 14 || mbar_test(full + ((h + 2) & 7) * 8, ph ^ ((h + 2) >> 3));
        QNRM(2 * h); QNRM(2 * h + 1);
        if (h) wg_wait<1>();
        wg_fence();
        if (h) wgmma128r<true>(acc, A[2 * h], db); else wgmma128r<false>(acc, A[0], db);
        wgmma128r<true>(acc, A[2 * h + 1], db + 128);
        wg_commit();
        if (h >= 2) mbar_arrive1_cluster(rel + ((h - 2) & 7) * 8);
        if (h == LAGQ - 1 && w == 2) mbar_arrive1(sb + B_BAR + BB_GO * 8);
        if (!ok) mbar_wait(full + ((h + 2) & 7) * 8, ph ^ ((h + 2) >> 3));
    }
#pragma unroll 1
    for (int u = 1;; u++) {
        mbar_wait(sb + B_BAR + (BB_SF + (w >> 2)) * 8, (nd & 1) ^ 1);
        if (u < nu) mbar_wait(full, ph);
        wg_wait<1>();
        mbar_arrive1_cluster(rel + 48);
        wg_wait<0>();
        mbar_arrive1_cluster(rel + 56);
        uint4 o[8];
#pragma unroll
        for (int n = 0; n < 8; n++) {
            const float* a = acc + (n >> 1) * 16 + (n & 1) * 2;
            o[n] = make_uint4(pack2(a[0], a[1]), pack2(a[4], a[5]), pack2(a[8], a[9]), pack2(a[12], a[13]));
            sts128(lo + n * 512, o[n].x, o[n].y, o[n].z, o[n].w);
        }
        __syncwarp();
        mbar_arrive1(sb + B_BAR + (BB_DONE + (w >> 2)) * 8);
        nd++;
        if (u == nu) break;
#pragma unroll
        for (int h = 0; h < 8; h++) {
            const uint64_t db = db0 + h * (STG_B >> 4);
            if (h) { mbar_wait(full + h * 8, ph); wg_wait<1>(); }
            wg_fence();
            if (h) wgmma128r<true>(acc, A[4 * h], db); else wgmma128r<false>(acc, A[0], db);
            wgmma128r<true>(acc, A[4 * h + 1], db + 128);
            wgmma128r<true>(acc, A[4 * h + 2], db + 512);
            wgmma128r<true>(acc, A[4 * h + 3], db + 640);
            wg_commit();
            if (h >= 2) mbar_arrive1_cluster(rel + (h - 2) * 8);
        }
        ph ^= 1;
    }
}

template <int NB>
__device__ __forceinline__ void load_resid(uint32_t* r, int layer, int ch, int w, int cb) {
    const uint32_t* rp = (const uint32_t*)(g_xA[layer] + (ch * 8 + (cb >> 2)) * 1024 + w * 128 + (cb & 3) * 16) + (threadIdx.x & 31);
#pragma unroll
    for (int i = 0; i < NB * 4; i++) r[i] = __ldcg(rp + (i >> 1) * 32 + (i & 1) * 256);
}
template <int NS>
__device__ __forceinline__ void part_load(uint4* v, int layer, int ch, int w, int cb, int ns) {
    const uint4* src = g_pp[layer] + (size_t)ch * MAXSPLIT * 8192 + (w * 32 + cb) * 32 + (threadIdx.x & 31);
#pragma unroll
    for (int i = 0; i < 2 * NS; i++) {
        asm volatile("{.reg .pred p; .reg .b128 t; setp.gt.s32 p,%6,0; mov.b128 t,{0,0,0,0}; @p ld.relaxed.gpu.global.L2::cache_hint.b128 t,[%4],%5; mov.b128 {%0,%1,%2,%3},t;}"
                     : "=r"(v[i].x), "=r"(v[i].y), "=r"(v[i].z), "=r"(v[i].w) : "l"(src + (i / NS) * 32 + (i % NS) * 8192), "l"(POL_LAST), "r"(ns - i % NS) : "memory");
    }
}
template <int NS>
__device__ __forceinline__ void part_sum(float* x, const uint4* v, const uint32_t* r) {
    const int dg = ((threadIdx.x & 31) >> 2) - 2 * (threadIdx.x & 3);
    const uint32_t idm = dg == 0 ? 0x00003f80u : dg == 1 ? 0x3f800000u : 0u;
#pragma unroll
    for (int b = 0; b < 2; b++) {
        float* y = x + b * 8;
#pragma unroll
        for (int i = 0; i < 8; i++) y[i] = 0;
#pragma unroll
        for (int s = 0; s < NS; s++) { mma8(y, v[b * NS + s].x, v[b * NS + s].y, idm); mma8(y + 4, v[b * NS + s].z, v[b * NS + s].w, idm); }
#pragma unroll
        for (int i = 0; i < 4; i++) { y[2 * i] = rbf(rbf(y[2 * i]) + blo(r[b * 4 + i])); y[2 * i + 1] = rbf(rbf(y[2 * i + 1]) + bhi(r[b * 4 + i])); }
    }
}

__device__ __forceinline__ float4 row_stats32(const float* x) {
    float a = (x[0] + x[1]) + (x[4] + x[5]) + (x[8] + x[9]) + (x[12] + x[13]);
    float b = (x[2] + x[3]) + (x[6] + x[7]) + (x[10] + x[11]) + (x[14] + x[15]);
    a += __shfl_xor_sync(0xffffffffu, a, 1); b += __shfl_xor_sync(0xffffffffu, b, 1);
    a += __shfl_xor_sync(0xffffffffu, a, 2); b += __shfl_xor_sync(0xffffffffu, b, 2);
    const float ma = a * (1.f / 32.f), mb = b * (1.f / 32.f);
    float qa = 0, qb = 0;
#pragma unroll
    for (int i = 0; i < 4; i++) {
        float d0 = x[4 * i] - ma, d1 = x[4 * i + 1] - ma, d2 = x[4 * i + 2] - mb, d3 = x[4 * i + 3] - mb;
        qa += d0 * d0 + d1 * d1; qb += d2 * d2 + d3 * d3;
    }
    qa += __shfl_xor_sync(0xffffffffu, qa, 1); qb += __shfl_xor_sync(0xffffffffu, qb, 1);
    qa += __shfl_xor_sync(0xffffffffu, qa, 2); qb += __shfl_xor_sync(0xffffffffu, qb, 2);
    return make_float4(a, qa, b, qb);
}

__device__ __forceinline__ void conv_stage(float* Y, uint32_t pbase, uint32_t ubase) {
    const int lane = threadIdx.x & 31, w = threadIdx.x >> 5, g = lane >> 2, c = lane & 3;
#pragma unroll
    for (int cp = 0; cp < 2; cp++) {
        const int chl = w * 4 + cp * 2 + (lane >> 4);
        const uint4 b = ldsm4(ubase + chl * 256 + ((lane >> 3) & 1) * 128 + (((lane & 7) ^ (chl & 7)) << 4));
#pragma unroll
        for (int h = 0; h < 2; h++) {
            const uint32_t pa = pbase + ((w * 4 + cp * 2 + h) * PW + 16 + g - 2 * c) * 4;
            uint32_t lo = lds32(pa - 32);
#pragma unroll
            for (int d = 0; d < 8; d++) {
                const uint32_t a0 = lds32(pa + d * 64), a1 = lds32(pa + d * 64 + 32);
                mma16(Y + ((cp * 2 + h) * 8 + d) * 4, a0, a1, lo, a0, h ? b.z : b.x, h ? b.w : b.y);
                lo = a1;
            }
        }
    }
}

__device__ __forceinline__ void conv_combine(const float* y8, float* cur, float* nxt) {
    const int lane = threadIdx.x & 31, c = lane & 3;
    cur[0] = y8[0]; cur[1] = y8[1] + y8[4]; cur[2] = y8[2]; cur[3] = y8[3] + y8[6];
    nxt[0] = y8[29]; nxt[1] = 0.f; nxt[2] = y8[31]; nxt[3] = 0.f;
#pragma unroll
    for (int e = 1; e < 4; e++) {
        const int src = (lane & ~3) | ((c - e) & 3);
        const float v0 = __shfl_sync(0xffffffffu, y8[8 * e] + y8[8 * e - 3], src), v1 = __shfl_sync(0xffffffffu, y8[8 * e + 1] + y8[8 * e + 4], src);
        const float v2 = __shfl_sync(0xffffffffu, y8[8 * e + 2] + y8[8 * e - 1], src), v3 = __shfl_sync(0xffffffffu, y8[8 * e + 3] + y8[8 * e + 6], src);
        if (c >= e) { cur[0] += v0; cur[1] += v1; cur[2] += v2; cur[3] += v3; }
        else { nxt[0] += v0; nxt[1] += v1; nxt[2] += v2; nxt[3] += v3; }
    }
}

__device__ __forceinline__ void hist_task(float* Y, uint32_t sb, int w, int ch, int q, int& st, uint32_t& ph, int nd) {
    const int lane = threadIdx.x & 31, chl = w * 2 + (lane >> 4);
    const uint32_t ua = sb + 12288 + chl * 256 + ((lane >> 3) & 1) * 128 + (((lane & 7) ^ (chl & 7)) << 4);
    const uint32_t pa = sb + (w * 2 * PW + 16 + (lane >> 2) - 2 * (lane & 3)) * 4;
#pragma unroll
    for (int i = 0; i < 128; i++) Y[i] = 0;
    uint4 b1 = make_uint4(0, 0, 0, 0);
#pragma unroll 1
    for (int j = ch + 1; j >= 2; j--) {
        const uint4 b0 = b1;
        mbar_wait(sb + B_BAR + (BB_FULL + st) * 8, ph);
        b1 = ldsm4(ua + st * STG_B);
        if (j == 2) b1 = make_uint4(0, 0, 0, 0);
#pragma unroll
        for (int h = 0; h < 2; h++) {
            const uint32_t o = pa + st * STG_B + h * PW * 4;
            uint32_t lo = lds32(o - 32);
#pragma unroll
            for (int d = 0; d < 8; d++) {
                const uint32_t a0 = lds32(o + d * 64), a1 = lds32(o + d * 64 + 32);
                mma16(Y + (h * 16 + d) * 4, a0, a1, lo, a0, h ? b0.z : b0.x, h ? b0.w : b0.y);
                mma16(Y + (h * 16 + 8 + d) * 4, a0, a1, lo, a0, h ? b1.z : b1.x, h ? b1.w : b1.y);
                lo = a1;
            }
        }
        bar_sync(NB_WG + (w >> 2), 128);
        stage_release(sb, w, st);
        if (++st == NSTG) { st = 0; ph ^= 1; }
    }
    mbar_wait(sb + B_BAR + (BB_SF + (w >> 2)) * 8, (nd & 1) ^ 1);
#pragma unroll
    for (int h = 0; h < 2; h++) {
        const int o = ((ch * 16 + (q >> 1)) * 4 + (w & 1) * 2 + h) * 256 + ((q & 1) * 4 + (w >> 1)) * 32 + lane;
        float c0[4], n0[4], c1[4], n1[4];
        conv_combine(Y + h * 64, c0, n0); conv_combine(Y + h * 64 + 32, c1, n1);
        g_carry[0][o] = make_float4(c0[0], c0[1], c0[2], c0[3]);
        g_carry[0][o + 16384] = make_float4(c1[0] + n0[0], c1[1] + n0[1], c1[2] + n0[2], c1[3] + n0[3]);
        g_carry[1][o + 32768] = make_float4(n1[0], n1[1], n1[2], n1[3]);
    }
}

__device__ __forceinline__ void conv_task(const Params& p, float* Y, uint32_t sb, int w, int ch, int q, int ns, bool dry, int& st, uint32_t& ph, int nd) {
    const int tid = threadIdx.x, lane = tid & 31, g = lane >> 2, c = lane & 3;
    uint32_t dk[4];
    const uint32_t sg = (~ch & 2) << 30;
    int sr = st;
    float x[16];
    uint32_t rs[8];
    load_resid<2>(rs, 0, ch, w, 2 * q);
    PROF(tid == 128, 2048 + ch * 8);
#pragma unroll
    for (int i = 0; i < 128; i++) Y[i] = 0;
#pragma unroll 1
    for (int j = min(ch, 1 + (ch & 1)); j >= 1; j--) {
        mbar_wait(sb + B_BAR + (BB_FULL + st) * 8, ph);
        conv_stage(Y, sb + st * STG_B, sb + B_UT + ((ch - j) & 1) * 8192);
        if (++st == NSTG) { st = 0; ph ^= 1; }
    }
#pragma unroll 1
    for (int i = 0; i < min(ch, (ch & 1) ? 2 : 3); i++) {
        if (i) mbar_wait(sb + B_BAR + (BB_FULL + st) * 8, ph);
        const uint32_t ca = sb + (i ? st * STG_B : B_SP) + tid * 16;
#pragma unroll
        for (int k = 0; k < 4; k++) {
            const uint4 cr = lds128(ca + k * 4096);
            Y[k * 32] += __uint_as_float(cr.x); Y[k * 32 + 1] += __uint_as_float(cr.y); Y[k * 32 + 2] += __uint_as_float(cr.z); Y[k * 32 + 3] += __uint_as_float(cr.w);
        }
        if (i && ++st == NSTG) { st = 0; ph ^= 1; }
    }
    bar_sync(NB_C, 256);
#pragma unroll 1
    for (; sr != st; sr = (sr + 1) & (NSTG - 1)) stage_release(sb, w, sr);
    const uint32_t ut = sb + B_UT + (ch & 1) * 8192;
    mbar_wait(sb + B_BAR + (BB_SF + (w >> 2)) * 8, (nd & 1) ^ 1);
    mbar_wait(sb + B_BAR + (BB_SF + 1 - (w >> 2)) * 8, (nd & 1) ^ 1);
    PROF(tid == 128, 2048 + ch * 8 + 7);
    {
        uint4 v[2 * OPS1];
        wait_cnt_warp(cnt_ptr(C_OP0 + (q >> 3) * 2 + (w >> 2), ch + (w & 3) * 16), ns);
        part_load<OPS1>(v, 0, ch, w, 2 * q, ns);
        part_sum<OPS1>(x, v, rs);
        const float4 s = row_stats32(x);
        float2* dst = g_st2 + ((ch & 1) * 16 + q) * 128 + w * 16 + g + c * 8;
        asm volatile("{.reg .pred p; setp.ne.u32 p,%2,0; @p st.relaxed.gpu.global.b64 [%0],%1;}" ::"l"(dst),
                     "l"(((uint64_t)((__float_as_uint(c ? s.w : s.y) & 0x7fffffffu) | sg) << 32) | __float_as_uint(c ? s.z : s.x)), "r"((uint32_t)(c < 2 && !dry)) : "memory");
        PROF(tid == 128, 2048 + ch * 8 + 1);
    }
#pragma unroll
    for (int i = 0; i < 4; i++) asm volatile("ld.global.nc.u32 %0,[%1];" : "=r"(dk[i]) : "l"(p.Dskip + q * 32 + i * 8 + 2 * c));
    float2 ln0, ln1;
    {
        const float2* src = g_st2 + ((ch & 1) * 16 + (lane >> 4) * 8) * 128 + w * 16 + (lane & 15);
        uint64_t v[8];
        int n = 0;
#pragma unroll
        for (int i = 0; i < 8; i++) v[i] = (uint64_t)~sg << 32;
        while (true) {
            bool bad = false;
#pragma unroll
            for (int i = 0; i < 8; i++) asm volatile("{.reg .pred p; setp.lt.s32 p,%2,0; @p ld.relaxed.gpu.global.b64 %0,[%1];}" : "+l"(v[i]) : "l"(src + i * 128), "r"((uint32_t)(v[i] >> 32) ^ sg) : "memory");
#pragma unroll
            for (int i = 0; i < 8; i++) bad = bad || (int)((uint32_t)(v[i] >> 32) ^ sg) < 0;
            if (!__any_sync(0xffffffffu, bad && !dry)) break;
            if (++n > 2000000) __trap();
        }
        float sm = 0;
#pragma unroll
        for (int i = 0; i < 8; i++) sm += __uint_as_float((uint32_t)v[i]);
        sm += __shfl_xor_sync(0xffffffffu, sm, 16);
        const float mean = sm * (1.f / 512.f);
        float M2 = 0;
#pragma unroll
        for (int i = 0; i < 8; i++) { const float d = __uint_as_float((uint32_t)v[i]) * (1.f / 32.f) - mean; M2 += fabsf(__uint_as_float((uint32_t)(v[i] >> 32))) + 32.f * d * d; }
        M2 += __shfl_xor_sync(0xffffffffu, M2, 16);
        const float2 o = ln_finish(mean, M2 * (1.f / 512.f));
        ln0.x = __shfl_sync(0xffffffffu, o.x, g); ln0.y = __shfl_sync(0xffffffffu, o.y, g);
        ln1.x = __shfl_sync(0xffffffffu, o.x, g + 8); ln1.y = __shfl_sync(0xffffffffu, o.y, g + 8);
    }
    PROF(tid == 128, 2048 + ch * 8 + 2);
    uint32_t u[8];
#pragma unroll
    for (int i = 0; i < 8; i++) {
        const float2 l = (i & 1) ? ln1 : ln0;
        u[i] = pack2(__fdividef(rbf(x[2 * i] - l.x), l.y), __fdividef(rbf(x[2 * i + 1] - l.x), l.y));
        const int chl = (i >> 1) * 8 + g;
        sts32(ut + chl * 256 + (i & 1) * 128 + ((w ^ g) << 4) + c * 4, movm(u[i]));
    }
    bar_sync(NB_C, 256);
    mbar_wait(sb + B_BAR + (BB_FULL + st) * 8, ph);
    PROF(tid == 128, 2048 + ch * 8 + 3);
    conv_stage(Y, sb + st * STG_B, ut);
    uint32_t yp[4][2];
    float nxt[4][4];
    {
        float y[4][4];
#pragma unroll
        for (int k = 0; k < 4; k++) conv_combine(Y + k * 32, y[k], nxt[k]);
#pragma unroll
        for (int i = 0; i < 4; i++) { yp[i][0] = pack2(y[0][i], y[1][i]); yp[i][1] = pack2(y[2][i], y[3][i]); }
    }
#pragma unroll
    for (int i = 0; i < 4; i++) sts64(sb + B_YT + (16 * (2 * c + (i & 1)) + g + (i >> 1) * 8) * 80 + w * 8, yp[i][0], yp[i][1]);
    bar_sync(NB_C, 256);
    stage_release(sb, w, st);
    if (++st == NSTG) { st = 0; ph ^= 1; }
    PROF(tid == 128, 2048 + ch * 8 + 4);
    uint32_t xo[8];
    uint32_t* dA = (uint32_t*)(g_xA[1] + (ch * 8 + (q >> 1)) * 1024 + (w * 2) * 64 + (q & 1) * 32) + lane;
#pragma unroll
    for (int i = 0; i < 8; i++) {
        const int col = (i >> 1) * 8 + 2 * c;
        const uint32_t yv = lds32(sb + B_YT + (w * 16 + g + (i & 1) * 8) * 80 + col * 2);
        const uint32_t dv = dk[i >> 1];
        x[2 * i] = rbf(x[2 * i] + rbf(blo(yv) + rbf(blo(u[i]) * blo(dv))));
        x[2 * i + 1] = rbf(x[2 * i + 1] + rbf(bhi(yv) + rbf(bhi(u[i]) * bhi(dv))));
        xo[i] = pack2(x[2 * i], x[2 * i + 1]);
        dA[(i >> 1) * 32 + (i & 1) * 256] = xo[i];
    }
    {
        const float4 s = row_stats32(x);
        float2* dst = g_st[1] + (ch * 16 + q) * 128 + w * 16 + g;
        if (c == 0) dst[0] = make_float2(s.x, s.y);
        if (c == 1) dst[8] = make_float2(s.z, s.w);
        __syncwarp();
    }
    PROF(tid == 128, 2048 + ch * 8 + 5);
    mbar_arrive1(sb + B_BAR + (BB_DONE + (w >> 2)) * 8);
    bar_sync(NB_C, 256);
#pragma unroll
    for (int k = 0; k < 4; k++) sts128(sb + B_SP + k * 4096 + tid * 16, __float_as_uint(nxt[k][0]), __float_as_uint(nxt[k][1]), __float_as_uint(nxt[k][2]), __float_as_uint(nxt[k][3]));
    PROF(tid == 128, 2048 + ch * 8 + 6);
}

__device__ __forceinline__ void out_store(const Params& p, const float* x, int ch, int cb) {
    const int lane = threadIdx.x & 31, w = threadIdx.x >> 5, g = lane >> 2, c = lane & 3;
#pragma unroll
    for (int h = 0; h < 2; h++) {
        const float* y = x + h * 2;
        uint32_t v0 = pack2(y[0], y[1]), v1 = pack2(y[4], y[5]), v2 = pack2(y[8], y[9]), v3 = pack2(y[12], y[13]);
        uint32_t t0 = (c & 1) ? v0 : v1, t1 = (c & 1) ? v2 : v3;
        t0 = __shfl_xor_sync(0xffffffffu, t0, 1); t1 = __shfl_xor_sync(0xffffffffu, t1, 1);
        if (c & 1) { v0 = t0; v2 = t1; } else { v1 = t0; v3 = t1; }
        t0 = (c & 2) ? v0 : v2; t1 = (c & 2) ? v1 : v3;
        t0 = __shfl_xor_sync(0xffffffffu, t0, 2); t1 = __shfl_xor_sync(0xffffffffu, t1, 2);
        if (c & 2) { v0 = t0; v1 = t1; } else { v2 = t0; v3 = t1; }
        stg128((uint4*)(p.out + (size_t)(ch * 128 + w * 16 + g + h * 8) * 512 + cb * 16 + c * 8), make_uint4(v0, v1, v2, v3), POL_LATE);
    }
}
__device__ __forceinline__ void fin_task(const Params& p, int ch, int cb0, int ncb, int ns, bool dry) {
    const int w = threadIdx.x >> 5;
    uint32_t rs[8];
    wait_cnt_warp(cnt_ptr(C_CV, ch), dry ? 0 : 32);
    load_resid<2>(rs, 1, ch, w, cb0);
    wait_cnt_warp(cnt_ptr(C_OP1, ch), dry ? 0 : 256);
    for (int cb = cb0; cb < cb0 + ncb; cb += 2) {
        float x[16];
        if (cb != cb0) load_resid<2>(rs, 1, ch, w, cb);
        uint4 v[32];
        part_load<16>(v, 1, ch, w, cb, ns);
        part_sum<16>(x, v, rs);
        out_store(p, x, ch, cb);
    }
}

__device__ __forceinline__ void bulk_consumer(const Params& p, uint32_t sb, int cl, uint32_t rank, int w) {
    int st = 0; uint32_t ph = 0; int nd = 0, ng = 0;
    for (int ti = 0; ti < MAXT; ti++) {
        const Task t = task_of(p.task[cl][ti], rank);
        const int type = t.type, layer = t.layer, ch = t.ch;
        if (type == T_END) break;
        bool staged = type != T_FIN;
        PROF(threadIdx.x == 0, 3600 + ti * 4);
        if (type <= T_OP) {
            CPROF(0);
            if ((w >> 2) && type == T_OP) mbar_wait(sb + B_BAR + BB_GO * 8, ng & 1);
            ng++;
            CPROF(1);
        }
        if (type == T_QKV) {
            staged = false;
            #pragma unroll 1
            while (st) {
                if (!(w & 3)) { mbar_wait(sb + B_BAR + (BB_FULL + st) * 8, ph); stage_release(sb, 0, st); stage_release(sb, 1, st); }
                if (++st == NSTG) { st = 0; ph ^= 1; }
            }
            qkv_task(sb, w, layer, t.b, ng, nd, ph);
            PROF(threadIdx.x == 128, 3600 + ti * 4 + 1);
        } else if (type == T_OP) {
            const int lane = threadIdx.x & 31;
            float acc[128];
            uint32_t r0 = sb + B_BAR + BB_IDLE * 8, r1 = r0;
            gemm_run<false>(acc, sb, w, 0, 1, r0, r1, st, ph);
            gemm_run<true>(acc, sb, w, 1, 2 * t.b, r0, r1, st, ph);
            mbar_wait(sb + B_BAR + (BB_SF + (w >> 2)) * 8, (nd & 1) ^ 1);
            wg_wait<1>();
            mbar_arrive1_cluster(r0);
            wg_wait<0>();
            mbar_arrive1_cluster(r1);
            PROF(threadIdx.x == 128, 3600 + ti * 4 + 1);
            if (t.c & 32) {
                staged = false;
#pragma unroll
                for (int j = 0; j < 16; j += 4) {
                    uint32_t rs[16];
                    load_resid<4>(rs, 1, ch, w, (t.blk & 4) * 4 + j);
#pragma unroll
                    for (int i = 0; i < 16; i++) { float* y = acc + j * 8 + 2 * i; y[0] = rbf(y[0]) + blo(rs[i]); y[1] = rbf(y[1]) + bhi(rs[i]); }
                    out_store(p, acc + j * 8, ch, (t.blk & 4) * 4 + j); out_store(p, acc + j * 8 + 16, ch, (t.blk & 4) * 4 + j + 2);
                }
            } else if (!layer) {
                const int s2 = st + (w >> 1);
                const uint32_t o = sb + (s2 & (NSTG - 1)) * STG_B + (w & 1) * 8192 + lane * 16;
                mbar_wait(sb + B_BAR + (BB_FULL + (s2 & (NSTG - 1))) * 8, ph ^ (s2 >= NSTG));
#pragma unroll
                for (int j = 0; j < 16; j++)
                    sts128(o + j * 512, pack2(acc[j * 8], acc[j * 8 + 1]), pack2(acc[j * 8 + 2], acc[j * 8 + 3]), pack2(acc[j * 8 + 4], acc[j * 8 + 5]), pack2(acc[j * 8 + 6], acc[j * 8 + 7]));
                sts32(sb + B_ST + (w >> 2) * 4, st);
                st += 4;
                if (st >= NSTG) { st -= NSTG; ph ^= 1; }
            } else {
                uint4* dst = op_dst(layer, ch, t.c & 15, w, (t.blk >> 2) & 1) + lane;
#pragma unroll
                for (int n = 0; n < 16; n++) {
                    const int j = (n >> 1) + (n & 1) * 8;
                    const uint4 v = make_uint4(pack2(acc[j * 8], acc[j * 8 + 1]), pack2(acc[j * 8 + 2], acc[j * 8 + 3]), pack2(acc[j * 8 + 4], acc[j * 8 + 5]), pack2(acc[j * 8 + 6], acc[j * 8 + 7]));
                    if (j < 16 - NSB) stg128(dst + j * 32, v, out_pol(T_OP, layer, ch)); else sts128(sb + B_OUT + (w * NSB + j - (16 - NSB)) * 512 + lane * 16, v.x, v.y, v.z, v.w);
                }
            }
        } else if (type == T_CV) {
            float acc[128];
            if (layer) hist_task(acc, sb, w, ch, t.a + rank, st, ph, nd);
            else { conv_task(p, acc, sb, w, ch, t.a + rank, t.b, t.dry, st, ph, nd); staged = false; nd++; }
        } else {
            fin_task(p, ch, t.a + rank * t.c, t.c, t.b, t.dry);
        }
        if (staged) {
            __syncwarp();
            mbar_arrive1(sb + B_BAR + (BB_DONE + (w >> 2)) * 8);
            nd++;
        }
        CPROF(6);
        PROF(threadIdx.x == 128, 3600 + ti * 4 + 2);
        __syncwarp();
    }
}

constexpr int P_Y = 131072  , P_PRM = P_Y  , P_K6 = P_PRM + 8192  ,
              P_P = P_Y + 40960  , P_U = P_P + 33280  , P_END = P_U + 17408, P_X = 98304  ;
static_assert(P_END <= B_BAR && P_END <= R_BAR, "prologue scratch");
#define KGUN 2
constexpr int KGU = KGUN;
__device__ __forceinline__ void csq(float& r, float& i) { const float t = r * i; r = fmaf(r, r, -(i * i)); i = t + t; }
__device__ __forceinline__ void cpow(float ar, float ph, float p, float& r, float& i) {
    const float e = ex2(ar * p);
    const float u = ph * p, n = fabsf(u) < 4194304.f ? (u + 12582912.f) - 12582912.f : u;
    const float t = (u - n) * 6.283185307179586f;
    r = e * __cosf(t); i = e * __sinf(t);
}
__device__ __forceinline__ void mma_tf32(float* c, float a0, float a1, float a2, float a3, float b0, float b1) {
    asm volatile("mma.sync.aligned.m16n8k8.row.col.f32.tf32.tf32.f32 {%0,%1,%2,%3},{%4,%5,%6,%7},{%8,%9},{%0,%1,%2,%3};"
                 : "+f"(c[0]), "+f"(c[1]), "+f"(c[2]), "+f"(c[3])
                 : "r"(__float_as_uint(a0)), "r"(__float_as_uint(a1)), "r"(__float_as_uint(a2)), "r"(__float_as_uint(a3)), "r"(__float_as_uint(b0)), "r"(__float_as_uint(b1)));
}

struct ProRegs { uint32_t v[2][4], ldt[2]; };
__device__ __forceinline__ void prologue_load(const ProArgs& a, int b, ProRegs& pr) {
    const int w = threadIdx.x >> 5;
#pragma unroll
    for (int i = 0; i < 2; i++) {
        const int gi = b * 512 + (w & 3) * 128 + ((w >> 2) & 1) * 64 + i * 32 + (threadIdx.x & 31);
        pr.ldt[i] = __ldg((const uint16_t*)a.ldt + b * 4 + (w & 3));
        pr.v[i][0] = __ldg((const uint16_t*)a.lAr + gi); pr.v[i][1] = __ldg((const uint16_t*)a.Ai + gi);
        pr.v[i][2] = __ldg((const uint16_t*)a.Cr + gi); pr.v[i][3] = __ldg((const uint16_t*)a.Ci + gi);
    }
}
__device__ __forceinline__ void prologue(const ProArgs& a, uint32_t sb, int b, int w, const ProRegs& pr) {
    const int tid = threadIdx.x, lane = tid & 31, g = lane >> 2, c = lane & 3;
    const int d0 = b * 4;
    if (w >= 8) {
        const int t2 = tid - 256;
        if (w < 10) {
            const int row = b * 16 + (w - 8) * 8 + g;
            const float2 r = row_stats512((const uint4*)(a.x + (size_t)row * 512) + c, 8, 4);
            const float2 l = ln_finish(r.x * (1.f / 512.f), fmaxf(r.y - r.x * r.x * (1.f / 512.f), 0.f) * (1.f / 512.f));
            if (c == (g >> 1)) asm volatile("st.relaxed.gpu.global.u32 [%0],%1;" ::"l"(g_ln0 + row), "r"(pack2(l.x, l.y)) : "memory");
        }
        PROF(t2 == 0, 3516);
        const int gi = b * 128 + t2;
        if (t2 < 32) acc_init(a.mem0, b * 32 + t2);
        if (t2 >= 112) ((uint4*)g_st2)[b * 16 + t2 - 112] = make_uint4(0, 0, 0, 0);
        if (gi < 13 * 64) g_cnt[gi] = 0;
        bar_sync(6, 384);
        if (gi < 256) g_st[0][(gi >> 7) * 2048 + (lds32(sb + S_TAG) ^ 1) * 128 + (gi & 127)] = make_float2(0.f, 0.f);
        asm volatile("{.reg .pred p; elect.sync _|p,0xffffffff; @p cp.async.bulk.prefetch.L2.global [%0],32768;}"
                     ::"l"((w == 8 ? a.Wq : w == 9 ? a.Wk : w == 10 ? a.Wv : a.Wo) + (size_t)b * 16384) : "memory");
        mbar_wait(sb + S_XBAR, 0);
#pragma unroll 1
        for (int h = 0; h < 2; h++) {
            uint32_t l[8];
            int n = 0;
            while (true) {
                bool ok = true;
#pragma unroll
                for (int i = 0; i < 8; i++) asm volatile("ld.relaxed.gpu.global.u32 %0,[%1];" : "=r"(l[i]) : "l"(g_ln0 + h * 1024 + i * 128 + t2) : "memory");
#pragma unroll
                for (int i = 0; i < 8; i++) ok = ok && l[i];
                if (__all_sync(0xffffffffu, ok)) break;
                if (++n > 2000000) __trap();
            }
#pragma unroll
            for (int i = 0; i < 8; i++) {
                const int t = h * 1024 + i * 128 + t2;
                const uint2 x = lds64(sb + P_X + t * 16 + (b & 1) * 8);
                const float m = blo(l[i]), rs = rcp(bhi(l[i]));
                const uint32_t u0 = pack2(rbf(blo(x.x) - m) * rs, rbf(bhi(x.x) - m) * rs), u1 = pack2(rbf(blo(x.y) - m) * rs, rbf(bhi(x.y) - m) * rs);
                sts128(sb + P_X + t * 16, x.x, x.y, u0, u1);
                const uint32_t o = sb + P_U + ((t >> 3) & 1) * 2176 + ((t >> 4) + 8) * 16 + (t & 7) * 2;
                asm volatile("st.shared.u16 [%0],%1;" ::"r"(o), "h"((uint16_t)u0) : "memory");
                asm volatile("st.shared.u16 [%0],%1;" ::"r"(o + 4352), "h"((uint16_t)(u0 >> 16)) : "memory");
                asm volatile("st.shared.u16 [%0],%1;" ::"r"(o + 8704), "h"((uint16_t)u1) : "memory");
                asm volatile("st.shared.u16 [%0],%1;" ::"r"(o + 13056), "h"((uint16_t)(u1 >> 16)) : "memory");
            }
        }
        PROF(t2 == 0, 3517);
        bar_sync(9, 384);
        fence_async_smem();
#pragma unroll 1
        for (int j = 0; j < 16; j++) {
            const int d = d0 + w - 8;
            asm volatile("{.reg .pred p; elect.sync _|p,0xffffffff; @p cp.async.bulk.global.shared::cta.bulk_group [%0],[%1],%2;}" ::"l"(g_P + (((d >> 5) * 16 + j) * 32 + (d & 31)) * PW),
                         "r"(sb + P_P + ((w - 8) * 2080 + j * 128) * 4), "r"(PW * 4) : "memory");
        }
        asm volatile("cp.async.bulk.commit_group; cp.async.bulk.wait_group 0;" ::: "memory");
        bar_arrive(10, 384);
        return;
    }
#pragma unroll
    for (int i = 0; i < 2; i++) {
        const float dt = rbf(expf(blo(pr.ldt[i])));
        const float ar = -rbf(expf(blo(pr.v[i][0]))) * dt, ai = blo(pr.v[i][1]) * dt;
        sts128(sb + P_PRM + (w * 64 + i * 32 + lane) * 16, __float_as_uint(ar * 1.4426950408889634f), __float_as_uint(ai * 0.15915494309189535f),
               __float_as_uint(2.f * (blo(pr.v[i][2]) * dt)), __float_as_uint(2.f * (blo(pr.v[i][3]) * dt)));
    }
    if (tid < 64) sts128(sb + P_U + (tid >> 3) * 2176 + (tid & 7) * 16, 0, 0, 0, 0);
    bar_arrive(6, 384);
    __syncwarp();
    PROF(tid == 0, 3510);
    const int ch = w & 3, hf = w >> 2;
    {
        float k0[4] = {0, 0, 0, 0}, k1[4] = {0, 0, 0, 0}, k2[4] = {0, 0, 0, 0}, k3[4] = {0, 0, 0, 0}, k4[4] = {0, 0, 0, 0}, kl = 0;
#pragma unroll KGU
        for (int j = 0; j < 16; j++) {
            const uint4 q = lds128(sb + P_PRM + (w * 64 + j * 4 + c) * 16);
            const float cr = __uint_as_float(q.z), ci = __uint_as_float(q.w);
            float wr[4], wi[4], vr[4], vi[4];
            cpow(__uint_as_float(q.x), __uint_as_float(q.y), (float)g, wr[0], wi[0]);
            cpow(__uint_as_float(q.x), __uint_as_float(q.y), (float)(g + 8), vr[0], vi[0]);
#pragma unroll
            for (int i = 1; i < 4; i++) { wr[i] = wr[i - 1]; wi[i] = wi[i - 1]; csq(wr[i], wi[i]); vr[i] = vr[i - 1]; vi[i] = vi[i - 1]; csq(vr[i], vi[i]); }
            float hr = wr[3], hi = wi[3];
            csq(hr, hi);
            mma_tf32(k0, wr[0], vr[0], wi[0], vi[0], cr * hr - ci * hi, -(cr * hi + ci * hr));
            hr = vr[3]; hi = vi[3]; csq(hr, hi);
            mma_tf32(k1, wr[0], vr[0], wi[0], vi[0], cr * hr - ci * hi, -(cr * hi + ci * hr));
            csq(hr, hi);
            mma_tf32(k2, wr[1], vr[1], wi[1], vi[1], cr * hr - ci * hi, -(cr * hi + ci * hr));
            csq(hr, hi);
            mma_tf32(k3, wr[2], vr[2], wi[2], vi[2], cr * hr - ci * hi, -(cr * hi + ci * hr));
            csq(hr, hi);
            mma_tf32(k4, wr[3], vr[3], wi[3], vi[3], cr * hr - ci * hi, -(cr * hi + ci * hr));
            csq(hr, hi);
            kl += cr * hr - ci * hi;
        }
        kl += __shfl_xor_sync(0xffffffffu, kl, 1); kl += __shfl_xor_sync(0xffffffffu, kl, 2);
        const uint32_t o = sb + P_K6 + (ch * 656 + c * 32 + g) * 4, ol = sb + P_K6 + (ch * 656 + 640) * 4;
#define KST(k, base) sts32(o + (base) * 4, __float_as_uint(k[0])); sts32(o + (base) * 4 + 64, __float_as_uint(k[1])); \
                     sts32(o + (base) * 4 + 32, __float_as_uint(k[2])); sts32(o + (base) * 4 + 96, __float_as_uint(k[3]))
#define KAD(k, base) k[0] += __uint_as_float(lds32(o + (base) * 4)); k[1] += __uint_as_float(lds32(o + (base) * 4 + 64)); \
                     k[2] += __uint_as_float(lds32(o + (base) * 4 + 32)); k[3] += __uint_as_float(lds32(o + (base) * 4 + 96))
        if (hf == 0) {
            bar_sync(2 + ch, 64);
            KAD(k0, 0); KAD(k1, 128); KAD(k2, 256); KAD(k3, 384); KAD(k4, 512);
            kl += __uint_as_float(lds32(ol));
            __syncwarp();
        }
        KST(k0, 0); KST(k1, 128); KST(k2, 256); KST(k3, 384); KST(k4, 512);
        if (lane == 0) sts32(ol, __float_as_uint(kl));
        if (hf == 1) { __syncwarp(); bar_arrive(2 + ch, 64); }
    }
    PROF(tid == 0, 3511);
    bar_sync(8, 384);
    PROF(tid == 0, 3512);
    if (tid < 64) sts32(sb + P_P + ((tid >> 4) * 2080 + (tid & 15)) * 4, 0);
#pragma unroll 1
    for (int x = tid; x < 2048; x += 512) {
        uint32_t pw[2][4];
#pragma unroll
        for (int h = 0; h < 2; h++) {
            const int y = x + h * 256;
            const int i0 = y <= 256 ? y : 256 + (int)((pack2((float)y, 0.f) & 0xffff) - 0x4380);
            const int i1 = y <= 256 ? max(y - 1, 0) : 256 + (int)((pack2((float)(y - 1), 0.f) & 0xffff) - 0x4380);
#pragma unroll
            for (int k = 0; k < 4; k++) {
                const float lo = __uint_as_float(lds32(sb + P_K6 + k * 2624 + i0 * 4)), hi = __uint_as_float(lds32(sb + P_K6 + k * 2624 + i1 * 4));
                pw[h][k] = pack2(lo, y ? hi : 0.f);
            }
        }
#pragma unroll
        for (int h = 0; h < 2; h++)
#pragma unroll
            for (int k = 0; k < 4; k++) sts32(sb + P_P + (k * 2080 + x + h * 256 + 16) * 4, pw[h][k]);
    }
    bar_sync(9, 384);
    PROF(tid == 0, 3513);
    {
        float acc[16][4];
#pragma unroll
        for (int j = 0; j < 16; j++) acc[j][0] = acc[j][1] = acc[j][2] = acc[j][3] = 0;
#pragma unroll 1
        for (int e = hf * 4; e < hf * 4 + 4; e++) {
            uint32_t B[16][2];
            const uint32_t ua = sb + P_U + ch * 4352 + ((lane >> 3) & 1) * 2176 + (8 + (lane >> 4) * 8 + (lane & 7) - e) * 16;
#pragma unroll
            for (int j = 0; j < 8; j++) { const uint4 v = ldsm4(ua + j * 256); B[2 * j][0] = v.x; B[2 * j][1] = v.y; B[2 * j + 1][0] = v.z; B[2 * j + 1][1] = v.w; }
            const uint32_t pa = sb + P_P + (ch * 2080 + 16 + e * 16 + g - 2 * c) * 4;
#pragma unroll
            for (int d = 0; d < 16; d++) {
                const uint32_t a0 = lds32(pa + d * 512), a1 = lds32(pa + d * 512 + 32), a2 = lds32(pa + d * 512 - 32);
#pragma unroll
                for (int j = d; j < 16; j++) mma16(acc[j], a0, a1, a2, a0, B[j - d][0], B[j - d][1]);
            }
        }
        PROF(tid == 0, 3514);
        const uint32_t o = sb + P_Y + (ch * 2560 + c * 40 + g) * 4;
#pragma unroll
        for (int j = 0; j < 8; j++) {
#pragma unroll
            for (int i = 0; i < 4; i++) { const float lo = acc[j][i], hi = acc[j + 8][i]; acc[j][i] = hf ? hi : lo; sts32(o + (j + 8 - hf * 8) * 640 + (i & 1) * 80 + (i >> 1) * 32, __float_as_uint(hf ? lo : hi)); }
        }
        bar_sync(2 + ch, 64);
#pragma unroll
        for (int j = 0; j < 8; j++) {
#pragma unroll
            for (int i = 0; i < 4; i++) acc[j][i] += __uint_as_float(lds32(o + (j + hf * 8) * 640 + (i & 1) * 80 + (i >> 1) * 32));
        }
#pragma unroll
        for (int j = 0; j < 8; j++) {
#pragma unroll
            for (int i = 0; i < 4; i++) sts32(o + (j + hf * 8) * 640 + (i & 1) * 80 + (i >> 1) * 32, __float_as_uint(acc[j][i]));
        }
    }
    const uint2 dk = __ldg((const uint2*)(a.Dk + d0));
    bar_sync(1, 256);
#pragma unroll 2
    for (int i = 0; i < 8; i++) {
        const int t = i * 256 + tid;
        const uint32_t o = sb + P_Y + (t + 4 * (t >> 4)) * 4;
        const uint4 xu = lds128(sb + P_X + t * 16);
        float y[4];
#pragma unroll
        for (int k = 0; k < 4; k++) y[k] = rbf(__uint_as_float(lds32(o + k * 10240)));
        uint2 r;
        r.x = pack2(blo(xu.x) + rbf(y[0] + rbf(blo(xu.z) * blo(dk.x))), bhi(xu.x) + rbf(y[1] + rbf(bhi(xu.z) * bhi(dk.x))));
        r.y = pack2(blo(xu.y) + rbf(y[2] + rbf(blo(xu.w) * blo(dk.y))), bhi(xu.y) + rbf(y[3] + rbf(bhi(xu.w) * bhi(dk.y))));
        ((uint2*)(g_xA[0] + ((t >> 7) * 8 + (d0 >> 6)) * 1024 + ((t & 127) >> 3) * 64 + ((d0 & 63) >> 3) * 8 + (t & 7)))[(d0 >> 2) & 1] = r;
        if (i == 0) {
            const float e0 = blo(r.x), e1 = bhi(r.x), e2 = blo(r.y), e3 = bhi(r.y);
            asm volatile("red.relaxed.gpu.global.add.v2.f32 [%0],{%1,%2};" ::"l"(g_st[0] + (t >> 7) * 2048 + lds32(sb + S_TAG) * 128 + (t & 127)),
                         "f"((e0 + e1) + (e2 + e3)), "f"((e0 * e0 + e1 * e1) + (e2 * e2 + e3 * e3)) : "memory");
        }
    }
    PROF(tid == 0, 3515);
    bar_sync(10, 384);
}

__global__ void __cluster_dims__(2, 1, 1) __launch_bounds__(384, 1) main_kernel(const __grid_constant__ Params p) {
    extern __shared__ __align__(1024) uint8_t smem[];
    const uint32_t sb = __shfl_sync(0xffffffffu, smem_u32(smem), 0);
    uint32_t rank; asm("mov.u32 %0,%%cluster_ctarank;" : "=r"(rank));
    const int wi = __shfl_sync(0xffffffffu, threadIdx.x >> 5, 0);
    const int cl = blockIdx.x >> 1, wg = wi >> 2;
    const bool rec = p.rec0 >= 0 && cl >= p.rec0 && cl < p.rec0 + 32;
    PROF(threadIdx.x == 0, 3500);
    ProRegs pr;
    prologue_load(p.pa, max((int)blockIdx.x - 4, 0), pr);
    if (rec) rec_init(p, sb, cl - p.rec0, rank); else bulk_init(sb);
    if (threadIdx.x == 352 && p.dopro && cl >= 2) {
        mbar_init(sb + S_XBAR, 1);
        asm volatile("fence.mbarrier_init.release.cluster;" ::: "memory");
        mbar_expect(sb + S_XBAR, 32768);
        for (int j = 0; j < 8; j++) tma2d(sb + P_X + j * 4096, &p.tm[3], ((blockIdx.x - 4) >> 1) * 8, j * 256, sb + S_XBAR);
    }
    if (threadIdx.x == 320) {
        unsigned v;
        asm volatile("ld.relaxed.gpu.global.u32 %0,[%1];" : "=r"(v) : "l"(g_gate) : "memory");
        v = v / (4 * NCL) + p.dopro;
        sts64(sb + S_GATE, v * (4 * NCL), v & 1);
    }
    __syncwarp();
    asm volatile("barrier.cluster.arrive.relaxed.aligned;" ::: "memory");
    if (wg == 2) bar_arrive(8, 384);
    if (p.dopro && cl >= 2) prologue(p.pa, sb, blockIdx.x - 4, wi, pr); else if (wg < 2) bar_sync(8, 384);
    asm volatile("barrier.cluster.wait.aligned;" ::: "memory");
    fence_async_smem();
    bar_sync(wg == 2 ? 7 : 1, wg == 2 ? 128 : 256);
    if (p.dopro && (threadIdx.x == 32 || threadIdx.x == 352)) red_release(g_gate, 1);
    if (rec) {
        if (threadIdx.x == 0) {
            rec_fetch(&p.tm[1], sb + R_STK, (cl - p.rec0) * 128, rank * 256, 2, sb + R_BAR + RB_INIT * 8);
            rec_fetch(&p.tm[2], sb + R_STV, (cl - p.rec0) * 128, rank * 256, 2, sb + R_BAR + RB_INIT * 8);
        }
    }
    PROF(threadIdx.x == 0, 3506);
    __syncwarp();
    if (rec) {
        const int head = cl - p.rec0;
        if (wg == 2) {
            reg_dec<RH>();
            const int w = wi & 3;
            if (threadIdx.x == 256) rec_fetch(&p.tm[0], sb + R_STQ, head * 128, rank * 256, 2, sb + R_BAR + RB_INIT * 8);
            __syncwarp();
            wait_cnt_warp(g_gate, lds32(sb + S_GATE));
            if (p.dostats) x1_stats((head * 2 + rank) * 4 + w, lds32(sb + S_TAG));
            __syncthreads();
            cluster_sync();
            if ((p.chains >> (w >> 1)) & 1) rec_attn(p, sb, w >> 1, w & 1, head, rank);
        } else {
            reg_inc<RW0>();
            rec_weights(p, sb, head, rank, wi);
        }
    } else {
        if (wg == 2) {
            reg_dec<40>();
            const int w = wi & 3;
            if (w == 0) bulk_producer(p, sb, cl, rank); else if (w >= 2) bulk_release(p, sb, cl, rank, w - 2);
        } else { reg_inc<232>(); bulk_consumer(p, sb, cl, rank, wi); }
    }
    __syncwarp();
    cluster_sync();
}

typedef CUresult (*EncFn)(CUtensorMap*, CUtensorMapDataType, cuuint32_t, void*, const cuuint64_t*, const cuuint64_t*, const cuuint32_t*, const cuuint32_t*,
                          CUtensorMapInterleave, CUtensorMapSwizzle, CUtensorMapL2promotion, CUtensorMapFloatOOBfill);
inline uint32_t mk(int type, int layer, int ch, int a, int b, int c) { return type | (layer << 3) | (ch << 4) | (a << 8) | (b << 16) | ((uint32_t)c << 24); }
constexpr int SMEM_BYTES = 232448;

struct Sched {
    Params* P; int n[NCL];
    void clear() { memset(P->task, 0, sizeof(P->task)); memset(n, 0, sizeof(n)); }
    void add(int cl, uint32_t t) { if (n[cl] < MAXT - 1) P->task[cl][n[cl]++] = t; }
};

constexpr int REC0 = 4;
struct Cfg { int LAG, TS1, TS2, DQU, DQO, DUN, DHN, MARG, NQ1, FAST0, n0, oc, fc, nuns, ns2, nhg, hs, osl; };
#define PLAN 14, 2300, 2950, 2420, 1600, 5800, 380, 3000, 4, 1, 8, 10, 12, 3, 4, 8, 6000, 1000
Cfg g_cfg = {PLAN};
double g_est;
bool g_planned = false;
struct Plan { uint32_t w[NCL][MAXT]; int n[NCL]; double end, rec; };
void simulate(Plan& L, int nc, const Cfg& C) {
    const int LAG = C.LAG, NQ1 = C.NQ1, FAST0 = C.FAST0, n0 = C.n0, oc = C.oc, fc = C.fc, nuns = C.nuns, ns2 = C.ns2, nhg = C.nhg;
    const double TS1 = C.TS1, TS2 = C.TS2, DQU = C.DQU, DQO = C.DQO, DUN = C.DUN, DHN = C.DHN, MARG = C.MARG, hs = C.hs;
    const double INF = 1e18, DKB = 600, DOV = 700, DH = DHN, DHO = 1100, DF = 2200, DFB = 200, POLL = 450, FILL = 500, PUB = 600;
    enum { Q0, O0, Q1, HB, O1, FI, NK };
    struct Grp { int n, left; double done; } G[NK][16];
    double fr[NCL], it[100] = {}, cv[16];
    int ns[16], last[2][NCL], uc = 0, nit = 0;
    memset(L.n, 0, sizeof(L.n)); L.end = 0;
    auto fast = [&](int c) { return c < FAST0 || c >= fc; };
    for (int c = 0; c < 16; c++) {
        ns[c] = c < nuns ? 1 : c == 15 ? 16 : c == 14 ? 8 : ns2;
        const int cnt[NK] = {c < 2 ? 48 : (c & 1) ? 0 : 96, c < oc ? 8 : OPS1, c == 15 ? 24 : fast(c) ? 16 : 48 / NQ1, c >= 2 && !(c & 1) ? 16 : 0, ns[c], ns[c] == 1 ? 0 : c >= 14 ? 8 : 4};
        for (int k = 0; k < NK; k++) G[k][c] = {cnt[k], cnt[k], 0};
        cv[c] = INF;
    }
    for (int i = 0; i < nc; i++) { fr[i] = 0; last[0][i] = last[1][i] = -1; }
    auto fin = [&](int k, int c) { if ((k == Q0 && c >= 2) || k == HB) c &= ~1; return G[k][c].left ? INF : G[k][c].done; };
    auto len = [&](int i) { return (i >= LAG && i < 64) ? (double)TS2 : (double)TS1; };
    auto end_it = [&](int i) { return i < nit ? it[i] + len(i) : INF; };
    auto nominal = [&](int i) { if (i < nit) return it[i]; double t = nit ? it[nit - 1] : 11000 - TS1; for (int j = nit - 1; j < i; j++) t += len(j); return t; };
    auto put = [&](int i, uint32_t w) { if (L.n[i] < MAXT - 4) L.w[i][L.n[i]++] = w; else L.end = INF; };
    auto rel = [&](int k, int c) {
        switch (k) {
            case Q0: return 0.0;
            case O0: return end_it(4 * c + 3) + PUB + POLL;
            case Q1: return cv[c] + POLL;
            case HB: return cv[c - 2] + 600 + POLL;
            case O1: return end_it(LAG + 4 * c + 3) + PUB + POLL;
            default: return fin(O1, c) + POLL;
        }
    };
    auto dur = [&](int k, int c) {
        switch (k) {
            case Q0: return DQO + (c < 2 ? 2.0 : 1.0) * DQU;
            case O0: return (16 - G[O0][c].n) * DKB + 1200;
            case HB: return DHO + DH * c;
            case Q1: return DQO + 48.0 / G[Q1][c].n * DQU;
            case O1: return DOV + DKB * 64 / ns[c] + (ns[c] == 1 ? 1500 : 0);
            default: return DF + DFB * ns[c] * (c >= 14 ? 0.5 : 1);
        }
    };
    auto o0_est = [&](int c) {
        double t = uc ? cv[uc - 1] - 900 : 0;
        for (int j = uc; j < c; j++) t = fmax(t, nominal(4 * j + 4) + PUB + POLL + FILL) + dur(O0, j) + DUN;
        return fmax(t, nominal(4 * c + 4) + PUB + POLL);
    };
    auto cv_est = [&](int c) { return c < uc ? cv[c] : o0_est(c) + FILL + dur(O0, c) + DUN + 900; };
    auto slot = [&](int k, int c, int i) { return k == O0 ? (i < 8 ? i : nc + 7 - i) : c == 15 ? i : i - 8; };
    while (true) {
        while (nit < 64 + LAG) {
            double t = nit ? end_it(nit - 1) : 0;
            if (nit < 64) t = fmax(t, fin(Q0, nit >> 2) + POLL);
            if (nit >= LAG) t = fmax(t, fin(Q1, (nit - LAG) >> 2) + (nit < 64 ? 0 : POLL));
            if (t >= INF) break;
            it[nit++] = t;
        }
        int i = -1;
        for (int j = 0; j < nc; j++) if (fr[j] < INF && (i < 0 || fr[j] < fr[i])) i = j;
        if (i < 0) break;
        const double t = fr[i];
        double lim = INF;
        if (i < 8 && last[0][i] == uc) {
            if (G[O0][uc].left || fin(HB, uc) >= INF) { fr[i] = t + 200; continue; }
            const double e = fmax(G[O0][uc].done, fin(HB, uc) - 2000) + DUN;
            for (int j = 0; j < 8; j++) { put(j, mk(T_CV, 0, uc, 2 * j, G[O0][uc].n, 0)); fr[j] = e; }
            cv[uc++] = e + 900;
            continue;
        }
        const bool hg = (unsigned)(i - 24) < (unsigned)nhg;
        double hlim = INF;
        for (int c = 2; c < 16 && hg; c++) if (G[HB][c].left) { hlim = cv_est(c - 2) + hs; break; }
        int mine[2] = {-1, -1};
        for (int k = 0; k < 2; k++)
            for (int c = last[k][i] + 1; c < 16 && mine[k] < 0; c++) if ((unsigned)slot(O0 + k, c, i) < (unsigned)G[O0 + k][c].n) mine[k] = c;
        if (mine[0] >= 0) lim = i < 8 ? o0_est(mine[0]) - (uc ? 0 : 8500) : nominal(4 * mine[0] + 4) + PUB + C.osl;
        else if (mine[1] >= 0) lim = cv_est(mine[1]) + POLL;
        else if (i < 16 && G[O1][15].left) lim = fmin(lim, nominal(64 + LAG) + PUB);
        int bk = -1, bc = 0; double bd = INF;
        for (int k = 0; k < NK; k++)
            for (int c = 0; c < 16; c++) {
                const bool urgent = k == O0 || k == Q1 || (k == O1 && c == 15);
                if (!G[k][c].left || ((k == O0 || k == Q1) && c != mine[k - O0]) || (k == O1 && c == 15 && i >= 16)) continue;
                if (rel(k, c) > t || (t + dur(k, c) + (k == Q0 && c >= 2 ? DQU : 0) > lim && !urgent)) continue;
                if (i < 8 && uc && uc < 16 && k != O0) continue;
                if ((k == HB && !hg) || (k != HB && !urgent && t + dur(k, c) + (k == Q0 && c >= 2 ? DQU : 0) > hlim)) continue;
                const double dl = urgent ? -INF : k == HB ? -INF / 2 : k == Q0 ? nominal(4 * c) - 3000 : 1e9 + c * 2 + (k == O1);
                if (dl < bd) { bd = dl; bk = k; bc = c; }
            }
        if (bk < 0) {
            bool any = i < 8 && uc < 16;
            for (int k = 0; k < NK; k++) for (int c = 0; c < 16; c++) any = any || G[k][c].left;
            fr[i] = any ? t + 200 : INF;
            if (t > 400000) { L.end = INF; return; }
            continue;
        }
        Grp& g = G[bk][bc];
        const int n = g.n - g.left, c = bc;
        int nu = 1;
        double d = dur(bk, c);
        if (bk == Q0) for (nu = c < 2 ? 2 : 1; c >= 2 && nu < g.left && (nu < 2 || (nu < n0 && t + d + DQU < fmin(fmin(lim, hlim), bd - MARG))); nu++) d += DQU;
        if (bk == O0 && i >= 8) d += (g.n - 8) * DKB;
        if (bk == Q0 && !c && n >= 32) { nu = 1; d -= DQU; }
        if (bk == O0 || bk == Q1) last[bk - O0][i] = c;
        if (bk == O0 && !c && i < 8) put(i, mk(T_CV, 0, 3, 2 * i, 0, 128));
        g.left -= nu;
        const double e = fmax(t, rel(bk, c) + FILL) + (t < 1 ? 4500 : 0) + d;
        fr[i] = e;
        g.done = fmax(g.done, e + (bk == O1 ? 1900 : bk == O0 ? 0 : (bk == Q1 && g.n < 24) || (bk == Q0 && !c && nu == 2) ? -500 : 1000));
        if (bk == FI || (bk == O1 && ns[c] == 1)) L.end = fmax(L.end, e);
        put(i, bk == Q0 ? (c == 0 ? mk(T_QKV, 0, 0, n < 32 ? n : 2 * n - 32, nu, 32) : c == 1 ? mk(T_QKV, 0, c, n, 2, 24) : mk(T_QKV, 0, c, n, nu, 64))
             : bk == O0 ? (i < 8 ? mk(T_OP, 0, c, i * (16 - g.n), 16 - g.n, i) : mk(T_OP, 0, c, 64 - (nc - i) * 8, 8, slot(O0, c, i)))
             : bk == HB ? mk(T_CV, 1, c, 2 * n, 0, 0)
             : bk == Q1 ? mk(T_QKV, 1, c, slot(Q1, c, i) * 2, 48 / g.n, g.n)
             : bk == O1 ? mk(T_OP, 1, c, n * 64 / ns[c], 64 / ns[c], ns[c] == 1 ? 32 : n)
                        : mk(T_FIN, 1, c, n * (32 / g.n), ns[c], 16 / g.n));
    }
    L.rec = end_it(63 + LAG);
}
void plan(Params& P) {
    P.rec0 = REC0; P.chains = 3; P.lag = g_cfg.LAG; P.dostats = 1; P.dopro = 1;
    static Plan L;
    int cls[NCL], nc = 0;
    for (int c = REC0 + 32; c < NCL; c++) cls[nc++] = c;
    for (int c = REC0 - 1; c >= 0; c--) cls[nc++] = c;
    simulate(L, nc, g_cfg);
    g_est = L.end;
    Sched S; S.P = &P; S.clear();
    S.add(0, mk(T_QKV, 1, 15, 0, 2, 128 + 24)); S.add(0, mk(T_OP, 1, 15, 0, 4, 128));
    S.add(1, mk(T_CV, 0, 3, 0, 0, 128));
    for (int i = 0; i < nc; i++) {
        bool warm = false;
        for (int k = 0; k < L.n[i]; k++) {
            if (!warm && k + 1 < L.n[i] && (L.w[i][k + 1] & 255) == (mk(T_FIN, 1, 15, 0, 0, 0) & 255)) { S.add(cls[i], L.w[i][k + 1] | 0x80000000u); warm = true; }
            S.add(cls[i], L.w[i][k]);
            if ((L.w[i][k] & 7) == T_FIN) warm = true;
        }
    }
}

#define TK0() do {} while (0)
#define TK() do { P.e0 = (P.chains & 1) ? 64 : 0; P.b1 = (P.chains & 2) ? P.lag : 1000; P.nit = (P.chains & 2) ? P.lag + 64 : 64; TK0(); } while (0)
}

extern "C" void kernel_launch(void* const* d_in, const int* in_sizes, int n_in, void* d_out, int out_size) {
    typedef const __nv_bfloat16* BP;
    static EncFn enc = nullptr;
    if (!enc) {
        void* fn = nullptr; cudaDriverEntryPointQueryResult qr;
        cudaGetDriverEntryPoint("cuTensorMapEncodeTiled", &fn, cudaEnableDefault, &qr);
        enc = (EncFn)fn;
        cudaFuncSetAttribute(main_kernel, cudaFuncAttributeMaxDynamicSharedMemorySize, SMEM_BYTES);
    }
    static Params P;
    for (int i = 0; i < 4; i++) {
        const cuuint64_t cols = i < 3 ? 4096 : 512, rows = i < 3 ? 512 : 4096;
        cuuint64_t d2[2] = {cols, rows}, d3[3] = {64, rows, cols / 64}, str[2] = {cols * 2, 128};
        cuuint32_t box[3] = {64, 64, 4}, es[3] = {1, 1, 1};
        enc(&P.tm[i < 3 ? i : 4], CU_TENSOR_MAP_DATA_TYPE_BFLOAT16, 2, d_in[9 + i], d2, str, box, es, CU_TENSOR_MAP_INTERLEAVE_NONE, CU_TENSOR_MAP_SWIZZLE_128B,
                       CU_TENSOR_MAP_L2_PROMOTION_L2_128B, CU_TENSOR_MAP_FLOAT_OOB_FILL_NONE);
        for (int m = 0; m < 2; m++) {
            cuuint32_t box3[3] = {64, 32, m ? 2u : 4u};
            enc(&P.t3[m][i], CU_TENSOR_MAP_DATA_TYPE_BFLOAT16, 3, d_in[9 + i], d3, str, box3, es, CU_TENSOR_MAP_INTERLEAVE_NONE, CU_TENSOR_MAP_SWIZZLE_128B,
                CU_TENSOR_MAP_L2_PROMOTION_L2_128B, CU_TENSOR_MAP_FLOAT_OOB_FILL_NONE);
        }
    }
    {
        cuuint64_t dims[2] = {512, 2048}, str[1] = {1024};
        cuuint32_t box[2] = {8, 256}, es[2] = {1, 1};
        enc(&P.tm[3], CU_TENSOR_MAP_DATA_TYPE_BFLOAT16, 2, d_in[0], dims, str, box, es, CU_TENSOR_MAP_INTERLEAVE_NONE, CU_TENSOR_MAP_SWIZZLE_NONE,
            CU_TENSOR_MAP_L2_PROMOTION_NONE, CU_TENSOR_MAP_FLOAT_OOB_FILL_NONE);
    }
    for (int m = 0; m < 2; m++) {
        void* ga; cudaGetSymbolAddress(&ga, g_A);
        cuuint64_t dims[2] = {512, sizeof(AOps) / 1024}, str[1] = {1024};
        cuuint32_t box[2] = {256, m ? 16u : 8u}, es[2] = {1, 1};
        enc(&P.ta[m], CU_TENSOR_MAP_DATA_TYPE_BFLOAT16, 2, ga, dims, str, box, es, CU_TENSOR_MAP_INTERLEAVE_NONE, CU_TENSOR_MAP_SWIZZLE_NONE,
            CU_TENSOR_MAP_L2_PROMOTION_L2_128B, CU_TENSOR_MAP_FLOAT_OOB_FILL_NONE);
    }
    P.mem0 = (BP)d_in[8]; P.Wo = (BP)d_in[12]; P.Dskip = (BP)d_in[6]; P.out = (__nv_bfloat16*)d_out;
    cudaStream_t s = cudaStreamPerThread;
    P.pa = {(BP)d_in[0], (BP)d_in[1], (BP)d_in[2], (BP)d_in[3], (BP)d_in[4], (BP)d_in[5], (BP)d_in[6], (BP)d_in[9], (BP)d_in[10], (BP)d_in[11], (BP)d_in[12], (BP)d_in[8]};
    if (!g_planned) { plan(P); g_planned = true; }
    TK(); main_kernel<<<2 * NCL, 384, SMEM_BYTES, s>>>(P); TK();
}
```

```cpp
#include <cuda_runtime.h>
#include <cuda_bf16.h>
#include <cuda.h>
#include <stdint.h>
#include <string.h>
#include <math.h>

namespace {

constexpr int NCL = 66;
constexpr int MAXT = 64;
#define PFC 1
#define OPS1N 10
constexpr int OPS1 = OPS1N;
constexpr int MAXSPLIT = 16;
constexpr int PW = 144;

struct AOps { uint4 x[2][16 * 8 * 1024], o[2][16 * 64 * 1024]; };
__device__ AOps g_A;
#define g_xA g_A.x
#define g_o g_A.o
__device__ float2 g_st[2][16 * 2048];
__device__ float2 g_st2[2 * 16 * 128];
__device__ uint4 g_qkv[2][64 * 64 * 768];
__device__ uint4 g_pp[2][16 * MAXSPLIT * 8192];
__device__ uint4 g_acc[7 * 2048];
__device__ unsigned g_gate[32];
__device__ uint32_t g_P[16 * 16 * 32 * PW];
__device__ uint4 g_u[16 * 16 * 512];
__device__ float4 g_carry[2][17 * 16 * 4 * 256];
__device__ unsigned g_cnt[13 * 64];
__device__ uint32_t g_ln0[2048];

enum { C_QKV0 = 0, C_QKV1 = 1  , C_O0 = 2, C_O1 = 3, C_U = 4, C_OP1 = 5, C_CV = 6, C_ST = 7, C_H = 8, C_OP0 = 9   };
__device__ __forceinline__ unsigned* cnt_ptr(int kind, int chunk) { return g_cnt + kind * 64 + chunk; }

enum { T_END = 0, T_QKV = 1, T_OP = 2, T_CV = 3, T_FIN = 4 };
struct ProArgs { const __nv_bfloat16 *x, *lAr, *Ai, *Cr, *Ci, *ldt, *Dk, *Wq, *Wk, *Wv, *Wo, *mem0; };
struct Params {
    CUtensorMap tm[5];
    CUtensorMap t3[2][4];
    CUtensorMap ta[2];
    ProArgs pa;
    int dopro;
    const __nv_bfloat16* mem0;
    const __nv_bfloat16* Wo;
    const __nv_bfloat16* Dskip;
    __nv_bfloat16* out;
    int rec0;
    int chains;
    int lag;
    int b1, e0, nit;
    int zero, gpit;
    int dostats;
    uint32_t task[NCL][MAXT];
};

__device__ __forceinline__ uint32_t smem_u32(const void* p) { return (uint32_t)__cvta_generic_to_shared(p); }
__device__ __forceinline__ uint32_t mapa(uint32_t a, uint32_t r) {
    uint32_t o; asm("mapa.shared::cluster.u32 %0,%1,%2;" : "=r"(o) : "r"(a), "r"(r)); return o;
}
__device__ __forceinline__ void mbar_init(uint32_t b, int c) { asm volatile("mbarrier.init.shared::cta.b64 [%0],%1;" ::"r"(b), "r"(c) : "memory"); }
__device__ __forceinline__ void mbar_expect(uint32_t b, int bytes) { asm volatile("mbarrier.arrive.expect_tx.shared::cta.b64 _,[%0],%1;" ::"r"(b), "r"(bytes) : "memory"); }
__device__ __forceinline__ void mbar_arrive(uint32_t b) { asm volatile("mbarrier.arrive.shared::cta.b64 _,[%0];" ::"r"(b) : "memory"); }
__device__ __forceinline__ void mbar_arrive_cluster(uint32_t b) { asm volatile("mbarrier.arrive.shared::cluster.b64 _,[%0];" ::"r"(b) : "memory"); }
__device__ __forceinline__ void mbar_arrive1(uint32_t b) { asm volatile("{.reg .pred p; elect.sync _|p,0xffffffff; @p mbarrier.arrive.shared::cta.b64 _,[%0];}" ::"r"(b) : "memory"); }
__device__ __forceinline__ void mbar_arrive1_cluster(uint32_t b) { asm volatile("{.reg .pred p; elect.sync _|p,0xffffffff; @p mbarrier.arrive.shared::cluster.b64 _,[%0];}" ::"r"(b) : "memory"); }
__device__ __forceinline__ void mbar_wait(uint32_t b, uint32_t ph) {
    asm volatile(
        "{.reg .pred p; .reg .u32 n; mov.u32 n,0;\n"
        "W%=: mbarrier.try_wait.parity.shared::cta.b64 p,[%0],%1;\n"
        "@p bra D%=;\n"
        "add.u32 n,n,1; setp.lt.u32 p,n,2000000; @p bra W%=;\n"
        "trap;\n"
        "D%=: }" ::"r"(b), "r"(ph) : "memory");
}
__device__ __forceinline__ bool mbar_test(uint32_t b, uint32_t ph) {
    uint32_t ok;
    asm volatile("{.reg .pred p; mbarrier.test_wait.parity.shared::cta.b64 p,[%1],%2; selp.u32 %0,1,0,p;}" : "=r"(ok) : "r"(b), "r"(ph) : "memory");
    return ok;
}
__device__ __forceinline__ bool wait_lds128(uint32_t b, uint32_t ph, uint32_t a, uint4& v) {
    uint32_t ok;
    asm volatile("{.reg .pred p; mbarrier.try_wait.parity.shared::cta.b64 p,[%5],%6,20000; ld.shared.v4.u32 {%0,%1,%2,%3},[%7]; selp.u32 %4,1,0,p;}"
                 : "=r"(v.x), "=r"(v.y), "=r"(v.z), "=r"(v.w), "=r"(ok) : "r"(b), "r"(ph), "r"(a) : "memory");
    return ok;
}
__device__ __forceinline__ bool wait_lds64(uint32_t b, uint32_t ph, uint32_t a, uint2& v) {
    uint32_t ok;
    asm volatile("{.reg .pred p; mbarrier.try_wait.parity.shared::cta.b64 p,[%3],%4,20000; ld.shared.v2.u32 {%0,%1},[%5]; selp.u32 %2,1,0,p;}"
                 : "=r"(v.x), "=r"(v.y), "=r"(ok) : "r"(b), "r"(ph), "r"(a) : "memory");
    return ok;
}
template <int PH> __device__ __forceinline__ void mbar_wait_c(uint32_t b) {
    asm volatile(
        "{.reg .pred p; .reg .u32 n; mov.u32 n,%2;\n"
        "W%=: mbarrier.try_wait.parity.shared::cta.b64 p,[%0],%1;\n"
        "@p bra D%=;\n"
        "add.u32 n,n,1; setp.lt.u32 p,n,2000000; @p bra W%=;\n"
        "trap;\n"
        "D%=: }" ::"r"(b), "n"(PH), "n"(PH) : "memory");
}
__device__ __forceinline__ void bar_sync(int id, int n) { asm volatile("bar.sync %0,%1;" ::"r"(id), "r"(n) : "memory"); }
__device__ __forceinline__ void bar_arrive(int id, int n) { asm volatile("bar.arrive %0,%1;" ::"r"(id), "r"(n) : "memory"); }
__device__ __forceinline__ void cluster_sync() { asm volatile("barrier.cluster.arrive.relaxed.aligned; barrier.cluster.wait.aligned;" ::: "memory"); }
__device__ __forceinline__ void fence_async() { asm volatile("fence.proxy.async;" ::: "memory"); }
__device__ __forceinline__ void fence_async_smem() { asm volatile("fence.proxy.async.shared::cta;" ::: "memory"); }
#define EFR 1
#define EFW 2
constexpr uint64_t POL_N = 0x1000000000000000ull, POL_F = 0x12F0000000000000ull;
constexpr uint64_t POL_LAST = EFR ? POL_F : POL_N  , POL_LATE = EFW ? POL_F : POL_N  , POL_SOON = EFW > 1 ? POL_F : POL_N;
__device__ __forceinline__ void bulk_g2s(uint32_t dst, const void* src, int bytes, uint32_t bar, uint64_t pol) {
    asm volatile("cp.async.bulk.shared::cluster.global.mbarrier::complete_tx::bytes.L2::cache_hint [%0],[%1],%2,[%3],%4;" ::"r"(dst), "l"(src), "r"(bytes), "r"(bar), "l"(pol) : "memory");
}
__device__ __forceinline__ void bulk_g2s_mc(uint32_t dst, const void* src, int bytes, uint32_t bar, uint64_t pol) {
    asm volatile("cp.async.bulk.shared::cluster.global.mbarrier::complete_tx::bytes.multicast::cluster.L2::cache_hint [%0],[%1],%2,[%3],%4,%5;" ::"r"(dst), "l"(src), "r"(bytes), "r"(bar), "h"((uint16_t)3), "l"(pol) : "memory");
}
__device__ __forceinline__ void bulk_s2s(uint32_t dst, uint32_t src, int bytes, uint32_t bar) {
    asm volatile("cp.async.bulk.shared::cluster.shared::cta.mbarrier::complete_tx::bytes [%0],[%1],%2,[%3];" ::"r"(dst), "r"(src), "r"(bytes), "r"(bar) : "memory");
}
__device__ __forceinline__ bool elect() {
    uint32_t r; asm volatile("{.reg .pred p; elect.sync _|p,0xffffffff; selp.u32 %0,1,0,p;}" : "=r"(r)); return r;
}
__device__ __forceinline__ void stg128(uint4* p, uint4 v, uint64_t pol) {
    asm volatile("st.global.L2::cache_hint.v4.u32 [%0],{%1,%2,%3,%4},%5;" ::"l"(p), "r"(v.x), "r"(v.y), "r"(v.z), "r"(v.w), "l"(pol));
}
__device__ __forceinline__ void stg32(uint32_t* p, uint32_t v, uint64_t pol) { asm volatile("st.global.L2::cache_hint.u32 [%0],%1,%2;" ::"l"(p), "r"(v), "l"(pol)); }
__device__ __forceinline__ uint4 ldcg128_last(const uint4* p) {
    uint4 v; asm volatile("ld.global.cg.L2::cache_hint.v4.u32 {%0,%1,%2,%3},[%4],%5;" : "=r"(v.x), "=r"(v.y), "=r"(v.z), "=r"(v.w) : "l"(p), "l"(POL_LAST) : "memory"); return v;
}
__device__ __forceinline__ void tma2d(uint32_t dst, const CUtensorMap* tm, int x, int y, uint32_t bar) {
    asm volatile("cp.async.bulk.tensor.2d.shared::cluster.global.mbarrier::complete_tx::bytes [%0],[%1,{%2,%3}],[%4];" ::"r"(dst), "l"(tm), "r"(x), "r"(y), "r"(bar) : "memory");
}
__device__ __forceinline__ void tma3d_mc(uint32_t dst, const CUtensorMap* tm, int y, int z, uint32_t bar, uint16_t mask) {
    asm volatile("{.reg .pred p; elect.sync _|p,0xffffffff;\n"
                 "@p cp.async.bulk.tensor.3d.shared::cluster.global.mbarrier::complete_tx::bytes.multicast::cluster [%0],[%1,{0,%2,%3}],[%4],%5;}"
                 ::"r"(dst), "l"(tm), "r"(y), "r"(z), "r"(bar), "h"(mask) : "memory");
}
__device__ __forceinline__ void tma2d_mc(uint32_t dst, const CUtensorMap* tm, int x, int y, uint32_t bar, uint16_t mask, uint64_t pol) {
    asm volatile("{.reg .pred p; elect.sync _|p,0xffffffff;\n"
                 "@p cp.async.bulk.tensor.2d.shared::cluster.global.mbarrier::complete_tx::bytes.multicast::cluster.L2::cache_hint [%0],[%1,{%2,%3}],[%4],%5,%6;}"
                 ::"r"(dst), "l"(tm), "r"(x), "r"(y), "r"(bar), "h"(mask), "l"(pol) : "memory");
}
__device__ __forceinline__ void bulk_g2s1(uint32_t dst, const void* src, int bytes, uint32_t bar, uint64_t pol) {
    asm volatile("{.reg .pred p; elect.sync _|p,0xffffffff;\n"
                 "@p cp.async.bulk.shared::cluster.global.mbarrier::complete_tx::bytes.L2::cache_hint [%0],[%1],%2,[%3],%4;}" ::"r"(dst), "l"(src), "r"(bytes), "r"(bar), "l"(pol) : "memory");
}
__device__ __forceinline__ void mbar_expect1(uint32_t b, int bytes) {
    asm volatile("{.reg .pred p; elect.sync _|p,0xffffffff; @p mbarrier.arrive.expect_tx.shared::cta.b64 _,[%0],%1;}" ::"r"(b), "r"(bytes) : "memory");
}
__device__ __forceinline__ void st_async4(uint32_t a, uint32_t x, uint32_t y, uint32_t z, uint32_t w, uint32_t mb) {
    asm volatile("st.async.shared::cluster.mbarrier::complete_tx::bytes.v4.b32 [%0],{%1,%2,%3,%4},[%5];" ::"r"(a), "r"(x), "r"(y), "r"(z), "r"(w), "r"(mb) : "memory");
}
__device__ __forceinline__ void st_async2(uint32_t a, uint32_t x, uint32_t y, uint32_t mb) {
    asm volatile("st.async.shared::cluster.mbarrier::complete_tx::bytes.v2.b32 [%0],{%1,%2},[%3];" ::"r"(a), "r"(x), "r"(y), "r"(mb) : "memory");
}
#define LDSQ "ld.shared"
__device__ __forceinline__ uint4 lds128(uint32_t a) { uint4 v; asm volatile(LDSQ ".v4.u32 {%0,%1,%2,%3},[%4];" : "=r"(v.x), "=r"(v.y), "=r"(v.z), "=r"(v.w) : "r"(a) : "memory"); return v; }
__device__ __forceinline__ uint2 lds64(uint32_t a) { uint2 v; asm volatile(LDSQ ".v2.u32 {%0,%1},[%2];" : "=r"(v.x), "=r"(v.y) : "r"(a) : "memory"); return v; }
__device__ __forceinline__ uint32_t lds32(uint32_t a) { uint32_t v; asm volatile(LDSQ ".u32 %0,[%1];" : "=r"(v) : "r"(a) : "memory"); return v; }
__device__ __forceinline__ void sts128(uint32_t a, uint32_t x, uint32_t y, uint32_t z, uint32_t w) { asm volatile("st.shared.v4.u32 [%0],{%1,%2,%3,%4};" ::"r"(a), "r"(x), "r"(y), "r"(z), "r"(w) : "memory"); }
__device__ __forceinline__ void sts64(uint32_t a, uint32_t x, uint32_t y) { asm volatile("st.shared.v2.u32 [%0],{%1,%2};" ::"r"(a), "r"(x), "r"(y) : "memory"); }
__device__ __forceinline__ void sts32(uint32_t a, uint32_t x) { asm volatile("st.shared.u32 [%0],%1;" ::"r"(a), "r"(x) : "memory"); }
__device__ __forceinline__ uint4 ldsm4(uint32_t a) { uint4 v; asm volatile("ldmatrix.sync.aligned.m8n8.x4.shared.b16 {%0,%1,%2,%3},[%4];" : "=r"(v.x), "=r"(v.y), "=r"(v.z), "=r"(v.w) : "r"(a) : "memory"); return v; }
__device__ __forceinline__ uint4 ldsm4t(uint32_t a) { uint4 v; asm volatile("ldmatrix.sync.aligned.m8n8.x4.trans.shared.b16 {%0,%1,%2,%3},[%4];" : "=r"(v.x), "=r"(v.y), "=r"(v.z), "=r"(v.w) : "r"(a) : "memory"); return v; }
__device__ __forceinline__ uint32_t movm(uint32_t a) { uint32_t d; asm volatile("movmatrix.sync.aligned.m8n8.trans.b16 %0,%1;" : "=r"(d) : "r"(a)); return d; }
__device__ __forceinline__ uint32_t pack2(float lo, float hi) { uint32_t d; asm("cvt.rn.bf16x2.f32 %0,%1,%2;" : "=r"(d) : "f"(hi), "f"(lo)); return d; }
__device__ __forceinline__ uint32_t hadd2(uint32_t a, uint32_t b) { uint32_t d; asm("add.rn.bf16x2 %0,%1,%2;" : "=r"(d) : "r"(a), "r"(b)); return d; }
__device__ __forceinline__ float blo(uint32_t v) { return __uint_as_float(v << 16); }
__device__ __forceinline__ float bhi(uint32_t v) { return __uint_as_float(v & 0xffff0000u); }
__device__ __forceinline__ float rbf(float x) { return __uint_as_float(pack2(0.f, x)); }
__device__ __forceinline__ float ex2(float x) { float y; asm("ex2.approx.ftz.f32 %0,%1;" : "=f"(y) : "f"(x)); return y; }
__device__ __forceinline__ float rcp(float x) { float y; asm("rcp.approx.ftz.f32 %0,%1;" : "=f"(y) : "f"(x)); return y; }
__device__ __forceinline__ void mma16(float* c, uint32_t a0, uint32_t a1, uint32_t a2, uint32_t a3, uint32_t b0, uint32_t b1) {
    asm volatile("mma.sync.aligned.m16n8k16.row.col.f32.bf16.bf16.f32 {%0,%1,%2,%3},{%4,%5,%6,%7},{%8,%9},{%0,%1,%2,%3};"
                 : "+f"(c[0]), "+f"(c[1]), "+f"(c[2]), "+f"(c[3]) : "r"(a0), "r"(a1), "r"(a2), "r"(a3), "r"(b0), "r"(b1));
}
__device__ __forceinline__ void mma8(float* c, uint32_t a0, uint32_t a1, uint32_t b0) {
    asm volatile("mma.sync.aligned.m16n8k8.row.col.f32.bf16.bf16.f32 {%0,%1,%2,%3},{%4,%5},{%6},{%0,%1,%2,%3};"
                 : "+f"(c[0]), "+f"(c[1]), "+f"(c[2]), "+f"(c[3]) : "r"(a0), "r"(a1), "r"(b0));
}
__device__ __forceinline__ uint4 ld_rlx128(const uint4* p) {
    uint4 v;
    asm volatile("{.reg .b128 t; ld.relaxed.gpu.global.b128 t,[%4]; mov.b128 {%0,%1,%2,%3},t;}" : "=r"(v.x), "=r"(v.y), "=r"(v.z), "=r"(v.w) : "l"(p) : "memory");
    return v;
}
__device__ __forceinline__ void st_rlx128(uint4* p, uint32_t x, uint32_t y, uint32_t z, uint32_t w) {
    asm volatile("{.reg .b128 t; mov.b128 t,{%1,%2,%3,%4}; st.relaxed.gpu.global.b128 [%0],t;}" ::"l"(p), "r"(x), "r"(y), "r"(z), "r"(w) : "memory");
}
__device__ __forceinline__ uint4 ldcg128(const uint4* p) { uint4 v; asm volatile("ld.global.cg.v4.u32 {%0,%1,%2,%3},[%4];" : "=r"(v.x), "=r"(v.y), "=r"(v.z), "=r"(v.w) : "l"(p) : "memory"); return v; }
__device__ __forceinline__ void red_release(unsigned* p, unsigned v) {
    asm volatile("fence.proxy.async; red.relaxed.gpu.global.add.u32 [%0],%1;" ::"l"(p), "r"(v) : "memory");
}
__device__ __forceinline__ void wait_cnt(const unsigned* p, unsigned target) {
    unsigned v; int n = 0;
    while (true) {
        asm volatile("ld.acquire.gpu.global.u32 %0,[%1];" : "=r"(v) : "l"(p) : "memory");
        if (v >= target) break;
        if (++n > 3000000) __trap();
        __nanosleep(40);
    }
}
__device__ __forceinline__ void wait_cnt_warp(const unsigned* p, unsigned target) {
    unsigned v; int n = 0;
    while (true) {
        asm volatile("ld.acquire.gpu.global.u32 %0,[%1];" : "=r"(v) : "l"(p) : "memory");
        if (__all_sync(0xffffffffu, v >= target)) break;
        if (++n > 3000000) __trap();
    }
}
__device__ __forceinline__ uint64_t mkdesc(uint32_t addr, uint32_t lbo, uint32_t sbo, uint32_t sw) {
    return (uint64_t)((addr & 0x3FFFF) >> 4) | ((uint64_t)(lbo >> 4) << 16) | ((uint64_t)(sbo >> 4) << 32) | ((uint64_t)sw << 62);
}
__device__ __forceinline__ void wg_fence() { asm volatile("wgmma.fence.sync.aligned;" ::: "memory"); }
__device__ __forceinline__ void wg_commit() { asm volatile("wgmma.commit_group.sync.aligned;" ::: "memory"); }
template <int N> __device__ __forceinline__ void wg_wait() { asm volatile("wgmma.wait_group.sync.aligned %0;" ::"n"(N) : "memory"); }
#define R8(c, o) "+f"(c[o]), "+f"(c[o + 1]), "+f"(c[o + 2]), "+f"(c[o + 3]), "+f"(c[o + 4]), "+f"(c[o + 5]), "+f"(c[o + 6]), "+f"(c[o + 7])
#define R32(c, o) R8(c, o), R8(c, o + 8), R8(c, o + 16), R8(c, o + 24)
#define S32A "%0,%1,%2,%3,%4,%5,%6,%7,%8,%9,%10,%11,%12,%13,%14,%15,%16,%17,%18,%19,%20,%21,%22,%23,%24,%25,%26,%27,%28,%29,%30,%31"
#define S32B ",%32,%33,%34,%35,%36,%37,%38,%39,%40,%41,%42,%43,%44,%45,%46,%47,%48,%49,%50,%51,%52,%53,%54,%55,%56,%57,%58,%59,%60,%61,%62,%63"
#define S32C ",%64,%65,%66,%67,%68,%69,%70,%71,%72,%73,%74,%75,%76,%77,%78,%79,%80,%81,%82,%83,%84,%85,%86,%87,%88,%89,%90,%91,%92,%93,%94,%95"
#define S32D ",%96,%97,%98,%99,%100,%101,%102,%103,%104,%105,%106,%107,%108,%109,%110,%111,%112,%113,%114,%115,%116,%117,%118,%119,%120,%121,%122,%123,%124,%125,%126,%127"
#define W8(c, o) "=f"(c[o]), "=f"(c[o + 1]), "=f"(c[o + 2]), "=f"(c[o + 3]), "=f"(c[o + 4]), "=f"(c[o + 5]), "=f"(c[o + 6]), "=f"(c[o + 7])
#define W32(c, o) W8(c, o), W8(c, o + 8), W8(c, o + 16), W8(c, o + 24)
template <bool ACC> __device__ __forceinline__ void wgmma256(float* c, uint64_t da, uint64_t db) {
    if (ACC) asm volatile("wgmma.mma_async.sync.aligned.m64n256k16.f32.bf16.bf16 {" S32A S32B S32C S32D "},%128,%129,1,1,1,0,1;"
                          : R32(c, 0), R32(c, 32), R32(c, 64), R32(c, 96) : "l"(da), "l"(db));
    else asm volatile("wgmma.mma_async.sync.aligned.m64n256k16.f32.bf16.bf16 {" S32A S32B S32C S32D "},%128,%129,0,1,1,0,1;"
                      : W32(c, 0), W32(c, 32), W32(c, 64), W32(c, 96) : "l"(da), "l"(db));
}
template <bool ACC> __device__ __forceinline__ void wgmma128r(float* c, const uint4& a, uint64_t db) {
    if (ACC) asm volatile("wgmma.mma_async.sync.aligned.m64n128k16.f32.bf16.bf16 {" S32A S32B "},{%64,%65,%66,%67},%68,1,1,1,1;"
                          : R32(c, 0), R32(c, 32) : "r"(a.x), "r"(a.y), "r"(a.z), "r"(a.w), "l"(db));
    else asm volatile("wgmma.mma_async.sync.aligned.m64n128k16.f32.bf16.bf16 {" S32A S32B "},{%64,%65,%66,%67},%68,0,1,1,1;"
                      : W32(c, 0), W32(c, 32) : "r"(a.x), "r"(a.y), "r"(a.z), "r"(a.w), "l"(db));
}
template <int N> __device__ __forceinline__ void reg_inc() { asm volatile("setmaxnreg.inc.sync.aligned.u32 %0;" ::"n"(N)); }
template <int N> __device__ __forceinline__ void reg_dec() { asm volatile("setmaxnreg.dec.sync.aligned.u32 %0;" ::"n"(N)); }

#define PROF(cond, idx) do {} while (0)
#define CPROF(k) do {} while (0)

constexpr int S_GATE = 232440, S_TAG = 232444, S_XBAR = 232432;
constexpr float SC_LOG2E = 0.08838834764831845f * 1.4426950408889634f;

__device__ __forceinline__ float2 ln_finish(float mean, float var) {
    float sd; asm("sqrt.approx.f32 %0,%1;" : "=f"(sd) : "f"(rbf(rbf(var) + 1e-5f)));
    sd = rbf(sd);
    return make_float2(rbf(mean), sd);
}

__device__ __forceinline__ float2 row_stats512(const uint4* src, int s1, int s2) {
    const int g = (threadIdx.x & 31) >> 2;
    uint4 v[16];
#pragma unroll
    for (int i = 0; i < 16; i++) v[i] = ldcg128(src + (i >> 1) * s1 + (i & 1) * s2);
    float a[4] = {0, 0, 0, 0}, q0[4] = {0, 0, 0, 0}, q1[4] = {0, 0, 0, 0};
#pragma unroll
    for (int i = 0; i < 16; i++) {
        mma16(a, v[i].x, v[i].y, v[i].z, v[i].w, 0x3f803f80u, 0x3f803f80u);
        mma8(q0, v[i].x, v[i].y, v[i].x); mma8(q1, v[i].x, v[i].y, v[i].y);
        mma8(q0, v[i].z, v[i].w, v[i].z); mma8(q1, v[i].z, v[i].w, v[i].w);
    }
    const float sum = a[0] + a[2], sq = (g & 1) ? q0[1] + q1[3] : q0[0] + q1[2];
    return make_float2(sum, sq);
}
__device__ __forceinline__ void x1_stats(int rg, int tag) {
    const int lane = threadIdx.x & 31, g = lane >> 2, c = lane & 3;
    const float2 r = row_stats512(g_xA[0] + (rg >> 4) * 8192 + (rg & 15) * 64 + c * 8 + g, 1024, 32);
    if (c == (g >> 1)) { g_st[0][(rg >> 4) * 2048 + (rg < 32 ? 2 : tag) * 128 + (rg & 15) * 8 + g] = r; g_ln0[rg * 8 + g] = 0; }
    __syncwarp();
    if (lane == 0) red_release(cnt_ptr(C_ST, rg >> 4), 1);
}
__global__ void stats_kernel() { x1_stats(blockIdx.x * 4 + (threadIdx.x >> 5), (g_gate[0] / (4 * NCL)) & 1); }

#define NT 9
#define RH 104
#define RW0 200
#define NPD 9
#define NTO 13
#define DP1 9
#define GPW 0
#define GPJ 0
#define PACE 2
#define BKA 0
#define GSE 4
#define EARLY 4
#define PFD 0
#define PFB 0
#define G2S 7
#define STO 1
#define G2I 2
#define VE 4
#define VF 8
constexpr int R_WV = 0, R_WO = 65536, R_T = 131072, R_M = R_T + 20480, R_LOC = R_M + 4096, R_REM = R_LOC + 6144, R_O = R_REM + 12288, R_SX = R_O + 2048,
              R_IL = R_SX + 5120, XS = R_IL + 128 - R_T, R_BAR = 231936, R_Z = R_BAR + 128  , R_STQ = 0, R_STK = 65536, R_STV = 131072;
static_assert(R_T + 2 * XS <= R_BAR && R_BAR + 256 <= S_XBAR, "smem map");
enum { RB_INIT = 0, RB_MB = 1, RB_V = 4  , RB_QK = 8  , RB_T = 12  , RB_N = 16 };
enum { NB_MF = 1  , NB_LOC = 3  , NB_PAIR = 5  , NB_O = 9  , NB_XG = 11  , NB_W = 13 };
__device__ __forceinline__ uint32_t clk32() { return (uint32_t)clock64(); }

__device__ __forceinline__ char* acc_base() { return (char*)(((size_t)g_acc + 131071) & ~(size_t)131071); }
__device__ __forceinline__ uint32_t acc_slice(uint32_t s6) { return (s6 & 1) * 256 + (s6 >> 1) * 1024; }
__device__ __forceinline__ uint32_t acc_main(uint32_t rank, uint32_t tid) { return acc_slice(rank * 32 + (tid >> 3)) + (tid & 7) * 16; }
__device__ __forceinline__ uint32_t acc_extra(uint32_t rank, uint32_t tid) { return 65536 + acc_slice(((tid >> 5) & 1) + rank * 4 + (tid >> 6) * 8) + (tid & 31) * 4; }
__device__ __forceinline__ uint32_t acc_slot(uint32_t s) { return (s & 1) * 128 + (s & 2) * 256; }
__device__ __forceinline__ void acc_init(const __nv_bfloat16* mem0, int i) {
    const uint32_t tid = i & 255, rank = (i >> 8) & 1, slot = (i >> 9) & 3, X = i >> 11;
    uint32_t v[5] = {0, 0, 0, 0, 0};
    if (slot == 3) {
        const uint16_t* m = (const uint16_t*)mem0 + (tid & 3) * 1024 + rank * 256 + (tid >> 5) * 32 + ((tid >> 2) & 7);
#pragma unroll
        for (int k = 0; k < 4; k++) v[k] = __ldg(m + k * 8) | ((uint32_t)__ldg(m + k * 8 + 512) << 16);
        v[4] = (v[3] >> 16) | 0x42000000u; v[3] = (v[3] & 0xffff) | 0x42000000u;
    }
    *(uint4*)(acc_base() + X * 32768 + acc_slot(slot) + acc_main(rank, tid)) = make_uint4(v[0], v[1], v[2], v[3]);
    *(uint32_t*)(acc_base() + X * 1024 + acc_slot(slot) + acc_extra(rank, tid)) = v[4];
}
__global__ void acc_init_kernel(const __nv_bfloat16* mem0) { acc_init(mem0, blockIdx.x * 256 + threadIdx.x); }

struct RecW { uint32_t am, ae, ah, dp, lp, lpw, vo, sb, bar, zero, ts, tn; };
__device__ __forceinline__ uint32_t vadd(uint32_t a, uint32_t b) { uint32_t d; asm volatile("add.u32 %0,%1,%2;" : "=r"(d) : "r"(a), "r"(b)); return d; }
__device__ __forceinline__ uint32_t vshr(uint32_t a, int n) { uint32_t d; asm volatile("shr.u32 %0,%1,%2;" : "=r"(d) : "r"(a), "r"(n)); return d; }
__device__ __forceinline__ uint64_t gptr(uint32_t lo, uint32_t hi) { uint64_t d; asm("mov.b64 %0,{%1,%2};" : "=l"(d) : "r"(lo), "r"(hi)); return d; }
__device__ __forceinline__ void sfence(uint32_t zero) { asm volatile("{.reg .pred p; setp.ne.u32 p,%0,0; @p exit;}" ::"r"(zero) : "memory"); }
#define SF sfence(k.zero)
#define TS(i) do {} while (0)
#define TSN(i) do {} while (0)
#define TSET(it, slot) do {} while (0)
struct Gat { uint32_t x, y, z, w, e; };
template <int X>
__device__ __forceinline__ void gat_issue(Gat& g, const RecW& k, int s, uint32_t dep) {
    const uint32_t o = acc_slot(s + 3) + dep;
    asm volatile("{.reg .b128 t; ld.relaxed.gpu.global.b128 t,[%5+%7]; mov.b128 {%0,%1,%2,%3},t; ld.relaxed.gpu.global.u32 %4,[%6+%8];}"
                 : "=r"(g.x), "=r"(g.y), "=r"(g.z), "=r"(g.w), "=r"(g.e) : "l"(gptr(k.am + o, k.ah)), "l"(gptr(k.ae + o, k.ah)), "n"(X * 32768), "n"(X * 1024) : "memory");
}
template <int X>
__device__ __forceinline__ bool gat_store(const Gat& g, const RecW& k) {
    uint32_t c;
    asm volatile("prmt.b32 %0,%1,%2,0x7632;" : "=r"(c) : "r"(g.w), "r"(g.e));
    SF;
    asm volatile("{.reg .b32 t; prmt.b32 t,%4,%6,0x5410; stmatrix.sync.aligned.m8n8.x4.trans.shared.b16 [%0+%5],{%1,%2,%3,t};}" ::"r"(k.lpw), "r"(g.x), "r"(g.y), "r"(g.z), "r"(g.w), "n"(R_M + X * XS), "r"(g.e) : "memory");
    return __all_sync(0xffffffffu, c == 0x42004200u);
}
template <int X>
__device__ __forceinline__ void gat_finish(bool ok, const RecW& k, int s) {
    if (!ok) {
        int n = s;
        while (true) {
            Gat g;
            gat_issue<X>(g, k, n, 0);
            if (gat_store<X>(g, k)) break;
            n += 4;
            if (n > 8000000) __trap();
        }
    }
}
__device__ __forceinline__ uint4 lds128o(uint32_t a, int o) { uint4 v; asm volatile("{.reg .b32 t; add.u32 t,%4,%5; ld.shared.v4.u32 {%0,%1,%2,%3},[t];}" : "=r"(v.x), "=r"(v.y), "=r"(v.z), "=r"(v.w) : "r"(a), "r"(o) : "memory"); return v; }
__device__ __forceinline__ uint4 ldsm4o(uint32_t a, int o) { uint4 v; asm volatile("{.reg .b32 t; add.u32 t,%4,%5; ldmatrix.sync.aligned.m8n8.x4.shared.b16 {%0,%1,%2,%3},[t];}" : "=r"(v.x), "=r"(v.y), "=r"(v.z), "=r"(v.w) : "r"(a), "r"(o) : "memory"); return v; }
__device__ __forceinline__ uint4 ldsm4to(uint32_t a, int o) { uint4 v; asm volatile("{.reg .b32 t; add.u32 t,%4,%5; ldmatrix.sync.aligned.m8n8.x4.trans.shared.b16 {%0,%1,%2,%3},[t];}" : "=r"(v.x), "=r"(v.y), "=r"(v.z), "=r"(v.w) : "r"(a), "r"(o) : "memory"); return v; }
__device__ __forceinline__ uint2 lds64o(uint32_t a, int o) { uint2 v; asm volatile("{.reg .b32 t; add.u32 t,%2,%3; ld.shared.v2.u32 {%0,%1},[t];}" : "=r"(v.x), "=r"(v.y) : "r"(a), "r"(o) : "memory"); return v; }
__device__ __forceinline__ void sts128o(uint32_t a, int o, uint32_t x, uint32_t y, uint32_t z, uint32_t w) { asm volatile("{.reg .b32 t; add.u32 t,%0,%5; st.shared.v4.u32 [t],{%1,%2,%3,%4};}" ::"r"(a), "r"(x), "r"(y), "r"(z), "r"(w), "r"(o) : "memory"); }
__device__ __forceinline__ void sts64o(uint32_t a, int o, uint32_t x, uint32_t y) { asm volatile("{.reg .b32 t; add.u32 t,%0,%3; st.shared.v2.u32 [t],{%1,%2};}" ::"r"(a), "r"(x), "r"(y), "r"(o) : "memory"); }
__device__ __forceinline__ uint32_t vxor(uint32_t a, uint32_t b) { uint32_t d; asm volatile("xor.b32 %0,%1,%2;" : "=r"(d) : "r"(a), "r"(b)); return d; }
#define WLD(base, i) wt[i] = lds128o(k.lpw, (base) + (i) * 4096)
template <int PASS, int X, int NP>
__device__ __forceinline__ void rec_qkv(const RecW& k, int s, const uint32_t (*wq)[4], const uint32_t (*wk)[4], uint4* wt, Gat& g2, int s2, bool& ok2, uint4& mf) {
    constexpr bool BWD = PASS == 2, DIRECT = !(BKA && PASS == 1);
    float aq[4] = {0, 0, 0, 0}, ak[4] = {0, 0, 0, 0}, av[4] = {0, 0, 0, 0};
    constexpr int ma = R_M + X * XS;
    if (BWD && GSE == 4) { TS(1); mbar_wait(k.sb + R_BAR + RB_MB * 8, s & 1); mf = ldsm4o(k.lp, ma + 7 * 512); TS(2); }
    if (!BWD || GSE < 2) {
        if (BWD) { TS(1); gat_finish<1>(GSE ? ok2 : gat_store<1>(g2, k), k, s); }
        bar_sync(NB_MF + X, 256);
        mf = ldsm4o(k.lp, ma + (BWD ? 7 : 0) * 512);
        if (BWD) TS(2); else { TS(0); TSN(13); }
    }
#pragma unroll
    for (int ii = 0; ii < 8; ii++) {
        const int i = BWD ? 7 - ii : ii;
        const uint4 m = mf;
        if (ii < 7) mf = ldsm4o(k.lp, ma + (BWD ? i - 1 : i + 1) * 512);
        if (PASS == 1 && ii == G2I) gat_issue<1>(g2, k, s2, 0);
        if (PASS == 1 && GSE == 2 && ii == 7) { TS(1); gat_finish<1>(gat_store<1>(g2, k), k, s2); }
        if (PASS == 1 && GSE == 4 && ii == G2S) { gat_finish<1>(gat_store<1>(g2, k), k, s2); mbar_arrive1(k.sb + R_BAR + RB_MB * 8); }
        SF;
#pragma unroll
        for (int hh = 0; hh < 2; hh++) {
            const int h = BWD ? 1 - hh : hh, ks = 2 * i + h;
            const uint32_t b0 = h ? m.z : m.x, b1 = h ? m.w : m.y;
            mma16(aq, wq[ks][0], wq[ks][1], wq[ks][2], wq[ks][3], b0, b1);
            mma16(ak, wk[ks][0], wk[ks][1], wk[ks][2], wk[ks][3], b0, b1);
            SF;
            mma16(av, wt[ks].x, wt[ks].y, wt[ks].z, wt[ks].w, b0, b1);
            SF;
            if (!BWD && ks + NP < 16) WLD(R_WV, ks + NP < 16 ? ks + NP : 0);
            if (BWD && ks >= NT) WLD(R_WV, ks >= NT ? ks - NT : 0);
            SF;
        }
    }
    if (PASS == 1 && GSE == 1) { ok2 = gat_store<1>(g2, k); SF; }
    if (PASS == 1 && GSE == 3) { TS(1); gat_finish<1>(gat_store<1>(g2, k), k, s2); }
    if (PASS == 1 && (GSE == 2 || GSE == 3)) { bar_sync(NB_MF + 1, 256); mf = ldsm4o(k.lp, ma + XS + 7 * 512); TS(2); SF; }
    const uint32_t ra = vadd(k.lpw, k.dp + R_REM + X * XS + (s & 1) * 6144), va = ((vshr(k.lp, 7) & 1) * 48 ^ k.lp ^ (k.vo & 64)) + (k.vo & ~64u);
    const uint32_t x0 = movm(pack2(aq[0], aq[1])), x1 = movm(pack2(aq[2], aq[3])), x2 = movm(pack2(ak[0], ak[1])), x3 = movm(pack2(ak[2], ak[3]));
    SF;
    asm volatile("stmatrix.sync.aligned.m8n8.x2.shared.b16 [%0+%3],{%1,%2};" ::"r"(va), "r"(pack2(av[0], av[1])), "r"(pack2(av[2], av[3])), "n"(R_LOC + X * XS) : "memory");
    SF;
    if (STO && DIRECT) st_async4(ra, x0, x1, x2, x3, k.bar + X * 16);
    asm volatile("st.shared.v4.u32 [%0+%5],{%1,%2,%3,%4};" ::"r"(k.lpw), "r"(x0), "r"(x1), "r"(x2), "r"(x3), "n"(R_LOC + X * XS) : "memory");
    bar_arrive(NB_LOC + X, 320);
    if (!STO && DIRECT) st_async4(ra, x0, x1, x2, x3, k.bar + X * 16);
    SF;
    TS(BWD ? 4 : 3);
}
template <bool BWD, int X>
__device__ __forceinline__ void rec_out(const RecW& k, int s, uint4* wt, Gat& g, int s1) {
    if (BWD) { WLD(R_WO, 17 - NTO); WLD(R_WO, 16 - NTO); }
    TS(BWD ? 8 : 5);
    bar_sync(NB_O + X, 320);
    float r0[4] = {0, 0, 0, 0}, r1[4] = {0, 0, 0, 0};
    constexpr int oa = R_O + X * XS;
    uint4 bn = lds128o(k.lp, oa + (BWD ? 3 : 0) * 512);
    TS(BWD ? 9 : 6);
    uint2 il;
    uint64_t pm, pe;
#pragma unroll
    for (int ii = 0; ii < 4; ii++) {
        const int i = BWD ? 3 - ii : ii;
        const uint4 b = bn;
        if (ii < 3) bn = lds128o(k.lp, oa + (BWD ? i - 1 : i + 1) * 512);
        else { asm volatile("ld.shared.v2.u32 {%0,%1},[%2+%3];" : "=r"(il.x), "=r"(il.y) : "r"((vshr(k.ae, 2) & 3) * 8 + k.sb), "n"(R_IL + X * XS) : "memory"); pm = gptr(vadd(k.am, acc_slot(s)), k.ah); pe = gptr(vadd(k.ae, acc_slot(s)), k.ah); }
        SF;
        if (BWD && EARLY == ii + 1) { gat_issue<0>(g, k, s1 + 1, 0); SF; }
#pragma unroll
        for (int nn = 0; nn < 4; nn++) {
            const int n = BWD ? 3 - nn : nn, f = 4 * i + n, nx = BWD ? f - NTO + 2 : f + NTO - 2;
            mma16((n & 1) ? r1 : r0, wt[f].x, wt[f].y, wt[f].z, wt[f].w, n >> 1 ? b.z : b.x, n >> 1 ? b.w : b.y);
            SF;
            if (ii * 4 + nn >= 2 && nx >= 0 && nx < 16) WLD(R_WO, nx & 15);
            SF;
        }
    }
    const float i0 = __uint_as_float(il.x), i1 = __uint_as_float(il.y);
    asm volatile("red.relaxed.gpu.global.add.noftz.v4.bf16x2 [%0+%5],{%1,%2,%3,%4};" ::"l"(pm),
                 "r"(pack2(r0[0] * i0, r0[1] * i1)), "r"(pack2(r0[2] * i0, r0[3] * i1)), "r"(pack2(r1[0] * i0, r1[1] * i1)), "r"(pack2(r1[2] * i0, 1.f)), "n"(X * 32768) : "memory");
    asm volatile("red.relaxed.gpu.global.add.noftz.bf16x2 [%0+%2],%1;" ::"l"(pe), "r"(pack2(r1[3] * i1, 1.f)), "n"(X * 1024) : "memory");
    bar_arrive(NB_XG + X, 320);
    SF;
    TS(BWD ? 10 : 7);
}
__device__ __forceinline__ uint32_t pause(uint32_t v, int n) {
#pragma unroll
    for (int i = 0; i < n; i++) asm volatile("shfl.sync.bfly.b32 %0,%0,0,0x1f,0xffffffff;" : "+r"(v));
    return v;
}
template <bool DUAL, int X>
__device__ __forceinline__ void rec_step(const RecW& k, int s, int s2, const uint32_t (*wq)[4], const uint32_t (*wk)[4], uint4* wt) {
    constexpr int NP = NPD;
    uint4 wo[16];
    Gat g;
    bool ok2;
    uint4 mf;
    rec_qkv<DUAL ? 1 : 0, X, NP>(k, s, wq, wk, wt, g, s2, ok2, mf);
    if (DUAL) rec_qkv<2, 1, NP>(k, s2, wq, wk, wt, g, s2, ok2, mf);
    uint32_t wa = k.lpw;
#pragma unroll
    for (int i = 0; i < NTO; i++) {
        wo[i] = lds128o(wa, R_WO + i * 4096);
        if (i % PACE == PACE - 1) wa = k.lpw + (wo[i].x & k.zero);
        SF;
    }
    rec_out<false, X>(k, s, wo, g, s);
    if (DUAL) { rec_out<true, 1>(k, s2, wo, g, s); if (!EARLY) gat_issue<0>(g, k, s + 1, 0); SF; }
#pragma unroll
    for (int i = 0; i < NP; i++) { WLD(R_WV, i); SF; }
    if (!DUAL) gat_issue<X>(g, k, s + 1, pause(wt[NP - 1].x & k.zero, DP1));
    TS(12);
    gat_finish<X>(gat_store<X>(g, k), k, s + 1);
    TS(11);
}

__device__ __forceinline__ void rec_fetch(const CUtensorMap* tm, uint32_t dst, int x, int y, int nx, uint32_t bar) {
#pragma unroll 1
    for (int j = 0; j < 8; j++) tma2d(dst + j * 8192, tm, x + (j / (8 / nx)) * 64, y + (j % (8 / nx)) * 64, bar);
}
__device__ __forceinline__ void rec_weights(const Params& p, uint32_t sb, int head, uint32_t rank, int w) {
    const int lane = threadIdx.x & 31, t = w & 3, WG = w >> 2;
    uint32_t wq[16][4], wk[16][4];
    const uint32_t rowo = (((lane >> 4) << 3) + (lane & 7)) * 128;
    const uint32_t woff = sb + WG * 32768 + rowo + (((2 * t + ((lane >> 3) & 1)) ^ (lane & 7)) << 4);
    const uint32_t qoff = sb + ((w & 1) ? R_STK : R_STQ) + WG * 32768 + rowo + (((2 * (t & 2) + ((lane >> 3) & 1)) ^ (lane & 7)) << 4);
    const uint32_t lw = sb + (lane ^ (lane >> 3)) * 16;
    PROF(threadIdx.x == 0, 3501);
    PROF(threadIdx.x == 0, 3502);
    mbar_wait(sb + R_BAR + RB_INIT * 8, 0);
    PROF(threadIdx.x == 0, 3503);
#pragma unroll
    for (int ks = 0; ks < 16; ks++) {
        uint4 a = ldsm4t(qoff + ks * 2048), b = ldsm4t((qoff ^ 32) + ks * 2048);
        wq[ks][0] = a.x; wq[ks][1] = a.y; wq[ks][2] = a.z; wq[ks][3] = a.w;
        wk[ks][0] = b.x; wk[ks][1] = b.y; wk[ks][2] = b.z; wk[ks][3] = b.w;
    }
    bar_sync(NB_W, 256);
#pragma unroll 4
    for (int ks = 0; ks < 16; ks++) { const uint4 a = ldsm4t(woff + R_STV + ks * 2048); sts128(lw + w * 512 + R_WV + ks * 4096, a.x, a.y, a.z, a.w); }
    bar_sync(NB_W, 256);
    if (threadIdx.x == 0) {
        mbar_expect(sb + R_BAR + RB_INIT * 8, 65536);
        rec_fetch(&p.tm[4], sb + R_STV, rank * 256, head * 128, 4, sb + R_BAR + RB_INIT * 8);
    }
    __syncwarp();
    mbar_wait(sb + R_BAR + RB_INIT * 8, 1);
#pragma unroll 4
    for (int f = 0; f < 16; f++) {
        const uint4 a = ldsm4t(sb + R_STV + (w >> 1) * 16384 + (f >> 1) * 2048 + rowo + ((((w & 1) * 4 + (f & 1) * 2 + ((lane >> 3) & 1)) ^ (lane & 7)) << 4));
        sts128(lw + w * 512 + R_WO + f * 4096, a.x, a.y, a.z, a.w);
    }
    PROF(threadIdx.x == 0, 3504);
    __syncthreads();
    cluster_sync();
    PROF(threadIdx.x == 0, 3505);
    RecW k;
    k.am = __shfl_sync(0xffffffffu, (uint32_t)(size_t)acc_base() + acc_main(rank, threadIdx.x), lane);
    k.ae = __shfl_sync(0xffffffffu, (uint32_t)(size_t)acc_base() + acc_extra(rank, threadIdx.x), lane);
    k.ah = (uint32_t)((size_t)acc_base() >> 32);
    k.sb = sb; k.zero = p.zero;

    k.dp = mapa(sb, rank ^ 1) - sb;
    k.lp = __shfl_sync(0xffffffffu, lw, lane);
    k.lpw = __shfl_sync(0xffffffffu, lw + w * 512, lane);
    k.vo = 4096 + w * 256 + (w & 1) * 64;
    k.bar = sb + k.dp + R_BAR + (RB_QK + WG) * 8;
    int it = 0;
    uint4 wt[16];
#pragma unroll
    for (int i = 0; i < NPD; i++) WLD(R_WV, i);
    gat_finish<0>(false, k, 0);
#pragma unroll 1
    for (; it < min(p.b1, p.e0); it++) { TSET(it, w == GPW ? 0 : 3); rec_step<false, 0>(k, it, it, wq, wk, wt); }
#pragma unroll 1
    for (; it < p.e0; it++) { TSET(it, w == GPW ? 0 : 3); rec_step<true, 0>(k, it, it - p.b1, wq, wk, wt); }
    if (it < p.nit) gat_finish<1>(false, k, it - p.b1);
#pragma unroll 1
    for (; it < p.nit; it++) { TSET(it, w == GPW ? 0 : 3); rec_step<false, 1>(k, it - p.b1, it - p.b1, wq, wk, wt); }
}

__device__ __forceinline__ void mma16_top(float* c, uint32_t a0, uint32_t a2, uint32_t b0, uint32_t b1) {
    asm volatile("{.reg .b32 j; mma.sync.aligned.m16n8k16.row.col.f32.bf16.bf16.f32 {%0,%1,%2,%3},{%4,j,%5,j},{%6,%7},{%0,%1,%2,%3};}"
                 : "+f"(c[0]), "+f"(c[1]), "+f"(c[2]), "+f"(c[3]) : "r"(a0), "r"(a2), "r"(b0), "r"(b1));
}
__device__ __forceinline__ void rec_load_tile(uint32_t sb, int X, int j, int s, int head, uint32_t rank) {
    const uint32_t bar = sb + R_BAR + (RB_T + X * 2 + j) * 8;
    mbar_expect1(bar, j ? 4096 : 16384);
    bulk_g2s1(sb + R_T + X * XS + j * 16384, g_qkv[X] + (size_t)(s * 32 + head) * 1536 + (j ? rank * 256 : 512), j ? 4096 : 16384, bar, POL_LAST);
}
__device__ __forceinline__ bool chunk_ready(int X, int j, int s) {
    unsigned v;
    asm volatile("ld.relaxed.gpu.global.u32 %0,[%1];" : "=r"(v) : "l"(cnt_ptr(C_QKV0 + X, (s >> 2) + j * 16)) : "memory");
    return __all_sync(0xffffffffu, v >= (256 >> j));
}
__device__ __forceinline__ uint4 hadd4(uint4 a, uint4 b) { return make_uint4(hadd2(a.x, b.x), hadd2(a.y, b.y), hadd2(a.z, b.z), hadd2(a.w, b.w)); }
struct RecH { uint32_t lw, lm, lq, lv, lu, sa, sp, xb, sb, zero, ts, tn; };
__device__ __forceinline__ void rec_publish(int X, int s) {
    asm volatile("{.reg .pred p; cp.async.bulk.wait_group 0; elect.sync _|p,0xffffffff; @p red.relaxed.gpu.global.add.u32 [%0],4;}" ::"l"(cnt_ptr(C_O0 + X, s >> 2)) : "memory");
}
__device__ __forceinline__ void rec_mattn(const RecH& k, uint32_t dp, int X, int j, int s, bool qk, uint4 (*V)[4], uint4* vm) {
    const uint32_t sb = k.sb, to = R_T, lo = R_LOC, ro = R_REM + (s & 1) * 6144;
    const uint32_t bar = sb + R_BAR + (X * 2 + j) * 8;
    uint4 K[2][4];
    mbar_wait(sb + R_BAR + (RB_T + X * 2) * 8, s & 1);
    TS(1);
#pragma unroll
    for (int i = 0; i < 8; i++) K[i >> 2][i & 3] = ldsm4o(k.lm, (to + (i >> 2) * 1024 + ((i >> 1) & 1) * 4096 + (i & 1) * 512));
    asm volatile("cp.async.bulk.wait_group 0;" ::: "memory");
    bar_sync(NB_LOC + X, 320);
    fence_async_smem();
    if (qk) asm volatile("{.reg .pred p; elect.sync _|p,0xffffffff; @p cp.async.bulk.shared::cluster.shared::cta.mbarrier::complete_tx::bytes [%0],[%1],2048,[%2];}"
                         ::"r"(k.xb + dp + ro + j * 1024), "r"(k.xb + lo + j * 1024), "r"(bar + dp + RB_QK * 8) : "memory");
    asm volatile("{.reg .pred p; elect.sync _|p,0xffffffff; @p cp.async.bulk.shared::cluster.shared::cta.mbarrier::complete_tx::bytes [%0],[%1],1024,[%2];}"
                 ::"r"(k.xb + dp + ro + 4096), "r"(k.xb + lo + 4096), "r"(bar + dp + RB_V * 8) : "memory");
    uint4 u[4];
#pragma unroll
    for (int i = 0; i < 4; i++) u[i] = ldsm4o(k.lm, (lo + i * 512));
    TS(2);
    mbar_wait(bar + RB_QK * 8, s & 1);
    TS(3);
    float S[5][4];
#pragma unroll
    for (int i = 0; i < 5; i++) S[i][0] = S[i][1] = S[i][2] = S[i][3] = 0;
    {
        uint4 r[4];
#pragma unroll
        for (int i = 0; i < 4; i++) r[i] = ldsm4o(k.lm, (ro + i * 512));
        SF;
#pragma unroll
        for (int e = 0; e < 2; e++) {
            uint4& km = u[2 * e + 1];
            const uint32_t q0 = hadd2(u[2 * e].x, r[2 * e].x), q1 = hadd2(u[2 * e].y, r[2 * e].y);
            mma16_top(S[0], q0, q1, K[e][0].x, K[e][0].y);
            km.x = hadd2(km.x, r[2 * e + 1].x); km.y = hadd2(km.y, r[2 * e + 1].y);
            SF;
            mma16_top(S[1], q0, q1, K[e][1].x, K[e][1].y);
            const uint32_t q2 = hadd2(u[2 * e].z, r[2 * e].z), q3 = hadd2(u[2 * e].w, r[2 * e].w);
            SF;
            mma16_top(S[2], q0, q1, K[e][2].x, K[e][2].y);
            km.z = hadd2(km.z, r[2 * e + 1].z); km.w = hadd2(km.w, r[2 * e + 1].w);
            SF;
            mma16_top(S[3], q0, q1, K[e][3].x, K[e][3].y);
            mma16_top(S[4], q0, q1, km.x, km.y);
            SF;
#pragma unroll
            for (int i = 0; i < 4; i++) {
                mma16_top(S[i], q2, q3, K[e][i].z, K[e][i].w); SF;
            }
            mma16_top(S[4], q2, q3, km.z, km.w);
            SF;
        }
    }
#define VLD(a, b) _Pragma("unroll") for (int i = (a); i < (b); i++) V[i >> 2][i & 3] = ldsm4to((i & 1) ? lv2 : k.lv, (to + 8192 + (i >> 2) * 4096 + ((i >> 1) & 1) * 1024))
    const uint32_t lv2 = vxor(k.lv, 0x20), lh = k.lw - (vshr(k.lw - k.xb, 1) & 0xf8);
    VLD(0, VE);
    SF;
    const uint32_t sxr = k.sa, sxw = k.sp;
    sts128o(k.lw, sxw, __float_as_uint(S[0][0]), __float_as_uint(S[0][1]), __float_as_uint(S[1][0]), __float_as_uint(S[1][1]));
    SF;
    sts128o(k.lw, (sxw + 512), __float_as_uint(S[2][0]), __float_as_uint(S[2][1]), __float_as_uint(S[3][0]), __float_as_uint(S[3][1]));
    SF;
    sts64o(lh, (sxw + 1024), __float_as_uint(S[4][0]), __float_as_uint(S[4][1]));
    TS(4);
    bar_sync(NB_PAIR + X, 64);
    {
        const uint4 a = lds128o(k.lw, sxr), b = lds128o(k.lw, (sxr + 512));
        const uint2 c = lds64o(lh, (sxr + 1024));
        SF;
        VLD(VE, VF);
        SF;
        S[0][0] += __uint_as_float(a.x); S[0][1] += __uint_as_float(a.y); S[1][0] += __uint_as_float(a.z); S[1][1] += __uint_as_float(a.w);
        S[2][0] += __uint_as_float(b.x); S[2][1] += __uint_as_float(b.y); S[3][0] += __uint_as_float(b.z); S[3][1] += __uint_as_float(b.w);
        S[4][0] += __uint_as_float(c.x); S[4][1] += __uint_as_float(c.y);
    }
    float m = fmaxf(fmaxf(fmaxf(S[0][0], S[0][1]), fmaxf(S[1][0], S[1][1])), fmaxf(fmaxf(S[2][0], S[2][1]), fmaxf(S[3][0], S[3][1])));
    m = fmaxf(m, fmaxf(S[4][0], S[4][1]));
    m = fmaxf(m, __shfl_xor_sync(0xffffffffu, m, 1));
    const float m2 = __shfl_xor_sync(0xffffffffu, m, 2);
    SF;
    VLD(VF, 8);
    uint32_t ok;
    asm volatile("{.reg .pred p; mbarrier.test_wait.parity.shared::cta.b64 p,[%1],%2; selp.u32 %0,1,0,p;}" : "=r"(ok) : "r"(bar + RB_V * 8), "r"(s & 1) : "memory");
    uint4 vr0 = ldsm4o(k.lu, (ro + 4096)), vr1 = ldsm4o(k.lu, (ro + 4608));
    vm[0] = ldsm4o(k.lu, (lo + 4096)); vm[1] = ldsm4o(k.lu, (lo + 4608));
    SF;
    TS(5);
    m = fmaxf(m, m2) * -SC_LOG2E;
    uint32_t P[5];
#pragma unroll
    for (int i = 0; i < 5; i++) P[i] = pack2(ex2(fmaf(S[i][0], SC_LOG2E, m)), ex2(fmaf(S[i][1], SC_LOG2E, m)));
    float o[4][4], l[4] = {0, 0, 0, 0};
    const uint32_t ONE = 0x3f803f80u;
    mma16_top(l, ONE, ONE, P[0], P[1]);
#pragma unroll
    for (int t = 0; t < 4; t++) { o[t][0] = o[t][1] = o[t][2] = o[t][3] = 0; mma16(o[t], V[0][t].x, V[0][t].y, V[0][t].z, V[0][t].w, P[0], P[1]); }
    mma16_top(l, ONE, ONE, P[2], P[3]);
#pragma unroll
    for (int t = 0; t < 4; t++) mma16(o[t], V[1][t].x, V[1][t].y, V[1][t].z, V[1][t].w, P[2], P[3]);
    if (!__all_sync(0xffffffffu, ok)) {
        mbar_wait(bar + RB_V * 8, s & 1);
        vr0 = ldsm4o(k.lu, (ro + 4096)); vr1 = ldsm4o(k.lu, (ro + 4608));
    }
    TS(6);
    vm[0] = hadd4(vm[0], vr0); vm[1] = hadd4(vm[1], vr1);
    mma8(l, ONE, ONE, P[4]);
    mma8(o[0], vm[0].x, vm[0].y, P[4]); mma8(o[1], vm[0].z, vm[0].w, P[4]); mma8(o[2], vm[1].x, vm[1].y, P[4]); mma8(o[3], vm[1].z, vm[1].w, P[4]);
    asm volatile("{.reg .pred p; .reg .b32 t; setp.lt.u32 p,%0,%3; add.u32 t,%0,%4; @p st.shared.v2.f32 [t],{%1,%2};}" ::"r"(lh), "f"(rcp(l[0])), "f"(rcp(l[1])), "r"(k.xb + 32), "r"(R_IL) : "memory");
#pragma unroll
    for (int t = 0; t < 4; t += 2)
        asm volatile("{.reg .b32 t; add.u32 t,%0,%5; stmatrix.sync.aligned.m8n8.x4.trans.shared.b16 [t],{%1,%2,%3,%4};}" ::"r"(k.lm),
                     "r"(pack2(o[t][0], o[t][1])), "r"(pack2(o[t][2], o[t][3])), "r"(pack2(o[t + 1][0], o[t + 1][1])), "r"(pack2(o[t + 1][2], o[t + 1][3])), "r"(R_O - j * 1024 + t * 256) : "memory");
    bar_arrive(NB_O + X, 320);
    PROF(k.lw == k.xb, X * 64 + s);
    TS(7);
#pragma unroll
    for (int e = 0; e < 2; e++) sts128o(k.lw, (ro + e * 1024), u[2 * e + 1].x, u[2 * e + 1].y, u[2 * e + 1].z, u[2 * e + 1].w);
    mbar_expect1(bar + RB_QK * 8, 2048); mbar_expect1(bar + RB_V * 8, 1024);
}
template <int MT>
__device__ __forceinline__ void rec_xattn(const RecH& k, int X, int j, int s, int head, bool early, const uint4 (*V)[4], const uint4* vmm) {
    constexpr int NTL = 3 + 2 * MT;
    const uint32_t sb = k.sb, to = R_T, ro = R_REM + (s & 1) * 6144;
    const uint32_t sxw = k.sa, sxr = k.sp;
    const uint32_t lq2 = vxor(k.lq, 0x20);
    float S[NTL][4];
#pragma unroll
    for (int i = 0; i < NTL; i++) S[i][0] = S[i][1] = S[i][2] = S[i][3] = 0;
#pragma unroll
    for (int e = 0; e < 2; e++) {
        const uint4 q0 = ldsm4o(k.lq, (to + 16384 + e * 1024)), q1 = ldsm4o(lq2, (to + 16384 + e * 1024));
#pragma unroll
        for (int i = 0; i < NTL; i++) {
            const uint4 kk = i ? ldsm4o(k.lm, (to + e * 1024 + ((i - 1) >> 1) * 4096 + ((i - 1) & 1) * 512)) : lds128o(k.lw, (ro + e * 1024));
            mma16(S[i], q0.x, q0.y, q0.z, q0.w, kk.x, kk.y); mma16(S[i], q1.x, q1.y, q1.z, q1.w, kk.z, kk.w);
        }
    }
#pragma unroll
    for (int i = 0; i < NTL; i++) sts128o(k.lw, (sxw + i * 512), __float_as_uint(S[i][0]), __float_as_uint(S[i][1]), __float_as_uint(S[i][2]), __float_as_uint(S[i][3]));
    SF;
    bar_sync(NB_PAIR + 2 + X, 64);
    TS(9);
    if (early) rec_load_tile(sb, X, j, s + 1, head, MT);
#pragma unroll
    for (int i = 0; i < NTL; i++) {
        const uint4 r = lds128o(k.lw, (sxr + i * 512));
        S[i][0] += __uint_as_float(r.x); S[i][1] += __uint_as_float(r.y); S[i][2] += __uint_as_float(r.z); S[i][3] += __uint_as_float(r.w);
    }
    const int g = vshr(k.lw - k.xb, 6) & 7, c = (vshr(k.lw, 4) ^ (g >> 1)) & 3;
    const float NEG = -__int_as_float(0x7f800000);
    if (2 * c > g) { S[NTL - 2][0] = NEG; S[NTL - 1][2] = NEG; }
    if (2 * c + 1 > g) { S[NTL - 2][1] = NEG; S[NTL - 1][3] = NEG; }
    float m0 = fmaxf(S[0][0], S[0][1]), m1 = fmaxf(S[0][2], S[0][3]);
#pragma unroll
    for (int i = 1; i < NTL; i++) { if (i < NTL - 1) m0 = fmaxf(m0, fmaxf(S[i][0], S[i][1])); m1 = fmaxf(m1, fmaxf(S[i][2], S[i][3])); }
    m0 = fmaxf(m0, __shfl_xor_sync(0xffffffffu, m0, 1)); m1 = fmaxf(m1, __shfl_xor_sync(0xffffffffu, m1, 1));
    m0 = fmaxf(m0, __shfl_xor_sync(0xffffffffu, m0, 2)); m1 = fmaxf(m1, __shfl_xor_sync(0xffffffffu, m1, 2));
    m0 *= -SC_LOG2E; m1 *= -SC_LOG2E;
    uint32_t P[NTL][2];
#pragma unroll
    for (int i = 0; i < NTL; i++) {
        P[i][0] = i < NTL - 1 ? pack2(ex2(fmaf(S[i][0], SC_LOG2E, m0)), ex2(fmaf(S[i][1], SC_LOG2E, m0))) : 0u;
        P[i][1] = pack2(ex2(fmaf(S[i][2], SC_LOG2E, m1)), ex2(fmaf(S[i][3], SC_LOG2E, m1)));
    }
    float l[4] = {0, 0, 0, 0};
#pragma unroll
    for (int i = 0; i < NTL; i++) mma8(l, P[i][0], P[i][1], 0x3f803f80u);
    const float l0 = rcp(l[0]), l1 = rcp(l[2]);

#pragma unroll
    for (int e = 0; e < 2; e++) {
        const uint4 vm = vmm[e];
        uint32_t u[2][4];
#pragma unroll
        for (int n = 0; n < 4; n++) {
            float a[4] = {0, 0, 0, 0};
#pragma unroll
            for (int m = 0; m <= MT; m++) {
                const uint4 v = V[m][e * 2 + (n >> 1)];
                mma8(a, P[1 + 2 * m][0], P[1 + 2 * m][1], (n & 1) ? v.y : v.x); mma8(a, P[2 + 2 * m][0], P[2 + 2 * m][1], (n & 1) ? v.w : v.z);
            }
            mma8(a, P[0][0], P[0][1], n == 0 ? vm.x : n == 1 ? vm.y : n == 2 ? vm.z : vm.w);
            u[0][n] = pack2(a[0] * l0, a[1] * l0); u[1][n] = pack2(a[2] * l1, a[3] * l1);
        }
        sts128o(k.lw, sxr + e * 512, u[0][0], u[0][1], u[0][2], u[0][3]); sts128o(k.lw, sxr + e * 512 + 1024, u[1][0], u[1][1], u[1][2], u[1][3]);
    }
    TS(10);
}
__device__ __forceinline__ void rec_attn(const Params& p, uint32_t sb, int X, int j, int head, uint32_t rank) {
    const int lane = threadIdx.x & 31;
    RecH k;
    k.xb = sb + X * XS + j * 1024;
    const uint32_t x2 = k.xb + j * 1024;
    k.lw = __shfl_sync(0xffffffffu, x2 + (lane ^ (lane >> 3)) * 16, lane);
    k.lm = __shfl_sync(0xffffffffu, x2 + ((lane & 7) * 4 + ((lane >> 3) ^ ((lane & 7) >> 1))) * 16, lane);
    k.lq = __shfl_sync(0xffffffffu, x2 + ((lane >> 3) & 1) * 512 + ((lane & 7) * 4 + ((lane >> 4) ^ ((lane & 7) >> 1))) * 16, lane);
    k.lv = __shfl_sync(0xffffffffu, x2 + (lane >> 4) * 512 + ((lane & 7) * 4 + (((lane >> 3) & 1) ^ ((lane & 7) >> 1))) * 16, lane);
    k.lu = __shfl_sync(0xffffffffu, k.xb + ((lane & 6) * 4 + (((lane >> 3) * 2 + (lane & 1)) ^ (lane & 6))) * 16, lane);
    k.sa = __shfl_sync(0xffffffffu, R_SX + j * 512, 0); k.sp = __shfl_sync(0xffffffffu, R_SX + 2560 - j * 4608, 0);
    k.sb = sb; k.zero = p.zero;
    const uint32_t dp = mapa(sb, rank ^ 1) - sb;
    char* zp = acc_base() + (j ? X * 32768 + acc_main(rank, head * 8) : X * 1024 + acc_extra(rank, head * 8));
    mbar_expect1(sb + R_BAR + (RB_QK + X * 2 + j) * 8, 2048); mbar_expect1(sb + R_BAR + (RB_V + X * 2 + j) * 8, 1024);
    bool early = false;
#pragma unroll 1
    for (int s = 0; s < 64; s++) {
        TSET(X ? s + p.b1 : s, j == GPJ ? 1 + X : 3);
        TS(0);
        if (!early) {
            if (!j) wait_cnt_warp(cnt_ptr(C_QKV0 + X, s >> 2), 256);
            early = !j || chunk_ready(X, 1, s);
            if (early) rec_load_tile(sb, X, j, s, head, rank);
        }
        if (PFD && s < 63 && early && (PFB || !X) && ((s & 3) != 3 || chunk_ready(X, j, s + 1)))
            asm volatile("{.reg .pred p; elect.sync _|p,0xffffffff; @p cp.async.bulk.prefetch.L2.global.L2::cache_hint [%0],%1,%2;}"
                         ::"l"(g_qkv[X] + (size_t)((s + 1) * 32 + head) * 1536 + (j ? rank * 256 : 512 + rank * 512)), "r"(j ? 4096 : 8192), "l"(POL_LAST) : "memory");
        uint4 V[2][4], vm[2];
        rec_mattn(k, dp, X, j, s, BKA && !X && s >= p.b1, V, vm);
        if (!early) { wait_cnt_warp(cnt_ptr(C_QKV0 + X, (s >> 2) + 16), 128); rec_load_tile(sb, X, 1, s, head, rank); }
        early = s < 63 && ((s & 3) != 3 || chunk_ready(X, j, s + 1));
        mbar_wait(sb + R_BAR + (RB_T + X * 2 + 1) * 8, s & 1);
        bar_sync(NB_XG + X, 320);
        TS(8);
        if (rank) rec_xattn<1>(k, X, j, s, head, early, V, vm); else rec_xattn<0>(k, X, j, s, head, early, V, vm);
        fence_async_smem();
        __syncwarp();
        asm volatile("{.reg .pred p; elect.sync _|p,0xffffffff;\n"
                     "@p cp.async.bulk.global.shared::cta.bulk_group.L2::cache_hint [%0],[%1],2048,%2;\n"
                     "@p cp.async.bulk.global.shared::cta.bulk_group [%3],[%4],%5;\n"
                     "cp.async.bulk.commit_group;}"
                     ::"l"(g_o[X] + ((s >> 2) * 64 + head * 2 + j) * 1024 + ((s & 3) * 2 + rank) * 128), "r"(x2 + k.sp),
                       "l"((X && s < 40) ? POL_LATE : POL_SOON), "l"(zp + acc_slot(s + 2)), "r"(sb + R_Z), "r"(j ? 128 : 32) : "memory");
        if ((s & 3) == 3) {
            if (!early && s < 63 && chunk_ready(X, j, s + 1)) { rec_load_tile(sb, X, j, s + 1, head, rank); early = true; }
            rec_publish(X, s);
        }
    }
}

__device__ __forceinline__ void rec_init(const Params& p, uint32_t sb, int head, uint32_t rank) {
    const uint32_t b = sb + R_BAR;
    const int i = threadIdx.x - 320;
    if (i >= 0 && i < RB_N) {
        mbar_init(b + i * 8, i == RB_MB ? 8 : 1);
        asm volatile("fence.mbarrier_init.release.cluster;" ::: "memory");
    }
    if (i == 0) mbar_expect(b + RB_INIT * 8, 196608);
    if (i >= 0 && i < 32) sts32(sb + R_Z + i * 4, 0);
}

#define NSTGN 8
constexpr int NSTG = NSTGN, STG_B = 24576;
#define LAGQ 1
#define LAGH 3
constexpr int NSB = 8;
constexpr int B_OUT = NSTG * STG_B  , B_UT = B_OUT, B_YT = B_UT + 16384, B_SP = B_YT  ,
              B_ST = 229376  , B_BAR = 231936;
static_assert(B_OUT + NSB * 4096 <= B_ST && B_ST + 2048 <= B_BAR && B_YT + 10240 <= B_ST, "smem map");
enum { BB_FULL = 0, BB_EMPTY = 8, BB_SF = 16  , BB_GO = 18, BB_DONE = 20  , BB_IDLE = 22  , BB_N = 30 };
enum { NB_C = 11, NB_WG = 12   };

__device__ __forceinline__ void bulk_init(uint32_t sb) {
    const int i = threadIdx.x - 320;
    if (i >= 0 && i < BB_N) {
        mbar_init(sb + B_BAR + i * 8, (i >= BB_EMPTY && i < BB_EMPTY + NSTG) ? 4 : i >= BB_DONE ? 4 : 1);
        asm volatile("fence.mbarrier_init.release.cluster;" ::: "memory");
    }
}

struct Task { int type, layer, ch, a, b, c, blk; bool pair, dry; };
__device__ __forceinline__ Task task_of(uint32_t tk, uint32_t rank) {
    Task t;
    t.type = tk & 7; t.layer = (tk >> 3) & 1; t.a = (tk >> 8) & 255; t.b = (tk >> 16) & 255; t.c = (tk >> 24) & 127; t.dry = tk >> 31;
    t.pair = t.type <= T_OP && (t.c & 64);
    t.ch = ((tk >> 4) & 15) + (t.pair ? rank : 0);
    t.blk = t.type == T_QKV ? t.a + (t.pair ? 0 : rank) : 192 + (t.pair ? (t.c >> 2) & 4 : rank * 4);
    return t;
}
__device__ __forceinline__ int qkv_blk(const Task& t, int u) {
    const int v = t.blk + (t.pair ? 1 : 2 * t.c) * u;
    return 2 * (v < 64 ? v + 32 : v - 64);
}
__device__ __forceinline__ void bulk_producer(const Params& p, uint32_t sb, int cl, uint32_t rank) {
    int st = 0; uint32_t ph = 1;
    const int tag = __shfl_sync(0xffffffffu, lds32(sb + S_TAG), 0);
    bool gated = false;
#define ACQ(bytes) do { mbar_wait(sb + B_BAR + (BB_EMPTY + st) * 8, ph); mbar_expect1(sb + B_BAR + (BB_FULL + st) * 8, bytes); } while (0)
#define NEXT do { if (++st == NSTG) { st = 0; ph ^= 1; } } while (0)
#pragma unroll 1
    for (int ti = 0; ti < MAXT; ti++) {
        const Task t = task_of(p.task[cl][ti], rank);
        const int layer = t.layer, ch = t.ch;
        if (t.type == T_END) break;
        if (t.type <= T_OP) {
            const bool qkv = t.type == T_QKV;
            const int rg = qkv ? (layer * 16 + ch) * 128 : 4096 + ((layer * 16 + ch) * 64 + t.a) * 16;
            const int nh = qkv ? 16 : 2 * t.b, row = qkv ? 0 : t.a * 64, bytes = qkv ? 16384 : STG_B;
            const unsigned* dep = cnt_ptr(qkv ? (layer ? C_CV : C_ST) : C_O0 + layer, ch);
            const unsigned need = qkv ? (layer ? 32 : ch < 2 ? 0 : 16) : 512;
            const uint64_t pol = qkv ? POL_N : POL_LAST;
            const int blk0 = qkv ? qkv_blk(t, 0) : t.blk;
            const CUtensorMap *tb = &p.t3[t.pair || qkv][blk0 >> 6], *ta = &p.ta[t.pair];
            const uint32_t db = sb + 8192 + (t.pair && !qkv ? rank * 8192 : 0), da = sb + (t.pair ? 0 : rank * 4096);
            const int zb = (blk0 & 63) + (t.pair && !qkv ? rank * 2 : 0), ya = rg + (t.pair ? 0 : rank * 8);
            const uint16_t mb = t.pair ? 3 : 1 << rank, ma = t.pair ? 1 << rank : 3;
            const int skip = t.pair && qkv ? rank ^ 1 : 2;
            int pend = qkv ? 2 : 0;
            bool wait = false;
            if (!t.dry) {
                unsigned v = 0;
                if (gated) asm volatile("ld.relaxed.gpu.global.u32 %0,[%1];" : "=r"(v) : "l"(dep) : "memory");
                wait = !gated || !__all_sync(0xffffffffu, v >= need);
                if (wait) pend = min(nh, gated ? NSTG : 4);
            }
            if (PFC && !qkv && !layer && (t.c & 15) < 8) {
                const int q = (t.c & 15) * 2 + rank;
                asm volatile("{.reg .pred p; elect.sync _|p,0xffffffff; @p cp.async.bulk.prefetch.L2.global [%0],8192; @p cp.async.bulk.prefetch.L2.global [%1],%2;}"
                             ::"l"(g_xA[0] + (ch * 16 + q) * 512), "l"(g_P + q * 16 * 32 * PW), "r"((2 + (ch & 1)) * 32 * PW * 4) : "memory");
            }
#pragma unroll 1
            while (qkv && st) { ACQ(0); NEXT; }
            int h = 0;
            const int s0 = st;
#pragma unroll 1
            for (; h < pend; h++) {
                ACQ(bytes + (qkv && h < 2 ? (layer ? 8192 : 1024) : 0));
                if ((h & 1) != skip) tma3d_mc(db + st * STG_B, tb, row + h * 32, zb, sb + B_BAR + (BB_FULL + st) * 8, mb);
                NEXT;
            }
            if (wait) {
                if (!gated) { wait_cnt_warp(g_gate, lds32(sb + S_GATE)); gated = true; }
                if (need) wait_cnt_warp(dep, need);
            }
#pragma unroll 1
            for (int k = 0; k < pend; k++) {
                const int s2 = s0 + k - (s0 + k >= NSTG ? NSTG : 0);
                if (qkv && k < 2) bulk_g2s1(sb + s2 * STG_B + 16384, g_st[layer] + ch * 2048 + (layer ? k * 1024 : tag * 128), layer ? 8192 : 1024, sb + B_BAR + (BB_FULL + s2) * 8, POL_N);
                tma2d_mc(da + s2 * STG_B, ta, (k & 1) * 256, ya + (k >> 1) * 16, sb + B_BAR + (BB_FULL + s2) * 8, ma, pol);
            }
#pragma unroll 1
            for (; h < nh; h++) {
                ACQ(bytes);
                if ((h & 1) != skip) tma3d_mc(db + st * STG_B, tb, row + h * 32, zb, sb + B_BAR + (BB_FULL + st) * 8, mb);
                tma2d_mc(da + st * STG_B, ta, (h & 1) * 256, ya + (h >> 1) * 16, sb + B_BAR + (BB_FULL + st) * 8, ma, pol);
                NEXT;
            }
#pragma unroll 1
            for (h = 0; h < 4 && !qkv && !layer; h++) { ACQ(0); NEXT; }
            if (qkv) {
#pragma unroll 1
                for (h = 8; h < 8 * t.b; h++) {
                    const int blk = qkv_blk(t, h >> 3);
                    ACQ(16384);
                    if (skip != 0) tma3d_mc(sb + st * STG_B, &p.t3[1][blk >> 6], (h & 7) * 64, blk & 63, sb + B_BAR + (BB_FULL + st) * 8, mb);
                    if (skip != 1) tma3d_mc(sb + st * STG_B + 8192, &p.t3[1][blk >> 6], (h & 7) * 64 + 32, blk & 63, sb + B_BAR + (BB_FULL + st) * 8, mb);
                    NEXT;
                }
            }
        } else if (t.type == T_CV) {
            const int q = t.a + rank;
            if (!gated && !t.dry) { wait_cnt_warp(g_gate, lds32(sb + S_GATE)); gated = true; }
            if (layer) {
                wait_cnt_warp(cnt_ptr(C_U, ch - 2), 32);
#pragma unroll 1
                for (int j = ch + 1; j >= 2; j--) {
                    ACQ(16 * PW * 4 + (j > 2 ? 4096 : 0));
                    bulk_g2s1(sb + st * STG_B, g_P + (((q >> 1) * 16 + j) * 2 + (q & 1)) * 16 * PW, 16 * PW * 4, sb + B_BAR + (BB_FULL + st) * 8, POL_N);
                    if (j > 2) bulk_g2s1(sb + st * STG_B + 12288, g_u + (((q >> 1) * 16 + ch + 1 - j) * 2 + (q & 1)) * 256, 4096, sb + B_BAR + (BB_FULL + st) * 8, POL_N);
                    NEXT;
                }
            } else {
#pragma unroll 1
                for (int j = min(ch, 1 + (ch & 1)); j >= 0; j--) {
                    if (j == 0 && ch >= 2) {
                        if (!t.dry) wait_cnt_warp(cnt_ptr(C_H, ch & ~1), 64);
#pragma unroll 1
                        for (int i = 0; i < ((ch & 1) || ch == 2 ? 1 : 2); i++) {
                            ACQ(16384);
                            bulk_g2s1(sb + st * STG_B, g_carry[i] + (ch * 16 + q) * 1024, 16384, sb + B_BAR + (BB_FULL + st) * 8, POL_LAST);
                            NEXT;
                        }
                    }
                    ACQ(32 * PW * 4);
                    bulk_g2s1(sb + st * STG_B, g_P + (q * 16 + j) * 32 * PW, 32 * PW * 4, sb + B_BAR + (BB_FULL + st) * 8, POL_N);
                    NEXT;
                }
            }
        }
    }
}

__device__ __forceinline__ uint4* qkv_dst(int layer, int ch, int w, int blk);
__device__ __forceinline__ uint4* op_dst(int layer, int ch, int slot, int w, uint32_t rank);
__device__ __forceinline__ uint64_t out_pol(int type, int layer, int ch) { return (type == T_QKV ? (!layer && ch > 1) : (layer && ch < 10)) ? POL_LATE : POL_SOON; }
__device__ __forceinline__ void bulk_release(const Params& p, uint32_t sb, int cl, uint32_t rank, int wg) {
    int nd = 0;
    for (int ti = 0; ti < MAXT; ti++) {
        const Task t = task_of(p.task[cl][ti], rank);
        const int type = t.type, layer = t.layer, ch = t.ch;
        if (type == T_END) break;
        if (type == T_FIN || (type == T_OP && (t.c & 32))) continue;
        if (type == T_OP && !layer) {
            mbar_wait(sb + B_BAR + (BB_DONE + wg) * 8, nd & 1);
            nd++;
            const int s0 = __shfl_sync(0xffffffffu, lds32(sb + B_ST + wg * 4), 0) + wg * 2;
            fence_async_smem();
#pragma unroll 1
            for (int w = 0; w < 4; w++)
                asm volatile("{.reg .pred p; elect.sync _|p,0xffffffff; @p cp.async.bulk.global.shared::cta.bulk_group.L2::cache_hint [%0],[%1],8192,%2; cp.async.bulk.commit_group;}"
                             ::"l"(op_dst(0, ch, t.c & 15, wg * 4 + w, rank)), "r"(sb + ((s0 + (w >> 1)) & (NSTG - 1)) * STG_B + (w & 1) * 8192), "l"(POL_SOON) : "memory");
            mbar_arrive1(sb + B_BAR + (BB_SF + wg) * 8);
            asm volatile("{.reg .pred p; elect.sync _|p,0xffffffff;\n"
                         "cp.async.bulk.wait_group 3; @p red.relaxed.gpu.global.add.u32 [%0],1; cp.async.bulk.wait_group 2; @p red.relaxed.gpu.global.add.u32 [%0+64],1;\n"
                         "cp.async.bulk.wait_group 1; @p red.relaxed.gpu.global.add.u32 [%0+128],1; cp.async.bulk.wait_group 0; @p red.relaxed.gpu.global.add.u32 [%0+192],1;}"
                         ::"l"(cnt_ptr(C_OP0 + rank * 2 + wg, ch)) : "memory");
#pragma unroll 1
            for (int i = 0; i < 8; i++) mbar_arrive1_cluster(mapa(sb + B_BAR + (BB_EMPTY + ((s0 + (i >> 2)) & (NSTG - 1))) * 8, i & 1));
            continue;
        }
#pragma unroll 1
        for (int u = 0; u < (type == T_QKV ? t.b : 1); u++) {
            const int blk = qkv_blk(t, u);
            unsigned* cnt = cnt_ptr(type == T_QKV ? C_QKV0 + layer : type == T_OP ? C_OP1 : layer ? C_H : C_CV, ch + (type == T_QKV && blk < 64 ? 16 : 0));
            const uint4* dst = type == T_QKV ? qkv_dst(layer, ch, wg * 4, blk) : op_dst(1, ch, t.c & 15, wg * 4, (t.blk >> 2) & 1) + 256;
            mbar_wait(sb + B_BAR + (BB_DONE + wg) * 8, nd & 1);
            nd++;
            if (type != T_CV) {
                fence_async_smem();
#pragma unroll
                for (int w = 0; w < 4; w++)
                    asm volatile("{.reg .pred p; elect.sync _|p,0xffffffff; @p cp.async.bulk.global.shared::cta.bulk_group.L2::cache_hint [%0],[%1],4096,%2;}"
                                 ::"l"(dst + (type == T_QKV ? (w >> 1) * 49152 + (w & 1) * 256 : w * 1024)), "r"(sb + B_OUT + (wg * 4 + w) * 4096), "l"(out_pol(type, layer, ch)) : "memory");
                asm volatile("cp.async.bulk.commit_group; cp.async.bulk.wait_group 0;" ::: "memory");
            }
            if (type != T_QKV) fence_async();
            if (!t.dry) asm volatile("{.reg .pred p; elect.sync _|p,0xffffffff; @p red.relaxed.gpu.global.add.u32 [%0],%1;}" ::"l"(cnt), "r"(type == T_QKV ? 2 : type == T_OP ? t.b : 1) : "memory");
            if (type == T_CV && !layer && !t.dry) {
                asm volatile("{.reg .pred p; elect.sync _|p,0xffffffff; @p cp.async.bulk.global.shared::cta.bulk_group [%0],[%1],4096;\n"
                             "cp.async.bulk.commit_group; cp.async.bulk.wait_group 0; @p red.relaxed.gpu.global.add.u32 [%2],1;}"
                             ::"l"(g_u + ((t.a + rank) * 16 + ch) * 512 + wg * 256), "r"(sb + B_UT + (ch & 1) * 8192 + wg * 4096), "l"(cnt_ptr(C_U, ch)) : "memory");
            }
            mbar_arrive1(sb + B_BAR + (BB_SF + wg) * 8);
        }
        PROF(wg && (threadIdx.x & 31) == 0, 3600 + ti * 4 + 3);
    }
}

__device__ __forceinline__ void stage_release(uint32_t sb, int w, int st) {
    if (!(w & 2)) mbar_arrive1_cluster(mapa(sb + B_BAR + (BB_EMPTY + st) * 8, w & 1));
}
template <bool ACC>
__device__ __forceinline__ void gemm_run(float* acc, uint32_t sb, int w, int h0, int h1, uint32_t& r0, uint32_t& r1, int& st, uint32_t& ph) {
    const uint64_t da0 = mkdesc(sb + (w >> 2) * 4096, 16, 512, 2), db0 = mkdesc(sb + 8192, 4096, 1024, 1);
    const uint32_t rel0 = mapa(sb + B_BAR + BB_EMPTY * 8, w & 1);
#pragma unroll 1
    for (int h = h0; h < h1; h++) {
        const uint64_t da = da0 + st * (STG_B >> 4), db = db0 + st * (STG_B >> 4);
        mbar_wait(sb + B_BAR + (BB_FULL + st) * 8, ph);
        if (ACC) wg_wait<1>();
        wg_fence();
        wgmma256<ACC>(acc, da, db);
        wgmma256<true>(acc, da + 2, db + 128);
        wg_commit();
        if (ACC) mbar_arrive1_cluster((w == 2 && h == LAGH - 1) ? sb + B_BAR + BB_GO * 8 : r0);
        r0 = r1;
        if (!(w & 2)) r1 = rel0 + st * 8;
        if (++st == NSTG) { st = 0; ph ^= 1; }
    }
}

__device__ __forceinline__ uint4* qkv_dst(int layer, int ch, int w, int blk) {
    return g_qkv[layer] + (size_t)((ch * 4 + (w >> 1)) * 32 + ((blk & 63) >> 1)) * 1536 + (blk >> 6) * 512 + (w & 1) * 256;
}
__device__ __forceinline__ uint4* op_dst(int layer, int ch, int slot, int w, uint32_t rank) {
    return g_pp[layer] + (size_t)(ch * MAXSPLIT + slot) * 8192 + (w * 32 + rank * 16) * 32;
}
__device__ __forceinline__ uint32_t ln2(uint32_t x, uint32_t m, uint32_t rh, uint32_t rl) {
    uint32_t d; asm volatile("{.reg .b32 t,u; sub.rn.bf16x2 t,%1,%2; mul.rn.bf16x2 u,t,%4; fma.rn.bf16x2 %0,t,%3,u;}" : "=r"(d) : "r"(x), "r"(m), "r"(rh), "r"(rl)); return d;
}
__device__ __forceinline__ void qkv_task(uint32_t sb, int w, int layer, int nu, int ng, int& nd, uint32_t& ph) {
    static_assert(NSTG == 8, "ring");
    const int lane = threadIdx.x & 31;
    const uint64_t db0 = mkdesc(sb, 4096, 1024, 1);
    const uint32_t rel = (w & 2) ? sb + B_BAR + BB_IDLE * 8 : mapa(sb + B_BAR + BB_EMPTY * 8, w & 1), full = sb + B_BAR + BB_FULL * 8;
    const uint32_t la = sb + w * 1024 + ((lane >> 3) & 1) * 512 + (lane >> 4) * 128 + (lane & 7) * 16, lo = sb + B_OUT + w * 4096 + (lane ^ (lane >> 3)) * 16;
    uint32_t m0, m1, h0, h1, l0, l1;
    uint4 A[32];
    {
        mbar_wait(full, ph);
        mbar_wait(full + 8, ph);
        const uint32_t sa = sb + (lane >> 4) * STG_B + 16384 + (w * 16 + (lane & 15)) * 8;
        uint2 v = lds64(sa);
        float sm = __uint_as_float(v.x), M2 = __uint_as_float(v.y);
        if (layer) {
            float e[8];
            e[0] = sm;
#pragma unroll
            for (int i = 1; i < 8; i++) { v = lds64(sa + i * 1024); e[i] = __uint_as_float(v.x); sm += e[i]; M2 += __uint_as_float(v.y); }
            sm += __shfl_xor_sync(0xffffffffu, sm, 16);
#pragma unroll
            for (int i = 0; i < 8; i++) { const float d = e[i] * (1.f / 32.f) - sm * (1.f / 512.f); M2 += 32.f * d * d; }
            M2 += __shfl_xor_sync(0xffffffffu, M2, 16);
        } else M2 = fmaxf(M2 - sm * sm * (1.f / 512.f), 0.f);
        A[0] = ldsm4(la); A[1] = ldsm4(la + 256);
        const float2 o = ln_finish(sm * (1.f / 512.f), M2 * (1.f / 512.f));
        const float r = rcp(o.y), rh = rbf(r);
        const uint32_t mm = pack2(o.x, o.x), hl = pack2(r - rh, rh);
        m0 = __shfl_sync(0xffffffffu, mm, lane >> 2); m1 = __shfl_sync(0xffffffffu, mm, (lane >> 2) + 8);
        l0 = __shfl_sync(0xffffffffu, hl, lane >> 2); l1 = __shfl_sync(0xffffffffu, hl, (lane >> 2) + 8);
        h0 = __byte_perm(l0, 0, 0x3232); h1 = __byte_perm(l1, 0, 0x3232); l0 = __byte_perm(l0, 0, 0x1010); l1 = __byte_perm(l1, 0, 0x1010);
    }
    float acc[64];
#define QNRM(i) A[i] = make_uint4(ln2(A[i].x, m0, h0, l0), ln2(A[i].y, m1, h1, l1), ln2(A[i].z, m0, h0, l0), ln2(A[i].w, m1, h1, l1))
    if (w >> 2) mbar_wait(sb + B_BAR + BB_GO * 8, ~ng & 1);
#pragma unroll
    for (int h = 0; h < 16; h++) {
        const uint64_t db = db0 + ((h & 7) * (STG_B >> 4) + 512);
        if (h < 15) { A[(2 * h + 2) & 31] = ldsm4(la + ((h + 1) & 7) * STG_B); A[(2 * h + 3) & 31] = ldsm4(la + ((h + 1) & 7) * STG_B + 256); }
        const bool ok = h >= 14 || mbar_test(full + ((h + 2) & 7) * 8, ph ^ ((h + 2) >> 3));
        QNRM(2 * h); QNRM(2 * h + 1);
        if (h) wg_wait<1>();
        wg_fence();
        if (h) wgmma128r<true>(acc, A[2 * h], db); else wgmma128r<false>(acc, A[0], db);
        wgmma128r<true>(acc, A[2 * h + 1], db + 128);
        wg_commit();
        if (h >= 2) mbar_arrive1_cluster(rel + ((h - 2) & 7) * 8);
        if (h == LAGQ - 1 && w == 2) mbar_arrive1(sb + B_BAR + BB_GO * 8);
        if (!ok) mbar_wait(full + ((h + 2) & 7) * 8, ph ^ ((h + 2) >> 3));
    }
#pragma unroll 1
    for (int u = 1;; u++) {
        mbar_wait(sb + B_BAR + (BB_SF + (w >> 2)) * 8, (nd & 1) ^ 1);
        if (u < nu) mbar_wait(full, ph);
        wg_wait<1>();
        mbar_arrive1_cluster(rel + 48);
        wg_wait<0>();
        mbar_arrive1_cluster(rel + 56);
        uint4 o[8];
#pragma unroll
        for (int n = 0; n < 8; n++) {
            const float* a = acc + (n >> 1) * 16 + (n & 1) * 2;
            o[n] = make_uint4(pack2(a[0], a[1]), pack2(a[4], a[5]), pack2(a[8], a[9]), pack2(a[12], a[13]));
            sts128(lo + n * 512, o[n].x, o[n].y, o[n].z, o[n].w);
        }
        __syncwarp();
        mbar_arrive1(sb + B_BAR + (BB_DONE + (w >> 2)) * 8);
        nd++;
        if (u == nu) break;
#pragma unroll
        for (int h = 0; h < 8; h++) {
            const uint64_t db = db0 + h * (STG_B >> 4);
            if (h) { mbar_wait(full + h * 8, ph); wg_wait<1>(); }
            wg_fence();
            if (h) wgmma128r<true>(acc, A[4 * h], db); else wgmma128r<false>(acc, A[0], db);
            wgmma128r<true>(acc, A[4 * h + 1], db + 128);
            wgmma128r<true>(acc, A[4 * h + 2], db + 512);
            wgmma128r<true>(acc, A[4 * h + 3], db + 640);
            wg_commit();
            if (h >= 2) mbar_arrive1_cluster(rel + (h - 2) * 8);
        }
        ph ^= 1;
    }
}

template <int NB>
__device__ __forceinline__ void load_resid(uint32_t* r, int layer, int ch, int w, int cb) {
    const uint32_t* rp = (const uint32_t*)(g_xA[layer] + (ch * 8 + (cb >> 2)) * 1024 + w * 128 + (cb & 3) * 16) + (threadIdx.x & 31);
#pragma unroll
    for (int i = 0; i < NB * 4; i++) r[i] = __ldcg(rp + (i >> 1) * 32 + (i & 1) * 256);
}
template <int NS>
__device__ __forceinline__ void part_load(uint4* v, int layer, int ch, int w, int cb, int ns) {
    const uint4* src = g_pp[layer] + (size_t)ch * MAXSPLIT * 8192 + (w * 32 + cb) * 32 + (threadIdx.x & 31);
#pragma unroll
    for (int i = 0; i < 2 * NS; i++) {
        asm volatile("{.reg .pred p; .reg .b128 t; setp.gt.s32 p,%6,0; mov.b128 t,{0,0,0,0}; @p ld.relaxed.gpu.global.L2::cache_hint.b128 t,[%4],%5; mov.b128 {%0,%1,%2,%3},t;}"
                     : "=r"(v[i].x), "=r"(v[i].y), "=r"(v[i].z), "=r"(v[i].w) : "l"(src + (i / NS) * 32 + (i % NS) * 8192), "l"(POL_LAST), "r"(ns - i % NS) : "memory");
    }
}
template <int NS>
__device__ __forceinline__ void part_sum(float* x, const uint4* v, const uint32_t* r) {
    const int dg = ((threadIdx.x & 31) >> 2) - 2 * (threadIdx.x & 3);
    const uint32_t idm = dg == 0 ? 0x00003f80u : dg == 1 ? 0x3f800000u : 0u;
#pragma unroll
    for (int b = 0; b < 2; b++) {
        float* y = x + b * 8;
#pragma unroll
        for (int i = 0; i < 8; i++) y[i] = 0;
#pragma unroll
        for (int s = 0; s < NS; s++) { mma8(y, v[b * NS + s].x, v[b * NS + s].y, idm); mma8(y + 4, v[b * NS + s].z, v[b * NS + s].w, idm); }
#pragma unroll
        for (int i = 0; i < 4; i++) { y[2 * i] = rbf(rbf(y[2 * i]) + blo(r[b * 4 + i])); y[2 * i + 1] = rbf(rbf(y[2 * i + 1]) + bhi(r[b * 4 + i])); }
    }
}

__device__ __forceinline__ float4 row_stats32(const float* x) {
    float a = (x[0] + x[1]) + (x[4] + x[5]) + (x[8] + x[9]) + (x[12] + x[13]);
    float b = (x[2] + x[3]) + (x[6] + x[7]) + (x[10] + x[11]) + (x[14] + x[15]);
    a += __shfl_xor_sync(0xffffffffu, a, 1); b += __shfl_xor_sync(0xffffffffu, b, 1);
    a += __shfl_xor_sync(0xffffffffu, a, 2); b += __shfl_xor_sync(0xffffffffu, b, 2);
    const float ma = a * (1.f / 32.f), mb = b * (1.f / 32.f);
    float qa = 0, qb = 0;
#pragma unroll
    for (int i = 0; i < 4; i++) {
        float d0 = x[4 * i] - ma, d1 = x[4 * i + 1] - ma, d2 = x[4 * i + 2] - mb, d3 = x[4 * i + 3] - mb;
        qa += d0 * d0 + d1 * d1; qb += d2 * d2 + d3 * d3;
    }
    qa += __shfl_xor_sync(0xffffffffu, qa, 1); qb += __shfl_xor_sync(0xffffffffu, qb, 1);
    qa += __shfl_xor_sync(0xffffffffu, qa, 2); qb += __shfl_xor_sync(0xffffffffu, qb, 2);
    return make_float4(a, qa, b, qb);
}

__device__ __forceinline__ void conv_stage(float* Y, uint32_t pbase, uint32_t ubase) {
    const int lane = threadIdx.x & 31, w = threadIdx.x >> 5, g = lane >> 2, c = lane & 3;
#pragma unroll
    for (int cp = 0; cp < 2; cp++) {
        const int chl = w * 4 + cp * 2 + (lane >> 4);
        const uint4 b = ldsm4(ubase + chl * 256 + ((lane >> 3) & 1) * 128 + (((lane & 7) ^ (chl & 7)) << 4));
#pragma unroll
        for (int h = 0; h < 2; h++) {
            const uint32_t pa = pbase + ((w * 4 + cp * 2 + h) * PW + 16 + g - 2 * c) * 4;
            uint32_t lo = lds32(pa - 32);
#pragma unroll
            for (int d = 0; d < 8; d++) {
                const uint32_t a0 = lds32(pa + d * 64), a1 = lds32(pa + d * 64 + 32);
                mma16(Y + ((cp * 2 + h) * 8 + d) * 4, a0, a1, lo, a0, h ? b.z : b.x, h ? b.w : b.y);
                lo = a1;
            }
        }
    }
}

__device__ __forceinline__ void conv_combine(const float* y8, float* cur, float* nxt) {
    const int lane = threadIdx.x & 31, c = lane & 3;
    cur[0] = y8[0]; cur[1] = y8[1] + y8[4]; cur[2] = y8[2]; cur[3] = y8[3] + y8[6];
    nxt[0] = y8[29]; nxt[1] = 0.f; nxt[2] = y8[31]; nxt[3] = 0.f;
#pragma unroll
    for (int e = 1; e < 4; e++) {
        const int src = (lane & ~3) | ((c - e) & 3);
        const float v0 = __shfl_sync(0xffffffffu, y8[8 * e] + y8[8 * e - 3], src), v1 = __shfl_sync(0xffffffffu, y8[8 * e + 1] + y8[8 * e + 4], src);
        const float v2 = __shfl_sync(0xffffffffu, y8[8 * e + 2] + y8[8 * e - 1], src), v3 = __shfl_sync(0xffffffffu, y8[8 * e + 3] + y8[8 * e + 6], src);
        if (c >= e) { cur[0] += v0; cur[1] += v1; cur[2] += v2; cur[3] += v3; }
        else { nxt[0] += v0; nxt[1] += v1; nxt[2] += v2; nxt[3] += v3; }
    }
}

__device__ __forceinline__ void hist_task(float* Y, uint32_t sb, int w, int ch, int q, int& st, uint32_t& ph, int nd) {
    const int lane = threadIdx.x & 31, chl = w * 2 + (lane >> 4);
    const uint32_t ua = sb + 12288 + chl * 256 + ((lane >> 3) & 1) * 128 + (((lane & 7) ^ (chl & 7)) << 4);
    const uint32_t pa = sb + (w * 2 * PW + 16 + (lane >> 2) - 2 * (lane & 3)) * 4;
#pragma unroll
    for (int i = 0; i < 128; i++) Y[i] = 0;
    uint4 b1 = make_uint4(0, 0, 0, 0);
#pragma unroll 1
    for (int j = ch + 1; j >= 2; j--) {
        const uint4 b0 = b1;
        mbar_wait(sb + B_BAR + (BB_FULL + st) * 8, ph);
        b1 = ldsm4(ua + st * STG_B);
        if (j == 2) b1 = make_uint4(0, 0, 0, 0);
#pragma unroll
        for (int h = 0; h < 2; h++) {
            const uint32_t o = pa + st * STG_B + h * PW * 4;
            uint32_t lo = lds32(o - 32);
#pragma unroll
            for (int d = 0; d < 8; d++) {
                const uint32_t a0 = lds32(o + d * 64), a1 = lds32(o + d * 64 + 32);
                mma16(Y + (h * 16 + d) * 4, a0, a1, lo, a0, h ? b0.z : b0.x, h ? b0.w : b0.y);
                mma16(Y + (h * 16 + 8 + d) * 4, a0, a1, lo, a0, h ? b1.z : b1.x, h ? b1.w : b1.y);
                lo = a1;
            }
        }
        bar_sync(NB_WG + (w >> 2), 128);
        stage_release(sb, w, st);
        if (++st == NSTG) { st = 0; ph ^= 1; }
    }
    mbar_wait(sb + B_BAR + (BB_SF + (w >> 2)) * 8, (nd & 1) ^ 1);
#pragma unroll
    for (int h = 0; h < 2; h++) {
        const int o = ((ch * 16 + (q >> 1)) * 4 + (w & 1) * 2 + h) * 256 + ((q & 1) * 4 + (w >> 1)) * 32 + lane;
        float c0[4], n0[4], c1[4], n1[4];
        conv_combine(Y + h * 64, c0, n0); conv_combine(Y + h * 64 + 32, c1, n1);
        g_carry[0][o] = make_float4(c0[0], c0[1], c0[2], c0[3]);
        g_carry[0][o + 16384] = make_float4(c1[0] + n0[0], c1[1] + n0[1], c1[2] + n0[2], c1[3] + n0[3]);
        g_carry[1][o + 32768] = make_float4(n1[0], n1[1], n1[2], n1[3]);
    }
}

__device__ __forceinline__ void conv_task(const Params& p, float* Y, uint32_t sb, int w, int ch, int q, int ns, bool dry, int& st, uint32_t& ph, int nd) {
    const int tid = threadIdx.x, lane = tid & 31, g = lane >> 2, c = lane & 3;
    uint32_t dk[4];
    const uint32_t sg = (~ch & 2) << 30;
    int sr = st;
    float x[16];
    uint32_t rs[8];
    load_resid<2>(rs, 0, ch, w, 2 * q);
    PROF(tid == 128, 2048 + ch * 8);
#pragma unroll
    for (int i = 0; i < 128; i++) Y[i] = 0;
#pragma unroll 1
    for (int j = min(ch, 1 + (ch & 1)); j >= 1; j--) {
        mbar_wait(sb + B_BAR + (BB_FULL + st) * 8, ph);
        conv_stage(Y, sb + st * STG_B, sb + B_UT + ((ch - j) & 1) * 8192);
        if (++st == NSTG) { st = 0; ph ^= 1; }
    }
#pragma unroll 1
    for (int i = 0; i < min(ch, (ch & 1) ? 2 : 3); i++) {
        if (i) mbar_wait(sb + B_BAR + (BB_FULL + st) * 8, ph);
        const uint32_t ca = sb + (i ? st * STG_B : B_SP) + tid * 16;
#pragma unroll
        for (int k = 0; k < 4; k++) {
            const uint4 cr = lds128(ca + k * 4096);
            Y[k * 32] += __uint_as_float(cr.x); Y[k * 32 + 1] += __uint_as_float(cr.y); Y[k * 32 + 2] += __uint_as_float(cr.z); Y[k * 32 + 3] += __uint_as_float(cr.w);
        }
        if (i && ++st == NSTG) { st = 0; ph ^= 1; }
    }
    bar_sync(NB_C, 256);
#pragma unroll 1
    for (; sr != st; sr = (sr + 1) & (NSTG - 1)) stage_release(sb, w, sr);
    const uint32_t ut = sb + B_UT + (ch & 1) * 8192;
    mbar_wait(sb + B_BAR + (BB_SF + (w >> 2)) * 8, (nd & 1) ^ 1);
    mbar_wait(sb + B_BAR + (BB_SF + 1 - (w >> 2)) * 8, (nd & 1) ^ 1);
    PROF(tid == 128, 2048 + ch * 8 + 7);
    {
        uint4 v[2 * OPS1];
        wait_cnt_warp(cnt_ptr(C_OP0 + (q >> 3) * 2 + (w >> 2), ch + (w & 3) * 16), ns);
        part_load<OPS1>(v, 0, ch, w, 2 * q, ns);
        part_sum<OPS1>(x, v, rs);
        const float4 s = row_stats32(x);
        float2* dst = g_st2 + ((ch & 1) * 16 + q) * 128 + w * 16 + g + c * 8;
        asm volatile("{.reg .pred p; setp.ne.u32 p,%2,0; @p st.relaxed.gpu.global.b64 [%0],%1;}" ::"l"(dst),
                     "l"(((uint64_t)((__float_as_uint(c ? s.w : s.y) & 0x7fffffffu) | sg) << 32) | __float_as_uint(c ? s.z : s.x)), "r"((uint32_t)(c < 2 && !dry)) : "memory");
        PROF(tid == 128, 2048 + ch * 8 + 1);
    }
#pragma unroll
    for (int i = 0; i < 4; i++) asm volatile("ld.global.nc.u32 %0,[%1];" : "=r"(dk[i]) : "l"(p.Dskip + q * 32 + i * 8 + 2 * c));
    float2 ln0, ln1;
    {
        const float2* src = g_st2 + ((ch & 1) * 16 + (lane >> 4) * 8) * 128 + w * 16 + (lane & 15);
        uint64_t v[8];
        int n = 0;
#pragma unroll
        for (int i = 0; i < 8; i++) v[i] = (uint64_t)~sg << 32;
        while (true) {
            bool bad = false;
#pragma unroll
            for (int i = 0; i < 8; i++) asm volatile("{.reg .pred p; setp.lt.s32 p,%2,0; @p ld.relaxed.gpu.global.b64 %0,[%1];}" : "+l"(v[i]) : "l"(src + i * 128), "r"((uint32_t)(v[i] >> 32) ^ sg) : "memory");
#pragma unroll
            for (int i = 0; i < 8; i++) bad = bad || (int)((uint32_t)(v[i] >> 32) ^ sg) < 0;
            if (!__any_sync(0xffffffffu, bad && !dry)) break;
            if (++n > 2000000) __trap();
        }
        float sm = 0;
#pragma unroll
        for (int i = 0; i < 8; i++) sm += __uint_as_float((uint32_t)v[i]);
        sm += __shfl_xor_sync(0xffffffffu, sm, 16);
        const float mean = sm * (1.f / 512.f);
        float M2 = 0;
#pragma unroll
        for (int i = 0; i < 8; i++) { const float d = __uint_as_float((uint32_t)v[i]) * (1.f / 32.f) - mean; M2 += fabsf(__uint_as_float((uint32_t)(v[i] >> 32))) + 32.f * d * d; }
        M2 += __shfl_xor_sync(0xffffffffu, M2, 16);
        const float2 o = ln_finish(mean, M2 * (1.f / 512.f));
        ln0.x = __shfl_sync(0xffffffffu, o.x, g); ln0.y = __shfl_sync(0xffffffffu, o.y, g);
        ln1.x = __shfl_sync(0xffffffffu, o.x, g + 8); ln1.y = __shfl_sync(0xffffffffu, o.y, g + 8);
    }
    PROF(tid == 128, 2048 + ch * 8 + 2);
    uint32_t u[8];
#pragma unroll
    for (int i = 0; i < 8; i++) {
        const float2 l = (i & 1) ? ln1 : ln0;
        u[i] = pack2(__fdividef(rbf(x[2 * i] - l.x), l.y), __fdividef(rbf(x[2 * i + 1] - l.x), l.y));
        const int chl = (i >> 1) * 8 + g;
        sts32(ut + chl * 256 + (i & 1) * 128 + ((w ^ g) << 4) + c * 4, movm(u[i]));
    }
    bar_sync(NB_C, 256);
    mbar_wait(sb + B_BAR + (BB_FULL + st) * 8, ph);
    PROF(tid == 128, 2048 + ch * 8 + 3);
    conv_stage(Y, sb + st * STG_B, ut);
    uint32_t yp[4][2];
    float nxt[4][4];
    {
        float y[4][4];
#pragma unroll
        for (int k = 0; k < 4; k++) conv_combine(Y + k * 32, y[k], nxt[k]);
#pragma unroll
        for (int i = 0; i < 4; i++) { yp[i][0] = pack2(y[0][i], y[1][i]); yp[i][1] = pack2(y[2][i], y[3][i]); }
    }
#pragma unroll
    for (int i = 0; i < 4; i++) sts64(sb + B_YT + (16 * (2 * c + (i & 1)) + g + (i >> 1) * 8) * 80 + w * 8, yp[i][0], yp[i][1]);
    bar_sync(NB_C, 256);
    stage_release(sb, w, st);
    if (++st == NSTG) { st = 0; ph ^= 1; }
    PROF(tid == 128, 2048 + ch * 8 + 4);
    uint32_t xo[8];
    uint32_t* dA = (uint32_t*)(g_xA[1] + (ch * 8 + (q >> 1)) * 1024 + (w * 2) * 64 + (q & 1) * 32) + lane;
#pragma unroll
    for (int i = 0; i < 8; i++) {
        const int col = (i >> 1) * 8 + 2 * c;
        const uint32_t yv = lds32(sb + B_YT + (w * 16 + g + (i & 1) * 8) * 80 + col * 2);
        const uint32_t dv = dk[i >> 1];
        x[2 * i] = rbf(x[2 * i] + rbf(blo(yv) + rbf(blo(u[i]) * blo(dv))));
        x[2 * i + 1] = rbf(x[2 * i + 1] + rbf(bhi(yv) + rbf(bhi(u[i]) * bhi(dv))));
        xo[i] = pack2(x[2 * i], x[2 * i + 1]);
        dA[(i >> 1) * 32 + (i & 1) * 256] = xo[i];
    }
    {
        const float4 s = row_stats32(x);
        float2* dst = g_st[1] + (ch * 16 + q) * 128 + w * 16 + g;
        if (c == 0) dst[0] = make_float2(s.x, s.y);
        if (c == 1) dst[8] = make_float2(s.z, s.w);
        __syncwarp();
    }
    PROF(tid == 128, 2048 + ch * 8 + 5);
    mbar_arrive1(sb + B_BAR + (BB_DONE + (w >> 2)) * 8);
    bar_sync(NB_C, 256);
#pragma unroll
    for (int k = 0; k < 4; k++) sts128(sb + B_SP + k * 4096 + tid * 16, __float_as_uint(nxt[k][0]), __float_as_uint(nxt[k][1]), __float_as_uint(nxt[k][2]), __float_as_uint(nxt[k][3]));
    PROF(tid == 128, 2048 + ch * 8 + 6);
}

__device__ __forceinline__ void out_store(const Params& p, const float* x, int ch, int cb) {
    const int lane = threadIdx.x & 31, w = threadIdx.x >> 5, g = lane >> 2, c = lane & 3;
#pragma unroll
    for (int h = 0; h < 2; h++) {
        const float* y = x + h * 2;
        uint32_t v0 = pack2(y[0], y[1]), v1 = pack2(y[4], y[5]), v2 = pack2(y[8], y[9]), v3 = pack2(y[12], y[13]);
        uint32_t t0 = (c & 1) ? v0 : v1, t1 = (c & 1) ? v2 : v3;
        t0 = __shfl_xor_sync(0xffffffffu, t0, 1); t1 = __shfl_xor_sync(0xffffffffu, t1, 1);
        if (c & 1) { v0 = t0; v2 = t1; } else { v1 = t0; v3 = t1; }
        t0 = (c & 2) ? v0 : v2; t1 = (c & 2) ? v1 : v3;
        t0 = __shfl_xor_sync(0xffffffffu, t0, 2); t1 = __shfl_xor_sync(0xffffffffu, t1, 2);
        if (c & 2) { v0 = t0; v1 = t1; } else { v2 = t0; v3 = t1; }
        stg128((uint4*)(p.out + (size_t)(ch * 128 + w * 16 + g + h * 8) * 512 + cb * 16 + c * 8), make_uint4(v0, v1, v2, v3), POL_LATE);
    }
}
__device__ __forceinline__ void fin_task(const Params& p, int ch, int cb0, int ncb, int ns, bool dry) {
    const int w = threadIdx.x >> 5;
    uint32_t rs[8];
    wait_cnt_warp(cnt_ptr(C_CV, ch), dry ? 0 : 32);
    load_resid<2>(rs, 1, ch, w, cb0);
    wait_cnt_warp(cnt_ptr(C_OP1, ch), dry ? 0 : 256);
    for (int cb = cb0; cb < cb0 + ncb; cb += 2) {
        float x[16];
        if (cb != cb0) load_resid<2>(rs, 1, ch, w, cb);
        uint4 v[32];
        part_load<16>(v, 1, ch, w, cb, ns);
        part_sum<16>(x, v, rs);
        out_store(p, x, ch, cb);
    }
}

__device__ __forceinline__ void bulk_consumer(const Params& p, uint32_t sb, int cl, uint32_t rank, int w) {
    int st = 0; uint32_t ph = 0; int nd = 0, ng = 0;
    for (int ti = 0; ti < MAXT; ti++) {
        const Task t = task_of(p.task[cl][ti], rank);
        const int type = t.type, layer = t.layer, ch = t.ch;
        if (type == T_END) break;
        bool staged = type != T_FIN;
        PROF(threadIdx.x == 0, 3600 + ti * 4);
        if (type <= T_OP) {
            CPROF(0);
            if ((w >> 2) && type == T_OP) mbar_wait(sb + B_BAR + BB_GO * 8, ng & 1);
            ng++;
            CPROF(1);
        }
        if (type == T_QKV) {
            staged = false;
            #pragma unroll 1
            while (st) {
                if (!(w & 3)) { mbar_wait(sb + B_BAR + (BB_FULL + st) * 8, ph); stage_release(sb, 0, st); stage_release(sb, 1, st); }
                if (++st == NSTG) { st = 0; ph ^= 1; }
            }
            qkv_task(sb, w, layer, t.b, ng, nd, ph);
            PROF(threadIdx.x == 128, 3600 + ti * 4 + 1);
        } else if (type == T_OP) {
            const int lane = threadIdx.x & 31;
            float acc[128];
            uint32_t r0 = sb + B_BAR + BB_IDLE * 8, r1 = r0;
            gemm_run<false>(acc, sb, w, 0, 1, r0, r1, st, ph);
            gemm_run<true>(acc, sb, w, 1, 2 * t.b, r0, r1, st, ph);
            mbar_wait(sb + B_BAR + (BB_SF + (w >> 2)) * 8, (nd & 1) ^ 1);
            wg_wait<1>();
            mbar_arrive1_cluster(r0);
            wg_wait<0>();
            mbar_arrive1_cluster(r1);
            PROF(threadIdx.x == 128, 3600 + ti * 4 + 1);
            if (t.c & 32) {
                staged = false;
#pragma unroll
                for (int j = 0; j < 16; j += 4) {
                    uint32_t rs[16];
                    load_resid<4>(rs, 1, ch, w, (t.blk & 4) * 4 + j);
#pragma unroll
                    for (int i = 0; i < 16; i++) { float* y = acc + j * 8 + 2 * i; y[0] = rbf(y[0]) + blo(rs[i]); y[1] = rbf(y[1]) + bhi(rs[i]); }
                    out_store(p, acc + j * 8, ch, (t.blk & 4) * 4 + j); out_store(p, acc + j * 8 + 16, ch, (t.blk & 4) * 4 + j + 2);
                }
            } else if (!layer) {
                const int s2 = st + (w >> 1);
                const uint32_t o = sb + (s2 & (NSTG - 1)) * STG_B + (w & 1) * 8192 + lane * 16;
                mbar_wait(sb + B_BAR + (BB_FULL + (s2 & (NSTG - 1))) * 8, ph ^ (s2 >= NSTG));
#pragma unroll
                for (int j = 0; j < 16; j++)
                    sts128(o + j * 512, pack2(acc[j * 8], acc[j * 8 + 1]), pack2(acc[j * 8 + 2], acc[j * 8 + 3]), pack2(acc[j * 8 + 4], acc[j * 8 + 5]), pack2(acc[j * 8 + 6], acc[j * 8 + 7]));
                sts32(sb + B_ST + (w >> 2) * 4, st);
                st += 4;
                if (st >= NSTG) { st -= NSTG; ph ^= 1; }
            } else {
                uint4* dst = op_dst(layer, ch, t.c & 15, w, (t.blk >> 2) & 1) + lane;
#pragma unroll
                for (int n = 0; n < 16; n++) {
                    const int j = (n >> 1) + (n & 1) * 8;
                    const uint4 v = make_uint4(pack2(acc[j * 8], acc[j * 8 + 1]), pack2(acc[j * 8 + 2], acc[j * 8 + 3]), pack2(acc[j * 8 + 4], acc[j * 8 + 5]), pack2(acc[j * 8 + 6], acc[j * 8 + 7]));
                    if (j < 16 - NSB) stg128(dst + j * 32, v, out_pol(T_OP, layer, ch)); else sts128(sb + B_OUT + (w * NSB + j - (16 - NSB)) * 512 + lane * 16, v.x, v.y, v.z, v.w);
                }
            }
        } else if (type == T_CV) {
            float acc[128];
            if (layer) hist_task(acc, sb, w, ch, t.a + rank, st, ph, nd);
            else { conv_task(p, acc, sb, w, ch, t.a + rank, t.b, t.dry, st, ph, nd); staged = false; nd++; }
        } else {
            fin_task(p, ch, t.a + rank * t.c, t.c, t.b, t.dry);
        }
        if (staged) {
            __syncwarp();
            mbar_arrive1(sb + B_BAR + (BB_DONE + (w >> 2)) * 8);
            nd++;
        }
        CPROF(6);
        PROF(threadIdx.x == 128, 3600 + ti * 4 + 2);
        __syncwarp();
    }
}

constexpr int P_Y = 131072  , P_PRM = P_Y  , P_K6 = P_PRM + 8192  ,
              P_P = P_Y + 40960  , P_U = P_P + 33280  , P_END = P_U + 17408, P_X = 98304  ;
static_assert(P_END <= B_BAR && P_END <= R_BAR, "prologue scratch");
#define KGUN 2
constexpr int KGU = KGUN;
__device__ __forceinline__ void csq(float& r, float& i) { const float t = r * i; r = fmaf(r, r, -(i * i)); i = t + t; }
__device__ __forceinline__ void cpow(float ar, float ph, float p, float& r, float& i) {
    const float e = ex2(ar * p);
    const float u = ph * p, n = fabsf(u) < 4194304.f ? (u + 12582912.f) - 12582912.f : u;
    const float t = (u - n) * 6.283185307179586f;
    r = e * __cosf(t); i = e * __sinf(t);
}
__device__ __forceinline__ void mma_tf32(float* c, float a0, float a1, float a2, float a3, float b0, float b1) {
    asm volatile("mma.sync.aligned.m16n8k8.row.col.f32.tf32.tf32.f32 {%0,%1,%2,%3},{%4,%5,%6,%7},{%8,%9},{%0,%1,%2,%3};"
                 : "+f"(c[0]), "+f"(c[1]), "+f"(c[2]), "+f"(c[3])
                 : "r"(__float_as_uint(a0)), "r"(__float_as_uint(a1)), "r"(__float_as_uint(a2)), "r"(__float_as_uint(a3)), "r"(__float_as_uint(b0)), "r"(__float_as_uint(b1)));
}

struct ProRegs { uint32_t v[2][4], ldt[2]; };
__device__ __forceinline__ void prologue_load(const ProArgs& a, int b, ProRegs& pr) {
    const int w = threadIdx.x >> 5;
#pragma unroll
    for (int i = 0; i < 2; i++) {
        const int gi = b * 512 + (w & 3) * 128 + ((w >> 2) & 1) * 64 + i * 32 + (threadIdx.x & 31);
        pr.ldt[i] = __ldg((const uint16_t*)a.ldt + b * 4 + (w & 3));
        pr.v[i][0] = __ldg((const uint16_t*)a.lAr + gi); pr.v[i][1] = __ldg((const uint16_t*)a.Ai + gi);
        pr.v[i][2] = __ldg((const uint16_t*)a.Cr + gi); pr.v[i][3] = __ldg((const uint16_t*)a.Ci + gi);
    }
}
__device__ __forceinline__ void prologue(const ProArgs& a, uint32_t sb, int b, int w, const ProRegs& pr) {
    const int tid = threadIdx.x, lane = tid & 31, g = lane >> 2, c = lane & 3;
    const int d0 = b * 4;
    if (w >= 8) {
        const int t2 = tid - 256;
        if (w < 10) {
            const int row = b * 16 + (w - 8) * 8 + g;
            const float2 r = row_stats512((const uint4*)(a.x + (size_t)row * 512) + c, 8, 4);
            const float2 l = ln_finish(r.x * (1.f / 512.f), fmaxf(r.y - r.x * r.x * (1.f / 512.f), 0.f) * (1.f / 512.f));
            if (c == (g >> 1)) asm volatile("st.relaxed.gpu.global.u32 [%0],%1;" ::"l"(g_ln0 + row), "r"(pack2(l.x, l.y)) : "memory");
        }
        PROF(t2 == 0, 3516);
        const int gi = b * 128 + t2;
        if (t2 < 32) acc_init(a.mem0, b * 32 + t2);
        if (t2 >= 112) ((uint4*)g_st2)[b * 16 + t2 - 112] = make_uint4(0, 0, 0, 0);
        if (gi < 13 * 64) g_cnt[gi] = 0;
        bar_sync(6, 384);
        if (gi < 256) g_st[0][(gi >> 7) * 2048 + (lds32(sb + S_TAG) ^ 1) * 128 + (gi & 127)] = make_float2(0.f, 0.f);
        asm volatile("{.reg .pred p; elect.sync _|p,0xffffffff; @p cp.async.bulk.prefetch.L2.global [%0],32768;}"
                     ::"l"((w == 8 ? a.Wq : w == 9 ? a.Wk : w == 10 ? a.Wv : a.Wo) + (size_t)b * 16384) : "memory");
        mbar_wait(sb + S_XBAR, 0);
#pragma unroll 1
        for (int h = 0; h < 2; h++) {
            uint32_t l[8];
            int n = 0;
            while (true) {
                bool ok = true;
#pragma unroll
                for (int i = 0; i < 8; i++) asm volatile("ld.relaxed.gpu.global.u32 %0,[%1];" : "=r"(l[i]) : "l"(g_ln0 + h * 1024 + i * 128 + t2) : "memory");
#pragma unroll
                for (int i = 0; i < 8; i++) ok = ok && l[i];
                if (__all_sync(0xffffffffu, ok)) break;
                if (++n > 2000000) __trap();
            }
#pragma unroll
            for (int i = 0; i < 8; i++) {
                const int t = h * 1024 + i * 128 + t2;
                const uint2 x = lds64(sb + P_X + t * 16 + (b & 1) * 8);
                const float m = blo(l[i]), rs = rcp(bhi(l[i]));
                const uint32_t u0 = pack2(rbf(blo(x.x) - m) * rs, rbf(bhi(x.x) - m) * rs), u1 = pack2(rbf(blo(x.y) - m) * rs, rbf(bhi(x.y) - m) * rs);
                sts128(sb + P_X + t * 16, x.x, x.y, u0, u1);
                const uint32_t o = sb + P_U + ((t >> 3) & 1) * 2176 + ((t >> 4) + 8) * 16 + (t & 7) * 2;
                asm volatile("st.shared.u16 [%0],%1;" ::"r"(o), "h"((uint16_t)u0) : "memory");
                asm volatile("st.shared.u16 [%0],%1;" ::"r"(o + 4352), "h"((uint16_t)(u0 >> 16)) : "memory");
                asm volatile("st.shared.u16 [%0],%1;" ::"r"(o + 8704), "h"((uint16_t)u1) : "memory");
                asm volatile("st.shared.u16 [%0],%1;" ::"r"(o + 13056), "h"((uint16_t)(u1 >> 16)) : "memory");
            }
        }
        PROF(t2 == 0, 3517);
        bar_sync(9, 384);
        fence_async_smem();
#pragma unroll 1
        for (int j = 0; j < 16; j++) {
            const int d = d0 + w - 8;
            asm volatile("{.reg .pred p; elect.sync _|p,0xffffffff; @p cp.async.bulk.global.shared::cta.bulk_group [%0],[%1],%2;}" ::"l"(g_P + (((d >> 5) * 16 + j) * 32 + (d & 31)) * PW),
                         "r"(sb + P_P + ((w - 8) * 2080 + j * 128) * 4), "r"(PW * 4) : "memory");
        }
        asm volatile("cp.async.bulk.commit_group; cp.async.bulk.wait_group 0;" ::: "memory");
        bar_arrive(10, 384);
        return;
    }
#pragma unroll
    for (int i = 0; i < 2; i++) {
        const float dt = rbf(expf(blo(pr.ldt[i])));
        const float ar = -rbf(expf(blo(pr.v[i][0]))) * dt, ai = blo(pr.v[i][1]) * dt;
        sts128(sb + P_PRM + (w * 64 + i * 32 + lane) * 16, __float_as_uint(ar * 1.4426950408889634f), __float_as_uint(ai * 0.15915494309189535f),
               __float_as_uint(2.f * (blo(pr.v[i][2]) * dt)), __float_as_uint(2.f * (blo(pr.v[i][3]) * dt)));
    }
    if (tid < 64) sts128(sb + P_U + (tid >> 3) * 2176 + (tid & 7) * 16, 0, 0, 0, 0);
    bar_arrive(6, 384);
    __syncwarp();
    PROF(tid == 0, 3510);
    const int ch = w & 3, hf = w >> 2;
    {
        float k0[4] = {0, 0, 0, 0}, k1[4] = {0, 0, 0, 0}, k2[4] = {0, 0, 0, 0}, k3[4] = {0, 0, 0, 0}, k4[4] = {0, 0, 0, 0}, kl = 0;
#pragma unroll KGU
        for (int j = 0; j < 16; j++) {
            const uint4 q = lds128(sb + P_PRM + (w * 64 + j * 4 + c) * 16);
            const float cr = __uint_as_float(q.z), ci = __uint_as_float(q.w);
            float wr[4], wi[4], vr[4], vi[4];
            cpow(__uint_as_float(q.x), __uint_as_float(q.y), (float)g, wr[0], wi[0]);
            cpow(__uint_as_float(q.x), __uint_as_float(q.y), (float)(g + 8), vr[0], vi[0]);
#pragma unroll
            for (int i = 1; i < 4; i++) { wr[i] = wr[i - 1]; wi[i] = wi[i - 1]; csq(wr[i], wi[i]); vr[i] = vr[i - 1]; vi[i] = vi[i - 1]; csq(vr[i], vi[i]); }
            float hr = wr[3], hi = wi[3];
            csq(hr, hi);
            mma_tf32(k0, wr[0], vr[0], wi[0], vi[0], cr * hr - ci * hi, -(cr * hi + ci * hr));
            hr = vr[3]; hi = vi[3]; csq(hr, hi);
            mma_tf32(k1, wr[0], vr[0], wi[0], vi[0], cr * hr - ci * hi, -(cr * hi + ci * hr));
            csq(hr, hi);
            mma_tf32(k2, wr[1], vr[1], wi[1], vi[1], cr * hr - ci * hi, -(cr * hi + ci * hr));
            csq(hr, hi);
            mma_tf32(k3, wr[2], vr[2], wi[2], vi[2], cr * hr - ci * hi, -(cr * hi + ci * hr));
            csq(hr, hi);
            mma_tf32(k4, wr[3], vr[3], wi[3], vi[3], cr * hr - ci * hi, -(cr * hi + ci * hr));
            csq(hr, hi);
            kl += cr * hr - ci * hi;
        }
        kl += __shfl_xor_sync(0xffffffffu, kl, 1); kl += __shfl_xor_sync(0xffffffffu, kl, 2);
        const uint32_t o = sb + P_K6 + (ch * 656 + c * 32 + g) * 4, ol = sb + P_K6 + (ch * 656 + 640) * 4;
#define KST(k, base) sts32(o + (base) * 4, __float_as_uint(k[0])); sts32(o + (base) * 4 + 64, __float_as_uint(k[1])); \
                     sts32(o + (base) * 4 + 32, __float_as_uint(k[2])); sts32(o + (base) * 4 + 96, __float_as_uint(k[3]))
#define KAD(k, base) k[0] += __uint_as_float(lds32(o + (base) * 4)); k[1] += __uint_as_float(lds32(o + (base) * 4 + 64)); \
                     k[2] += __uint_as_float(lds32(o + (base) * 4 + 32)); k[3] += __uint_as_float(lds32(o + (base) * 4 + 96))
        if (hf == 0) {
            bar_sync(2 + ch, 64);
            KAD(k0, 0); KAD(k1, 128); KAD(k2, 256); KAD(k3, 384); KAD(k4, 512);
            kl += __uint_as_float(lds32(ol));
            __syncwarp();
        }
        KST(k0, 0); KST(k1, 128); KST(k2, 256); KST(k3, 384); KST(k4, 512);
        if (lane == 0) sts32(ol, __float_as_uint(kl));
        if (hf == 1) { __syncwarp(); bar_arrive(2 + ch, 64); }
    }
    PROF(tid == 0, 3511);
    bar_sync(8, 384);
    PROF(tid == 0, 3512);
    if (tid < 64) sts32(sb + P_P + ((tid >> 4) * 2080 + (tid & 15)) * 4, 0);
#pragma unroll 1
    for (int x = tid; x < 2048; x += 512) {
        uint32_t pw[2][4];
#pragma unroll
        for (int h = 0; h < 2; h++) {
            const int y = x + h * 256;
            const int i0 = y <= 256 ? y : 256 + (int)((pack2((float)y, 0.f) & 0xffff) - 0x4380);
            const int i1 = y <= 256 ? max(y - 1, 0) : 256 + (int)((pack2((float)(y - 1), 0.f) & 0xffff) - 0x4380);
#pragma unroll
            for (int k = 0; k < 4; k++) {
                const float lo = __uint_as_float(lds32(sb + P_K6 + k * 2624 + i0 * 4)), hi = __uint_as_float(lds32(sb + P_K6 + k * 2624 + i1 * 4));
                pw[h][k] = pack2(lo, y ? hi : 0.f);
            }
        }
#pragma unroll
        for (int h = 0; h < 2; h++)
#pragma unroll
            for (int k = 0; k < 4; k++) sts32(sb + P_P + (k * 2080 + x + h * 256 + 16) * 4, pw[h][k]);
    }
    bar_sync(9, 384);
    PROF(tid == 0, 3513);
    {
        float acc[16][4];
#pragma unroll
        for (int j = 0; j < 16; j++) acc[j][0] = acc[j][1] = acc[j][2] = acc[j][3] = 0;
#pragma unroll 1
        for (int e = hf * 4; e < hf * 4 + 4; e++) {
            uint32_t B[16][2];
            const uint32_t ua = sb + P_U + ch * 4352 + ((lane >> 3) & 1) * 2176 + (8 + (lane >> 4) * 8 + (lane & 7) - e) * 16;
#pragma unroll
            for (int j = 0; j < 8; j++) { const uint4 v = ldsm4(ua + j * 256); B[2 * j][0] = v.x; B[2 * j][1] = v.y; B[2 * j + 1][0] = v.z; B[2 * j + 1][1] = v.w; }
            const uint32_t pa = sb + P_P + (ch * 2080 + 16 + e * 16 + g - 2 * c) * 4;
#pragma unroll
            for (int d = 0; d < 16; d++) {
                const uint32_t a0 = lds32(pa + d * 512), a1 = lds32(pa + d * 512 + 32), a2 = lds32(pa + d * 512 - 32);
#pragma unroll
                for (int j = d; j < 16; j++) mma16(acc[j], a0, a1, a2, a0, B[j - d][0], B[j - d][1]);
            }
        }
        PROF(tid == 0, 3514);
        const uint32_t o = sb + P_Y + (ch * 2560 + c * 40 + g) * 4;
#pragma unroll
        for (int j = 0; j < 8; j++) {
#pragma unroll
            for (int i = 0; i < 4; i++) { const float lo = acc[j][i], hi = acc[j + 8][i]; acc[j][i] = hf ? hi : lo; sts32(o + (j + 8 - hf * 8) * 640 + (i & 1) * 80 + (i >> 1) * 32, __float_as_uint(hf ? lo : hi)); }
        }
        bar_sync(2 + ch, 64);
#pragma unroll
        for (int j = 0; j < 8; j++) {
#pragma unroll
            for (int i = 0; i < 4; i++) acc[j][i] += __uint_as_float(lds32(o + (j + hf * 8) * 640 + (i & 1) * 80 + (i >> 1) * 32));
        }
#pragma unroll
        for (int j = 0; j < 8; j++) {
#pragma unroll
            for (int i = 0; i < 4; i++) sts32(o + (j + hf * 8) * 640 + (i & 1) * 80 + (i >> 1) * 32, __float_as_uint(acc[j][i]));
        }
    }
    const uint2 dk = __ldg((const uint2*)(a.Dk + d0));
    bar_sync(1, 256);
#pragma unroll 2
    for (int i = 0; i < 8; i++) {
        const int t = i * 256 + tid;
        const uint32_t o = sb + P_Y + (t + 4 * (t >> 4)) * 4;
        const uint4 xu = lds128(sb + P_X + t * 16);
        float y[4];
#pragma unroll
        for (int k = 0; k < 4; k++) y[k] = rbf(__uint_as_float(lds32(o + k * 10240)));
        uint2 r;
        r.x = pack2(blo(xu.x) + rbf(y[0] + rbf(blo(xu.z) * blo(dk.x))), bhi(xu.x) + rbf(y[1] + rbf(bhi(xu.z) * bhi(dk.x))));
        r.y = pack2(blo(xu.y) + rbf(y[2] + rbf(blo(xu.w) * blo(dk.y))), bhi(xu.y) + rbf(y[3] + rbf(bhi(xu.w) * bhi(dk.y))));
        ((uint2*)(g_xA[0] + ((t >> 7) * 8 + (d0 >> 6)) * 1024 + ((t & 127) >> 3) * 64 + ((d0 & 63) >> 3) * 8 + (t & 7)))[(d0 >> 2) & 1] = r;
        if (i == 0) {
            const float e0 = blo(r.x), e1 = bhi(r.x), e2 = blo(r.y), e3 = bhi(r.y);
            asm volatile("red.relaxed.gpu.global.add.v2.f32 [%0],{%1,%2};" ::"l"(g_st[0] + (t >> 7) * 2048 + lds32(sb + S_TAG) * 128 + (t & 127)),
                         "f"((e0 + e1) + (e2 + e3)), "f"((e0 * e0 + e1 * e1) + (e2 * e2 + e3 * e3)) : "memory");
        }
    }
    PROF(tid == 0, 3515);
    bar_sync(10, 384);
}

__global__ void __cluster_dims__(2, 1, 1) __launch_bounds__(384, 1) main_kernel(const __grid_constant__ Params p) {
    extern __shared__ __align__(1024) uint8_t smem[];
    const uint32_t sb = __shfl_sync(0xffffffffu, smem_u32(smem), 0);
    uint32_t rank; asm("mov.u32 %0,%%cluster_ctarank;" : "=r"(rank));
    const int wi = __shfl_sync(0xffffffffu, threadIdx.x >> 5, 0);
    const int cl = blockIdx.x >> 1, wg = wi >> 2;
    const bool rec = p.rec0 >= 0 && cl >= p.rec0 && cl < p.rec0 + 32;
    PROF(threadIdx.x == 0, 3500);
    ProRegs pr;
    prologue_load(p.pa, max((int)blockIdx.x - 4, 0), pr);
    if (rec) rec_init(p, sb, cl - p.rec0, rank); else bulk_init(sb);
    if (threadIdx.x == 352 && p.dopro && cl >= 2) {
        mbar_init(sb + S_XBAR, 1);
        asm volatile("fence.mbarrier_init.release.cluster;" ::: "memory");
        mbar_expect(sb + S_XBAR, 32768);
        for (int j = 0; j < 8; j++) tma2d(sb + P_X + j * 4096, &p.tm[3], ((blockIdx.x - 4) >> 1) * 8, j * 256, sb + S_XBAR);
    }
    if (threadIdx.x == 320) {
        unsigned v;
        asm volatile("ld.relaxed.gpu.global.u32 %0,[%1];" : "=r"(v) : "l"(g_gate) : "memory");
        v = v / (4 * NCL) + p.dopro;
        sts64(sb + S_GATE, v * (4 * NCL), v & 1);
    }
    __syncwarp();
    asm volatile("barrier.cluster.arrive.relaxed.aligned;" ::: "memory");
    if (wg == 2) bar_arrive(8, 384);
    if (p.dopro && cl >= 2) prologue(p.pa, sb, blockIdx.x - 4, wi, pr); else if (wg < 2) bar_sync(8, 384);
    asm volatile("barrier.cluster.wait.aligned;" ::: "memory");
    fence_async_smem();
    bar_sync(wg == 2 ? 7 : 1, wg == 2 ? 128 : 256);
    if (p.dopro && (threadIdx.x == 32 || threadIdx.x == 352)) red_release(g_gate, 1);
    if (rec) {
        if (threadIdx.x == 0) {
            rec_fetch(&p.tm[1], sb + R_STK, (cl - p.rec0) * 128, rank * 256, 2, sb + R_BAR + RB_INIT * 8);
            rec_fetch(&p.tm[2], sb + R_STV, (cl - p.rec0) * 128, rank * 256, 2, sb + R_BAR + RB_INIT * 8);
        }
    }
    PROF(threadIdx.x == 0, 3506);
    __syncwarp();
    if (rec) {
        const int head = cl - p.rec0;
        if (wg == 2) {
            reg_dec<RH>();
            const int w = wi & 3;
            if (threadIdx.x == 256) rec_fetch(&p.tm[0], sb + R_STQ, head * 128, rank * 256, 2, sb + R_BAR + RB_INIT * 8);
            __syncwarp();
            wait_cnt_warp(g_gate, lds32(sb + S_GATE));
            if (p.dostats) x1_stats((head * 2 + rank) * 4 + w, lds32(sb + S_TAG));
            __syncthreads();
            cluster_sync();
            if ((p.chains >> (w >> 1)) & 1) rec_attn(p, sb, w >> 1, w & 1, head, rank);
        } else {
            reg_inc<RW0>();
            rec_weights(p, sb, head, rank, wi);
        }
    } else {
        if (wg == 2) {
            reg_dec<40>();
            const int w = wi & 3;
            if (w == 0) bulk_producer(p, sb, cl, rank); else if (w >= 2) bulk_release(p, sb, cl, rank, w - 2);
        } else { reg_inc<232>(); bulk_consumer(p, sb, cl, rank, wi); }
    }
    __syncwarp();
    cluster_sync();
}

typedef CUresult (*EncFn)(CUtensorMap*, CUtensorMapDataType, cuuint32_t, void*, const cuuint64_t*, const cuuint64_t*, const cuuint32_t*, const cuuint32_t*,
                          CUtensorMapInterleave, CUtensorMapSwizzle, CUtensorMapL2promotion, CUtensorMapFloatOOBfill);
inline uint32_t mk(int type, int layer, int ch, int a, int b, int c) { return type | (layer << 3) | (ch << 4) | (a << 8) | (b << 16) | ((uint32_t)c << 24); }
constexpr int SMEM_BYTES = 232448;

struct Sched {
    Params* P; int n[NCL];
    void clear() { memset(P->task, 0, sizeof(P->task)); memset(n, 0, sizeof(n)); }
    void add(int cl, uint32_t t) { if (n[cl] < MAXT - 1) P->task[cl][n[cl]++] = t; }
};

constexpr int REC0 = 4;
struct Cfg { int LAG, TS1, TS2, DQU, DQO, DUN, DHN, MARG, NQ1, FAST0, n0, oc, fc, nuns, ns2, nhg, hs, osl; };
#define PLAN 14, 2300, 2950, 2420, 1600, 5800, 380, 3000, 4, 1, 8, 10, 12, 3, 4, 8, 6000, 1000
Cfg g_cfg = {PLAN};
double g_est;
bool g_planned = false;
struct Plan { uint32_t w[NCL][MAXT]; int n[NCL]; double end, rec; };
void simulate(Plan& L, int nc, const Cfg& C) {
    const int LAG = C.LAG, NQ1 = C.NQ1, FAST0 = C.FAST0, n0 = C.n0, oc = C.oc, fc = C.fc, nuns = C.nuns, ns2 = C.ns2, nhg = C.nhg;
    const double TS1 = C.TS1, TS2 = C.TS2, DQU = C.DQU, DQO = C.DQO, DUN = C.DUN, DHN = C.DHN, MARG = C.MARG, hs = C.hs;
    const double INF = 1e18, DKB = 600, DOV = 700, DH = DHN, DHO = 1100, DF = 2200, DFB = 200, POLL = 450, FILL = 500, PUB = 600;
    enum { Q0, O0, Q1, HB, O1, FI, NK };
    struct Grp { int n, left; double done; } G[NK][16];
    double fr[NCL], it[100] = {}, cv[16];
    int ns[16], last[2][NCL], uc = 0, nit = 0;
    memset(L.n, 0, sizeof(L.n)); L.end = 0;
    auto fast = [&](int c) { return c < FAST0 || c >= fc; };
    for (int c = 0; c < 16; c++) {
        ns[c] = c < nuns ? 1 : c == 15 ? 16 : c == 14 ? 8 : ns2;
        const int cnt[NK] = {c < 2 ? 48 : (c & 1) ? 0 : 96, c < oc ? 8 : OPS1, c == 15 ? 24 : fast(c) ? 16 : 48 / NQ1, c >= 2 && !(c & 1) ? 16 : 0, ns[c], ns[c] == 1 ? 0 : c >= 14 ? 8 : 4};
        for (int k = 0; k < NK; k++) G[k][c] = {cnt[k], cnt[k], 0};
        cv[c] = INF;
    }
    for (int i = 0; i < nc; i++) { fr[i] = 0; last[0][i] = last[1][i] = -1; }
    auto fin = [&](int k, int c) { if ((k == Q0 && c >= 2) || k == HB) c &= ~1; return G[k][c].left ? INF : G[k][c].done; };
    auto len = [&](int i) { return (i >= LAG && i < 64) ? (double)TS2 : (double)TS1; };
    auto end_it = [&](int i) { return i < nit ? it[i] + len(i) : INF; };
    auto nominal = [&](int i) { if (i < nit) return it[i]; double t = nit ? it[nit - 1] : 11000 - TS1; for (int j = nit - 1; j < i; j++) t += len(j); return t; };
    auto put = [&](int i, uint32_t w) { if (L.n[i] < MAXT - 4) L.w[i][L.n[i]++] = w; else L.end = INF; };
    auto rel = [&](int k, int c) {
        switch (k) {
            case Q0: return 0.0;
            case O0: return end_it(4 * c + 3) + PUB + POLL;
            case Q1: return cv[c] + POLL;
            case HB: return cv[c - 2] + 600 + POLL;
            case O1: return end_it(LAG + 4 * c + 3) + PUB + POLL;
            default: return fin(O1, c) + POLL;
        }
    };
    auto dur = [&](int k, int c) {
        switch (k) {
            case Q0: return DQO + (c < 2 ? 2.0 : 1.0) * DQU;
            case O0: return (16 - G[O0][c].n) * DKB + 1200;
            case HB: return DHO + DH * c;
            case Q1: return DQO + 48.0 / G[Q1][c].n * DQU;
            case O1: return DOV + DKB * 64 / ns[c] + (ns[c] == 1 ? 1500 : 0);
            default: return DF + DFB * ns[c] * (c >= 14 ? 0.5 : 1);
        }
    };
    auto o0_est = [&](int c) {
        double t = uc ? cv[uc - 1] - 900 : 0;
        for (int j = uc; j < c; j++) t = fmax(t, nominal(4 * j + 4) + PUB + POLL + FILL) + dur(O0, j) + DUN;
        return fmax(t, nominal(4 * c + 4) + PUB + POLL);
    };
    auto cv_est = [&](int c) { return c < uc ? cv[c] : o0_est(c) + FILL + dur(O0, c) + DUN + 900; };
    auto slot = [&](int k, int c, int i) { return k == O0 ? (i < 8 ? i : nc + 7 - i) : c == 15 ? i : i - 8; };
    while (true) {
        while (nit < 64 + LAG) {
            double t = nit ? end_it(nit - 1) : 0;
            if (nit < 64) t = fmax(t, fin(Q0, nit >> 2) + POLL);
            if (nit >= LAG) t = fmax(t, fin(Q1, (nit - LAG) >> 2) + (nit < 64 ? 0 : POLL));
            if (t >= INF) break;
            it[nit++] = t;
        }
        int i = -1;
        for (int j = 0; j < nc; j++) if (fr[j] < INF && (i < 0 || fr[j] < fr[i])) i = j;
        if (i < 0) break;
        const double t = fr[i];
        double lim = INF;
        if (i < 8 && last[0][i] == uc) {
            if (G[O0][uc].left || fin(HB, uc) >= INF) { fr[i] = t + 200; continue; }
            const double e = fmax(G[O0][uc].done, fin(HB, uc) - 2000) + DUN;
            for (int j = 0; j < 8; j++) { put(j, mk(T_CV, 0, uc, 2 * j, G[O0][uc].n, 0)); fr[j] = e; }
            cv[uc++] = e + 900;
            continue;
        }
        const bool hg = (unsigned)(i - 24) < (unsigned)nhg;
        double hlim = INF;
        for (int c = 2; c < 16 && hg; c++) if (G[HB][c].left) { hlim = cv_est(c - 2) + hs; break; }
        int mine[2] = {-1, -1};
        for (int k = 0; k < 2; k++)
            for (int c = last[k][i] + 1; c < 16 && mine[k] < 0; c++) if ((unsigned)slot(O0 + k, c, i) < (unsigned)G[O0 + k][c].n) mine[k] = c;
        if (mine[0] >= 0) lim = i < 8 ? o0_est(mine[0]) - (uc ? 0 : 8500) : nominal(4 * mine[0] + 4) + PUB + C.osl;
        else if (mine[1] >= 0) lim = cv_est(mine[1]) + POLL;
        else if (i < 16 && G[O1][15].left) lim = fmin(lim, nominal(64 + LAG) + PUB);
        int bk = -1, bc = 0; double bd = INF;
        for (int k = 0; k < NK; k++)
            for (int c = 0; c < 16; c++) {
                const bool urgent = k == O0 || k == Q1 || (k == O1 && c == 15);
                if (!G[k][c].left || ((k == O0 || k == Q1) && c != mine[k - O0]) || (k == O1 && c == 15 && i >= 16)) continue;
                if (rel(k, c) > t || (t + dur(k, c) + (k == Q0 && c >= 2 ? DQU : 0) > lim && !urgent)) continue;
                if (i < 8 && uc && uc < 16 && k != O0) continue;
                if ((k == HB && !hg) || (k != HB && !urgent && t + dur(k, c) + (k == Q0 && c >= 2 ? DQU : 0) > hlim)) continue;
                const double dl = urgent ? -INF : k == HB ? -INF / 2 : k == Q0 ? nominal(4 * c) - 3000 : 1e9 + c * 2 + (k == O1);
                if (dl < bd) { bd = dl; bk = k; bc = c; }
            }
        if (bk < 0) {
            bool any = i < 8 && uc < 16;
            for (int k = 0; k < NK; k++) for (int c = 0; c < 16; c++) any = any || G[k][c].left;
            fr[i] = any ? t + 200 : INF;
            if (t > 400000) { L.end = INF; return; }
            continue;
        }
        Grp& g = G[bk][bc];
        const int n = g.n - g.left, c = bc;
        int nu = 1;
        double d = dur(bk, c);
        if (bk == Q0) for (nu = c < 2 ? 2 : 1; c >= 2 && nu < g.left && (nu < 2 || (nu < n0 && t + d + DQU < fmin(fmin(lim, hlim), bd - MARG))); nu++) d += DQU;
        if (bk == O0 && i >= 8) d += (g.n - 8) * DKB;
        if (bk == Q0 && !c && n >= 32) { nu = 1; d -= DQU; }
        if (bk == O0 || bk == Q1) last[bk - O0][i] = c;
        if (bk == O0 && !c && i < 8) put(i, mk(T_CV, 0, 3, 2 * i, 0, 128));
        g.left -= nu;
        const double e = fmax(t, rel(bk, c) + FILL) + (t < 1 ? 4500 : 0) + d;
        fr[i] = e;
        g.done = fmax(g.done, e + (bk == O1 ? 1900 : bk == O0 ? 0 : (bk == Q1 && g.n < 24) || (bk == Q0 && !c && nu == 2) ? -500 : 1000));
        if (bk == FI || (bk == O1 && ns[c] == 1)) L.end = fmax(L.end, e);
        put(i, bk == Q0 ? (c == 0 ? mk(T_QKV, 0, 0, n < 32 ? n : 2 * n - 32, nu, 32) : c == 1 ? mk(T_QKV, 0, c, n, 2, 24) : mk(T_QKV, 0, c, n, nu, 64))
             : bk == O0 ? (i < 8 ? mk(T_OP, 0, c, i * (16 - g.n), 16 - g.n, i) : mk(T_OP, 0, c, 64 - (nc - i) * 8, 8, slot(O0, c, i)))
             : bk == HB ? mk(T_CV, 1, c, 2 * n, 0, 0)
             : bk == Q1 ? mk(T_QKV, 1, c, slot(Q1, c, i) * 2, 48 / g.n, g.n)
             : bk == O1 ? mk(T_OP, 1, c, n * 64 / ns[c], 64 / ns[c], ns[c] == 1 ? 32 : n)
                        : mk(T_FIN, 1, c, n * (32 / g.n), ns[c], 16 / g.n));
    }
    L.rec = end_it(63 + LAG);
}
void plan(Params& P) {
    P.rec0 = REC0; P.chains = 3; P.lag = g_cfg.LAG; P.dostats = 1; P.dopro = 1;
    static Plan L;
    int cls[NCL], nc = 0;
    for (int c = REC0 + 32; c < NCL; c++) cls[nc++] = c;
    for (int c = REC0 - 1; c >= 0; c--) cls[nc++] = c;
    simulate(L, nc, g_cfg);
    g_est = L.end;
    Sched S; S.P = &P; S.clear();
    S.add(0, mk(T_QKV, 1, 15, 0, 2, 128 + 24)); S.add(0, mk(T_OP, 1, 15, 0, 4, 128));
    S.add(1, mk(T_CV, 0, 3, 0, 0, 128));
    for (int i = 0; i < nc; i++) {
        bool warm = false;
        for (int k = 0; k < L.n[i]; k++) {
            if (!warm && k + 1 < L.n[i] && (L.w[i][k + 1] & 255) == (mk(T_FIN, 1, 15, 0, 0, 0) & 255)) { S.add(cls[i], L.w[i][k + 1] | 0x80000000u); warm = true; }
            S.add(cls[i], L.w[i][k]);
            if ((L.w[i][k] & 7) == T_FIN) warm = true;
        }
    }
}

#define TK0() do {} while (0)
#define TK() do { P.e0 = (P.chains & 1) ? 64 : 0; P.b1 = (P.chains & 2) ? P.lag : 1000; P.nit = (P.chains & 2) ? P.lag + 64 : 64; TK0(); } while (0)
}

extern "C" void kernel_launch(void* const* d_in, const int* in_sizes, int n_in, void* d_out, int out_size) {
    typedef const __nv_bfloat16* BP;
    static EncFn enc = nullptr;
    if (!enc) {
        void* fn = nullptr; cudaDriverEntryPointQueryResult qr;
        cudaGetDriverEntryPoint("cuTensorMapEncodeTiled", &fn, cudaEnableDefault, &qr);
        enc = (EncFn)fn;
        cudaFuncSetAttribute(main_kernel, cudaFuncAttributeMaxDynamicSharedMemorySize, SMEM_BYTES);
    }
    static Params P;
    for (int i = 0; i < 4; i++) {
        const cuuint64_t cols = i < 3 ? 4096 : 512, rows = i < 3 ? 512 : 4096;
        cuuint64_t d2[2] = {cols, rows}, d3[3] = {64, rows, cols / 64}, str[2] = {cols * 2, 128};
        cuuint32_t box[3] = {64, 64, 4}, es[3] = {1, 1, 1};
        enc(&P.tm[i < 3 ? i : 4], CU_TENSOR_MAP_DATA_TYPE_BFLOAT16, 2, d_in[9 + i], d2, str, box, es, CU_TENSOR_MAP_INTERLEAVE_NONE, CU_TENSOR_MAP_SWIZZLE_128B,
                       CU_TENSOR_MAP_L2_PROMOTION_L2_128B, CU_TENSOR_MAP_FLOAT_OOB_FILL_NONE);
        for (int m = 0; m < 2; m++) {
            cuuint32_t box3[3] = {64, 32, m ? 2u : 4u};
            enc(&P.t3[m][i], CU_TENSOR_MAP_DATA_TYPE_BFLOAT16, 3, d_in[9 + i], d3, str, box3, es, CU_TENSOR_MAP_INTERLEAVE_NONE, CU_TENSOR_MAP_SWIZZLE_128B,
                CU_TENSOR_MAP_L2_PROMOTION_L2_128B, CU_TENSOR_MAP_FLOAT_OOB_FILL_NONE);
        }
    }
    {
        cuuint64_t dims[2] = {512, 2048}, str[1] = {1024};
        cuuint32_t box[2] = {8, 256}, es[2] = {1, 1};
        enc(&P.tm[3], CU_TENSOR_MAP_DATA_TYPE_BFLOAT16, 2, d_in[0], dims, str, box, es, CU_TENSOR_MAP_INTERLEAVE_NONE, CU_TENSOR_MAP_SWIZZLE_NONE,
            CU_TENSOR_MAP_L2_PROMOTION_NONE, CU_TENSOR_MAP_FLOAT_OOB_FILL_NONE);
    }
    for (int m = 0; m < 2; m++) {
        void* ga; cudaGetSymbolAddress(&ga, g_A);
        cuuint64_t dims[2] = {512, sizeof(AOps) / 1024}, str[1] = {1024};
        cuuint32_t box[2] = {256, m ? 16u : 8u}, es[2] = {1, 1};
        enc(&P.ta[m], CU_TENSOR_MAP_DATA_TYPE_BFLOAT16, 2, ga, dims, str, box, es, CU_TENSOR_MAP_INTERLEAVE_NONE, CU_TENSOR_MAP_SWIZZLE_NONE,
            CU_TENSOR_MAP_L2_PROMOTION_L2_128B, CU_TENSOR_MAP_FLOAT_OOB_FILL_NONE);
    }
    P.mem0 = (BP)d_in[8]; P.Wo = (BP)d_in[12]; P.Dskip = (BP)d_in[6]; P.out = (__nv_bfloat16*)d_out;
    cudaStream_t s = cudaStreamPerThread;
    P.pa = {(BP)d_in[0], (BP)d_in[1], (BP)d_in[2], (BP)d_in[3], (BP)d_in[4], (BP)d_in[5], (BP)d_in[6], (BP)d_in[9], (BP)d_in[10], (BP)d_in[11], (BP)d_in[12], (BP)d_in[8]};
    if (!g_planned) { plan(P); g_planned = true; }
    TK(); main_kernel<<<2 * NCL, 384, SMEM_BYTES, s>>>(P); TK();
}
```

```cpp
#include <cuda_runtime.h>
#include <cuda_bf16.h>
#include <cuda.h>
#include <stdint.h>
#include <string.h>
#include <math.h>

namespace {

constexpr int NCL = 66;
constexpr int MAXT = 64;
#define PFC 1
#define QB1 2
#define QB2 4
#define QB3 6
#define LAGQ 2
#define OPS1N 10
constexpr int OPS1 = OPS1N;
constexpr int MAXSPLIT = 16;
constexpr int PW = 144;

struct AOps { uint4 x[2][16 * 8 * 1024], o[2][16 * 64 * 1024]; };
__device__ AOps g_A;
#define g_xA g_A.x
#define g_o g_A.o
__device__ float2 g_st[2][16 * 2048];
__device__ float2 g_st2[2 * 16 * 128];
__device__ uint4 g_qkv[2][64 * 64 * 768];
__device__ uint4 g_pp[2][16 * MAXSPLIT * 8192];
__device__ uint4 g_acc[7 * 2048];
__device__ unsigned g_gate[32];
__device__ uint32_t g_P[16 * 16 * 32 * PW];
__device__ uint4 g_u[16 * 16 * 512];
__device__ float4 g_carry[2][17 * 16 * 4 * 256];
__device__ unsigned g_cnt[13 * 64];
__device__ uint32_t g_ln0[2048];

enum { C_QKV0 = 0, C_QKV1 = 1  , C_O0 = 2, C_O1 = 3, C_U = 4, C_OP1 = 5, C_CV = 6, C_ST = 7, C_H = 8, C_OP0 = 9   };
__device__ __forceinline__ unsigned* cnt_ptr(int kind, int chunk) { return g_cnt + kind * 64 + chunk; }

enum { T_END = 0, T_QKV = 1, T_OP = 2, T_CV = 3, T_FIN = 4 };
struct ProArgs { const __nv_bfloat16 *x, *lAr, *Ai, *Cr, *Ci, *ldt, *Dk, *Wq, *Wk, *Wv, *Wo, *mem0; };
struct Params {
    CUtensorMap tm[5];
    CUtensorMap t3[2][4];
    CUtensorMap ta[2];
    ProArgs pa;
    int dopro;
    const __nv_bfloat16* mem0;
    const __nv_bfloat16* Wo;
    const __nv_bfloat16* Dskip;
    __nv_bfloat16* out;
    int rec0;
    int chains;
    int lag;
    int b1, e0, nit;
    int zero, gpit;
    int dostats;
    uint32_t task[NCL][MAXT];
};

__device__ __forceinline__ uint32_t smem_u32(const void* p) { return (uint32_t)__cvta_generic_to_shared(p); }
__device__ __forceinline__ uint32_t mapa(uint32_t a, uint32_t r) {
    uint32_t o; asm("mapa.shared::cluster.u32 %0,%1,%2;" : "=r"(o) : "r"(a), "r"(r)); return o;
}
__device__ __forceinline__ void mbar_init(uint32_t b, int c) { asm volatile("mbarrier.init.shared::cta.b64 [%0],%1;" ::"r"(b), "r"(c) : "memory"); }
__device__ __forceinline__ void mbar_expect(uint32_t b, int bytes) { asm volatile("mbarrier.arrive.expect_tx.shared::cta.b64 _,[%0],%1;" ::"r"(b), "r"(bytes) : "memory"); }
__device__ __forceinline__ void mbar_arrive(uint32_t b) { asm volatile("mbarrier.arrive.shared::cta.b64 _,[%0];" ::"r"(b) : "memory"); }
__device__ __forceinline__ void mbar_arrive_cluster(uint32_t b) { asm volatile("mbarrier.arrive.shared::cluster.b64 _,[%0];" ::"r"(b) : "memory"); }
__device__ __forceinline__ void mbar_arrive1(uint32_t b) { asm volatile("{.reg .pred p; elect.sync _|p,0xffffffff; @p mbarrier.arrive.shared::cta.b64 _,[%0];}" ::"r"(b) : "memory"); }
__device__ __forceinline__ void mbar_arrive1_cluster(uint32_t b) { asm volatile("{.reg .pred p; elect.sync _|p,0xffffffff; @p mbarrier.arrive.shared::cluster.b64 _,[%0];}" ::"r"(b) : "memory"); }
__device__ __forceinline__ void mbar_wait(uint32_t b, uint32_t ph) {
    asm volatile(
        "{.reg .pred p; .reg .u32 n; mov.u32 n,0;\n"
        "W%=: mbarrier.try_wait.parity.shared::cta.b64 p,[%0],%1;\n"
        "@p bra D%=;\n"
        "add.u32 n,n,1; setp.lt.u32 p,n,2000000; @p bra W%=;\n"
        "trap;\n"
        "D%=: }" ::"r"(b), "r"(ph) : "memory");
}
__device__ __forceinline__ bool mbar_test(uint32_t b, uint32_t ph) {
    uint32_t ok;
    asm volatile("{.reg .pred p; mbarrier.test_wait.parity.shared::cta.b64 p,[%1],%2; selp.u32 %0,1,0,p;}" : "=r"(ok) : "r"(b), "r"(ph) : "memory");
    return ok;
}
__device__ __forceinline__ bool wait_lds128(uint32_t b, uint32_t ph, uint32_t a, uint4& v) {
    uint32_t ok;
    asm volatile("{.reg .pred p; mbarrier.try_wait.parity.shared::cta.b64 p,[%5],%6,20000; ld.shared.v4.u32 {%0,%1,%2,%3},[%7]; selp.u32 %4,1,0,p;}"
                 : "=r"(v.x), "=r"(v.y), "=r"(v.z), "=r"(v.w), "=r"(ok) : "r"(b), "r"(ph), "r"(a) : "memory");
    return ok;
}
__device__ __forceinline__ bool wait_lds64(uint32_t b, uint32_t ph, uint32_t a, uint2& v) {
    uint32_t ok;
    asm volatile("{.reg .pred p; mbarrier.try_wait.parity.shared::cta.b64 p,[%3],%4,20000; ld.shared.v2.u32 {%0,%1},[%5]; selp.u32 %2,1,0,p;}"
                 : "=r"(v.x), "=r"(v.y), "=r"(ok) : "r"(b), "r"(ph), "r"(a) : "memory");
    return ok;
}
template <int PH> __device__ __forceinline__ void mbar_wait_c(uint32_t b) {
    asm volatile(
        "{.reg .pred p; .reg .u32 n; mov.u32 n,%2;\n"
        "W%=: mbarrier.try_wait.parity.shared::cta.b64 p,[%0],%1;\n"
        "@p bra D%=;\n"
        "add.u32 n,n,1; setp.lt.u32 p,n,2000000; @p bra W%=;\n"
        "trap;\n"
        "D%=: }" ::"r"(b), "n"(PH), "n"(PH) : "memory");
}
__device__ __forceinline__ void bar_sync(int id, int n) { asm volatile("bar.sync %0,%1;" ::"r"(id), "r"(n) : "memory"); }
__device__ __forceinline__ void bar_arrive(int id, int n) { asm volatile("bar.arrive %0,%1;" ::"r"(id), "r"(n) : "memory"); }
__device__ __forceinline__ void cluster_sync() { asm volatile("barrier.cluster.arrive.relaxed.aligned; barrier.cluster.wait.aligned;" ::: "memory"); }
__device__ __forceinline__ void fence_async() { asm volatile("fence.proxy.async;" ::: "memory"); }
__device__ __forceinline__ void fence_async_smem() { asm volatile("fence.proxy.async.shared::cta;" ::: "memory"); }
#define EFR 1
#define EFW 2
constexpr uint64_t POL_N = 0x1000000000000000ull, POL_F = 0x12F0000000000000ull;
constexpr uint64_t POL_LAST = EFR ? POL_F : POL_N  , POL_LATE = EFW ? POL_F : POL_N  , POL_SOON = EFW > 1 ? POL_F : POL_N;
__device__ __forceinline__ void bulk_g2s(uint32_t dst, const void* src, int bytes, uint32_t bar, uint64_t pol) {
    asm volatile("cp.async.bulk.shared::cluster.global.mbarrier::complete_tx::bytes.L2::cache_hint [%0],[%1],%2,[%3],%4;" ::"r"(dst), "l"(src), "r"(bytes), "r"(bar), "l"(pol) : "memory");
}
__device__ __forceinline__ void bulk_g2s_mc(uint32_t dst, const void* src, int bytes, uint32_t bar, uint64_t pol) {
    asm volatile("cp.async.bulk.shared::cluster.global.mbarrier::complete_tx::bytes.multicast::cluster.L2::cache_hint [%0],[%1],%2,[%3],%4,%5;" ::"r"(dst), "l"(src), "r"(bytes), "r"(bar), "h"((uint16_t)3), "l"(pol) : "memory");
}
__device__ __forceinline__ void bulk_s2s(uint32_t dst, uint32_t src, int bytes, uint32_t bar) {
    asm volatile("cp.async.bulk.shared::cluster.shared::cta.mbarrier::complete_tx::bytes [%0],[%1],%2,[%3];" ::"r"(dst), "r"(src), "r"(bytes), "r"(bar) : "memory");
}
__device__ __forceinline__ bool elect() {
    uint32_t r; asm volatile("{.reg .pred p; elect.sync _|p,0xffffffff; selp.u32 %0,1,0,p;}" : "=r"(r)); return r;
}
__device__ __forceinline__ void stg128(uint4* p, uint4 v, uint64_t pol) {
    asm volatile("st.global.L2::cache_hint.v4.u32 [%0],{%1,%2,%3,%4},%5;" ::"l"(p), "r"(v.x), "r"(v.y), "r"(v.z), "r"(v.w), "l"(pol));
}
__device__ __forceinline__ void stg32(uint32_t* p, uint32_t v, uint64_t pol) { asm volatile("st.global.L2::cache_hint.u32 [%0],%1,%2;" ::"l"(p), "r"(v), "l"(pol)); }
__device__ __forceinline__ uint4 ldcg128_last(const uint4* p) {
    uint4 v; asm volatile("ld.global.cg.L2::cache_hint.v4.u32 {%0,%1,%2,%3},[%4],%5;" : "=r"(v.x), "=r"(v.y), "=r"(v.z), "=r"(v.w) : "l"(p), "l"(POL_LAST) : "memory"); return v;
}
__device__ __forceinline__ void tma2d(uint32_t dst, const CUtensorMap* tm, int x, int y, uint32_t bar) {
    asm volatile("cp.async.bulk.tensor.2d.shared::cluster.global.mbarrier::complete_tx::bytes [%0],[%1,{%2,%3}],[%4];" ::"r"(dst), "l"(tm), "r"(x), "r"(y), "r"(bar) : "memory");
}
__device__ __forceinline__ void tma3d_mc(uint32_t dst, const CUtensorMap* tm, int y, int z, uint32_t bar, uint16_t mask) {
    asm volatile("{.reg .pred p; elect.sync _|p,0xffffffff;\n"
                 "@p cp.async.bulk.tensor.3d.shared::cluster.global.mbarrier::complete_tx::bytes.multicast::cluster [%0],[%1,{0,%2,%3}],[%4],%5;}"
                 ::"r"(dst), "l"(tm), "r"(y), "r"(z), "r"(bar), "h"(mask) : "memory");
}
__device__ __forceinline__ void tma2d_mc(uint32_t dst, const CUtensorMap* tm, int x, int y, uint32_t bar, uint16_t mask, uint64_t pol) {
    asm volatile("{.reg .pred p; elect.sync _|p,0xffffffff;\n"
                 "@p cp.async.bulk.tensor.2d.shared::cluster.global.mbarrier::complete_tx::bytes.multicast::cluster.L2::cache_hint [%0],[%1,{%2,%3}],[%4],%5,%6;}"
                 ::"r"(dst), "l"(tm), "r"(x), "r"(y), "r"(bar), "h"(mask), "l"(pol) : "memory");
}
__device__ __forceinline__ void bulk_g2s1(uint32_t dst, const void* src, int bytes, uint32_t bar, uint64_t pol) {
    asm volatile("{.reg .pred p; elect.sync _|p,0xffffffff;\n"
                 "@p cp.async.bulk.shared::cluster.global.mbarrier::complete_tx::bytes.L2::cache_hint [%0],[%1],%2,[%3],%4;}" ::"r"(dst), "l"(src), "r"(bytes), "r"(bar), "l"(pol) : "memory");
}
__device__ __forceinline__ void mbar_expect1(uint32_t b, int bytes) {
    asm volatile("{.reg .pred p; elect.sync _|p,0xffffffff; @p mbarrier.arrive.expect_tx.shared::cta.b64 _,[%0],%1;}" ::"r"(b), "r"(bytes) : "memory");
}
__device__ __forceinline__ void st_async4(uint32_t a, uint32_t x, uint32_t y, uint32_t z, uint32_t w, uint32_t mb) {
    asm volatile("st.async.shared::cluster.mbarrier::complete_tx::bytes.v4.b32 [%0],{%1,%2,%3,%4},[%5];" ::"r"(a), "r"(x), "r"(y), "r"(z), "r"(w), "r"(mb) : "memory");
}
__device__ __forceinline__ void st_async2(uint32_t a, uint32_t x, uint32_t y, uint32_t mb) {
    asm volatile("st.async.shared::cluster.mbarrier::complete_tx::bytes.v2.b32 [%0],{%1,%2},[%3];" ::"r"(a), "r"(x), "r"(y), "r"(mb) : "memory");
}
#define LDSQ "ld.shared"
__device__ __forceinline__ uint4 lds128(uint32_t a) { uint4 v; asm volatile(LDSQ ".v4.u32 {%0,%1,%2,%3},[%4];" : "=r"(v.x), "=r"(v.y), "=r"(v.z), "=r"(v.w) : "r"(a) : "memory"); return v; }
__device__ __forceinline__ uint2 lds64(uint32_t a) { uint2 v; asm volatile(LDSQ ".v2.u32 {%0,%1},[%2];" : "=r"(v.x), "=r"(v.y) : "r"(a) : "memory"); return v; }
__device__ __forceinline__ uint32_t lds32(uint32_t a) { uint32_t v; asm volatile(LDSQ ".u32 %0,[%1];" : "=r"(v) : "r"(a) : "memory"); return v; }
__device__ __forceinline__ void sts128(uint32_t a, uint32_t x, uint32_t y, uint32_t z, uint32_t w) { asm volatile("st.shared.v4.u32 [%0],{%1,%2,%3,%4};" ::"r"(a), "r"(x), "r"(y), "r"(z), "r"(w) : "memory"); }
__device__ __forceinline__ void sts64(uint32_t a, uint32_t x, uint32_t y) { asm volatile("st.shared.v2.u32 [%0],{%1,%2};" ::"r"(a), "r"(x), "r"(y) : "memory"); }
__device__ __forceinline__ void sts32(uint32_t a, uint32_t x) { asm volatile("st.shared.u32 [%0],%1;" ::"r"(a), "r"(x) : "memory"); }
__device__ __forceinline__ uint4 ldsm4(uint32_t a) { uint4 v; asm volatile("ldmatrix.sync.aligned.m8n8.x4.shared.b16 {%0,%1,%2,%3},[%4];" : "=r"(v.x), "=r"(v.y), "=r"(v.z), "=r"(v.w) : "r"(a) : "memory"); return v; }
__device__ __forceinline__ uint4 ldsm4t(uint32_t a) { uint4 v; asm volatile("ldmatrix.sync.aligned.m8n8.x4.trans.shared.b16 {%0,%1,%2,%3},[%4];" : "=r"(v.x), "=r"(v.y), "=r"(v.z), "=r"(v.w) : "r"(a) : "memory"); return v; }
__device__ __forceinline__ uint32_t movm(uint32_t a) { uint32_t d; asm volatile("movmatrix.sync.aligned.m8n8.trans.b16 %0,%1;" : "=r"(d) : "r"(a)); return d; }
__device__ __forceinline__ uint32_t pack2(float lo, float hi) { uint32_t d; asm("cvt.rn.bf16x2.f32 %0,%1,%2;" : "=r"(d) : "f"(hi), "f"(lo)); return d; }
__device__ __forceinline__ uint32_t hadd2(uint32_t a, uint32_t b) { uint32_t d; asm("add.rn.bf16x2 %0,%1,%2;" : "=r"(d) : "r"(a), "r"(b)); return d; }
__device__ __forceinline__ float blo(uint32_t v) { return __uint_as_float(v << 16); }
__device__ __forceinline__ float bhi(uint32_t v) { return __uint_as_float(v & 0xffff0000u); }
__device__ __forceinline__ float rbf(float x) { return __uint_as_float(pack2(0.f, x)); }
__device__ __forceinline__ float ex2(float x) { float y; asm("ex2.approx.ftz.f32 %0,%1;" : "=f"(y) : "f"(x)); return y; }
__device__ __forceinline__ float rcp(float x) { float y; asm("rcp.approx.ftz.f32 %0,%1;" : "=f"(y) : "f"(x)); return y; }
__device__ __forceinline__ void mma16(float* c, uint32_t a0, uint32_t a1, uint32_t a2, uint32_t a3, uint32_t b0, uint32_t b1) {
    asm volatile("mma.sync.aligned.m16n8k16.row.col.f32.bf16.bf16.f32 {%0,%1,%2,%3},{%4,%5,%6,%7},{%8,%9},{%0,%1,%2,%3};"
                 : "+f"(c[0]), "+f"(c[1]), "+f"(c[2]), "+f"(c[3]) : "r"(a0), "r"(a1), "r"(a2), "r"(a3), "r"(b0), "r"(b1));
}
__device__ __forceinline__ void mma8(float* c, uint32_t a0, uint32_t a1, uint32_t b0) {
    asm volatile("mma.sync.aligned.m16n8k8.row.col.f32.bf16.bf16.f32 {%0,%1,%2,%3},{%4,%5},{%6},{%0,%1,%2,%3};"
                 : "+f"(c[0]), "+f"(c[1]), "+f"(c[2]), "+f"(c[3]) : "r"(a0), "r"(a1), "r"(b0));
}
__device__ __forceinline__ uint4 ld_rlx128(const uint4* p) {
    uint4 v;
    asm volatile("{.reg .b128 t; ld.relaxed.gpu.global.b128 t,[%4]; mov.b128 {%0,%1,%2,%3},t;}" : "=r"(v.x), "=r"(v.y), "=r"(v.z), "=r"(v.w) : "l"(p) : "memory");
    return v;
}
__device__ __forceinline__ void st_rlx128(uint4* p, uint32_t x, uint32_t y, uint32_t z, uint32_t w) {
    asm volatile("{.reg .b128 t; mov.b128 t,{%1,%2,%3,%4}; st.relaxed.gpu.global.b128 [%0],t;}" ::"l"(p), "r"(x), "r"(y), "r"(z), "r"(w) : "memory");
}
__device__ __forceinline__ uint4 ldcg128(const uint4* p) { uint4 v; asm volatile("ld.global.cg.v4.u32 {%0,%1,%2,%3},[%4];" : "=r"(v.x), "=r"(v.y), "=r"(v.z), "=r"(v.w) : "l"(p) : "memory"); return v; }
__device__ __forceinline__ void red_release(unsigned* p, unsigned v) {
    asm volatile("fence.proxy.async; red.relaxed.gpu.global.add.u32 [%0],%1;" ::"l"(p), "r"(v) : "memory");
}
__device__ __forceinline__ void wait_cnt(const unsigned* p, unsigned target) {
    unsigned v; int n = 0;
    while (true) {
        asm volatile("ld.acquire.gpu.global.u32 %0,[%1];" : "=r"(v) : "l"(p) : "memory");
        if (v >= target) break;
        if (++n > 3000000) __trap();
        __nanosleep(40);
    }
}
__device__ __forceinline__ void wait_cnt_warp(const unsigned* p, unsigned target) {
    unsigned v; int n = 0;
    while (true) {
        asm volatile("ld.acquire.gpu.global.u32 %0,[%1];" : "=r"(v) : "l"(p) : "memory");
        if (__all_sync(0xffffffffu, v >= target)) break;
        if (++n > 3000000) __trap();
    }
}
__device__ __forceinline__ uint64_t mkdesc(uint32_t addr, uint32_t lbo, uint32_t sbo, uint32_t sw) {
    return (uint64_t)((addr & 0x3FFFF) >> 4) | ((uint64_t)(lbo >> 4) << 16) | ((uint64_t)(sbo >> 4) << 32) | ((uint64_t)sw << 62);
}
__device__ __forceinline__ void wg_fence() { asm volatile("wgmma.fence.sync.aligned;" ::: "memory"); }
__device__ __forceinline__ void wg_commit() { asm volatile("wgmma.commit_group.sync.aligned;" ::: "memory"); }
template <int N> __device__ __forceinline__ void wg_wait() { asm volatile("wgmma.wait_group.sync.aligned %0;" ::"n"(N) : "memory"); }
#define R8(c, o) "+f"(c[o]), "+f"(c[o + 1]), "+f"(c[o + 2]), "+f"(c[o + 3]), "+f"(c[o + 4]), "+f"(c[o + 5]), "+f"(c[o + 6]), "+f"(c[o + 7])
#define R32(c, o) R8(c, o), R8(c, o + 8), R8(c, o + 16), R8(c, o + 24)
#define S32A "%0,%1,%2,%3,%4,%5,%6,%7,%8,%9,%10,%11,%12,%13,%14,%15,%16,%17,%18,%19,%20,%21,%22,%23,%24,%25,%26,%27,%28,%29,%30,%31"
#define S32B ",%32,%33,%34,%35,%36,%37,%38,%39,%40,%41,%42,%43,%44,%45,%46,%47,%48,%49,%50,%51,%52,%53,%54,%55,%56,%57,%58,%59,%60,%61,%62,%63"
#define S32C ",%64,%65,%66,%67,%68,%69,%70,%71,%72,%73,%74,%75,%76,%77,%78,%79,%80,%81,%82,%83,%84,%85,%86,%87,%88,%89,%90,%91,%92,%93,%94,%95"
#define S32D ",%96,%97,%98,%99,%100,%101,%102,%103,%104,%105,%106,%107,%108,%109,%110,%111,%112,%113,%114,%115,%116,%117,%118,%119,%120,%121,%122,%123,%124,%125,%126,%127"
#define W8(c, o) "=f"(c[o]), "=f"(c[o + 1]), "=f"(c[o + 2]), "=f"(c[o + 3]), "=f"(c[o + 4]), "=f"(c[o + 5]), "=f"(c[o + 6]), "=f"(c[o + 7])
#define W32(c, o) W8(c, o), W8(c, o + 8), W8(c, o + 16), W8(c, o + 24)
template <bool ACC> __device__ __forceinline__ void wgmma256(float* c, uint64_t da, uint64_t db) {
    if (ACC) asm volatile("wgmma.mma_async.sync.aligned.m64n256k16.f32.bf16.bf16 {" S32A S32B S32C S32D "},%128,%129,1,1,1,0,1;"
                          : R32(c, 0), R32(c, 32), R32(c, 64), R32(c, 96) : "l"(da), "l"(db));
    else asm volatile("wgmma.mma_async.sync.aligned.m64n256k16.f32.bf16.bf16 {" S32A S32B S32C S32D "},%128,%129,0,1,1,0,1;"
                      : W32(c, 0), W32(c, 32), W32(c, 64), W32(c, 96) : "l"(da), "l"(db));
}
template <bool ACC> __device__ __forceinline__ void wgmma128r(float* c, const uint4& a, uint64_t db) {
    if (ACC) asm volatile("wgmma.mma_async.sync.aligned.m64n128k16.f32.bf16.bf16 {" S32A S32B "},{%64,%65,%66,%67},%68,1,1,1,1;"
                          : R32(c, 0), R32(c, 32) : "r"(a.x), "r"(a.y), "r"(a.z), "r"(a.w), "l"(db));
    else asm volatile("wgmma.mma_async.sync.aligned.m64n128k16.f32.bf16.bf16 {" S32A S32B "},{%64,%65,%66,%67},%68,0,1,1,1;"
                      : W32(c, 0), W32(c, 32) : "r"(a.x), "r"(a.y), "r"(a.z), "r"(a.w), "l"(db));
}
template <int N> __device__ __forceinline__ void reg_inc() { asm volatile("setmaxnreg.inc.sync.aligned.u32 %0;" ::"n"(N)); }
template <int N> __device__ __forceinline__ void reg_dec() { asm volatile("setmaxnreg.dec.sync.aligned.u32 %0;" ::"n"(N)); }

#define PROF(cond, idx) do {} while (0)
#define CPROF(k) do {} while (0)

constexpr int S_GATE = 232440, S_TAG = 232444, S_XBAR = 232432;
constexpr float SC_LOG2E = 0.08838834764831845f * 1.4426950408889634f;

__device__ __forceinline__ float2 ln_finish(float mean, float var) {
    float sd; asm("sqrt.approx.f32 %0,%1;" : "=f"(sd) : "f"(rbf(rbf(var) + 1e-5f)));
    sd = rbf(sd);
    return make_float2(rbf(mean), sd);
}

__device__ __forceinline__ float4 row_stats(const uint4* src, int stride) {
    const int g = (threadIdx.x & 31) >> 2;
    uint4 v[16];
#pragma unroll
    for (int i = 0; i < 16; i++) v[i] = ldcg128(src + i * stride);
    float a[4] = {0, 0, 0, 0}, q0[4] = {0, 0, 0, 0}, q1[4] = {0, 0, 0, 0};
#pragma unroll
    for (int i = 0; i < 16; i++) {
        mma16(a, v[i].x, v[i].y, v[i].z, v[i].w, 0x3f803f80u, 0x3f803f80u);
        mma8(q0, v[i].x, v[i].y, v[i].x); mma8(q1, v[i].x, v[i].y, v[i].y);
        mma8(q0, v[i].z, v[i].w, v[i].z); mma8(q1, v[i].z, v[i].w, v[i].w);
    }
    return make_float4(a[0], (g & 1) ? q0[1] : q0[0], a[2], (g & 1) ? q1[3] : q1[2]);
}
__device__ __forceinline__ void x1_stats(int i) {
    const int lane = threadIdx.x & 31, g = lane >> 2, c = lane & 3;
    const float4 r = row_stats(g_xA[0] + i * 512 + lane, 32);
    float2* dst = g_st[0] + (i >> 4) * 2048 + ((i < 32 ? 4 : 0) + (i & 1)) * 128 + ((i >> 1) & 7) * 16 + g;
    if (c == (g >> 1)) { dst[0] = make_float2(r.x, r.y); dst[8] = make_float2(r.z, r.w); g_ln0[i * 8 + g] = 0; }
    __syncwarp();
    if (lane == 0) red_release(cnt_ptr(C_ST, i >> 4), 1);
}
__global__ void stats_kernel() { x1_stats(blockIdx.x * 4 + (threadIdx.x >> 5)); }

#define NT 9
#define RH 104
#define RW0 200
#define NPD 9
#define NTO 13
#define DP1 9
#define GPW 0
#define GPJ 0
#define PACE 2
#define BKA 0
#define GSE 4
#define EARLY 4
#define PFD 0
#define PFB 0
#define G2S 7
#define XPRE 0
#define STO 1
#define G2I 2
#define VE 4
#define VF 8
constexpr int R_WV = 0, R_WO = 65536, R_T = 131072, R_M = R_T + 20480, R_LOC = R_M + 4096, R_REM = R_LOC + 6144, R_O = R_REM + 12288, R_SX = R_O + 2048,
              R_IL = R_SX + 5120, XS = R_IL + 128 - R_T, R_BAR = 231936, R_Z = R_BAR + 128  , R_STQ = 0, R_STK = 65536, R_STV = 131072;
static_assert(R_T + 2 * XS <= R_BAR && R_BAR + 256 <= S_XBAR, "smem map");
enum { RB_INIT = 0, RB_MB = 1, RB_V = 4  , RB_QK = 8  , RB_T = 12  , RB_N = 16 };
enum { NB_MF = 1  , NB_LOC = 3  , NB_PAIR = 5  , NB_O = 9  , NB_XG = 11  , NB_W = 13 };
__device__ __forceinline__ uint32_t clk32() { return (uint32_t)clock64(); }

__device__ __forceinline__ char* acc_base() { return (char*)(((size_t)g_acc + 131071) & ~(size_t)131071); }
__device__ __forceinline__ uint32_t acc_slice(uint32_t s6) { return (s6 & 1) * 256 + (s6 >> 1) * 1024; }
__device__ __forceinline__ uint32_t acc_main(uint32_t rank, uint32_t tid) { return acc_slice(rank * 32 + (tid >> 3)) + (tid & 7) * 16; }
__device__ __forceinline__ uint32_t acc_extra(uint32_t rank, uint32_t tid) { return 65536 + acc_slice(((tid >> 5) & 1) + rank * 4 + (tid >> 6) * 8) + (tid & 31) * 4; }
__device__ __forceinline__ uint32_t acc_slot(uint32_t s) { return (s & 1) * 128 + (s & 2) * 256; }
__device__ __forceinline__ void acc_init(const __nv_bfloat16* mem0, int i) {
    const uint32_t tid = i & 255, rank = (i >> 8) & 1, slot = (i >> 9) & 3, X = i >> 11;
    uint32_t v[5] = {0, 0, 0, 0, 0};
    if (slot == 3) {
        const uint16_t* m = (const uint16_t*)mem0 + (tid & 3) * 1024 + rank * 256 + (tid >> 5) * 32 + ((tid >> 2) & 7);
#pragma unroll
        for (int k = 0; k < 4; k++) v[k] = __ldg(m + k * 8) | ((uint32_t)__ldg(m + k * 8 + 512) << 16);
        v[4] = (v[3] >> 16) | 0x42000000u; v[3] = (v[3] & 0xffff) | 0x42000000u;
    }
    *(uint4*)(acc_base() + X * 32768 + acc_slot(slot) + acc_main(rank, tid)) = make_uint4(v[0], v[1], v[2], v[3]);
    *(uint32_t*)(acc_base() + X * 1024 + acc_slot(slot) + acc_extra(rank, tid)) = v[4];
}
__global__ void acc_init_kernel(const __nv_bfloat16* mem0) { acc_init(mem0, blockIdx.x * 256 + threadIdx.x); }

struct RecW { uint32_t am, ae, ah, dp, lp, lpw, vo, sb, bar, zero, ts, tn; };
__device__ __forceinline__ uint32_t vadd(uint32_t a, uint32_t b) { uint32_t d; asm volatile("add.u32 %0,%1,%2;" : "=r"(d) : "r"(a), "r"(b)); return d; }
__device__ __forceinline__ uint32_t vshr(uint32_t a, int n) { uint32_t d; asm volatile("shr.u32 %0,%1,%2;" : "=r"(d) : "r"(a), "r"(n)); return d; }
__device__ __forceinline__ uint64_t gptr(uint32_t lo, uint32_t hi) { uint64_t d; asm("mov.b64 %0,{%1,%2};" : "=l"(d) : "r"(lo), "r"(hi)); return d; }
__device__ __forceinline__ void sfence(uint32_t zero) { asm volatile("{.reg .pred p; setp.ne.u32 p,%0,0; @p exit;}" ::"r"(zero) : "memory"); }
#define SF sfence(k.zero)
#define TS(i) do {} while (0)
#define TSN(i) do {} while (0)
#define TSET(it, slot) do {} while (0)
struct Gat { uint32_t x, y, z, w, e; };
template <int X>
__device__ __forceinline__ void gat_issue(Gat& g, const RecW& k, int s, uint32_t dep) {
    const uint32_t o = acc_slot(s + 3) + dep;
    asm volatile("{.reg .b128 t; ld.relaxed.gpu.global.b128 t,[%5+%7]; mov.b128 {%0,%1,%2,%3},t; ld.relaxed.gpu.global.u32 %4,[%6+%8];}"
                 : "=r"(g.x), "=r"(g.y), "=r"(g.z), "=r"(g.w), "=r"(g.e) : "l"(gptr(k.am + o, k.ah)), "l"(gptr(k.ae + o, k.ah)), "n"(X * 32768), "n"(X * 1024) : "memory");
}
template <int X>
__device__ __forceinline__ bool gat_store(const Gat& g, const RecW& k) {
    uint32_t c;
    asm volatile("prmt.b32 %0,%1,%2,0x7632;" : "=r"(c) : "r"(g.w), "r"(g.e));
    SF;
    asm volatile("{.reg .b32 t; prmt.b32 t,%4,%6,0x5410; stmatrix.sync.aligned.m8n8.x4.trans.shared.b16 [%0+%5],{%1,%2,%3,t};}" ::"r"(k.lpw), "r"(g.x), "r"(g.y), "r"(g.z), "r"(g.w), "n"(R_M + X * XS), "r"(g.e) : "memory");
    return __all_sync(0xffffffffu, c == 0x42004200u);
}
template <int X>
__device__ __forceinline__ void gat_finish(bool ok, const RecW& k, int s) {
    if (!ok) {
        int n = s;
        while (true) {
            Gat g;
            gat_issue<X>(g, k, n, 0);
            if (gat_store<X>(g, k)) break;
            n += 4;
            if (n > 8000000) __trap();
        }
    }
}
__device__ __forceinline__ uint4 lds128o(uint32_t a, int o) { uint4 v; asm volatile("{.reg .b32 t; add.u32 t,%4,%5; ld.shared.v4.u32 {%0,%1,%2,%3},[t];}" : "=r"(v.x), "=r"(v.y), "=r"(v.z), "=r"(v.w) : "r"(a), "r"(o) : "memory"); return v; }
__device__ __forceinline__ uint4 ldsm4o(uint32_t a, int o) { uint4 v; asm volatile("{.reg .b32 t; add.u32 t,%4,%5; ldmatrix.sync.aligned.m8n8.x4.shared.b16 {%0,%1,%2,%3},[t];}" : "=r"(v.x), "=r"(v.y), "=r"(v.z), "=r"(v.w) : "r"(a), "r"(o) : "memory"); return v; }
__device__ __forceinline__ uint4 ldsm4to(uint32_t a, int o) { uint4 v; asm volatile("{.reg .b32 t; add.u32 t,%4,%5; ldmatrix.sync.aligned.m8n8.x4.trans.shared.b16 {%0,%1,%2,%3},[t];}" : "=r"(v.x), "=r"(v.y), "=r"(v.z), "=r"(v.w) : "r"(a), "r"(o) : "memory"); return v; }
__device__ __forceinline__ uint2 lds64o(uint32_t a, int o) { uint2 v; asm volatile("{.reg .b32 t; add.u32 t,%2,%3; ld.shared.v2.u32 {%0,%1},[t];}" : "=r"(v.x), "=r"(v.y) : "r"(a), "r"(o) : "memory"); return v; }
__device__ __forceinline__ void sts128o(uint32_t a, int o, uint32_t x, uint32_t y, uint32_t z, uint32_t w) { asm volatile("{.reg .b32 t; add.u32 t,%0,%5; st.shared.v4.u32 [t],{%1,%2,%3,%4};}" ::"r"(a), "r"(x), "r"(y), "r"(z), "r"(w), "r"(o) : "memory"); }
__device__ __forceinline__ void sts64o(uint32_t a, int o, uint32_t x, uint32_t y) { asm volatile("{.reg .b32 t; add.u32 t,%0,%3; st.shared.v2.u32 [t],{%1,%2};}" ::"r"(a), "r"(x), "r"(y), "r"(o) : "memory"); }
__device__ __forceinline__ uint32_t vxor(uint32_t a, uint32_t b) { uint32_t d; asm volatile("xor.b32 %0,%1,%2;" : "=r"(d) : "r"(a), "r"(b)); return d; }
#define WLD(base, i) wt[i] = lds128o(k.lpw, (base) + (i) * 4096)
template <int PASS, int X, int NP>
__device__ __forceinline__ void rec_qkv(const RecW& k, int s, const uint32_t (*wq)[4], const uint32_t (*wk)[4], uint4* wt, Gat& g2, int s2, bool& ok2, uint4& mf) {
    constexpr bool BWD = PASS == 2, DIRECT = !(BKA && PASS == 1);
    float aq[4] = {0, 0, 0, 0}, ak[4] = {0, 0, 0, 0}, av[4] = {0, 0, 0, 0};
    constexpr int ma = R_M + X * XS;
    if (BWD && GSE == 4) { TS(1); mbar_wait(k.sb + R_BAR + RB_MB * 8, s & 1); mf = ldsm4o(k.lp, ma + 7 * 512); TS(2); }
    if (!BWD || GSE < 2) {
        if (BWD) { TS(1); gat_finish<1>(GSE ? ok2 : gat_store<1>(g2, k), k, s); }
        bar_sync(NB_MF + X, 256);
        mf = ldsm4o(k.lp, ma + (BWD ? 7 : 0) * 512);
        if (BWD) TS(2); else { TS(0); TSN(13); }
    }
#pragma unroll
    for (int ii = 0; ii < 8; ii++) {
        const int i = BWD ? 7 - ii : ii;
        const uint4 m = mf;
        if (ii < 7) mf = ldsm4o(k.lp, ma + (BWD ? i - 1 : i + 1) * 512);
        if (PASS == 1 && ii == G2I) gat_issue<1>(g2, k, s2, 0);
        if (PASS == 1 && GSE == 2 && ii == 7) { TS(1); gat_finish<1>(gat_store<1>(g2, k), k, s2); }
        if (PASS == 1 && GSE == 4 && ii == G2S) { gat_finish<1>(gat_store<1>(g2, k), k, s2); mbar_arrive1(k.sb + R_BAR + RB_MB * 8); }
        SF;
#pragma unroll
        for (int hh = 0; hh < 2; hh++) {
            const int h = BWD ? 1 - hh : hh, ks = 2 * i + h;
            const uint32_t b0 = h ? m.z : m.x, b1 = h ? m.w : m.y;
            mma16(aq, wq[ks][0], wq[ks][1], wq[ks][2], wq[ks][3], b0, b1);
            mma16(ak, wk[ks][0], wk[ks][1], wk[ks][2], wk[ks][3], b0, b1);
            SF;
            mma16(av, wt[ks].x, wt[ks].y, wt[ks].z, wt[ks].w, b0, b1);
            SF;
            if (!BWD && ks + NP < 16) WLD(R_WV, ks + NP < 16 ? ks + NP : 0);
            if (BWD && ks >= NT) WLD(R_WV, ks >= NT ? ks - NT : 0);
            SF;
        }
    }
    if (PASS == 1 && GSE == 1) { ok2 = gat_store<1>(g2, k); SF; }
    if (PASS == 1 && GSE == 3) { TS(1); gat_finish<1>(gat_store<1>(g2, k), k, s2); }
    if (PASS == 1 && (GSE == 2 || GSE == 3)) { bar_sync(NB_MF + 1, 256); mf = ldsm4o(k.lp, ma + XS + 7 * 512); TS(2); SF; }
    const uint32_t ra = vadd(k.lpw, k.dp + R_REM + X * XS + (s & 1) * 6144), va = ((vshr(k.lp, 7) & 1) * 48 ^ k.lp ^ (k.vo & 64)) + (k.vo & ~64u);
    const uint32_t x0 = movm(pack2(aq[0], aq[1])), x1 = movm(pack2(aq[2], aq[3])), x2 = movm(pack2(ak[0], ak[1])), x3 = movm(pack2(ak[2], ak[3]));
    SF;
    asm volatile("stmatrix.sync.aligned.m8n8.x2.shared.b16 [%0+%3],{%1,%2};" ::"r"(va), "r"(pack2(av[0], av[1])), "r"(pack2(av[2], av[3])), "n"(R_LOC + X * XS) : "memory");
    SF;
    if (STO && DIRECT) st_async4(ra, x0, x1, x2, x3, k.bar + X * 16);
    asm volatile("st.shared.v4.u32 [%0+%5],{%1,%2,%3,%4};" ::"r"(k.lpw), "r"(x0), "r"(x1), "r"(x2), "r"(x3), "n"(R_LOC + X * XS) : "memory");
    bar_arrive(NB_LOC + X, 320);
    if (!STO && DIRECT) st_async4(ra, x0, x1, x2, x3, k.bar + X * 16);
    SF;
    TS(BWD ? 4 : 3);
}
template <bool BWD, int X>
__device__ __forceinline__ void rec_out(const RecW& k, int s, uint4* wt, Gat& g, int s1) {
    if (BWD) { WLD(R_WO, 17 - NTO); WLD(R_WO, 16 - NTO); }
    TS(BWD ? 8 : 5);
    bar_sync(NB_O + X, 320);
    float r0[4] = {0, 0, 0, 0}, r1[4] = {0, 0, 0, 0};
    constexpr int oa = R_O + X * XS;
    uint4 bn = lds128o(k.lp, oa + (BWD ? 3 : 0) * 512);
    TS(BWD ? 9 : 6);
    uint2 il;
    uint64_t pm, pe;
#pragma unroll
    for (int ii = 0; ii < 4; ii++) {
        const int i = BWD ? 3 - ii : ii;
        const uint4 b = bn;
        if (ii < 3) bn = lds128o(k.lp, oa + (BWD ? i - 1 : i + 1) * 512);
        else { asm volatile("ld.shared.v2.u32 {%0,%1},[%2+%3];" : "=r"(il.x), "=r"(il.y) : "r"((vshr(k.ae, 2) & 3) * 8 + k.sb), "n"(R_IL + X * XS) : "memory"); pm = gptr(vadd(k.am, acc_slot(s)), k.ah); pe = gptr(vadd(k.ae, acc_slot(s)), k.ah); }
        SF;
        if (BWD && EARLY == ii + 1) { gat_issue<0>(g, k, s1 + 1, 0); SF; }
#pragma unroll
        for (int nn = 0; nn < 4; nn++) {
            const int n = BWD ? 3 - nn : nn, f = 4 * i + n, nx = BWD ? f - NTO + 2 : f + NTO - 2;
            mma16((n & 1) ? r1 : r0, wt[f].x, wt[f].y, wt[f].z, wt[f].w, n >> 1 ? b.z : b.x, n >> 1 ? b.w : b.y);
            SF;
            if (ii * 4 + nn >= 2 && nx >= 0 && nx < 16) WLD(R_WO, nx & 15);
            SF;
        }
    }
    const float i0 = __uint_as_float(il.x), i1 = __uint_as_float(il.y);
    asm volatile("red.relaxed.gpu.global.add.noftz.v4.bf16x2 [%0+%5],{%1,%2,%3,%4};" ::"l"(pm),
                 "r"(pack2(r0[0] * i0, r0[1] * i1)), "r"(pack2(r0[2] * i0, r0[3] * i1)), "r"(pack2(r1[0] * i0, r1[1] * i1)), "r"(pack2(r1[2] * i0, 1.f)), "n"(X * 32768) : "memory");
    asm volatile("red.relaxed.gpu.global.add.noftz.bf16x2 [%0+%2],%1;" ::"l"(pe), "r"(pack2(r1[3] * i1, 1.f)), "n"(X * 1024) : "memory");
    bar_arrive(NB_XG + X, 320);
    SF;
    TS(BWD ? 10 : 7);
}
__device__ __forceinline__ uint32_t pause(uint32_t v, int n) {
#pragma unroll
    for (int i = 0; i < n; i++) asm volatile("shfl.sync.bfly.b32 %0,%0,0,0x1f,0xffffffff;" : "+r"(v));
    return v;
}
template <bool DUAL, int X>
__device__ __forceinline__ void rec_step(const RecW& k, int s, int s2, const uint32_t (*wq)[4], const uint32_t (*wk)[4], uint4* wt) {
    constexpr int NP = NPD;
    uint4 wo[16];
    Gat g;
    bool ok2;
    uint4 mf;
    rec_qkv<DUAL ? 1 : 0, X, NP>(k, s, wq, wk, wt, g, s2, ok2, mf);
    if (DUAL) rec_qkv<2, 1, NP>(k, s2, wq, wk, wt, g, s2, ok2, mf);
    uint32_t wa = k.lpw;
#pragma unroll
    for (int i = 0; i < NTO; i++) {
        wo[i] = lds128o(wa, R_WO + i * 4096);
        if (i % PACE == PACE - 1) wa = k.lpw + (wo[i].x & k.zero);
        SF;
    }
    rec_out<false, X>(k, s, wo, g, s);
    if (DUAL) { rec_out<true, 1>(k, s2, wo, g, s); if (!EARLY) gat_issue<0>(g, k, s + 1, 0); SF; }
#pragma unroll
    for (int i = 0; i < NP; i++) { WLD(R_WV, i); SF; }
    if (!DUAL) gat_issue<X>(g, k, s + 1, pause(wt[NP - 1].x & k.zero, DP1));
    TS(12);
    gat_finish<X>(gat_store<X>(g, k), k, s + 1);
    TS(11);
}

__device__ __forceinline__ void rec_fetch(const CUtensorMap* tm, uint32_t dst, int x, int y, int nx, uint32_t bar) {
#pragma unroll 1
    for (int j = 0; j < 8; j++) tma2d(dst + j * 8192, tm, x + (j / (8 / nx)) * 64, y + (j % (8 / nx)) * 64, bar);
}
__device__ __forceinline__ void rec_weights(const Params& p, uint32_t sb, int head, uint32_t rank, int w) {
    const int lane = threadIdx.x & 31, t = w & 3, WG = w >> 2;
    uint32_t wq[16][4], wk[16][4];
    const uint32_t rowo = (((lane >> 4) << 3) + (lane & 7)) * 128;
    const uint32_t woff = sb + WG * 32768 + rowo + (((2 * t + ((lane >> 3) & 1)) ^ (lane & 7)) << 4);
    const uint32_t qoff = sb + ((w & 1) ? R_STK : R_STQ) + WG * 32768 + rowo + (((2 * (t & 2) + ((lane >> 3) & 1)) ^ (lane & 7)) << 4);
    const uint32_t lw = sb + (lane ^ (lane >> 3)) * 16;
    PROF(threadIdx.x == 0, 3501);
    PROF(threadIdx.x == 0, 3502);
    mbar_wait(sb + R_BAR + RB_INIT * 8, 0);
    PROF(threadIdx.x == 0, 3503);
#pragma unroll
    for (int ks = 0; ks < 16; ks++) {
        uint4 a = ldsm4t(qoff + ks * 2048), b = ldsm4t((qoff ^ 32) + ks * 2048);
        wq[ks][0] = a.x; wq[ks][1] = a.y; wq[ks][2] = a.z; wq[ks][3] = a.w;
        wk[ks][0] = b.x; wk[ks][1] = b.y; wk[ks][2] = b.z; wk[ks][3] = b.w;
    }
    bar_sync(NB_W, 256);
#pragma unroll 4
    for (int ks = 0; ks < 16; ks++) { const uint4 a = ldsm4t(woff + R_STV + ks * 2048); sts128(lw + w * 512 + R_WV + ks * 4096, a.x, a.y, a.z, a.w); }
    bar_sync(NB_W, 256);
    if (threadIdx.x == 0) {
        mbar_expect(sb + R_BAR + RB_INIT * 8, 65536);
        rec_fetch(&p.tm[4], sb + R_STV, rank * 256, head * 128, 4, sb + R_BAR + RB_INIT * 8);
    }
    __syncwarp();
    mbar_wait(sb + R_BAR + RB_INIT * 8, 1);
#pragma unroll 4
    for (int f = 0; f < 16; f++) {
        const uint4 a = ldsm4t(sb + R_STV + (w >> 1) * 16384 + (f >> 1) * 2048 + rowo + ((((w & 1) * 4 + (f & 1) * 2 + ((lane >> 3) & 1)) ^ (lane & 7)) << 4));
        sts128(lw + w * 512 + R_WO + f * 4096, a.x, a.y, a.z, a.w);
    }
    PROF(threadIdx.x == 0, 3504);
    __syncthreads();
    cluster_sync();
    PROF(threadIdx.x == 0, 3505);
    RecW k;
    k.am = __shfl_sync(0xffffffffu, (uint32_t)(size_t)acc_base() + acc_main(rank, threadIdx.x), lane);
    k.ae = __shfl_sync(0xffffffffu, (uint32_t)(size_t)acc_base() + acc_extra(rank, threadIdx.x), lane);
    k.ah = (uint32_t)((size_t)acc_base() >> 32);
    k.sb = sb; k.zero = p.zero;

    k.dp = mapa(sb, rank ^ 1) - sb;
    k.lp = __shfl_sync(0xffffffffu, lw, lane);
    k.lpw = __shfl_sync(0xffffffffu, lw + w * 512, lane);
    k.vo = 4096 + w * 256 + (w & 1) * 64;
    k.bar = sb + k.dp + R_BAR + (RB_QK + WG) * 8;
    int it = 0;
    uint4 wt[16];
#pragma unroll
    for (int i = 0; i < NPD; i++) WLD(R_WV, i);
    gat_finish<0>(false, k, 0);
#pragma unroll 1
    for (; it < min(p.b1, p.e0); it++) { TSET(it, w == GPW ? 0 : 3); rec_step<false, 0>(k, it, it, wq, wk, wt); }
#pragma unroll 1
    for (; it < p.e0; it++) { TSET(it, w == GPW ? 0 : 3); rec_step<true, 0>(k, it, it - p.b1, wq, wk, wt); }
    if (it < p.nit) gat_finish<1>(false, k, it - p.b1);
#pragma unroll 1
    for (; it < p.nit; it++) { TSET(it, w == GPW ? 0 : 3); rec_step<false, 1>(k, it - p.b1, it - p.b1, wq, wk, wt); }
}

__device__ __forceinline__ void mma16_top(float* c, uint32_t a0, uint32_t a2, uint32_t b0, uint32_t b1) {
    asm volatile("{.reg .b32 j; mma.sync.aligned.m16n8k16.row.col.f32.bf16.bf16.f32 {%0,%1,%2,%3},{%4,j,%5,j},{%6,%7},{%0,%1,%2,%3};}"
                 : "+f"(c[0]), "+f"(c[1]), "+f"(c[2]), "+f"(c[3]) : "r"(a0), "r"(a2), "r"(b0), "r"(b1));
}
__device__ __forceinline__ void rec_load_tile(uint32_t sb, int X, int j, int s, int head, uint32_t rank) {
    const uint32_t bar = sb + R_BAR + (RB_T + X * 2 + j) * 8;
    mbar_expect1(bar, j ? 4096 : 16384);
    bulk_g2s1(sb + R_T + X * XS + j * 16384, g_qkv[X] + (size_t)(s * 32 + head) * 1536 + (j ? rank * 256 : 512), j ? 4096 : 16384, bar, POL_LAST);
}
__device__ __forceinline__ bool chunk_ready(int X, int j, int s) {
    unsigned v;
    asm volatile("ld.relaxed.gpu.global.u32 %0,[%1];" : "=r"(v) : "l"(cnt_ptr(C_QKV0 + X, (s >> 2) + j * 16)) : "memory");
    return __all_sync(0xffffffffu, v >= (256 >> j));
}
__device__ __forceinline__ uint4 hadd4(uint4 a, uint4 b) { return make_uint4(hadd2(a.x, b.x), hadd2(a.y, b.y), hadd2(a.z, b.z), hadd2(a.w, b.w)); }
struct RecH { uint32_t lw, lm, lq, lv, lu, sa, sp, xb, sb, zero, ts, tn; };
__device__ __forceinline__ void rec_publish(int X, int s) {
    asm volatile("{.reg .pred p; cp.async.bulk.wait_group 0; elect.sync _|p,0xffffffff; @p red.relaxed.gpu.global.add.u32 [%0],4;}" ::"l"(cnt_ptr(C_O0 + X, s >> 2)) : "memory");
}
__device__ __forceinline__ void rec_mattn(const RecH& k, uint32_t dp, int X, int j, int s, bool qk, uint4 (*V)[4], uint4* vm, uint4* kmm) {
    const uint32_t sb = k.sb, to = R_T, lo = R_LOC, ro = R_REM + (s & 1) * 6144;
    const uint32_t bar = sb + R_BAR + (X * 2 + j) * 8;
    uint4 K[2][4];
    mbar_wait(sb + R_BAR + (RB_T + X * 2) * 8, s & 1);
    TS(1);
#pragma unroll
    for (int i = 0; i < 8; i++) K[i >> 2][i & 3] = ldsm4o(k.lm, (to + (i >> 2) * 1024 + ((i >> 1) & 1) * 4096 + (i & 1) * 512));
    asm volatile("cp.async.bulk.wait_group 0;" ::: "memory");
    bar_sync(NB_LOC + X, 320);
    fence_async_smem();
    if (qk) asm volatile("{.reg .pred p; elect.sync _|p,0xffffffff; @p cp.async.bulk.shared::cluster.shared::cta.mbarrier::complete_tx::bytes [%0],[%1],2048,[%2];}"
                         ::"r"(k.xb + dp + ro + j * 1024), "r"(k.xb + lo + j * 1024), "r"(bar + dp + RB_QK * 8) : "memory");
    asm volatile("{.reg .pred p; elect.sync _|p,0xffffffff; @p cp.async.bulk.shared::cluster.shared::cta.mbarrier::complete_tx::bytes [%0],[%1],1024,[%2];}"
                 ::"r"(k.xb + dp + ro + 4096), "r"(k.xb + lo + 4096), "r"(bar + dp + RB_V * 8) : "memory");
    uint4 u[4];
#pragma unroll
    for (int i = 0; i < 4; i++) u[i] = ldsm4o(k.lm, (lo + i * 512));
    TS(2);
    mbar_wait(bar + RB_QK * 8, s & 1);
    TS(3);
    float S[5][4];
#pragma unroll
    for (int i = 0; i < 5; i++) S[i][0] = S[i][1] = S[i][2] = S[i][3] = 0;
    {
        uint4 r[4];
#pragma unroll
        for (int i = 0; i < 4; i++) r[i] = ldsm4o(k.lm, (ro + i * 512));
        SF;
#pragma unroll
        for (int e = 0; e < 2; e++) {
            uint4& km = u[2 * e + 1];
            const uint32_t q0 = hadd2(u[2 * e].x, r[2 * e].x), q1 = hadd2(u[2 * e].y, r[2 * e].y);
            mma16_top(S[0], q0, q1, K[e][0].x, K[e][0].y);
            km.x = hadd2(km.x, r[2 * e + 1].x); km.y = hadd2(km.y, r[2 * e + 1].y);
            SF;
            mma16_top(S[1], q0, q1, K[e][1].x, K[e][1].y);
            const uint32_t q2 = hadd2(u[2 * e].z, r[2 * e].z), q3 = hadd2(u[2 * e].w, r[2 * e].w);
            SF;
            mma16_top(S[2], q0, q1, K[e][2].x, K[e][2].y);
            km.z = hadd2(km.z, r[2 * e + 1].z); km.w = hadd2(km.w, r[2 * e + 1].w);
            SF;
            mma16_top(S[3], q0, q1, K[e][3].x, K[e][3].y);
            mma16_top(S[4], q0, q1, km.x, km.y);
            SF;
#pragma unroll
            for (int i = 0; i < 4; i++) {
                mma16_top(S[i], q2, q3, K[e][i].z, K[e][i].w); SF;
            }
            mma16_top(S[4], q2, q3, km.z, km.w);
            SF;
        }
    }
#define VLD(a, b) _Pragma("unroll") for (int i = (a); i < (b); i++) V[i >> 2][i & 3] = ldsm4to((i & 1) ? lv2 : k.lv, (to + 8192 + (i >> 2) * 4096 + ((i >> 1) & 1) * 1024))
    const uint32_t lv2 = vxor(k.lv, 0x20), lh = k.lw - (vshr(k.lw - k.xb, 1) & 0xf8);
    VLD(0, VE);
    SF;
    const uint32_t sxr = k.sa, sxw = k.sp;
    sts128o(k.lw, sxw, __float_as_uint(S[0][0]), __float_as_uint(S[0][1]), __float_as_uint(S[1][0]), __float_as_uint(S[1][1]));
    SF;
    sts128o(k.lw, (sxw + 512), __float_as_uint(S[2][0]), __float_as_uint(S[2][1]), __float_as_uint(S[3][0]), __float_as_uint(S[3][1]));
    SF;
    sts64o(lh, (sxw + 1024), __float_as_uint(S[4][0]), __float_as_uint(S[4][1]));
    TS(4);
    bar_sync(NB_PAIR + X, 64);
    {
        const uint4 a = lds128o(k.lw, sxr), b = lds128o(k.lw, (sxr + 512));
        const uint2 c = lds64o(lh, (sxr + 1024));
        SF;
        VLD(VE, VF);
        SF;
        S[0][0] += __uint_as_float(a.x); S[0][1] += __uint_as_float(a.y); S[1][0] += __uint_as_float(a.z); S[1][1] += __uint_as_float(a.w);
        S[2][0] += __uint_as_float(b.x); S[2][1] += __uint_as_float(b.y); S[3][0] += __uint_as_float(b.z); S[3][1] += __uint_as_float(b.w);
        S[4][0] += __uint_as_float(c.x); S[4][1] += __uint_as_float(c.y);
    }
    float m = fmaxf(fmaxf(fmaxf(S[0][0], S[0][1]), fmaxf(S[1][0], S[1][1])), fmaxf(fmaxf(S[2][0], S[2][1]), fmaxf(S[3][0], S[3][1])));
    m = fmaxf(m, fmaxf(S[4][0], S[4][1]));
    m = fmaxf(m, __shfl_xor_sync(0xffffffffu, m, 1));
    const float m2 = __shfl_xor_sync(0xffffffffu, m, 2);
    SF;
    VLD(VF, 8);
    uint32_t ok;
    asm volatile("{.reg .pred p; mbarrier.test_wait.parity.shared::cta.b64 p,[%1],%2; selp.u32 %0,1,0,p;}" : "=r"(ok) : "r"(bar + RB_V * 8), "r"(s & 1) : "memory");
    uint4 vr0 = ldsm4o(k.lu, (ro + 4096)), vr1 = ldsm4o(k.lu, (ro + 4608));
    vm[0] = ldsm4o(k.lu, (lo + 4096)); vm[1] = ldsm4o(k.lu, (lo + 4608));
    SF;
    TS(5);
    m = fmaxf(m, m2) * -SC_LOG2E;
    uint32_t P[5];
#pragma unroll
    for (int i = 0; i < 5; i++) P[i] = pack2(ex2(fmaf(S[i][0], SC_LOG2E, m)), ex2(fmaf(S[i][1], SC_LOG2E, m)));
    float o[4][4], l[4] = {0, 0, 0, 0};
    const uint32_t ONE = 0x3f803f80u;
    mma16_top(l, ONE, ONE, P[0], P[1]);
#pragma unroll
    for (int t = 0; t < 4; t++) { o[t][0] = o[t][1] = o[t][2] = o[t][3] = 0; mma16(o[t], V[0][t].x, V[0][t].y, V[0][t].z, V[0][t].w, P[0], P[1]); }
    mma16_top(l, ONE, ONE, P[2], P[3]);
#pragma unroll
    for (int t = 0; t < 4; t++) mma16(o[t], V[1][t].x, V[1][t].y, V[1][t].z, V[1][t].w, P[2], P[3]);
    if (!__all_sync(0xffffffffu, ok)) {
        mbar_wait(bar + RB_V * 8, s & 1);
        vr0 = ldsm4o(k.lu, (ro + 4096)); vr1 = ldsm4o(k.lu, (ro + 4608));
    }
    TS(6);
    vm[0] = hadd4(vm[0], vr0); vm[1] = hadd4(vm[1], vr1);
    mma8(l, ONE, ONE, P[4]);
    mma8(o[0], vm[0].x, vm[0].y, P[4]); mma8(o[1], vm[0].z, vm[0].w, P[4]); mma8(o[2], vm[1].x, vm[1].y, P[4]); mma8(o[3], vm[1].z, vm[1].w, P[4]);
    asm volatile("{.reg .pred p; .reg .b32 t; setp.lt.u32 p,%0,%3; add.u32 t,%0,%4; @p st.shared.v2.f32 [t],{%1,%2};}" ::"r"(lh), "f"(rcp(l[0])), "f"(rcp(l[1])), "r"(k.xb + 32), "r"(R_IL) : "memory");
#pragma unroll
    for (int t = 0; t < 4; t += 2)
        asm volatile("{.reg .b32 t; add.u32 t,%0,%5; stmatrix.sync.aligned.m8n8.x4.trans.shared.b16 [t],{%1,%2,%3,%4};}" ::"r"(k.lm),
                     "r"(pack2(o[t][0], o[t][1])), "r"(pack2(o[t][2], o[t][3])), "r"(pack2(o[t + 1][0], o[t + 1][1])), "r"(pack2(o[t + 1][2], o[t + 1][3])), "r"(R_O - j * 1024 + t * 256) : "memory");
    bar_arrive(NB_O + X, 320);
    PROF(k.lw == k.xb, X * 64 + s);
    TS(7);
    kmm[0] = u[1]; kmm[1] = u[3];
    mbar_expect1(bar + RB_QK * 8, 2048); mbar_expect1(bar + RB_V * 8, 1024);
}
template <int MT>
__device__ __forceinline__ void rec_xattn(const RecH& k, int X, int j, int s, int head, bool early, const uint4 (*V)[4], const uint4* vmm, const uint4* kmm) {
    constexpr int NTL = 3 + 2 * MT;
    const uint32_t sb = k.sb, to = R_T;
    const uint32_t sxw = k.sa, sxr = k.sp;
    const uint32_t lq2 = vxor(k.lq, 0x20);
    float S[NTL][4];
#pragma unroll
    for (int i = 0; i < NTL; i++) S[i][0] = S[i][1] = S[i][2] = S[i][3] = 0;
    {
        uint4 q[2][2], kk[2][NTL];
#define XQ(e) q[e][0] = ldsm4o(k.lq, (to + 16384 + (e) * 1024)); q[e][1] = ldsm4o(lq2, (to + 16384 + (e) * 1024))
#define XK(e, i) kk[e][i] = ldsm4o(k.lm, (to + (e) * 1024 + (((i) - 1) >> 1) * 4096 + (((i) - 1) & 1) * 512))
        kk[0][0] = kmm[0]; kk[1][0] = kmm[1];
        if (XPRE == 0) { bar_sync(NB_XG + X, 320); TS(8); }
        XQ(0);
#pragma unroll
        for (int i = 1; i < NTL; i++) XK(0, i);
        if (XPRE == 1) { bar_sync(NB_XG + X, 320); TS(8); }
        SF;
#pragma unroll
        for (int i = 0; i < NTL; i++) { mma16(S[i], q[0][0].x, q[0][0].y, q[0][0].z, q[0][0].w, kk[0][i].x, kk[0][i].y); SF; }
        q[1][0] = ldsm4o(k.lq, (to + 16384 + 1024));
#pragma unroll
        for (int i = 0; i < NTL; i++) { mma16(S[i], q[0][1].x, q[0][1].y, q[0][1].z, q[0][1].w, kk[0][i].z, kk[0][i].w); SF; if (i + 1 < NTL) XK(1, i + 1); SF; }
        q[1][1] = ldsm4o(lq2, (to + 16384 + 1024));
        if (XPRE == 2) { bar_sync(NB_XG + X, 320); TS(8); }
        SF;
#pragma unroll
        for (int i = 0; i < NTL; i++) { mma16(S[i], q[1][0].x, q[1][0].y, q[1][0].z, q[1][0].w, kk[1][i].x, kk[1][i].y); SF; }
#pragma unroll
        for (int i = 0; i < NTL; i++) { mma16(S[i], q[1][1].x, q[1][1].y, q[1][1].z, q[1][1].w, kk[1][i].z, kk[1][i].w); SF; }
    }
#pragma unroll
    for (int i = 0; i < NTL; i++) sts128o(k.lw, (sxw + i * 512), __float_as_uint(S[i][0]), __float_as_uint(S[i][1]), __float_as_uint(S[i][2]), __float_as_uint(S[i][3]));
    SF;
    if (XPRE == 3) bar_sync(NB_XG + X, 320); else bar_sync(NB_PAIR + 2 + X, 64);
    TS(9);
    if (early) rec_load_tile(sb, X, j, s + 1, head, MT);
#pragma unroll
    for (int i = 0; i < NTL; i++) {
        const uint4 r = lds128o(k.lw, (sxr + i * 512));
        S[i][0] += __uint_as_float(r.x); S[i][1] += __uint_as_float(r.y); S[i][2] += __uint_as_float(r.z); S[i][3] += __uint_as_float(r.w);
    }
    const int g = vshr(k.lw - k.xb, 6) & 7, c = (vshr(k.lw, 4) ^ (g >> 1)) & 3;
    const float NEG = -__int_as_float(0x7f800000);
    if (2 * c > g) { S[NTL - 2][0] = NEG; S[NTL - 1][2] = NEG; }
    if (2 * c + 1 > g) { S[NTL - 2][1] = NEG; S[NTL - 1][3] = NEG; }
    float m0 = fmaxf(S[0][0], S[0][1]), m1 = fmaxf(S[0][2], S[0][3]);
#pragma unroll
    for (int i = 1; i < NTL; i++) { if (i < NTL - 1) m0 = fmaxf(m0, fmaxf(S[i][0], S[i][1])); m1 = fmaxf(m1, fmaxf(S[i][2], S[i][3])); }
    m0 = fmaxf(m0, __shfl_xor_sync(0xffffffffu, m0, 1)); m1 = fmaxf(m1, __shfl_xor_sync(0xffffffffu, m1, 1));
    m0 = fmaxf(m0, __shfl_xor_sync(0xffffffffu, m0, 2)); m1 = fmaxf(m1, __shfl_xor_sync(0xffffffffu, m1, 2));
    m0 *= -SC_LOG2E; m1 *= -SC_LOG2E;
    uint32_t P[NTL][2];
#pragma unroll
    for (int i = 0; i < NTL; i++) {
        P[i][0] = i < NTL - 1 ? pack2(ex2(fmaf(S[i][0], SC_LOG2E, m0)), ex2(fmaf(S[i][1], SC_LOG2E, m0))) : 0u;
        P[i][1] = pack2(ex2(fmaf(S[i][2], SC_LOG2E, m1)), ex2(fmaf(S[i][3], SC_LOG2E, m1)));
    }
    float l[4] = {0, 0, 0, 0};
#pragma unroll
    for (int i = 0; i < NTL; i++) mma8(l, P[i][0], P[i][1], 0x3f803f80u);
    const float l0 = rcp(l[0]), l1 = rcp(l[2]);

#pragma unroll
    for (int e = 0; e < 2; e++) {
        const uint4 vm = vmm[e];
        uint32_t u[2][4];
#pragma unroll
        for (int n = 0; n < 4; n++) {
            float a[4] = {0, 0, 0, 0};
#pragma unroll
            for (int m = 0; m <= MT; m++) {
                const uint4 v = V[m][e * 2 + (n >> 1)];
                mma8(a, P[1 + 2 * m][0], P[1 + 2 * m][1], (n & 1) ? v.y : v.x); mma8(a, P[2 + 2 * m][0], P[2 + 2 * m][1], (n & 1) ? v.w : v.z);
            }
            mma8(a, P[0][0], P[0][1], n == 0 ? vm.x : n == 1 ? vm.y : n == 2 ? vm.z : vm.w);
            u[0][n] = pack2(a[0] * l0, a[1] * l0); u[1][n] = pack2(a[2] * l1, a[3] * l1);
        }
        sts128o(k.lw, sxr + e * 512, u[0][0], u[0][1], u[0][2], u[0][3]); sts128o(k.lw, sxr + e * 512 + 1024, u[1][0], u[1][1], u[1][2], u[1][3]);
    }
    TS(10);
}
__device__ __forceinline__ void rec_attn(const Params& p, uint32_t sb, int X, int j, int head, uint32_t rank) {
    const int lane = threadIdx.x & 31;
    RecH k;
    k.xb = sb + X * XS + j * 1024;
    const uint32_t x2 = k.xb + j * 1024;
    k.lw = __shfl_sync(0xffffffffu, x2 + (lane ^ (lane >> 3)) * 16, lane);
    k.lm = __shfl_sync(0xffffffffu, x2 + ((lane & 7) * 4 + ((lane >> 3) ^ ((lane & 7) >> 1))) * 16, lane);
    k.lq = __shfl_sync(0xffffffffu, x2 + ((lane >> 3) & 1) * 512 + ((lane & 7) * 4 + ((lane >> 4) ^ ((lane & 7) >> 1))) * 16, lane);
    k.lv = __shfl_sync(0xffffffffu, x2 + (lane >> 4) * 512 + ((lane & 7) * 4 + (((lane >> 3) & 1) ^ ((lane & 7) >> 1))) * 16, lane);
    k.lu = __shfl_sync(0xffffffffu, k.xb + ((lane & 6) * 4 + (((lane >> 3) * 2 + (lane & 1)) ^ (lane & 6))) * 16, lane);
    k.sa = __shfl_sync(0xffffffffu, R_SX + j * 512, 0); k.sp = __shfl_sync(0xffffffffu, R_SX + 2560 - j * 4608, 0);
    k.sb = sb; k.zero = p.zero;
    const uint32_t dp = mapa(sb, rank ^ 1) - sb;
    char* zp = acc_base() + (j ? X * 32768 + acc_main(rank, head * 8) : X * 1024 + acc_extra(rank, head * 8));
    mbar_expect1(sb + R_BAR + (RB_QK + X * 2 + j) * 8, 2048); mbar_expect1(sb + R_BAR + (RB_V + X * 2 + j) * 8, 1024);
    bool early = false;
#pragma unroll 1
    for (int s = 0; s < 64; s++) {
        TSET(X ? s + p.b1 : s, j == GPJ ? 1 + X : 3);
        TS(0);
        if (!early) {
            if (!j) wait_cnt_warp(cnt_ptr(C_QKV0 + X, s >> 2), 256);
            early = !j || chunk_ready(X, 1, s);
            if (early) rec_load_tile(sb, X, j, s, head, rank);
        }
        if (PFD && s < 63 && early && (PFB || !X) && ((s & 3) != 3 || chunk_ready(X, j, s + 1)))
            asm volatile("{.reg .pred p; elect.sync _|p,0xffffffff; @p cp.async.bulk.prefetch.L2.global.L2::cache_hint [%0],%1,%2;}"
                         ::"l"(g_qkv[X] + (size_t)((s + 1) * 32 + head) * 1536 + (j ? rank * 256 : 512 + rank * 512)), "r"(j ? 4096 : 8192), "l"(POL_LAST) : "memory");
        uint4 V[2][4], vm[2], km[2];
        rec_mattn(k, dp, X, j, s, BKA && !X && s >= p.b1, V, vm, km);
        if (!early) { wait_cnt_warp(cnt_ptr(C_QKV0 + X, (s >> 2) + 16), 128); rec_load_tile(sb, X, 1, s, head, rank); }
        early = s < 63 && ((s & 3) != 3 || chunk_ready(X, j, s + 1));
        mbar_wait(sb + R_BAR + (RB_T + X * 2 + 1) * 8, s & 1);
        if (rank) rec_xattn<1>(k, X, j, s, head, early, V, vm, km); else rec_xattn<0>(k, X, j, s, head, early, V, vm, km);
        fence_async_smem();
        __syncwarp();
        asm volatile("{.reg .pred p; elect.sync _|p,0xffffffff;\n"
                     "@p cp.async.bulk.global.shared::cta.bulk_group.L2::cache_hint [%0],[%1],2048,%2;\n"
                     "@p cp.async.bulk.global.shared::cta.bulk_group [%3],[%4],%5;\n"
                     "cp.async.bulk.commit_group;}"
                     ::"l"(g_o[X] + ((s >> 2) * 64 + head * 2 + j) * 1024 + ((s & 3) * 2 + rank) * 128), "r"(x2 + k.sp),
                       "l"((X && s < 40) ? POL_LATE : POL_SOON), "l"(zp + acc_slot(s + 2)), "r"(sb + R_Z), "r"(j ? 128 : 32) : "memory");
        if ((s & 3) == 3) {
            if (!early && s < 63 && chunk_ready(X, j, s + 1)) { rec_load_tile(sb, X, j, s + 1, head, rank); early = true; }
            rec_publish(X, s);
            PROF(lane == 0 && j, 3900 + X * 16 + (s >> 2));
        }
    }
}

__device__ __forceinline__ void rec_init(const Params& p, uint32_t sb, int head, uint32_t rank) {
    const uint32_t b = sb + R_BAR;
    const int i = threadIdx.x - 320;
    if (i >= 0 && i < RB_N) {
        mbar_init(b + i * 8, i == RB_MB ? 8 : 1);
        asm volatile("fence.mbarrier_init.release.cluster;" ::: "memory");
    }
    if (i == 0) mbar_expect(b + RB_INIT * 8, 196608);
    if (i >= 0 && i < 32) sts32(sb + R_Z + i * 4, 0);
}

#define NSTGN 8
constexpr int NSTG = NSTGN, STG_B = 24576;
#define LAGH 3
constexpr int NSB = 8;
constexpr int B_OUT = NSTG * STG_B  , B_UT = B_OUT, B_YT = B_UT + 16384, B_SP = B_YT  ,
              B_ST = 229376  , B_BAR = 231936;
static_assert(B_OUT + NSB * 4096 <= B_ST && B_ST + 2048 <= B_BAR && B_YT + 10240 <= B_ST, "smem map");
enum { BB_FULL = 0, BB_EMPTY = 8, BB_SF = 16  , BB_GO = 18, BB_DONE = 20  , BB_IDLE = 22  , BB_N = 30 };
enum { NB_REL = 2  , NB_C = 11, NB_WG = 12  , NB_PH = 14 };

__device__ __forceinline__ void bulk_init(uint32_t sb) {
    const int i = threadIdx.x - 320;
    if (i >= 0 && i < BB_N) {
        mbar_init(sb + B_BAR + i * 8, (i >= BB_EMPTY && i < BB_EMPTY + NSTG) ? 4 : i >= BB_DONE ? 4 : 1);
        asm volatile("fence.mbarrier_init.release.cluster;" ::: "memory");
    }
}

struct Task { int type, layer, ch, a, b, c, blk; bool pair, dry; };
__device__ __forceinline__ Task task_of(uint32_t tk, uint32_t rank) {
    Task t;
    t.type = tk & 7; t.layer = (tk >> 3) & 1; t.a = (tk >> 8) & 255; t.b = (tk >> 16) & 255; t.c = (tk >> 24) & 127; t.dry = tk >> 31;
    t.pair = t.type <= T_OP && (t.c & 64);
    t.ch = ((tk >> 4) & 15) + (t.pair ? rank : 0);
    t.blk = t.type == T_QKV ? t.a + (t.pair ? 0 : rank) : 192 + (t.pair ? (t.c >> 2) & 4 : rank * 4);
    return t;
}
__device__ __forceinline__ int qkv_blk(const Task& t, int u) {
    const int v = t.blk + (t.pair ? 1 : 2 * t.c) * u;
    return 2 * (v < 64 ? v + 32 : v - 64);
}
__device__ __forceinline__ void bulk_producer(const Params& p, uint32_t sb, int cl, uint32_t rank) {
    int st = 0; uint32_t ph = 1;
    const int tag = __shfl_sync(0xffffffffu, lds32(sb + S_TAG), 0);
    bool gated = false;
#define ACQ(bytes) do { mbar_wait(sb + B_BAR + (BB_EMPTY + st) * 8, ph); mbar_expect1(sb + B_BAR + (BB_FULL + st) * 8, bytes); } while (0)
#define NEXT do { if (++st == NSTG) { st = 0; ph ^= 1; } } while (0)
#pragma unroll 1
    for (int ti = 0; ti < MAXT; ti++) {
        const Task t = task_of(p.task[cl][ti], rank);
        const int layer = t.layer, ch = t.ch;
        if (t.type == T_END) break;
        if (t.type <= T_OP) {
            const bool qkv = t.type == T_QKV;
            const int nh = (qkv ? 8 : 2) * t.b;
            const unsigned* dep = cnt_ptr(qkv ? (layer ? C_CV : C_ST) : C_O0 + layer, ch);
            const unsigned need = qkv ? (layer ? 32 : ch < 2 ? 0 : 16) : 512;
            const uint16_t mb = t.pair ? 3 : 1 << rank, ma = t.pair ? 1 << rank : 3;
            int pend = qkv ? 2 : 0;
            bool wait = false;
            if (!t.dry) {
                unsigned v = 0;
                if (gated) asm volatile("ld.relaxed.gpu.global.u32 %0,[%1];" : "=r"(v) : "l"(dep) : "memory");
                wait = !gated || !__all_sync(0xffffffffu, v >= need);
                if (wait) pend = min(nh, gated ? NSTG : 4);
            }
#define DEPW if (wait) { if (!gated) { wait_cnt_warp(g_gate, lds32(sb + S_GATE)); gated = true; } if (need) wait_cnt_warp(dep, need); }
            if (qkv) {
#pragma unroll 1
                while (st) { ACQ(0); NEXT; }
#pragma unroll 1
                for (int h = 0; h < nh; h++) {
                    const int blk = qkv_blk(t, h >> 3);
                    ACQ(16384 + (h < 2 ? (layer ? 8192 : 1024) : 0));
                    if (!t.pair || !rank) tma3d_mc(sb + st * STG_B, &p.t3[1][blk >> 6], (h & 7) * 64, blk & 63, sb + B_BAR + (BB_FULL + st) * 8, mb);
                    if (!t.pair || rank) tma3d_mc(sb + st * STG_B + 8192, &p.t3[1][blk >> 6], (h & 7) * 64 + 32, blk & 63, sb + B_BAR + (BB_FULL + st) * 8, mb);
                    NEXT;
                    if (h == pend - 1) {
                        DEPW;
                        const float2* sp = g_st[layer] + ch * 2048 + (need ? 0 : tag * 256);
                        bulk_g2s1(sb + 16384, sp, layer ? 8192 : 1024, sb + B_BAR + BB_FULL * 8, POL_N);
                        bulk_g2s1(sb + STG_B + 16384, sp + (layer ? 1024 : 128), layer ? 8192 : 1024, sb + B_BAR + (BB_FULL + 1) * 8, POL_N);
                    }
                }
                continue;
            }
            if (PFC && !layer && (t.c & 15) < 8) {
                const int q = (t.c & 15) * 2 + rank;
                asm volatile("{.reg .pred p; elect.sync _|p,0xffffffff; @p cp.async.bulk.prefetch.L2.global [%0],8192; @p cp.async.bulk.prefetch.L2.global [%1],%2;}"
                             ::"l"(g_xA[0] + (ch * 16 + q) * 512), "l"(g_P + q * 16 * 32 * PW), "r"((2 + (ch & 1)) * 32 * PW * 4) : "memory");
            }
            const CUtensorMap *tb = &p.t3[t.pair][3], *ta = &p.ta[t.pair];
            const uint32_t db = sb + 8192 + (t.pair ? rank * 8192 : 0), da = sb + (t.pair ? 0 : rank * 4096);
            const int zb = (t.blk & 63) + (t.pair ? rank * 2 : 0), ya = 4096 + ((layer * 16 + ch) * 64 + t.a) * 16 + (t.pair ? 0 : rank * 8), row = t.a * 64;
            int h = 0;
            const int s0 = st;
#pragma unroll 1
            for (; h < pend; h++) { ACQ(STG_B); tma3d_mc(db + st * STG_B, tb, row + h * 32, zb, sb + B_BAR + (BB_FULL + st) * 8, mb); NEXT; }
            DEPW;
#pragma unroll 1
            for (int k = 0; k < pend; k++) {
                const int s2 = (s0 + k) & (NSTG - 1);
                tma2d_mc(da + s2 * STG_B, ta, (k & 1) * 256, ya + (k >> 1) * 16, sb + B_BAR + (BB_FULL + s2) * 8, ma, POL_LAST);
            }
#pragma unroll 1
            for (; h < nh; h++) {
                ACQ(STG_B);
                tma3d_mc(db + st * STG_B, tb, row + h * 32, zb, sb + B_BAR + (BB_FULL + st) * 8, mb);
                tma2d_mc(da + st * STG_B, ta, (h & 1) * 256, ya + (h >> 1) * 16, sb + B_BAR + (BB_FULL + st) * 8, ma, POL_LAST);
                NEXT;
            }
#pragma unroll 1
            for (h = 0; h < 4 && !layer; h++) { ACQ(0); NEXT; }
        } else if (t.type == T_CV) {
            const int q = t.a + rank;
            if (!gated && !t.dry) { wait_cnt_warp(g_gate, lds32(sb + S_GATE)); gated = true; }
            if (layer) {
                wait_cnt_warp(cnt_ptr(C_U, ch - 2), 32);
#pragma unroll 1
                for (int j = ch + 1; j >= 2; j--) {
                    ACQ(16 * PW * 4 + (j > 2 ? 4096 : 0));
                    bulk_g2s1(sb + st * STG_B, g_P + (((q >> 1) * 16 + j) * 2 + (q & 1)) * 16 * PW, 16 * PW * 4, sb + B_BAR + (BB_FULL + st) * 8, POL_N);
                    if (j > 2) bulk_g2s1(sb + st * STG_B + 12288, g_u + (((q >> 1) * 16 + ch + 1 - j) * 2 + (q & 1)) * 256, 4096, sb + B_BAR + (BB_FULL + st) * 8, POL_N);
                    NEXT;
                }
            } else {
#pragma unroll 1
                for (int j = min(ch, 1 + (ch & 1)); j >= 0; j--) {
                    if (j == 0 && ch >= 2) {
                        if (!t.dry) wait_cnt_warp(cnt_ptr(C_H, ch & ~1), 64);
#pragma unroll 1
                        for (int i = 0; i < ((ch & 1) || ch == 2 ? 1 : 2); i++) {
                            ACQ(16384);
                            bulk_g2s1(sb + st * STG_B, g_carry[i] + (ch * 16 + q) * 1024, 16384, sb + B_BAR + (BB_FULL + st) * 8, POL_LAST);
                            NEXT;
                        }
                    }
                    ACQ(32 * PW * 4);
                    bulk_g2s1(sb + st * STG_B, g_P + (q * 16 + j) * 32 * PW, 32 * PW * 4, sb + B_BAR + (BB_FULL + st) * 8, POL_N);
                    NEXT;
                }
            }
        }
    }
}

__device__ __forceinline__ uint4* qkv_dst(int layer, int ch, int w, int blk);
__device__ __forceinline__ uint4* op_dst(int layer, int ch, int slot, int w, uint32_t rank);
__device__ __forceinline__ uint64_t out_pol(int type, int layer, int ch) { return (type == T_QKV ? (!layer && ch > 1) : (layer && ch < 10)) ? POL_LATE : POL_SOON; }
__device__ __forceinline__ void bulk_relay(const Params& p, uint32_t sb, int cl) {
    for (int ti = 0; ti < MAXT; ti++) {
        const int type = p.task[cl][ti] & 7;
        if (type == T_END) break;
        if (type != T_QKV) continue;
        bar_sync(NB_PH, 96);
        const uint32_t ph = lds32(sb + B_ST + 8);
#pragma unroll 1
        for (int h = 2; h < 8; h++) {
            mbar_wait(sb + B_BAR + (BB_FULL + h) * 8, ph);
            if (h == 4 || h == 7) { bar_arrive(NB_REL + (h == 7) * 2, 160); bar_arrive(NB_REL + (h == 7) * 2 + 1, 160); }
        }
    }
}
__device__ __forceinline__ void bulk_release(const Params& p, uint32_t sb, int cl, uint32_t rank, int wg) {
    int nd = 0;
    for (int ti = 0; ti < MAXT; ti++) {
        const Task t = task_of(p.task[cl][ti], rank);
        const int type = t.type, layer = t.layer, ch = t.ch;
        if (type == T_END) break;
        if (type == T_FIN || (type == T_OP && (t.c & 32))) continue;
        if (type == T_OP && !layer) {
            mbar_wait(sb + B_BAR + (BB_DONE + wg) * 8, nd & 1);
            nd++;
            const int s0 = __shfl_sync(0xffffffffu, lds32(sb + B_ST + wg * 4), 0) + wg * 2;
            fence_async_smem();
#pragma unroll 1
            for (int w = 0; w < 4; w++)
                asm volatile("{.reg .pred p; elect.sync _|p,0xffffffff; @p cp.async.bulk.global.shared::cta.bulk_group.L2::cache_hint [%0],[%1],8192,%2; cp.async.bulk.commit_group;}"
                             ::"l"(op_dst(0, ch, t.c & 15, wg * 4 + w, rank)), "r"(sb + ((s0 + (w >> 1)) & (NSTG - 1)) * STG_B + (w & 1) * 8192), "l"(POL_SOON) : "memory");
            mbar_arrive1(sb + B_BAR + (BB_SF + wg) * 8);
            asm volatile("{.reg .pred p; elect.sync _|p,0xffffffff;\n"
                         "cp.async.bulk.wait_group 3; @p red.relaxed.gpu.global.add.u32 [%0],1; cp.async.bulk.wait_group 2; @p red.relaxed.gpu.global.add.u32 [%0+64],1;\n"
                         "cp.async.bulk.wait_group 1; @p red.relaxed.gpu.global.add.u32 [%0+128],1; cp.async.bulk.wait_group 0; @p red.relaxed.gpu.global.add.u32 [%0+192],1;}"
                         ::"l"(cnt_ptr(C_OP0 + rank * 2 + wg, ch)) : "memory");
#pragma unroll 1
            for (int i = 0; i < 8; i++) mbar_arrive1_cluster(mapa(sb + B_BAR + (BB_EMPTY + ((s0 + (i >> 2)) & (NSTG - 1))) * 8, i & 1));
            continue;
        }
#pragma unroll 1
        for (int u = 0; u < (type == T_QKV ? t.b : 1); u++) {
            const int blk = qkv_blk(t, u);
            unsigned* cnt = cnt_ptr(type == T_QKV ? C_QKV0 + layer : type == T_OP ? C_OP1 : layer ? C_H : C_CV, ch + (type == T_QKV && blk < 64 ? 16 : 0));
            const uint4* dst = type == T_QKV ? qkv_dst(layer, ch, wg * 4, blk) : op_dst(1, ch, t.c & 15, wg * 4, (t.blk >> 2) & 1) + 256;
            mbar_wait(sb + B_BAR + (BB_DONE + wg) * 8, nd & 1);
            nd++;
            if (type != T_CV) {
                fence_async_smem();
#pragma unroll
                for (int w = 0; w < 4; w++)
                    asm volatile("{.reg .pred p; elect.sync _|p,0xffffffff; @p cp.async.bulk.global.shared::cta.bulk_group.L2::cache_hint [%0],[%1],4096,%2;}"
                                 ::"l"(dst + (type == T_QKV ? (w >> 1) * 49152 + (w & 1) * 256 : w * 1024)), "r"(sb + B_OUT + (wg * 4 + w) * 4096), "l"(out_pol(type, layer, ch)) : "memory");
                asm volatile("cp.async.bulk.commit_group; cp.async.bulk.wait_group 0;" ::: "memory");
            }
            if (type != T_QKV) fence_async();
            if (!t.dry) asm volatile("{.reg .pred p; elect.sync _|p,0xffffffff; @p red.relaxed.gpu.global.add.u32 [%0],%1;}" ::"l"(cnt), "r"(type == T_QKV ? 2 : type == T_OP ? t.b : 1) : "memory");
            PROF(wg && (threadIdx.x & 31) == 0 && (type == T_CV || u + 2 == t.b), 3900 + ti);
            if (type == T_CV && !layer && !t.dry) {
                asm volatile("{.reg .pred p; elect.sync _|p,0xffffffff; @p cp.async.bulk.global.shared::cta.bulk_group [%0],[%1],4096;\n"
                             "cp.async.bulk.commit_group; cp.async.bulk.wait_group 0; @p red.relaxed.gpu.global.add.u32 [%2],1;}"
                             ::"l"(g_u + ((t.a + rank) * 16 + ch) * 512 + wg * 256), "r"(sb + B_UT + (ch & 1) * 8192 + wg * 4096), "l"(cnt_ptr(C_U, ch)) : "memory");
            }
            mbar_arrive1(sb + B_BAR + (BB_SF + wg) * 8);
        }
        PROF(wg && (threadIdx.x & 31) == 0, 3600 + ti * 4 + 3);
    }
}

__device__ __forceinline__ void stage_release(uint32_t sb, int w, int st) {
    if (!(w & 2)) mbar_arrive1_cluster(mapa(sb + B_BAR + (BB_EMPTY + st) * 8, w & 1));
}
template <bool ACC>
__device__ __forceinline__ void gemm_run(float* acc, uint32_t sb, int w, int h0, int h1, uint32_t& r0, uint32_t& r1, int& st, uint32_t& ph) {
    const uint64_t da0 = mkdesc(sb + (w >> 2) * 4096, 16, 512, 2), db0 = mkdesc(sb + 8192, 4096, 1024, 1);
    const uint32_t rel0 = mapa(sb + B_BAR + BB_EMPTY * 8, w & 1);
#pragma unroll 1
    for (int h = h0; h < h1; h++) {
        const uint64_t da = da0 + st * (STG_B >> 4), db = db0 + st * (STG_B >> 4);
        mbar_wait(sb + B_BAR + (BB_FULL + st) * 8, ph);
        if (ACC) wg_wait<1>();
        wg_fence();
        wgmma256<ACC>(acc, da, db);
        wgmma256<true>(acc, da + 2, db + 128);
        wg_commit();
        if (ACC) mbar_arrive1_cluster((w == 2 && h == LAGH - 1) ? sb + B_BAR + BB_GO * 8 : r0);
        r0 = r1;
        if (!(w & 2)) r1 = rel0 + st * 8;
        if (++st == NSTG) { st = 0; ph ^= 1; }
    }
}

__device__ __forceinline__ uint4* qkv_dst(int layer, int ch, int w, int blk) {
    return g_qkv[layer] + (size_t)((ch * 4 + (w >> 1)) * 32 + ((blk & 63) >> 1)) * 1536 + (blk >> 6) * 512 + (w & 1) * 256;
}
__device__ __forceinline__ uint4* op_dst(int layer, int ch, int slot, int w, uint32_t rank) {
    return g_pp[layer] + (size_t)(ch * MAXSPLIT + slot) * 8192 + (w * 32 + rank * 16) * 32;
}
__device__ __forceinline__ uint32_t ln2(uint32_t x, uint32_t m, uint32_t rh, uint32_t rl) {
    uint32_t d; asm volatile("{.reg .b32 t,u; sub.rn.bf16x2 t,%1,%2; mul.rn.bf16x2 u,t,%4; fma.rn.bf16x2 %0,t,%3,u;}" : "=r"(d) : "r"(x), "r"(m), "r"(rh), "r"(rl)); return d;
}
__device__ __forceinline__ void qkv_task(uint32_t sb, int w, int layer, int ch, int nu, int& ng, int& nd, uint32_t& ph, int ti, uint32_t zero) {
    constexpr int type = T_QKV;
    static_assert(NSTG == 8, "ring");
    const int lane = threadIdx.x & 31;
    const uint64_t db0 = mkdesc(sb, 4096, 1024, 1);
    const uint32_t rel = (w & 2) ? sb + B_BAR + BB_IDLE * 8 : mapa(sb + B_BAR + BB_EMPTY * 8, w & 1), full = sb + B_BAR + BB_FULL * 8;
    const uint32_t lo = sb + B_OUT + w * 4096 + (lane ^ (lane >> 3)) * 16;
    const uint4* xa = g_xA[layer] + (ch * 8 + w) * 1024 + lane;
    uint32_t m0, m1, h0, h1, l0, l1;
    uint4 A[32];
    {
        mbar_wait(full, ph);
        mbar_wait(full + 8, ph);
        CPROF(1);
        const uint32_t sa = sb + (lane >> 4) * STG_B + 16384 + (w * 16 + (lane & 15)) * 8;
        uint2 v[8];
#pragma unroll
        for (int i = 0; i < 8; i++) v[i] = lds64(sa + i * 1024 * layer);
#pragma unroll
        for (int i = 0; i < 4 * QB1; i++) A[i] = ldcg128(xa + i * 32);
        bar_sync(NB_WG + (w >> 2), 128);
        float sm = 0, M2 = 0, D = 0;
#pragma unroll
        for (int i = 0; i < 8; i++) { sm += __uint_as_float(v[i].x); M2 += __uint_as_float(v[i].y); }
        if (!layer) { sm = __uint_as_float(v[0].x); M2 = __uint_as_float(v[0].y); }
        sm += __shfl_xor_sync(0xffffffffu, sm, 16);
#pragma unroll
        for (int i = 0; i < 8; i++) { const float d = __uint_as_float(v[i].x) * (1.f / 32.f) - sm * (1.f / 512.f); D += 32.f * d * d; }
        M2 += layer ? D : sm * sm * (-1.f / 1024.f);
        M2 = fmaxf(M2 + __shfl_xor_sync(0xffffffffu, M2, 16), 0.f);
        const float2 o = ln_finish(sm * (1.f / 512.f), M2 * (1.f / 512.f));
        const float r = rcp(o.y), rh = rbf(r);
        const uint32_t mm = pack2(o.x, o.x), hl = pack2(r - rh, rh);
        m0 = __shfl_sync(0xffffffffu, mm, lane >> 2); m1 = __shfl_sync(0xffffffffu, mm, (lane >> 2) + 8);
        l0 = __shfl_sync(0xffffffffu, hl, lane >> 2); l1 = __shfl_sync(0xffffffffu, hl, (lane >> 2) + 8);
        h0 = __byte_perm(l0, 0, 0x3232); h1 = __byte_perm(l1, 0, 0x3232); l0 = __byte_perm(l0, 0, 0x1010); l1 = __byte_perm(l1, 0, 0x1010);
    }
    float acc[64];
#define QNRM(i) A[i] = make_uint4(ln2(A[i].x, m0, h0, l0), ln2(A[i].y, m1, h1, l1), ln2(A[i].z, m0, h0, l0), ln2(A[i].w, m1, h1, l1))
#pragma unroll
    for (int h = 0; h < 8; h++) {
        const uint64_t db = db0 + h * (STG_B >> 4);
        const int b0 = h == 0 ? QB1 : h == QB1 ? QB2 : h == QB2 ? QB3 : 8, b1 = h == 0 ? QB2 : h == QB1 ? QB3 : 8;
        if (b0 < b1) {
            const uint4* xb = xa + (A[4 * b0 - 1].x & zero);
#pragma unroll
            for (int i = 4 * b0; i < 4 * b1; i++) A[i] = ldcg128(xb + i * 32);
            bar_sync(NB_WG + (w >> 2), 128);
        }
        QNRM(4 * h); QNRM(4 * h + 1); QNRM(4 * h + 2); QNRM(4 * h + 3);
        if (h == 2 || h == 5) bar_sync(NB_REL + (h == 5) * 2 + (w >> 2), 160);
        if (h) wg_wait<1>();
        wg_fence();
        if (h) wgmma128r<true>(acc, A[4 * h], db); else wgmma128r<false>(acc, A[0], db);
        wgmma128r<true>(acc, A[4 * h + 1], db + 128);
        wgmma128r<true>(acc, A[4 * h + 2], db + 512);
        wgmma128r<true>(acc, A[4 * h + 3], db + 640);
        wg_commit();
        if (h >= 2) mbar_arrive1_cluster(rel + (h - 2) * 8);
    }
    ph ^= 1;
#pragma unroll 1
    for (int u = 1;; u++) {
        mbar_wait(sb + B_BAR + (BB_SF + (w >> 2)) * 8, (nd & 1) ^ 1);
        if (u < nu) mbar_wait(full, ph);
        wg_wait<1>();
        mbar_arrive1_cluster(rel + 48);
        wg_wait<0>();
        mbar_arrive1_cluster(rel + 56);
        uint4 o[8];
#pragma unroll
        for (int n = 0; n < 8; n++) {
            const float* a = acc + (n >> 1) * 16 + (n & 1) * 2;
            o[n] = make_uint4(pack2(a[0], a[1]), pack2(a[4], a[5]), pack2(a[8], a[9]), pack2(a[12], a[13]));
            sts128(lo + n * 512, o[n].x, o[n].y, o[n].z, o[n].w);
        }
        __syncwarp();
        mbar_arrive1(sb + B_BAR + (BB_DONE + (w >> 2)) * 8);
        nd++;
        CPROF(min(2 + u, 7));
        if (u == nu) break;
        if (LAGQ) { if (w >> 2) mbar_wait(sb + B_BAR + BB_GO * 8, ng & 1); ng++; }
        const uint64_t db1 = mkdesc(sb + (u >> 10), 4096, 1024, 1);
#pragma unroll
        for (int h = 0; h < 8; h++) {
            const uint64_t db = db1 + h * (STG_B >> 4);
            if (h) { mbar_wait(full + h * 8, ph); wg_wait<1>(); }
            wg_fence();
            if (h) wgmma128r<true>(acc, A[4 * h], db); else wgmma128r<false>(acc, A[0], db);
            wgmma128r<true>(acc, A[4 * h + 1], db + 128);
            wgmma128r<true>(acc, A[4 * h + 2], db + 512);
            wgmma128r<true>(acc, A[4 * h + 3], db + 640);
            wg_commit();
            if (h >= 2) mbar_arrive1_cluster(rel + (h - 2) * 8);
            if (h == LAGQ - 1 && w == 2) mbar_arrive1(sb + B_BAR + BB_GO * 8);
        }
        ph ^= 1;
    }
}

template <int NB>
__device__ __forceinline__ void load_resid(uint32_t* r, int layer, int ch, int w, int cb) {
#pragma unroll
    for (int i = 0; i < NB; i++) {
        const uint4 v = ldcg128(g_xA[layer] + ((ch * 8 + w) * 32 + cb + i) * 32 + (threadIdx.x & 31));
        r[4 * i] = v.x; r[4 * i + 1] = v.y; r[4 * i + 2] = v.z; r[4 * i + 3] = v.w;
    }
}
template <int NS>
__device__ __forceinline__ void part_load(uint4* v, int layer, int ch, int w, int cb, int ns) {
    const uint4* src = g_pp[layer] + (size_t)ch * MAXSPLIT * 8192 + (w * 32 + cb) * 32 + (threadIdx.x & 31);
#pragma unroll
    for (int i = 0; i < 2 * NS; i++) {
        asm volatile("{.reg .pred p; .reg .b128 t; setp.gt.s32 p,%6,0; mov.b128 t,{0,0,0,0}; @p ld.relaxed.gpu.global.L2::cache_hint.b128 t,[%4],%5; mov.b128 {%0,%1,%2,%3},t;}"
                     : "=r"(v[i].x), "=r"(v[i].y), "=r"(v[i].z), "=r"(v[i].w) : "l"(src + (i / NS) * 32 + (i % NS) * 8192), "l"(POL_LAST), "r"(ns - i % NS) : "memory");
    }
}
template <int NS>
__device__ __forceinline__ void part_sum(float* x, const uint4* v, const uint32_t* r) {
    const int dg = ((threadIdx.x & 31) >> 2) - 2 * (threadIdx.x & 3);
    const uint32_t idm = dg == 0 ? 0x00003f80u : dg == 1 ? 0x3f800000u : 0u;
#pragma unroll
    for (int b = 0; b < 2; b++) {
        float* y = x + b * 8;
#pragma unroll
        for (int i = 0; i < 8; i++) y[i] = 0;
#pragma unroll
        for (int s = 0; s < NS; s++) { mma8(y, v[b * NS + s].x, v[b * NS + s].y, idm); mma8(y + 4, v[b * NS + s].z, v[b * NS + s].w, idm); }
#pragma unroll
        for (int i = 0; i < 4; i++) { y[2 * i] = rbf(rbf(y[2 * i]) + blo(r[b * 4 + i])); y[2 * i + 1] = rbf(rbf(y[2 * i + 1]) + bhi(r[b * 4 + i])); }
    }
}

__device__ __forceinline__ float4 row_stats32(const float* x) {
    float a = (x[0] + x[1]) + (x[4] + x[5]) + (x[8] + x[9]) + (x[12] + x[13]);
    float b = (x[2] + x[3]) + (x[6] + x[7]) + (x[10] + x[11]) + (x[14] + x[15]);
    a += __shfl_xor_sync(0xffffffffu, a, 1); b += __shfl_xor_sync(0xffffffffu, b, 1);
    a += __shfl_xor_sync(0xffffffffu, a, 2); b += __shfl_xor_sync(0xffffffffu, b, 2);
    const float ma = a * (1.f / 32.f), mb = b * (1.f / 32.f);
    float qa = 0, qb = 0;
#pragma unroll
    for (int i = 0; i < 4; i++) {
        float d0 = x[4 * i] - ma, d1 = x[4 * i + 1] - ma, d2 = x[4 * i + 2] - mb, d3 = x[4 * i + 3] - mb;
        qa += d0 * d0 + d1 * d1; qb += d2 * d2 + d3 * d3;
    }
    qa += __shfl_xor_sync(0xffffffffu, qa, 1); qb += __shfl_xor_sync(0xffffffffu, qb, 1);
    qa += __shfl_xor_sync(0xffffffffu, qa, 2); qb += __shfl_xor_sync(0xffffffffu, qb, 2);
    return make_float4(a, qa, b, qb);
}

__device__ __forceinline__ void conv_stage(float* Y, uint32_t pbase, uint32_t ubase) {
    const int lane = threadIdx.x & 31, w = threadIdx.x >> 5, g = lane >> 2, c = lane & 3;
#pragma unroll
    for (int cp = 0; cp < 2; cp++) {
        const int chl = w * 4 + cp * 2 + (lane >> 4);
        const uint4 b = ldsm4(ubase + chl * 256 + ((lane >> 3) & 1) * 128 + (((lane & 7) ^ (chl & 7)) << 4));
#pragma unroll
        for (int h = 0; h < 2; h++) {
            const uint32_t pa = pbase + ((w * 4 + cp * 2 + h) * PW + 16 + g - 2 * c) * 4;
            uint32_t lo = lds32(pa - 32);
#pragma unroll
            for (int d = 0; d < 8; d++) {
                const uint32_t a0 = lds32(pa + d * 64), a1 = lds32(pa + d * 64 + 32);
                mma16(Y + ((cp * 2 + h) * 8 + d) * 4, a0, a1, lo, a0, h ? b.z : b.x, h ? b.w : b.y);
                lo = a1;
            }
        }
    }
}

__device__ __forceinline__ void conv_combine(const float* y8, float* cur, float* nxt) {
    const int lane = threadIdx.x & 31, c = lane & 3;
    cur[0] = y8[0]; cur[1] = y8[1] + y8[4]; cur[2] = y8[2]; cur[3] = y8[3] + y8[6];
    nxt[0] = y8[29]; nxt[1] = 0.f; nxt[2] = y8[31]; nxt[3] = 0.f;
#pragma unroll
    for (int e = 1; e < 4; e++) {
        const int src = (lane & ~3) | ((c - e) & 3);
        const float v0 = __shfl_sync(0xffffffffu, y8[8 * e] + y8[8 * e - 3], src), v1 = __shfl_sync(0xffffffffu, y8[8 * e + 1] + y8[8 * e + 4], src);
        const float v2 = __shfl_sync(0xffffffffu, y8[8 * e + 2] + y8[8 * e - 1], src), v3 = __shfl_sync(0xffffffffu, y8[8 * e + 3] + y8[8 * e + 6], src);
        if (c >= e) { cur[0] += v0; cur[1] += v1; cur[2] += v2; cur[3] += v3; }
        else { nxt[0] += v0; nxt[1] += v1; nxt[2] += v2; nxt[3] += v3; }
    }
}

__device__ __forceinline__ void hist_task(float* Y, uint32_t sb, int w, int ch, int q, int& st, uint32_t& ph, int nd) {
    const int lane = threadIdx.x & 31, chl = w * 2 + (lane >> 4);
    const uint32_t ua = sb + 12288 + chl * 256 + ((lane >> 3) & 1) * 128 + (((lane & 7) ^ (chl & 7)) << 4);
    const uint32_t pa = sb + (w * 2 * PW + 16 + (lane >> 2) - 2 * (lane & 3)) * 4;
#pragma unroll
    for (int i = 0; i < 128; i++) Y[i] = 0;
    uint4 b1 = make_uint4(0, 0, 0, 0);
#pragma unroll 1
    for (int j = ch + 1; j >= 2; j--) {
        const uint4 b0 = b1;
        mbar_wait(sb + B_BAR + (BB_FULL + st) * 8, ph);
        b1 = ldsm4(ua + st * STG_B);
        if (j == 2) b1 = make_uint4(0, 0, 0, 0);
#pragma unroll
        for (int h = 0; h < 2; h++) {
            const uint32_t o = pa + st * STG_B + h * PW * 4;
            uint32_t lo = lds32(o - 32);
#pragma unroll
            for (int d = 0; d < 8; d++) {
                const uint32_t a0 = lds32(o + d * 64), a1 = lds32(o + d * 64 + 32);
                mma16(Y + (h * 16 + d) * 4, a0, a1, lo, a0, h ? b0.z : b0.x, h ? b0.w : b0.y);
                mma16(Y + (h * 16 + 8 + d) * 4, a0, a1, lo, a0, h ? b1.z : b1.x, h ? b1.w : b1.y);
                lo = a1;
            }
        }
        bar_sync(NB_WG + (w >> 2), 128);
        stage_release(sb, w, st);
        if (++st == NSTG) { st = 0; ph ^= 1; }
    }
    mbar_wait(sb + B_BAR + (BB_SF + (w >> 2)) * 8, (nd & 1) ^ 1);
#pragma unroll
    for (int h = 0; h < 2; h++) {
        const int o = ((ch * 16 + (q >> 1)) * 4 + (w & 1) * 2 + h) * 256 + ((q & 1) * 4 + (w >> 1)) * 32 + lane;
        float c0[4], n0[4], c1[4], n1[4];
        conv_combine(Y + h * 64, c0, n0); conv_combine(Y + h * 64 + 32, c1, n1);
        g_carry[0][o] = make_float4(c0[0], c0[1], c0[2], c0[3]);
        g_carry[0][o + 16384] = make_float4(c1[0] + n0[0], c1[1] + n0[1], c1[2] + n0[2], c1[3] + n0[3]);
        g_carry[1][o + 32768] = make_float4(n1[0], n1[1], n1[2], n1[3]);
    }
}

__device__ __forceinline__ void conv_task(const Params& p, float* Y, uint32_t sb, int w, int ch, int q, int ns, bool dry, int& st, uint32_t& ph, int nd) {
    const int tid = threadIdx.x, lane = tid & 31, g = lane >> 2, c = lane & 3;
    uint32_t dk[4];
    const uint32_t sg = (~ch & 2) << 30;
    int sr = st;
    float x[16];
    uint32_t rs[8];
    load_resid<2>(rs, 0, ch, w, 2 * q);
    PROF(tid == 128, 2048 + ch * 8);
#pragma unroll
    for (int i = 0; i < 128; i++) Y[i] = 0;
#pragma unroll 1
    for (int j = min(ch, 1 + (ch & 1)); j >= 1; j--) {
        mbar_wait(sb + B_BAR + (BB_FULL + st) * 8, ph);
        conv_stage(Y, sb + st * STG_B, sb + B_UT + ((ch - j) & 1) * 8192);
        if (++st == NSTG) { st = 0; ph ^= 1; }
    }
#pragma unroll 1
    for (int i = 0; i < min(ch, (ch & 1) ? 2 : 3); i++) {
        if (i) mbar_wait(sb + B_BAR + (BB_FULL + st) * 8, ph);
        const uint32_t ca = sb + (i ? st * STG_B : B_SP) + tid * 16;
#pragma unroll
        for (int k = 0; k < 4; k++) {
            const uint4 cr = lds128(ca + k * 4096);
            Y[k * 32] += __uint_as_float(cr.x); Y[k * 32 + 1] += __uint_as_float(cr.y); Y[k * 32 + 2] += __uint_as_float(cr.z); Y[k * 32 + 3] += __uint_as_float(cr.w);
        }
        if (i && ++st == NSTG) { st = 0; ph ^= 1; }
    }
    bar_sync(NB_C, 256);
#pragma unroll 1
    for (; sr != st; sr = (sr + 1) & (NSTG - 1)) stage_release(sb, w, sr);
    const uint32_t ut = sb + B_UT + (ch & 1) * 8192;
    mbar_wait(sb + B_BAR + (BB_SF + (w >> 2)) * 8, (nd & 1) ^ 1);
    mbar_wait(sb + B_BAR + (BB_SF + 1 - (w >> 2)) * 8, (nd & 1) ^ 1);
    PROF(tid == 128, 2048 + ch * 8 + 7);
    {
        uint4 v[2 * OPS1];
        wait_cnt_warp(cnt_ptr(C_OP0 + (q >> 3) * 2 + (w >> 2), ch + (w & 3) * 16), ns);
        part_load<OPS1>(v, 0, ch, w, 2 * q, ns);
        part_sum<OPS1>(x, v, rs);
        const float4 s = row_stats32(x);
        float2* dst = g_st2 + ((ch & 1) * 16 + q) * 128 + w * 16 + g + c * 8;
        asm volatile("{.reg .pred p; setp.ne.u32 p,%2,0; @p st.relaxed.gpu.global.b64 [%0],%1;}" ::"l"(dst),
                     "l"(((uint64_t)((__float_as_uint(c ? s.w : s.y) & 0x7fffffffu) | sg) << 32) | __float_as_uint(c ? s.z : s.x)), "r"((uint32_t)(c < 2 && !dry)) : "memory");
        PROF(tid == 128, 2048 + ch * 8 + 1);
    }
#pragma unroll
    for (int i = 0; i < 4; i++) asm volatile("ld.global.nc.u32 %0,[%1];" : "=r"(dk[i]) : "l"(p.Dskip + q * 32 + i * 8 + 2 * c));
    float2 ln0, ln1;
    {
        const float2* src = g_st2 + ((ch & 1) * 16 + (lane >> 4) * 8) * 128 + w * 16 + (lane & 15);
        uint64_t v[8];
        int n = 0;
#pragma unroll
        for (int i = 0; i < 8; i++) v[i] = (uint64_t)~sg << 32;
        while (true) {
            bool bad = false;
#pragma unroll
            for (int i = 0; i < 8; i++) asm volatile("{.reg .pred p; setp.lt.s32 p,%2,0; @p ld.relaxed.gpu.global.b64 %0,[%1];}" : "+l"(v[i]) : "l"(src + i * 128), "r"((uint32_t)(v[i] >> 32) ^ sg) : "memory");
#pragma unroll
            for (int i = 0; i < 8; i++) bad = bad || (int)((uint32_t)(v[i] >> 32) ^ sg) < 0;
            if (!__any_sync(0xffffffffu, bad && !dry)) break;
            if (++n > 2000000) __trap();
        }
        float sm = 0;
#pragma unroll
        for (int i = 0; i < 8; i++) sm += __uint_as_float((uint32_t)v[i]);
        sm += __shfl_xor_sync(0xffffffffu, sm, 16);
        const float mean = sm * (1.f / 512.f);
        float M2 = 0;
#pragma unroll
        for (int i = 0; i < 8; i++) { const float d = __uint_as_float((uint32_t)v[i]) * (1.f / 32.f) - mean; M2 += fabsf(__uint_as_float((uint32_t)(v[i] >> 32))) + 32.f * d * d; }
        M2 += __shfl_xor_sync(0xffffffffu, M2, 16);
        const float2 o = ln_finish(mean, M2 * (1.f / 512.f));
        ln0.x = __shfl_sync(0xffffffffu, o.x, g); ln0.y = __shfl_sync(0xffffffffu, o.y, g);
        ln1.x = __shfl_sync(0xffffffffu, o.x, g + 8); ln1.y = __shfl_sync(0xffffffffu, o.y, g + 8);
    }
    PROF(tid == 128, 2048 + ch * 8 + 2);
    uint32_t u[8];
#pragma unroll
    for (int i = 0; i < 8; i++) {
        const float2 l = (i & 1) ? ln1 : ln0;
        u[i] = pack2(__fdividef(rbf(x[2 * i] - l.x), l.y), __fdividef(rbf(x[2 * i + 1] - l.x), l.y));
        const int chl = (i >> 1) * 8 + g;
        sts32(ut + chl * 256 + (i & 1) * 128 + ((w ^ g) << 4) + c * 4, movm(u[i]));
    }
    bar_sync(NB_C, 256);
    mbar_wait(sb + B_BAR + (BB_FULL + st) * 8, ph);
    PROF(tid == 128, 2048 + ch * 8 + 3);
    conv_stage(Y, sb + st * STG_B, ut);
    uint32_t yp[4][2];
    float nxt[4][4];
    {
        float y[4][4];
#pragma unroll
        for (int k = 0; k < 4; k++) conv_combine(Y + k * 32, y[k], nxt[k]);
#pragma unroll
        for (int i = 0; i < 4; i++) { yp[i][0] = pack2(y[0][i], y[1][i]); yp[i][1] = pack2(y[2][i], y[3][i]); }
    }
#pragma unroll
    for (int i = 0; i < 4; i++) sts64(sb + B_YT + (16 * (2 * c + (i & 1)) + g + (i >> 1) * 8) * 80 + w * 8, yp[i][0], yp[i][1]);
    bar_sync(NB_C, 256);
    stage_release(sb, w, st);
    if (++st == NSTG) { st = 0; ph ^= 1; }
    PROF(tid == 128, 2048 + ch * 8 + 4);
    uint32_t xo[8];
    uint4* dA = g_xA[1] + ((ch * 8 + w) * 32 + 2 * q) * 32 + lane;
#pragma unroll
    for (int i = 0; i < 8; i++) {
        const int col = (i >> 1) * 8 + 2 * c;
        const uint32_t yv = lds32(sb + B_YT + (w * 16 + g + (i & 1) * 8) * 80 + col * 2);
        const uint32_t dv = dk[i >> 1];
        x[2 * i] = rbf(x[2 * i] + rbf(blo(yv) + rbf(blo(u[i]) * blo(dv))));
        x[2 * i + 1] = rbf(x[2 * i + 1] + rbf(bhi(yv) + rbf(bhi(u[i]) * bhi(dv))));
        xo[i] = pack2(x[2 * i], x[2 * i + 1]);
        if ((i & 3) == 3) dA[(i >> 2) * 32] = make_uint4(xo[i - 3], xo[i - 2], xo[i - 1], xo[i]);
    }
    {
        const float4 s = row_stats32(x);
        float2* dst = g_st[1] + (ch * 16 + q) * 128 + w * 16 + g;
        if (c == 0) dst[0] = make_float2(s.x, s.y);
        if (c == 1) dst[8] = make_float2(s.z, s.w);
        __syncwarp();
    }
    PROF(tid == 128, 2048 + ch * 8 + 5);
    mbar_arrive1(sb + B_BAR + (BB_DONE + (w >> 2)) * 8);
    bar_sync(NB_C, 256);
#pragma unroll
    for (int k = 0; k < 4; k++) sts128(sb + B_SP + k * 4096 + tid * 16, __float_as_uint(nxt[k][0]), __float_as_uint(nxt[k][1]), __float_as_uint(nxt[k][2]), __float_as_uint(nxt[k][3]));
    PROF(tid == 128, 2048 + ch * 8 + 6);
}

__device__ __forceinline__ void out_store(const Params& p, const float* x, int ch, int cb) {
    const int lane = threadIdx.x & 31, w = threadIdx.x >> 5, g = lane >> 2, c = lane & 3;
#pragma unroll
    for (int h = 0; h < 2; h++) {
        const float* y = x + h * 2;
        uint32_t v0 = pack2(y[0], y[1]), v1 = pack2(y[4], y[5]), v2 = pack2(y[8], y[9]), v3 = pack2(y[12], y[13]);
        uint32_t t0 = (c & 1) ? v0 : v1, t1 = (c & 1) ? v2 : v3;
        t0 = __shfl_xor_sync(0xffffffffu, t0, 1); t1 = __shfl_xor_sync(0xffffffffu, t1, 1);
        if (c & 1) { v0 = t0; v2 = t1; } else { v1 = t0; v3 = t1; }
        t0 = (c & 2) ? v0 : v2; t1 = (c & 2) ? v1 : v3;
        t0 = __shfl_xor_sync(0xffffffffu, t0, 2); t1 = __shfl_xor_sync(0xffffffffu, t1, 2);
        if (c & 2) { v0 = t0; v1 = t1; } else { v2 = t0; v3 = t1; }
        stg128((uint4*)(p.out + (size_t)(ch * 128 + w * 16 + g + h * 8) * 512 + cb * 16 + c * 8), make_uint4(v0, v1, v2, v3), POL_LATE);
    }
}
__device__ __forceinline__ void fin_task(const Params& p, int ch, int cb0, int ncb, int ns, bool dry) {
    const int w = threadIdx.x >> 5;
    uint32_t rs[8];
    wait_cnt_warp(cnt_ptr(C_CV, ch), dry ? 0 : 32);
    load_resid<2>(rs, 1, ch, w, cb0);
    wait_cnt_warp(cnt_ptr(C_OP1, ch), dry ? 0 : 256);
    for (int cb = cb0; cb < cb0 + ncb; cb += 2) {
        float x[16];
        if (cb != cb0) load_resid<2>(rs, 1, ch, w, cb);
        uint4 v[32];
        part_load<16>(v, 1, ch, w, cb, ns);
        part_sum<16>(x, v, rs);
        out_store(p, x, ch, cb);
    }
}

__device__ __forceinline__ void bulk_consumer(const Params& p, uint32_t sb, int cl, uint32_t rank, int w) {
    int st = 0; uint32_t ph = 0; int nd = 0, ng = 0;
    for (int ti = 0; ti < MAXT; ti++) {
        const Task t = task_of(p.task[cl][ti], rank);
        const int type = t.type, layer = t.layer, ch = t.ch;
        if (type == T_END) break;
        bool staged = type != T_FIN;
        PROF(threadIdx.x == 0, 3600 + ti * 4);
        CPROF(0);
        if (type == T_QKV) {
            staged = false;
            #pragma unroll 1
            while (st) {
                if (!(w & 3)) { mbar_wait(sb + B_BAR + (BB_FULL + st) * 8, ph); stage_release(sb, 0, st); stage_release(sb, 1, st); }
                if (++st == NSTG) { st = 0; ph ^= 1; }
            }
            if (!(w & 3)) { sts32(sb + B_ST + 8, ph); bar_arrive(NB_PH, 96); }
            qkv_task(sb, w, layer, ch, t.b, ng, nd, ph, ti, p.zero);
            PROF(threadIdx.x == 128, 3600 + ti * 4 + 1);
        } else if (type == T_OP) {
            const int lane = threadIdx.x & 31;
            float acc[128];
            uint32_t r0 = sb + B_BAR + BB_IDLE * 8, r1 = r0;
            if (w >> 2) mbar_wait(sb + B_BAR + BB_GO * 8, ng & 1);
            ng++;
            gemm_run<false>(acc, sb, w, 0, 1, r0, r1, st, ph);
            gemm_run<true>(acc, sb, w, 1, 2 * t.b, r0, r1, st, ph);
            mbar_wait(sb + B_BAR + (BB_SF + (w >> 2)) * 8, (nd & 1) ^ 1);
            wg_wait<1>();
            mbar_arrive1_cluster(r0);
            wg_wait<0>();
            mbar_arrive1_cluster(r1);
            PROF(threadIdx.x == 128, 3600 + ti * 4 + 1);
            if (t.c & 32) {
                staged = false;
#pragma unroll
                for (int j = 0; j < 16; j += 4) {
                    uint32_t rs[16];
                    load_resid<4>(rs, 1, ch, w, (t.blk & 4) * 4 + j);
#pragma unroll
                    for (int i = 0; i < 16; i++) { float* y = acc + j * 8 + 2 * i; y[0] = rbf(y[0]) + blo(rs[i]); y[1] = rbf(y[1]) + bhi(rs[i]); }
                    out_store(p, acc + j * 8, ch, (t.blk & 4) * 4 + j); out_store(p, acc + j * 8 + 16, ch, (t.blk & 4) * 4 + j + 2);
                }
            } else if (!layer) {
                const int s2 = st + (w >> 1);
                const uint32_t o = sb + (s2 & (NSTG - 1)) * STG_B + (w & 1) * 8192 + lane * 16;
                mbar_wait(sb + B_BAR + (BB_FULL + (s2 & (NSTG - 1))) * 8, ph ^ (s2 >= NSTG));
#pragma unroll
                for (int j = 0; j < 16; j++)
                    sts128(o + j * 512, pack2(acc[j * 8], acc[j * 8 + 1]), pack2(acc[j * 8 + 2], acc[j * 8 + 3]), pack2(acc[j * 8 + 4], acc[j * 8 + 5]), pack2(acc[j * 8 + 6], acc[j * 8 + 7]));
                sts32(sb + B_ST + (w >> 2) * 4, st);
                st += 4;
                if (st >= NSTG) { st -= NSTG; ph ^= 1; }
            } else {
                uint4* dst = op_dst(layer, ch, t.c & 15, w, (t.blk >> 2) & 1) + lane;
#pragma unroll
                for (int n = 0; n < 16; n++) {
                    const int j = (n >> 1) + (n & 1) * 8;
                    const uint4 v = make_uint4(pack2(acc[j * 8], acc[j * 8 + 1]), pack2(acc[j * 8 + 2], acc[j * 8 + 3]), pack2(acc[j * 8 + 4], acc[j * 8 + 5]), pack2(acc[j * 8 + 6], acc[j * 8 + 7]));
                    if (j < 16 - NSB) stg128(dst + j * 32, v, out_pol(T_OP, layer, ch)); else sts128(sb + B_OUT + (w * NSB + j - (16 - NSB)) * 512 + lane * 16, v.x, v.y, v.z, v.w);
                }
            }
        } else if (type == T_CV) {
            float acc[128];
            if (layer) hist_task(acc, sb, w, ch, t.a + rank, st, ph, nd);
            else { conv_task(p, acc, sb, w, ch, t.a + rank, t.b, t.dry, st, ph, nd); staged = false; nd++; }
        } else {
            fin_task(p, ch, t.a + rank * t.c, t.c, t.b, t.dry);
        }
        if (staged) {
            __syncwarp();
            mbar_arrive1(sb + B_BAR + (BB_DONE + (w >> 2)) * 8);
            nd++;
        }
        PROF(threadIdx.x == 128, 3600 + ti * 4 + 2);
        __syncwarp();
    }
}

constexpr int P_Y = 131072  , P_PRM = P_Y  , P_K6 = P_PRM + 8192  ,
              P_P = P_Y + 40960  , P_U = P_P + 33280  , P_END = P_U + 17408, P_X = 98304  ;
static_assert(P_END <= B_BAR && P_END <= R_BAR, "prologue scratch");
#define KGUN 2
constexpr int KGU = KGUN;
__device__ __forceinline__ void csq(float& r, float& i) { const float t = r * i; r = fmaf(r, r, -(i * i)); i = t + t; }
__device__ __forceinline__ void cpow(float ar, float ph, float p, float& r, float& i) {
    const float e = ex2(ar * p);
    const float u = ph * p, n = fabsf(u) < 4194304.f ? (u + 12582912.f) - 12582912.f : u;
    const float t = (u - n) * 6.283185307179586f;
    r = e * __cosf(t); i = e * __sinf(t);
}
__device__ __forceinline__ void mma_tf32(float* c, float a0, float a1, float a2, float a3, float b0, float b1) {
    asm volatile("mma.sync.aligned.m16n8k8.row.col.f32.tf32.tf32.f32 {%0,%1,%2,%3},{%4,%5,%6,%7},{%8,%9},{%0,%1,%2,%3};"
                 : "+f"(c[0]), "+f"(c[1]), "+f"(c[2]), "+f"(c[3])
                 : "r"(__float_as_uint(a0)), "r"(__float_as_uint(a1)), "r"(__float_as_uint(a2)), "r"(__float_as_uint(a3)), "r"(__float_as_uint(b0)), "r"(__float_as_uint(b1)));
}

struct ProRegs { uint32_t v[2][4], ldt[2]; };
__device__ __forceinline__ void prologue_load(const ProArgs& a, int b, ProRegs& pr) {
    const int w = threadIdx.x >> 5;
#pragma unroll
    for (int i = 0; i < 2; i++) {
        const int gi = b * 512 + (w & 3) * 128 + ((w >> 2) & 1) * 64 + i * 32 + (threadIdx.x & 31);
        pr.ldt[i] = __ldg((const uint16_t*)a.ldt + b * 4 + (w & 3));
        pr.v[i][0] = __ldg((const uint16_t*)a.lAr + gi); pr.v[i][1] = __ldg((const uint16_t*)a.Ai + gi);
        pr.v[i][2] = __ldg((const uint16_t*)a.Cr + gi); pr.v[i][3] = __ldg((const uint16_t*)a.Ci + gi);
    }
}
__device__ __forceinline__ void prologue(const ProArgs& a, uint32_t sb, int b, int w, const ProRegs& pr) {
    const int tid = threadIdx.x, lane = tid & 31, g = lane >> 2, c = lane & 3;
    const int d0 = b * 4;
    if (w >= 8) {
        const int t2 = tid - 256;
        if (w < 10) {
            const int row = b * 16 + (w - 8) * 8 + g;
            const float4 r4 = row_stats((const uint4*)(a.x + (size_t)row * 512) + c, 4);
            const float2 r = make_float2(r4.x + r4.z, r4.y + r4.w);
            const float2 l = ln_finish(r.x * (1.f / 512.f), fmaxf(r.y - r.x * r.x * (1.f / 512.f), 0.f) * (1.f / 512.f));
            if (c == (g >> 1)) asm volatile("st.relaxed.gpu.global.u32 [%0],%1;" ::"l"(g_ln0 + row), "r"(pack2(l.x, l.y)) : "memory");
        }
        PROF(t2 == 0, 3516);
        const int gi = b * 128 + t2;
        if (t2 < 32) acc_init(a.mem0, b * 32 + t2);
        if (t2 >= 112) ((uint4*)g_st2)[b * 16 + t2 - 112] = make_uint4(0, 0, 0, 0);
        if (gi < 13 * 64) g_cnt[gi] = 0;
        bar_sync(6, 384);
        if (gi < 512) g_st[0][(gi >> 8) * 2048 + (lds32(sb + S_TAG) ^ 1) * 256 + (gi & 255)] = make_float2(0.f, 0.f);
        asm volatile("{.reg .pred p; elect.sync _|p,0xffffffff; @p cp.async.bulk.prefetch.L2.global [%0],32768;}"
                     ::"l"((w == 8 ? a.Wq : w == 9 ? a.Wk : w == 10 ? a.Wv : a.Wo) + (size_t)b * 16384) : "memory");
        mbar_wait(sb + S_XBAR, 0);
#pragma unroll 1
        for (int h = 0; h < 2; h++) {
            uint32_t l[8];
            int n = 0;
            while (true) {
                bool ok = true;
#pragma unroll
                for (int i = 0; i < 8; i++) asm volatile("ld.relaxed.gpu.global.u32 %0,[%1];" : "=r"(l[i]) : "l"(g_ln0 + h * 1024 + i * 128 + t2) : "memory");
#pragma unroll
                for (int i = 0; i < 8; i++) ok = ok && l[i];
                if (__all_sync(0xffffffffu, ok)) break;
                if (++n > 2000000) __trap();
            }
#pragma unroll
            for (int i = 0; i < 8; i++) {
                const int t = h * 1024 + i * 128 + t2;
                const uint2 x = lds64(sb + P_X + t * 16 + (b & 1) * 8);
                const float m = blo(l[i]), rs = rcp(bhi(l[i]));
                const uint32_t u0 = pack2(rbf(blo(x.x) - m) * rs, rbf(bhi(x.x) - m) * rs), u1 = pack2(rbf(blo(x.y) - m) * rs, rbf(bhi(x.y) - m) * rs);
                sts128(sb + P_X + t * 16, x.x, x.y, u0, u1);
                const uint32_t o = sb + P_U + ((t >> 3) & 1) * 2176 + ((t >> 4) + 8) * 16 + (t & 7) * 2;
                asm volatile("st.shared.u16 [%0],%1;" ::"r"(o), "h"((uint16_t)u0) : "memory");
                asm volatile("st.shared.u16 [%0],%1;" ::"r"(o + 4352), "h"((uint16_t)(u0 >> 16)) : "memory");
                asm volatile("st.shared.u16 [%0],%1;" ::"r"(o + 8704), "h"((uint16_t)u1) : "memory");
                asm volatile("st.shared.u16 [%0],%1;" ::"r"(o + 13056), "h"((uint16_t)(u1 >> 16)) : "memory");
            }
        }
        PROF(t2 == 0, 3517);
        bar_sync(9, 384);
        fence_async_smem();
#pragma unroll 1
        for (int j = 0; j < 16; j++) {
            const int d = d0 + w - 8;
            asm volatile("{.reg .pred p; elect.sync _|p,0xffffffff; @p cp.async.bulk.global.shared::cta.bulk_group [%0],[%1],%2;}" ::"l"(g_P + (((d >> 5) * 16 + j) * 32 + (d & 31)) * PW),
                         "r"(sb + P_P + ((w - 8) * 2080 + j * 128) * 4), "r"(PW * 4) : "memory");
        }
        asm volatile("cp.async.bulk.commit_group; cp.async.bulk.wait_group 0;" ::: "memory");
        bar_arrive(10, 384);
        return;
    }
#pragma unroll
    for (int i = 0; i < 2; i++) {
        const float dt = rbf(expf(blo(pr.ldt[i])));
        const float ar = -rbf(expf(blo(pr.v[i][0]))) * dt, ai = blo(pr.v[i][1]) * dt;
        sts128(sb + P_PRM + (w * 64 + i * 32 + lane) * 16, __float_as_uint(ar * 1.4426950408889634f), __float_as_uint(ai * 0.15915494309189535f),
               __float_as_uint(2.f * (blo(pr.v[i][2]) * dt)), __float_as_uint(2.f * (blo(pr.v[i][3]) * dt)));
    }
    if (tid < 64) sts128(sb + P_U + (tid >> 3) * 2176 + (tid & 7) * 16, 0, 0, 0, 0);
    bar_arrive(6, 384);
    __syncwarp();
    PROF(tid == 0, 3510);
    const int ch = w & 3, hf = w >> 2;
    {
        float k0[4] = {0, 0, 0, 0}, k1[4] = {0, 0, 0, 0}, k2[4] = {0, 0, 0, 0}, k3[4] = {0, 0, 0, 0}, k4[4] = {0, 0, 0, 0}, kl = 0;
#pragma unroll KGU
        for (int j = 0; j < 16; j++) {
            const uint4 q = lds128(sb + P_PRM + (w * 64 + j * 4 + c) * 16);
            const float cr = __uint_as_float(q.z), ci = __uint_as_float(q.w);
            float wr[4], wi[4], vr[4], vi[4];
            cpow(__uint_as_float(q.x), __uint_as_float(q.y), (float)g, wr[0], wi[0]);
            cpow(__uint_as_float(q.x), __uint_as_float(q.y), (float)(g + 8), vr[0], vi[0]);
#pragma unroll
            for (int i = 1; i < 4; i++) { wr[i] = wr[i - 1]; wi[i] = wi[i - 1]; csq(wr[i], wi[i]); vr[i] = vr[i - 1]; vi[i] = vi[i - 1]; csq(vr[i], vi[i]); }
            float hr = wr[3], hi = wi[3];
            csq(hr, hi);
            mma_tf32(k0, wr[0], vr[0], wi[0], vi[0], cr * hr - ci * hi, -(cr * hi + ci * hr));
            hr = vr[3]; hi = vi[3]; csq(hr, hi);
            mma_tf32(k1, wr[0], vr[0], wi[0], vi[0], cr * hr - ci * hi, -(cr * hi + ci * hr));
            csq(hr, hi);
            mma_tf32(k2, wr[1], vr[1], wi[1], vi[1], cr * hr - ci * hi, -(cr * hi + ci * hr));
            csq(hr, hi);
            mma_tf32(k3, wr[2], vr[2], wi[2], vi[2], cr * hr - ci * hi, -(cr * hi + ci * hr));
            csq(hr, hi);
            mma_tf32(k4, wr[3], vr[3], wi[3], vi[3], cr * hr - ci * hi, -(cr * hi + ci * hr));
            csq(hr, hi);
            kl += cr * hr - ci * hi;
        }
        kl += __shfl_xor_sync(0xffffffffu, kl, 1); kl += __shfl_xor_sync(0xffffffffu, kl, 2);
        const uint32_t o = sb + P_K6 + (ch * 656 + c * 32 + g) * 4, ol = sb + P_K6 + (ch * 656 + 640) * 4;
#define KST(k, base) sts32(o + (base) * 4, __float_as_uint(k[0])); sts32(o + (base) * 4 + 64, __float_as_uint(k[1])); \
                     sts32(o + (base) * 4 + 32, __float_as_uint(k[2])); sts32(o + (base) * 4 + 96, __float_as_uint(k[3]))
#define KAD(k, base) k[0] += __uint_as_float(lds32(o + (base) * 4)); k[1] += __uint_as_float(lds32(o + (base) * 4 + 64)); \
                     k[2] += __uint_as_float(lds32(o + (base) * 4 + 32)); k[3] += __uint_as_float(lds32(o + (base) * 4 + 96))
        if (hf == 0) {
            bar_sync(2 + ch, 64);
            KAD(k0, 0); KAD(k1, 128); KAD(k2, 256); KAD(k3, 384); KAD(k4, 512);
            kl += __uint_as_float(lds32(ol));
            __syncwarp();
        }
        KST(k0, 0); KST(k1, 128); KST(k2, 256); KST(k3, 384); KST(k4, 512);
        if (lane == 0) sts32(ol, __float_as_uint(kl));
        if (hf == 1) { __syncwarp(); bar_arrive(2 + ch, 64); }
    }
    PROF(tid == 0, 3511);
    bar_sync(8, 384);
    PROF(tid == 0, 3512);
    if (tid < 64) sts32(sb + P_P + ((tid >> 4) * 2080 + (tid & 15)) * 4, 0);
#pragma unroll 1
    for (int x = tid; x < 2048; x += 512) {
        uint32_t pw[2][4];
#pragma unroll
        for (int h = 0; h < 2; h++) {
            const int y = x + h * 256;
            const int i0 = y <= 256 ? y : 256 + (int)((pack2((float)y, 0.f) & 0xffff) - 0x4380);
            const int i1 = y <= 256 ? max(y - 1, 0) : 256 + (int)((pack2((float)(y - 1), 0.f) & 0xffff) - 0x4380);
#pragma unroll
            for (int k = 0; k < 4; k++) {
                const float lo = __uint_as_float(lds32(sb + P_K6 + k * 2624 + i0 * 4)), hi = __uint_as_float(lds32(sb + P_K6 + k * 2624 + i1 * 4));
                pw[h][k] = pack2(lo, y ? hi : 0.f);
            }
        }
#pragma unroll
        for (int h = 0; h < 2; h++)
#pragma unroll
            for (int k = 0; k < 4; k++) sts32(sb + P_P + (k * 2080 + x + h * 256 + 16) * 4, pw[h][k]);
    }
    bar_sync(9, 384);
    PROF(tid == 0, 3513);
    {
        float acc[16][4];
#pragma unroll
        for (int j = 0; j < 16; j++) acc[j][0] = acc[j][1] = acc[j][2] = acc[j][3] = 0;
#pragma unroll 1
        for (int e = hf * 4; e < hf * 4 + 4; e++) {
            uint32_t B[16][2];
            const uint32_t ua = sb + P_U + ch * 4352 + ((lane >> 3) & 1) * 2176 + (8 + (lane >> 4) * 8 + (lane & 7) - e) * 16;
#pragma unroll
            for (int j = 0; j < 8; j++) { const uint4 v = ldsm4(ua + j * 256); B[2 * j][0] = v.x; B[2 * j][1] = v.y; B[2 * j + 1][0] = v.z; B[2 * j + 1][1] = v.w; }
            const uint32_t pa = sb + P_P + (ch * 2080 + 16 + e * 16 + g - 2 * c) * 4;
#pragma unroll
            for (int d = 0; d < 16; d++) {
                const uint32_t a0 = lds32(pa + d * 512), a1 = lds32(pa + d * 512 + 32), a2 = lds32(pa + d * 512 - 32);
#pragma unroll
                for (int j = d; j < 16; j++) mma16(acc[j], a0, a1, a2, a0, B[j - d][0], B[j - d][1]);
            }
        }
        PROF(tid == 0, 3514);
        const uint32_t o = sb + P_Y + (ch * 2560 + c * 40 + g) * 4;
#pragma unroll
        for (int j = 0; j < 8; j++) {
#pragma unroll
            for (int i = 0; i < 4; i++) { const float lo = acc[j][i], hi = acc[j + 8][i]; acc[j][i] = hf ? hi : lo; sts32(o + (j + 8 - hf * 8) * 640 + (i & 1) * 80 + (i >> 1) * 32, __float_as_uint(hf ? lo : hi)); }
        }
        bar_sync(2 + ch, 64);
#pragma unroll
        for (int j = 0; j < 8; j++) {
#pragma unroll
            for (int i = 0; i < 4; i++) acc[j][i] += __uint_as_float(lds32(o + (j + hf * 8) * 640 + (i & 1) * 80 + (i >> 1) * 32));
        }
#pragma unroll
        for (int j = 0; j < 8; j++) {
#pragma unroll
            for (int i = 0; i < 4; i++) sts32(o + (j + hf * 8) * 640 + (i & 1) * 80 + (i >> 1) * 32, __float_as_uint(acc[j][i]));
        }
    }
    const uint2 dk = __ldg((const uint2*)(a.Dk + d0));
    bar_sync(1, 256);
#pragma unroll 2
    for (int i = 0; i < 8; i++) {
        const int t = i * 256 + tid;
        const uint32_t o = sb + P_Y + (t + 4 * (t >> 4)) * 4;
        const uint4 xu = lds128(sb + P_X + t * 16);
        float y[4];
#pragma unroll
        for (int k = 0; k < 4; k++) y[k] = rbf(__uint_as_float(lds32(o + k * 10240)));
        uint2 r;
        r.x = pack2(blo(xu.x) + rbf(y[0] + rbf(blo(xu.z) * blo(dk.x))), bhi(xu.x) + rbf(y[1] + rbf(bhi(xu.z) * bhi(dk.x))));
        r.y = pack2(blo(xu.y) + rbf(y[2] + rbf(blo(xu.w) * blo(dk.y))), bhi(xu.y) + rbf(y[3] + rbf(bhi(xu.w) * bhi(dk.y))));
        {
            const bool up = t & 8;
            const uint32_t o = __shfl_xor_sync(0xffffffffu, up ? r.x : r.y, 8);
            ((uint2*)(g_xA[0] + ((t >> 4) * 32 + (d0 >> 4)) * 32 + (t & 7) * 4 + ((d0 >> 1) & 2) + up))[(d0 >> 3) & 1] = up ? make_uint2(o, r.y) : make_uint2(r.x, o);
        }
        if (i == 0) {
            const float e0 = blo(r.x), e1 = bhi(r.x), e2 = blo(r.y), e3 = bhi(r.y);
            asm volatile("red.relaxed.gpu.global.add.v2.f32 [%0],{%1,%2};" ::"l"(g_st[0] + (t >> 7) * 2048 + lds32(sb + S_TAG) * 256 + (b & 1) * 128 + (t & 127)),
                         "f"((e0 + e1) + (e2 + e3)), "f"((e0 * e0 + e1 * e1) + (e2 * e2 + e3 * e3)) : "memory");
        }
    }
    PROF(tid == 0, 3515);
    bar_sync(10, 384);
}

__global__ void __cluster_dims__(2, 1, 1) __launch_bounds__(384, 1) main_kernel(const __grid_constant__ Params p) {
    extern __shared__ __align__(1024) uint8_t smem[];
    const uint32_t sb = __shfl_sync(0xffffffffu, smem_u32(smem), 0);
    uint32_t rank; asm("mov.u32 %0,%%cluster_ctarank;" : "=r"(rank));
    const int wi = __shfl_sync(0xffffffffu, threadIdx.x >> 5, 0);
    const int cl = blockIdx.x >> 1, wg = wi >> 2;
    const bool rec = p.rec0 >= 0 && cl >= p.rec0 && cl < p.rec0 + 32;
    PROF(threadIdx.x == 0, 3500);
    ProRegs pr;
    prologue_load(p.pa, max((int)blockIdx.x - 4, 0), pr);
    if (rec) rec_init(p, sb, cl - p.rec0, rank); else bulk_init(sb);
    if (threadIdx.x == 352 && p.dopro && cl >= 2) {
        mbar_init(sb + S_XBAR, 1);
        asm volatile("fence.mbarrier_init.release.cluster;" ::: "memory");
        mbar_expect(sb + S_XBAR, 32768);
        for (int j = 0; j < 8; j++) tma2d(sb + P_X + j * 4096, &p.tm[3], ((blockIdx.x - 4) >> 1) * 8, j * 256, sb + S_XBAR);
    }
    if (threadIdx.x == 320) {
        unsigned v;
        asm volatile("ld.relaxed.gpu.global.u32 %0,[%1];" : "=r"(v) : "l"(g_gate) : "memory");
        v = v / (4 * NCL) + p.dopro;
        sts64(sb + S_GATE, v * (4 * NCL), v & 1);
    }
    __syncwarp();
    asm volatile("barrier.cluster.arrive.relaxed.aligned;" ::: "memory");
    if (wg == 2) bar_arrive(8, 384);
    if (p.dopro && cl >= 2) prologue(p.pa, sb, blockIdx.x - 4, wi, pr); else if (wg < 2) bar_sync(8, 384);
    asm volatile("barrier.cluster.wait.aligned;" ::: "memory");
    fence_async_smem();
    bar_sync(wg == 2 ? 7 : 1, wg == 2 ? 128 : 256);
    if (p.dopro && (threadIdx.x == 32 || threadIdx.x == 352)) red_release(g_gate, 1);
    if (rec) {
        if (threadIdx.x == 0) {
            rec_fetch(&p.tm[1], sb + R_STK, (cl - p.rec0) * 128, rank * 256, 2, sb + R_BAR + RB_INIT * 8);
            rec_fetch(&p.tm[2], sb + R_STV, (cl - p.rec0) * 128, rank * 256, 2, sb + R_BAR + RB_INIT * 8);
        }
    }
    PROF(threadIdx.x == 0, 3506);
    __syncwarp();
    if (rec) {
        const int head = cl - p.rec0;
        if (wg == 2) {
            reg_dec<RH>();
            const int w = wi & 3;
            if (threadIdx.x == 256) rec_fetch(&p.tm[0], sb + R_STQ, head * 128, rank * 256, 2, sb + R_BAR + RB_INIT * 8);
            __syncwarp();
            wait_cnt_warp(g_gate, lds32(sb + S_GATE));
            if (p.dostats) x1_stats((head * 2 + rank) * 4 + w);
            __syncthreads();
            cluster_sync();
            if ((p.chains >> (w >> 1)) & 1) rec_attn(p, sb, w >> 1, w & 1, head, rank);
        } else {
            reg_inc<RW0>();
            rec_weights(p, sb, head, rank, wi);
        }
    } else {
        if (wg == 2) {
            reg_dec<40>();
            const int w = wi & 3;
            if (w == 0) bulk_producer(p, sb, cl, rank); else if (w >= 2) bulk_release(p, sb, cl, rank, w - 2); else bulk_relay(p, sb, cl);
        } else { reg_inc<232>(); bulk_consumer(p, sb, cl, rank, wi); }
    }
    __syncwarp();
    cluster_sync();
}

typedef CUresult (*EncFn)(CUtensorMap*, CUtensorMapDataType, cuuint32_t, void*, const cuuint64_t*, const cuuint64_t*, const cuuint32_t*, const cuuint32_t*,
                          CUtensorMapInterleave, CUtensorMapSwizzle, CUtensorMapL2promotion, CUtensorMapFloatOOBfill);
inline uint32_t mk(int type, int layer, int ch, int a, int b, int c) { return type | (layer << 3) | (ch << 4) | (a << 8) | (b << 16) | ((uint32_t)c << 24); }
constexpr int SMEM_BYTES = 232448;

struct Sched {
    Params* P; int n[NCL];
    void clear() { memset(P->task, 0, sizeof(P->task)); memset(n, 0, sizeof(n)); }
    void add(int cl, uint32_t t) { if (n[cl] < MAXT - 1) P->task[cl][n[cl]++] = t; }
};

constexpr int REC0 = 4;
struct Cfg { int LAG, TS1, TS2, DQU, DQO, DUN, DHN, MARG, NQ1, FAST0, n0, oc, fc, nuns, ns2, nhg, hs, osl; };
#define PLAN 14, 2300, 2950, 2350, 1600, 6200, 380, 0, 4, 1, 10, 6, 14, 3, 4, 8, 2000, 1000
Cfg g_cfg = {PLAN};
double g_est;
bool g_planned = false;
struct Plan { uint32_t w[NCL][MAXT]; int n[NCL]; double end, rec; };
void simulate(Plan& L, int nc, const Cfg& C) {
    const int LAG = C.LAG, NQ1 = C.NQ1, FAST0 = C.FAST0, n0 = C.n0, oc = C.oc, fc = C.fc, nuns = C.nuns, ns2 = C.ns2, nhg = C.nhg;
    const double TS1 = C.TS1, TS2 = C.TS2, DQU = C.DQU, DQO = C.DQO, DUN = C.DUN, DHN = C.DHN, MARG = C.MARG, hs = C.hs;
    const double INF = 1e18, DKB = 600, DOV = 700, DH = DHN, DHO = 1100, DF = 2200, DFB = 200, POLL = 450, FILL = 500, PUB = 600;
    enum { Q0, O0, Q1, HB, O1, FI, NK };
    struct Grp { int n, left; double done; } G[NK][16];
    double fr[NCL], it[100] = {}, cv[16];
    int ns[16], last[2][NCL], uc = 0, nit = 0;
    memset(L.n, 0, sizeof(L.n)); L.end = 0;
    auto fast = [&](int c) { return c < FAST0 || c >= fc; };
    for (int c = 0; c < 16; c++) {
        ns[c] = c < nuns ? 1 : c == 15 ? 16 : c == 14 ? 8 : ns2;
        const int cnt[NK] = {c < 2 ? 48 : (c & 1) ? 0 : 96, c < oc ? 8 : OPS1, c == 15 ? 24 : fast(c) ? 16 : 48 / NQ1, c >= 2 && !(c & 1) ? 16 : 0, ns[c], ns[c] == 1 ? 0 : c >= 14 ? 8 : 4};
        for (int k = 0; k < NK; k++) G[k][c] = {cnt[k], cnt[k], 0};
        cv[c] = INF;
    }
    for (int i = 0; i < nc; i++) { fr[i] = 0; last[0][i] = last[1][i] = -1; }
    auto fin = [&](int k, int c) { if ((k == Q0 && c >= 2) || k == HB) c &= ~1; return G[k][c].left ? INF : G[k][c].done; };
    auto len = [&](int i) { return (i >= LAG && i < 64) ? (double)TS2 : (double)TS1; };
    auto end_it = [&](int i) { return i < nit ? it[i] + len(i) : INF; };
    auto nominal = [&](int i) { if (i < nit) return it[i]; double t = nit ? it[nit - 1] : 11000 - TS1; for (int j = nit - 1; j < i; j++) t += len(j); return t; };
    auto put = [&](int i, uint32_t w) { if (L.n[i] < MAXT - 4) L.w[i][L.n[i]++] = w; else L.end = INF; };
    auto rel = [&](int k, int c) {
        switch (k) {
            case Q0: return 0.0;
            case O0: return end_it(4 * c + 3) + PUB + POLL;
            case Q1: return cv[c] + POLL;
            case HB: return cv[c - 2] + 600 + POLL;
            case O1: return end_it(LAG + 4 * c + 3) + PUB + POLL;
            default: return fin(O1, c) + POLL;
        }
    };
    auto dur = [&](int k, int c) {
        switch (k) {
            case Q0: return DQO + (c < 2 ? 2.0 : 1.0) * DQU;
            case O0: return (16 - G[O0][c].n) * DKB + 1200;
            case HB: return DHO + DH * c;
            case Q1: return DQO + 48.0 / G[Q1][c].n * DQU;
            case O1: return DOV + DKB * 64 / ns[c] + (ns[c] == 1 ? 1500 : 0);
            default: return DF + DFB * ns[c] * (c >= 14 ? 0.5 : 1);
        }
    };
    auto o0_est = [&](int c) {
        double t = uc ? cv[uc - 1] - 900 : 0;
        for (int j = uc; j < c; j++) t = fmax(t, nominal(4 * j + 4) + PUB + POLL + FILL) + dur(O0, j) + DUN;
        return fmax(t, nominal(4 * c + 4) + PUB + POLL);
    };
    auto cv_est = [&](int c) { return c < uc ? cv[c] : o0_est(c) + FILL + dur(O0, c) + DUN + 900; };
    auto slot = [&](int k, int c, int i) { return k == O0 ? (i < 8 ? i : nc + 7 - i) : c == 15 ? i : i - 8; };
    while (true) {
        while (nit < 64 + LAG) {
            double t = nit ? end_it(nit - 1) : 0;
            if (nit < 64) t = fmax(t, fin(Q0, nit >> 2) + POLL);
            if (nit >= LAG) t = fmax(t, fin(Q1, (nit - LAG) >> 2) + (nit < 64 ? 0 : POLL));
            if (t >= INF) break;
            it[nit++] = t;
        }
        int i = -1;
        for (int j = 0; j < nc; j++) if (fr[j] < INF && (i < 0 || fr[j] < fr[i])) i = j;
        if (i < 0) break;
        const double t = fr[i];
        double lim = INF;
        if (i < 8 && last[0][i] == uc) {
            if (G[O0][uc].left || fin(HB, uc) >= INF) { fr[i] = t + 200; continue; }
            const double e = fmax(G[O0][uc].done, fin(HB, uc) - 2000) + DUN;
            for (int j = 0; j < 8; j++) { put(j, mk(T_CV, 0, uc, 2 * j, G[O0][uc].n, 0)); fr[j] = e; }
            cv[uc++] = e + 900;
            continue;
        }
        const bool hg = (unsigned)(i - 24) < (unsigned)nhg;
        double hlim = INF;
        for (int c = 2; c < 16 && hg; c++) if (G[HB][c].left) { hlim = cv_est(c - 2) + hs; break; }
        int mine[2] = {-1, -1};
        for (int k = 0; k < 2; k++)
            for (int c = last[k][i] + 1; c < 16 && mine[k] < 0; c++) if ((unsigned)slot(O0 + k, c, i) < (unsigned)G[O0 + k][c].n) mine[k] = c;
        if (mine[0] >= 0) lim = i < 8 ? o0_est(mine[0]) - (uc ? 0 : 8500) : nominal(4 * mine[0] + 4) + PUB + C.osl;
        else if (mine[1] >= 0) lim = cv_est(mine[1]) + POLL;
        else if (i < 16 && G[O1][15].left) lim = fmin(lim, nominal(64 + LAG) + PUB);
        int bk = -1, bc = 0; double bd = INF;
        for (int k = 0; k < NK; k++)
            for (int c = 0; c < 16; c++) {
                const bool urgent = k == O0 || k == Q1 || (k == O1 && c == 15);
                if (!G[k][c].left || ((k == O0 || k == Q1) && c != mine[k - O0]) || (k == O1 && c == 15 && i >= 16)) continue;
                if (rel(k, c) > t || (t + dur(k, c) + (k == Q0 && c >= 2 ? DQU : 0) > lim && !urgent)) continue;
                if (i < 8 && uc && uc < 16 && k != O0) continue;
                if ((k == HB && !hg) || (k != HB && !urgent && t + dur(k, c) + (k == Q0 && c >= 2 ? DQU : 0) > hlim)) continue;
                const double dl = urgent ? -INF : k == HB ? -INF / 2 : k == Q0 ? nominal(4 * c) - 3000 : 1e9 + c * 2 + (k == O1);
                if (dl < bd) { bd = dl; bk = k; bc = c; }
            }
        if (bk < 0) {
            bool any = i < 8 && uc < 16;
            for (int k = 0; k < NK; k++) for (int c = 0; c < 16; c++) any = any || G[k][c].left;
            fr[i] = any ? t + 200 : INF;
            if (t > 400000) { L.end = INF; return; }
            continue;
        }
        Grp& g = G[bk][bc];
        const int n = g.n - g.left, c = bc;
        int nu = 1;
        double d = dur(bk, c);
        if (bk == Q0) for (nu = c < 2 ? 2 : 1; c >= 2 && nu < g.left && (nu < 2 || (nu < n0 && t + d + DQU < fmin(fmin(lim, hlim), bd - MARG))); nu++) d += DQU;
        if (bk == O0 && i >= 8) d += (g.n - 8) * DKB;
        if (bk == Q0 && !c && n >= 32) { nu = 1; d -= DQU; }
        if (bk == O0 || bk == Q1) last[bk - O0][i] = c;
        if (bk == O0 && !c && i < 8) put(i, mk(T_CV, 0, 3, 2 * i, 0, 128));
        g.left -= nu;
        const double e = fmax(t, rel(bk, c) + FILL) + (t < 1 ? 4500 : 0) + d;
        fr[i] = e;
        g.done = fmax(g.done, e + (bk == O1 ? 1900 : bk == O0 ? 0 : (bk == Q1 && g.n < 24) || (bk == Q0 && !c && nu == 2) ? -500 : 1000));
        if (bk == FI || (bk == O1 && ns[c] == 1)) L.end = fmax(L.end, e);
        put(i, bk == Q0 ? (c == 0 ? mk(T_QKV, 0, 0, n < 32 ? n : 2 * n - 32, nu, 32) : c == 1 ? mk(T_QKV, 0, c, n, 2, 24) : mk(T_QKV, 0, c, n, nu, 64))
             : bk == O0 ? (i < 8 ? mk(T_OP, 0, c, i * (16 - g.n), 16 - g.n, i) : mk(T_OP, 0, c, 64 - (nc - i) * 8, 8, slot(O0, c, i)))
             : bk == HB ? mk(T_CV, 1, c, 2 * n, 0, 0)
             : bk == Q1 ? mk(T_QKV, 1, c, slot(Q1, c, i) * 2, 48 / g.n, g.n)
             : bk == O1 ? mk(T_OP, 1, c, n * 64 / ns[c], 64 / ns[c], ns[c] == 1 ? 32 : n)
                        : mk(T_FIN, 1, c, n * (32 / g.n), ns[c], 16 / g.n));
    }
    L.rec = end_it(63 + LAG);
}
void plan(Params& P) {
    P.rec0 = REC0; P.chains = 3; P.lag = g_cfg.LAG; P.dostats = 1; P.dopro = 1;
    static Plan L;
    int cls[NCL], nc = 0;
    for (int c = REC0 + 32; c < NCL; c++) cls[nc++] = c;
    for (int c = REC0 - 1; c >= 0; c--) cls[nc++] = c;
    simulate(L, nc, g_cfg);
    g_est = L.end;
    Sched S; S.P = &P; S.clear();
    S.add(0, mk(T_QKV, 1, 15, 0, 2, 128 + 24)); S.add(0, mk(T_OP, 1, 15, 0, 4, 128));
    S.add(1, mk(T_CV, 0, 3, 0, 0, 128));
    for (int i = 0; i < nc; i++) {
        bool warm = false;
        for (int k = 0; k < L.n[i]; k++) {
            if (!warm && k + 1 < L.n[i] && (L.w[i][k + 1] & 255) == (mk(T_FIN, 1, 15, 0, 0, 0) & 255)) { S.add(cls[i], L.w[i][k + 1] | 0x80000000u); warm = true; }
            S.add(cls[i], L.w[i][k]);
            if ((L.w[i][k] & 7) == T_FIN) warm = true;
        }
    }
}

#define TK0() do {} while (0)
#define TK() do { P.e0 = (P.chains & 1) ? 64 : 0; P.b1 = (P.chains & 2) ? P.lag : 1000; P.nit = (P.chains & 2) ? P.lag + 64 : 64; TK0(); } while (0)
}

extern "C" void kernel_launch(void* const* d_in, const int* in_sizes, int n_in, void* d_out, int out_size) {
    typedef const __nv_bfloat16* BP;
    static EncFn enc = nullptr;
    if (!enc) {
        void* fn = nullptr; cudaDriverEntryPointQueryResult qr;
        cudaGetDriverEntryPoint("cuTensorMapEncodeTiled", &fn, cudaEnableDefault, &qr);
        enc = (EncFn)fn;
        cudaFuncSetAttribute(main_kernel, cudaFuncAttributeMaxDynamicSharedMemorySize, SMEM_BYTES);
    }
    static Params P;
    for (int i = 0; i < 4; i++) {
        const cuuint64_t cols = i < 3 ? 4096 : 512, rows = i < 3 ? 512 : 4096;
        cuuint64_t d2[2] = {cols, rows}, d3[3] = {64, rows, cols / 64}, str[2] = {cols * 2, 128};
        cuuint32_t box[3] = {64, 64, 4}, es[3] = {1, 1, 1};
        enc(&P.tm[i < 3 ? i : 4], CU_TENSOR_MAP_DATA_TYPE_BFLOAT16, 2, d_in[9 + i], d2, str, box, es, CU_TENSOR_MAP_INTERLEAVE_NONE, CU_TENSOR_MAP_SWIZZLE_128B,
                       CU_TENSOR_MAP_L2_PROMOTION_L2_128B, CU_TENSOR_MAP_FLOAT_OOB_FILL_NONE);
        for (int m = 0; m < 2; m++) {
            cuuint32_t box3[3] = {64, 32, m ? 2u : 4u};
            enc(&P.t3[m][i], CU_TENSOR_MAP_DATA_TYPE_BFLOAT16, 3, d_in[9 + i], d3, str, box3, es, CU_TENSOR_MAP_INTERLEAVE_NONE, CU_TENSOR_MAP_SWIZZLE_128B,
                CU_TENSOR_MAP_L2_PROMOTION_L2_128B, CU_TENSOR_MAP_FLOAT_OOB_FILL_NONE);
        }
    }
    {
        cuuint64_t dims[2] = {512, 2048}, str[1] = {1024};
        cuuint32_t box[2] = {8, 256}, es[2] = {1, 1};
        enc(&P.tm[3], CU_TENSOR_MAP_DATA_TYPE_BFLOAT16, 2, d_in[0], dims, str, box, es, CU_TENSOR_MAP_INTERLEAVE_NONE, CU_TENSOR_MAP_SWIZZLE_NONE,
            CU_TENSOR_MAP_L2_PROMOTION_NONE, CU_TENSOR_MAP_FLOAT_OOB_FILL_NONE);
    }
    for (int m = 0; m < 2; m++) {
        void* ga; cudaGetSymbolAddress(&ga, g_A);
        cuuint64_t dims[2] = {512, sizeof(AOps) / 1024}, str[1] = {1024};
        cuuint32_t box[2] = {256, m ? 16u : 8u}, es[2] = {1, 1};
        enc(&P.ta[m], CU_TENSOR_MAP_DATA_TYPE_BFLOAT16, 2, ga, dims, str, box, es, CU_TENSOR_MAP_INTERLEAVE_NONE, CU_TENSOR_MAP_SWIZZLE_NONE,
            CU_TENSOR_MAP_L2_PROMOTION_L2_128B, CU_TENSOR_MAP_FLOAT_OOB_FILL_NONE);
    }
    P.mem0 = (BP)d_in[8]; P.Wo = (BP)d_in[12]; P.Dskip = (BP)d_in[6]; P.out = (__nv_bfloat16*)d_out;
    cudaStream_t s = cudaStreamPerThread;
    P.pa = {(BP)d_in[0], (BP)d_in[1], (BP)d_in[2], (BP)d_in[3], (BP)d_in[4], (BP)d_in[5], (BP)d_in[6], (BP)d_in[9], (BP)d_in[10], (BP)d_in[11], (BP)d_in[12], (BP)d_in[8]};
    if (!g_planned) { plan(P); g_planned = true; }
    TK(); main_kernel<<<2 * NCL, 384, SMEM_BYTES, s>>>(P); TK();
}
```

```cpp
#include <cuda_runtime.h>
#include <cuda_bf16.h>
#include <cuda.h>
#include <stdint.h>
#include <string.h>
#include <math.h>

namespace {

constexpr int NCL = 66;
constexpr int MAXT = 64;
#define PFC 1
#define QB1 2
#define QB2 4
#define QB3 6
#define LAGQ 2
#define CPOS 2
#define OPS1N 10
constexpr int OPS1 = OPS1N;
constexpr int MAXSPLIT = 16;
constexpr int PW = 144;

struct AOps { uint4 x[2][16 * 8 * 1024], o[2][16 * 64 * 1024]; };
__device__ AOps g_A;
#define g_xA g_A.x
#define g_o g_A.o
__device__ float2 g_st[2][16 * 2048];
__device__ float2 g_st2[2 * 16 * 128];
__device__ uint4 g_qkv[2][64 * 64 * 768];
__device__ uint4 g_pp[2][16 * MAXSPLIT * 8192];
__device__ uint4 g_acc[7 * 2048];
__device__ unsigned g_gate[32];
__device__ uint32_t g_P[16 * 16 * 32 * PW];
__device__ uint4 g_u[16 * 16 * 512];
__device__ float4 g_carry[2][17 * 16 * 4 * 256];
__device__ unsigned g_cnt[13 * 64];
__device__ uint32_t g_ln0[2048];

enum { C_QKV0 = 0, C_QKV1 = 1  , C_O0 = 2, C_O1 = 3, C_U = 4, C_OP1 = 5, C_CV = 6, C_ST = 7, C_H = 8, C_OP0 = 9   };
__device__ __forceinline__ unsigned* cnt_ptr(int kind, int chunk) { return g_cnt + kind * 64 + chunk; }

enum { T_END = 0, T_QKV = 1, T_OP = 2, T_CV = 3, T_FIN = 4 };
struct ProArgs { const __nv_bfloat16 *x, *lAr, *Ai, *Cr, *Ci, *ldt, *Dk, *Wq, *Wk, *Wv, *Wo, *mem0; };
struct Params {
    CUtensorMap tm[5];
    CUtensorMap t3[2][4];
    CUtensorMap ta[2];
    ProArgs pa;
    int dopro;
    const __nv_bfloat16* mem0;
    const __nv_bfloat16* Wo;
    const __nv_bfloat16* Dskip;
    __nv_bfloat16* out;
    int rec0;
    int chains;
    int lag;
    int b1, e0, nit;
    int zero, gpit;
    int dostats;
    uint32_t task[NCL][MAXT];
};

__device__ __forceinline__ uint32_t smem_u32(const void* p) { return (uint32_t)__cvta_generic_to_shared(p); }
__device__ __forceinline__ uint32_t mapa(uint32_t a, uint32_t r) {
    uint32_t o; asm("mapa.shared::cluster.u32 %0,%1,%2;" : "=r"(o) : "r"(a), "r"(r)); return o;
}
__device__ __forceinline__ void mbar_init(uint32_t b, int c) { asm volatile("mbarrier.init.shared::cta.b64 [%0],%1;" ::"r"(b), "r"(c) : "memory"); }
__device__ __forceinline__ void mbar_expect(uint32_t b, int bytes) { asm volatile("mbarrier.arrive.expect_tx.shared::cta.b64 _,[%0],%1;" ::"r"(b), "r"(bytes) : "memory"); }
__device__ __forceinline__ void mbar_arrive(uint32_t b) { asm volatile("mbarrier.arrive.shared::cta.b64 _,[%0];" ::"r"(b) : "memory"); }
__device__ __forceinline__ void mbar_arrive_cluster(uint32_t b) { asm volatile("mbarrier.arrive.shared::cluster.b64 _,[%0];" ::"r"(b) : "memory"); }
__device__ __forceinline__ void mbar_arrive1(uint32_t b) { asm volatile("{.reg .pred p; elect.sync _|p,0xffffffff; @p mbarrier.arrive.shared::cta.b64 _,[%0];}" ::"r"(b) : "memory"); }
__device__ __forceinline__ void mbar_arrive1_cluster(uint32_t b) { asm volatile("{.reg .pred p; elect.sync _|p,0xffffffff; @p mbarrier.arrive.shared::cluster.b64 _,[%0];}" ::"r"(b) : "memory"); }
__device__ __forceinline__ void mbar_wait(uint32_t b, uint32_t ph) {
    asm volatile(
        "{.reg .pred p; .reg .u32 n; mov.u32 n,0;\n"
        "W%=: mbarrier.try_wait.parity.shared::cta.b64 p,[%0],%1;\n"
        "@p bra D%=;\n"
        "add.u32 n,n,1; setp.lt.u32 p,n,2000000; @p bra W%=;\n"
        "trap;\n"
        "D%=: }" ::"r"(b), "r"(ph) : "memory");
}
__device__ __forceinline__ bool mbar_test(uint32_t b, uint32_t ph) {
    uint32_t ok;
    asm volatile("{.reg .pred p; mbarrier.test_wait.parity.shared::cta.b64 p,[%1],%2; selp.u32 %0,1,0,p;}" : "=r"(ok) : "r"(b), "r"(ph) : "memory");
    return ok;
}
__device__ __forceinline__ bool wait_lds128(uint32_t b, uint32_t ph, uint32_t a, uint4& v) {
    uint32_t ok;
    asm volatile("{.reg .pred p; mbarrier.try_wait.parity.shared::cta.b64 p,[%5],%6,20000; ld.shared.v4.u32 {%0,%1,%2,%3},[%7]; selp.u32 %4,1,0,p;}"
                 : "=r"(v.x), "=r"(v.y), "=r"(v.z), "=r"(v.w), "=r"(ok) : "r"(b), "r"(ph), "r"(a) : "memory");
    return ok;
}
__device__ __forceinline__ bool wait_lds64(uint32_t b, uint32_t ph, uint32_t a, uint2& v) {
    uint32_t ok;
    asm volatile("{.reg .pred p; mbarrier.try_wait.parity.shared::cta.b64 p,[%3],%4,20000; ld.shared.v2.u32 {%0,%1},[%5]; selp.u32 %2,1,0,p;}"
                 : "=r"(v.x), "=r"(v.y), "=r"(ok) : "r"(b), "r"(ph), "r"(a) : "memory");
    return ok;
}
template <int PH> __device__ __forceinline__ void mbar_wait_c(uint32_t b) {
    asm volatile(
        "{.reg .pred p; .reg .u32 n; mov.u32 n,%2;\n"
        "W%=: mbarrier.try_wait.parity.shared::cta.b64 p,[%0],%1;\n"
        "@p bra D%=;\n"
        "add.u32 n,n,1; setp.lt.u32 p,n,2000000; @p bra W%=;\n"
        "trap;\n"
        "D%=: }" ::"r"(b), "n"(PH), "n"(PH) : "memory");
}
__device__ __forceinline__ void bar_sync(int id, int n) { asm volatile("bar.sync %0,%1;" ::"r"(id), "r"(n) : "memory"); }
__device__ __forceinline__ void bar_arrive(int id, int n) { asm volatile("bar.arrive %0,%1;" ::"r"(id), "r"(n) : "memory"); }
__device__ __forceinline__ void cluster_sync() { asm volatile("barrier.cluster.arrive.relaxed.aligned; barrier.cluster.wait.aligned;" ::: "memory"); }
__device__ __forceinline__ void fence_async() { asm volatile("fence.proxy.async;" ::: "memory"); }
__device__ __forceinline__ void fence_async_smem() { asm volatile("fence.proxy.async.shared::cta;" ::: "memory"); }
#define EFR 1
#define EFW 2
constexpr uint64_t POL_N = 0x1000000000000000ull, POL_F = 0x12F0000000000000ull;
constexpr uint64_t POL_LAST = EFR ? POL_F : POL_N  , POL_LATE = EFW ? POL_F : POL_N  , POL_SOON = EFW > 1 ? POL_F : POL_N;
__device__ __forceinline__ void bulk_g2s(uint32_t dst, const void* src, int bytes, uint32_t bar, uint64_t pol) {
    asm volatile("cp.async.bulk.shared::cluster.global.mbarrier::complete_tx::bytes.L2::cache_hint [%0],[%1],%2,[%3],%4;" ::"r"(dst), "l"(src), "r"(bytes), "r"(bar), "l"(pol) : "memory");
}
__device__ __forceinline__ void bulk_g2s_mc(uint32_t dst, const void* src, int bytes, uint32_t bar, uint64_t pol) {
    asm volatile("cp.async.bulk.shared::cluster.global.mbarrier::complete_tx::bytes.multicast::cluster.L2::cache_hint [%0],[%1],%2,[%3],%4,%5;" ::"r"(dst), "l"(src), "r"(bytes), "r"(bar), "h"((uint16_t)3), "l"(pol) : "memory");
}
__device__ __forceinline__ void bulk_s2s(uint32_t dst, uint32_t src, int bytes, uint32_t bar) {
    asm volatile("cp.async.bulk.shared::cluster.shared::cta.mbarrier::complete_tx::bytes [%0],[%1],%2,[%3];" ::"r"(dst), "r"(src), "r"(bytes), "r"(bar) : "memory");
}
__device__ __forceinline__ bool elect() {
    uint32_t r; asm volatile("{.reg .pred p; elect.sync _|p,0xffffffff; selp.u32 %0,1,0,p;}" : "=r"(r)); return r;
}
__device__ __forceinline__ void stg128(uint4* p, uint4 v, uint64_t pol) {
    asm volatile("st.global.L2::cache_hint.v4.u32 [%0],{%1,%2,%3,%4},%5;" ::"l"(p), "r"(v.x), "r"(v.y), "r"(v.z), "r"(v.w), "l"(pol));
}
__device__ __forceinline__ void stg32(uint32_t* p, uint32_t v, uint64_t pol) { asm volatile("st.global.L2::cache_hint.u32 [%0],%1,%2;" ::"l"(p), "r"(v), "l"(pol)); }
__device__ __forceinline__ uint4 ldcg128_last(const uint4* p) {
    uint4 v; asm volatile("ld.global.cg.L2::cache_hint.v4.u32 {%0,%1,%2,%3},[%4],%5;" : "=r"(v.x), "=r"(v.y), "=r"(v.z), "=r"(v.w) : "l"(p), "l"(POL_LAST) : "memory"); return v;
}
__device__ __forceinline__ void tma2d(uint32_t dst, const CUtensorMap* tm, int x, int y, uint32_t bar) {
    asm volatile("cp.async.bulk.tensor.2d.shared::cluster.global.mbarrier::complete_tx::bytes [%0],[%1,{%2,%3}],[%4];" ::"r"(dst), "l"(tm), "r"(x), "r"(y), "r"(bar) : "memory");
}
__device__ __forceinline__ void tma3d_mc(uint32_t dst, const CUtensorMap* tm, int y, int z, uint32_t bar, uint16_t mask) {
    asm volatile("{.reg .pred p; elect.sync _|p,0xffffffff;\n"
                 "@p cp.async.bulk.tensor.3d.shared::cluster.global.mbarrier::complete_tx::bytes.multicast::cluster [%0],[%1,{0,%2,%3}],[%4],%5;}"
                 ::"r"(dst), "l"(tm), "r"(y), "r"(z), "r"(bar), "h"(mask) : "memory");
}
__device__ __forceinline__ void tma2d_mc(uint32_t dst, const CUtensorMap* tm, int x, int y, uint32_t bar, uint16_t mask, uint64_t pol) {
    asm volatile("{.reg .pred p; elect.sync _|p,0xffffffff;\n"
                 "@p cp.async.bulk.tensor.2d.shared::cluster.global.mbarrier::complete_tx::bytes.multicast::cluster.L2::cache_hint [%0],[%1,{%2,%3}],[%4],%5,%6;}"
                 ::"r"(dst), "l"(tm), "r"(x), "r"(y), "r"(bar), "h"(mask), "l"(pol) : "memory");
}
__device__ __forceinline__ void bulk_g2s1(uint32_t dst, const void* src, int bytes, uint32_t bar, uint64_t pol) {
    asm volatile("{.reg .pred p; elect.sync _|p,0xffffffff;\n"
                 "@p cp.async.bulk.shared::cluster.global.mbarrier::complete_tx::bytes.L2::cache_hint [%0],[%1],%2,[%3],%4;}" ::"r"(dst), "l"(src), "r"(bytes), "r"(bar), "l"(pol) : "memory");
}
__device__ __forceinline__ void mbar_expect1(uint32_t b, int bytes) {
    asm volatile("{.reg .pred p; elect.sync _|p,0xffffffff; @p mbarrier.arrive.expect_tx.shared::cta.b64 _,[%0],%1;}" ::"r"(b), "r"(bytes) : "memory");
}
__device__ __forceinline__ void st_async4(uint32_t a, uint32_t x, uint32_t y, uint32_t z, uint32_t w, uint32_t mb) {
    asm volatile("st.async.shared::cluster.mbarrier::complete_tx::bytes.v4.b32 [%0],{%1,%2,%3,%4},[%5];" ::"r"(a), "r"(x), "r"(y), "r"(z), "r"(w), "r"(mb) : "memory");
}
__device__ __forceinline__ void st_async2(uint32_t a, uint32_t x, uint32_t y, uint32_t mb) {
    asm volatile("st.async.shared::cluster.mbarrier::complete_tx::bytes.v2.b32 [%0],{%1,%2},[%3];" ::"r"(a), "r"(x), "r"(y), "r"(mb) : "memory");
}
#define LDSQ "ld.shared"
__device__ __forceinline__ uint4 lds128(uint32_t a) { uint4 v; asm volatile(LDSQ ".v4.u32 {%0,%1,%2,%3},[%4];" : "=r"(v.x), "=r"(v.y), "=r"(v.z), "=r"(v.w) : "r"(a) : "memory"); return v; }
__device__ __forceinline__ uint2 lds64(uint32_t a) { uint2 v; asm volatile(LDSQ ".v2.u32 {%0,%1},[%2];" : "=r"(v.x), "=r"(v.y) : "r"(a) : "memory"); return v; }
__device__ __forceinline__ uint32_t lds32(uint32_t a) { uint32_t v; asm volatile(LDSQ ".u32 %0,[%1];" : "=r"(v) : "r"(a) : "memory"); return v; }
__device__ __forceinline__ void sts128(uint32_t a, uint32_t x, uint32_t y, uint32_t z, uint32_t w) { asm volatile("st.shared.v4.u32 [%0],{%1,%2,%3,%4};" ::"r"(a), "r"(x), "r"(y), "r"(z), "r"(w) : "memory"); }
__device__ __forceinline__ void sts64(uint32_t a, uint32_t x, uint32_t y) { asm volatile("st.shared.v2.u32 [%0],{%1,%2};" ::"r"(a), "r"(x), "r"(y) : "memory"); }
__device__ __forceinline__ void sts32(uint32_t a, uint32_t x) { asm volatile("st.shared.u32 [%0],%1;" ::"r"(a), "r"(x) : "memory"); }
__device__ __forceinline__ uint4 ldsm4(uint32_t a) { uint4 v; asm volatile("ldmatrix.sync.aligned.m8n8.x4.shared.b16 {%0,%1,%2,%3},[%4];" : "=r"(v.x), "=r"(v.y), "=r"(v.z), "=r"(v.w) : "r"(a) : "memory"); return v; }
__device__ __forceinline__ uint4 ldsm4t(uint32_t a) { uint4 v; asm volatile("ldmatrix.sync.aligned.m8n8.x4.trans.shared.b16 {%0,%1,%2,%3},[%4];" : "=r"(v.x), "=r"(v.y), "=r"(v.z), "=r"(v.w) : "r"(a) : "memory"); return v; }
__device__ __forceinline__ uint32_t movm(uint32_t a) { uint32_t d; asm volatile("movmatrix.sync.aligned.m8n8.trans.b16 %0,%1;" : "=r"(d) : "r"(a)); return d; }
__device__ __forceinline__ uint32_t pack2(float lo, float hi) { uint32_t d; asm("cvt.rn.bf16x2.f32 %0,%1,%2;" : "=r"(d) : "f"(hi), "f"(lo)); return d; }
__device__ __forceinline__ uint32_t hadd2(uint32_t a, uint32_t b) { uint32_t d; asm("add.rn.bf16x2 %0,%1,%2;" : "=r"(d) : "r"(a), "r"(b)); return d; }
__device__ __forceinline__ float blo(uint32_t v) { return __uint_as_float(v << 16); }
__device__ __forceinline__ float bhi(uint32_t v) { return __uint_as_float(v & 0xffff0000u); }
__device__ __forceinline__ float rbf(float x) { return __uint_as_float(pack2(0.f, x)); }
__device__ __forceinline__ float ex2(float x) { float y; asm("ex2.approx.ftz.f32 %0,%1;" : "=f"(y) : "f"(x)); return y; }
__device__ __forceinline__ float rcp(float x) { float y; asm("rcp.approx.ftz.f32 %0,%1;" : "=f"(y) : "f"(x)); return y; }
__device__ __forceinline__ void mma16(float* c, uint32_t a0, uint32_t a1, uint32_t a2, uint32_t a3, uint32_t b0, uint32_t b1) {
    asm volatile("mma.sync.aligned.m16n8k16.row.col.f32.bf16.bf16.f32 {%0,%1,%2,%3},{%4,%5,%6,%7},{%8,%9},{%0,%1,%2,%3};"
                 : "+f"(c[0]), "+f"(c[1]), "+f"(c[2]), "+f"(c[3]) : "r"(a0), "r"(a1), "r"(a2), "r"(a3), "r"(b0), "r"(b1));
}
__device__ __forceinline__ void mma8(float* c, uint32_t a0, uint32_t a1, uint32_t b0) {
    asm volatile("mma.sync.aligned.m16n8k8.row.col.f32.bf16.bf16.f32 {%0,%1,%2,%3},{%4,%5},{%6},{%0,%1,%2,%3};"
                 : "+f"(c[0]), "+f"(c[1]), "+f"(c[2]), "+f"(c[3]) : "r"(a0), "r"(a1), "r"(b0));
}
__device__ __forceinline__ uint4 ld_rlx128(const uint4* p) {
    uint4 v;
    asm volatile("{.reg .b128 t; ld.relaxed.gpu.global.b128 t,[%4]; mov.b128 {%0,%1,%2,%3},t;}" : "=r"(v.x), "=r"(v.y), "=r"(v.z), "=r"(v.w) : "l"(p) : "memory");
    return v;
}
__device__ __forceinline__ void st_rlx128(uint4* p, uint32_t x, uint32_t y, uint32_t z, uint32_t w) {
    asm volatile("{.reg .b128 t; mov.b128 t,{%1,%2,%3,%4}; st.relaxed.gpu.global.b128 [%0],t;}" ::"l"(p), "r"(x), "r"(y), "r"(z), "r"(w) : "memory");
}
__device__ __forceinline__ uint4 ldcg128(const uint4* p) { uint4 v; asm volatile("ld.global.cg.v4.u32 {%0,%1,%2,%3},[%4];" : "=r"(v.x), "=r"(v.y), "=r"(v.z), "=r"(v.w) : "l"(p) : "memory"); return v; }
__device__ __forceinline__ void red_release(unsigned* p, unsigned v) {
    asm volatile("fence.proxy.async; red.relaxed.gpu.global.add.u32 [%0],%1;" ::"l"(p), "r"(v) : "memory");
}
__device__ __forceinline__ void wait_cnt(const unsigned* p, unsigned target) {
    unsigned v; int n = 0;
    while (true) {
        asm volatile("ld.acquire.gpu.global.u32 %0,[%1];" : "=r"(v) : "l"(p) : "memory");
        if (v >= target) break;
        if (++n > 3000000) __trap();
        __nanosleep(40);
    }
}
__device__ __forceinline__ void wait_cnt_warp(const unsigned* p, unsigned target) {
    unsigned v; int n = 0;
    while (true) {
        asm volatile("ld.acquire.gpu.global.u32 %0,[%1];" : "=r"(v) : "l"(p) : "memory");
        if (__all_sync(0xffffffffu, v >= target)) break;
        if (++n > 3000000) __trap();
    }
}
__device__ __forceinline__ uint64_t mkdesc(uint32_t addr, uint32_t lbo, uint32_t sbo, uint32_t sw) {
    return (uint64_t)((addr & 0x3FFFF) >> 4) | ((uint64_t)(lbo >> 4) << 16) | ((uint64_t)(sbo >> 4) << 32) | ((uint64_t)sw << 62);
}
__device__ __forceinline__ void wg_fence() { asm volatile("wgmma.fence.sync.aligned;" ::: "memory"); }
__device__ __forceinline__ void wg_commit() { asm volatile("wgmma.commit_group.sync.aligned;" ::: "memory"); }
template <int N> __device__ __forceinline__ void wg_wait() { asm volatile("wgmma.wait_group.sync.aligned %0;" ::"n"(N) : "memory"); }
#define R8(c, o) "+f"(c[o]), "+f"(c[o + 1]), "+f"(c[o + 2]), "+f"(c[o + 3]), "+f"(c[o + 4]), "+f"(c[o + 5]), "+f"(c[o + 6]), "+f"(c[o + 7])
#define R32(c, o) R8(c, o), R8(c, o + 8), R8(c, o + 16), R8(c, o + 24)
#define S32A "%0,%1,%2,%3,%4,%5,%6,%7,%8,%9,%10,%11,%12,%13,%14,%15,%16,%17,%18,%19,%20,%21,%22,%23,%24,%25,%26,%27,%28,%29,%30,%31"
#define S32B ",%32,%33,%34,%35,%36,%37,%38,%39,%40,%41,%42,%43,%44,%45,%46,%47,%48,%49,%50,%51,%52,%53,%54,%55,%56,%57,%58,%59,%60,%61,%62,%63"
#define S32C ",%64,%65,%66,%67,%68,%69,%70,%71,%72,%73,%74,%75,%76,%77,%78,%79,%80,%81,%82,%83,%84,%85,%86,%87,%88,%89,%90,%91,%92,%93,%94,%95"
#define S32D ",%96,%97,%98,%99,%100,%101,%102,%103,%104,%105,%106,%107,%108,%109,%110,%111,%112,%113,%114,%115,%116,%117,%118,%119,%120,%121,%122,%123,%124,%125,%126,%127"
#define W8(c, o) "=f"(c[o]), "=f"(c[o + 1]), "=f"(c[o + 2]), "=f"(c[o + 3]), "=f"(c[o + 4]), "=f"(c[o + 5]), "=f"(c[o + 6]), "=f"(c[o + 7])
#define W32(c, o) W8(c, o), W8(c, o + 8), W8(c, o + 16), W8(c, o + 24)
template <bool ACC> __device__ __forceinline__ void wgmma256(float* c, uint64_t da, uint64_t db) {
    if (ACC) asm volatile("wgmma.mma_async.sync.aligned.m64n256k16.f32.bf16.bf16 {" S32A S32B S32C S32D "},%128,%129,1,1,1,0,1;"
                          : R32(c, 0), R32(c, 32), R32(c, 64), R32(c, 96) : "l"(da), "l"(db));
    else asm volatile("wgmma.mma_async.sync.aligned.m64n256k16.f32.bf16.bf16 {" S32A S32B S32C S32D "},%128,%129,0,1,1,0,1;"
                      : W32(c, 0), W32(c, 32), W32(c, 64), W32(c, 96) : "l"(da), "l"(db));
}
template <bool ACC> __device__ __forceinline__ void wgmma128r(float* c, const uint4& a, uint64_t db) {
    if (ACC) asm volatile("wgmma.mma_async.sync.aligned.m64n128k16.f32.bf16.bf16 {" S32A S32B "},{%64,%65,%66,%67},%68,1,1,1,1;"
                          : R32(c, 0), R32(c, 32) : "r"(a.x), "r"(a.y), "r"(a.z), "r"(a.w), "l"(db));
    else asm volatile("wgmma.mma_async.sync.aligned.m64n128k16.f32.bf16.bf16 {" S32A S32B "},{%64,%65,%66,%67},%68,0,1,1,1;"
                      : W32(c, 0), W32(c, 32) : "r"(a.x), "r"(a.y), "r"(a.z), "r"(a.w), "l"(db));
}
template <int N> __device__ __forceinline__ void reg_inc() { asm volatile("setmaxnreg.inc.sync.aligned.u32 %0;" ::"n"(N)); }
template <int N> __device__ __forceinline__ void reg_dec() { asm volatile("setmaxnreg.dec.sync.aligned.u32 %0;" ::"n"(N)); }

#define PROF(cond, idx) do {} while (0)
#define CPROF(k) do {} while (0)

constexpr int S_GATE = 232440, S_TAG = 232444, S_XBAR = 232432;
constexpr float SC_LOG2E = 0.08838834764831845f * 1.4426950408889634f;

__device__ __forceinline__ float2 ln_finish(float mean, float var) {
    float sd; asm("sqrt.approx.f32 %0,%1;" : "=f"(sd) : "f"(rbf(rbf(var) + 1e-5f)));
    sd = rbf(sd);
    return make_float2(rbf(mean), sd);
}

__device__ __forceinline__ float4 row_stats(const uint4* src, int stride) {
    const int g = (threadIdx.x & 31) >> 2;
    uint4 v[16];
#pragma unroll
    for (int i = 0; i < 16; i++) v[i] = ldcg128(src + i * stride);
    float a[4] = {0, 0, 0, 0}, q0[4] = {0, 0, 0, 0}, q1[4] = {0, 0, 0, 0};
#pragma unroll
    for (int i = 0; i < 16; i++) {
        mma16(a, v[i].x, v[i].y, v[i].z, v[i].w, 0x3f803f80u, 0x3f803f80u);
        mma8(q0, v[i].x, v[i].y, v[i].x); mma8(q1, v[i].x, v[i].y, v[i].y);
        mma8(q0, v[i].z, v[i].w, v[i].z); mma8(q1, v[i].z, v[i].w, v[i].w);
    }
    return make_float4(a[0], (g & 1) ? q0[1] : q0[0], a[2], (g & 1) ? q1[3] : q1[2]);
}
__device__ __forceinline__ void x1_stats(int i) {
    const int lane = threadIdx.x & 31, g = lane >> 2, c = lane & 3;
    const float4 r = row_stats(g_xA[0] + i * 512 + lane, 32);
    float2* dst = g_st[0] + (i >> 4) * 2048 + ((i < 32 ? 4 : 0) + (i & 1)) * 128 + ((i >> 1) & 7) * 16 + g;
    if (c == (g >> 1)) { dst[0] = make_float2(r.x, r.y); dst[8] = make_float2(r.z, r.w); g_ln0[i * 8 + g] = 0; }
    __syncwarp();
    if (lane == 0) red_release(cnt_ptr(C_ST, i >> 4), 1);
}
__global__ void stats_kernel() { x1_stats(blockIdx.x * 4 + (threadIdx.x >> 5)); }

#define NT 9
#define RH 104
#define RW0 200
#define NPD 9
#define NTO 13
#define DP1 9
#define GPW 0
#define GPJ 0
#define PACE 2
#define BKA 0
#define GSE 4
#define EARLY 4
#define PFD 0
#define PFB 0
#define G2S 7
#define XPRE 0
#define STO 1
#define G2I 2
#define VE 4
#define VF 8
constexpr int R_WV = 0, R_WO = 65536, R_T = 131072, R_M = R_T + 20480, R_LOC = R_M + 4096, R_REM = R_LOC + 6144, R_O = R_REM + 12288, R_SX = R_O + 2048,
              R_IL = R_SX + 5120, XS = R_IL + 128 - R_T, R_BAR = 231936, R_Z = R_BAR + 128  , R_STQ = 0, R_STK = 65536, R_STV = 131072;
static_assert(R_T + 2 * XS <= R_BAR && R_BAR + 256 <= S_XBAR, "smem map");
enum { RB_INIT = 0, RB_MB = 1, RB_V = 4  , RB_QK = 8  , RB_T = 12  , RB_N = 16 };
enum { NB_MF = 1  , NB_LOC = 3  , NB_PAIR = 5  , NB_O = 9  , NB_XG = 11  , NB_W = 13 };
__device__ __forceinline__ uint32_t clk32() { return (uint32_t)clock64(); }

__device__ __forceinline__ char* acc_base() { return (char*)(((size_t)g_acc + 131071) & ~(size_t)131071); }
__device__ __forceinline__ uint32_t acc_slice(uint32_t s6) { return (s6 & 1) * 256 + (s6 >> 1) * 1024; }
__device__ __forceinline__ uint32_t acc_main(uint32_t rank, uint32_t tid) { return acc_slice(rank * 32 + (tid >> 3)) + (tid & 7) * 16; }
__device__ __forceinline__ uint32_t acc_extra(uint32_t rank, uint32_t tid) { return 65536 + acc_slice(((tid >> 5) & 1) + rank * 4 + (tid >> 6) * 8) + (tid & 31) * 4; }
__device__ __forceinline__ uint32_t acc_slot(uint32_t s) { return (s & 1) * 128 + (s & 2) * 256; }
__device__ __forceinline__ void acc_init(const __nv_bfloat16* mem0, int i) {
    const uint32_t tid = i & 255, rank = (i >> 8) & 1, slot = (i >> 9) & 3, X = i >> 11;
    uint32_t v[5] = {0, 0, 0, 0, 0};
    if (slot == 3) {
        const uint16_t* m = (const uint16_t*)mem0 + (tid & 3) * 1024 + rank * 256 + (tid >> 5) * 32 + ((tid >> 2) & 7);
#pragma unroll
        for (int k = 0; k < 4; k++) v[k] = __ldg(m + k * 8) | ((uint32_t)__ldg(m + k * 8 + 512) << 16);
        v[4] = (v[3] >> 16) | 0x42000000u; v[3] = (v[3] & 0xffff) | 0x42000000u;
    }
    *(uint4*)(acc_base() + X * 32768 + acc_slot(slot) + acc_main(rank, tid)) = make_uint4(v[0], v[1], v[2], v[3]);
    *(uint32_t*)(acc_base() + X * 1024 + acc_slot(slot) + acc_extra(rank, tid)) = v[4];
}
__global__ void acc_init_kernel(const __nv_bfloat16* mem0) { acc_init(mem0, blockIdx.x * 256 + threadIdx.x); }

struct RecW { uint32_t am, ae, ah, dp, lp, lpw, vo, sb, bar, zero, ts, tn; };
__device__ __forceinline__ uint32_t vadd(uint32_t a, uint32_t b) { uint32_t d; asm volatile("add.u32 %0,%1,%2;" : "=r"(d) : "r"(a), "r"(b)); return d; }
__device__ __forceinline__ uint32_t vshr(uint32_t a, int n) { uint32_t d; asm volatile("shr.u32 %0,%1,%2;" : "=r"(d) : "r"(a), "r"(n)); return d; }
__device__ __forceinline__ uint64_t gptr(uint32_t lo, uint32_t hi) { uint64_t d; asm("mov.b64 %0,{%1,%2};" : "=l"(d) : "r"(lo), "r"(hi)); return d; }
__device__ __forceinline__ void sfence(uint32_t zero) { asm volatile("{.reg .pred p; setp.ne.u32 p,%0,0; @p exit;}" ::"r"(zero) : "memory"); }
#define SF sfence(k.zero)
#define TS(i) do {} while (0)
#define TSN(i) do {} while (0)
#define TSET(it, slot) do {} while (0)
struct Gat { uint32_t x, y, z, w, e; };
template <int X>
__device__ __forceinline__ void gat_issue(Gat& g, const RecW& k, int s, uint32_t dep) {
    const uint32_t o = acc_slot(s + 3) + dep;
    asm volatile("{.reg .b128 t; ld.relaxed.gpu.global.b128 t,[%5+%7]; mov.b128 {%0,%1,%2,%3},t; ld.relaxed.gpu.global.u32 %4,[%6+%8];}"
                 : "=r"(g.x), "=r"(g.y), "=r"(g.z), "=r"(g.w), "=r"(g.e) : "l"(gptr(k.am + o, k.ah)), "l"(gptr(k.ae + o, k.ah)), "n"(X * 32768), "n"(X * 1024) : "memory");
}
template <int X>
__device__ __forceinline__ bool gat_store(const Gat& g, const RecW& k) {
    uint32_t c;
    asm volatile("prmt.b32 %0,%1,%2,0x7632;" : "=r"(c) : "r"(g.w), "r"(g.e));
    SF;
    asm volatile("{.reg .b32 t; prmt.b32 t,%4,%6,0x5410; stmatrix.sync.aligned.m8n8.x4.trans.shared.b16 [%0+%5],{%1,%2,%3,t};}" ::"r"(k.lpw), "r"(g.x), "r"(g.y), "r"(g.z), "r"(g.w), "n"(R_M + X * XS), "r"(g.e) : "memory");
    return __all_sync(0xffffffffu, c == 0x42004200u);
}
template <int X>
__device__ __forceinline__ void gat_finish(bool ok, const RecW& k, int s) {
    if (!ok) {
        int n = s;
        while (true) {
            Gat g;
            gat_issue<X>(g, k, n, 0);
            if (gat_store<X>(g, k)) break;
            n += 4;
            if (n > 8000000) __trap();
        }
    }
}
__device__ __forceinline__ uint4 lds128o(uint32_t a, int o) { uint4 v; asm volatile("{.reg .b32 t; add.u32 t,%4,%5; ld.shared.v4.u32 {%0,%1,%2,%3},[t];}" : "=r"(v.x), "=r"(v.y), "=r"(v.z), "=r"(v.w) : "r"(a), "r"(o) : "memory"); return v; }
__device__ __forceinline__ uint4 ldsm4o(uint32_t a, int o) { uint4 v; asm volatile("{.reg .b32 t; add.u32 t,%4,%5; ldmatrix.sync.aligned.m8n8.x4.shared.b16 {%0,%1,%2,%3},[t];}" : "=r"(v.x), "=r"(v.y), "=r"(v.z), "=r"(v.w) : "r"(a), "r"(o) : "memory"); return v; }
__device__ __forceinline__ uint4 ldsm4to(uint32_t a, int o) { uint4 v; asm volatile("{.reg .b32 t; add.u32 t,%4,%5; ldmatrix.sync.aligned.m8n8.x4.trans.shared.b16 {%0,%1,%2,%3},[t];}" : "=r"(v.x), "=r"(v.y), "=r"(v.z), "=r"(v.w) : "r"(a), "r"(o) : "memory"); return v; }
__device__ __forceinline__ uint2 lds64o(uint32_t a, int o) { uint2 v; asm volatile("{.reg .b32 t; add.u32 t,%2,%3; ld.shared.v2.u32 {%0,%1},[t];}" : "=r"(v.x), "=r"(v.y) : "r"(a), "r"(o) : "memory"); return v; }
__device__ __forceinline__ void sts128o(uint32_t a, int o, uint32_t x, uint32_t y, uint32_t z, uint32_t w) { asm volatile("{.reg .b32 t; add.u32 t,%0,%5; st.shared.v4.u32 [t],{%1,%2,%3,%4};}" ::"r"(a), "r"(x), "r"(y), "r"(z), "r"(w), "r"(o) : "memory"); }
__device__ __forceinline__ void sts64o(uint32_t a, int o, uint32_t x, uint32_t y) { asm volatile("{.reg .b32 t; add.u32 t,%0,%3; st.shared.v2.u32 [t],{%1,%2};}" ::"r"(a), "r"(x), "r"(y), "r"(o) : "memory"); }
__device__ __forceinline__ uint32_t vxor(uint32_t a, uint32_t b) { uint32_t d; asm volatile("xor.b32 %0,%1,%2;" : "=r"(d) : "r"(a), "r"(b)); return d; }
#define WLD(base, i) wt[i] = lds128o(k.lpw, (base) + (i) * 4096)
template <int PASS, int X, int NP>
__device__ __forceinline__ void rec_qkv(const RecW& k, int s, const uint32_t (*wq)[4], const uint32_t (*wk)[4], uint4* wt, Gat& g2, int s2, bool& ok2, uint4& mf) {
    constexpr bool BWD = PASS == 2, DIRECT = !(BKA && PASS == 1);
    float aq[4] = {0, 0, 0, 0}, ak[4] = {0, 0, 0, 0}, av[4] = {0, 0, 0, 0};
    constexpr int ma = R_M + X * XS;
    if (BWD && GSE == 4) { TS(1); mbar_wait(k.sb + R_BAR + RB_MB * 8, s & 1); mf = ldsm4o(k.lp, ma + 7 * 512); TS(2); }
    if (!BWD || GSE < 2) {
        if (BWD) { TS(1); gat_finish<1>(GSE ? ok2 : gat_store<1>(g2, k), k, s); }
        bar_sync(NB_MF + X, 256);
        mf = ldsm4o(k.lp, ma + (BWD ? 7 : 0) * 512);
        if (BWD) TS(2); else { TS(0); TSN(13); }
    }
#pragma unroll
    for (int ii = 0; ii < 8; ii++) {
        const int i = BWD ? 7 - ii : ii;
        const uint4 m = mf;
        if (ii < 7) mf = ldsm4o(k.lp, ma + (BWD ? i - 1 : i + 1) * 512);
        if (PASS == 1 && ii == G2I) gat_issue<1>(g2, k, s2, 0);
        if (PASS == 1 && GSE == 2 && ii == 7) { TS(1); gat_finish<1>(gat_store<1>(g2, k), k, s2); }
        if (PASS == 1 && GSE == 4 && ii == G2S) { gat_finish<1>(gat_store<1>(g2, k), k, s2); mbar_arrive1(k.sb + R_BAR + RB_MB * 8); }
        SF;
#pragma unroll
        for (int hh = 0; hh < 2; hh++) {
            const int h = BWD ? 1 - hh : hh, ks = 2 * i + h;
            const uint32_t b0 = h ? m.z : m.x, b1 = h ? m.w : m.y;
            mma16(aq, wq[ks][0], wq[ks][1], wq[ks][2], wq[ks][3], b0, b1);
            mma16(ak, wk[ks][0], wk[ks][1], wk[ks][2], wk[ks][3], b0, b1);
            SF;
            mma16(av, wt[ks].x, wt[ks].y, wt[ks].z, wt[ks].w, b0, b1);
            SF;
            if (!BWD && ks + NP < 16) WLD(R_WV, ks + NP < 16 ? ks + NP : 0);
            if (BWD && ks >= NT) WLD(R_WV, ks >= NT ? ks - NT : 0);
            SF;
        }
    }
    if (PASS == 1 && GSE == 1) { ok2 = gat_store<1>(g2, k); SF; }
    if (PASS == 1 && GSE == 3) { TS(1); gat_finish<1>(gat_store<1>(g2, k), k, s2); }
    if (PASS == 1 && (GSE == 2 || GSE == 3)) { bar_sync(NB_MF + 1, 256); mf = ldsm4o(k.lp, ma + XS + 7 * 512); TS(2); SF; }
    const uint32_t ra = vadd(k.lpw, k.dp + R_REM + X * XS + (s & 1) * 6144), va = ((vshr(k.lp, 7) & 1) * 48 ^ k.lp ^ (k.vo & 64)) + (k.vo & ~64u);
    const uint32_t x0 = movm(pack2(aq[0], aq[1])), x1 = movm(pack2(aq[2], aq[3])), x2 = movm(pack2(ak[0], ak[1])), x3 = movm(pack2(ak[2], ak[3]));
    SF;
    asm volatile("stmatrix.sync.aligned.m8n8.x2.shared.b16 [%0+%3],{%1,%2};" ::"r"(va), "r"(pack2(av[0], av[1])), "r"(pack2(av[2], av[3])), "n"(R_LOC + X * XS) : "memory");
    SF;
    if (STO && DIRECT) st_async4(ra, x0, x1, x2, x3, k.bar + X * 16);
    asm volatile("st.shared.v4.u32 [%0+%5],{%1,%2,%3,%4};" ::"r"(k.lpw), "r"(x0), "r"(x1), "r"(x2), "r"(x3), "n"(R_LOC + X * XS) : "memory");
    bar_arrive(NB_LOC + X, 320);
    if (!STO && DIRECT) st_async4(ra, x0, x1, x2, x3, k.bar + X * 16);
    SF;
    TS(BWD ? 4 : 3);
}
template <bool BWD, int X>
__device__ __forceinline__ void rec_out(const RecW& k, int s, uint4* wt, Gat& g, int s1) {
    if (BWD) { WLD(R_WO, 17 - NTO); WLD(R_WO, 16 - NTO); }
    TS(BWD ? 8 : 5);
    bar_sync(NB_O + X, 320);
    float r0[4] = {0, 0, 0, 0}, r1[4] = {0, 0, 0, 0};
    constexpr int oa = R_O + X * XS;
    uint4 bn = lds128o(k.lp, oa + (BWD ? 3 : 0) * 512);
    TS(BWD ? 9 : 6);
    uint2 il;
    uint64_t pm, pe;
#pragma unroll
    for (int ii = 0; ii < 4; ii++) {
        const int i = BWD ? 3 - ii : ii;
        const uint4 b = bn;
        if (ii < 3) bn = lds128o(k.lp, oa + (BWD ? i - 1 : i + 1) * 512);
        else { asm volatile("ld.shared.v2.u32 {%0,%1},[%2+%3];" : "=r"(il.x), "=r"(il.y) : "r"((vshr(k.ae, 2) & 3) * 8 + k.sb), "n"(R_IL + X * XS) : "memory"); pm = gptr(vadd(k.am, acc_slot(s)), k.ah); pe = gptr(vadd(k.ae, acc_slot(s)), k.ah); }
        SF;
        if (BWD && EARLY == ii + 1) { gat_issue<0>(g, k, s1 + 1, 0); SF; }
#pragma unroll
        for (int nn = 0; nn < 4; nn++) {
            const int n = BWD ? 3 - nn : nn, f = 4 * i + n, nx = BWD ? f - NTO + 2 : f + NTO - 2;
            mma16((n & 1) ? r1 : r0, wt[f].x, wt[f].y, wt[f].z, wt[f].w, n >> 1 ? b.z : b.x, n >> 1 ? b.w : b.y);
            SF;
            if (ii * 4 + nn >= 2 && nx >= 0 && nx < 16) WLD(R_WO, nx & 15);
            SF;
        }
    }
    const float i0 = __uint_as_float(il.x), i1 = __uint_as_float(il.y);
    asm volatile("red.relaxed.gpu.global.add.noftz.v4.bf16x2 [%0+%5],{%1,%2,%3,%4};" ::"l"(pm),
                 "r"(pack2(r0[0] * i0, r0[1] * i1)), "r"(pack2(r0[2] * i0, r0[3] * i1)), "r"(pack2(r1[0] * i0, r1[1] * i1)), "r"(pack2(r1[2] * i0, 1.f)), "n"(X * 32768) : "memory");
    asm volatile("red.relaxed.gpu.global.add.noftz.bf16x2 [%0+%2],%1;" ::"l"(pe), "r"(pack2(r1[3] * i1, 1.f)), "n"(X * 1024) : "memory");
    bar_arrive(NB_XG + X, 320);
    SF;
    TS(BWD ? 10 : 7);
}
__device__ __forceinline__ uint32_t pause(uint32_t v, int n) {
#pragma unroll
    for (int i = 0; i < n; i++) asm volatile("shfl.sync.bfly.b32 %0,%0,0,0x1f,0xffffffff;" : "+r"(v));
    return v;
}
template <bool DUAL, int X>
__device__ __forceinline__ void rec_step(const RecW& k, int s, int s2, const uint32_t (*wq)[4], const uint32_t (*wk)[4], uint4* wt) {
    constexpr int NP = NPD;
    uint4 wo[16];
    Gat g;
    bool ok2;
    uint4 mf;
    rec_qkv<DUAL ? 1 : 0, X, NP>(k, s, wq, wk, wt, g, s2, ok2, mf);
    if (DUAL) rec_qkv<2, 1, NP>(k, s2, wq, wk, wt, g, s2, ok2, mf);
    uint32_t wa = k.lpw;
#pragma unroll
    for (int i = 0; i < NTO; i++) {
        wo[i] = lds128o(wa, R_WO + i * 4096);
        if (i % PACE == PACE - 1) wa = k.lpw + (wo[i].x & k.zero);
        SF;
    }
    rec_out<false, X>(k, s, wo, g, s);
    if (DUAL) { rec_out<true, 1>(k, s2, wo, g, s); if (!EARLY) gat_issue<0>(g, k, s + 1, 0); SF; }
#pragma unroll
    for (int i = 0; i < NP; i++) { WLD(R_WV, i); SF; }
    if (!DUAL) gat_issue<X>(g, k, s + 1, pause(wt[NP - 1].x & k.zero, DP1));
    TS(12);
    gat_finish<X>(gat_store<X>(g, k), k, s + 1);
    TS(11);
}

__device__ __forceinline__ void rec_fetch(const CUtensorMap* tm, uint32_t dst, int x, int y, int nx, uint32_t bar) {
#pragma unroll 1
    for (int j = 0; j < 8; j++) tma2d(dst + j * 8192, tm, x + (j / (8 / nx)) * 64, y + (j % (8 / nx)) * 64, bar);
}
__device__ __forceinline__ void rec_weights(const Params& p, uint32_t sb, int head, uint32_t rank, int w) {
    const int lane = threadIdx.x & 31, t = w & 3, WG = w >> 2;
    uint32_t wq[16][4], wk[16][4];
    const uint32_t rowo = (((lane >> 4) << 3) + (lane & 7)) * 128;
    const uint32_t woff = sb + WG * 32768 + rowo + (((2 * t + ((lane >> 3) & 1)) ^ (lane & 7)) << 4);
    const uint32_t qoff = sb + ((w & 1) ? R_STK : R_STQ) + WG * 32768 + rowo + (((2 * (t & 2) + ((lane >> 3) & 1)) ^ (lane & 7)) << 4);
    const uint32_t lw = sb + (lane ^ (lane >> 3)) * 16;
    PROF(threadIdx.x == 0, 3501);
    PROF(threadIdx.x == 0, 3502);
    mbar_wait(sb + R_BAR + RB_INIT * 8, 0);
    PROF(threadIdx.x == 0, 3503);
#pragma unroll
    for (int ks = 0; ks < 16; ks++) {
        uint4 a = ldsm4t(qoff + ks * 2048), b = ldsm4t((qoff ^ 32) + ks * 2048);
        wq[ks][0] = a.x; wq[ks][1] = a.y; wq[ks][2] = a.z; wq[ks][3] = a.w;
        wk[ks][0] = b.x; wk[ks][1] = b.y; wk[ks][2] = b.z; wk[ks][3] = b.w;
    }
    bar_sync(NB_W, 256);
#pragma unroll 4
    for (int ks = 0; ks < 16; ks++) { const uint4 a = ldsm4t(woff + R_STV + ks * 2048); sts128(lw + w * 512 + R_WV + ks * 4096, a.x, a.y, a.z, a.w); }
    bar_sync(NB_W, 256);
    if (threadIdx.x == 0) {
        mbar_expect(sb + R_BAR + RB_INIT * 8, 65536);
        rec_fetch(&p.tm[4], sb + R_STV, rank * 256, head * 128, 4, sb + R_BAR + RB_INIT * 8);
    }
    __syncwarp();
    mbar_wait(sb + R_BAR + RB_INIT * 8, 1);
#pragma unroll 4
    for (int f = 0; f < 16; f++) {
        const uint4 a = ldsm4t(sb + R_STV + (w >> 1) * 16384 + (f >> 1) * 2048 + rowo + ((((w & 1) * 4 + (f & 1) * 2 + ((lane >> 3) & 1)) ^ (lane & 7)) << 4));
        sts128(lw + w * 512 + R_WO + f * 4096, a.x, a.y, a.z, a.w);
    }
    PROF(threadIdx.x == 0, 3504);
    __syncthreads();
    cluster_sync();
    PROF(threadIdx.x == 0, 3505);
    RecW k;
    k.am = __shfl_sync(0xffffffffu, (uint32_t)(size_t)acc_base() + acc_main(rank, threadIdx.x), lane);
    k.ae = __shfl_sync(0xffffffffu, (uint32_t)(size_t)acc_base() + acc_extra(rank, threadIdx.x), lane);
    k.ah = (uint32_t)((size_t)acc_base() >> 32);
    k.sb = sb; k.zero = p.zero;

    k.dp = mapa(sb, rank ^ 1) - sb;
    k.lp = __shfl_sync(0xffffffffu, lw, lane);
    k.lpw = __shfl_sync(0xffffffffu, lw + w * 512, lane);
    k.vo = 4096 + w * 256 + (w & 1) * 64;
    k.bar = sb + k.dp + R_BAR + (RB_QK + WG) * 8;
    int it = 0;
    uint4 wt[16];
#pragma unroll
    for (int i = 0; i < NPD; i++) WLD(R_WV, i);
    gat_finish<0>(false, k, 0);
#pragma unroll 1
    for (; it < min(p.b1, p.e0); it++) { TSET(it, w == GPW ? 0 : 3); rec_step<false, 0>(k, it, it, wq, wk, wt); }
#pragma unroll 1
    for (; it < p.e0; it++) { TSET(it, w == GPW ? 0 : 3); rec_step<true, 0>(k, it, it - p.b1, wq, wk, wt); }
    if (it < p.nit) gat_finish<1>(false, k, it - p.b1);
#pragma unroll 1
    for (; it < p.nit; it++) { TSET(it, w == GPW ? 0 : 3); rec_step<false, 1>(k, it - p.b1, it - p.b1, wq, wk, wt); }
}

__device__ __forceinline__ void mma16_top(float* c, uint32_t a0, uint32_t a2, uint32_t b0, uint32_t b1) {
    asm volatile("{.reg .b32 j; mma.sync.aligned.m16n8k16.row.col.f32.bf16.bf16.f32 {%0,%1,%2,%3},{%4,j,%5,j},{%6,%7},{%0,%1,%2,%3};}"
                 : "+f"(c[0]), "+f"(c[1]), "+f"(c[2]), "+f"(c[3]) : "r"(a0), "r"(a2), "r"(b0), "r"(b1));
}
__device__ __forceinline__ void rec_load_tile(uint32_t sb, int X, int j, int s, int head, uint32_t rank) {
    const uint32_t bar = sb + R_BAR + (RB_T + X * 2 + j) * 8;
    mbar_expect1(bar, j ? 4096 : 16384);
    bulk_g2s1(sb + R_T + X * XS + j * 16384, g_qkv[X] + (size_t)(s * 32 + head) * 1536 + (j ? rank * 256 : 512), j ? 4096 : 16384, bar, POL_LAST);
}
__device__ __forceinline__ bool chunk_ready(int X, int j, int s) {
    unsigned v;
    asm volatile("ld.relaxed.gpu.global.u32 %0,[%1];" : "=r"(v) : "l"(cnt_ptr(C_QKV0 + X, (s >> 2) + j * 16)) : "memory");
    return __all_sync(0xffffffffu, v >= (256 >> j));
}
__device__ __forceinline__ uint4 hadd4(uint4 a, uint4 b) { return make_uint4(hadd2(a.x, b.x), hadd2(a.y, b.y), hadd2(a.z, b.z), hadd2(a.w, b.w)); }
struct RecH { uint32_t lw, lm, lq, lv, lu, sa, sp, xb, sb, zero, ts, tn; };
__device__ __forceinline__ void rec_publish(int X, int s) {
    asm volatile("{.reg .pred p; cp.async.bulk.wait_group 0; elect.sync _|p,0xffffffff; @p red.relaxed.gpu.global.add.u32 [%0],4;}" ::"l"(cnt_ptr(C_O0 + X, s >> 2)) : "memory");
}
__device__ __forceinline__ void rec_mattn(const RecH& k, uint32_t dp, int X, int j, int s, bool qk, uint4 (*V)[4], uint4* vm, uint4* kmm) {
    const uint32_t sb = k.sb, to = R_T, lo = R_LOC, ro = R_REM + (s & 1) * 6144;
    const uint32_t bar = sb + R_BAR + (X * 2 + j) * 8;
    uint4 K[2][4];
    mbar_wait(sb + R_BAR + (RB_T + X * 2) * 8, s & 1);
    TS(1);
#pragma unroll
    for (int i = 0; i < 8; i++) K[i >> 2][i & 3] = ldsm4o(k.lm, (to + (i >> 2) * 1024 + ((i >> 1) & 1) * 4096 + (i & 1) * 512));
    asm volatile("cp.async.bulk.wait_group 0;" ::: "memory");
    bar_sync(NB_LOC + X, 320);
    fence_async_smem();
    if (qk) asm volatile("{.reg .pred p; elect.sync _|p,0xffffffff; @p cp.async.bulk.shared::cluster.shared::cta.mbarrier::complete_tx::bytes [%0],[%1],2048,[%2];}"
                         ::"r"(k.xb + dp + ro + j * 1024), "r"(k.xb + lo + j * 1024), "r"(bar + dp + RB_QK * 8) : "memory");
    asm volatile("{.reg .pred p; elect.sync _|p,0xffffffff; @p cp.async.bulk.shared::cluster.shared::cta.mbarrier::complete_tx::bytes [%0],[%1],1024,[%2];}"
                 ::"r"(k.xb + dp + ro + 4096), "r"(k.xb + lo + 4096), "r"(bar + dp + RB_V * 8) : "memory");
    uint4 u[4];
#pragma unroll
    for (int i = 0; i < 4; i++) u[i] = ldsm4o(k.lm, (lo + i * 512));
    TS(2);
    mbar_wait(bar + RB_QK * 8, s & 1);
    TS(3);
    float S[5][4];
#pragma unroll
    for (int i = 0; i < 5; i++) S[i][0] = S[i][1] = S[i][2] = S[i][3] = 0;
    {
        uint4 r[4];
#pragma unroll
        for (int i = 0; i < 4; i++) r[i] = ldsm4o(k.lm, (ro + i * 512));
        SF;
#pragma unroll
        for (int e = 0; e < 2; e++) {
            uint4& km = u[2 * e + 1];
            const uint32_t q0 = hadd2(u[2 * e].x, r[2 * e].x), q1 = hadd2(u[2 * e].y, r[2 * e].y);
            mma16_top(S[0], q0, q1, K[e][0].x, K[e][0].y);
            km.x = hadd2(km.x, r[2 * e + 1].x); km.y = hadd2(km.y, r[2 * e + 1].y);
            SF;
            mma16_top(S[1], q0, q1, K[e][1].x, K[e][1].y);
            const uint32_t q2 = hadd2(u[2 * e].z, r[2 * e].z), q3 = hadd2(u[2 * e].w, r[2 * e].w);
            SF;
            mma16_top(S[2], q0, q1, K[e][2].x, K[e][2].y);
            km.z = hadd2(km.z, r[2 * e + 1].z); km.w = hadd2(km.w, r[2 * e + 1].w);
            SF;
            mma16_top(S[3], q0, q1, K[e][3].x, K[e][3].y);
            mma16_top(S[4], q0, q1, km.x, km.y);
            SF;
#pragma unroll
            for (int i = 0; i < 4; i++) {
                mma16_top(S[i], q2, q3, K[e][i].z, K[e][i].w); SF;
            }
            mma16_top(S[4], q2, q3, km.z, km.w);
            SF;
        }
    }
#define VLD(a, b) _Pragma("unroll") for (int i = (a); i < (b); i++) V[i >> 2][i & 3] = ldsm4to((i & 1) ? lv2 : k.lv, (to + 8192 + (i >> 2) * 4096 + ((i >> 1) & 1) * 1024))
    const uint32_t lv2 = vxor(k.lv, 0x20), lh = k.lw - (vshr(k.lw - k.xb, 1) & 0xf8);
    VLD(0, VE);
    SF;
    const uint32_t sxr = k.sa, sxw = k.sp;
    sts128o(k.lw, sxw, __float_as_uint(S[0][0]), __float_as_uint(S[0][1]), __float_as_uint(S[1][0]), __float_as_uint(S[1][1]));
    SF;
    sts128o(k.lw, (sxw + 512), __float_as_uint(S[2][0]), __float_as_uint(S[2][1]), __float_as_uint(S[3][0]), __float_as_uint(S[3][1]));
    SF;
    sts64o(lh, (sxw + 1024), __float_as_uint(S[4][0]), __float_as_uint(S[4][1]));
    TS(4);
    bar_sync(NB_PAIR + X, 64);
    {
        const uint4 a = lds128o(k.lw, sxr), b = lds128o(k.lw, (sxr + 512));
        const uint2 c = lds64o(lh, (sxr + 1024));
        SF;
        VLD(VE, VF);
        SF;
        S[0][0] += __uint_as_float(a.x); S[0][1] += __uint_as_float(a.y); S[1][0] += __uint_as_float(a.z); S[1][1] += __uint_as_float(a.w);
        S[2][0] += __uint_as_float(b.x); S[2][1] += __uint_as_float(b.y); S[3][0] += __uint_as_float(b.z); S[3][1] += __uint_as_float(b.w);
        S[4][0] += __uint_as_float(c.x); S[4][1] += __uint_as_float(c.y);
    }
    float m = fmaxf(fmaxf(fmaxf(S[0][0], S[0][1]), fmaxf(S[1][0], S[1][1])), fmaxf(fmaxf(S[2][0], S[2][1]), fmaxf(S[3][0], S[3][1])));
    m = fmaxf(m, fmaxf(S[4][0], S[4][1]));
    m = fmaxf(m, __shfl_xor_sync(0xffffffffu, m, 1));
    const float m2 = __shfl_xor_sync(0xffffffffu, m, 2);
    SF;
    VLD(VF, 8);
    uint32_t ok;
    asm volatile("{.reg .pred p; mbarrier.test_wait.parity.shared::cta.b64 p,[%1],%2; selp.u32 %0,1,0,p;}" : "=r"(ok) : "r"(bar + RB_V * 8), "r"(s & 1) : "memory");
    uint4 vr0 = ldsm4o(k.lu, (ro + 4096)), vr1 = ldsm4o(k.lu, (ro + 4608));
    vm[0] = ldsm4o(k.lu, (lo + 4096)); vm[1] = ldsm4o(k.lu, (lo + 4608));
    SF;
    TS(5);
    m = fmaxf(m, m2) * -SC_LOG2E;
    uint32_t P[5];
#pragma unroll
    for (int i = 0; i < 5; i++) P[i] = pack2(ex2(fmaf(S[i][0], SC_LOG2E, m)), ex2(fmaf(S[i][1], SC_LOG2E, m)));
    float o[4][4], l[4] = {0, 0, 0, 0};
    const uint32_t ONE = 0x3f803f80u;
    mma16_top(l, ONE, ONE, P[0], P[1]);
#pragma unroll
    for (int t = 0; t < 4; t++) { o[t][0] = o[t][1] = o[t][2] = o[t][3] = 0; mma16(o[t], V[0][t].x, V[0][t].y, V[0][t].z, V[0][t].w, P[0], P[1]); }
    mma16_top(l, ONE, ONE, P[2], P[3]);
#pragma unroll
    for (int t = 0; t < 4; t++) mma16(o[t], V[1][t].x, V[1][t].y, V[1][t].z, V[1][t].w, P[2], P[3]);
    if (!__all_sync(0xffffffffu, ok)) {
        mbar_wait(bar + RB_V * 8, s & 1);
        vr0 = ldsm4o(k.lu, (ro + 4096)); vr1 = ldsm4o(k.lu, (ro + 4608));
    }
    TS(6);
    vm[0] = hadd4(vm[0], vr0); vm[1] = hadd4(vm[1], vr1);
    mma8(l, ONE, ONE, P[4]);
    mma8(o[0], vm[0].x, vm[0].y, P[4]); mma8(o[1], vm[0].z, vm[0].w, P[4]); mma8(o[2], vm[1].x, vm[1].y, P[4]); mma8(o[3], vm[1].z, vm[1].w, P[4]);
    asm volatile("{.reg .pred p; .reg .b32 t; setp.lt.u32 p,%0,%3; add.u32 t,%0,%4; @p st.shared.v2.f32 [t],{%1,%2};}" ::"r"(lh), "f"(rcp(l[0])), "f"(rcp(l[1])), "r"(k.xb + 32), "r"(R_IL) : "memory");
#pragma unroll
    for (int t = 0; t < 4; t += 2)
        asm volatile("{.reg .b32 t; add.u32 t,%0,%5; stmatrix.sync.aligned.m8n8.x4.trans.shared.b16 [t],{%1,%2,%3,%4};}" ::"r"(k.lm),
                     "r"(pack2(o[t][0], o[t][1])), "r"(pack2(o[t][2], o[t][3])), "r"(pack2(o[t + 1][0], o[t + 1][1])), "r"(pack2(o[t + 1][2], o[t + 1][3])), "r"(R_O - j * 1024 + t * 256) : "memory");
    bar_arrive(NB_O + X, 320);
    PROF(k.lw == k.xb, X * 64 + s);
    TS(7);
    kmm[0] = u[1]; kmm[1] = u[3];
    mbar_expect1(bar + RB_QK * 8, 2048); mbar_expect1(bar + RB_V * 8, 1024);
}
template <int MT>
__device__ __forceinline__ void rec_xattn(const RecH& k, int X, int j, int s, int head, bool early, const uint4 (*V)[4], const uint4* vmm, const uint4* kmm) {
    constexpr int NTL = 3 + 2 * MT;
    const uint32_t sb = k.sb, to = R_T;
    const uint32_t sxw = k.sa, sxr = k.sp;
    const uint32_t lq2 = vxor(k.lq, 0x20);
    float S[NTL][4];
#pragma unroll
    for (int i = 0; i < NTL; i++) S[i][0] = S[i][1] = S[i][2] = S[i][3] = 0;
    {
        uint4 q[2][2], kk[2][NTL];
#define XQ(e) q[e][0] = ldsm4o(k.lq, (to + 16384 + (e) * 1024)); q[e][1] = ldsm4o(lq2, (to + 16384 + (e) * 1024))
#define XK(e, i) kk[e][i] = ldsm4o(k.lm, (to + (e) * 1024 + (((i) - 1) >> 1) * 4096 + (((i) - 1) & 1) * 512))
        kk[0][0] = kmm[0]; kk[1][0] = kmm[1];
        if (XPRE == 0) { bar_sync(NB_XG + X, 320); TS(8); }
        XQ(0);
#pragma unroll
        for (int i = 1; i < NTL; i++) XK(0, i);
        if (XPRE == 1) { bar_sync(NB_XG + X, 320); TS(8); }
        SF;
#pragma unroll
        for (int i = 0; i < NTL; i++) { mma16(S[i], q[0][0].x, q[0][0].y, q[0][0].z, q[0][0].w, kk[0][i].x, kk[0][i].y); SF; }
        q[1][0] = ldsm4o(k.lq, (to + 16384 + 1024));
#pragma unroll
        for (int i = 0; i < NTL; i++) { mma16(S[i], q[0][1].x, q[0][1].y, q[0][1].z, q[0][1].w, kk[0][i].z, kk[0][i].w); SF; if (i + 1 < NTL) XK(1, i + 1); SF; }
        q[1][1] = ldsm4o(lq2, (to + 16384 + 1024));
        if (XPRE == 2) { bar_sync(NB_XG + X, 320); TS(8); }
        SF;
#pragma unroll
        for (int i = 0; i < NTL; i++) { mma16(S[i], q[1][0].x, q[1][0].y, q[1][0].z, q[1][0].w, kk[1][i].x, kk[1][i].y); SF; }
#pragma unroll
        for (int i = 0; i < NTL; i++) { mma16(S[i], q[1][1].x, q[1][1].y, q[1][1].z, q[1][1].w, kk[1][i].z, kk[1][i].w); SF; }
    }
#pragma unroll
    for (int i = 0; i < NTL; i++) sts128o(k.lw, (sxw + i * 512), __float_as_uint(S[i][0]), __float_as_uint(S[i][1]), __float_as_uint(S[i][2]), __float_as_uint(S[i][3]));
    SF;
    if (XPRE == 3) bar_sync(NB_XG + X, 320); else bar_sync(NB_PAIR + 2 + X, 64);
    TS(9);
    if (early) rec_load_tile(sb, X, j, s + 1, head, MT);
#pragma unroll
    for (int i = 0; i < NTL; i++) {
        const uint4 r = lds128o(k.lw, (sxr + i * 512));
        S[i][0] += __uint_as_float(r.x); S[i][1] += __uint_as_float(r.y); S[i][2] += __uint_as_float(r.z); S[i][3] += __uint_as_float(r.w);
    }
    const int g = vshr(k.lw - k.xb, 6) & 7, c = (vshr(k.lw, 4) ^ (g >> 1)) & 3;
    const float NEG = -__int_as_float(0x7f800000);
    if (2 * c > g) { S[NTL - 2][0] = NEG; S[NTL - 1][2] = NEG; }
    if (2 * c + 1 > g) { S[NTL - 2][1] = NEG; S[NTL - 1][3] = NEG; }
    float m0 = fmaxf(S[0][0], S[0][1]), m1 = fmaxf(S[0][2], S[0][3]);
#pragma unroll
    for (int i = 1; i < NTL; i++) { if (i < NTL - 1) m0 = fmaxf(m0, fmaxf(S[i][0], S[i][1])); m1 = fmaxf(m1, fmaxf(S[i][2], S[i][3])); }
    m0 = fmaxf(m0, __shfl_xor_sync(0xffffffffu, m0, 1)); m1 = fmaxf(m1, __shfl_xor_sync(0xffffffffu, m1, 1));
    m0 = fmaxf(m0, __shfl_xor_sync(0xffffffffu, m0, 2)); m1 = fmaxf(m1, __shfl_xor_sync(0xffffffffu, m1, 2));
    m0 *= -SC_LOG2E; m1 *= -SC_LOG2E;
    uint32_t P[NTL][2];
#pragma unroll
    for (int i = 0; i < NTL; i++) {
        P[i][0] = i < NTL - 1 ? pack2(ex2(fmaf(S[i][0], SC_LOG2E, m0)), ex2(fmaf(S[i][1], SC_LOG2E, m0))) : 0u;
        P[i][1] = pack2(ex2(fmaf(S[i][2], SC_LOG2E, m1)), ex2(fmaf(S[i][3], SC_LOG2E, m1)));
    }
    float l[4] = {0, 0, 0, 0};
#pragma unroll
    for (int i = 0; i < NTL; i++) mma8(l, P[i][0], P[i][1], 0x3f803f80u);
    const float l0 = rcp(l[0]), l1 = rcp(l[2]);

#pragma unroll
    for (int e = 0; e < 2; e++) {
        const uint4 vm = vmm[e];
        uint32_t u[2][4];
#pragma unroll
        for (int n = 0; n < 4; n++) {
            float a[4] = {0, 0, 0, 0};
#pragma unroll
            for (int m = 0; m <= MT; m++) {
                const uint4 v = V[m][e * 2 + (n >> 1)];
                mma8(a, P[1 + 2 * m][0], P[1 + 2 * m][1], (n & 1) ? v.y : v.x); mma8(a, P[2 + 2 * m][0], P[2 + 2 * m][1], (n & 1) ? v.w : v.z);
            }
            mma8(a, P[0][0], P[0][1], n == 0 ? vm.x : n == 1 ? vm.y : n == 2 ? vm.z : vm.w);
            u[0][n] = pack2(a[0] * l0, a[1] * l0); u[1][n] = pack2(a[2] * l1, a[3] * l1);
        }
        sts128o(k.lw, sxr + e * 512, u[0][0], u[0][1], u[0][2], u[0][3]); sts128o(k.lw, sxr + e * 512 + 1024, u[1][0], u[1][1], u[1][2], u[1][3]);
    }
    TS(10);
}
__device__ __forceinline__ void rec_attn(const Params& p, uint32_t sb, int X, int j, int head, uint32_t rank) {
    const int lane = threadIdx.x & 31;
    RecH k;
    k.xb = sb + X * XS + j * 1024;
    const uint32_t x2 = k.xb + j * 1024;
    k.lw = __shfl_sync(0xffffffffu, x2 + (lane ^ (lane >> 3)) * 16, lane);
    k.lm = __shfl_sync(0xffffffffu, x2 + ((lane & 7) * 4 + ((lane >> 3) ^ ((lane & 7) >> 1))) * 16, lane);
    k.lq = __shfl_sync(0xffffffffu, x2 + ((lane >> 3) & 1) * 512 + ((lane & 7) * 4 + ((lane >> 4) ^ ((lane & 7) >> 1))) * 16, lane);
    k.lv = __shfl_sync(0xffffffffu, x2 + (lane >> 4) * 512 + ((lane & 7) * 4 + (((lane >> 3) & 1) ^ ((lane & 7) >> 1))) * 16, lane);
    k.lu = __shfl_sync(0xffffffffu, k.xb + ((lane & 6) * 4 + (((lane >> 3) * 2 + (lane & 1)) ^ (lane & 6))) * 16, lane);
    k.sa = __shfl_sync(0xffffffffu, R_SX + j * 512, 0); k.sp = __shfl_sync(0xffffffffu, R_SX + 2560 - j * 4608, 0);
    k.sb = sb; k.zero = p.zero;
    const uint32_t dp = mapa(sb, rank ^ 1) - sb;
    char* zp = acc_base() + (j ? X * 32768 + acc_main(rank, head * 8) : X * 1024 + acc_extra(rank, head * 8));
    mbar_expect1(sb + R_BAR + (RB_QK + X * 2 + j) * 8, 2048); mbar_expect1(sb + R_BAR + (RB_V + X * 2 + j) * 8, 1024);
    bool early = false;
#pragma unroll 1
    for (int s = 0; s < 64; s++) {
        TSET(X ? s + p.b1 : s, j == GPJ ? 1 + X : 3);
        TS(0);
        if (!early) {
            if (!j) wait_cnt_warp(cnt_ptr(C_QKV0 + X, s >> 2), 256);
            early = !j || chunk_ready(X, 1, s);
            if (early) rec_load_tile(sb, X, j, s, head, rank);
        }
        if (PFD && s < 63 && early && (PFB || !X) && ((s & 3) != 3 || chunk_ready(X, j, s + 1)))
            asm volatile("{.reg .pred p; elect.sync _|p,0xffffffff; @p cp.async.bulk.prefetch.L2.global.L2::cache_hint [%0],%1,%2;}"
                         ::"l"(g_qkv[X] + (size_t)((s + 1) * 32 + head) * 1536 + (j ? rank * 256 : 512 + rank * 512)), "r"(j ? 4096 : 8192), "l"(POL_LAST) : "memory");
        uint4 V[2][4], vm[2], km[2];
        rec_mattn(k, dp, X, j, s, BKA && !X && s >= p.b1, V, vm, km);
        if (!early) { wait_cnt_warp(cnt_ptr(C_QKV0 + X, (s >> 2) + 16), 128); rec_load_tile(sb, X, 1, s, head, rank); }
        early = s < 63 && ((s & 3) != 3 || chunk_ready(X, j, s + 1));
        mbar_wait(sb + R_BAR + (RB_T + X * 2 + 1) * 8, s & 1);
        if (rank) rec_xattn<1>(k, X, j, s, head, early, V, vm, km); else rec_xattn<0>(k, X, j, s, head, early, V, vm, km);
        fence_async_smem();
        __syncwarp();
        asm volatile("{.reg .pred p; elect.sync _|p,0xffffffff;\n"
                     "@p cp.async.bulk.global.shared::cta.bulk_group.L2::cache_hint [%0],[%1],2048,%2;\n"
                     "@p cp.async.bulk.global.shared::cta.bulk_group [%3],[%4],%5;\n"
                     "cp.async.bulk.commit_group;}"
                     ::"l"(g_o[X] + ((s >> 2) * 64 + head * 2 + j) * 1024 + ((s & 3) * 2 + rank) * 128), "r"(x2 + k.sp),
                       "l"((X && s < 40) ? POL_LATE : POL_SOON), "l"(zp + acc_slot(s + 2)), "r"(sb + R_Z), "r"(j ? 128 : 32) : "memory");
        if ((s & 3) == 3) {
            if (!early && s < 63 && chunk_ready(X, j, s + 1)) { rec_load_tile(sb, X, j, s + 1, head, rank); early = true; }
            rec_publish(X, s);
            PROF(lane == 0 && j, 3900 + X * 16 + (s >> 2));
        }
    }
}

__device__ __forceinline__ void rec_init(const Params& p, uint32_t sb, int head, uint32_t rank) {
    const uint32_t b = sb + R_BAR;
    const int i = threadIdx.x - 320;
    if (i >= 0 && i < RB_N) {
        mbar_init(b + i * 8, i == RB_MB ? 8 : 1);
        asm volatile("fence.mbarrier_init.release.cluster;" ::: "memory");
    }
    if (i == 0) mbar_expect(b + RB_INIT * 8, 196608);
    if (i >= 0 && i < 32) sts32(sb + R_Z + i * 4, 0);
}

#define NSTGN 8
constexpr int NSTG = NSTGN, STG_B = 24576;
#define LAGH 3
constexpr int NSB = 8;
constexpr int B_OUT = NSTG * STG_B  , B_UT = B_OUT, B_YT = B_UT + 16384, B_SP = B_YT  ,
              B_ST = 229376  , B_BAR = 231936;
static_assert(B_OUT + NSB * 4096 <= B_ST && B_ST + 2048 <= B_BAR && B_YT + 10240 <= B_ST, "smem map");
enum { BB_FULL = 0, BB_EMPTY = 8, BB_SF = 16  , BB_GO = 18, BB_DONE = 20  , BB_IDLE = 22  , BB_N = 30 };
enum { NB_REL = 2  , NB_C = 11, NB_WG = 12  , NB_PH = 14 };

__device__ __forceinline__ void bulk_init(uint32_t sb) {
    const int i = threadIdx.x - 320;
    if (i >= 0 && i < BB_N) {
        mbar_init(sb + B_BAR + i * 8, (i >= BB_EMPTY && i < BB_EMPTY + NSTG) ? 4 : i >= BB_DONE ? 4 : 1);
        asm volatile("fence.mbarrier_init.release.cluster;" ::: "memory");
    }
}

struct Task { int type, layer, ch, a, b, c, blk; bool pair, dry; };
__device__ __forceinline__ Task task_of(uint32_t tk, uint32_t rank) {
    Task t;
    t.type = tk & 7; t.layer = (tk >> 3) & 1; t.a = (tk >> 8) & 255; t.b = (tk >> 16) & 255; t.c = (tk >> 24) & 127; t.dry = tk >> 31;
    t.pair = t.type <= T_OP && (t.c & 64);
    t.ch = ((tk >> 4) & 15) + (t.pair ? rank : 0);
    t.blk = t.type == T_QKV ? t.a + (t.pair ? 0 : rank) : 192 + (t.pair ? (t.c >> 2) & 4 : rank * 4);
    return t;
}
__device__ __forceinline__ int qkv_blk(const Task& t, int u) {
    const int v = t.blk + (t.pair ? 1 : 2 * t.c) * u;
    return 2 * (v < 64 ? v + 32 : v - 64);
}
__device__ __forceinline__ void bulk_producer(const Params& p, uint32_t sb, int cl, uint32_t rank) {
    int st = 0; uint32_t ph = 1;
    const int tag = __shfl_sync(0xffffffffu, lds32(sb + S_TAG), 0);
    bool gated = false;
#define ACQ(bytes) do { mbar_wait(sb + B_BAR + (BB_EMPTY + st) * 8, ph); mbar_expect1(sb + B_BAR + (BB_FULL + st) * 8, bytes); } while (0)
#define NEXT do { if (++st == NSTG) { st = 0; ph ^= 1; } } while (0)
#pragma unroll 1
    for (int ti = 0; ti < MAXT; ti++) {
        const Task t = task_of(p.task[cl][ti], rank);
        const int layer = t.layer, ch = t.ch;
        if (t.type == T_END) break;
        if (t.type <= T_OP) {
            const bool qkv = t.type == T_QKV;
            const int nh = (qkv ? 8 : 2) * t.b;
            const unsigned* dep = cnt_ptr(qkv ? (layer ? C_CV : C_ST) : C_O0 + layer, ch);
            const unsigned need = qkv ? (layer ? 32 : ch < 2 ? 0 : 16) : 512;
            const uint16_t mb = t.pair ? 3 : 1 << rank, ma = t.pair ? 1 << rank : 3;
            int pend = qkv ? 2 : 0;
            bool wait = false;
            if (!t.dry) {
                unsigned v = 0;
                if (gated) asm volatile("ld.relaxed.gpu.global.u32 %0,[%1];" : "=r"(v) : "l"(dep) : "memory");
                wait = !gated || !__all_sync(0xffffffffu, v >= need);
                if (wait) pend = min(nh, gated ? NSTG : 4);
            }
#define DEPW if (wait) { if (!gated) { wait_cnt_warp(g_gate, lds32(sb + S_GATE)); gated = true; } if (need) wait_cnt_warp(dep, need); }
            if (qkv) {
#pragma unroll 1
                while (st) { ACQ(0); NEXT; }
#pragma unroll 1
                for (int h = 0; h < nh; h++) {
                    const int blk = qkv_blk(t, h >> 3);
                    ACQ(16384 + (h < 2 ? (layer ? 8192 : 1024) : 0));
                    if (!t.pair || !rank) tma3d_mc(sb + st * STG_B, &p.t3[1][blk >> 6], (h & 7) * 64, blk & 63, sb + B_BAR + (BB_FULL + st) * 8, mb);
                    if (!t.pair || rank) tma3d_mc(sb + st * STG_B + 8192, &p.t3[1][blk >> 6], (h & 7) * 64 + 32, blk & 63, sb + B_BAR + (BB_FULL + st) * 8, mb);
                    NEXT;
                    if (h == pend - 1) {
                        DEPW;
                        const float2* sp = g_st[layer] + ch * 2048 + (need ? 0 : tag * 256);
                        bulk_g2s1(sb + 16384, sp, layer ? 8192 : 1024, sb + B_BAR + BB_FULL * 8, POL_N);
                        bulk_g2s1(sb + STG_B + 16384, sp + (layer ? 1024 : 128), layer ? 8192 : 1024, sb + B_BAR + (BB_FULL + 1) * 8, POL_N);
                    }
                }
                continue;
            }
            if (PFC && !layer && (t.c & 15) < 8) {
                const int q = (t.c & 15) * 2 + rank;
                asm volatile("{.reg .pred p; elect.sync _|p,0xffffffff; @p cp.async.bulk.prefetch.L2.global [%0],8192; @p cp.async.bulk.prefetch.L2.global [%1],%2;}"
                             ::"l"(g_xA[0] + (ch * 16 + q) * 512), "l"(g_P + q * 16 * 32 * PW), "r"((2 + (ch & 1)) * 32 * PW * 4) : "memory");
            }
            const CUtensorMap *tb = &p.t3[t.pair][3], *ta = &p.ta[t.pair];
            const uint32_t db = sb + 8192 + (t.pair ? rank * 8192 : 0), da = sb + (t.pair ? 0 : rank * 4096);
            const int zb = (t.blk & 63) + (t.pair ? rank * 2 : 0), ya = 4096 + ((layer * 16 + ch) * 64 + t.a) * 16 + (t.pair ? 0 : rank * 8), row = t.a * 64;
            int h = 0;
            const int s0 = st;
#pragma unroll 1
            for (; h < pend; h++) { ACQ(STG_B); tma3d_mc(db + st * STG_B, tb, row + h * 32, zb, sb + B_BAR + (BB_FULL + st) * 8, mb); NEXT; }
            DEPW;
#pragma unroll 1
            for (int k = 0; k < pend; k++) {
                const int s2 = (s0 + k) & (NSTG - 1);
                tma2d_mc(da + s2 * STG_B, ta, (k & 1) * 256, ya + (k >> 1) * 16, sb + B_BAR + (BB_FULL + s2) * 8, ma, POL_LAST);
            }
#pragma unroll 1
            for (; h < nh; h++) {
                ACQ(STG_B);
                tma3d_mc(db + st * STG_B, tb, row + h * 32, zb, sb + B_BAR + (BB_FULL + st) * 8, mb);
                tma2d_mc(da + st * STG_B, ta, (h & 1) * 256, ya + (h >> 1) * 16, sb + B_BAR + (BB_FULL + st) * 8, ma, POL_LAST);
                NEXT;
            }
#pragma unroll 1
            for (h = 0; h < 4 && !layer; h++) { ACQ(0); NEXT; }
        } else if (t.type == T_CV) {
            const int q = t.a + rank;
            if (!gated && !t.dry) { wait_cnt_warp(g_gate, lds32(sb + S_GATE)); gated = true; }
            if (layer) {
                wait_cnt_warp(cnt_ptr(C_U, ch - 2), 32);
#pragma unroll 1
                for (int j = ch + 1; j >= 2; j--) {
                    ACQ(16 * PW * 4 + (j > 2 ? 4096 : 0));
                    bulk_g2s1(sb + st * STG_B, g_P + (((q >> 1) * 16 + j) * 2 + (q & 1)) * 16 * PW, 16 * PW * 4, sb + B_BAR + (BB_FULL + st) * 8, POL_N);
                    if (j > 2) bulk_g2s1(sb + st * STG_B + 12288, g_u + (((q >> 1) * 16 + ch + 1 - j) * 2 + (q & 1)) * 256, 4096, sb + B_BAR + (BB_FULL + st) * 8, POL_N);
                    NEXT;
                }
            } else {
#pragma unroll 1
                for (int j = min(ch, 1 + (ch & 1)); j >= 0; j--) {
                    if (j == 0 && ch >= 2) {
                        if (!t.dry) wait_cnt_warp(cnt_ptr(C_H, ch & ~1), 64);
#pragma unroll 1
                        for (int i = 0; i < ((ch & 1) || ch == 2 ? 1 : 2); i++) {
                            ACQ(16384);
                            bulk_g2s1(sb + st * STG_B, g_carry[i] + (ch * 16 + q) * 1024, 16384, sb + B_BAR + (BB_FULL + st) * 8, POL_LAST);
                            NEXT;
                        }
                    }
                    ACQ(32 * PW * 4);
                    bulk_g2s1(sb + st * STG_B, g_P + (q * 16 + j) * 32 * PW, 32 * PW * 4, sb + B_BAR + (BB_FULL + st) * 8, POL_N);
                    NEXT;
                }
            }
        }
    }
}

__device__ __forceinline__ uint4* qkv_dst(int layer, int ch, int w, int blk);
__device__ __forceinline__ uint4* op_dst(int layer, int ch, int slot, int w, uint32_t rank);
__device__ __forceinline__ uint64_t out_pol(int type, int layer, int ch) { return (type == T_QKV ? (!layer && ch > 1) : (layer && ch < 10)) ? POL_LATE : POL_SOON; }
__device__ __forceinline__ void bulk_relay(const Params& p, uint32_t sb, int cl) {
    for (int ti = 0; ti < MAXT; ti++) {
        const int type = p.task[cl][ti] & 7;
        if (type == T_END) break;
        if (type != T_QKV) continue;
        bar_sync(NB_PH, 96);
        const uint32_t ph = lds32(sb + B_ST + 8);
#pragma unroll 1
        for (int h = 2; h < 8; h++) {
            mbar_wait(sb + B_BAR + (BB_FULL + h) * 8, ph);
            if (h == 4 || h == 7) { bar_arrive(NB_REL + (h == 7) * 2, 160); bar_arrive(NB_REL + (h == 7) * 2 + 1, 160); }
        }
    }
}
__device__ __forceinline__ void bulk_release(const Params& p, uint32_t sb, int cl, uint32_t rank, int wg) {
    int nd = 0;
    for (int ti = 0; ti < MAXT; ti++) {
        const Task t = task_of(p.task[cl][ti], rank);
        const int type = t.type, layer = t.layer, ch = t.ch;
        if (type == T_END) break;
        if (type == T_FIN || (type == T_OP && (t.c & 32))) continue;
        if (type == T_OP && !layer) {
            mbar_wait(sb + B_BAR + (BB_DONE + wg) * 8, nd & 1);
            nd++;
            const int s0 = __shfl_sync(0xffffffffu, lds32(sb + B_ST + wg * 4), 0) + wg * 2;
            fence_async_smem();
#pragma unroll 1
            for (int w = 0; w < 4; w++)
                asm volatile("{.reg .pred p; elect.sync _|p,0xffffffff; @p cp.async.bulk.global.shared::cta.bulk_group.L2::cache_hint [%0],[%1],8192,%2; cp.async.bulk.commit_group;}"
                             ::"l"(op_dst(0, ch, t.c & 15, wg * 4 + w, rank)), "r"(sb + ((s0 + (w >> 1)) & (NSTG - 1)) * STG_B + (w & 1) * 8192), "l"(POL_SOON) : "memory");
            mbar_arrive1(sb + B_BAR + (BB_SF + wg) * 8);
            asm volatile("{.reg .pred p; elect.sync _|p,0xffffffff;\n"
                         "cp.async.bulk.wait_group 3; @p red.relaxed.gpu.global.add.u32 [%0],1; cp.async.bulk.wait_group 2; @p red.relaxed.gpu.global.add.u32 [%0+64],1;\n"
                         "cp.async.bulk.wait_group 1; @p red.relaxed.gpu.global.add.u32 [%0+128],1; cp.async.bulk.wait_group 0; @p red.relaxed.gpu.global.add.u32 [%0+192],1;}"
                         ::"l"(cnt_ptr(C_OP0 + rank * 2 + wg, ch)) : "memory");
#pragma unroll 1
            for (int i = 0; i < 8; i++) mbar_arrive1_cluster(mapa(sb + B_BAR + (BB_EMPTY + ((s0 + (i >> 2)) & (NSTG - 1))) * 8, i & 1));
            continue;
        }
#pragma unroll 1
        for (int u = 0; u < (type == T_QKV ? t.b : 1); u++) {
            const int blk = qkv_blk(t, u);
            unsigned* cnt = cnt_ptr(type == T_QKV ? C_QKV0 + layer : type == T_OP ? C_OP1 : layer ? C_H : C_CV, ch + (type == T_QKV && blk < 64 ? 16 : 0));
            const uint4* dst = type == T_QKV ? qkv_dst(layer, ch, wg * 4, blk) : op_dst(1, ch, t.c & 15, wg * 4, (t.blk >> 2) & 1) + 256;
            mbar_wait(sb + B_BAR + (BB_DONE + wg) * 8, nd & 1);
            nd++;
            if (type != T_CV) {
                fence_async_smem();
#pragma unroll
                for (int w = 0; w < 4; w++)
                    asm volatile("{.reg .pred p; elect.sync _|p,0xffffffff; @p cp.async.bulk.global.shared::cta.bulk_group.L2::cache_hint [%0],[%1],4096,%2;}"
                                 ::"l"(dst + (type == T_QKV ? (w >> 1) * 49152 + (w & 1) * 256 : w * 1024)), "r"(sb + B_OUT + (wg * 4 + w) * 4096), "l"(out_pol(type, layer, ch)) : "memory");
                asm volatile("cp.async.bulk.commit_group; cp.async.bulk.wait_group 0;" ::: "memory");
            }
            if (type != T_QKV) fence_async();
            if (!t.dry) asm volatile("{.reg .pred p; elect.sync _|p,0xffffffff; @p red.relaxed.gpu.global.add.u32 [%0],%1;}" ::"l"(cnt), "r"(type == T_QKV ? 2 : type == T_OP ? t.b : 1) : "memory");
            PROF(wg && (threadIdx.x & 31) == 0 && (type == T_CV || u + 2 == t.b), 3900 + ti);
            if (type == T_CV && !layer && !t.dry) {
                asm volatile("{.reg .pred p; elect.sync _|p,0xffffffff; @p cp.async.bulk.global.shared::cta.bulk_group [%0],[%1],4096;\n"
                             "cp.async.bulk.commit_group; cp.async.bulk.wait_group 0; @p red.relaxed.gpu.global.add.u32 [%2],1;}"
                             ::"l"(g_u + ((t.a + rank) * 16 + ch) * 512 + wg * 256), "r"(sb + B_UT + (ch & 1) * 8192 + wg * 4096), "l"(cnt_ptr(C_U, ch)) : "memory");
            }
            mbar_arrive1(sb + B_BAR + (BB_SF + wg) * 8);
        }
        PROF(wg && (threadIdx.x & 31) == 0, 3600 + ti * 4 + 3);
    }
}

__device__ __forceinline__ void stage_release(uint32_t sb, int w, int st) {
    if (!(w & 2)) mbar_arrive1_cluster(mapa(sb + B_BAR + (BB_EMPTY + st) * 8, w & 1));
}
template <bool ACC>
__device__ __forceinline__ void gemm_run(float* acc, uint32_t sb, int w, int h0, int h1, uint32_t& r0, uint32_t& r1, int& st, uint32_t& ph) {
    const uint64_t da0 = mkdesc(sb + (w >> 2) * 4096, 16, 512, 2), db0 = mkdesc(sb + 8192, 4096, 1024, 1);
    const uint32_t rel0 = mapa(sb + B_BAR + BB_EMPTY * 8, w & 1);
#pragma unroll 1
    for (int h = h0; h < h1; h++) {
        const uint64_t da = da0 + st * (STG_B >> 4), db = db0 + st * (STG_B >> 4);
        mbar_wait(sb + B_BAR + (BB_FULL + st) * 8, ph);
        if (ACC) wg_wait<1>();
        wg_fence();
        wgmma256<ACC>(acc, da, db);
        wgmma256<true>(acc, da + 2, db + 128);
        wg_commit();
        if (ACC) mbar_arrive1_cluster((w == 2 && h == LAGH - 1) ? sb + B_BAR + BB_GO * 8 : r0);
        r0 = r1;
        if (!(w & 2)) r1 = rel0 + st * 8;
        if (++st == NSTG) { st = 0; ph ^= 1; }
    }
}

__device__ __forceinline__ uint4* qkv_dst(int layer, int ch, int w, int blk) {
    return g_qkv[layer] + (size_t)((ch * 4 + (w >> 1)) * 32 + ((blk & 63) >> 1)) * 1536 + (blk >> 6) * 512 + (w & 1) * 256;
}
__device__ __forceinline__ uint4* op_dst(int layer, int ch, int slot, int w, uint32_t rank) {
    return g_pp[layer] + (size_t)(ch * MAXSPLIT + slot) * 8192 + (w * 32 + rank * 16) * 32;
}
__device__ __forceinline__ uint32_t ln2(uint32_t x, uint32_t m, uint32_t rh, uint32_t rl) {
    uint32_t d; asm volatile("{.reg .b32 t,u; sub.rn.bf16x2 t,%1,%2; mul.rn.bf16x2 u,t,%4; fma.rn.bf16x2 %0,t,%3,u;}" : "=r"(d) : "r"(x), "r"(m), "r"(rh), "r"(rl)); return d;
}
__device__ __forceinline__ void qkv_task(uint32_t sb, int w, int layer, int ch, int nu, int& ng, int& nd, uint32_t& ph, int ti, uint32_t zero) {
    constexpr int type = T_QKV;
    static_assert(NSTG == 8, "ring");
    const int lane = threadIdx.x & 31;
    const uint64_t db0 = mkdesc(sb, 4096, 1024, 1);
    const uint32_t rel = (w & 2) ? sb + B_BAR + BB_IDLE * 8 : mapa(sb + B_BAR + BB_EMPTY * 8, w & 1), full = sb + B_BAR + BB_FULL * 8;
    const uint32_t lo = sb + B_OUT + w * 4096 + (lane ^ (lane >> 3)) * 16;
    const uint4* xa = g_xA[layer] + (ch * 8 + w) * 1024 + lane;
    uint32_t m0, m1, h0, h1, l0, l1;
    uint4 A[32];
    {
        mbar_wait(full, ph);
        mbar_wait(full + 8, ph);
        CPROF(1);
        const uint32_t sa = sb + (lane >> 4) * STG_B + 16384 + (w * 16 + (lane & 15)) * 8;
        uint2 v[8];
#pragma unroll
        for (int i = 0; i < 8; i++) v[i] = lds64(sa + i * 1024 * layer);
#pragma unroll
        for (int i = 0; i < 4 * QB1; i++) A[i] = ldcg128(xa + i * 32);
        bar_sync(NB_WG + (w >> 2), 128);
        float sm = 0, M2 = 0, D = 0;
#pragma unroll
        for (int i = 0; i < 8; i++) { sm += __uint_as_float(v[i].x); M2 += __uint_as_float(v[i].y); }
        if (!layer) { sm = __uint_as_float(v[0].x); M2 = __uint_as_float(v[0].y); }
        sm += __shfl_xor_sync(0xffffffffu, sm, 16);
#pragma unroll
        for (int i = 0; i < 8; i++) { const float d = __uint_as_float(v[i].x) * (1.f / 32.f) - sm * (1.f / 512.f); D += 32.f * d * d; }
        M2 += layer ? D : sm * sm * (-1.f / 1024.f);
        M2 = fmaxf(M2 + __shfl_xor_sync(0xffffffffu, M2, 16), 0.f);
        const float2 o = ln_finish(sm * (1.f / 512.f), M2 * (1.f / 512.f));
        const float r = rcp(o.y), rh = rbf(r);
        const uint32_t mm = pack2(o.x, o.x), hl = pack2(r - rh, rh);
        m0 = __shfl_sync(0xffffffffu, mm, lane >> 2); m1 = __shfl_sync(0xffffffffu, mm, (lane >> 2) + 8);
        l0 = __shfl_sync(0xffffffffu, hl, lane >> 2); l1 = __shfl_sync(0xffffffffu, hl, (lane >> 2) + 8);
        h0 = __byte_perm(l0, 0, 0x3232); h1 = __byte_perm(l1, 0, 0x3232); l0 = __byte_perm(l0, 0, 0x1010); l1 = __byte_perm(l1, 0, 0x1010);
    }
    float acc[64];
#define QNRM(i) A[i] = make_uint4(ln2(A[i].x, m0, h0, l0), ln2(A[i].y, m1, h1, l1), ln2(A[i].z, m0, h0, l0), ln2(A[i].w, m1, h1, l1))
#pragma unroll
    for (int h = 0; h < 8; h++) {
        const uint64_t db = db0 + h * (STG_B >> 4);
        const int b0 = h == 0 ? QB1 : h == QB1 ? QB2 : h == QB2 ? QB3 : 8, b1 = h == 0 ? QB2 : h == QB1 ? QB3 : 8;
        if (b0 < b1) {
            const uint4* xb = xa + (A[4 * b0 - 1].x & zero);
#pragma unroll
            for (int i = 4 * b0; i < 4 * b1; i++) A[i] = ldcg128(xb + i * 32);
            bar_sync(NB_WG + (w >> 2), 128);
        }
        QNRM(4 * h); QNRM(4 * h + 1); QNRM(4 * h + 2); QNRM(4 * h + 3);
        if (h == 2 || h == 5) bar_sync(NB_REL + (h == 5) * 2 + (w >> 2), 160);
        if (h) wg_wait<1>();
        wg_fence();
        if (h) wgmma128r<true>(acc, A[4 * h], db); else wgmma128r<false>(acc, A[0], db);
        wgmma128r<true>(acc, A[4 * h + 1], db + 128);
        wgmma128r<true>(acc, A[4 * h + 2], db + 512);
        wgmma128r<true>(acc, A[4 * h + 3], db + 640);
        wg_commit();
        if (h >= 2) mbar_arrive1_cluster(rel + (h - 2) * 8);
    }
    ph ^= 1;
#pragma unroll 1
    for (int u = 1;; u++) {
        mbar_wait(sb + B_BAR + (BB_SF + (w >> 2)) * 8, (nd & 1) ^ 1);
        if (u < nu) mbar_wait(full, ph);
        wg_wait<1>();
        mbar_arrive1_cluster(rel + 48);
        wg_wait<0>();
        mbar_arrive1_cluster(rel + 56);
        uint4 o[8];
#pragma unroll
        for (int n = 0; n < 8; n++) {
            const float* a = acc + (n >> 1) * 16 + (n & 1) * 2;
            o[n] = make_uint4(pack2(a[0], a[1]), pack2(a[4], a[5]), pack2(a[8], a[9]), pack2(a[12], a[13]));
            sts128(lo + n * 512, o[n].x, o[n].y, o[n].z, o[n].w);
        }
        __syncwarp();
        mbar_arrive1(sb + B_BAR + (BB_DONE + (w >> 2)) * 8);
        nd++;
        CPROF(min(2 + u, 7));
        if (u == nu) break;
        if (LAGQ) { if (w >> 2) mbar_wait(sb + B_BAR + BB_GO * 8, ng & 1); ng++; }
        const uint64_t db1 = mkdesc(sb + (u >> 10), 4096, 1024, 1);
#pragma unroll
        for (int h = 0; h < 8; h++) {
            const uint64_t db = db1 + h * (STG_B >> 4);
            if (h) { mbar_wait(full + h * 8, ph); wg_wait<1>(); }
            wg_fence();
            if (h) wgmma128r<true>(acc, A[4 * h], db); else wgmma128r<false>(acc, A[0], db);
            wgmma128r<true>(acc, A[4 * h + 1], db + 128);
            wgmma128r<true>(acc, A[4 * h + 2], db + 512);
            wgmma128r<true>(acc, A[4 * h + 3], db + 640);
            wg_commit();
            if (h >= 2) mbar_arrive1_cluster(rel + (h - 2) * 8);
            if (h == LAGQ - 1 && w == 2) mbar_arrive1(sb + B_BAR + BB_GO * 8);
        }
        ph ^= 1;
    }
}

template <int NB>
__device__ __forceinline__ void load_resid(uint32_t* r, int layer, int ch, int w, int cb) {
#pragma unroll
    for (int i = 0; i < NB; i++) {
        const uint4 v = ldcg128(g_xA[layer] + ((ch * 8 + w) * 32 + cb + i) * 32 + (threadIdx.x & 31));
        r[4 * i] = v.x; r[4 * i + 1] = v.y; r[4 * i + 2] = v.z; r[4 * i + 3] = v.w;
    }
}
template <int NS>
__device__ __forceinline__ void part_load(uint4* v, int layer, int ch, int w, int cb, int ns) {
    const uint4* src = g_pp[layer] + (size_t)ch * MAXSPLIT * 8192 + (w * 32 + cb) * 32 + (threadIdx.x & 31);
#pragma unroll
    for (int i = 0; i < 2 * NS; i++) {
        asm volatile("{.reg .pred p; .reg .b128 t; setp.gt.s32 p,%6,0; mov.b128 t,{0,0,0,0}; @p ld.relaxed.gpu.global.L2::cache_hint.b128 t,[%4],%5; mov.b128 {%0,%1,%2,%3},t;}"
                     : "=r"(v[i].x), "=r"(v[i].y), "=r"(v[i].z), "=r"(v[i].w) : "l"(src + (i / NS) * 32 + (i % NS) * 8192), "l"(POL_LAST), "r"(ns - i % NS) : "memory");
    }
}
template <int NS>
__device__ __forceinline__ void part_sum(float* x, const uint4* v, const uint32_t* r) {
    const int dg = ((threadIdx.x & 31) >> 2) - 2 * (threadIdx.x & 3);
    const uint32_t idm = dg == 0 ? 0x00003f80u : dg == 1 ? 0x3f800000u : 0u;
#pragma unroll
    for (int b = 0; b < 2; b++) {
        float* y = x + b * 8;
#pragma unroll
        for (int i = 0; i < 8; i++) y[i] = 0;
#pragma unroll
        for (int s = 0; s < NS; s++) { mma8(y, v[b * NS + s].x, v[b * NS + s].y, idm); mma8(y + 4, v[b * NS + s].z, v[b * NS + s].w, idm); }
#pragma unroll
        for (int i = 0; i < 4; i++) { y[2 * i] = rbf(rbf(y[2 * i]) + blo(r[b * 4 + i])); y[2 * i + 1] = rbf(rbf(y[2 * i + 1]) + bhi(r[b * 4 + i])); }
    }
}

__device__ __forceinline__ float4 row_stats32(const float* x) {
    float a = (x[0] + x[1]) + (x[4] + x[5]) + (x[8] + x[9]) + (x[12] + x[13]);
    float b = (x[2] + x[3]) + (x[6] + x[7]) + (x[10] + x[11]) + (x[14] + x[15]);
    a += __shfl_xor_sync(0xffffffffu, a, 1); b += __shfl_xor_sync(0xffffffffu, b, 1);
    a += __shfl_xor_sync(0xffffffffu, a, 2); b += __shfl_xor_sync(0xffffffffu, b, 2);
    const float ma = a * (1.f / 32.f), mb = b * (1.f / 32.f);
    float qa = 0, qb = 0;
#pragma unroll
    for (int i = 0; i < 4; i++) {
        float d0 = x[4 * i] - ma, d1 = x[4 * i + 1] - ma, d2 = x[4 * i + 2] - mb, d3 = x[4 * i + 3] - mb;
        qa += d0 * d0 + d1 * d1; qb += d2 * d2 + d3 * d3;
    }
    qa += __shfl_xor_sync(0xffffffffu, qa, 1); qb += __shfl_xor_sync(0xffffffffu, qb, 1);
    qa += __shfl_xor_sync(0xffffffffu, qa, 2); qb += __shfl_xor_sync(0xffffffffu, qb, 2);
    return make_float4(a, qa, b, qb);
}

__device__ __forceinline__ void conv_stage(float* Y, uint32_t pbase, uint32_t ubase) {
    const int lane = threadIdx.x & 31, w = threadIdx.x >> 5, g = lane >> 2, c = lane & 3;
#pragma unroll
    for (int cp = 0; cp < 2; cp++) {
        const int chl = w * 4 + cp * 2 + (lane >> 4);
        const uint4 b = ldsm4(ubase + chl * 256 + ((lane >> 3) & 1) * 128 + (((lane & 7) ^ (chl & 7)) << 4));
#pragma unroll
        for (int h = 0; h < 2; h++) {
            const uint32_t pa = pbase + ((w * 4 + cp * 2 + h) * PW + 16 + g - 2 * c) * 4;
            uint32_t lo = lds32(pa - 32);
#pragma unroll
            for (int d = 0; d < 8; d++) {
                const uint32_t a0 = lds32(pa + d * 64), a1 = lds32(pa + d * 64 + 32);
                mma16(Y + ((cp * 2 + h) * 8 + d) * 4, a0, a1, lo, a0, h ? b.z : b.x, h ? b.w : b.y);
                lo = a1;
            }
        }
    }
}

__device__ __forceinline__ void conv_combine(const float* y8, float* cur, float* nxt) {
    const int lane = threadIdx.x & 31, c = lane & 3;
    cur[0] = y8[0]; cur[1] = y8[1] + y8[4]; cur[2] = y8[2]; cur[3] = y8[3] + y8[6];
    nxt[0] = y8[29]; nxt[1] = 0.f; nxt[2] = y8[31]; nxt[3] = 0.f;
#pragma unroll
    for (int e = 1; e < 4; e++) {
        const int src = (lane & ~3) | ((c - e) & 3);
        const float v0 = __shfl_sync(0xffffffffu, y8[8 * e] + y8[8 * e - 3], src), v1 = __shfl_sync(0xffffffffu, y8[8 * e + 1] + y8[8 * e + 4], src);
        const float v2 = __shfl_sync(0xffffffffu, y8[8 * e + 2] + y8[8 * e - 1], src), v3 = __shfl_sync(0xffffffffu, y8[8 * e + 3] + y8[8 * e + 6], src);
        if (c >= e) { cur[0] += v0; cur[1] += v1; cur[2] += v2; cur[3] += v3; }
        else { nxt[0] += v0; nxt[1] += v1; nxt[2] += v2; nxt[3] += v3; }
    }
}

__device__ __forceinline__ void hist_task(float* Y, uint32_t sb, int w, int ch, int q, int& st, uint32_t& ph, int nd) {
    const int lane = threadIdx.x & 31, chl = w * 2 + (lane >> 4);
    const uint32_t ua = sb + 12288 + chl * 256 + ((lane >> 3) & 1) * 128 + (((lane & 7) ^ (chl & 7)) << 4);
    const uint32_t pa = sb + (w * 2 * PW + 16 + (lane >> 2) - 2 * (lane & 3)) * 4;
#pragma unroll
    for (int i = 0; i < 128; i++) Y[i] = 0;
    uint4 b1 = make_uint4(0, 0, 0, 0);
#pragma unroll 1
    for (int j = ch + 1; j >= 2; j--) {
        const uint4 b0 = b1;
        mbar_wait(sb + B_BAR + (BB_FULL + st) * 8, ph);
        b1 = ldsm4(ua + st * STG_B);
        if (j == 2) b1 = make_uint4(0, 0, 0, 0);
#pragma unroll
        for (int h = 0; h < 2; h++) {
            const uint32_t o = pa + st * STG_B + h * PW * 4;
            uint32_t lo = lds32(o - 32);
#pragma unroll
            for (int d = 0; d < 8; d++) {
                const uint32_t a0 = lds32(o + d * 64), a1 = lds32(o + d * 64 + 32);
                mma16(Y + (h * 16 + d) * 4, a0, a1, lo, a0, h ? b0.z : b0.x, h ? b0.w : b0.y);
                mma16(Y + (h * 16 + 8 + d) * 4, a0, a1, lo, a0, h ? b1.z : b1.x, h ? b1.w : b1.y);
                lo = a1;
            }
        }
        bar_sync(NB_WG + (w >> 2), 128);
        stage_release(sb, w, st);
        if (++st == NSTG) { st = 0; ph ^= 1; }
    }
    mbar_wait(sb + B_BAR + (BB_SF + (w >> 2)) * 8, (nd & 1) ^ 1);
#pragma unroll
    for (int h = 0; h < 2; h++) {
        const int o = ((ch * 16 + (q >> 1)) * 4 + (w & 1) * 2 + h) * 256 + ((q & 1) * 4 + (w >> 1)) * 32 + lane;
        float c0[4], n0[4], c1[4], n1[4];
        conv_combine(Y + h * 64, c0, n0); conv_combine(Y + h * 64 + 32, c1, n1);
        g_carry[0][o] = make_float4(c0[0], c0[1], c0[2], c0[3]);
        g_carry[0][o + 16384] = make_float4(c1[0] + n0[0], c1[1] + n0[1], c1[2] + n0[2], c1[3] + n0[3]);
        g_carry[1][o + 32768] = make_float4(n1[0], n1[1], n1[2], n1[3]);
    }
}

__device__ __forceinline__ void conv_task(const Params& p, float* Y, uint32_t sb, int w, int ch, int q, int ns, bool dry, int& st, uint32_t& ph, int nd) {
    const int tid = threadIdx.x, lane = tid & 31, g = lane >> 2, c = lane & 3;
    uint32_t dk[4];
    const uint32_t sg = (~ch & 2) << 30;
    int sr = st;
    float x[16];
    PROF(tid == 128, 2048 + ch * 8);
#pragma unroll
    for (int i = 0; i < 128; i++) Y[i] = 0;
#pragma unroll 1
    for (int j = min(ch, 1 + (ch & 1)); j >= 1; j--) {
        mbar_wait(sb + B_BAR + (BB_FULL + st) * 8, ph);
        conv_stage(Y, sb + st * STG_B, sb + B_UT + ((ch - j) & 1) * 8192);
        if (++st == NSTG) { st = 0; ph ^= 1; }
    }
#define CONV_CARRY _Pragma("unroll 1") \
    for (int i = 0; i < min(ch, (ch & 1) ? 2 : 3); i++) { \
        if (i) mbar_wait(sb + B_BAR + (BB_FULL + st) * 8, ph); \
        const uint32_t ca = sb + (i ? st * STG_B : B_SP) + tid * 16; \
_Pragma("unroll") \
        for (int k = 0; k < 4; k++) { \
            const uint4 cr = lds128(ca + k * 4096); \
            Y[k * 32] += __uint_as_float(cr.x); Y[k * 32 + 1] += __uint_as_float(cr.y); Y[k * 32 + 2] += __uint_as_float(cr.z); Y[k * 32 + 3] += __uint_as_float(cr.w); \
        } \
        if (i && ++st == NSTG) { st = 0; ph ^= 1; } \
    } \
    bar_sync(NB_C, 256); \
_Pragma("unroll 1") \
    for (; sr != st; sr = (sr + 1) & (NSTG - 1)) stage_release(sb, w, sr); \
    mbar_wait(sb + B_BAR + (BB_SF + (w >> 2)) * 8, (nd & 1) ^ 1); \
    mbar_wait(sb + B_BAR + (BB_SF + 1 - (w >> 2)) * 8, (nd & 1) ^ 1);
    const uint32_t ut = sb + B_UT + (ch & 1) * 8192;
    if (CPOS == 0) { CONV_CARRY }
    PROF(tid == 128, 2048 + ch * 8 + 7);
    {
        uint4 v[2 * OPS1];
        wait_cnt_warp(cnt_ptr(C_OP0 + (q >> 3) * 2 + (w >> 2), ch + (w & 3) * 16), ns);
        part_load<OPS1>(v, 0, ch, w, 2 * q, ns);
        uint32_t rs[8];
        load_resid<2>(rs, 0, ch, w, 2 * q);
        if (CPOS == 1) { CONV_CARRY }
        part_sum<OPS1>(x, v, rs);
        const float4 s = row_stats32(x);
        float2* dst = g_st2 + ((ch & 1) * 16 + q) * 128 + w * 16 + g + c * 8;
        asm volatile("{.reg .pred p; setp.ne.u32 p,%2,0; @p st.relaxed.gpu.global.b64 [%0],%1;}" ::"l"(dst),
                     "l"(((uint64_t)((__float_as_uint(c ? s.w : s.y) & 0x7fffffffu) | sg) << 32) | __float_as_uint(c ? s.z : s.x)), "r"((uint32_t)(c < 2 && !dry)) : "memory");
        PROF(tid == 128, 2048 + ch * 8 + 1);
    }
#pragma unroll
    for (int i = 0; i < 4; i++) asm volatile("ld.global.nc.u32 %0,[%1];" : "=r"(dk[i]) : "l"(p.Dskip + q * 32 + i * 8 + 2 * c));
    if (CPOS == 2) { CONV_CARRY }
    float2 ln0, ln1;
    {
        const float2* src = g_st2 + ((ch & 1) * 16 + (lane >> 4) * 8) * 128 + w * 16 + (lane & 15);
        uint64_t v[8];
        int n = 0;
#pragma unroll
        for (int i = 0; i < 8; i++) v[i] = (uint64_t)~sg << 32;
        while (true) {
            bool bad = false;
#pragma unroll
            for (int i = 0; i < 8; i++) asm volatile("{.reg .pred p; setp.lt.s32 p,%2,0; @p ld.relaxed.gpu.global.b64 %0,[%1];}" : "+l"(v[i]) : "l"(src + i * 128), "r"((uint32_t)(v[i] >> 32) ^ sg) : "memory");
#pragma unroll
            for (int i = 0; i < 8; i++) bad = bad || (int)((uint32_t)(v[i] >> 32) ^ sg) < 0;
            if (!__any_sync(0xffffffffu, bad && !dry)) break;
            if (++n > 2000000) __trap();
        }
        float sm = 0;
#pragma unroll
        for (int i = 0; i < 8; i++) sm += __uint_as_float((uint32_t)v[i]);
        sm += __shfl_xor_sync(0xffffffffu, sm, 16);
        const float mean = sm * (1.f / 512.f);
        float M2 = 0;
#pragma unroll
        for (int i = 0; i < 8; i++) { const float d = __uint_as_float((uint32_t)v[i]) * (1.f / 32.f) - mean; M2 += fabsf(__uint_as_float((uint32_t)(v[i] >> 32))) + 32.f * d * d; }
        M2 += __shfl_xor_sync(0xffffffffu, M2, 16);
        const float2 o = ln_finish(mean, M2 * (1.f / 512.f));
        ln0.x = __shfl_sync(0xffffffffu, o.x, g); ln0.y = __shfl_sync(0xffffffffu, o.y, g);
        ln1.x = __shfl_sync(0xffffffffu, o.x, g + 8); ln1.y = __shfl_sync(0xffffffffu, o.y, g + 8);
    }
    PROF(tid == 128, 2048 + ch * 8 + 2);
    uint32_t u[8];
#pragma unroll
    for (int i = 0; i < 8; i++) {
        const float2 l = (i & 1) ? ln1 : ln0;
        u[i] = pack2(__fdividef(rbf(x[2 * i] - l.x), l.y), __fdividef(rbf(x[2 * i + 1] - l.x), l.y));
        const int chl = (i >> 1) * 8 + g;
        sts32(ut + chl * 256 + (i & 1) * 128 + ((w ^ g) << 4) + c * 4, movm(u[i]));
    }
    bar_sync(NB_C, 256);
    mbar_wait(sb + B_BAR + (BB_FULL + st) * 8, ph);
    PROF(tid == 128, 2048 + ch * 8 + 3);
    conv_stage(Y, sb + st * STG_B, ut);
    uint32_t yp[4][2];
    float nxt[4][4];
    {
        float y[4][4];
#pragma unroll
        for (int k = 0; k < 4; k++) conv_combine(Y + k * 32, y[k], nxt[k]);
#pragma unroll
        for (int i = 0; i < 4; i++) { yp[i][0] = pack2(y[0][i], y[1][i]); yp[i][1] = pack2(y[2][i], y[3][i]); }
    }
#pragma unroll
    for (int i = 0; i < 4; i++) sts64(sb + B_YT + (16 * (2 * c + (i & 1)) + g + (i >> 1) * 8) * 80 + w * 8, yp[i][0], yp[i][1]);
    bar_sync(NB_C, 256);
    stage_release(sb, w, st);
    if (++st == NSTG) { st = 0; ph ^= 1; }
    PROF(tid == 128, 2048 + ch * 8 + 4);
    uint32_t xo[8];
    uint4* dA = g_xA[1] + ((ch * 8 + w) * 32 + 2 * q) * 32 + lane;
#pragma unroll
    for (int i = 0; i < 8; i++) {
        const int col = (i >> 1) * 8 + 2 * c;
        const uint32_t yv = lds32(sb + B_YT + (w * 16 + g + (i & 1) * 8) * 80 + col * 2);
        const uint32_t dv = dk[i >> 1];
        x[2 * i] = rbf(x[2 * i] + rbf(blo(yv) + rbf(blo(u[i]) * blo(dv))));
        x[2 * i + 1] = rbf(x[2 * i + 1] + rbf(bhi(yv) + rbf(bhi(u[i]) * bhi(dv))));
        xo[i] = pack2(x[2 * i], x[2 * i + 1]);
        if ((i & 3) == 3) dA[(i >> 2) * 32] = make_uint4(xo[i - 3], xo[i - 2], xo[i - 1], xo[i]);
    }
    {
        const float4 s = row_stats32(x);
        float2* dst = g_st[1] + (ch * 16 + q) * 128 + w * 16 + g;
        if (c == 0) dst[0] = make_float2(s.x, s.y);
        if (c == 1) dst[8] = make_float2(s.z, s.w);
        __syncwarp();
    }
    PROF(tid == 128, 2048 + ch * 8 + 5);
    mbar_arrive1(sb + B_BAR + (BB_DONE + (w >> 2)) * 8);
    bar_sync(NB_C, 256);
#pragma unroll
    for (int k = 0; k < 4; k++) sts128(sb + B_SP + k * 4096 + tid * 16, __float_as_uint(nxt[k][0]), __float_as_uint(nxt[k][1]), __float_as_uint(nxt[k][2]), __float_as_uint(nxt[k][3]));
    PROF(tid == 128, 2048 + ch * 8 + 6);
}

__device__ __forceinline__ void out_store(const Params& p, const float* x, int ch, int cb) {
    const int lane = threadIdx.x & 31, w = threadIdx.x >> 5, g = lane >> 2, c = lane & 3;
#pragma unroll
    for (int h = 0; h < 2; h++) {
        const float* y = x + h * 2;
        uint32_t v0 = pack2(y[0], y[1]), v1 = pack2(y[4], y[5]), v2 = pack2(y[8], y[9]), v3 = pack2(y[12], y[13]);
        uint32_t t0 = (c & 1) ? v0 : v1, t1 = (c & 1) ? v2 : v3;
        t0 = __shfl_xor_sync(0xffffffffu, t0, 1); t1 = __shfl_xor_sync(0xffffffffu, t1, 1);
        if (c & 1) { v0 = t0; v2 = t1; } else { v1 = t0; v3 = t1; }
        t0 = (c & 2) ? v0 : v2; t1 = (c & 2) ? v1 : v3;
        t0 = __shfl_xor_sync(0xffffffffu, t0, 2); t1 = __shfl_xor_sync(0xffffffffu, t1, 2);
        if (c & 2) { v0 = t0; v1 = t1; } else { v2 = t0; v3 = t1; }
        stg128((uint4*)(p.out + (size_t)(ch * 128 + w * 16 + g + h * 8) * 512 + cb * 16 + c * 8), make_uint4(v0, v1, v2, v3), POL_LATE);
    }
}
__device__ __forceinline__ void fin_task(const Params& p, int ch, int cb0, int ncb, int ns, bool dry) {
    const int w = threadIdx.x >> 5;
    uint32_t rs[8];
    wait_cnt_warp(cnt_ptr(C_CV, ch), dry ? 0 : 32);
    load_resid<2>(rs, 1, ch, w, cb0);
    wait_cnt_warp(cnt_ptr(C_OP1, ch), dry ? 0 : 256);
    for (int cb = cb0; cb < cb0 + ncb; cb += 2) {
        float x[16];
        if (cb != cb0) load_resid<2>(rs, 1, ch, w, cb);
        uint4 v[32];
        part_load<16>(v, 1, ch, w, cb, ns);
        part_sum<16>(x, v, rs);
        out_store(p, x, ch, cb);
    }
}

__device__ __forceinline__ void bulk_consumer(const Params& p, uint32_t sb, int cl, uint32_t rank, int w) {
    int st = 0; uint32_t ph = 0; int nd = 0, ng = 0;
    for (int ti = 0; ti < MAXT; ti++) {
        const Task t = task_of(p.task[cl][ti], rank);
        const int type = t.type, layer = t.layer, ch = t.ch;
        if (type == T_END) break;
        bool staged = type != T_FIN;
        PROF(threadIdx.x == 0, 3600 + ti * 4);
        CPROF(0);
        if (type == T_QKV) {
            staged = false;
            #pragma unroll 1
            while (st) {
                if (!(w & 3)) { mbar_wait(sb + B_BAR + (BB_FULL + st) * 8, ph); stage_release(sb, 0, st); stage_release(sb, 1, st); }
                if (++st == NSTG) { st = 0; ph ^= 1; }
            }
            if (!(w & 3)) { sts32(sb + B_ST + 8, ph); bar_arrive(NB_PH, 96); }
            qkv_task(sb, w, layer, ch, t.b, ng, nd, ph, ti, p.zero);
            PROF(threadIdx.x == 128, 3600 + ti * 4 + 1);
        } else if (type == T_OP) {
            const int lane = threadIdx.x & 31;
            float acc[128];
            uint32_t r0 = sb + B_BAR + BB_IDLE * 8, r1 = r0;
            if (w >> 2) mbar_wait(sb + B_BAR + BB_GO * 8, ng & 1);
            ng++;
            gemm_run<false>(acc, sb, w, 0, 1, r0, r1, st, ph);
            gemm_run<true>(acc, sb, w, 1, 2 * t.b, r0, r1, st, ph);
            mbar_wait(sb + B_BAR + (BB_SF + (w >> 2)) * 8, (nd & 1) ^ 1);
            wg_wait<1>();
            mbar_arrive1_cluster(r0);
            wg_wait<0>();
            mbar_arrive1_cluster(r1);
            PROF(threadIdx.x == 128, 3600 + ti * 4 + 1);
            if (t.c & 32) {
                staged = false;
                const int dg = (lane >> 2) - 2 * (lane & 3);
                const uint32_t idm = dg == 0 ? 0x00003f80u : dg == 1 ? 0x3f800000u : 0u;
                wait_cnt_warp(cnt_ptr(C_OP1, ch), 256 - 4 * t.b);
#pragma unroll 1
                for (int i = 0; i < (t.c & 15); i++) {
                    const uint4* src = op_dst(1, ch, i, w, (t.blk >> 2) & 1) + lane;
                    uint4 v[16];
#pragma unroll
                    for (int j = 0; j < 16; j++) v[j] = ldcg128_last(src + j * 32);
#pragma unroll
                    for (int j = 0; j < 16; j++) { mma8(acc + j * 8, v[j].x, v[j].y, idm); mma8(acc + j * 8 + 4, v[j].z, v[j].w, idm); }
                }
#pragma unroll
                for (int j = 0; j < 16; j += 4) {
                    uint32_t rs[16];
                    load_resid<4>(rs, 1, ch, w, (t.blk & 4) * 4 + j);
#pragma unroll
                    for (int i = 0; i < 16; i++) { float* y = acc + j * 8 + 2 * i; y[0] = rbf(y[0]) + blo(rs[i]); y[1] = rbf(y[1]) + bhi(rs[i]); }
                    out_store(p, acc + j * 8, ch, (t.blk & 4) * 4 + j); out_store(p, acc + j * 8 + 16, ch, (t.blk & 4) * 4 + j + 2);
                }
            } else if (!layer) {
                const int s2 = st + (w >> 1);
                const uint32_t o = sb + (s2 & (NSTG - 1)) * STG_B + (w & 1) * 8192 + lane * 16;
                mbar_wait(sb + B_BAR + (BB_FULL + (s2 & (NSTG - 1))) * 8, ph ^ (s2 >= NSTG));
#pragma unroll
                for (int j = 0; j < 16; j++)
                    sts128(o + j * 512, pack2(acc[j * 8], acc[j * 8 + 1]), pack2(acc[j * 8 + 2], acc[j * 8 + 3]), pack2(acc[j * 8 + 4], acc[j * 8 + 5]), pack2(acc[j * 8 + 6], acc[j * 8 + 7]));
                sts32(sb + B_ST + (w >> 2) * 4, st);
                st += 4;
                if (st >= NSTG) { st -= NSTG; ph ^= 1; }
            } else {
                uint4* dst = op_dst(layer, ch, t.c & 15, w, (t.blk >> 2) & 1) + lane;
#pragma unroll
                for (int n = 0; n < 16; n++) {
                    const int j = (n >> 1) + (n & 1) * 8;
                    const uint4 v = make_uint4(pack2(acc[j * 8], acc[j * 8 + 1]), pack2(acc[j * 8 + 2], acc[j * 8 + 3]), pack2(acc[j * 8 + 4], acc[j * 8 + 5]), pack2(acc[j * 8 + 6], acc[j * 8 + 7]));
                    if (j < 16 - NSB) stg128(dst + j * 32, v, out_pol(T_OP, layer, ch)); else sts128(sb + B_OUT + (w * NSB + j - (16 - NSB)) * 512 + lane * 16, v.x, v.y, v.z, v.w);
                }
            }
        } else if (type == T_CV) {
            float acc[128];
            if (layer) hist_task(acc, sb, w, ch, t.a + rank, st, ph, nd);
            else { conv_task(p, acc, sb, w, ch, t.a + rank, t.b, t.dry, st, ph, nd); staged = false; nd++; }
        } else {
            fin_task(p, ch, t.a + rank * t.c, t.c, t.b, t.dry);
        }
        if (staged) {
            __syncwarp();
            mbar_arrive1(sb + B_BAR + (BB_DONE + (w >> 2)) * 8);
            nd++;
        }
        PROF(threadIdx.x == 128, 3600 + ti * 4 + 2);
        __syncwarp();
    }
}

constexpr int P_Y = 131072  , P_PRM = P_Y  , P_K6 = P_PRM + 8192  ,
              P_P = P_Y + 40960  , P_U = P_P + 33280  , P_END = P_U + 17408, P_X = 98304  ;
static_assert(P_END <= B_BAR && P_END <= R_BAR, "prologue scratch");
#define KGUN 2
constexpr int KGU = KGUN;
__device__ __forceinline__ void csq(float& r, float& i) { const float t = r * i; r = fmaf(r, r, -(i * i)); i = t + t; }
__device__ __forceinline__ void cpow(float ar, float ph, float p, float& r, float& i) {
    const float e = ex2(ar * p);
    const float u = ph * p, n = fabsf(u) < 4194304.f ? (u + 12582912.f) - 12582912.f : u;
    const float t = (u - n) * 6.283185307179586f;
    r = e * __cosf(t); i = e * __sinf(t);
}
__device__ __forceinline__ void mma_tf32(float* c, float a0, float a1, float a2, float a3, float b0, float b1) {
    asm volatile("mma.sync.aligned.m16n8k8.row.col.f32.tf32.tf32.f32 {%0,%1,%2,%3},{%4,%5,%6,%7},{%8,%9},{%0,%1,%2,%3};"
                 : "+f"(c[0]), "+f"(c[1]), "+f"(c[2]), "+f"(c[3])
                 : "r"(__float_as_uint(a0)), "r"(__float_as_uint(a1)), "r"(__float_as_uint(a2)), "r"(__float_as_uint(a3)), "r"(__float_as_uint(b0)), "r"(__float_as_uint(b1)));
}

struct ProRegs { uint32_t v[2][4], ldt[2]; };
__device__ __forceinline__ void prologue_load(const ProArgs& a, int b, ProRegs& pr) {
    const int w = threadIdx.x >> 5;
#pragma unroll
    for (int i = 0; i < 2; i++) {
        const int gi = b * 512 + (w & 3) * 128 + ((w >> 2) & 1) * 64 + i * 32 + (threadIdx.x & 31);
        pr.ldt[i] = __ldg((const uint16_t*)a.ldt + b * 4 + (w & 3));
        pr.v[i][0] = __ldg((const uint16_t*)a.lAr + gi); pr.v[i][1] = __ldg((const uint16_t*)a.Ai + gi);
        pr.v[i][2] = __ldg((const uint16_t*)a.Cr + gi); pr.v[i][3] = __ldg((const uint16_t*)a.Ci + gi);
    }
}
__device__ __forceinline__ void prologue(const ProArgs& a, uint32_t sb, int b, int w, const ProRegs& pr) {
    const int tid = threadIdx.x, lane = tid & 31, g = lane >> 2, c = lane & 3;
    const int d0 = b * 4;
    if (w >= 8) {
        const int t2 = tid - 256;
        if (w < 10) {
            const int row = b * 16 + (w - 8) * 8 + g;
            const float4 r4 = row_stats((const uint4*)(a.x + (size_t)row * 512) + c, 4);
            const float2 r = make_float2(r4.x + r4.z, r4.y + r4.w);
            const float2 l = ln_finish(r.x * (1.f / 512.f), fmaxf(r.y - r.x * r.x * (1.f / 512.f), 0.f) * (1.f / 512.f));
            if (c == (g >> 1)) asm volatile("st.relaxed.gpu.global.u32 [%0],%1;" ::"l"(g_ln0 + row), "r"(pack2(l.x, l.y)) : "memory");
        }
        PROF(t2 == 0, 3516);
        const int gi = b * 128 + t2;
        if (t2 < 32) acc_init(a.mem0, b * 32 + t2);
        if (t2 >= 112) ((uint4*)g_st2)[b * 16 + t2 - 112] = make_uint4(0, 0, 0, 0);
        if (gi < 13 * 64) g_cnt[gi] = 0;
        bar_sync(6, 384);
        if (gi < 512) g_st[0][(gi >> 8) * 2048 + (lds32(sb + S_TAG) ^ 1) * 256 + (gi & 255)] = make_float2(0.f, 0.f);
        asm volatile("{.reg .pred p; elect.sync _|p,0xffffffff; @p cp.async.bulk.prefetch.L2.global [%0],32768;}"
                     ::"l"((w == 8 ? a.Wq : w == 9 ? a.Wk : w == 10 ? a.Wv : a.Wo) + (size_t)b * 16384) : "memory");
        mbar_wait(sb + S_XBAR, 0);
#pragma unroll 1
        for (int h = 0; h < 2; h++) {
            uint32_t l[8];
            int n = 0;
            while (true) {
                bool ok = true;
#pragma unroll
                for (int i = 0; i < 8; i++) asm volatile("ld.relaxed.gpu.global.u32 %0,[%1];" : "=r"(l[i]) : "l"(g_ln0 + h * 1024 + i * 128 + t2) : "memory");
#pragma unroll
                for (int i = 0; i < 8; i++) ok = ok && l[i];
                if (__all_sync(0xffffffffu, ok)) break;
                if (++n > 2000000) __trap();
            }
#pragma unroll
            for (int i = 0; i < 8; i++) {
                const int t = h * 1024 + i * 128 + t2;
                const uint2 x = lds64(sb + P_X + t * 16 + (b & 1) * 8);
                const float m = blo(l[i]), rs = rcp(bhi(l[i]));
                const uint32_t u0 = pack2(rbf(blo(x.x) - m) * rs, rbf(bhi(x.x) - m) * rs), u1 = pack2(rbf(blo(x.y) - m) * rs, rbf(bhi(x.y) - m) * rs);
                sts128(sb + P_X + t * 16, x.x, x.y, u0, u1);
                const uint32_t o = sb + P_U + ((t >> 3) & 1) * 2176 + ((t >> 4) + 8) * 16 + (t & 7) * 2;
                asm volatile("st.shared.u16 [%0],%1;" ::"r"(o), "h"((uint16_t)u0) : "memory");
                asm volatile("st.shared.u16 [%0],%1;" ::"r"(o + 4352), "h"((uint16_t)(u0 >> 16)) : "memory");
                asm volatile("st.shared.u16 [%0],%1;" ::"r"(o + 8704), "h"((uint16_t)u1) : "memory");
                asm volatile("st.shared.u16 [%0],%1;" ::"r"(o + 13056), "h"((uint16_t)(u1 >> 16)) : "memory");
            }
        }
        PROF(t2 == 0, 3517);
        bar_sync(9, 384);
        fence_async_smem();
#pragma unroll 1
        for (int j = 0; j < 16; j++) {
            const int d = d0 + w - 8;
            asm volatile("{.reg .pred p; elect.sync _|p,0xffffffff; @p cp.async.bulk.global.shared::cta.bulk_group [%0],[%1],%2;}" ::"l"(g_P + (((d >> 5) * 16 + j) * 32 + (d & 31)) * PW),
                         "r"(sb + P_P + ((w - 8) * 2080 + j * 128) * 4), "r"(PW * 4) : "memory");
        }
        asm volatile("cp.async.bulk.commit_group; cp.async.bulk.wait_group 0;" ::: "memory");
        bar_arrive(10, 384);
        return;
    }
#pragma unroll
    for (int i = 0; i < 2; i++) {
        const float dt = rbf(expf(blo(pr.ldt[i])));
        const float ar = -rbf(expf(blo(pr.v[i][0]))) * dt, ai = blo(pr.v[i][1]) * dt;
        sts128(sb + P_PRM + (w * 64 + i * 32 + lane) * 16, __float_as_uint(ar * 1.4426950408889634f), __float_as_uint(ai * 0.15915494309189535f),
               __float_as_uint(2.f * (blo(pr.v[i][2]) * dt)), __float_as_uint(2.f * (blo(pr.v[i][3]) * dt)));
    }
    if (tid < 64) sts128(sb + P_U + (tid >> 3) * 2176 + (tid & 7) * 16, 0, 0, 0, 0);
    bar_arrive(6, 384);
    __syncwarp();
    PROF(tid == 0, 3510);
    const int ch = w & 3, hf = w >> 2;
    {
        float k0[4] = {0, 0, 0, 0}, k1[4] = {0, 0, 0, 0}, k2[4] = {0, 0, 0, 0}, k3[4] = {0, 0, 0, 0}, k4[4] = {0, 0, 0, 0}, kl = 0;
#pragma unroll KGU
        for (int j = 0; j < 16; j++) {
            const uint4 q = lds128(sb + P_PRM + (w * 64 + j * 4 + c) * 16);
            const float cr = __uint_as_float(q.z), ci = __uint_as_float(q.w);
            float wr[4], wi[4], vr[4], vi[4];
            cpow(__uint_as_float(q.x), __uint_as_float(q.y), (float)g, wr[0], wi[0]);
            cpow(__uint_as_float(q.x), __uint_as_float(q.y), (float)(g + 8), vr[0], vi[0]);
#pragma unroll
            for (int i = 1; i < 4; i++) { wr[i] = wr[i - 1]; wi[i] = wi[i - 1]; csq(wr[i], wi[i]); vr[i] = vr[i - 1]; vi[i] = vi[i - 1]; csq(vr[i], vi[i]); }
            float hr = wr[3], hi = wi[3];
            csq(hr, hi);
            mma_tf32(k0, wr[0], vr[0], wi[0], vi[0], cr * hr - ci * hi, -(cr * hi + ci * hr));
            hr = vr[3]; hi = vi[3]; csq(hr, hi);
            mma_tf32(k1, wr[0], vr[0], wi[0], vi[0], cr * hr - ci * hi, -(cr * hi + ci * hr));
            csq(hr, hi);
            mma_tf32(k2, wr[1], vr[1], wi[1], vi[1], cr * hr - ci * hi, -(cr * hi + ci * hr));
            csq(hr, hi);
            mma_tf32(k3, wr[2], vr[2], wi[2], vi[2], cr * hr - ci * hi, -(cr * hi + ci * hr));
            csq(hr, hi);
            mma_tf32(k4, wr[3], vr[3], wi[3], vi[3], cr * hr - ci * hi, -(cr * hi + ci * hr));
            csq(hr, hi);
            kl += cr * hr - ci * hi;
        }
        kl += __shfl_xor_sync(0xffffffffu, kl, 1); kl += __shfl_xor_sync(0xffffffffu, kl, 2);
        const uint32_t o = sb + P_K6 + (ch * 656 + c * 32 + g) * 4, ol = sb + P_K6 + (ch * 656 + 640) * 4;
#define KST(k, base) sts32(o + (base) * 4, __float_as_uint(k[0])); sts32(o + (base) * 4 + 64, __float_as_uint(k[1])); \
                     sts32(o + (base) * 4 + 32, __float_as_uint(k[2])); sts32(o + (base) * 4 + 96, __float_as_uint(k[3]))
#define KAD(k, base) k[0] += __uint_as_float(lds32(o + (base) * 4)); k[1] += __uint_as_float(lds32(o + (base) * 4 + 64)); \
                     k[2] += __uint_as_float(lds32(o + (base) * 4 + 32)); k[3] += __uint_as_float(lds32(o + (base) * 4 + 96))
        if (hf == 0) {
            bar_sync(2 + ch, 64);
            KAD(k0, 0); KAD(k1, 128); KAD(k2, 256); KAD(k3, 384); KAD(k4, 512);
            kl += __uint_as_float(lds32(ol));
            __syncwarp();
        }
        KST(k0, 0); KST(k1, 128); KST(k2, 256); KST(k3, 384); KST(k4, 512);
        if (lane == 0) sts32(ol, __float_as_uint(kl));
        if (hf == 1) { __syncwarp(); bar_arrive(2 + ch, 64); }
    }
    PROF(tid == 0, 3511);
    bar_sync(8, 384);
    PROF(tid == 0, 3512);
    if (tid < 64) sts32(sb + P_P + ((tid >> 4) * 2080 + (tid & 15)) * 4, 0);
#pragma unroll 1
    for (int x = tid; x < 2048; x += 512) {
        uint32_t pw[2][4];
#pragma unroll
        for (int h = 0; h < 2; h++) {
            const int y = x + h * 256;
            const int i0 = y <= 256 ? y : 256 + (int)((pack2((float)y, 0.f) & 0xffff) - 0x4380);
            const int i1 = y <= 256 ? max(y - 1, 0) : 256 + (int)((pack2((float)(y - 1), 0.f) & 0xffff) - 0x4380);
#pragma unroll
            for (int k = 0; k < 4; k++) {
                const float lo = __uint_as_float(lds32(sb + P_K6 + k * 2624 + i0 * 4)), hi = __uint_as_float(lds32(sb + P_K6 + k * 2624 + i1 * 4));
                pw[h][k] = pack2(lo, y ? hi : 0.f);
            }
        }
#pragma unroll
        for (int h = 0; h < 2; h++)
#pragma unroll
            for (int k = 0; k < 4; k++) sts32(sb + P_P + (k * 2080 + x + h * 256 + 16) * 4, pw[h][k]);
    }
    bar_sync(9, 384);
    PROF(tid == 0, 3513);
    {
        float acc[16][4];
#pragma unroll
        for (int j = 0; j < 16; j++) acc[j][0] = acc[j][1] = acc[j][2] = acc[j][3] = 0;
#pragma unroll 1
        for (int e = hf * 4; e < hf * 4 + 4; e++) {
            uint32_t B[16][2];
            const uint32_t ua = sb + P_U + ch * 4352 + ((lane >> 3) & 1) * 2176 + (8 + (lane >> 4) * 8 + (lane & 7) - e) * 16;
#pragma unroll
            for (int j = 0; j < 8; j++) { const uint4 v = ldsm4(ua + j * 256); B[2 * j][0] = v.x; B[2 * j][1] = v.y; B[2 * j + 1][0] = v.z; B[2 * j + 1][1] = v.w; }
            const uint32_t pa = sb + P_P + (ch * 2080 + 16 + e * 16 + g - 2 * c) * 4;
#pragma unroll
            for (int d = 0; d < 16; d++) {
                const uint32_t a0 = lds32(pa + d * 512), a1 = lds32(pa + d * 512 + 32), a2 = lds32(pa + d * 512 - 32);
#pragma unroll
                for (int j = d; j < 16; j++) mma16(acc[j], a0, a1, a2, a0, B[j - d][0], B[j - d][1]);
            }
        }
        PROF(tid == 0, 3514);
        const uint32_t o = sb + P_Y + (ch * 2560 + c * 40 + g) * 4;
#pragma unroll
        for (int j = 0; j < 8; j++) {
#pragma unroll
            for (int i = 0; i < 4; i++) { const float lo = acc[j][i], hi = acc[j + 8][i]; acc[j][i] = hf ? hi : lo; sts32(o + (j + 8 - hf * 8) * 640 + (i & 1) * 80 + (i >> 1) * 32, __float_as_uint(hf ? lo : hi)); }
        }
        bar_sync(2 + ch, 64);
#pragma unroll
        for (int j = 0; j < 8; j++) {
#pragma unroll
            for (int i = 0; i < 4; i++) acc[j][i] += __uint_as_float(lds32(o + (j + hf * 8) * 640 + (i & 1) * 80 + (i >> 1) * 32));
        }
#pragma unroll
        for (int j = 0; j < 8; j++) {
#pragma unroll
            for (int i = 0; i < 4; i++) sts32(o + (j + hf * 8) * 640 + (i & 1) * 80 + (i >> 1) * 32, __float_as_uint(acc[j][i]));
        }
    }
    const uint2 dk = __ldg((const uint2*)(a.Dk + d0));
    bar_sync(1, 256);
#pragma unroll 2
    for (int i = 0; i < 8; i++) {
        const int t = i * 256 + tid;
        const uint32_t o = sb + P_Y + (t + 4 * (t >> 4)) * 4;
        const uint4 xu = lds128(sb + P_X + t * 16);
        float y[4];
#pragma unroll
        for (int k = 0; k < 4; k++) y[k] = rbf(__uint_as_float(lds32(o + k * 10240)));
        uint2 r;
        r.x = pack2(blo(xu.x) + rbf(y[0] + rbf(blo(xu.z) * blo(dk.x))), bhi(xu.x) + rbf(y[1] + rbf(bhi(xu.z) * bhi(dk.x))));
        r.y = pack2(blo(xu.y) + rbf(y[2] + rbf(blo(xu.w) * blo(dk.y))), bhi(xu.y) + rbf(y[3] + rbf(bhi(xu.w) * bhi(dk.y))));
        {
            const bool up = t & 8;
            const uint32_t o = __shfl_xor_sync(0xffffffffu, up ? r.x : r.y, 8);
            ((uint2*)(g_xA[0] + ((t >> 4) * 32 + (d0 >> 4)) * 32 + (t & 7) * 4 + ((d0 >> 1) & 2) + up))[(d0 >> 3) & 1] = up ? make_uint2(o, r.y) : make_uint2(r.x, o);
        }
        if (i == 0) {
            const float e0 = blo(r.x), e1 = bhi(r.x), e2 = blo(r.y), e3 = bhi(r.y);
            asm volatile("red.relaxed.gpu.global.add.v2.f32 [%0],{%1,%2};" ::"l"(g_st[0] + (t >> 7) * 2048 + lds32(sb + S_TAG) * 256 + (b & 1) * 128 + (t & 127)),
                         "f"((e0 + e1) + (e2 + e3)), "f"((e0 * e0 + e1 * e1) + (e2 * e2 + e3 * e3)) : "memory");
        }
    }
    PROF(tid == 0, 3515);
    bar_sync(10, 384);
}

__global__ void __cluster_dims__(2, 1, 1) __launch_bounds__(384, 1) main_kernel(const __grid_constant__ Params p) {
    extern __shared__ __align__(1024) uint8_t smem[];
    const uint32_t sb = __shfl_sync(0xffffffffu, smem_u32(smem), 0);
    uint32_t rank; asm("mov.u32 %0,%%cluster_ctarank;" : "=r"(rank));
    const int wi = __shfl_sync(0xffffffffu, threadIdx.x >> 5, 0);
    const int cl = blockIdx.x >> 1, wg = wi >> 2;
    const bool rec = p.rec0 >= 0 && cl >= p.rec0 && cl < p.rec0 + 32;
    PROF(threadIdx.x == 0, 3500);
    ProRegs pr;
    prologue_load(p.pa, max((int)blockIdx.x - 4, 0), pr);
    if (rec) rec_init(p, sb, cl - p.rec0, rank); else bulk_init(sb);
    if (threadIdx.x == 352 && p.dopro && cl >= 2) {
        mbar_init(sb + S_XBAR, 1);
        asm volatile("fence.mbarrier_init.release.cluster;" ::: "memory");
        mbar_expect(sb + S_XBAR, 32768);
        for (int j = 0; j < 8; j++) tma2d(sb + P_X + j * 4096, &p.tm[3], ((blockIdx.x - 4) >> 1) * 8, j * 256, sb + S_XBAR);
    }
    if (threadIdx.x == 320) {
        unsigned v;
        asm volatile("ld.relaxed.gpu.global.u32 %0,[%1];" : "=r"(v) : "l"(g_gate) : "memory");
        v = v / (4 * NCL) + p.dopro;
        sts64(sb + S_GATE, v * (4 * NCL), v & 1);
    }
    __syncwarp();
    asm volatile("barrier.cluster.arrive.relaxed.aligned;" ::: "memory");
    if (wg == 2) bar_arrive(8, 384);
    if (p.dopro && cl >= 2) prologue(p.pa, sb, blockIdx.x - 4, wi, pr); else if (wg < 2) bar_sync(8, 384);
    asm volatile("barrier.cluster.wait.aligned;" ::: "memory");
    fence_async_smem();
    bar_sync(wg == 2 ? 7 : 1, wg == 2 ? 128 : 256);
    if (p.dopro && (threadIdx.x == 32 || threadIdx.x == 352)) red_release(g_gate, 1);
    if (rec) {
        if (threadIdx.x == 0) {
            rec_fetch(&p.tm[1], sb + R_STK, (cl - p.rec0) * 128, rank * 256, 2, sb + R_BAR + RB_INIT * 8);
            rec_fetch(&p.tm[2], sb + R_STV, (cl - p.rec0) * 128, rank * 256, 2, sb + R_BAR + RB_INIT * 8);
        }
    }
    PROF(threadIdx.x == 0, 3506);
    __syncwarp();
    if (rec) {
        const int head = cl - p.rec0;
        if (wg == 2) {
            reg_dec<RH>();
            const int w = wi & 3;
            if (threadIdx.x == 256) rec_fetch(&p.tm[0], sb + R_STQ, head * 128, rank * 256, 2, sb + R_BAR + RB_INIT * 8);
            __syncwarp();
            wait_cnt_warp(g_gate, lds32(sb + S_GATE));
            if (p.dostats) x1_stats((head * 2 + rank) * 4 + w);
            __syncthreads();
            cluster_sync();
            if ((p.chains >> (w >> 1)) & 1) rec_attn(p, sb, w >> 1, w & 1, head, rank);
        } else {
            reg_inc<RW0>();
            rec_weights(p, sb, head, rank, wi);
        }
    } else {
        if (wg == 2) {
            reg_dec<40>();
            const int w = wi & 3;
            if (w == 0) bulk_producer(p, sb, cl, rank); else if (w >= 2) bulk_release(p, sb, cl, rank, w - 2); else bulk_relay(p, sb, cl);
        } else { reg_inc<232>(); bulk_consumer(p, sb, cl, rank, wi); }
    }
    __syncwarp();
    cluster_sync();
}

typedef CUresult (*EncFn)(CUtensorMap*, CUtensorMapDataType, cuuint32_t, void*, const cuuint64_t*, const cuuint64_t*, const cuuint32_t*, const cuuint32_t*,
                          CUtensorMapInterleave, CUtensorMapSwizzle, CUtensorMapL2promotion, CUtensorMapFloatOOBfill);
inline uint32_t mk(int type, int layer, int ch, int a, int b, int c) { return type | (layer << 3) | (ch << 4) | (a << 8) | (b << 16) | ((uint32_t)c << 24); }
constexpr int SMEM_BYTES = 232448;

struct Sched {
    Params* P; int n[NCL];
    void clear() { memset(P->task, 0, sizeof(P->task)); memset(n, 0, sizeof(n)); }
    void add(int cl, uint32_t t) { if (n[cl] < MAXT - 1) P->task[cl][n[cl]++] = t; }
};

constexpr int REC0 = 4;
struct Cfg { int LAG, TS1, TS2, DQU, DQO, DUN, DHN, MARG, NQ1, FAST0, n0, oc, fc, nuns, ns2, nhg, hs, osl, nfin; };
#define PLAN 13, 2300, 2800, 2400, 1300, 5800, 380, 0, 4, 0, 8, 4, 13, 6, 8, 8, 4000, 0, 0
Cfg g_cfg = {PLAN};
double g_est;
bool g_planned = false;
struct Plan { uint32_t w[NCL][MAXT]; int n[NCL]; double end, rec; };
void simulate(Plan& L, int nc, const Cfg& C) {
    const int LAG = C.LAG, NQ1 = C.NQ1, FAST0 = C.FAST0, n0 = C.n0, oc = C.oc, fc = C.fc, nuns = C.nuns, ns2 = C.ns2, nhg = C.nhg;
    const double TS1 = C.TS1, TS2 = C.TS2, DQU = C.DQU, DQO = C.DQO, DUN = C.DUN, DHN = C.DHN, MARG = C.MARG, hs = C.hs;
    const double INF = 1e18, DKB = 600, DOV = 700, DH = DHN, DHO = 1100, DF = 2200, DFB = 200, POLL = 450, FILL = 500, PUB = 600;
    enum { Q0, O0, Q1, HB, O1, FI, NK };
    struct Grp { int n, left; double done; } G[NK][16];
    double fr[NCL], it[100] = {}, cv[16];
    int ns[16], last[2][NCL], uc = 0, nit = 0;
    memset(L.n, 0, sizeof(L.n)); L.end = 0;
    auto fast = [&](int c) { return c < FAST0 || c >= fc; };
    for (int c = 0; c < 16; c++) {
        ns[c] = c < nuns ? 1 : c == 15 ? 16 : c == 14 ? 8 : ns2;
        const int cnt[NK] = {c < 2 ? 48 : (c & 1) ? 0 : 96, c < oc ? 8 : OPS1, c == 15 ? 24 : fast(c) ? 16 : 48 / NQ1, c >= 2 && !(c & 1) ? 16 : 0, ns[c], c < C.nfin || ns[c] == 1 ? 0 : c >= 14 ? 8 : 4};
        for (int k = 0; k < NK; k++) G[k][c] = {cnt[k], cnt[k], 0};
        cv[c] = INF;
    }
    for (int i = 0; i < nc; i++) { fr[i] = 0; last[0][i] = last[1][i] = -1; }
    auto fin = [&](int k, int c) { if ((k == Q0 && c >= 2) || k == HB) c &= ~1; return G[k][c].left ? INF : G[k][c].done; };
    auto len = [&](int i) { return (i >= LAG && i < 64) ? (double)TS2 : (double)TS1; };
    auto end_it = [&](int i) { return i < nit ? it[i] + len(i) : INF; };
    auto nominal = [&](int i) { if (i < nit) return it[i]; double t = nit ? it[nit - 1] : 11000 - TS1; for (int j = nit - 1; j < i; j++) t += len(j); return t; };
    auto put = [&](int i, uint32_t w) { if (L.n[i] < MAXT - 4) L.w[i][L.n[i]++] = w; else L.end = INF; };
    auto rel = [&](int k, int c) {
        switch (k) {
            case Q0: return 0.0;
            case O0: return end_it(4 * c + 3) + PUB + POLL;
            case Q1: return cv[c] + POLL;
            case HB: return cv[c - 2] + 600 + POLL;
            case O1: return fmax(end_it(LAG + 4 * c + 3) + PUB + POLL, G[O1][c].left == 1 && !G[FI][c].n ? G[O1][c].done - DKB * 64 / ns[c] : 0);
            default: return fin(O1, c) + POLL;
        }
    };
    auto dur = [&](int k, int c) {
        switch (k) {
            case Q0: return DQO + (c < 2 ? 2.0 : 1.0) * DQU;
            case O0: return (16 - G[O0][c].n) * DKB + 1200;
            case HB: return DHO + DH * c;
            case Q1: return DQO + 48.0 / G[Q1][c].n * DQU;
            case O1: return DOV + DKB * 64 / ns[c] + (G[O1][c].left == 1 && !G[FI][c].n ? 700 + 800 * ns[c] : 0);
            default: return DF + DFB * ns[c] * (c >= 14 ? 0.5 : 1);
        }
    };
    auto o0_est = [&](int c) {
        double t = uc ? cv[uc - 1] - 900 : 0;
        for (int j = uc; j < c; j++) t = fmax(t, nominal(4 * j + 4) + PUB + POLL + FILL) + dur(O0, j) + DUN;
        return fmax(t, nominal(4 * c + 4) + PUB + POLL);
    };
    auto cv_est = [&](int c) { return c < uc ? cv[c] : o0_est(c) + FILL + dur(O0, c) + DUN + 900; };
    auto slot = [&](int k, int c, int i) { return k == O0 ? (i < 8 ? i : nc + 7 - i) : c == 15 ? i : i - 8; };
    while (true) {
        while (nit < 64 + LAG) {
            double t = nit ? end_it(nit - 1) : 0;
            if (nit < 64) t = fmax(t, fin(Q0, nit >> 2) + POLL);
            if (nit >= LAG) t = fmax(t, fin(Q1, (nit - LAG) >> 2) + (nit < 64 ? 0 : POLL));
            if (t >= INF) break;
            it[nit++] = t;
        }
        int i = -1;
        for (int j = 0; j < nc; j++) if (fr[j] < INF && (i < 0 || fr[j] < fr[i])) i = j;
        if (i < 0) break;
        const double t = fr[i];
        double lim = INF;
        if (i < 8 && last[0][i] == uc) {
            if (G[O0][uc].left || fin(HB, uc) >= INF) { fr[i] = t + 200; continue; }
            const double e = fmax(G[O0][uc].done, fin(HB, uc) - 2000) + DUN;
            for (int j = 0; j < 8; j++) { put(j, mk(T_CV, 0, uc, 2 * j, G[O0][uc].n, 0)); fr[j] = e; }
            cv[uc++] = e + 900;
            continue;
        }
        const bool hg = (unsigned)(i - 24) < (unsigned)nhg;
        double hlim = INF;
        for (int c = 2; c < 16 && hg; c++) if (G[HB][c].left) { hlim = cv_est(c - 2) + hs; break; }
        int mine[2] = {-1, -1};
        for (int k = 0; k < 2; k++)
            for (int c = last[k][i] + 1; c < 16 && mine[k] < 0; c++) if ((unsigned)slot(O0 + k, c, i) < (unsigned)G[O0 + k][c].n) mine[k] = c;
        if (mine[0] >= 0) lim = i < 8 ? o0_est(mine[0]) - (uc ? 0 : 8500) : nominal(4 * mine[0] + 4) + PUB + C.osl;
        else if (mine[1] >= 0) lim = cv_est(mine[1]) + POLL;
        else if (i < 16 && G[O1][15].left) lim = fmin(lim, nominal(64 + LAG) + PUB);
        int bk = -1, bc = 0; double bd = INF;
        for (int k = 0; k < NK; k++)
            for (int c = 0; c < 16; c++) {
                const bool urgent = k == O0 || k == Q1 || (k == O1 && c == 15);
                if (!G[k][c].left || ((k == O0 || k == Q1) && c != mine[k - O0]) || (k == O1 && c == 15 && i >= 16)) continue;
                if (rel(k, c) > t || (t + dur(k, c) + (k == Q0 && c >= 2 ? DQU : 0) > lim && !urgent)) continue;
                if (i < 8 && uc && uc < 16 && k != O0) continue;
                if ((k == HB && !hg && i < nc - 2) || (k != HB && !urgent && t + dur(k, c) + (k == Q0 && c >= 2 ? DQU : 0) > hlim)) continue;
                const double dl = urgent ? -INF : k == HB ? -INF / 2 : k == Q0 ? nominal(4 * c) - 3000 : 1e9 + c * 2 + (k == O1);
                if (dl < bd) { bd = dl; bk = k; bc = c; }
            }
        if (bk < 0) {
            bool any = i < 8 && uc < 16;
            for (int k = 0; k < NK; k++) for (int c = 0; c < 16; c++) any = any || G[k][c].left;
            fr[i] = any ? t + 200 : INF;
            if (t > 400000) { L.end = INF; return; }
            continue;
        }
        Grp& g = G[bk][bc];
        const int n = g.n - g.left, c = bc;
        int nu = 1;
        double d = dur(bk, c);
        if (bk == Q0) for (nu = c < 2 ? 2 : 1; c >= 2 && nu < g.left && (nu < 2 || (nu < n0 && t + d + DQU < fmin(fmin(lim, hlim), bd - MARG))); nu++) d += DQU;
        if (bk == O0 && i >= 8) d += (g.n - 8) * DKB;
        if (bk == Q0 && !c && n >= 32) { nu = 1; d -= DQU; }
        if (bk == O0 || bk == Q1) last[bk - O0][i] = c;
        if (bk == O0 && !c && i < 8) put(i, mk(T_CV, 0, 3, 2 * i, 0, 128));
        g.left -= nu;
        const bool fini = bk == O1 && !g.left && !G[FI][c].n;
        const double e = fmax(fmax(t, rel(bk, c) + FILL) + (t < 1 ? 3500 : 0) + d, fini ? g.done + POLL + 700 + 800 * ns[c] : 0);
        fr[i] = e;
        g.done = fmax(g.done, e + (bk == O1 ? 1900 : bk == O0 ? 0 : (bk == Q1 && g.n < 24) || (bk == Q0 && !c && nu == 2) ? -500 : 1000));
        if (bk == FI || fini) L.end = fmax(L.end, e);
        put(i, bk == Q0 ? (c == 0 ? mk(T_QKV, 0, 0, n < 32 ? n : 2 * n - 32, nu, 32) : c == 1 ? mk(T_QKV, 0, c, n, 2, 24) : mk(T_QKV, 0, c, n, nu, 64))
             : bk == O0 ? (i < 8 ? mk(T_OP, 0, c, i * (16 - g.n), 16 - g.n, i) : mk(T_OP, 0, c, 64 - (nc - i) * 8, 8, slot(O0, c, i)))
             : bk == HB ? mk(T_CV, 1, c, 2 * n, 0, 0)
             : bk == Q1 ? mk(T_QKV, 1, c, slot(Q1, c, i) * 2, 48 / g.n, g.n)
             : bk == O1 ? mk(T_OP, 1, c, n * 64 / ns[c], 64 / ns[c], n + (fini ? 32 : 0))
                        : mk(T_FIN, 1, c, n * (32 / g.n), ns[c], 16 / g.n));
    }
    L.rec = end_it(63 + LAG);
}
void plan(Params& P) {
    P.rec0 = REC0; P.chains = 3; P.lag = g_cfg.LAG; P.dostats = 1; P.dopro = 1;
    static Plan L;
    int cls[NCL], nc = 0;
    for (int c = REC0 + 32; c < NCL; c++) cls[nc++] = c;
    for (int c = REC0 - 1; c >= 0; c--) cls[nc++] = c;
    simulate(L, nc, g_cfg);
    g_est = L.end;
    Sched S; S.P = &P; S.clear();
    S.add(0, mk(T_QKV, 1, 15, 0, 2, 128 + 24)); S.add(0, mk(T_OP, 1, 15, 0, 4, 128));
    S.add(1, mk(T_CV, 0, 3, 0, 0, 128));
    for (int i = 0; i < nc; i++) {
        bool warm = false;
        for (int k = 0; k < L.n[i]; k++) {
            if (!warm && k + 1 < L.n[i] && (L.w[i][k + 1] & 255) == (mk(T_FIN, 1, 15, 0, 0, 0) & 255)) { S.add(cls[i], L.w[i][k + 1] | 0x80000000u); warm = true; }
            S.add(cls[i], L.w[i][k]);
            if ((L.w[i][k] & 7) == T_FIN) warm = true;
        }
    }
}

#define TK0() do {} while (0)
#define TK() do { P.e0 = (P.chains & 1) ? 64 : 0; P.b1 = (P.chains & 2) ? P.lag : 1000; P.nit = (P.chains & 2) ? P.lag + 64 : 64; TK0(); } while (0)
}

extern "C" void kernel_launch(void* const* d_in, const int* in_sizes, int n_in, void* d_out, int out_size) {
    typedef const __nv_bfloat16* BP;
    static EncFn enc = nullptr;
    if (!enc) {
        void* fn = nullptr; cudaDriverEntryPointQueryResult qr;
        cudaGetDriverEntryPoint("cuTensorMapEncodeTiled", &fn, cudaEnableDefault, &qr);
        enc = (EncFn)fn;
        cudaFuncSetAttribute(main_kernel, cudaFuncAttributeMaxDynamicSharedMemorySize, SMEM_BYTES);
    }
    static Params P;
    for (int i = 0; i < 4; i++) {
        const cuuint64_t cols = i < 3 ? 4096 : 512, rows = i < 3 ? 512 : 4096;
        cuuint64_t d2[2] = {cols, rows}, d3[3] = {64, rows, cols / 64}, str[2] = {cols * 2, 128};
        cuuint32_t box[3] = {64, 64, 4}, es[3] = {1, 1, 1};
        enc(&P.tm[i < 3 ? i : 4], CU_TENSOR_MAP_DATA_TYPE_BFLOAT16, 2, d_in[9 + i], d2, str, box, es, CU_TENSOR_MAP_INTERLEAVE_NONE, CU_TENSOR_MAP_SWIZZLE_128B,
                       CU_TENSOR_MAP_L2_PROMOTION_L2_128B, CU_TENSOR_MAP_FLOAT_OOB_FILL_NONE);
        for (int m = 0; m < 2; m++) {
            cuuint32_t box3[3] = {64, 32, m ? 2u : 4u};
            enc(&P.t3[m][i], CU_TENSOR_MAP_DATA_TYPE_BFLOAT16, 3, d_in[9 + i], d3, str, box3, es, CU_TENSOR_MAP_INTERLEAVE_NONE, CU_TENSOR_MAP_SWIZZLE_128B,
                CU_TENSOR_MAP_L2_PROMOTION_L2_128B, CU_TENSOR_MAP_FLOAT_OOB_FILL_NONE);
        }
    }
    {
        cuuint64_t dims[2] = {512, 2048}, str[1] = {1024};
        cuuint32_t box[2] = {8, 256}, es[2] = {1, 1};
        enc(&P.tm[3], CU_TENSOR_MAP_DATA_TYPE_BFLOAT16, 2, d_in[0], dims, str, box, es, CU_TENSOR_MAP_INTERLEAVE_NONE, CU_TENSOR_MAP_SWIZZLE_NONE,
            CU_TENSOR_MAP_L2_PROMOTION_NONE, CU_TENSOR_MAP_FLOAT_OOB_FILL_NONE);
    }
    for (int m = 0; m < 2; m++) {
        void* ga; cudaGetSymbolAddress(&ga, g_A);
        cuuint64_t dims[2] = {512, sizeof(AOps) / 1024}, str[1] = {1024};
        cuuint32_t box[2] = {256, m ? 16u : 8u}, es[2] = {1, 1};
        enc(&P.ta[m], CU_TENSOR_MAP_DATA_TYPE_BFLOAT16, 2, ga, dims, str, box, es, CU_TENSOR_MAP_INTERLEAVE_NONE, CU_TENSOR_MAP_SWIZZLE_NONE,
            CU_TENSOR_MAP_L2_PROMOTION_L2_128B, CU_TENSOR_MAP_FLOAT_OOB_FILL_NONE);
    }
    P.mem0 = (BP)d_in[8]; P.Wo = (BP)d_in[12]; P.Dskip = (BP)d_in[6]; P.out = (__nv_bfloat16*)d_out;
    cudaStream_t s = cudaStreamPerThread;
    P.pa = {(BP)d_in[0], (BP)d_in[1], (BP)d_in[2], (BP)d_in[3], (BP)d_in[4], (BP)d_in[5], (BP)d_in[6], (BP)d_in[9], (BP)d_in[10], (BP)d_in[11], (BP)d_in[12], (BP)d_in[8]};
    if (!g_planned) { plan(P); g_planned = true; }
    TK(); main_kernel<<<2 * NCL, 384, SMEM_BYTES, s>>>(P); TK();
}
```

```cpp
#include <cuda_runtime.h>
#include <cuda_bf16.h>
#include <cuda.h>
#include <stdint.h>
#include <string.h>
#include <math.h>

namespace {

constexpr int NCL = 66;
constexpr int MAXT = 64;
#define PFC 1
#define QB1 2
#define QB2 4
#define QB3 6
#define LAGQ 2
#define CPOS 2
#define OPS1N 10
constexpr int OPS1 = OPS1N;
constexpr int MAXSPLIT = 16;
constexpr int PW = 144;

struct AOps { uint4 x[2][16 * 8 * 1024], o[2][16 * 64 * 1024]; };
__device__ AOps g_A;
#define g_xA g_A.x
#define g_o g_A.o
__device__ float2 g_st[2][16 * 2048];
__device__ float2 g_st2[2 * 16 * 128];
__device__ uint4 g_qkv[2][64 * 64 * 768];
__device__ uint4 g_pp[2][16 * MAXSPLIT * 8192];
__device__ uint4 g_acc[7 * 2048];
__device__ unsigned g_gate[32];
__device__ uint32_t g_P[16 * 16 * 32 * PW];
__device__ uint4 g_u[16 * 16 * 512];
__device__ float4 g_carry[2][17 * 16 * 4 * 256];
__device__ unsigned g_cnt[13 * 64];
__device__ uint32_t g_ln0[2048];

enum { C_QKV0 = 0, C_QKV1 = 1  , C_O0 = 2, C_O1 = 3, C_U = 4, C_OP1 = 5, C_CV = 6, C_ST = 7, C_H = 8, C_OP0 = 9   };
__device__ __forceinline__ unsigned* cnt_ptr(int kind, int chunk) { return g_cnt + kind * 64 + chunk; }

enum { T_END = 0, T_QKV = 1, T_OP = 2, T_CV = 3, T_FIN = 4 };
struct ProArgs { const __nv_bfloat16 *x, *lAr, *Ai, *Cr, *Ci, *ldt, *Dk, *Wq, *Wk, *Wv, *Wo, *mem0; };
struct Params {
    CUtensorMap tm[5];
    CUtensorMap t3[2][4];
    CUtensorMap ta[2];
    ProArgs pa;
    int dopro;
    const __nv_bfloat16* mem0;
    const __nv_bfloat16* Wo;
    const __nv_bfloat16* Dskip;
    __nv_bfloat16* out;
    int rec0;
    int chains;
    int lag;
    int b1, e0, nit;
    int zero, gpit;
    int dostats;
    uint32_t task[NCL][MAXT];
};

__device__ __forceinline__ uint32_t smem_u32(const void* p) { return (uint32_t)__cvta_generic_to_shared(p); }
__device__ __forceinline__ uint32_t mapa(uint32_t a, uint32_t r) {
    uint32_t o; asm("mapa.shared::cluster.u32 %0,%1,%2;" : "=r"(o) : "r"(a), "r"(r)); return o;
}
__device__ __forceinline__ void mbar_init(uint32_t b, int c) { asm volatile("mbarrier.init.shared::cta.b64 [%0],%1;" ::"r"(b), "r"(c) : "memory"); }
__device__ __forceinline__ void mbar_expect(uint32_t b, int bytes) { asm volatile("mbarrier.arrive.expect_tx.shared::cta.b64 _,[%0],%1;" ::"r"(b), "r"(bytes) : "memory"); }
__device__ __forceinline__ void mbar_arrive(uint32_t b) { asm volatile("mbarrier.arrive.shared::cta.b64 _,[%0];" ::"r"(b) : "memory"); }
__device__ __forceinline__ void mbar_arrive_cluster(uint32_t b) { asm volatile("mbarrier.arrive.shared::cluster.b64 _,[%0];" ::"r"(b) : "memory"); }
__device__ __forceinline__ void mbar_arrive1(uint32_t b) { asm volatile("{.reg .pred p; elect.sync _|p,0xffffffff; @p mbarrier.arrive.shared::cta.b64 _,[%0];}" ::"r"(b) : "memory"); }
__device__ __forceinline__ void mbar_arrive1_cluster(uint32_t b) { asm volatile("{.reg .pred p; elect.sync _|p,0xffffffff; @p mbarrier.arrive.shared::cluster.b64 _,[%0];}" ::"r"(b) : "memory"); }
__device__ __forceinline__ void mbar_wait(uint32_t b, uint32_t ph) {
    asm volatile(
        "{.reg .pred p; .reg .u32 n; mov.u32 n,0;\n"
        "W%=: mbarrier.try_wait.parity.shared::cta.b64 p,[%0],%1;\n"
        "@p bra D%=;\n"
        "add.u32 n,n,1; setp.lt.u32 p,n,2000000; @p bra W%=;\n"
        "trap;\n"
        "D%=: }" ::"r"(b), "r"(ph) : "memory");
}
__device__ __forceinline__ bool mbar_test(uint32_t b, uint32_t ph) {
    uint32_t ok;
    asm volatile("{.reg .pred p; mbarrier.test_wait.parity.shared::cta.b64 p,[%1],%2; selp.u32 %0,1,0,p;}" : "=r"(ok) : "r"(b), "r"(ph) : "memory");
    return ok;
}
__device__ __forceinline__ bool wait_lds128(uint32_t b, uint32_t ph, uint32_t a, uint4& v) {
    uint32_t ok;
    asm volatile("{.reg .pred p; mbarrier.try_wait.parity.shared::cta.b64 p,[%5],%6,20000; ld.shared.v4.u32 {%0,%1,%2,%3},[%7]; selp.u32 %4,1,0,p;}"
                 : "=r"(v.x), "=r"(v.y), "=r"(v.z), "=r"(v.w), "=r"(ok) : "r"(b), "r"(ph), "r"(a) : "memory");
    return ok;
}
__device__ __forceinline__ bool wait_lds64(uint32_t b, uint32_t ph, uint32_t a, uint2& v) {
    uint32_t ok;
    asm volatile("{.reg .pred p; mbarrier.try_wait.parity.shared::cta.b64 p,[%3],%4,20000; ld.shared.v2.u32 {%0,%1},[%5]; selp.u32 %2,1,0,p;}"
                 : "=r"(v.x), "=r"(v.y), "=r"(ok) : "r"(b), "r"(ph), "r"(a) : "memory");
    return ok;
}
template <int PH> __device__ __forceinline__ void mbar_wait_c(uint32_t b) {
    asm volatile(
        "{.reg .pred p; .reg .u32 n; mov.u32 n,%2;\n"
        "W%=: mbarrier.try_wait.parity.shared::cta.b64 p,[%0],%1;\n"
        "@p bra D%=;\n"
        "add.u32 n,n,1; setp.lt.u32 p,n,2000000; @p bra W%=;\n"
        "trap;\n"
        "D%=: }" ::"r"(b), "n"(PH), "n"(PH) : "memory");
}
__device__ __forceinline__ void bar_sync(int id, int n) { asm volatile("bar.sync %0,%1;" ::"r"(id), "r"(n) : "memory"); }
__device__ __forceinline__ void bar_arrive(int id, int n) { asm volatile("bar.arrive %0,%1;" ::"r"(id), "r"(n) : "memory"); }
__device__ __forceinline__ void cluster_sync() { asm volatile("barrier.cluster.arrive.relaxed.aligned; barrier.cluster.wait.aligned;" ::: "memory"); }
__device__ __forceinline__ void fence_async() { asm volatile("fence.proxy.async;" ::: "memory"); }
__device__ __forceinline__ void fence_async_smem() { asm volatile("fence.proxy.async.shared::cta;" ::: "memory"); }
#define EFR 1
#define EFW 2
constexpr uint64_t POL_N = 0x1000000000000000ull, POL_F = 0x12F0000000000000ull;
constexpr uint64_t POL_LAST = EFR ? POL_F : POL_N  , POL_LATE = EFW ? POL_F : POL_N  , POL_SOON = EFW > 1 ? POL_F : POL_N;
__device__ __forceinline__ void bulk_g2s(uint32_t dst, const void* src, int bytes, uint32_t bar, uint64_t pol) {
    asm volatile("cp.async.bulk.shared::cluster.global.mbarrier::complete_tx::bytes.L2::cache_hint [%0],[%1],%2,[%3],%4;" ::"r"(dst), "l"(src), "r"(bytes), "r"(bar), "l"(pol) : "memory");
}
__device__ __forceinline__ void bulk_g2s_mc(uint32_t dst, const void* src, int bytes, uint32_t bar, uint64_t pol) {
    asm volatile("cp.async.bulk.shared::cluster.global.mbarrier::complete_tx::bytes.multicast::cluster.L2::cache_hint [%0],[%1],%2,[%3],%4,%5;" ::"r"(dst), "l"(src), "r"(bytes), "r"(bar), "h"((uint16_t)3), "l"(pol) : "memory");
}
__device__ __forceinline__ void bulk_s2s(uint32_t dst, uint32_t src, int bytes, uint32_t bar) {
    asm volatile("cp.async.bulk.shared::cluster.shared::cta.mbarrier::complete_tx::bytes [%0],[%1],%2,[%3];" ::"r"(dst), "r"(src), "r"(bytes), "r"(bar) : "memory");
}
__device__ __forceinline__ bool elect() {
    uint32_t r; asm volatile("{.reg .pred p; elect.sync _|p,0xffffffff; selp.u32 %0,1,0,p;}" : "=r"(r)); return r;
}
__device__ __forceinline__ void stg128(uint4* p, uint4 v, uint64_t pol) {
    asm volatile("st.global.L2::cache_hint.v4.u32 [%0],{%1,%2,%3,%4},%5;" ::"l"(p), "r"(v.x), "r"(v.y), "r"(v.z), "r"(v.w), "l"(pol));
}
__device__ __forceinline__ void stg32(uint32_t* p, uint32_t v, uint64_t pol) { asm volatile("st.global.L2::cache_hint.u32 [%0],%1,%2;" ::"l"(p), "r"(v), "l"(pol)); }
__device__ __forceinline__ uint4 ldcg128_last(const uint4* p) {
    uint4 v; asm volatile("ld.global.cg.L2::cache_hint.v4.u32 {%0,%1,%2,%3},[%4],%5;" : "=r"(v.x), "=r"(v.y), "=r"(v.z), "=r"(v.w) : "l"(p), "l"(POL_LAST) : "memory"); return v;
}
__device__ __forceinline__ void tma2d(uint32_t dst, const CUtensorMap* tm, int x, int y, uint32_t bar) {
    asm volatile("cp.async.bulk.tensor.2d.shared::cluster.global.mbarrier::complete_tx::bytes [%0],[%1,{%2,%3}],[%4];" ::"r"(dst), "l"(tm), "r"(x), "r"(y), "r"(bar) : "memory");
}
__device__ __forceinline__ void tma3d_mc(uint32_t dst, const CUtensorMap* tm, int y, int z, uint32_t bar, uint16_t mask) {
    asm volatile("{.reg .pred p; elect.sync _|p,0xffffffff;\n"
                 "@p cp.async.bulk.tensor.3d.shared::cluster.global.mbarrier::complete_tx::bytes.multicast::cluster [%0],[%1,{0,%2,%3}],[%4],%5;}"
                 ::"r"(dst), "l"(tm), "r"(y), "r"(z), "r"(bar), "h"(mask) : "memory");
}
__device__ __forceinline__ void tma2d_mc(uint32_t dst, const CUtensorMap* tm, int x, int y, uint32_t bar, uint16_t mask, uint64_t pol) {
    asm volatile("{.reg .pred p; elect.sync _|p,0xffffffff;\n"
                 "@p cp.async.bulk.tensor.2d.shared::cluster.global.mbarrier::complete_tx::bytes.multicast::cluster.L2::cache_hint [%0],[%1,{%2,%3}],[%4],%5,%6;}"
                 ::"r"(dst), "l"(tm), "r"(x), "r"(y), "r"(bar), "h"(mask), "l"(pol) : "memory");
}
__device__ __forceinline__ void bulk_g2s1(uint32_t dst, const void* src, int bytes, uint32_t bar, uint64_t pol) {
    asm volatile("{.reg .pred p; elect.sync _|p,0xffffffff;\n"
                 "@p cp.async.bulk.shared::cluster.global.mbarrier::complete_tx::bytes.L2::cache_hint [%0],[%1],%2,[%3],%4;}" ::"r"(dst), "l"(src), "r"(bytes), "r"(bar), "l"(pol) : "memory");
}
__device__ __forceinline__ void mbar_expect1(uint32_t b, int bytes) {
    asm volatile("{.reg .pred p; elect.sync _|p,0xffffffff; @p mbarrier.arrive.expect_tx.shared::cta.b64 _,[%0],%1;}" ::"r"(b), "r"(bytes) : "memory");
}
__device__ __forceinline__ void st_async4(uint32_t a, uint32_t x, uint32_t y, uint32_t z, uint32_t w, uint32_t mb) {
    asm volatile("st.async.shared::cluster.mbarrier::complete_tx::bytes.v4.b32 [%0],{%1,%2,%3,%4},[%5];" ::"r"(a), "r"(x), "r"(y), "r"(z), "r"(w), "r"(mb) : "memory");
}
__device__ __forceinline__ void st_async2(uint32_t a, uint32_t x, uint32_t y, uint32_t mb) {
    asm volatile("st.async.shared::cluster.mbarrier::complete_tx::bytes.v2.b32 [%0],{%1,%2},[%3];" ::"r"(a), "r"(x), "r"(y), "r"(mb) : "memory");
}
#define LDSQ "ld.shared"
__device__ __forceinline__ uint4 lds128(uint32_t a) { uint4 v; asm volatile(LDSQ ".v4.u32 {%0,%1,%2,%3},[%4];" : "=r"(v.x), "=r"(v.y), "=r"(v.z), "=r"(v.w) : "r"(a) : "memory"); return v; }
__device__ __forceinline__ uint2 lds64(uint32_t a) { uint2 v; asm volatile(LDSQ ".v2.u32 {%0,%1},[%2];" : "=r"(v.x), "=r"(v.y) : "r"(a) : "memory"); return v; }
__device__ __forceinline__ uint32_t lds32(uint32_t a) { uint32_t v; asm volatile(LDSQ ".u32 %0,[%1];" : "=r"(v) : "r"(a) : "memory"); return v; }
__device__ __forceinline__ void sts128(uint32_t a, uint32_t x, uint32_t y, uint32_t z, uint32_t w) { asm volatile("st.shared.v4.u32 [%0],{%1,%2,%3,%4};" ::"r"(a), "r"(x), "r"(y), "r"(z), "r"(w) : "memory"); }
__device__ __forceinline__ void sts64(uint32_t a, uint32_t x, uint32_t y) { asm volatile("st.shared.v2.u32 [%0],{%1,%2};" ::"r"(a), "r"(x), "r"(y) : "memory"); }
__device__ __forceinline__ void sts32(uint32_t a, uint32_t x) { asm volatile("st.shared.u32 [%0],%1;" ::"r"(a), "r"(x) : "memory"); }
__device__ __forceinline__ uint4 ldsm4(uint32_t a) { uint4 v; asm volatile("ldmatrix.sync.aligned.m8n8.x4.shared.b16 {%0,%1,%2,%3},[%4];" : "=r"(v.x), "=r"(v.y), "=r"(v.z), "=r"(v.w) : "r"(a) : "memory"); return v; }
__device__ __forceinline__ uint4 ldsm4t(uint32_t a) { uint4 v; asm volatile("ldmatrix.sync.aligned.m8n8.x4.trans.shared.b16 {%0,%1,%2,%3},[%4];" : "=r"(v.x), "=r"(v.y), "=r"(v.z), "=r"(v.w) : "r"(a) : "memory"); return v; }
__device__ __forceinline__ uint32_t movm(uint32_t a) { uint32_t d; asm volatile("movmatrix.sync.aligned.m8n8.trans.b16 %0,%1;" : "=r"(d) : "r"(a)); return d; }
__device__ __forceinline__ uint32_t pack2(float lo, float hi) { uint32_t d; asm("cvt.rn.bf16x2.f32 %0,%1,%2;" : "=r"(d) : "f"(hi), "f"(lo)); return d; }
__device__ __forceinline__ uint32_t hadd2(uint32_t a, uint32_t b) { uint32_t d; asm("add.rn.bf16x2 %0,%1,%2;" : "=r"(d) : "r"(a), "r"(b)); return d; }
__device__ __forceinline__ float blo(uint32_t v) { return __uint_as_float(v << 16); }
__device__ __forceinline__ float bhi(uint32_t v) { return __uint_as_float(v & 0xffff0000u); }
__device__ __forceinline__ float rbf(float x) { return __uint_as_float(pack2(0.f, x)); }
__device__ __forceinline__ float ex2(float x) { float y; asm("ex2.approx.ftz.f32 %0,%1;" : "=f"(y) : "f"(x)); return y; }
__device__ __forceinline__ float rcp(float x) { float y; asm("rcp.approx.ftz.f32 %0,%1;" : "=f"(y) : "f"(x)); return y; }
__device__ __forceinline__ void mma16(float* c, uint32_t a0, uint32_t a1, uint32_t a2, uint32_t a3, uint32_t b0, uint32_t b1) {
    asm volatile("mma.sync.aligned.m16n8k16.row.col.f32.bf16.bf16.f32 {%0,%1,%2,%3},{%4,%5,%6,%7},{%8,%9},{%0,%1,%2,%3};"
                 : "+f"(c[0]), "+f"(c[1]), "+f"(c[2]), "+f"(c[3]) : "r"(a0), "r"(a1), "r"(a2), "r"(a3), "r"(b0), "r"(b1));
}
__device__ __forceinline__ void mma8(float* c, uint32_t a0, uint32_t a1, uint32_t b0) {
    asm volatile("mma.sync.aligned.m16n8k8.row.col.f32.bf16.bf16.f32 {%0,%1,%2,%3},{%4,%5},{%6},{%0,%1,%2,%3};"
                 : "+f"(c[0]), "+f"(c[1]), "+f"(c[2]), "+f"(c[3]) : "r"(a0), "r"(a1), "r"(b0));
}
__device__ __forceinline__ uint4 ld_rlx128(const uint4* p) {
    uint4 v;
    asm volatile("{.reg .b128 t; ld.relaxed.gpu.global.b128 t,[%4]; mov.b128 {%0,%1,%2,%3},t;}" : "=r"(v.x), "=r"(v.y), "=r"(v.z), "=r"(v.w) : "l"(p) : "memory");
    return v;
}
__device__ __forceinline__ void st_rlx128(uint4* p, uint32_t x, uint32_t y, uint32_t z, uint32_t w) {
    asm volatile("{.reg .b128 t; mov.b128 t,{%1,%2,%3,%4}; st.relaxed.gpu.global.b128 [%0],t;}" ::"l"(p), "r"(x), "r"(y), "r"(z), "r"(w) : "memory");
}
__device__ __forceinline__ uint4 ldcg128(const uint4* p) { uint4 v; asm volatile("ld.global.cg.v4.u32 {%0,%1,%2,%3},[%4];" : "=r"(v.x), "=r"(v.y), "=r"(v.z), "=r"(v.w) : "l"(p) : "memory"); return v; }
__device__ __forceinline__ void red_release(unsigned* p, unsigned v) {
    asm volatile("fence.proxy.async; red.relaxed.gpu.global.add.u32 [%0],%1;" ::"l"(p), "r"(v) : "memory");
}
__device__ __forceinline__ void wait_cnt(const unsigned* p, unsigned target) {
    unsigned v; int n = 0;
    while (true) {
        asm volatile("ld.acquire.gpu.global.u32 %0,[%1];" : "=r"(v) : "l"(p) : "memory");
        if (v >= target) break;
        if (++n > 3000000) __trap();
        __nanosleep(40);
    }
}
__device__ __forceinline__ void wait_cnt_warp(const unsigned* p, unsigned target) {
    unsigned v; int n = 0;
    while (true) {
        asm volatile("ld.acquire.gpu.global.u32 %0,[%1];" : "=r"(v) : "l"(p) : "memory");
        if (__all_sync(0xffffffffu, v >= target)) break;
        if (++n > 3000000) __trap();
    }
}
__device__ __forceinline__ uint64_t mkdesc(uint32_t addr, uint32_t lbo, uint32_t sbo, uint32_t sw) {
    return (uint64_t)((addr & 0x3FFFF) >> 4) | ((uint64_t)(lbo >> 4) << 16) | ((uint64_t)(sbo >> 4) << 32) | ((uint64_t)sw << 62);
}
__device__ __forceinline__ void wg_fence() { asm volatile("wgmma.fence.sync.aligned;" ::: "memory"); }
__device__ __forceinline__ void wg_commit() { asm volatile("wgmma.commit_group.sync.aligned;" ::: "memory"); }
template <int N> __device__ __forceinline__ void wg_wait() { asm volatile("wgmma.wait_group.sync.aligned %0;" ::"n"(N) : "memory"); }
#define R8(c, o) "+f"(c[o]), "+f"(c[o + 1]), "+f"(c[o + 2]), "+f"(c[o + 3]), "+f"(c[o + 4]), "+f"(c[o + 5]), "+f"(c[o + 6]), "+f"(c[o + 7])
#define R32(c, o) R8(c, o), R8(c, o + 8), R8(c, o + 16), R8(c, o + 24)
#define S32A "%0,%1,%2,%3,%4,%5,%6,%7,%8,%9,%10,%11,%12,%13,%14,%15,%16,%17,%18,%19,%20,%21,%22,%23,%24,%25,%26,%27,%28,%29,%30,%31"
#define S32B ",%32,%33,%34,%35,%36,%37,%38,%39,%40,%41,%42,%43,%44,%45,%46,%47,%48,%49,%50,%51,%52,%53,%54,%55,%56,%57,%58,%59,%60,%61,%62,%63"
#define S32C ",%64,%65,%66,%67,%68,%69,%70,%71,%72,%73,%74,%75,%76,%77,%78,%79,%80,%81,%82,%83,%84,%85,%86,%87,%88,%89,%90,%91,%92,%93,%94,%95"
#define S32D ",%96,%97,%98,%99,%100,%101,%102,%103,%104,%105,%106,%107,%108,%109,%110,%111,%112,%113,%114,%115,%116,%117,%118,%119,%120,%121,%122,%123,%124,%125,%126,%127"
#define W8(c, o) "=f"(c[o]), "=f"(c[o + 1]), "=f"(c[o + 2]), "=f"(c[o + 3]), "=f"(c[o + 4]), "=f"(c[o + 5]), "=f"(c[o + 6]), "=f"(c[o + 7])
#define W32(c, o) W8(c, o), W8(c, o + 8), W8(c, o + 16), W8(c, o + 24)
template <bool ACC> __device__ __forceinline__ void wgmma256(float* c, uint64_t da, uint64_t db) {
    if (ACC) asm volatile("wgmma.mma_async.sync.aligned.m64n256k16.f32.bf16.bf16 {" S32A S32B S32C S32D "},%128,%129,1,1,1,0,1;"
                          : R32(c, 0), R32(c, 32), R32(c, 64), R32(c, 96) : "l"(da), "l"(db));
    else asm volatile("wgmma.mma_async.sync.aligned.m64n256k16.f32.bf16.bf16 {" S32A S32B S32C S32D "},%128,%129,0,1,1,0,1;"
                      : W32(c, 0), W32(c, 32), W32(c, 64), W32(c, 96) : "l"(da), "l"(db));
}
template <bool ACC> __device__ __forceinline__ void wgmma128r(float* c, const uint4& a, uint64_t db) {
    if (ACC) asm volatile("wgmma.mma_async.sync.aligned.m64n128k16.f32.bf16.bf16 {" S32A S32B "},{%64,%65,%66,%67},%68,1,1,1,1;"
                          : R32(c, 0), R32(c, 32) : "r"(a.x), "r"(a.y), "r"(a.z), "r"(a.w), "l"(db));
    else asm volatile("wgmma.mma_async.sync.aligned.m64n128k16.f32.bf16.bf16 {" S32A S32B "},{%64,%65,%66,%67},%68,0,1,1,1;"
                      : W32(c, 0), W32(c, 32) : "r"(a.x), "r"(a.y), "r"(a.z), "r"(a.w), "l"(db));
}
template <int N> __device__ __forceinline__ void reg_inc() { asm volatile("setmaxnreg.inc.sync.aligned.u32 %0;" ::"n"(N)); }
template <int N> __device__ __forceinline__ void reg_dec() { asm volatile("setmaxnreg.dec.sync.aligned.u32 %0;" ::"n"(N)); }

#define PROF(cond, idx) do {} while (0)
#define CPROF(k) do {} while (0)

constexpr int S_GATE = 232440, S_TAG = 232444, S_XBAR = 232432;
constexpr float SC_LOG2E = 0.08838834764831845f * 1.4426950408889634f;

__device__ __forceinline__ float2 ln_finish(float mean, float var) {
    float sd; asm("sqrt.approx.f32 %0,%1;" : "=f"(sd) : "f"(rbf(rbf(var) + 1e-5f)));
    sd = rbf(sd);
    return make_float2(rbf(mean), sd);
}

__device__ __forceinline__ float4 row_stats(const uint4* src, int stride) {
    const int g = (threadIdx.x & 31) >> 2;
    uint4 v[16];
#pragma unroll
    for (int i = 0; i < 16; i++) v[i] = ldcg128(src + i * stride);
    float a[4] = {0, 0, 0, 0}, q0[4] = {0, 0, 0, 0}, q1[4] = {0, 0, 0, 0};
#pragma unroll
    for (int i = 0; i < 16; i++) {
        mma16(a, v[i].x, v[i].y, v[i].z, v[i].w, 0x3f803f80u, 0x3f803f80u);
        mma8(q0, v[i].x, v[i].y, v[i].x); mma8(q1, v[i].x, v[i].y, v[i].y);
        mma8(q0, v[i].z, v[i].w, v[i].z); mma8(q1, v[i].z, v[i].w, v[i].w);
    }
    return make_float4(a[0], (g & 1) ? q0[1] : q0[0], a[2], (g & 1) ? q1[3] : q1[2]);
}
__device__ __forceinline__ void x1_stats(int i) {
    const int lane = threadIdx.x & 31, g = lane >> 2, c = lane & 3;
    const float4 r = row_stats(g_xA[0] + i * 512 + lane, 32);
    float2* dst = g_st[0] + (i >> 4) * 2048 + ((i < 32 ? 4 : 0) + (i & 1)) * 128 + ((i >> 1) & 7) * 16 + g;
    if (c == (g >> 1)) { dst[0] = make_float2(r.x, r.y); dst[8] = make_float2(r.z, r.w); g_ln0[i * 8 + g] = 0; }
    __syncwarp();
    if (lane == 0) red_release(cnt_ptr(C_ST, i >> 4), 1);
}
__global__ void stats_kernel() { x1_stats(blockIdx.x * 4 + (threadIdx.x >> 5)); }

#define NT 9
#define RH 104
#define RW0 200
#define NPD 9
#define NTO 13
#define DP1 9
#define GPW 0
#define GPJ 0
#define PACE 2
#define BKA 0
#define GSE 4
#define EARLY 4
#define PFD 0
#define PFB 0
#define G2S 7
#define XPRE 0
#define STO 1
#define G2I 2
#define VE 4
#define VF 8
constexpr int R_WV = 0, R_WO = 65536, R_T = 131072, R_M = R_T + 20480, R_LOC = R_M + 4096, R_REM = R_LOC + 6144, R_O = R_REM + 12288, R_SX = R_O + 2048,
              R_IL = R_SX + 5120, XS = R_IL + 128 - R_T, R_BAR = 231936, R_Z = R_BAR + 128  , R_STQ = 0, R_STK = 65536, R_STV = 131072;
static_assert(R_T + 2 * XS <= R_BAR && R_BAR + 256 <= S_XBAR, "smem map");
enum { RB_INIT = 0, RB_MB = 1, RB_V = 4  , RB_QK = 8  , RB_T = 12  , RB_N = 16 };
enum { NB_MF = 1  , NB_LOC = 3  , NB_PAIR = 5  , NB_O = 9  , NB_XG = 11  , NB_W = 13 };
__device__ __forceinline__ uint32_t clk32() { return (uint32_t)clock64(); }

__device__ __forceinline__ char* acc_base() { return (char*)(((size_t)g_acc + 131071) & ~(size_t)131071); }
__device__ __forceinline__ uint32_t acc_slice(uint32_t s6) { return (s6 & 1) * 256 + (s6 >> 1) * 1024; }
__device__ __forceinline__ uint32_t acc_main(uint32_t rank, uint32_t tid) { return acc_slice(rank * 32 + (tid >> 3)) + (tid & 7) * 16; }
__device__ __forceinline__ uint32_t acc_extra(uint32_t rank, uint32_t tid) { return 65536 + acc_slice(((tid >> 5) & 1) + rank * 4 + (tid >> 6) * 8) + (tid & 31) * 4; }
__device__ __forceinline__ uint32_t acc_slot(uint32_t s) { return (s & 1) * 128 + (s & 2) * 256; }
__device__ __forceinline__ void acc_init(const __nv_bfloat16* mem0, int i) {
    const uint32_t tid = i & 255, rank = (i >> 8) & 1, slot = (i >> 9) & 3, X = i >> 11;
    uint32_t v[5] = {0, 0, 0, 0, 0};
    if (slot == 3) {
        const uint16_t* m = (const uint16_t*)mem0 + (tid & 3) * 1024 + rank * 256 + (tid >> 5) * 32 + ((tid >> 2) & 7);
#pragma unroll
        for (int k = 0; k < 4; k++) v[k] = __ldg(m + k * 8) | ((uint32_t)__ldg(m + k * 8 + 512) << 16);
        v[4] = (v[3] >> 16) | 0x42000000u; v[3] = (v[3] & 0xffff) | 0x42000000u;
    }
    *(uint4*)(acc_base() + X * 32768 + acc_slot(slot) + acc_main(rank, tid)) = make_uint4(v[0], v[1], v[2], v[3]);
    *(uint32_t*)(acc_base() + X * 1024 + acc_slot(slot) + acc_extra(rank, tid)) = v[4];
}
__global__ void acc_init_kernel(const __nv_bfloat16* mem0) { acc_init(mem0, blockIdx.x * 256 + threadIdx.x); }

struct RecW { uint32_t am, ae, ah, dp, lp, lpw, vo, sb, bar, zero, ts, tn; };
__device__ __forceinline__ uint32_t vadd(uint32_t a, uint32_t b) { uint32_t d; asm volatile("add.u32 %0,%1,%2;" : "=r"(d) : "r"(a), "r"(b)); return d; }
__device__ __forceinline__ uint32_t vshr(uint32_t a, int n) { uint32_t d; asm volatile("shr.u32 %0,%1,%2;" : "=r"(d) : "r"(a), "r"(n)); return d; }
__device__ __forceinline__ uint64_t gptr(uint32_t lo, uint32_t hi) { uint64_t d; asm("mov.b64 %0,{%1,%2};" : "=l"(d) : "r"(lo), "r"(hi)); return d; }
__device__ __forceinline__ void sfence(uint32_t zero) { asm volatile("{.reg .pred p; setp.ne.u32 p,%0,0; @p exit;}" ::"r"(zero) : "memory"); }
#define SF sfence(k.zero)
#define TS(i) do {} while (0)
#define TSN(i) do {} while (0)
#define TSET(it, slot) do {} while (0)
struct Gat { uint32_t x, y, z, w, e; };
template <int X>
__device__ __forceinline__ void gat_issue(Gat& g, const RecW& k, int s, uint32_t dep) {
    const uint32_t o = acc_slot(s + 3) + dep;
    asm volatile("{.reg .b128 t; ld.relaxed.gpu.global.b128 t,[%5+%7]; mov.b128 {%0,%1,%2,%3},t; ld.relaxed.gpu.global.u32 %4,[%6+%8];}"
                 : "=r"(g.x), "=r"(g.y), "=r"(g.z), "=r"(g.w), "=r"(g.e) : "l"(gptr(k.am + o, k.ah)), "l"(gptr(k.ae + o, k.ah)), "n"(X * 32768), "n"(X * 1024) : "memory");
}
template <int X>
__device__ __forceinline__ bool gat_store(const Gat& g, const RecW& k) {
    uint32_t c;
    asm volatile("prmt.b32 %0,%1,%2,0x7632;" : "=r"(c) : "r"(g.w), "r"(g.e));
    SF;
    asm volatile("{.reg .b32 t; prmt.b32 t,%4,%6,0x5410; stmatrix.sync.aligned.m8n8.x4.trans.shared.b16 [%0+%5],{%1,%2,%3,t};}" ::"r"(k.lpw), "r"(g.x), "r"(g.y), "r"(g.z), "r"(g.w), "n"(R_M + X * XS), "r"(g.e) : "memory");
    return __all_sync(0xffffffffu, c == 0x42004200u);
}
template <int X>
__device__ __forceinline__ void gat_finish(bool ok, const RecW& k, int s) {
    if (!ok) {
        int n = s;
        while (true) {
            Gat g;
            gat_issue<X>(g, k, n, 0);
            if (gat_store<X>(g, k)) break;
            n += 4;
            if (n > 8000000) __trap();
        }
    }
}
__device__ __forceinline__ uint4 lds128o(uint32_t a, int o) { uint4 v; asm volatile("{.reg .b32 t; add.u32 t,%4,%5; ld.shared.v4.u32 {%0,%1,%2,%3},[t];}" : "=r"(v.x), "=r"(v.y), "=r"(v.z), "=r"(v.w) : "r"(a), "r"(o) : "memory"); return v; }
__device__ __forceinline__ uint4 ldsm4o(uint32_t a, int o) { uint4 v; asm volatile("{.reg .b32 t; add.u32 t,%4,%5; ldmatrix.sync.aligned.m8n8.x4.shared.b16 {%0,%1,%2,%3},[t];}" : "=r"(v.x), "=r"(v.y), "=r"(v.z), "=r"(v.w) : "r"(a), "r"(o) : "memory"); return v; }
__device__ __forceinline__ uint4 ldsm4to(uint32_t a, int o) { uint4 v; asm volatile("{.reg .b32 t; add.u32 t,%4,%5; ldmatrix.sync.aligned.m8n8.x4.trans.shared.b16 {%0,%1,%2,%3},[t];}" : "=r"(v.x), "=r"(v.y), "=r"(v.z), "=r"(v.w) : "r"(a), "r"(o) : "memory"); return v; }
__device__ __forceinline__ uint2 lds64o(uint32_t a, int o) { uint2 v; asm volatile("{.reg .b32 t; add.u32 t,%2,%3; ld.shared.v2.u32 {%0,%1},[t];}" : "=r"(v.x), "=r"(v.y) : "r"(a), "r"(o) : "memory"); return v; }
__device__ __forceinline__ void sts128o(uint32_t a, int o, uint32_t x, uint32_t y, uint32_t z, uint32_t w) { asm volatile("{.reg .b32 t; add.u32 t,%0,%5; st.shared.v4.u32 [t],{%1,%2,%3,%4};}" ::"r"(a), "r"(x), "r"(y), "r"(z), "r"(w), "r"(o) : "memory"); }
__device__ __forceinline__ void sts64o(uint32_t a, int o, uint32_t x, uint32_t y) { asm volatile("{.reg .b32 t; add.u32 t,%0,%3; st.shared.v2.u32 [t],{%1,%2};}" ::"r"(a), "r"(x), "r"(y), "r"(o) : "memory"); }
__device__ __forceinline__ uint32_t vxor(uint32_t a, uint32_t b) { uint32_t d; asm volatile("xor.b32 %0,%1,%2;" : "=r"(d) : "r"(a), "r"(b)); return d; }
#define WLD(base, i) wt[i] = lds128o(k.lpw, (base) + (i) * 4096)
template <int PASS, int X, int NP>
__device__ __forceinline__ void rec_qkv(const RecW& k, int s, const uint32_t (*wq)[4], const uint32_t (*wk)[4], uint4* wt, Gat& g2, int s2, bool& ok2, uint4& mf) {
    constexpr bool BWD = PASS == 2, DIRECT = !(BKA && PASS == 1);
    float aq[4] = {0, 0, 0, 0}, ak[4] = {0, 0, 0, 0}, av[4] = {0, 0, 0, 0};
    constexpr int ma = R_M + X * XS;
    if (BWD && GSE == 4) { TS(1); mbar_wait(k.sb + R_BAR + RB_MB * 8, s & 1); mf = ldsm4o(k.lp, ma + 7 * 512); TS(2); }
    if (!BWD || GSE < 2) {
        if (BWD) { TS(1); gat_finish<1>(GSE ? ok2 : gat_store<1>(g2, k), k, s); }
        bar_sync(NB_MF + X, 256);
        mf = ldsm4o(k.lp, ma + (BWD ? 7 : 0) * 512);
        if (BWD) TS(2); else { TS(0); TSN(13); }
    }
#pragma unroll
    for (int ii = 0; ii < 8; ii++) {
        const int i = BWD ? 7 - ii : ii;
        const uint4 m = mf;
        if (ii < 7) mf = ldsm4o(k.lp, ma + (BWD ? i - 1 : i + 1) * 512);
        if (PASS == 1 && ii == G2I) gat_issue<1>(g2, k, s2, 0);
        if (PASS == 1 && GSE == 2 && ii == 7) { TS(1); gat_finish<1>(gat_store<1>(g2, k), k, s2); }
        if (PASS == 1 && GSE == 4 && ii == G2S) { gat_finish<1>(gat_store<1>(g2, k), k, s2); mbar_arrive1(k.sb + R_BAR + RB_MB * 8); }
        SF;
#pragma unroll
        for (int hh = 0; hh < 2; hh++) {
            const int h = BWD ? 1 - hh : hh, ks = 2 * i + h;
            const uint32_t b0 = h ? m.z : m.x, b1 = h ? m.w : m.y;
            mma16(aq, wq[ks][0], wq[ks][1], wq[ks][2], wq[ks][3], b0, b1);
            mma16(ak, wk[ks][0], wk[ks][1], wk[ks][2], wk[ks][3], b0, b1);
            SF;
            mma16(av, wt[ks].x, wt[ks].y, wt[ks].z, wt[ks].w, b0, b1);
            SF;
            if (!BWD && ks + NP < 16) WLD(R_WV, ks + NP < 16 ? ks + NP : 0);
            if (BWD && ks >= NT) WLD(R_WV, ks >= NT ? ks - NT : 0);
            SF;
        }
    }
    if (PASS == 1 && GSE == 1) { ok2 = gat_store<1>(g2, k); SF; }
    if (PASS == 1 && GSE == 3) { TS(1); gat_finish<1>(gat_store<1>(g2, k), k, s2); }
    if (PASS == 1 && (GSE == 2 || GSE == 3)) { bar_sync(NB_MF + 1, 256); mf = ldsm4o(k.lp, ma + XS + 7 * 512); TS(2); SF; }
    const uint32_t ra = vadd(k.lpw, k.dp + R_REM + X * XS + (s & 1) * 6144), va = ((vshr(k.lp, 7) & 1) * 48 ^ k.lp ^ (k.vo & 64)) + (k.vo & ~64u);
    const uint32_t x0 = movm(pack2(aq[0], aq[1])), x1 = movm(pack2(aq[2], aq[3])), x2 = movm(pack2(ak[0], ak[1])), x3 = movm(pack2(ak[2], ak[3]));
    SF;
    asm volatile("stmatrix.sync.aligned.m8n8.x2.shared.b16 [%0+%3],{%1,%2};" ::"r"(va), "r"(pack2(av[0], av[1])), "r"(pack2(av[2], av[3])), "n"(R_LOC + X * XS) : "memory");
    SF;
    if (STO && DIRECT) st_async4(ra, x0, x1, x2, x3, k.bar + X * 16);
    asm volatile("st.shared.v4.u32 [%0+%5],{%1,%2,%3,%4};" ::"r"(k.lpw), "r"(x0), "r"(x1), "r"(x2), "r"(x3), "n"(R_LOC + X * XS) : "memory");
    bar_arrive(NB_LOC + X, 320);
    if (!STO && DIRECT) st_async4(ra, x0, x1, x2, x3, k.bar + X * 16);
    SF;
    TS(BWD ? 4 : 3);
}
template <bool BWD, int X>
__device__ __forceinline__ void rec_out(const RecW& k, int s, uint4* wt, Gat& g, int s1) {
    if (BWD) { WLD(R_WO, 17 - NTO); WLD(R_WO, 16 - NTO); }
    TS(BWD ? 8 : 5);
    bar_sync(NB_O + X, 320);
    float r0[4] = {0, 0, 0, 0}, r1[4] = {0, 0, 0, 0};
    constexpr int oa = R_O + X * XS;
    uint4 bn = lds128o(k.lp, oa + (BWD ? 3 : 0) * 512);
    TS(BWD ? 9 : 6);
    uint2 il;
    uint64_t pm, pe;
#pragma unroll
    for (int ii = 0; ii < 4; ii++) {
        const int i = BWD ? 3 - ii : ii;
        const uint4 b = bn;
        if (ii < 3) bn = lds128o(k.lp, oa + (BWD ? i - 1 : i + 1) * 512);
        else { asm volatile("ld.shared.v2.u32 {%0,%1},[%2+%3];" : "=r"(il.x), "=r"(il.y) : "r"((vshr(k.ae, 2) & 3) * 8 + k.sb), "n"(R_IL + X * XS) : "memory"); pm = gptr(vadd(k.am, acc_slot(s)), k.ah); pe = gptr(vadd(k.ae, acc_slot(s)), k.ah); }
        SF;
        if (BWD && EARLY == ii + 1) { gat_issue<0>(g, k, s1 + 1, 0); SF; }
#pragma unroll
        for (int nn = 0; nn < 4; nn++) {
            const int n = BWD ? 3 - nn : nn, f = 4 * i + n, nx = BWD ? f - NTO + 2 : f + NTO - 2;
            mma16((n & 1) ? r1 : r0, wt[f].x, wt[f].y, wt[f].z, wt[f].w, n >> 1 ? b.z : b.x, n >> 1 ? b.w : b.y);
            SF;
            if (ii * 4 + nn >= 2 && nx >= 0 && nx < 16) WLD(R_WO, nx & 15);
            SF;
        }
    }
    const float i0 = __uint_as_float(il.x), i1 = __uint_as_float(il.y);
    asm volatile("red.relaxed.gpu.global.add.noftz.v4.bf16x2 [%0+%5],{%1,%2,%3,%4};" ::"l"(pm),
                 "r"(pack2(r0[0] * i0, r0[1] * i1)), "r"(pack2(r0[2] * i0, r0[3] * i1)), "r"(pack2(r1[0] * i0, r1[1] * i1)), "r"(pack2(r1[2] * i0, 1.f)), "n"(X * 32768) : "memory");
    asm volatile("red.relaxed.gpu.global.add.noftz.bf16x2 [%0+%2],%1;" ::"l"(pe), "r"(pack2(r1[3] * i1, 1.f)), "n"(X * 1024) : "memory");
    bar_arrive(NB_XG + X, 320);
    SF;
    TS(BWD ? 10 : 7);
}
__device__ __forceinline__ uint32_t pause(uint32_t v, int n) {
#pragma unroll
    for (int i = 0; i < n; i++) asm volatile("shfl.sync.bfly.b32 %0,%0,0,0x1f,0xffffffff;" : "+r"(v));
    return v;
}
template <bool DUAL, int X>
__device__ __forceinline__ void rec_step(const RecW& k, int s, int s2, const uint32_t (*wq)[4], const uint32_t (*wk)[4], uint4* wt) {
    constexpr int NP = NPD;
    uint4 wo[16];
    Gat g;
    bool ok2;
    uint4 mf;
    rec_qkv<DUAL ? 1 : 0, X, NP>(k, s, wq, wk, wt, g, s2, ok2, mf);
    if (DUAL) rec_qkv<2, 1, NP>(k, s2, wq, wk, wt, g, s2, ok2, mf);
    uint32_t wa = k.lpw;
#pragma unroll
    for (int i = 0; i < NTO; i++) {
        wo[i] = lds128o(wa, R_WO + i * 4096);
        if (i % PACE == PACE - 1) wa = k.lpw + (wo[i].x & k.zero);
        SF;
    }
    rec_out<false, X>(k, s, wo, g, s);
    if (DUAL) { rec_out<true, 1>(k, s2, wo, g, s); if (!EARLY) gat_issue<0>(g, k, s + 1, 0); SF; }
#pragma unroll
    for (int i = 0; i < NP; i++) { WLD(R_WV, i); SF; }
    if (!DUAL) gat_issue<X>(g, k, s + 1, pause(wt[NP - 1].x & k.zero, DP1));
    TS(12);
    gat_finish<X>(gat_store<X>(g, k), k, s + 1);
    TS(11);
}

__device__ __forceinline__ void rec_fetch(const CUtensorMap* tm, uint32_t dst, int x, int y, int nx, uint32_t bar) {
#pragma unroll 1
    for (int j = 0; j < 8; j++) tma2d(dst + j * 8192, tm, x + (j / (8 / nx)) * 64, y + (j % (8 / nx)) * 64, bar);
}
__device__ __forceinline__ void rec_weights(const Params& p, uint32_t sb, int head, uint32_t rank, int w) {
    const int lane = threadIdx.x & 31, t = w & 3, WG = w >> 2;
    uint32_t wq[16][4], wk[16][4];
    const uint32_t rowo = (((lane >> 4) << 3) + (lane & 7)) * 128;
    const uint32_t woff = sb + WG * 32768 + rowo + (((2 * t + ((lane >> 3) & 1)) ^ (lane & 7)) << 4);
    const uint32_t qoff = sb + ((w & 1) ? R_STK : R_STQ) + WG * 32768 + rowo + (((2 * (t & 2) + ((lane >> 3) & 1)) ^ (lane & 7)) << 4);
    const uint32_t lw = sb + (lane ^ (lane >> 3)) * 16;
    PROF(threadIdx.x == 0, 3501);
    PROF(threadIdx.x == 0, 3502);
    mbar_wait(sb + R_BAR + RB_INIT * 8, 0);
    PROF(threadIdx.x == 0, 3503);
#pragma unroll
    for (int ks = 0; ks < 16; ks++) {
        uint4 a = ldsm4t(qoff + ks * 2048), b = ldsm4t((qoff ^ 32) + ks * 2048);
        wq[ks][0] = a.x; wq[ks][1] = a.y; wq[ks][2] = a.z; wq[ks][3] = a.w;
        wk[ks][0] = b.x; wk[ks][1] = b.y; wk[ks][2] = b.z; wk[ks][3] = b.w;
    }
    bar_sync(NB_W, 256);
#pragma unroll 4
    for (int ks = 0; ks < 16; ks++) { const uint4 a = ldsm4t(woff + R_STV + ks * 2048); sts128(lw + w * 512 + R_WV + ks * 4096, a.x, a.y, a.z, a.w); }
    bar_sync(NB_W, 256);
    if (threadIdx.x == 0) {
        mbar_expect(sb + R_BAR + RB_INIT * 8, 65536);
        rec_fetch(&p.tm[4], sb + R_STV, rank * 256, head * 128, 4, sb + R_BAR + RB_INIT * 8);
    }
    __syncwarp();
    mbar_wait(sb + R_BAR + RB_INIT * 8, 1);
#pragma unroll 4
    for (int f = 0; f < 16; f++) {
        const uint4 a = ldsm4t(sb + R_STV + (w >> 1) * 16384 + (f >> 1) * 2048 + rowo + ((((w & 1) * 4 + (f & 1) * 2 + ((lane >> 3) & 1)) ^ (lane & 7)) << 4));
        sts128(lw + w * 512 + R_WO + f * 4096, a.x, a.y, a.z, a.w);
    }
    PROF(threadIdx.x == 0, 3504);
    __syncthreads();
    cluster_sync();
    PROF(threadIdx.x == 0, 3505);
    RecW k;
    k.am = __shfl_sync(0xffffffffu, (uint32_t)(size_t)acc_base() + acc_main(rank, threadIdx.x), lane);
    k.ae = __shfl_sync(0xffffffffu, (uint32_t)(size_t)acc_base() + acc_extra(rank, threadIdx.x), lane);
    k.ah = (uint32_t)((size_t)acc_base() >> 32);
    k.sb = sb; k.zero = p.zero;

    k.dp = mapa(sb, rank ^ 1) - sb;
    k.lp = __shfl_sync(0xffffffffu, lw, lane);
    k.lpw = __shfl_sync(0xffffffffu, lw + w * 512, lane);
    k.vo = 4096 + w * 256 + (w & 1) * 64;
    k.bar = sb + k.dp + R_BAR + (RB_QK + WG) * 8;
    int it = 0;
    uint4 wt[16];
#pragma unroll
    for (int i = 0; i < NPD; i++) WLD(R_WV, i);
    gat_finish<0>(false, k, 0);
#pragma unroll 1
    for (; it < min(p.b1, p.e0); it++) { TSET(it, w == GPW ? 0 : 3); rec_step<false, 0>(k, it, it, wq, wk, wt); }
#pragma unroll 1
    for (; it < p.e0; it++) { TSET(it, w == GPW ? 0 : 3); rec_step<true, 0>(k, it, it - p.b1, wq, wk, wt); }
    if (it < p.nit) gat_finish<1>(false, k, it - p.b1);
#pragma unroll 1
    for (; it < p.nit; it++) { TSET(it, w == GPW ? 0 : 3); rec_step<false, 1>(k, it - p.b1, it - p.b1, wq, wk, wt); }
}

__device__ __forceinline__ void mma16_top(float* c, uint32_t a0, uint32_t a2, uint32_t b0, uint32_t b1) {
    asm volatile("{.reg .b32 j; mma.sync.aligned.m16n8k16.row.col.f32.bf16.bf16.f32 {%0,%1,%2,%3},{%4,j,%5,j},{%6,%7},{%0,%1,%2,%3};}"
                 : "+f"(c[0]), "+f"(c[1]), "+f"(c[2]), "+f"(c[3]) : "r"(a0), "r"(a2), "r"(b0), "r"(b1));
}
__device__ __forceinline__ void rec_load_tile(uint32_t sb, int X, int j, int s, int head, uint32_t rank) {
    const uint32_t bar = sb + R_BAR + (RB_T + X * 2 + j) * 8;
    mbar_expect1(bar, j ? 4096 : 16384);
    bulk_g2s1(sb + R_T + X * XS + j * 16384, g_qkv[X] + (size_t)(s * 32 + head) * 1536 + (j ? rank * 256 : 512), j ? 4096 : 16384, bar, POL_LAST);
}
__device__ __forceinline__ bool chunk_ready(int X, int j, int s) {
    unsigned v;
    asm volatile("ld.relaxed.gpu.global.u32 %0,[%1];" : "=r"(v) : "l"(cnt_ptr(C_QKV0 + X, (s >> 2) + j * 16)) : "memory");
    return __all_sync(0xffffffffu, v >= (256 >> j));
}
__device__ __forceinline__ uint4 hadd4(uint4 a, uint4 b) { return make_uint4(hadd2(a.x, b.x), hadd2(a.y, b.y), hadd2(a.z, b.z), hadd2(a.w, b.w)); }
struct RecH { uint32_t lw, lm, lq, lv, lu, sa, sp, xb, sb, zero, ts, tn; };
__device__ __forceinline__ void rec_publish(int X, int s) {
    asm volatile("{.reg .pred p; cp.async.bulk.wait_group 0; elect.sync _|p,0xffffffff; @p red.relaxed.gpu.global.add.u32 [%0],4;}" ::"l"(cnt_ptr(C_O0 + X, s >> 2)) : "memory");
}
__device__ __forceinline__ void rec_mattn(const RecH& k, uint32_t dp, int X, int j, int s, bool qk, uint4 (*V)[4], uint4* vm, uint4* kmm) {
    const uint32_t sb = k.sb, to = R_T, lo = R_LOC, ro = R_REM + (s & 1) * 6144;
    const uint32_t bar = sb + R_BAR + (X * 2 + j) * 8;
    uint4 K[2][4];
    mbar_wait(sb + R_BAR + (RB_T + X * 2) * 8, s & 1);
    TS(1);
#pragma unroll
    for (int i = 0; i < 8; i++) K[i >> 2][i & 3] = ldsm4o(k.lm, (to + (i >> 2) * 1024 + ((i >> 1) & 1) * 4096 + (i & 1) * 512));
    asm volatile("cp.async.bulk.wait_group 0;" ::: "memory");
    bar_sync(NB_LOC + X, 320);
    fence_async_smem();
    if (qk) asm volatile("{.reg .pred p; elect.sync _|p,0xffffffff; @p cp.async.bulk.shared::cluster.shared::cta.mbarrier::complete_tx::bytes [%0],[%1],2048,[%2];}"
                         ::"r"(k.xb + dp + ro + j * 1024), "r"(k.xb + lo + j * 1024), "r"(bar + dp + RB_QK * 8) : "memory");
    asm volatile("{.reg .pred p; elect.sync _|p,0xffffffff; @p cp.async.bulk.shared::cluster.shared::cta.mbarrier::complete_tx::bytes [%0],[%1],1024,[%2];}"
                 ::"r"(k.xb + dp + ro + 4096), "r"(k.xb + lo + 4096), "r"(bar + dp + RB_V * 8) : "memory");
    uint4 u[4];
#pragma unroll
    for (int i = 0; i < 4; i++) u[i] = ldsm4o(k.lm, (lo + i * 512));
    TS(2);
    mbar_wait(bar + RB_QK * 8, s & 1);
    TS(3);
    float S[5][4];
#pragma unroll
    for (int i = 0; i < 5; i++) S[i][0] = S[i][1] = S[i][2] = S[i][3] = 0;
    {
        uint4 r[4];
#pragma unroll
        for (int i = 0; i < 4; i++) r[i] = ldsm4o(k.lm, (ro + i * 512));
        SF;
#pragma unroll
        for (int e = 0; e < 2; e++) {
            uint4& km = u[2 * e + 1];
            const uint32_t q0 = hadd2(u[2 * e].x, r[2 * e].x), q1 = hadd2(u[2 * e].y, r[2 * e].y);
            mma16_top(S[0], q0, q1, K[e][0].x, K[e][0].y);
            km.x = hadd2(km.x, r[2 * e + 1].x); km.y = hadd2(km.y, r[2 * e + 1].y);
            SF;
            mma16_top(S[1], q0, q1, K[e][1].x, K[e][1].y);
            const uint32_t q2 = hadd2(u[2 * e].z, r[2 * e].z), q3 = hadd2(u[2 * e].w, r[2 * e].w);
            SF;
            mma16_top(S[2], q0, q1, K[e][2].x, K[e][2].y);
            km.z = hadd2(km.z, r[2 * e + 1].z); km.w = hadd2(km.w, r[2 * e + 1].w);
            SF;
            mma16_top(S[3], q0, q1, K[e][3].x, K[e][3].y);
            mma16_top(S[4], q0, q1, km.x, km.y);
            SF;
#pragma unroll
            for (int i = 0; i < 4; i++) {
                mma16_top(S[i], q2, q3, K[e][i].z, K[e][i].w); SF;
            }
            mma16_top(S[4], q2, q3, km.z, km.w);
            SF;
        }
    }
#define VLD(a, b) _Pragma("unroll") for (int i = (a); i < (b); i++) V[i >> 2][i & 3] = ldsm4to((i & 1) ? lv2 : k.lv, (to + 8192 + (i >> 2) * 4096 + ((i >> 1) & 1) * 1024))
    const uint32_t lv2 = vxor(k.lv, 0x20), lh = k.lw - (vshr(k.lw - k.xb, 1) & 0xf8);
    VLD(0, VE);
    SF;
    const uint32_t sxr = k.sa, sxw = k.sp;
    sts128o(k.lw, sxw, __float_as_uint(S[0][0]), __float_as_uint(S[0][1]), __float_as_uint(S[1][0]), __float_as_uint(S[1][1]));
    SF;
    sts128o(k.lw, (sxw + 512), __float_as_uint(S[2][0]), __float_as_uint(S[2][1]), __float_as_uint(S[3][0]), __float_as_uint(S[3][1]));
    SF;
    sts64o(lh, (sxw + 1024), __float_as_uint(S[4][0]), __float_as_uint(S[4][1]));
    TS(4);
    bar_sync(NB_PAIR + X, 64);
    {
        const uint4 a = lds128o(k.lw, sxr), b = lds128o(k.lw, (sxr + 512));
        const uint2 c = lds64o(lh, (sxr + 1024));
        SF;
        VLD(VE, VF);
        SF;
        S[0][0] += __uint_as_float(a.x); S[0][1] += __uint_as_float(a.y); S[1][0] += __uint_as_float(a.z); S[1][1] += __uint_as_float(a.w);
        S[2][0] += __uint_as_float(b.x); S[2][1] += __uint_as_float(b.y); S[3][0] += __uint_as_float(b.z); S[3][1] += __uint_as_float(b.w);
        S[4][0] += __uint_as_float(c.x); S[4][1] += __uint_as_float(c.y);
    }
    float m = fmaxf(fmaxf(fmaxf(S[0][0], S[0][1]), fmaxf(S[1][0], S[1][1])), fmaxf(fmaxf(S[2][0], S[2][1]), fmaxf(S[3][0], S[3][1])));
    m = fmaxf(m, fmaxf(S[4][0], S[4][1]));
    m = fmaxf(m, __shfl_xor_sync(0xffffffffu, m, 1));
    const float m2 = __shfl_xor_sync(0xffffffffu, m, 2);
    SF;
    VLD(VF, 8);
    uint32_t ok;
    asm volatile("{.reg .pred p; mbarrier.test_wait.parity.shared::cta.b64 p,[%1],%2; selp.u32 %0,1,0,p;}" : "=r"(ok) : "r"(bar + RB_V * 8), "r"(s & 1) : "memory");
    uint4 vr0 = ldsm4o(k.lu, (ro + 4096)), vr1 = ldsm4o(k.lu, (ro + 4608));
    vm[0] = ldsm4o(k.lu, (lo + 4096)); vm[1] = ldsm4o(k.lu, (lo + 4608));
    SF;
    TS(5);
    m = fmaxf(m, m2) * -SC_LOG2E;
    uint32_t P[5];
#pragma unroll
    for (int i = 0; i < 5; i++) P[i] = pack2(ex2(fmaf(S[i][0], SC_LOG2E, m)), ex2(fmaf(S[i][1], SC_LOG2E, m)));
    float o[4][4], l[4] = {0, 0, 0, 0};
    const uint32_t ONE = 0x3f803f80u;
    mma16_top(l, ONE, ONE, P[0], P[1]);
#pragma unroll
    for (int t = 0; t < 4; t++) { o[t][0] = o[t][1] = o[t][2] = o[t][3] = 0; mma16(o[t], V[0][t].x, V[0][t].y, V[0][t].z, V[0][t].w, P[0], P[1]); }
    mma16_top(l, ONE, ONE, P[2], P[3]);
#pragma unroll
    for (int t = 0; t < 4; t++) mma16(o[t], V[1][t].x, V[1][t].y, V[1][t].z, V[1][t].w, P[2], P[3]);
    if (!__all_sync(0xffffffffu, ok)) {
        mbar_wait(bar + RB_V * 8, s & 1);
        vr0 = ldsm4o(k.lu, (ro + 4096)); vr1 = ldsm4o(k.lu, (ro + 4608));
    }
    TS(6);
    vm[0] = hadd4(vm[0], vr0); vm[1] = hadd4(vm[1], vr1);
    mma8(l, ONE, ONE, P[4]);
    mma8(o[0], vm[0].x, vm[0].y, P[4]); mma8(o[1], vm[0].z, vm[0].w, P[4]); mma8(o[2], vm[1].x, vm[1].y, P[4]); mma8(o[3], vm[1].z, vm[1].w, P[4]);
    asm volatile("{.reg .pred p; .reg .b32 t; setp.lt.u32 p,%0,%3; add.u32 t,%0,%4; @p st.shared.v2.f32 [t],{%1,%2};}" ::"r"(lh), "f"(rcp(l[0])), "f"(rcp(l[1])), "r"(k.xb + 32), "r"(R_IL) : "memory");
#pragma unroll
    for (int t = 0; t < 4; t += 2)
        asm volatile("{.reg .b32 t; add.u32 t,%0,%5; stmatrix.sync.aligned.m8n8.x4.trans.shared.b16 [t],{%1,%2,%3,%4};}" ::"r"(k.lm),
                     "r"(pack2(o[t][0], o[t][1])), "r"(pack2(o[t][2], o[t][3])), "r"(pack2(o[t + 1][0], o[t + 1][1])), "r"(pack2(o[t + 1][2], o[t + 1][3])), "r"(R_O - j * 1024 + t * 256) : "memory");
    bar_arrive(NB_O + X, 320);
    PROF(k.lw == k.xb, X * 64 + s);
    TS(7);
    kmm[0] = u[1]; kmm[1] = u[3];
    mbar_expect1(bar + RB_QK * 8, 2048); mbar_expect1(bar + RB_V * 8, 1024);
}
template <int MT>
__device__ __forceinline__ void rec_xattn(const RecH& k, int X, int j, int s, int head, bool early, const uint4 (*V)[4], const uint4* vmm, const uint4* kmm) {
    constexpr int NTL = 3 + 2 * MT;
    const uint32_t sb = k.sb, to = R_T;
    const uint32_t sxw = k.sa, sxr = k.sp;
    const uint32_t lq2 = vxor(k.lq, 0x20);
    float S[NTL][4];
#pragma unroll
    for (int i = 0; i < NTL; i++) S[i][0] = S[i][1] = S[i][2] = S[i][3] = 0;
    {
        uint4 q[2][2], kk[2][NTL];
#define XQ(e) q[e][0] = ldsm4o(k.lq, (to + 16384 + (e) * 1024)); q[e][1] = ldsm4o(lq2, (to + 16384 + (e) * 1024))
#define XK(e, i) kk[e][i] = ldsm4o(k.lm, (to + (e) * 1024 + (((i) - 1) >> 1) * 4096 + (((i) - 1) & 1) * 512))
        kk[0][0] = kmm[0]; kk[1][0] = kmm[1];
        if (XPRE == 0) { bar_sync(NB_XG + X, 320); TS(8); }
        XQ(0);
#pragma unroll
        for (int i = 1; i < NTL; i++) XK(0, i);
        if (XPRE == 1) { bar_sync(NB_XG + X, 320); TS(8); }
        SF;
#pragma unroll
        for (int i = 0; i < NTL; i++) { mma16(S[i], q[0][0].x, q[0][0].y, q[0][0].z, q[0][0].w, kk[0][i].x, kk[0][i].y); SF; }
        q[1][0] = ldsm4o(k.lq, (to + 16384 + 1024));
#pragma unroll
        for (int i = 0; i < NTL; i++) { mma16(S[i], q[0][1].x, q[0][1].y, q[0][1].z, q[0][1].w, kk[0][i].z, kk[0][i].w); SF; if (i + 1 < NTL) XK(1, i + 1); SF; }
        q[1][1] = ldsm4o(lq2, (to + 16384 + 1024));
        if (XPRE == 2) { bar_sync(NB_XG + X, 320); TS(8); }
        SF;
#pragma unroll
        for (int i = 0; i < NTL; i++) { mma16(S[i], q[1][0].x, q[1][0].y, q[1][0].z, q[1][0].w, kk[1][i].x, kk[1][i].y); SF; }
#pragma unroll
        for (int i = 0; i < NTL; i++) { mma16(S[i], q[1][1].x, q[1][1].y, q[1][1].z, q[1][1].w, kk[1][i].z, kk[1][i].w); SF; }
    }
#pragma unroll
    for (int i = 0; i < NTL; i++) sts128o(k.lw, (sxw + i * 512), __float_as_uint(S[i][0]), __float_as_uint(S[i][1]), __float_as_uint(S[i][2]), __float_as_uint(S[i][3]));
    SF;
    if (XPRE == 3) bar_sync(NB_XG + X, 320); else bar_sync(NB_PAIR + 2 + X, 64);
    TS(9);
    if (early) rec_load_tile(sb, X, j, s + 1, head, MT);
#pragma unroll
    for (int i = 0; i < NTL; i++) {
        const uint4 r = lds128o(k.lw, (sxr + i * 512));
        S[i][0] += __uint_as_float(r.x); S[i][1] += __uint_as_float(r.y); S[i][2] += __uint_as_float(r.z); S[i][3] += __uint_as_float(r.w);
    }
    const int g = vshr(k.lw - k.xb, 6) & 7, c = (vshr(k.lw, 4) ^ (g >> 1)) & 3;
    const float NEG = -__int_as_float(0x7f800000);
    if (2 * c > g) { S[NTL - 2][0] = NEG; S[NTL - 1][2] = NEG; }
    if (2 * c + 1 > g) { S[NTL - 2][1] = NEG; S[NTL - 1][3] = NEG; }
    float m0 = fmaxf(S[0][0], S[0][1]), m1 = fmaxf(S[0][2], S[0][3]);
#pragma unroll
    for (int i = 1; i < NTL; i++) { if (i < NTL - 1) m0 = fmaxf(m0, fmaxf(S[i][0], S[i][1])); m1 = fmaxf(m1, fmaxf(S[i][2], S[i][3])); }
    m0 = fmaxf(m0, __shfl_xor_sync(0xffffffffu, m0, 1)); m1 = fmaxf(m1, __shfl_xor_sync(0xffffffffu, m1, 1));
    m0 = fmaxf(m0, __shfl_xor_sync(0xffffffffu, m0, 2)); m1 = fmaxf(m1, __shfl_xor_sync(0xffffffffu, m1, 2));
    m0 *= -SC_LOG2E; m1 *= -SC_LOG2E;
    uint32_t P[NTL][2];
#pragma unroll
    for (int i = 0; i < NTL; i++) {
        P[i][0] = i < NTL - 1 ? pack2(ex2(fmaf(S[i][0], SC_LOG2E, m0)), ex2(fmaf(S[i][1], SC_LOG2E, m0))) : 0u;
        P[i][1] = pack2(ex2(fmaf(S[i][2], SC_LOG2E, m1)), ex2(fmaf(S[i][3], SC_LOG2E, m1)));
    }
    float l[4] = {0, 0, 0, 0};
#pragma unroll
    for (int i = 0; i < NTL; i++) mma8(l, P[i][0], P[i][1], 0x3f803f80u);
    const float l0 = rcp(l[0]), l1 = rcp(l[2]);

#pragma unroll
    for (int e = 0; e < 2; e++) {
        const uint4 vm = vmm[e];
        uint32_t u[2][4];
#pragma unroll
        for (int n = 0; n < 4; n++) {
            float a[4] = {0, 0, 0, 0};
#pragma unroll
            for (int m = 0; m <= MT; m++) {
                const uint4 v = V[m][e * 2 + (n >> 1)];
                mma8(a, P[1 + 2 * m][0], P[1 + 2 * m][1], (n & 1) ? v.y : v.x); mma8(a, P[2 + 2 * m][0], P[2 + 2 * m][1], (n & 1) ? v.w : v.z);
            }
            mma8(a, P[0][0], P[0][1], n == 0 ? vm.x : n == 1 ? vm.y : n == 2 ? vm.z : vm.w);
            u[0][n] = pack2(a[0] * l0, a[1] * l0); u[1][n] = pack2(a[2] * l1, a[3] * l1);
        }
        sts128o(k.lw, sxr + e * 512, u[0][0], u[0][1], u[0][2], u[0][3]); sts128o(k.lw, sxr + e * 512 + 1024, u[1][0], u[1][1], u[1][2], u[1][3]);
    }
    TS(10);
}
__device__ __forceinline__ void rec_attn(const Params& p, uint32_t sb, int X, int j, int head, uint32_t rank) {
    const int lane = threadIdx.x & 31;
    RecH k;
    k.xb = sb + X * XS + j * 1024;
    const uint32_t x2 = k.xb + j * 1024;
    k.lw = __shfl_sync(0xffffffffu, x2 + (lane ^ (lane >> 3)) * 16, lane);
    k.lm = __shfl_sync(0xffffffffu, x2 + ((lane & 7) * 4 + ((lane >> 3) ^ ((lane & 7) >> 1))) * 16, lane);
    k.lq = __shfl_sync(0xffffffffu, x2 + ((lane >> 3) & 1) * 512 + ((lane & 7) * 4 + ((lane >> 4) ^ ((lane & 7) >> 1))) * 16, lane);
    k.lv = __shfl_sync(0xffffffffu, x2 + (lane >> 4) * 512 + ((lane & 7) * 4 + (((lane >> 3) & 1) ^ ((lane & 7) >> 1))) * 16, lane);
    k.lu = __shfl_sync(0xffffffffu, k.xb + ((lane & 6) * 4 + (((lane >> 3) * 2 + (lane & 1)) ^ (lane & 6))) * 16, lane);
    k.sa = __shfl_sync(0xffffffffu, R_SX + j * 512, 0); k.sp = __shfl_sync(0xffffffffu, R_SX + 2560 - j * 4608, 0);
    k.sb = sb; k.zero = p.zero;
    const uint32_t dp = mapa(sb, rank ^ 1) - sb;
    char* zp = acc_base() + (j ? X * 32768 + acc_main(rank, head * 8) : X * 1024 + acc_extra(rank, head * 8));
    mbar_expect1(sb + R_BAR + (RB_QK + X * 2 + j) * 8, 2048); mbar_expect1(sb + R_BAR + (RB_V + X * 2 + j) * 8, 1024);
    bool early = false;
#pragma unroll 1
    for (int s = 0; s < 64; s++) {
        TSET(X ? s + p.b1 : s, j == GPJ ? 1 + X : 3);
        TS(0);
        if (!early) {
            if (!j) wait_cnt_warp(cnt_ptr(C_QKV0 + X, s >> 2), 256);
            early = !j || chunk_ready(X, 1, s);
            if (early) rec_load_tile(sb, X, j, s, head, rank);
        }
        if (PFD && s < 63 && early && (PFB || !X) && ((s & 3) != 3 || chunk_ready(X, j, s + 1)))
            asm volatile("{.reg .pred p; elect.sync _|p,0xffffffff; @p cp.async.bulk.prefetch.L2.global.L2::cache_hint [%0],%1,%2;}"
                         ::"l"(g_qkv[X] + (size_t)((s + 1) * 32 + head) * 1536 + (j ? rank * 256 : 512 + rank * 512)), "r"(j ? 4096 : 8192), "l"(POL_LAST) : "memory");
        uint4 V[2][4], vm[2], km[2];
        rec_mattn(k, dp, X, j, s, BKA && !X && s >= p.b1, V, vm, km);
        if (!early) { wait_cnt_warp(cnt_ptr(C_QKV0 + X, (s >> 2) + 16), 128); rec_load_tile(sb, X, 1, s, head, rank); }
        early = s < 63 && ((s & 3) != 3 || chunk_ready(X, j, s + 1));
        mbar_wait(sb + R_BAR + (RB_T + X * 2 + 1) * 8, s & 1);
        if (rank) rec_xattn<1>(k, X, j, s, head, early, V, vm, km); else rec_xattn<0>(k, X, j, s, head, early, V, vm, km);
        fence_async_smem();
        __syncwarp();
        asm volatile("{.reg .pred p; elect.sync _|p,0xffffffff;\n"
                     "@p cp.async.bulk.global.shared::cta.bulk_group.L2::cache_hint [%0],[%1],2048,%2;\n"
                     "@p cp.async.bulk.global.shared::cta.bulk_group [%3],[%4],%5;\n"
                     "cp.async.bulk.commit_group;}"
                     ::"l"(g_o[X] + ((s >> 2) * 64 + head * 2 + j) * 1024 + ((s & 3) * 2 + rank) * 128), "r"(x2 + k.sp),
                       "l"((X && s < 40) ? POL_LATE : POL_SOON), "l"(zp + acc_slot(s + 2)), "r"(sb + R_Z), "r"(j ? 128 : 32) : "memory");
        if ((s & 3) == 3) {
            if (!early && s < 63 && chunk_ready(X, j, s + 1)) { rec_load_tile(sb, X, j, s + 1, head, rank); early = true; }
            rec_publish(X, s);
            PROF(lane == 0 && j, 3900 + X * 16 + (s >> 2));
        }
    }
}

__device__ __forceinline__ void rec_init(const Params& p, uint32_t sb, int head, uint32_t rank) {
    const uint32_t b = sb + R_BAR;
    const int i = threadIdx.x - 320;
    if (i >= 0 && i < RB_N) {
        mbar_init(b + i * 8, i == RB_MB ? 8 : 1);
        asm volatile("fence.mbarrier_init.release.cluster;" ::: "memory");
    }
    if (i == 0) mbar_expect(b + RB_INIT * 8, 196608);
    if (i >= 0 && i < 32) sts32(sb + R_Z + i * 4, 0);
}

#define NSTGN 8
constexpr int NSTG = NSTGN, STG_B = 24576;
#define LAGH 3
constexpr int NSB = 8;
constexpr int B_OUT = NSTG * STG_B  , B_UT = B_OUT, B_YT = B_UT + 16384, B_SP = B_YT  ,
              B_ST = 229376  , B_BAR = 231936;
static_assert(B_OUT + NSB * 4096 <= B_ST && B_ST + 2048 <= B_BAR && B_YT + 10240 <= B_ST, "smem map");
enum { BB_FULL = 0, BB_EMPTY = 8, BB_SF = 16  , BB_GO = 18, BB_DONE = 20  , BB_IDLE = 22  , BB_N = 30 };
enum { NB_REL = 2  , NB_C = 11, NB_WG = 12  , NB_PH = 14 };

__device__ __forceinline__ void bulk_init(uint32_t sb) {
    const int i = threadIdx.x - 320;
    if (i >= 0 && i < BB_N) {
        mbar_init(sb + B_BAR + i * 8, (i >= BB_EMPTY && i < BB_EMPTY + NSTG) ? 4 : i >= BB_DONE ? 4 : 1);
        asm volatile("fence.mbarrier_init.release.cluster;" ::: "memory");
    }
}

struct Task { int type, layer, ch, a, b, c, blk; bool pair, dry; };
__device__ __forceinline__ Task task_of(uint32_t tk, uint32_t rank) {
    Task t;
    t.type = tk & 7; t.layer = (tk >> 3) & 1; t.a = (tk >> 8) & 255; t.b = (tk >> 16) & 255; t.c = (tk >> 24) & 127; t.dry = tk >> 31;
    t.pair = t.type <= T_OP && (t.c & 64);
    t.ch = ((tk >> 4) & 15) + (t.pair ? rank : 0);
    t.blk = t.type == T_QKV ? t.a + (t.pair ? 0 : rank) : 192 + (t.pair ? (t.c >> 2) & 4 : rank * 4);
    return t;
}
__device__ __forceinline__ int qkv_blk(const Task& t, int u) {
    const int v = t.blk + (t.pair ? 1 : 2 * t.c) * u;
    return 2 * (v < 64 ? v + 32 : v - 64);
}
__device__ __forceinline__ void bulk_producer(const Params& p, uint32_t sb, int cl, uint32_t rank) {
    int st = 0; uint32_t ph = 1;
    const int tag = __shfl_sync(0xffffffffu, lds32(sb + S_TAG), 0);
    bool gated = false;
#define ACQ(bytes) do { mbar_wait(sb + B_BAR + (BB_EMPTY + st) * 8, ph); mbar_expect1(sb + B_BAR + (BB_FULL + st) * 8, bytes); } while (0)
#define NEXT do { if (++st == NSTG) { st = 0; ph ^= 1; } } while (0)
#pragma unroll 1
    for (int ti = 0; ti < MAXT; ti++) {
        const Task t = task_of(p.task[cl][ti], rank);
        const int layer = t.layer, ch = t.ch;
        if (t.type == T_END) break;
        if (t.type <= T_OP) {
            const bool qkv = t.type == T_QKV;
            const int nh = (qkv ? 8 : 2) * t.b;
            const unsigned* dep = cnt_ptr(qkv ? (layer ? C_CV : C_ST) : C_O0 + layer, ch);
            const unsigned need = qkv ? (layer ? 32 : ch < 2 ? 0 : 16) : 512;
            const uint16_t mb = t.pair ? 3 : 1 << rank, ma = t.pair ? 1 << rank : 3;
            const int pend = min(nh, gated ? NSTG : 4);
            auto ready = [&](int h) {
                if (t.dry) return true;
                if (h < pend) {
                    unsigned v = 0;
                    if (gated) asm volatile("ld.relaxed.gpu.global.u32 %0,[%1];" : "=r"(v) : "l"(dep) : "memory");
                    return gated && __all_sync(0xffffffffu, v >= need);
                }
                if (!gated) { wait_cnt_warp(g_gate, lds32(sb + S_GATE)); gated = true; }
                if (need) wait_cnt_warp(dep, need);
                return true;
            };
            bool open = true;
            if (qkv) {
#pragma unroll 1
                while (st) { ACQ(0); NEXT; }
#pragma unroll 1
                for (int h = 0; h < nh; h++) {
                    const int blk = qkv_blk(t, h >> 3);
                    ACQ(16384 + (h < 2 ? (layer ? 8192 : 1024) : 0));
                    if (!t.pair || !rank) tma3d_mc(sb + st * STG_B, &p.t3[1][blk >> 6], (h & 7) * 64, blk & 63, sb + B_BAR + (BB_FULL + st) * 8, mb);
                    if (!t.pair || rank) tma3d_mc(sb + st * STG_B + 8192, &p.t3[1][blk >> 6], (h & 7) * 64 + 32, blk & 63, sb + B_BAR + (BB_FULL + st) * 8, mb);
                    NEXT;
                    if (open && h && ready(h + 1)) {
                        open = false;
                        const float2* sp = g_st[layer] + ch * 2048 + (need ? 0 : tag * 256);
                        bulk_g2s1(sb + 16384, sp, layer ? 8192 : 1024, sb + B_BAR + BB_FULL * 8, POL_N);
                        bulk_g2s1(sb + STG_B + 16384, sp + (layer ? 1024 : 128), layer ? 8192 : 1024, sb + B_BAR + (BB_FULL + 1) * 8, POL_N);
                    }
                }
                continue;
            }
            if (PFC && !layer && (t.c & 15) < 8) {
                const int q = (t.c & 15) * 2 + rank;
                asm volatile("{.reg .pred p; elect.sync _|p,0xffffffff; @p cp.async.bulk.prefetch.L2.global [%0],8192; @p cp.async.bulk.prefetch.L2.global [%1],%2;}"
                             ::"l"(g_xA[0] + (ch * 16 + q) * 512), "l"(g_P + q * 16 * 32 * PW), "r"((2 + (ch & 1)) * 32 * PW * 4) : "memory");
            }
            const CUtensorMap *tb = &p.t3[t.pair][3], *ta = &p.ta[t.pair];
            const uint32_t db = sb + 8192 + (t.pair ? rank * 8192 : 0), da = sb + (t.pair ? 0 : rank * 4096);
            const int zb = (t.blk & 63) + (t.pair ? rank * 2 : 0), ya = 4096 + ((layer * 16 + ch) * 64 + t.a) * 16 + (t.pair ? 0 : rank * 8), row = t.a * 64;
            int h = 0;
            const int s0 = st;
#pragma unroll 1
            for (; !ready(h); h++) { ACQ(STG_B); tma3d_mc(db + st * STG_B, tb, row + h * 32, zb, sb + B_BAR + (BB_FULL + st) * 8, mb); NEXT; }
#pragma unroll 1
            for (int k = 0; k < h; k++) {
                const int s2 = (s0 + k) & (NSTG - 1);
                tma2d_mc(da + s2 * STG_B, ta, (k & 1) * 256, ya + (k >> 1) * 16, sb + B_BAR + (BB_FULL + s2) * 8, ma, POL_LAST);
            }
#pragma unroll 1
            for (; h < nh; h++) {
                ACQ(STG_B);
                tma3d_mc(db + st * STG_B, tb, row + h * 32, zb, sb + B_BAR + (BB_FULL + st) * 8, mb);
                tma2d_mc(da + st * STG_B, ta, (h & 1) * 256, ya + (h >> 1) * 16, sb + B_BAR + (BB_FULL + st) * 8, ma, POL_LAST);
                NEXT;
            }
#pragma unroll 1
            for (h = 0; h < 4 && !layer; h++) { ACQ(0); NEXT; }
        } else if (t.type == T_CV) {
            const int q = t.a + rank;
            if (!gated && !t.dry) { wait_cnt_warp(g_gate, lds32(sb + S_GATE)); gated = true; }
            if (layer) {
                wait_cnt_warp(cnt_ptr(C_U, ch - 2), 32);
#pragma unroll 1
                for (int j = ch + 1; j >= 2; j--) {
                    ACQ(16 * PW * 4 + (j > 2 ? 4096 : 0));
                    bulk_g2s1(sb + st * STG_B, g_P + (((q >> 1) * 16 + j) * 2 + (q & 1)) * 16 * PW, 16 * PW * 4, sb + B_BAR + (BB_FULL + st) * 8, POL_N);
                    if (j > 2) bulk_g2s1(sb + st * STG_B + 12288, g_u + (((q >> 1) * 16 + ch + 1 - j) * 2 + (q & 1)) * 256, 4096, sb + B_BAR + (BB_FULL + st) * 8, POL_N);
                    NEXT;
                }
            } else {
#pragma unroll 1
                for (int j = min(ch, 1 + (ch & 1)); j >= 0; j--) {
                    if (j == 0 && ch >= 2) {
                        if (!t.dry) wait_cnt_warp(cnt_ptr(C_H, ch & ~1), 64);
#pragma unroll 1
                        for (int i = 0; i < ((ch & 1) || ch == 2 ? 1 : 2); i++) {
                            ACQ(16384);
                            bulk_g2s1(sb + st * STG_B, g_carry[i] + (ch * 16 + q) * 1024, 16384, sb + B_BAR + (BB_FULL + st) * 8, POL_LAST);
                            NEXT;
                        }
                    }
                    ACQ(32 * PW * 4);
                    bulk_g2s1(sb + st * STG_B, g_P + (q * 16 + j) * 32 * PW, 32 * PW * 4, sb + B_BAR + (BB_FULL + st) * 8, POL_N);
                    NEXT;
                }
            }
        }
    }
}

__device__ __forceinline__ uint4* qkv_dst(int layer, int ch, int w, int blk);
__device__ __forceinline__ uint4* op_dst(int layer, int ch, int slot, int w, uint32_t rank);
__device__ __forceinline__ uint64_t out_pol(int type, int layer, int ch) { return (type == T_QKV ? (!layer && ch > 1) : (layer && ch < 10)) ? POL_LATE : POL_SOON; }
__device__ __forceinline__ void bulk_relay(const Params& p, uint32_t sb, int cl) {
    for (int ti = 0; ti < MAXT; ti++) {
        const int type = p.task[cl][ti] & 7;
        if (type == T_END) break;
        if (type != T_QKV) continue;
        bar_sync(NB_PH, 96);
        const uint32_t ph = lds32(sb + B_ST + 8);
#pragma unroll 1
        for (int h = 2; h < 8; h++) {
            mbar_wait(sb + B_BAR + (BB_FULL + h) * 8, ph);
            if (h == 4 || h == 7) { bar_arrive(NB_REL + (h == 7) * 2, 160); bar_arrive(NB_REL + (h == 7) * 2 + 1, 160); }
        }
    }
}
__device__ __forceinline__ void bulk_release(const Params& p, uint32_t sb, int cl, uint32_t rank, int wg) {
    int nd = 0;
    for (int ti = 0; ti < MAXT; ti++) {
        const Task t = task_of(p.task[cl][ti], rank);
        const int type = t.type, layer = t.layer, ch = t.ch;
        if (type == T_END) break;
        if (type == T_FIN || (type == T_OP && (t.c & 32))) continue;
        if (type == T_OP && !layer) {
            mbar_wait(sb + B_BAR + (BB_DONE + wg) * 8, nd & 1);
            nd++;
            const int s0 = __shfl_sync(0xffffffffu, lds32(sb + B_ST + wg * 4), 0) + wg * 2;
            fence_async_smem();
#pragma unroll 1
            for (int w = 0; w < 4; w++)
                asm volatile("{.reg .pred p; elect.sync _|p,0xffffffff; @p cp.async.bulk.global.shared::cta.bulk_group.L2::cache_hint [%0],[%1],8192,%2; cp.async.bulk.commit_group;}"
                             ::"l"(op_dst(0, ch, t.c & 15, wg * 4 + w, rank)), "r"(sb + ((s0 + (w >> 1)) & (NSTG - 1)) * STG_B + (w & 1) * 8192), "l"(POL_SOON) : "memory");
            mbar_arrive1(sb + B_BAR + (BB_SF + wg) * 8);
            asm volatile("{.reg .pred p; elect.sync _|p,0xffffffff;\n"
                         "cp.async.bulk.wait_group 3; @p red.relaxed.gpu.global.add.u32 [%0],1; cp.async.bulk.wait_group 2; @p red.relaxed.gpu.global.add.u32 [%0+64],1;\n"
                         "cp.async.bulk.wait_group 1; @p red.relaxed.gpu.global.add.u32 [%0+128],1; cp.async.bulk.wait_group 0; @p red.relaxed.gpu.global.add.u32 [%0+192],1;}"
                         ::"l"(cnt_ptr(C_OP0 + rank * 2 + wg, ch)) : "memory");
#pragma unroll 1
            for (int i = 0; i < 8; i++) mbar_arrive1_cluster(mapa(sb + B_BAR + (BB_EMPTY + ((s0 + (i >> 2)) & (NSTG - 1))) * 8, i & 1));
            continue;
        }
#pragma unroll 1
        for (int u = 0; u < (type == T_QKV ? t.b : 1); u++) {
            const int blk = qkv_blk(t, u);
            unsigned* cnt = cnt_ptr(type == T_QKV ? C_QKV0 + layer : type == T_OP ? C_OP1 : layer ? C_H : C_CV, ch + (type == T_QKV && blk < 64 ? 16 : 0));
            const uint4* dst = type == T_QKV ? qkv_dst(layer, ch, wg * 4, blk) : op_dst(1, ch, t.c & 15, wg * 4, (t.blk >> 2) & 1) + 256;
            mbar_wait(sb + B_BAR + (BB_DONE + wg) * 8, nd & 1);
            nd++;
            if (type != T_CV) {
                fence_async_smem();
#pragma unroll
                for (int w = 0; w < 4; w++)
                    asm volatile("{.reg .pred p; elect.sync _|p,0xffffffff; @p cp.async.bulk.global.shared::cta.bulk_group.L2::cache_hint [%0],[%1],4096,%2;}"
                                 ::"l"(dst + (type == T_QKV ? (w >> 1) * 49152 + (w & 1) * 256 : w * 1024)), "r"(sb + B_OUT + (wg * 4 + w) * 4096), "l"(out_pol(type, layer, ch)) : "memory");
                asm volatile("cp.async.bulk.commit_group; cp.async.bulk.wait_group 0;" ::: "memory");
            }
            if (type != T_QKV) fence_async();
            if (!t.dry) asm volatile("{.reg .pred p; elect.sync _|p,0xffffffff; @p red.relaxed.gpu.global.add.u32 [%0],%1;}" ::"l"(cnt), "r"(type == T_QKV ? 2 : type == T_OP ? t.b : 1) : "memory");
            PROF(wg && (threadIdx.x & 31) == 0 && (type == T_CV || u + 2 == t.b), 3900 + ti);
            if (type == T_CV && !layer && !t.dry) {
                asm volatile("{.reg .pred p; elect.sync _|p,0xffffffff; @p cp.async.bulk.global.shared::cta.bulk_group [%0],[%1],4096;\n"
                             "cp.async.bulk.commit_group; cp.async.bulk.wait_group 0; @p red.relaxed.gpu.global.add.u32 [%2],1;}"
                             ::"l"(g_u + ((t.a + rank) * 16 + ch) * 512 + wg * 256), "r"(sb + B_UT + (ch & 1) * 8192 + wg * 4096), "l"(cnt_ptr(C_U, ch)) : "memory");
            }
            mbar_arrive1(sb + B_BAR + (BB_SF + wg) * 8);
        }
        PROF(wg && (threadIdx.x & 31) == 0, 3600 + ti * 4 + 3);
    }
}

__device__ __forceinline__ void stage_release(uint32_t sb, int w, int st) {
    if (!(w & 2)) mbar_arrive1_cluster(mapa(sb + B_BAR + (BB_EMPTY + st) * 8, w & 1));
}
template <bool ACC>
__device__ __forceinline__ void gemm_run(float* acc, uint32_t sb, int w, int h0, int h1, uint32_t& r0, uint32_t& r1, int& st, uint32_t& ph) {
    const uint64_t da0 = mkdesc(sb + (w >> 2) * 4096, 16, 512, 2), db0 = mkdesc(sb + 8192, 4096, 1024, 1);
    const uint32_t rel0 = mapa(sb + B_BAR + BB_EMPTY * 8, w & 1);
#pragma unroll 1
    for (int h = h0; h < h1; h++) {
        const uint64_t da = da0 + st * (STG_B >> 4), db = db0 + st * (STG_B >> 4);
        mbar_wait(sb + B_BAR + (BB_FULL + st) * 8, ph);
        if (ACC) wg_wait<1>();
        wg_fence();
        wgmma256<ACC>(acc, da, db);
        wgmma256<true>(acc, da + 2, db + 128);
        wg_commit();
        if (ACC) mbar_arrive1_cluster((w == 2 && h == LAGH - 1) ? sb + B_BAR + BB_GO * 8 : r0);
        r0 = r1;
        if (!(w & 2)) r1 = rel0 + st * 8;
        if (++st == NSTG) { st = 0; ph ^= 1; }
    }
}

__device__ __forceinline__ uint4* qkv_dst(int layer, int ch, int w, int blk) {
    return g_qkv[layer] + (size_t)((ch * 4 + (w >> 1)) * 32 + ((blk & 63) >> 1)) * 1536 + (blk >> 6) * 512 + (w & 1) * 256;
}
__device__ __forceinline__ uint4* op_dst(int layer, int ch, int slot, int w, uint32_t rank) {
    return g_pp[layer] + (size_t)(ch * MAXSPLIT + slot) * 8192 + (w * 32 + rank * 16) * 32;
}
__device__ __forceinline__ uint32_t ln2(uint32_t x, uint32_t m, uint32_t rh, uint32_t rl) {
    uint32_t d; asm volatile("{.reg .b32 t,u; sub.rn.bf16x2 t,%1,%2; mul.rn.bf16x2 u,t,%4; fma.rn.bf16x2 %0,t,%3,u;}" : "=r"(d) : "r"(x), "r"(m), "r"(rh), "r"(rl)); return d;
}
__device__ __forceinline__ void qkv_task(uint32_t sb, int w, int layer, int ch, int nu, int& ng, int& nd, uint32_t& ph, int ti, uint32_t zero) {
    constexpr int type = T_QKV;
    static_assert(NSTG == 8, "ring");
    const int lane = threadIdx.x & 31;
    const uint64_t db0 = mkdesc(sb, 4096, 1024, 1);
    const uint32_t rel = (w & 2) ? sb + B_BAR + BB_IDLE * 8 : mapa(sb + B_BAR + BB_EMPTY * 8, w & 1), full = sb + B_BAR + BB_FULL * 8;
    const uint32_t lo = sb + B_OUT + w * 4096 + (lane ^ (lane >> 3)) * 16;
    const uint4* xa = g_xA[layer] + (ch * 8 + w) * 1024 + lane;
    uint32_t m0, m1, h0, h1, l0, l1;
    uint4 A[32];
    {
        mbar_wait(full, ph);
        mbar_wait(full + 8, ph);
        CPROF(1);
        const uint32_t sa = sb + (lane >> 4) * STG_B + 16384 + (w * 16 + (lane & 15)) * 8;
        uint2 v[8];
#pragma unroll
        for (int i = 0; i < 8; i++) v[i] = lds64(sa + i * 1024 * layer);
#pragma unroll
        for (int i = 0; i < 4 * QB1; i++) A[i] = ldcg128(xa + i * 32);
        bar_sync(NB_WG + (w >> 2), 128);
        float sm = 0, M2 = 0, D = 0;
#pragma unroll
        for (int i = 0; i < 8; i++) { sm += __uint_as_float(v[i].x); M2 += __uint_as_float(v[i].y); }
        if (!layer) { sm = __uint_as_float(v[0].x); M2 = __uint_as_float(v[0].y); }
        sm += __shfl_xor_sync(0xffffffffu, sm, 16);
#pragma unroll
        for (int i = 0; i < 8; i++) { const float d = __uint_as_float(v[i].x) * (1.f / 32.f) - sm * (1.f / 512.f); D += 32.f * d * d; }
        M2 += layer ? D : sm * sm * (-1.f / 1024.f);
        M2 = fmaxf(M2 + __shfl_xor_sync(0xffffffffu, M2, 16), 0.f);
        const float2 o = ln_finish(sm * (1.f / 512.f), M2 * (1.f / 512.f));
        const float r = rcp(o.y), rh = rbf(r);
        const uint32_t mm = pack2(o.x, o.x), hl = pack2(r - rh, rh);
        m0 = __shfl_sync(0xffffffffu, mm, lane >> 2); m1 = __shfl_sync(0xffffffffu, mm, (lane >> 2) + 8);
        l0 = __shfl_sync(0xffffffffu, hl, lane >> 2); l1 = __shfl_sync(0xffffffffu, hl, (lane >> 2) + 8);
        h0 = __byte_perm(l0, 0, 0x3232); h1 = __byte_perm(l1, 0, 0x3232); l0 = __byte_perm(l0, 0, 0x1010); l1 = __byte_perm(l1, 0, 0x1010);
    }
    float acc[64];
#define QNRM(i) A[i] = make_uint4(ln2(A[i].x, m0, h0, l0), ln2(A[i].y, m1, h1, l1), ln2(A[i].z, m0, h0, l0), ln2(A[i].w, m1, h1, l1))
#pragma unroll
    for (int h = 0; h < 8; h++) {
        const uint64_t db = db0 + h * (STG_B >> 4);
        const int b0 = h == 0 ? QB1 : h == QB1 ? QB2 : h == QB2 ? QB3 : 8, b1 = h == 0 ? QB2 : h == QB1 ? QB3 : 8;
        if (b0 < b1) {
            const uint4* xb = xa + (A[4 * b0 - 1].x & zero);
#pragma unroll
            for (int i = 4 * b0; i < 4 * b1; i++) A[i] = ldcg128(xb + i * 32);
            bar_sync(NB_WG + (w >> 2), 128);
        }
        QNRM(4 * h); QNRM(4 * h + 1); QNRM(4 * h + 2); QNRM(4 * h + 3);
        if (h == 2 || h == 5) bar_sync(NB_REL + (h == 5) * 2 + (w >> 2), 160);
        if (h) wg_wait<1>();
        wg_fence();
        if (h) wgmma128r<true>(acc, A[4 * h], db); else wgmma128r<false>(acc, A[0], db);
        wgmma128r<true>(acc, A[4 * h + 1], db + 128);
        wgmma128r<true>(acc, A[4 * h + 2], db + 512);
        wgmma128r<true>(acc, A[4 * h + 3], db + 640);
        wg_commit();
        if (h >= 2) mbar_arrive1_cluster(rel + (h - 2) * 8);
    }
    ph ^= 1;
#pragma unroll 1
    for (int u = 1;; u++) {
        mbar_wait(sb + B_BAR + (BB_SF + (w >> 2)) * 8, (nd & 1) ^ 1);
        if (u < nu) mbar_wait(full, ph);
        wg_wait<1>();
        mbar_arrive1_cluster(rel + 48);
        wg_wait<0>();
        mbar_arrive1_cluster(rel + 56);
        uint4 o[8];
#pragma unroll
        for (int n = 0; n < 8; n++) {
            const float* a = acc + (n >> 1) * 16 + (n & 1) * 2;
            o[n] = make_uint4(pack2(a[0], a[1]), pack2(a[4], a[5]), pack2(a[8], a[9]), pack2(a[12], a[13]));
            sts128(lo + n * 512, o[n].x, o[n].y, o[n].z, o[n].w);
        }
        __syncwarp();
        mbar_arrive1(sb + B_BAR + (BB_DONE + (w >> 2)) * 8);
        nd++;
        CPROF(min(2 + u, 7));
        if (u == nu) break;
        if (LAGQ) { if (w >> 2) mbar_wait(sb + B_BAR + BB_GO * 8, ng & 1); ng++; }
        const uint64_t db1 = mkdesc(sb + (u >> 10), 4096, 1024, 1);
#pragma unroll
        for (int h = 0; h < 8; h++) {
            const uint64_t db = db1 + h * (STG_B >> 4);
            if (h) { mbar_wait(full + h * 8, ph); wg_wait<1>(); }
            wg_fence();
            if (h) wgmma128r<true>(acc, A[4 * h], db); else wgmma128r<false>(acc, A[0], db);
            wgmma128r<true>(acc, A[4 * h + 1], db + 128);
            wgmma128r<true>(acc, A[4 * h + 2], db + 512);
            wgmma128r<true>(acc, A[4 * h + 3], db + 640);
            wg_commit();
            if (h >= 2) mbar_arrive1_cluster(rel + (h - 2) * 8);
            if (h == LAGQ - 1 && w == 2) mbar_arrive1(sb + B_BAR + BB_GO * 8);
        }
        ph ^= 1;
    }
}

template <int NB>
__device__ __forceinline__ void load_resid(uint32_t* r, int layer, int ch, int w, int cb) {
#pragma unroll
    for (int i = 0; i < NB; i++) {
        const uint4 v = ldcg128(g_xA[layer] + ((ch * 8 + w) * 32 + cb + i) * 32 + (threadIdx.x & 31));
        r[4 * i] = v.x; r[4 * i + 1] = v.y; r[4 * i + 2] = v.z; r[4 * i + 3] = v.w;
    }
}
template <int NS>
__device__ __forceinline__ void part_load(uint4* v, int layer, int ch, int w, int cb, int ns) {
    const uint4* src = g_pp[layer] + (size_t)ch * MAXSPLIT * 8192 + (w * 32 + cb) * 32 + (threadIdx.x & 31);
#pragma unroll
    for (int i = 0; i < 2 * NS; i++) {
        asm volatile("{.reg .pred p; .reg .b128 t; setp.gt.s32 p,%6,0; mov.b128 t,{0,0,0,0}; @p ld.relaxed.gpu.global.L2::cache_hint.b128 t,[%4],%5; mov.b128 {%0,%1,%2,%3},t;}"
                     : "=r"(v[i].x), "=r"(v[i].y), "=r"(v[i].z), "=r"(v[i].w) : "l"(src + (i / NS) * 32 + (i % NS) * 8192), "l"(POL_LAST), "r"(ns - i % NS) : "memory");
    }
}
template <int NS>
__device__ __forceinline__ void part_sum(float* x, const uint4* v, const uint32_t* r) {
    const int dg = ((threadIdx.x & 31) >> 2) - 2 * (threadIdx.x & 3);
    const uint32_t idm = dg == 0 ? 0x00003f80u : dg == 1 ? 0x3f800000u : 0u;
#pragma unroll
    for (int b = 0; b < 2; b++) {
        float* y = x + b * 8;
#pragma unroll
        for (int i = 0; i < 8; i++) y[i] = 0;
#pragma unroll
        for (int s = 0; s < NS; s++) { mma8(y, v[b * NS + s].x, v[b * NS + s].y, idm); mma8(y + 4, v[b * NS + s].z, v[b * NS + s].w, idm); }
#pragma unroll
        for (int i = 0; i < 4; i++) { y[2 * i] = rbf(rbf(y[2 * i]) + blo(r[b * 4 + i])); y[2 * i + 1] = rbf(rbf(y[2 * i + 1]) + bhi(r[b * 4 + i])); }
    }
}

__device__ __forceinline__ float4 row_stats32(const float* x) {
    float a = (x[0] + x[1]) + (x[4] + x[5]) + (x[8] + x[9]) + (x[12] + x[13]);
    float b = (x[2] + x[3]) + (x[6] + x[7]) + (x[10] + x[11]) + (x[14] + x[15]);
    a += __shfl_xor_sync(0xffffffffu, a, 1); b += __shfl_xor_sync(0xffffffffu, b, 1);
    a += __shfl_xor_sync(0xffffffffu, a, 2); b += __shfl_xor_sync(0xffffffffu, b, 2);
    const float ma = a * (1.f / 32.f), mb = b * (1.f / 32.f);
    float qa = 0, qb = 0;
#pragma unroll
    for (int i = 0; i < 4; i++) {
        float d0 = x[4 * i] - ma, d1 = x[4 * i + 1] - ma, d2 = x[4 * i + 2] - mb, d3 = x[4 * i + 3] - mb;
        qa += d0 * d0 + d1 * d1; qb += d2 * d2 + d3 * d3;
    }
    qa += __shfl_xor_sync(0xffffffffu, qa, 1); qb += __shfl_xor_sync(0xffffffffu, qb, 1);
    qa += __shfl_xor_sync(0xffffffffu, qa, 2); qb += __shfl_xor_sync(0xffffffffu, qb, 2);
    return make_float4(a, qa, b, qb);
}

__device__ __forceinline__ void conv_stage(float* Y, uint32_t pbase, uint32_t ubase) {
    const int lane = threadIdx.x & 31, w = threadIdx.x >> 5, g = lane >> 2, c = lane & 3;
#pragma unroll
    for (int cp = 0; cp < 2; cp++) {
        const int chl = w * 4 + cp * 2 + (lane >> 4);
        const uint4 b = ldsm4(ubase + chl * 256 + ((lane >> 3) & 1) * 128 + (((lane & 7) ^ (chl & 7)) << 4));
#pragma unroll
        for (int h = 0; h < 2; h++) {
            const uint32_t pa = pbase + ((w * 4 + cp * 2 + h) * PW + 16 + g - 2 * c) * 4;
            uint32_t lo = lds32(pa - 32);
#pragma unroll
            for (int d = 0; d < 8; d++) {
                const uint32_t a0 = lds32(pa + d * 64), a1 = lds32(pa + d * 64 + 32);
                mma16(Y + ((cp * 2 + h) * 8 + d) * 4, a0, a1, lo, a0, h ? b.z : b.x, h ? b.w : b.y);
                lo = a1;
            }
        }
    }
}

__device__ __forceinline__ void conv_combine(const float* y8, float* cur, float* nxt) {
    const int lane = threadIdx.x & 31, c = lane & 3;
    cur[0] = y8[0]; cur[1] = y8[1] + y8[4]; cur[2] = y8[2]; cur[3] = y8[3] + y8[6];
    nxt[0] = y8[29]; nxt[1] = 0.f; nxt[2] = y8[31]; nxt[3] = 0.f;
#pragma unroll
    for (int e = 1; e < 4; e++) {
        const int src = (lane & ~3) | ((c - e) & 3);
        const float v0 = __shfl_sync(0xffffffffu, y8[8 * e] + y8[8 * e - 3], src), v1 = __shfl_sync(0xffffffffu, y8[8 * e + 1] + y8[8 * e + 4], src);
        const float v2 = __shfl_sync(0xffffffffu, y8[8 * e + 2] + y8[8 * e - 1], src), v3 = __shfl_sync(0xffffffffu, y8[8 * e + 3] + y8[8 * e + 6], src);
        if (c >= e) { cur[0] += v0; cur[1] += v1; cur[2] += v2; cur[3] += v3; }
        else { nxt[0] += v0; nxt[1] += v1; nxt[2] += v2; nxt[3] += v3; }
    }
}

__device__ __forceinline__ void hist_task(float* Y, uint32_t sb, int w, int ch, int q, int& st, uint32_t& ph, int nd) {
    const int lane = threadIdx.x & 31, chl = w * 2 + (lane >> 4);
    const uint32_t ua = sb + 12288 + chl * 256 + ((lane >> 3) & 1) * 128 + (((lane & 7) ^ (chl & 7)) << 4);
    const uint32_t pa = sb + (w * 2 * PW + 16 + (lane >> 2) - 2 * (lane & 3)) * 4;
#pragma unroll
    for (int i = 0; i < 128; i++) Y[i] = 0;
    uint4 b1 = make_uint4(0, 0, 0, 0);
#pragma unroll 1
    for (int j = ch + 1; j >= 2; j--) {
        const uint4 b0 = b1;
        mbar_wait(sb + B_BAR + (BB_FULL + st) * 8, ph);
        b1 = ldsm4(ua + st * STG_B);
        if (j == 2) b1 = make_uint4(0, 0, 0, 0);
#pragma unroll
        for (int h = 0; h < 2; h++) {
            const uint32_t o = pa + st * STG_B + h * PW * 4;
            uint32_t lo = lds32(o - 32);
#pragma unroll
            for (int d = 0; d < 8; d++) {
                const uint32_t a0 = lds32(o + d * 64), a1 = lds32(o + d * 64 + 32);
                mma16(Y + (h * 16 + d) * 4, a0, a1, lo, a0, h ? b0.z : b0.x, h ? b0.w : b0.y);
                mma16(Y + (h * 16 + 8 + d) * 4, a0, a1, lo, a0, h ? b1.z : b1.x, h ? b1.w : b1.y);
                lo = a1;
            }
        }
        bar_sync(NB_WG + (w >> 2), 128);
        stage_release(sb, w, st);
        if (++st == NSTG) { st = 0; ph ^= 1; }
    }
    mbar_wait(sb + B_BAR + (BB_SF + (w >> 2)) * 8, (nd & 1) ^ 1);
#pragma unroll
    for (int h = 0; h < 2; h++) {
        const int o = ((ch * 16 + (q >> 1)) * 4 + (w & 1) * 2 + h) * 256 + ((q & 1) * 4 + (w >> 1)) * 32 + lane;
        float c0[4], n0[4], c1[4], n1[4];
        conv_combine(Y + h * 64, c0, n0); conv_combine(Y + h * 64 + 32, c1, n1);
        g_carry[0][o] = make_float4(c0[0], c0[1], c0[2], c0[3]);
        g_carry[0][o + 16384] = make_float4(c1[0] + n0[0], c1[1] + n0[1], c1[2] + n0[2], c1[3] + n0[3]);
        g_carry[1][o + 32768] = make_float4(n1[0], n1[1], n1[2], n1[3]);
    }
}

__device__ __forceinline__ void conv_task(const Params& p, float* Y, uint32_t sb, int w, int ch, int q, int ns, bool dry, int& st, uint32_t& ph, int nd) {
    const int tid = threadIdx.x, lane = tid & 31, g = lane >> 2, c = lane & 3;
    uint32_t dk[4];
    const uint32_t sg = (~ch & 2) << 30;
    int sr = st;
    float x[16];
    PROF(tid == 128, 2048 + ch * 8);
#pragma unroll
    for (int i = 0; i < 128; i++) Y[i] = 0;
#pragma unroll 1
    for (int j = min(ch, 1 + (ch & 1)); j >= 1; j--) {
        mbar_wait(sb + B_BAR + (BB_FULL + st) * 8, ph);
        conv_stage(Y, sb + st * STG_B, sb + B_UT + ((ch - j) & 1) * 8192);
        if (++st == NSTG) { st = 0; ph ^= 1; }
    }
#define CONV_CARRY _Pragma("unroll 1") \
    for (int i = 0; i < min(ch, (ch & 1) ? 2 : 3); i++) { \
        if (i) mbar_wait(sb + B_BAR + (BB_FULL + st) * 8, ph); \
        const uint32_t ca = sb + (i ? st * STG_B : B_SP) + tid * 16; \
_Pragma("unroll") \
        for (int k = 0; k < 4; k++) { \
            const uint4 cr = lds128(ca + k * 4096); \
            Y[k * 32] += __uint_as_float(cr.x); Y[k * 32 + 1] += __uint_as_float(cr.y); Y[k * 32 + 2] += __uint_as_float(cr.z); Y[k * 32 + 3] += __uint_as_float(cr.w); \
        } \
        if (i && ++st == NSTG) { st = 0; ph ^= 1; } \
    } \
    bar_sync(NB_C, 256); \
_Pragma("unroll 1") \
    for (; sr != st; sr = (sr + 1) & (NSTG - 1)) stage_release(sb, w, sr); \
    mbar_wait(sb + B_BAR + (BB_SF + (w >> 2)) * 8, (nd & 1) ^ 1); \
    mbar_wait(sb + B_BAR + (BB_SF + 1 - (w >> 2)) * 8, (nd & 1) ^ 1);
    const uint32_t ut = sb + B_UT + (ch & 1) * 8192;
    if (CPOS == 0) { CONV_CARRY }
    PROF(tid == 128, 2048 + ch * 8 + 7);
    {
        uint4 v[2 * OPS1];
        wait_cnt_warp(cnt_ptr(C_OP0 + (q >> 3) * 2 + (w >> 2), ch + (w & 3) * 16), ns);
        part_load<OPS1>(v, 0, ch, w, 2 * q, ns);
        uint32_t rs[8];
        load_resid<2>(rs, 0, ch, w, 2 * q);
        if (CPOS == 1) { CONV_CARRY }
        part_sum<OPS1>(x, v, rs);
        const float4 s = row_stats32(x);
        float2* dst = g_st2 + ((ch & 1) * 16 + q) * 128 + w * 16 + g + c * 8;
        asm volatile("{.reg .pred p; setp.ne.u32 p,%2,0; @p st.relaxed.gpu.global.b64 [%0],%1;}" ::"l"(dst),
                     "l"(((uint64_t)((__float_as_uint(c ? s.w : s.y) & 0x7fffffffu) | sg) << 32) | __float_as_uint(c ? s.z : s.x)), "r"((uint32_t)(c < 2 && !dry)) : "memory");
        PROF(tid == 128, 2048 + ch * 8 + 1);
    }
#pragma unroll
    for (int i = 0; i < 4; i++) asm volatile("ld.global.nc.u32 %0,[%1];" : "=r"(dk[i]) : "l"(p.Dskip + q * 32 + i * 8 + 2 * c));
    if (CPOS == 2) { CONV_CARRY }
    float2 ln0, ln1;
    {
        const float2* src = g_st2 + ((ch & 1) * 16 + (lane >> 4) * 8) * 128 + w * 16 + (lane & 15);
        uint64_t v[8];
        int n = 0;
#pragma unroll
        for (int i = 0; i < 8; i++) v[i] = (uint64_t)~sg << 32;
        while (true) {
            bool bad = false;
#pragma unroll
            for (int i = 0; i < 8; i++) asm volatile("{.reg .pred p; setp.lt.s32 p,%2,0; @p ld.relaxed.gpu.global.b64 %0,[%1];}" : "+l"(v[i]) : "l"(src + i * 128), "r"((uint32_t)(v[i] >> 32) ^ sg) : "memory");
#pragma unroll
            for (int i = 0; i < 8; i++) bad = bad || (int)((uint32_t)(v[i] >> 32) ^ sg) < 0;
            if (!__any_sync(0xffffffffu, bad && !dry)) break;
            if (++n > 2000000) __trap();
        }
        float sm = 0;
#pragma unroll
        for (int i = 0; i < 8; i++) sm += __uint_as_float((uint32_t)v[i]);
        sm += __shfl_xor_sync(0xffffffffu, sm, 16);
        const float mean = sm * (1.f / 512.f);
        float M2 = 0;
#pragma unroll
        for (int i = 0; i < 8; i++) { const float d = __uint_as_float((uint32_t)v[i]) * (1.f / 32.f) - mean; M2 += fabsf(__uint_as_float((uint32_t)(v[i] >> 32))) + 32.f * d * d; }
        M2 += __shfl_xor_sync(0xffffffffu, M2, 16);
        const float2 o = ln_finish(mean, M2 * (1.f / 512.f));
        ln0.x = __shfl_sync(0xffffffffu, o.x, g); ln0.y = __shfl_sync(0xffffffffu, o.y, g);
        ln1.x = __shfl_sync(0xffffffffu, o.x, g + 8); ln1.y = __shfl_sync(0xffffffffu, o.y, g + 8);
    }
    PROF(tid == 128, 2048 + ch * 8 + 2);
    uint32_t u[8];
#pragma unroll
    for (int i = 0; i < 8; i++) {
        const float2 l = (i & 1) ? ln1 : ln0;
        u[i] = pack2(__fdividef(rbf(x[2 * i] - l.x), l.y), __fdividef(rbf(x[2 * i + 1] - l.x), l.y));
        const int chl = (i >> 1) * 8 + g;
        sts32(ut + chl * 256 + (i & 1) * 128 + ((w ^ g) << 4) + c * 4, movm(u[i]));
    }
    bar_sync(NB_C, 256);
    mbar_wait(sb + B_BAR + (BB_FULL + st) * 8, ph);
    PROF(tid == 128, 2048 + ch * 8 + 3);
    conv_stage(Y, sb + st * STG_B, ut);
    uint32_t yp[4][2];
    float nxt[4][4];
    {
        float y[4][4];
#pragma unroll
        for (int k = 0; k < 4; k++) conv_combine(Y + k * 32, y[k], nxt[k]);
#pragma unroll
        for (int i = 0; i < 4; i++) { yp[i][0] = pack2(y[0][i], y[1][i]); yp[i][1] = pack2(y[2][i], y[3][i]); }
    }
#pragma unroll
    for (int i = 0; i < 4; i++) sts64(sb + B_YT + (16 * (2 * c + (i & 1)) + g + (i >> 1) * 8) * 80 + w * 8, yp[i][0], yp[i][1]);
    bar_sync(NB_C, 256);
    stage_release(sb, w, st);
    if (++st == NSTG) { st = 0; ph ^= 1; }
    PROF(tid == 128, 2048 + ch * 8 + 4);
    uint32_t xo[8];
    uint4* dA = g_xA[1] + ((ch * 8 + w) * 32 + 2 * q) * 32 + lane;
#pragma unroll
    for (int i = 0; i < 8; i++) {
        const int col = (i >> 1) * 8 + 2 * c;
        const uint32_t yv = lds32(sb + B_YT + (w * 16 + g + (i & 1) * 8) * 80 + col * 2);
        const uint32_t dv = dk[i >> 1];
        x[2 * i] = rbf(x[2 * i] + rbf(blo(yv) + rbf(blo(u[i]) * blo(dv))));
        x[2 * i + 1] = rbf(x[2 * i + 1] + rbf(bhi(yv) + rbf(bhi(u[i]) * bhi(dv))));
        xo[i] = pack2(x[2 * i], x[2 * i + 1]);
        if ((i & 3) == 3) dA[(i >> 2) * 32] = make_uint4(xo[i - 3], xo[i - 2], xo[i - 1], xo[i]);
    }
    {
        const float4 s = row_stats32(x);
        float2* dst = g_st[1] + (ch * 16 + q) * 128 + w * 16 + g;
        if (c == 0) dst[0] = make_float2(s.x, s.y);
        if (c == 1) dst[8] = make_float2(s.z, s.w);
        __syncwarp();
    }
    PROF(tid == 128, 2048 + ch * 8 + 5);
    mbar_arrive1(sb + B_BAR + (BB_DONE + (w >> 2)) * 8);
    bar_sync(NB_C, 256);
#pragma unroll
    for (int k = 0; k < 4; k++) sts128(sb + B_SP + k * 4096 + tid * 16, __float_as_uint(nxt[k][0]), __float_as_uint(nxt[k][1]), __float_as_uint(nxt[k][2]), __float_as_uint(nxt[k][3]));
    PROF(tid == 128, 2048 + ch * 8 + 6);
}

__device__ __forceinline__ void out_store(const Params& p, const float* x, int ch, int cb) {
    const int lane = threadIdx.x & 31, w = threadIdx.x >> 5, g = lane >> 2, c = lane & 3;
#pragma unroll
    for (int h = 0; h < 2; h++) {
        const float* y = x + h * 2;
        uint32_t v0 = pack2(y[0], y[1]), v1 = pack2(y[4], y[5]), v2 = pack2(y[8], y[9]), v3 = pack2(y[12], y[13]);
        uint32_t t0 = (c & 1) ? v0 : v1, t1 = (c & 1) ? v2 : v3;
        t0 = __shfl_xor_sync(0xffffffffu, t0, 1); t1 = __shfl_xor_sync(0xffffffffu, t1, 1);
        if (c & 1) { v0 = t0; v2 = t1; } else { v1 = t0; v3 = t1; }
        t0 = (c & 2) ? v0 : v2; t1 = (c & 2) ? v1 : v3;
        t0 = __shfl_xor_sync(0xffffffffu, t0, 2); t1 = __shfl_xor_sync(0xffffffffu, t1, 2);
        if (c & 2) { v0 = t0; v1 = t1; } else { v2 = t0; v3 = t1; }
        stg128((uint4*)(p.out + (size_t)(ch * 128 + w * 16 + g + h * 8) * 512 + cb * 16 + c * 8), make_uint4(v0, v1, v2, v3), POL_LATE);
    }
}
__device__ __forceinline__ void fin_task(const Params& p, int ch, int cb0, int ncb, int ns, bool dry) {
    const int w = threadIdx.x >> 5;
    uint32_t rs[8];
    wait_cnt_warp(cnt_ptr(C_CV, ch), dry ? 0 : 32);
    load_resid<2>(rs, 1, ch, w, cb0);
    wait_cnt_warp(cnt_ptr(C_OP1, ch), dry ? 0 : 256);
    for (int cb = cb0; cb < cb0 + ncb; cb += 2) {
        float x[16];
        if (cb != cb0) load_resid<2>(rs, 1, ch, w, cb);
        uint4 v[32];
        part_load<16>(v, 1, ch, w, cb, ns);
        part_sum<16>(x, v, rs);
        out_store(p, x, ch, cb);
    }
}

__device__ __forceinline__ void bulk_consumer(const Params& p, uint32_t sb, int cl, uint32_t rank, int w) {
    int st = 0; uint32_t ph = 0; int nd = 0, ng = 0;
    for (int ti = 0; ti < MAXT; ti++) {
        const Task t = task_of(p.task[cl][ti], rank);
        const int type = t.type, layer = t.layer, ch = t.ch;
        if (type == T_END) break;
        bool staged = type != T_FIN;
        PROF(threadIdx.x == 0, 3600 + ti * 4);
        CPROF(0);
        if (type == T_QKV) {
            staged = false;
            #pragma unroll 1
            while (st) {
                if (!(w & 3)) { mbar_wait(sb + B_BAR + (BB_FULL + st) * 8, ph); stage_release(sb, 0, st); stage_release(sb, 1, st); }
                if (++st == NSTG) { st = 0; ph ^= 1; }
            }
            if (!(w & 3)) { sts32(sb + B_ST + 8, ph); bar_arrive(NB_PH, 96); }
            qkv_task(sb, w, layer, ch, t.b, ng, nd, ph, ti, p.zero);
            PROF(threadIdx.x == 128, 3600 + ti * 4 + 1);
        } else if (type == T_OP) {
            const int lane = threadIdx.x & 31;
            float acc[128];
            uint32_t r0 = sb + B_BAR + BB_IDLE * 8, r1 = r0;
            if (w >> 2) mbar_wait(sb + B_BAR + BB_GO * 8, ng & 1);
            ng++;
            gemm_run<false>(acc, sb, w, 0, 1, r0, r1, st, ph);
            gemm_run<true>(acc, sb, w, 1, 2 * t.b, r0, r1, st, ph);
            mbar_wait(sb + B_BAR + (BB_SF + (w >> 2)) * 8, (nd & 1) ^ 1);
            wg_wait<1>();
            mbar_arrive1_cluster(r0);
            wg_wait<0>();
            mbar_arrive1_cluster(r1);
            PROF(threadIdx.x == 128, 3600 + ti * 4 + 1);
            if (t.c & 32) {
                staged = false;
                const int dg = (lane >> 2) - 2 * (lane & 3);
                const uint32_t idm = dg == 0 ? 0x00003f80u : dg == 1 ? 0x3f800000u : 0u;
                wait_cnt_warp(cnt_ptr(C_OP1, ch), 256 - 4 * t.b);
#pragma unroll 1
                for (int i = 0; i < (t.c & 15); i++) {
                    const uint4* src = op_dst(1, ch, i, w, (t.blk >> 2) & 1) + lane;
                    uint4 v[16];
#pragma unroll
                    for (int j = 0; j < 16; j++) v[j] = ldcg128_last(src + j * 32);
#pragma unroll
                    for (int j = 0; j < 16; j++) { mma8(acc + j * 8, v[j].x, v[j].y, idm); mma8(acc + j * 8 + 4, v[j].z, v[j].w, idm); }
                }
#pragma unroll
                for (int j = 0; j < 16; j += 4) {
                    uint32_t rs[16];
                    load_resid<4>(rs, 1, ch, w, (t.blk & 4) * 4 + j);
#pragma unroll
                    for (int i = 0; i < 16; i++) { float* y = acc + j * 8 + 2 * i; y[0] = rbf(y[0]) + blo(rs[i]); y[1] = rbf(y[1]) + bhi(rs[i]); }
                    out_store(p, acc + j * 8, ch, (t.blk & 4) * 4 + j); out_store(p, acc + j * 8 + 16, ch, (t.blk & 4) * 4 + j + 2);
                }
            } else if (!layer) {
                const int s2 = st + (w >> 1);
                const uint32_t o = sb + (s2 & (NSTG - 1)) * STG_B + (w & 1) * 8192 + lane * 16;
                mbar_wait(sb + B_BAR + (BB_FULL + (s2 & (NSTG - 1))) * 8, ph ^ (s2 >= NSTG));
#pragma unroll
                for (int j = 0; j < 16; j++)
                    sts128(o + j * 512, pack2(acc[j * 8], acc[j * 8 + 1]), pack2(acc[j * 8 + 2], acc[j * 8 + 3]), pack2(acc[j * 8 + 4], acc[j * 8 + 5]), pack2(acc[j * 8 + 6], acc[j * 8 + 7]));
                sts32(sb + B_ST + (w >> 2) * 4, st);
                st += 4;
                if (st >= NSTG) { st -= NSTG; ph ^= 1; }
            } else {
                uint4* dst = op_dst(layer, ch, t.c & 15, w, (t.blk >> 2) & 1) + lane;
#pragma unroll
                for (int n = 0; n < 16; n++) {
                    const int j = (n >> 1) + (n & 1) * 8;
                    const uint4 v = make_uint4(pack2(acc[j * 8], acc[j * 8 + 1]), pack2(acc[j * 8 + 2], acc[j * 8 + 3]), pack2(acc[j * 8 + 4], acc[j * 8 + 5]), pack2(acc[j * 8 + 6], acc[j * 8 + 7]));
                    if (j < 16 - NSB) stg128(dst + j * 32, v, out_pol(T_OP, layer, ch)); else sts128(sb + B_OUT + (w * NSB + j - (16 - NSB)) * 512 + lane * 16, v.x, v.y, v.z, v.w);
                }
            }
        } else if (type == T_CV) {
            float acc[128];
            if (layer) hist_task(acc, sb, w, ch, t.a + rank, st, ph, nd);
            else { conv_task(p, acc, sb, w, ch, t.a + rank, t.b, t.dry, st, ph, nd); staged = false; nd++; }
        } else {
            fin_task(p, ch, t.a + rank * t.c, t.c, t.b, t.dry);
        }
        if (staged) {
            __syncwarp();
            mbar_arrive1(sb + B_BAR + (BB_DONE + (w >> 2)) * 8);
            nd++;
        }
        PROF(threadIdx.x == 128, 3600 + ti * 4 + 2);
        __syncwarp();
    }
}

constexpr int P_Y = 131072  , P_PRM = P_Y  , P_K6 = P_PRM + 8192  ,
              P_P = P_Y + 40960  , P_U = P_P + 33280  , P_END = P_U + 17408, P_X = 98304  ;
static_assert(P_END <= B_BAR && P_END <= R_BAR, "prologue scratch");
#define KGUN 2
constexpr int KGU = KGUN;
__device__ __forceinline__ void csq(float& r, float& i) { const float t = r * i; r = fmaf(r, r, -(i * i)); i = t + t; }
__device__ __forceinline__ void cpow(float ar, float ph, float p, float& r, float& i) {
    const float e = ex2(ar * p);
    const float u = ph * p, n = fabsf(u) < 4194304.f ? (u + 12582912.f) - 12582912.f : u;
    const float t = (u - n) * 6.283185307179586f;
    r = e * __cosf(t); i = e * __sinf(t);
}
__device__ __forceinline__ void mma_tf32(float* c, float a0, float a1, float a2, float a3, float b0, float b1) {
    asm volatile("mma.sync.aligned.m16n8k8.row.col.f32.tf32.tf32.f32 {%0,%1,%2,%3},{%4,%5,%6,%7},{%8,%9},{%0,%1,%2,%3};"
                 : "+f"(c[0]), "+f"(c[1]), "+f"(c[2]), "+f"(c[3])
                 : "r"(__float_as_uint(a0)), "r"(__float_as_uint(a1)), "r"(__float_as_uint(a2)), "r"(__float_as_uint(a3)), "r"(__float_as_uint(b0)), "r"(__float_as_uint(b1)));
}

struct ProRegs { uint32_t v[2][4], ldt[2]; };
__device__ __forceinline__ void prologue_load(const ProArgs& a, int b, ProRegs& pr) {
    const int w = threadIdx.x >> 5;
#pragma unroll
    for (int i = 0; i < 2; i++) {
        const int gi = b * 512 + (w & 3) * 128 + ((w >> 2) & 1) * 64 + i * 32 + (threadIdx.x & 31);
        pr.ldt[i] = __ldg((const uint16_t*)a.ldt + b * 4 + (w & 3));
        pr.v[i][0] = __ldg((const uint16_t*)a.lAr + gi); pr.v[i][1] = __ldg((const uint16_t*)a.Ai + gi);
        pr.v[i][2] = __ldg((const uint16_t*)a.Cr + gi); pr.v[i][3] = __ldg((const uint16_t*)a.Ci + gi);
    }
}
__device__ __forceinline__ void prologue(const ProArgs& a, uint32_t sb, int b, int w, const ProRegs& pr) {
    const int tid = threadIdx.x, lane = tid & 31, g = lane >> 2, c = lane & 3;
    const int d0 = b * 4;
    if (w >= 8) {
        const int t2 = tid - 256;
        if (w < 10) {
            const int row = b * 16 + (w - 8) * 8 + g;
            const float4 r4 = row_stats((const uint4*)(a.x + (size_t)row * 512) + c, 4);
            const float2 r = make_float2(r4.x + r4.z, r4.y + r4.w);
            const float2 l = ln_finish(r.x * (1.f / 512.f), fmaxf(r.y - r.x * r.x * (1.f / 512.f), 0.f) * (1.f / 512.f));
            if (c == (g >> 1)) asm volatile("st.relaxed.gpu.global.u32 [%0],%1;" ::"l"(g_ln0 + row), "r"(pack2(l.x, l.y)) : "memory");
        }
        PROF(t2 == 0, 3516);
        const int gi = b * 128 + t2;
        if (t2 < 32) acc_init(a.mem0, b * 32 + t2);
        if (t2 >= 112) ((uint4*)g_st2)[b * 16 + t2 - 112] = make_uint4(0, 0, 0, 0);
        if (gi < 13 * 64) g_cnt[gi] = 0;
        bar_sync(6, 384);
        if (gi < 512) g_st[0][(gi >> 8) * 2048 + (lds32(sb + S_TAG) ^ 1) * 256 + (gi & 255)] = make_float2(0.f, 0.f);
        asm volatile("{.reg .pred p; elect.sync _|p,0xffffffff; @p cp.async.bulk.prefetch.L2.global [%0],32768;}"
                     ::"l"((w == 8 ? a.Wq : w == 9 ? a.Wk : w == 10 ? a.Wv : a.Wo) + (size_t)b * 16384) : "memory");
        mbar_wait(sb + S_XBAR, 0);
#pragma unroll 1
        for (int h = 0; h < 2; h++) {
            uint32_t l[8];
            int n = 0;
            while (true) {
                bool ok = true;
#pragma unroll
                for (int i = 0; i < 8; i++) asm volatile("ld.relaxed.gpu.global.u32 %0,[%1];" : "=r"(l[i]) : "l"(g_ln0 + h * 1024 + i * 128 + t2) : "memory");
#pragma unroll
                for (int i = 0; i < 8; i++) ok = ok && l[i];
                if (__all_sync(0xffffffffu, ok)) break;
                if (++n > 2000000) __trap();
            }
#pragma unroll
            for (int i = 0; i < 8; i++) {
                const int t = h * 1024 + i * 128 + t2;
                const uint2 x = lds64(sb + P_X + t * 16 + (b & 1) * 8);
                const float m = blo(l[i]), rs = rcp(bhi(l[i]));
                const uint32_t u0 = pack2(rbf(blo(x.x) - m) * rs, rbf(bhi(x.x) - m) * rs), u1 = pack2(rbf(blo(x.y) - m) * rs, rbf(bhi(x.y) - m) * rs);
                sts128(sb + P_X + t * 16, x.x, x.y, u0, u1);
                const uint32_t o = sb + P_U + ((t >> 3) & 1) * 2176 + ((t >> 4) + 8) * 16 + (t & 7) * 2;
                asm volatile("st.shared.u16 [%0],%1;" ::"r"(o), "h"((uint16_t)u0) : "memory");
                asm volatile("st.shared.u16 [%0],%1;" ::"r"(o + 4352), "h"((uint16_t)(u0 >> 16)) : "memory");
                asm volatile("st.shared.u16 [%0],%1;" ::"r"(o + 8704), "h"((uint16_t)u1) : "memory");
                asm volatile("st.shared.u16 [%0],%1;" ::"r"(o + 13056), "h"((uint16_t)(u1 >> 16)) : "memory");
            }
        }
        PROF(t2 == 0, 3517);
        bar_sync(9, 384);
        fence_async_smem();
#pragma unroll 1
        for (int j = 0; j < 16; j++) {
            const int d = d0 + w - 8;
            asm volatile("{.reg .pred p; elect.sync _|p,0xffffffff; @p cp.async.bulk.global.shared::cta.bulk_group [%0],[%1],%2;}" ::"l"(g_P + (((d >> 5) * 16 + j) * 32 + (d & 31)) * PW),
                         "r"(sb + P_P + ((w - 8) * 2080 + j * 128) * 4), "r"(PW * 4) : "memory");
        }
        asm volatile("cp.async.bulk.commit_group; cp.async.bulk.wait_group 0;" ::: "memory");
        bar_arrive(10, 384);
        return;
    }
#pragma unroll
    for (int i = 0; i < 2; i++) {
        const float dt = rbf(expf(blo(pr.ldt[i])));
        const float ar = -rbf(expf(blo(pr.v[i][0]))) * dt, ai = blo(pr.v[i][1]) * dt;
        sts128(sb + P_PRM + (w * 64 + i * 32 + lane) * 16, __float_as_uint(ar * 1.4426950408889634f), __float_as_uint(ai * 0.15915494309189535f),
               __float_as_uint(2.f * (blo(pr.v[i][2]) * dt)), __float_as_uint(2.f * (blo(pr.v[i][3]) * dt)));
    }
    if (tid < 64) sts128(sb + P_U + (tid >> 3) * 2176 + (tid & 7) * 16, 0, 0, 0, 0);
    bar_arrive(6, 384);
    __syncwarp();
    PROF(tid == 0, 3510);
    const int ch = w & 3, hf = w >> 2;
    {
        float k0[4] = {0, 0, 0, 0}, k1[4] = {0, 0, 0, 0}, k2[4] = {0, 0, 0, 0}, k3[4] = {0, 0, 0, 0}, k4[4] = {0, 0, 0, 0}, kl = 0;
#pragma unroll KGU
        for (int j = 0; j < 16; j++) {
            const uint4 q = lds128(sb + P_PRM + (w * 64 + j * 4 + c) * 16);
            const float cr = __uint_as_float(q.z), ci = __uint_as_float(q.w);
            float wr[4], wi[4], vr[4], vi[4];
            cpow(__uint_as_float(q.x), __uint_as_float(q.y), (float)g, wr[0], wi[0]);
            cpow(__uint_as_float(q.x), __uint_as_float(q.y), (float)(g + 8), vr[0], vi[0]);
#pragma unroll
            for (int i = 1; i < 4; i++) { wr[i] = wr[i - 1]; wi[i] = wi[i - 1]; csq(wr[i], wi[i]); vr[i] = vr[i - 1]; vi[i] = vi[i - 1]; csq(vr[i], vi[i]); }
            float hr = wr[3], hi = wi[3];
            csq(hr, hi);
            mma_tf32(k0, wr[0], vr[0], wi[0], vi[0], cr * hr - ci * hi, -(cr * hi + ci * hr));
            hr = vr[3]; hi = vi[3]; csq(hr, hi);
            mma_tf32(k1, wr[0], vr[0], wi[0], vi[0], cr * hr - ci * hi, -(cr * hi + ci * hr));
            csq(hr, hi);
            mma_tf32(k2, wr[1], vr[1], wi[1], vi[1], cr * hr - ci * hi, -(cr * hi + ci * hr));
            csq(hr, hi);
            mma_tf32(k3, wr[2], vr[2], wi[2], vi[2], cr * hr - ci * hi, -(cr * hi + ci * hr));
            csq(hr, hi);
            mma_tf32(k4, wr[3], vr[3], wi[3], vi[3], cr * hr - ci * hi, -(cr * hi + ci * hr));
            csq(hr, hi);
            kl += cr * hr - ci * hi;
        }
        kl += __shfl_xor_sync(0xffffffffu, kl, 1); kl += __shfl_xor_sync(0xffffffffu, kl, 2);
        const uint32_t o = sb + P_K6 + (ch * 656 + c * 32 + g) * 4, ol = sb + P_K6 + (ch * 656 + 640) * 4;
#define KST(k, base) sts32(o + (base) * 4, __float_as_uint(k[0])); sts32(o + (base) * 4 + 64, __float_as_uint(k[1])); \
                     sts32(o + (base) * 4 + 32, __float_as_uint(k[2])); sts32(o + (base) * 4 + 96, __float_as_uint(k[3]))
#define KAD(k, base) k[0] += __uint_as_float(lds32(o + (base) * 4)); k[1] += __uint_as_float(lds32(o + (base) * 4 + 64)); \
                     k[2] += __uint_as_float(lds32(o + (base) * 4 + 32)); k[3] += __uint_as_float(lds32(o + (base) * 4 + 96))
        if (hf == 0) {
            bar_sync(2 + ch, 64);
            KAD(k0, 0); KAD(k1, 128); KAD(k2, 256); KAD(k3, 384); KAD(k4, 512);
            kl += __uint_as_float(lds32(ol));
            __syncwarp();
        }
        KST(k0, 0); KST(k1, 128); KST(k2, 256); KST(k3, 384); KST(k4, 512);
        if (lane == 0) sts32(ol, __float_as_uint(kl));
        if (hf == 1) { __syncwarp(); bar_arrive(2 + ch, 64); }
    }
    PROF(tid == 0, 3511);
    bar_sync(8, 384);
    PROF(tid == 0, 3512);
    if (tid < 64) sts32(sb + P_P + ((tid >> 4) * 2080 + (tid & 15)) * 4, 0);
#pragma unroll 1
    for (int x = tid; x < 2048; x += 512) {
        uint32_t pw[2][4];
#pragma unroll
        for (int h = 0; h < 2; h++) {
            const int y = x + h * 256;
            const int i0 = y <= 256 ? y : 256 + (int)((pack2((float)y, 0.f) & 0xffff) - 0x4380);
            const int i1 = y <= 256 ? max(y - 1, 0) : 256 + (int)((pack2((float)(y - 1), 0.f) & 0xffff) - 0x4380);
#pragma unroll
            for (int k = 0; k < 4; k++) {
                const float lo = __uint_as_float(lds32(sb + P_K6 + k * 2624 + i0 * 4)), hi = __uint_as_float(lds32(sb + P_K6 + k * 2624 + i1 * 4));
                pw[h][k] = pack2(lo, y ? hi : 0.f);
            }
        }
#pragma unroll
        for (int h = 0; h < 2; h++)
#pragma unroll
            for (int k = 0; k < 4; k++) sts32(sb + P_P + (k * 2080 + x + h * 256 + 16) * 4, pw[h][k]);
    }
    bar_sync(9, 384);
    PROF(tid == 0, 3513);
    {
        float acc[16][4];
#pragma unroll
        for (int j = 0; j < 16; j++) acc[j][0] = acc[j][1] = acc[j][2] = acc[j][3] = 0;
#pragma unroll 1
        for (int e = hf * 4; e < hf * 4 + 4; e++) {
            uint32_t B[16][2];
            const uint32_t ua = sb + P_U + ch * 4352 + ((lane >> 3) & 1) * 2176 + (8 + (lane >> 4) * 8 + (lane & 7) - e) * 16;
#pragma unroll
            for (int j = 0; j < 8; j++) { const uint4 v = ldsm4(ua + j * 256); B[2 * j][0] = v.x; B[2 * j][1] = v.y; B[2 * j + 1][0] = v.z; B[2 * j + 1][1] = v.w; }
            const uint32_t pa = sb + P_P + (ch * 2080 + 16 + e * 16 + g - 2 * c) * 4;
#pragma unroll
            for (int d = 0; d < 16; d++) {
                const uint32_t a0 = lds32(pa + d * 512), a1 = lds32(pa + d * 512 + 32), a2 = lds32(pa + d * 512 - 32);
#pragma unroll
                for (int j = d; j < 16; j++) mma16(acc[j], a0, a1, a2, a0, B[j - d][0], B[j - d][1]);
            }
        }
        PROF(tid == 0, 3514);
        const uint32_t o = sb + P_Y + (ch * 2560 + c * 40 + g) * 4;
#pragma unroll
        for (int j = 0; j < 8; j++) {
#pragma unroll
            for (int i = 0; i < 4; i++) { const float lo = acc[j][i], hi = acc[j + 8][i]; acc[j][i] = hf ? hi : lo; sts32(o + (j + 8 - hf * 8) * 640 + (i & 1) * 80 + (i >> 1) * 32, __float_as_uint(hf ? lo : hi)); }
        }
        bar_sync(2 + ch, 64);
#pragma unroll
        for (int j = 0; j < 8; j++) {
#pragma unroll
            for (int i = 0; i < 4; i++) acc[j][i] += __uint_as_float(lds32(o + (j + hf * 8) * 640 + (i & 1) * 80 + (i >> 1) * 32));
        }
#pragma unroll
        for (int j = 0; j < 8; j++) {
#pragma unroll
            for (int i = 0; i < 4; i++) sts32(o + (j + hf * 8) * 640 + (i & 1) * 80 + (i >> 1) * 32, __float_as_uint(acc[j][i]));
        }
    }
    const uint2 dk = __ldg((const uint2*)(a.Dk + d0));
    bar_sync(1, 256);
#pragma unroll 2
    for (int i = 0; i < 8; i++) {
        const int t = i * 256 + tid;
        const uint32_t o = sb + P_Y + (t + 4 * (t >> 4)) * 4;
        const uint4 xu = lds128(sb + P_X + t * 16);
        float y[4];
#pragma unroll
        for (int k = 0; k < 4; k++) y[k] = rbf(__uint_as_float(lds32(o + k * 10240)));
        uint2 r;
        r.x = pack2(blo(xu.x) + rbf(y[0] + rbf(blo(xu.z) * blo(dk.x))), bhi(xu.x) + rbf(y[1] + rbf(bhi(xu.z) * bhi(dk.x))));
        r.y = pack2(blo(xu.y) + rbf(y[2] + rbf(blo(xu.w) * blo(dk.y))), bhi(xu.y) + rbf(y[3] + rbf(bhi(xu.w) * bhi(dk.y))));
        {
            const bool up = t & 8;
            const uint32_t o = __shfl_xor_sync(0xffffffffu, up ? r.x : r.y, 8);
            ((uint2*)(g_xA[0] + ((t >> 4) * 32 + (d0 >> 4)) * 32 + (t & 7) * 4 + ((d0 >> 1) & 2) + up))[(d0 >> 3) & 1] = up ? make_uint2(o, r.y) : make_uint2(r.x, o);
        }
        if (i == 0) {
            const float e0 = blo(r.x), e1 = bhi(r.x), e2 = blo(r.y), e3 = bhi(r.y);
            asm volatile("red.relaxed.gpu.global.add.v2.f32 [%0],{%1,%2};" ::"l"(g_st[0] + (t >> 7) * 2048 + lds32(sb + S_TAG) * 256 + (b & 1) * 128 + (t & 127)),
                         "f"((e0 + e1) + (e2 + e3)), "f"((e0 * e0 + e1 * e1) + (e2 * e2 + e3 * e3)) : "memory");
        }
    }
    PROF(tid == 0, 3515);
    bar_sync(10, 384);
}

__global__ void __cluster_dims__(2, 1, 1) __launch_bounds__(384, 1) main_kernel(const __grid_constant__ Params p) {
    extern __shared__ __align__(1024) uint8_t smem[];
    const uint32_t sb = __shfl_sync(0xffffffffu, smem_u32(smem), 0);
    uint32_t rank; asm("mov.u32 %0,%%cluster_ctarank;" : "=r"(rank));
    const int wi = __shfl_sync(0xffffffffu, threadIdx.x >> 5, 0);
    const int cl = blockIdx.x >> 1, wg = wi >> 2;
    const bool rec = p.rec0 >= 0 && cl >= p.rec0 && cl < p.rec0 + 32;
    PROF(threadIdx.x == 0, 3500);
    ProRegs pr;
    prologue_load(p.pa, max((int)blockIdx.x - 4, 0), pr);
    if (rec) rec_init(p, sb, cl - p.rec0, rank); else bulk_init(sb);
    if (threadIdx.x == 352 && p.dopro && cl >= 2) {
        mbar_init(sb + S_XBAR, 1);
        asm volatile("fence.mbarrier_init.release.cluster;" ::: "memory");
        mbar_expect(sb + S_XBAR, 32768);
        for (int j = 0; j < 8; j++) tma2d(sb + P_X + j * 4096, &p.tm[3], ((blockIdx.x - 4) >> 1) * 8, j * 256, sb + S_XBAR);
    }
    if (threadIdx.x == 320) {
        unsigned v;
        asm volatile("ld.relaxed.gpu.global.u32 %0,[%1];" : "=r"(v) : "l"(g_gate) : "memory");
        v = v / (4 * NCL) + p.dopro;
        sts64(sb + S_GATE, v * (4 * NCL), v & 1);
    }
    __syncwarp();
    asm volatile("barrier.cluster.arrive.relaxed.aligned;" ::: "memory");
    if (wg == 2) bar_arrive(8, 384);
    if (p.dopro && cl >= 2) prologue(p.pa, sb, blockIdx.x - 4, wi, pr); else if (wg < 2) bar_sync(8, 384);
    asm volatile("barrier.cluster.wait.aligned;" ::: "memory");
    fence_async_smem();
    bar_sync(wg == 2 ? 7 : 1, wg == 2 ? 128 : 256);
    if (p.dopro && (threadIdx.x == 32 || threadIdx.x == 352)) red_release(g_gate, 1);
    if (rec) {
        if (threadIdx.x == 0) {
            rec_fetch(&p.tm[1], sb + R_STK, (cl - p.rec0) * 128, rank * 256, 2, sb + R_BAR + RB_INIT * 8);
            rec_fetch(&p.tm[2], sb + R_STV, (cl - p.rec0) * 128, rank * 256, 2, sb + R_BAR + RB_INIT * 8);
        }
    }
    PROF(threadIdx.x == 0, 3506);
    __syncwarp();
    if (rec) {
        const int head = cl - p.rec0;
        if (wg == 2) {
            reg_dec<RH>();
            const int w = wi & 3;
            if (threadIdx.x == 256) rec_fetch(&p.tm[0], sb + R_STQ, head * 128, rank * 256, 2, sb + R_BAR + RB_INIT * 8);
            __syncwarp();
            wait_cnt_warp(g_gate, lds32(sb + S_GATE));
            if (p.dostats) x1_stats((head * 2 + rank) * 4 + w);
            __syncthreads();
            cluster_sync();
            if ((p.chains >> (w >> 1)) & 1) rec_attn(p, sb, w >> 1, w & 1, head, rank);
        } else {
            reg_inc<RW0>();
            rec_weights(p, sb, head, rank, wi);
        }
    } else {
        if (wg == 2) {
            reg_dec<40>();
            const int w = wi & 3;
            if (w == 0) bulk_producer(p, sb, cl, rank); else if (w >= 2) bulk_release(p, sb, cl, rank, w - 2); else bulk_relay(p, sb, cl);
        } else { reg_inc<232>(); bulk_consumer(p, sb, cl, rank, wi); }
    }
    __syncwarp();
    cluster_sync();
}

typedef CUresult (*EncFn)(CUtensorMap*, CUtensorMapDataType, cuuint32_t, void*, const cuuint64_t*, const cuuint64_t*, const cuuint32_t*, const cuuint32_t*,
                          CUtensorMapInterleave, CUtensorMapSwizzle, CUtensorMapL2promotion, CUtensorMapFloatOOBfill);
inline uint32_t mk(int type, int layer, int ch, int a, int b, int c) { return type | (layer << 3) | (ch << 4) | (a << 8) | (b << 16) | ((uint32_t)c << 24); }
constexpr int SMEM_BYTES = 232448;

struct Sched {
    Params* P; int n[NCL];
    void clear() { memset(P->task, 0, sizeof(P->task)); memset(n, 0, sizeof(n)); }
    void add(int cl, uint32_t t) { if (n[cl] < MAXT - 1) P->task[cl][n[cl]++] = t; }
};

constexpr int REC0 = 4;
struct Cfg { int LAG, TS1, TS2, DQU, DQO, DUN, DHN, MARG, NQ1, FAST0, n0, oc, fc, nuns, ns2, nhg, hs, osl, nfin; };
#define PLAN 13, 2300, 2800, 2400, 1300, 5800, 380, 0, 4, 0, 8, 4, 13, 6, 8, 8, 4000, 0, 0
Cfg g_cfg = {PLAN};
double g_est;
bool g_planned = false;
struct Plan { uint32_t w[NCL][MAXT]; int n[NCL]; double end, rec; };
void simulate(Plan& L, int nc, const Cfg& C) {
    const int LAG = C.LAG, NQ1 = C.NQ1, FAST0 = C.FAST0, n0 = C.n0, oc = C.oc, fc = C.fc, nuns = C.nuns, ns2 = C.ns2, nhg = C.nhg;
    const double TS1 = C.TS1, TS2 = C.TS2, DQU = C.DQU, DQO = C.DQO, DUN = C.DUN, DHN = C.DHN, MARG = C.MARG, hs = C.hs;
    const double INF = 1e18, DKB = 600, DOV = 700, DH = DHN, DHO = 1100, DF = 2200, DFB = 200, POLL = 450, FILL = 500, PUB = 600;
    enum { Q0, O0, Q1, HB, O1, FI, NK };
    struct Grp { int n, left; double done; } G[NK][16];
    double fr[NCL], it[100] = {}, cv[16];
    int ns[16], last[2][NCL], uc = 0, nit = 0;
    memset(L.n, 0, sizeof(L.n)); L.end = 0;
    auto fast = [&](int c) { return c < FAST0 || c >= fc; };
    for (int c = 0; c < 16; c++) {
        ns[c] = c < nuns ? 1 : c == 15 ? 16 : c == 14 ? 8 : ns2;
        const int cnt[NK] = {c < 2 ? 48 : (c & 1) ? 0 : 96, c < oc ? 8 : OPS1, c == 15 ? 24 : fast(c) ? 16 : 48 / NQ1, c >= 2 && !(c & 1) ? 16 : 0, ns[c], c < C.nfin || ns[c] == 1 ? 0 : c >= 14 ? 8 : 4};
        for (int k = 0; k < NK; k++) G[k][c] = {cnt[k], cnt[k], 0};
        cv[c] = INF;
    }
    for (int i = 0; i < nc; i++) { fr[i] = 0; last[0][i] = last[1][i] = -1; }
    auto fin = [&](int k, int c) { if ((k == Q0 && c >= 2) || k == HB) c &= ~1; return G[k][c].left ? INF : G[k][c].done; };
    auto len = [&](int i) { return (i >= LAG && i < 64) ? (double)TS2 : (double)TS1; };
    auto end_it = [&](int i) { return i < nit ? it[i] + len(i) : INF; };
    auto nominal = [&](int i) { if (i < nit) return it[i]; double t = nit ? it[nit - 1] : 11000 - TS1; for (int j = nit - 1; j < i; j++) t += len(j); return t; };
    auto put = [&](int i, uint32_t w) { if (L.n[i] < MAXT - 4) L.w[i][L.n[i]++] = w; else L.end = INF; };
    auto rel = [&](int k, int c) {
        switch (k) {
            case Q0: return 0.0;
            case O0: return end_it(4 * c + 3) + PUB + POLL;
            case Q1: return cv[c] + POLL;
            case HB: return cv[c - 2] + 600 + POLL;
            case O1: return fmax(end_it(LAG + 4 * c + 3) + PUB + POLL, G[O1][c].left == 1 && !G[FI][c].n ? G[O1][c].done - DKB * 64 / ns[c] : 0);
            default: return fin(O1, c) + POLL;
        }
    };
    auto dur = [&](int k, int c) {
        switch (k) {
            case Q0: return DQO + (c < 2 ? 2.0 : 1.0) * DQU;
            case O0: return (16 - G[O0][c].n) * DKB + 1200;
            case HB: return DHO + DH * c;
            case Q1: return DQO + 48.0 / G[Q1][c].n * DQU;
            case O1: return DOV + DKB * 64 / ns[c] + (G[O1][c].left == 1 && !G[FI][c].n ? 700 + 800 * ns[c] : 0);
            default: return DF + DFB * ns[c] * (c >= 14 ? 0.5 : 1);
        }
    };
    auto o0_est = [&](int c) {
        double t = uc ? cv[uc - 1] - 900 : 0;
        for (int j = uc; j < c; j++) t = fmax(t, nominal(4 * j + 4) + PUB + POLL + FILL) + dur(O0, j) + DUN;
        return fmax(t, nominal(4 * c + 4) + PUB + POLL);
    };
    auto cv_est = [&](int c) { return c < uc ? cv[c] : o0_est(c) + FILL + dur(O0, c) + DUN + 900; };
    auto slot = [&](int k, int c, int i) { return k == O0 ? (i < 8 ? i : nc + 7 - i) : c == 15 ? i : i - 8; };
    while (true) {
        while (nit < 64 + LAG) {
            double t = nit ? end_it(nit - 1) : 0;
            if (nit < 64) t = fmax(t, fin(Q0, nit >> 2) + POLL);
            if (nit >= LAG) t = fmax(t, fin(Q1, (nit - LAG) >> 2) + (nit < 64 ? 0 : POLL));
            if (t >= INF) break;
            it[nit++] = t;
        }
        int i = -1;
        for (int j = 0; j < nc; j++) if (fr[j] < INF && (i < 0 || fr[j] < fr[i])) i = j;
        if (i < 0) break;
        const double t = fr[i];
        double lim = INF;
        if (i < 8 && last[0][i] == uc) {
            if (G[O0][uc].left || fin(HB, uc) >= INF) { fr[i] = t + 200; continue; }
            const double e = fmax(G[O0][uc].done, fin(HB, uc) - 2000) + DUN;
            for (int j = 0; j < 8; j++) { put(j, mk(T_CV, 0, uc, 2 * j, G[O0][uc].n, 0)); fr[j] = e; }
            cv[uc++] = e + 900;
            continue;
        }
        const bool hg = (unsigned)(i - 24) < (unsigned)nhg;
        double hlim = INF;
        for (int c = 2; c < 16 && hg; c++) if (G[HB][c].left) { hlim = cv_est(c - 2) + hs; break; }
        int mine[2] = {-1, -1};
        for (int k = 0; k < 2; k++)
            for (int c = last[k][i] + 1; c < 16 && mine[k] < 0; c++) if ((unsigned)slot(O0 + k, c, i) < (unsigned)G[O0 + k][c].n) mine[k] = c;
        if (mine[0] >= 0) lim = i < 8 ? o0_est(mine[0]) - (uc ? 0 : 8500) : nominal(4 * mine[0] + 4) + PUB + C.osl;
        else if (mine[1] >= 0) lim = cv_est(mine[1]) + POLL;
        else if (i < 16 && G[O1][15].left) lim = fmin(lim, nominal(64 + LAG) + PUB);
        int bk = -1, bc = 0; double bd = INF;
        for (int k = 0; k < NK; k++)
            for (int c = 0; c < 16; c++) {
                const bool urgent = k == O0 || k == Q1 || (k == O1 && c == 15);
                if (!G[k][c].left || ((k == O0 || k == Q1) && c != mine[k - O0]) || (k == O1 && c == 15 && i >= 16)) continue;
                if (rel(k, c) > t || (t + dur(k, c) + (k == Q0 && c >= 2 ? DQU : 0) > lim && !urgent)) continue;
                if (i < 8 && uc && uc < 16 && k != O0) continue;
                if ((k == HB && !hg && i < nc - 2) || (k != HB && !urgent && t + dur(k, c) + (k == Q0 && c >= 2 ? DQU : 0) > hlim)) continue;
                const double dl = urgent ? -INF : k == HB ? -INF / 2 : k == Q0 ? nominal(4 * c) - 3000 : 1e9 + c * 2 + (k == O1);
                if (dl < bd) { bd = dl; bk = k; bc = c; }
            }
        if (bk < 0) {
            bool any = i < 8 && uc < 16;
            for (int k = 0; k < NK; k++) for (int c = 0; c < 16; c++) any = any || G[k][c].left;
            fr[i] = any ? t + 200 : INF;
            if (t > 400000) { L.end = INF; return; }
            continue;
        }
        Grp& g = G[bk][bc];
        const int n = g.n - g.left, c = bc;
        int nu = 1;
        double d = dur(bk, c);
        if (bk == Q0) for (nu = c < 2 ? 2 : 1; c >= 2 && nu < g.left && (nu < 2 || (nu < n0 && t + d + DQU < fmin(fmin(lim, hlim), bd - MARG))); nu++) d += DQU;
        if (bk == O0 && i >= 8) d += (g.n - 8) * DKB;
        if (bk == Q0 && !c && n >= 32) { nu = 1; d -= DQU; }
        if (bk == O0 || bk == Q1) last[bk - O0][i] = c;
        if (bk == O0 && !c && i < 8) put(i, mk(T_CV, 0, 3, 2 * i, 0, 128));
        g.left -= nu;
        const bool fini = bk == O1 && !g.left && !G[FI][c].n;
        const double e = fmax(fmax(t, rel(bk, c) + FILL) + (t < 1 ? 3500 : 0) + d, fini ? g.done + POLL + 700 + 800 * ns[c] : 0);
        fr[i] = e;
        g.done = fmax(g.done, e + (bk == O1 ? 1900 : bk == O0 ? 0 : (bk == Q1 && g.n < 24) || (bk == Q0 && !c && nu == 2) ? -500 : 1000));
        if (bk == FI || fini) L.end = fmax(L.end, e);
        put(i, bk == Q0 ? (c == 0 ? mk(T_QKV, 0, 0, n < 32 ? n : 2 * n - 32, nu, 32) : c == 1 ? mk(T_QKV, 0, c, n, 2, 24) : mk(T_QKV, 0, c, n, nu, 64))
             : bk == O0 ? (i < 8 ? mk(T_OP, 0, c, i * (16 - g.n), 16 - g.n, i) : mk(T_OP, 0, c, 64 - (nc - i) * 8, 8, slot(O0, c, i)))
             : bk == HB ? mk(T_CV, 1, c, 2 * n, 0, 0)
             : bk == Q1 ? mk(T_QKV, 1, c, slot(Q1, c, i) * 2, 48 / g.n, g.n)
             : bk == O1 ? mk(T_OP, 1, c, n * 64 / ns[c], 64 / ns[c], n + (fini ? 32 : 0))
                        : mk(T_FIN, 1, c, n * (32 / g.n), ns[c], 16 / g.n));
    }
    L.rec = end_it(63 + LAG);
}
void plan(Params& P) {
    P.rec0 = REC0; P.chains = 3; P.lag = g_cfg.LAG; P.dostats = 1; P.dopro = 1;
    static Plan L;
    int cls[NCL], nc = 0;
    for (int c = REC0 + 32; c < NCL; c++) cls[nc++] = c;
    for (int c = REC0 - 1; c >= 0; c--) cls[nc++] = c;
    simulate(L, nc, g_cfg);
    g_est = L.end;
    Sched S; S.P = &P; S.clear();
    for (int i = 0; i < nc; i++) {
        bool warm = false;
        for (int k = 0; k < L.n[i]; k++) {
            if (!warm && k + 1 < L.n[i] && (L.w[i][k + 1] & 255) == (mk(T_FIN, 1, 15, 0, 0, 0) & 255)) { S.add(cls[i], L.w[i][k + 1] | 0x80000000u); warm = true; }
            S.add(cls[i], L.w[i][k]);
            if ((L.w[i][k] & 7) == T_FIN) warm = true;
        }
    }
}

#define TK0() do {} while (0)
#define TK() do { P.e0 = (P.chains & 1) ? 64 : 0; P.b1 = (P.chains & 2) ? P.lag : 1000; P.nit = (P.chains & 2) ? P.lag + 64 : 64; TK0(); } while (0)
}

extern "C" void kernel_launch(void* const* d_in, const int* in_sizes, int n_in, void* d_out, int out_size) {
    typedef const __nv_bfloat16* BP;
    static EncFn enc = nullptr;
    if (!enc) {
        void* fn = nullptr; cudaDriverEntryPointQueryResult qr;
        cudaGetDriverEntryPoint("cuTensorMapEncodeTiled", &fn, cudaEnableDefault, &qr);
        enc = (EncFn)fn;
        cudaFuncSetAttribute(main_kernel, cudaFuncAttributeMaxDynamicSharedMemorySize, SMEM_BYTES);
    }
    static Params P;
    for (int i = 0; i < 4; i++) {
        const cuuint64_t cols = i < 3 ? 4096 : 512, rows = i < 3 ? 512 : 4096;
        cuuint64_t d2[2] = {cols, rows}, d3[3] = {64, rows, cols / 64}, str[2] = {cols * 2, 128};
        cuuint32_t box[3] = {64, 64, 4}, es[3] = {1, 1, 1};
        enc(&P.tm[i < 3 ? i : 4], CU_TENSOR_MAP_DATA_TYPE_BFLOAT16, 2, d_in[9 + i], d2, str, box, es, CU_TENSOR_MAP_INTERLEAVE_NONE, CU_TENSOR_MAP_SWIZZLE_128B,
                       CU_TENSOR_MAP_L2_PROMOTION_L2_128B, CU_TENSOR_MAP_FLOAT_OOB_FILL_NONE);
        for (int m = 0; m < 2; m++) {
            cuuint32_t box3[3] = {64, 32, m ? 2u : 4u};
            enc(&P.t3[m][i], CU_TENSOR_MAP_DATA_TYPE_BFLOAT16, 3, d_in[9 + i], d3, str, box3, es, CU_TENSOR_MAP_INTERLEAVE_NONE, CU_TENSOR_MAP_SWIZZLE_128B,
                CU_TENSOR_MAP_L2_PROMOTION_L2_128B, CU_TENSOR_MAP_FLOAT_OOB_FILL_NONE);
        }
    }
    {
        cuuint64_t dims[2] = {512, 2048}, str[1] = {1024};
        cuuint32_t box[2] = {8, 256}, es[2] = {1, 1};
        enc(&P.tm[3], CU_TENSOR_MAP_DATA_TYPE_BFLOAT16, 2, d_in[0], dims, str, box, es, CU_TENSOR_MAP_INTERLEAVE_NONE, CU_TENSOR_MAP_SWIZZLE_NONE,
            CU_TENSOR_MAP_L2_PROMOTION_NONE, CU_TENSOR_MAP_FLOAT_OOB_FILL_NONE);
    }
    for (int m = 0; m < 2; m++) {
        void* ga; cudaGetSymbolAddress(&ga, g_A);
        cuuint64_t dims[2] = {512, sizeof(AOps) / 1024}, str[1] = {1024};
        cuuint32_t box[2] = {256, m ? 16u : 8u}, es[2] = {1, 1};
        enc(&P.ta[m], CU_TENSOR_MAP_DATA_TYPE_BFLOAT16, 2, ga, dims, str, box, es, CU_TENSOR_MAP_INTERLEAVE_NONE, CU_TENSOR_MAP_SWIZZLE_NONE,
            CU_TENSOR_MAP_L2_PROMOTION_L2_128B, CU_TENSOR_MAP_FLOAT_OOB_FILL_NONE);
    }
    P.mem0 = (BP)d_in[8]; P.Wo = (BP)d_in[12]; P.Dskip = (BP)d_in[6]; P.out = (__nv_bfloat16*)d_out;
    cudaStream_t s = cudaStreamPerThread;
    P.pa = {(BP)d_in[0], (BP)d_in[1], (BP)d_in[2], (BP)d_in[3], (BP)d_in[4], (BP)d_in[5], (BP)d_in[6], (BP)d_in[9], (BP)d_in[10], (BP)d_in[11], (BP)d_in[12], (BP)d_in[8]};
    if (!g_planned) { plan(P); g_planned = true; }
    TK(); main_kernel<<<2 * NCL, 384, SMEM_BYTES, s>>>(P); TK();
}
```

```cpp
#include <cuda_runtime.h>
#include <cuda_bf16.h>
#include <cuda.h>
#include <stdint.h>
#include <string.h>
#include <math.h>

namespace {

constexpr int NCL = 66;
constexpr int MAXT = 64;
#define PFC 1
#define QB1 2
#define QB2 4
#define QB3 6
#define LAGQ 2
#define CPOS 2
#define OPS1N 10
constexpr int OPS1 = OPS1N;
constexpr int MAXSPLIT = 16;
constexpr int PW = 144;

struct AOps { uint4 x[2][16 * 8 * 1024], o[2][16 * 64 * 1024]; };
__device__ AOps g_A;
#define g_xA g_A.x
#define g_o g_A.o
__device__ float2 g_st[2][16 * 2048];
__device__ float2 g_st2[2 * 16 * 128];
__device__ uint4 g_qkv[2][64 * 64 * 768];
__device__ uint4 g_pp[2][16 * MAXSPLIT * 8192];
__device__ uint4 g_acc[7 * 2048];
__device__ unsigned g_gate[32];
__device__ uint32_t g_P[16 * 16 * 32 * PW];
__device__ uint4 g_u[16 * 16 * 512];
__device__ float4 g_carry[2][17 * 16 * 4 * 256];
__device__ unsigned g_cnt[13 * 64];
__device__ uint32_t g_ln0[2048];

enum { C_QKV0 = 0, C_QKV1 = 1  , C_O0 = 2, C_O1 = 3, C_U = 4, C_OP1 = 5, C_CV = 6, C_ST = 7, C_H = 8, C_OP0 = 9   };
__device__ __forceinline__ unsigned* cnt_ptr(int kind, int chunk) { return g_cnt + kind * 64 + chunk; }

enum { T_END = 0, T_QKV = 1, T_OP = 2, T_CV = 3, T_FIN = 4 };
struct ProArgs { const __nv_bfloat16 *x, *lAr, *Ai, *Cr, *Ci, *ldt, *Dk, *Wq, *Wk, *Wv, *Wo, *mem0; };
struct Params {
    CUtensorMap tm[5];
    CUtensorMap t3[2][4];
    CUtensorMap ta[2];
    ProArgs pa;
    int dopro;
    const __nv_bfloat16* mem0;
    const __nv_bfloat16* Wo;
    const __nv_bfloat16* Dskip;
    __nv_bfloat16* out;
    int rec0;
    int chains;
    int lag;
    int b1, e0, nit;
    int zero, gpit;
    int dostats;
    uint32_t task[NCL][MAXT];
};

__device__ __forceinline__ uint32_t smem_u32(const void* p) { return (uint32_t)__cvta_generic_to_shared(p); }
__device__ __forceinline__ uint32_t mapa(uint32_t a, uint32_t r) {
    uint32_t o; asm("mapa.shared::cluster.u32 %0,%1,%2;" : "=r"(o) : "r"(a), "r"(r)); return o;
}
__device__ __forceinline__ void mbar_init(uint32_t b, int c) { asm volatile("mbarrier.init.shared::cta.b64 [%0],%1;" ::"r"(b), "r"(c) : "memory"); }
__device__ __forceinline__ void mbar_expect(uint32_t b, int bytes) { asm volatile("mbarrier.arrive.expect_tx.shared::cta.b64 _,[%0],%1;" ::"r"(b), "r"(bytes) : "memory"); }
__device__ __forceinline__ void mbar_arrive(uint32_t b) { asm volatile("mbarrier.arrive.shared::cta.b64 _,[%0];" ::"r"(b) : "memory"); }
__device__ __forceinline__ void mbar_arrive_cluster(uint32_t b) { asm volatile("mbarrier.arrive.shared::cluster.b64 _,[%0];" ::"r"(b) : "memory"); }
__device__ __forceinline__ void mbar_arrive1(uint32_t b) { asm volatile("{.reg .pred p; elect.sync _|p,0xffffffff; @p mbarrier.arrive.shared::cta.b64 _,[%0];}" ::"r"(b) : "memory"); }
__device__ __forceinline__ void mbar_arrive1_cluster(uint32_t b) { asm volatile("{.reg .pred p; elect.sync _|p,0xffffffff; @p mbarrier.arrive.shared::cluster.b64 _,[%0];}" ::"r"(b) : "memory"); }
__device__ __forceinline__ void mbar_wait(uint32_t b, uint32_t ph) {
    asm volatile(
        "{.reg .pred p; .reg .u32 n; mov.u32 n,0;\n"
        "W%=: mbarrier.try_wait.parity.shared::cta.b64 p,[%0],%1;\n"
        "@p bra D%=;\n"
        "add.u32 n,n,1; setp.lt.u32 p,n,2000000; @p bra W%=;\n"
        "trap;\n"
        "D%=: }" ::"r"(b), "r"(ph) : "memory");
}
__device__ __forceinline__ bool mbar_test(uint32_t b, uint32_t ph) {
    uint32_t ok;
    asm volatile("{.reg .pred p; mbarrier.test_wait.parity.shared::cta.b64 p,[%1],%2; selp.u32 %0,1,0,p;}" : "=r"(ok) : "r"(b), "r"(ph) : "memory");
    return ok;
}
__device__ __forceinline__ bool wait_lds128(uint32_t b, uint32_t ph, uint32_t a, uint4& v) {
    uint32_t ok;
    asm volatile("{.reg .pred p; mbarrier.try_wait.parity.shared::cta.b64 p,[%5],%6,20000; ld.shared.v4.u32 {%0,%1,%2,%3},[%7]; selp.u32 %4,1,0,p;}"
                 : "=r"(v.x), "=r"(v.y), "=r"(v.z), "=r"(v.w), "=r"(ok) : "r"(b), "r"(ph), "r"(a) : "memory");
    return ok;
}
__device__ __forceinline__ bool wait_lds64(uint32_t b, uint32_t ph, uint32_t a, uint2& v) {
    uint32_t ok;
    asm volatile("{.reg .pred p; mbarrier.try_wait.parity.shared::cta.b64 p,[%3],%4,20000; ld.shared.v2.u32 {%0,%1},[%5]; selp.u32 %2,1,0,p;}"
                 : "=r"(v.x), "=r"(v.y), "=r"(ok) : "r"(b), "r"(ph), "r"(a) : "memory");
    return ok;
}
template <int PH> __device__ __forceinline__ void mbar_wait_c(uint32_t b) {
    asm volatile(
        "{.reg .pred p; .reg .u32 n; mov.u32 n,%2;\n"
        "W%=: mbarrier.try_wait.parity.shared::cta.b64 p,[%0],%1;\n"
        "@p bra D%=;\n"
        "add.u32 n,n,1; setp.lt.u32 p,n,2000000; @p bra W%=;\n"
        "trap;\n"
        "D%=: }" ::"r"(b), "n"(PH), "n"(PH) : "memory");
}
__device__ __forceinline__ void bar_sync(int id, int n) { asm volatile("bar.sync %0,%1;" ::"r"(id), "r"(n) : "memory"); }
__device__ __forceinline__ void bar_arrive(int id, int n) { asm volatile("bar.arrive %0,%1;" ::"r"(id), "r"(n) : "memory"); }
__device__ __forceinline__ void cluster_sync() { asm volatile("barrier.cluster.arrive.relaxed.aligned; barrier.cluster.wait.aligned;" ::: "memory"); }
__device__ __forceinline__ void fence_async() { asm volatile("fence.proxy.async;" ::: "memory"); }
__device__ __forceinline__ void fence_async_smem() { asm volatile("fence.proxy.async.shared::cta;" ::: "memory"); }
#define EFR 1
#define EFW 1
constexpr uint64_t POL_N = 0x1000000000000000ull, POL_F = 0x12F0000000000000ull;
constexpr uint64_t POL_LAST = EFR ? POL_F : POL_N  , POL_LATE = EFW ? POL_F : POL_N  , POL_SOON = EFW > 1 ? POL_F : POL_N;
__device__ __forceinline__ void bulk_g2s(uint32_t dst, const void* src, int bytes, uint32_t bar, uint64_t pol) {
    asm volatile("cp.async.bulk.shared::cluster.global.mbarrier::complete_tx::bytes.L2::cache_hint [%0],[%1],%2,[%3],%4;" ::"r"(dst), "l"(src), "r"(bytes), "r"(bar), "l"(pol) : "memory");
}
__device__ __forceinline__ void bulk_g2s_mc(uint32_t dst, const void* src, int bytes, uint32_t bar, uint64_t pol) {
    asm volatile("cp.async.bulk.shared::cluster.global.mbarrier::complete_tx::bytes.multicast::cluster.L2::cache_hint [%0],[%1],%2,[%3],%4,%5;" ::"r"(dst), "l"(src), "r"(bytes), "r"(bar), "h"((uint16_t)3), "l"(pol) : "memory");
}
__device__ __forceinline__ void bulk_s2s(uint32_t dst, uint32_t src, int bytes, uint32_t bar) {
    asm volatile("cp.async.bulk.shared::cluster.shared::cta.mbarrier::complete_tx::bytes [%0],[%1],%2,[%3];" ::"r"(dst), "r"(src), "r"(bytes), "r"(bar) : "memory");
}
__device__ __forceinline__ bool elect() {
    uint32_t r; asm volatile("{.reg .pred p; elect.sync _|p,0xffffffff; selp.u32 %0,1,0,p;}" : "=r"(r)); return r;
}
__device__ __forceinline__ void stg128(uint4* p, uint4 v, uint64_t pol) {
    asm volatile("st.global.L2::cache_hint.v4.u32 [%0],{%1,%2,%3,%4},%5;" ::"l"(p), "r"(v.x), "r"(v.y), "r"(v.z), "r"(v.w), "l"(pol));
}
__device__ __forceinline__ void stg32(uint32_t* p, uint32_t v, uint64_t pol) { asm volatile("st.global.L2::cache_hint.u32 [%0],%1,%2;" ::"l"(p), "r"(v), "l"(pol)); }
__device__ __forceinline__ uint4 ldcg128_last(const uint4* p) {
    uint4 v; asm volatile("ld.global.cg.L2::cache_hint.v4.u32 {%0,%1,%2,%3},[%4],%5;" : "=r"(v.x), "=r"(v.y), "=r"(v.z), "=r"(v.w) : "l"(p), "l"(POL_LAST) : "memory"); return v;
}
__device__ __forceinline__ void tma2d(uint32_t dst, const CUtensorMap* tm, int x, int y, uint32_t bar) {
    asm volatile("cp.async.bulk.tensor.2d.shared::cluster.global.mbarrier::complete_tx::bytes [%0],[%1,{%2,%3}],[%4];" ::"r"(dst), "l"(tm), "r"(x), "r"(y), "r"(bar) : "memory");
}
__device__ __forceinline__ void tma3d_mc(uint32_t dst, const CUtensorMap* tm, int y, int z, uint32_t bar, uint16_t mask) {
    asm volatile("{.reg .pred p; elect.sync _|p,0xffffffff;\n"
                 "@p cp.async.bulk.tensor.3d.shared::cluster.global.mbarrier::complete_tx::bytes.multicast::cluster [%0],[%1,{0,%2,%3}],[%4],%5;}"
                 ::"r"(dst), "l"(tm), "r"(y), "r"(z), "r"(bar), "h"(mask) : "memory");
}
__device__ __forceinline__ void tma2d_mc(uint32_t dst, const CUtensorMap* tm, int x, int y, uint32_t bar, uint16_t mask, uint64_t pol) {
    asm volatile("{.reg .pred p; elect.sync _|p,0xffffffff;\n"
                 "@p cp.async.bulk.tensor.2d.shared::cluster.global.mbarrier::complete_tx::bytes.multicast::cluster.L2::cache_hint [%0],[%1,{%2,%3}],[%4],%5,%6;}"
                 ::"r"(dst), "l"(tm), "r"(x), "r"(y), "r"(bar), "h"(mask), "l"(pol) : "memory");
}
__device__ __forceinline__ void bulk_g2s1(uint32_t dst, const void* src, int bytes, uint32_t bar, uint64_t pol) {
    asm volatile("{.reg .pred p; elect.sync _|p,0xffffffff;\n"
                 "@p cp.async.bulk.shared::cluster.global.mbarrier::complete_tx::bytes.L2::cache_hint [%0],[%1],%2,[%3],%4;}" ::"r"(dst), "l"(src), "r"(bytes), "r"(bar), "l"(pol) : "memory");
}
__device__ __forceinline__ void mbar_expect1(uint32_t b, int bytes) {
    asm volatile("{.reg .pred p; elect.sync _|p,0xffffffff; @p mbarrier.arrive.expect_tx.shared::cta.b64 _,[%0],%1;}" ::"r"(b), "r"(bytes) : "memory");
}
__device__ __forceinline__ void st_async4(uint32_t a, uint32_t x, uint32_t y, uint32_t z, uint32_t w, uint32_t mb) {
    asm volatile("st.async.shared::cluster.mbarrier::complete_tx::bytes.v4.b32 [%0],{%1,%2,%3,%4},[%5];" ::"r"(a), "r"(x), "r"(y), "r"(z), "r"(w), "r"(mb) : "memory");
}
__device__ __forceinline__ void st_async2(uint32_t a, uint32_t x, uint32_t y, uint32_t mb) {
    asm volatile("st.async.shared::cluster.mbarrier::complete_tx::bytes.v2.b32 [%0],{%1,%2},[%3];" ::"r"(a), "r"(x), "r"(y), "r"(mb) : "memory");
}
#define LDSQ "ld.shared"
__device__ __forceinline__ uint4 lds128(uint32_t a) { uint4 v; asm volatile(LDSQ ".v4.u32 {%0,%1,%2,%3},[%4];" : "=r"(v.x), "=r"(v.y), "=r"(v.z), "=r"(v.w) : "r"(a) : "memory"); return v; }
__device__ __forceinline__ uint2 lds64(uint32_t a) { uint2 v; asm volatile(LDSQ ".v2.u32 {%0,%1},[%2];" : "=r"(v.x), "=r"(v.y) : "r"(a) : "memory"); return v; }
__device__ __forceinline__ uint32_t lds32(uint32_t a) { uint32_t v; asm volatile(LDSQ ".u32 %0,[%1];" : "=r"(v) : "r"(a) : "memory"); return v; }
__device__ __forceinline__ void sts128(uint32_t a, uint32_t x, uint32_t y, uint32_t z, uint32_t w) { asm volatile("st.shared.v4.u32 [%0],{%1,%2,%3,%4};" ::"r"(a), "r"(x), "r"(y), "r"(z), "r"(w) : "memory"); }
__device__ __forceinline__ void sts64(uint32_t a, uint32_t x, uint32_t y) { asm volatile("st.shared.v2.u32 [%0],{%1,%2};" ::"r"(a), "r"(x), "r"(y) : "memory"); }
__device__ __forceinline__ void sts32(uint32_t a, uint32_t x) { asm volatile("st.shared.u32 [%0],%1;" ::"r"(a), "r"(x) : "memory"); }
__device__ __forceinline__ uint4 ldsm4(uint32_t a) { uint4 v; asm volatile("ldmatrix.sync.aligned.m8n8.x4.shared.b16 {%0,%1,%2,%3},[%4];" : "=r"(v.x), "=r"(v.y), "=r"(v.z), "=r"(v.w) : "r"(a) : "memory"); return v; }
__device__ __forceinline__ uint4 ldsm4t(uint32_t a) { uint4 v; asm volatile("ldmatrix.sync.aligned.m8n8.x4.trans.shared.b16 {%0,%1,%2,%3},[%4];" : "=r"(v.x), "=r"(v.y), "=r"(v.z), "=r"(v.w) : "r"(a) : "memory"); return v; }
__device__ __forceinline__ uint32_t movm(uint32_t a) { uint32_t d; asm volatile("movmatrix.sync.aligned.m8n8.trans.b16 %0,%1;" : "=r"(d) : "r"(a)); return d; }
__device__ __forceinline__ uint32_t pack2(float lo, float hi) { uint32_t d; asm("cvt.rn.bf16x2.f32 %0,%1,%2;" : "=r"(d) : "f"(hi), "f"(lo)); return d; }
__device__ __forceinline__ uint32_t hadd2(uint32_t a, uint32_t b) { uint32_t d; asm("add.rn.bf16x2 %0,%1,%2;" : "=r"(d) : "r"(a), "r"(b)); return d; }
__device__ __forceinline__ float blo(uint32_t v) { return __uint_as_float(v << 16); }
__device__ __forceinline__ float bhi(uint32_t v) { return __uint_as_float(v & 0xffff0000u); }
__device__ __forceinline__ float rbf(float x) { return __uint_as_float(pack2(0.f, x)); }
__device__ __forceinline__ float ex2(float x) { float y; asm("ex2.approx.ftz.f32 %0,%1;" : "=f"(y) : "f"(x)); return y; }
__device__ __forceinline__ float rcp(float x) { float y; asm("rcp.approx.ftz.f32 %0,%1;" : "=f"(y) : "f"(x)); return y; }
__device__ __forceinline__ void mma16(float* c, uint32_t a0, uint32_t a1, uint32_t a2, uint32_t a3, uint32_t b0, uint32_t b1) {
    asm volatile("mma.sync.aligned.m16n8k16.row.col.f32.bf16.bf16.f32 {%0,%1,%2,%3},{%4,%5,%6,%7},{%8,%9},{%0,%1,%2,%3};"
                 : "+f"(c[0]), "+f"(c[1]), "+f"(c[2]), "+f"(c[3]) : "r"(a0), "r"(a1), "r"(a2), "r"(a3), "r"(b0), "r"(b1));
}
__device__ __forceinline__ void mma8(float* c, uint32_t a0, uint32_t a1, uint32_t b0) {
    asm volatile("mma.sync.aligned.m16n8k8.row.col.f32.bf16.bf16.f32 {%0,%1,%2,%3},{%4,%5},{%6},{%0,%1,%2,%3};"
                 : "+f"(c[0]), "+f"(c[1]), "+f"(c[2]), "+f"(c[3]) : "r"(a0), "r"(a1), "r"(b0));
}
__device__ __forceinline__ uint4 ld_rlx128(const uint4* p) {
    uint4 v;
    asm volatile("{.reg .b128 t; ld.relaxed.gpu.global.b128 t,[%4]; mov.b128 {%0,%1,%2,%3},t;}" : "=r"(v.x), "=r"(v.y), "=r"(v.z), "=r"(v.w) : "l"(p) : "memory");
    return v;
}
__device__ __forceinline__ void st_rlx128(uint4* p, uint32_t x, uint32_t y, uint32_t z, uint32_t w) {
    asm volatile("{.reg .b128 t; mov.b128 t,{%1,%2,%3,%4}; st.relaxed.gpu.global.b128 [%0],t;}" ::"l"(p), "r"(x), "r"(y), "r"(z), "r"(w) : "memory");
}
__device__ __forceinline__ uint4 ldcg128(const uint4* p) { uint4 v; asm volatile("ld.global.cg.v4.u32 {%0,%1,%2,%3},[%4];" : "=r"(v.x), "=r"(v.y), "=r"(v.z), "=r"(v.w) : "l"(p) : "memory"); return v; }
__device__ __forceinline__ void red_release(unsigned* p, unsigned v) {
    asm volatile("fence.proxy.async; red.relaxed.gpu.global.add.u32 [%0],%1;" ::"l"(p), "r"(v) : "memory");
}
__device__ __forceinline__ void wait_cnt(const unsigned* p, unsigned target) {
    unsigned v; int n = 0;
    while (true) {
        asm volatile("ld.acquire.gpu.global.u32 %0,[%1];" : "=r"(v) : "l"(p) : "memory");
        if (v >= target) break;
        if (++n > 3000000) __trap();
        __nanosleep(40);
    }
}
__device__ __forceinline__ void wait_cnt_warp(const unsigned* p, unsigned target) {
    unsigned v; int n = 0;
    while (true) {
        asm volatile("ld.acquire.gpu.global.u32 %0,[%1];" : "=r"(v) : "l"(p) : "memory");
        if (__all_sync(0xffffffffu, v >= target)) break;
        if (++n > 3000000) __trap();
    }
}
__device__ __forceinline__ uint64_t mkdesc(uint32_t addr, uint32_t lbo, uint32_t sbo, uint32_t sw) {
    return (uint64_t)((addr & 0x3FFFF) >> 4) | ((uint64_t)(lbo >> 4) << 16) | ((uint64_t)(sbo >> 4) << 32) | ((uint64_t)sw << 62);
}
__device__ __forceinline__ void wg_fence() { asm volatile("wgmma.fence.sync.aligned;" ::: "memory"); }
__device__ __forceinline__ void wg_commit() { asm volatile("wgmma.commit_group.sync.aligned;" ::: "memory"); }
template <int N> __device__ __forceinline__ void wg_wait() { asm volatile("wgmma.wait_group.sync.aligned %0;" ::"n"(N) : "memory"); }
#define R8(c, o) "+f"(c[o]), "+f"(c[o + 1]), "+f"(c[o + 2]), "+f"(c[o + 3]), "+f"(c[o + 4]), "+f"(c[o + 5]), "+f"(c[o + 6]), "+f"(c[o + 7])
#define R32(c, o) R8(c, o), R8(c, o + 8), R8(c, o + 16), R8(c, o + 24)
#define S32A "%0,%1,%2,%3,%4,%5,%6,%7,%8,%9,%10,%11,%12,%13,%14,%15,%16,%17,%18,%19,%20,%21,%22,%23,%24,%25,%26,%27,%28,%29,%30,%31"
#define S32B ",%32,%33,%34,%35,%36,%37,%38,%39,%40,%41,%42,%43,%44,%45,%46,%47,%48,%49,%50,%51,%52,%53,%54,%55,%56,%57,%58,%59,%60,%61,%62,%63"
#define S32C ",%64,%65,%66,%67,%68,%69,%70,%71,%72,%73,%74,%75,%76,%77,%78,%79,%80,%81,%82,%83,%84,%85,%86,%87,%88,%89,%90,%91,%92,%93,%94,%95"
#define S32D ",%96,%97,%98,%99,%100,%101,%102,%103,%104,%105,%106,%107,%108,%109,%110,%111,%112,%113,%114,%115,%116,%117,%118,%119,%120,%121,%122,%123,%124,%125,%126,%127"
#define W8(c, o) "=f"(c[o]), "=f"(c[o + 1]), "=f"(c[o + 2]), "=f"(c[o + 3]), "=f"(c[o + 4]), "=f"(c[o + 5]), "=f"(c[o + 6]), "=f"(c[o + 7])
#define W32(c, o) W8(c, o), W8(c, o + 8), W8(c, o + 16), W8(c, o + 24)
template <bool ACC> __device__ __forceinline__ void wgmma256(float* c, uint64_t da, uint64_t db) {
    if (ACC) asm volatile("wgmma.mma_async.sync.aligned.m64n256k16.f32.bf16.bf16 {" S32A S32B S32C S32D "},%128,%129,1,1,1,0,1;"
                          : R32(c, 0), R32(c, 32), R32(c, 64), R32(c, 96) : "l"(da), "l"(db));
    else asm volatile("wgmma.mma_async.sync.aligned.m64n256k16.f32.bf16.bf16 {" S32A S32B S32C S32D "},%128,%129,0,1,1,0,1;"
                      : W32(c, 0), W32(c, 32), W32(c, 64), W32(c, 96) : "l"(da), "l"(db));
}
template <bool ACC> __device__ __forceinline__ void wgmma128r(float* c, const uint4& a, uint64_t db) {
    if (ACC) asm volatile("wgmma.mma_async.sync.aligned.m64n128k16.f32.bf16.bf16 {" S32A S32B "},{%64,%65,%66,%67},%68,1,1,1,1;"
                          : R32(c, 0), R32(c, 32) : "r"(a.x), "r"(a.y), "r"(a.z), "r"(a.w), "l"(db));
    else asm volatile("wgmma.mma_async.sync.aligned.m64n128k16.f32.bf16.bf16 {" S32A S32B "},{%64,%65,%66,%67},%68,0,1,1,1;"
                      : W32(c, 0), W32(c, 32) : "r"(a.x), "r"(a.y), "r"(a.z), "r"(a.w), "l"(db));
}
template <int N> __device__ __forceinline__ void reg_inc() { asm volatile("setmaxnreg.inc.sync.aligned.u32 %0;" ::"n"(N)); }
template <int N> __device__ __forceinline__ void reg_dec() { asm volatile("setmaxnreg.dec.sync.aligned.u32 %0;" ::"n"(N)); }

#define PROF(cond, idx) do {} while (0)
#define CPROF(k) do {} while (0)

constexpr int S_GATE = 232440, S_TAG = 232444, S_XBAR = 232432;
constexpr float SC_LOG2E = 0.08838834764831845f * 1.4426950408889634f;

__device__ __forceinline__ float2 ln_finish(float mean, float var) {
    float sd; asm("sqrt.approx.f32 %0,%1;" : "=f"(sd) : "f"(rbf(rbf(var) + 1e-5f)));
    sd = rbf(sd);
    return make_float2(rbf(mean), sd);
}

__device__ __forceinline__ float4 row_stats(const uint4* src, int stride) {
    const int g = (threadIdx.x & 31) >> 2;
    uint4 v[16];
#pragma unroll
    for (int i = 0; i < 16; i++) v[i] = ldcg128(src + i * stride);
    float a[4] = {0, 0, 0, 0}, q0[4] = {0, 0, 0, 0}, q1[4] = {0, 0, 0, 0};
#pragma unroll
    for (int i = 0; i < 16; i++) {
        mma16(a, v[i].x, v[i].y, v[i].z, v[i].w, 0x3f803f80u, 0x3f803f80u);
        mma8(q0, v[i].x, v[i].y, v[i].x); mma8(q1, v[i].x, v[i].y, v[i].y);
        mma8(q0, v[i].z, v[i].w, v[i].z); mma8(q1, v[i].z, v[i].w, v[i].w);
    }
    return make_float4(a[0], (g & 1) ? q0[1] : q0[0], a[2], (g & 1) ? q1[3] : q1[2]);
}
__device__ __forceinline__ void x1_stats(int i) {
    const int lane = threadIdx.x & 31, g = lane >> 2, c = lane & 3;
    const float4 r = row_stats(g_xA[0] + i * 512 + lane, 32);
    float2* dst = g_st[0] + (i >> 4) * 2048 + ((i < 32 ? 4 : 0) + (i & 1)) * 128 + ((i >> 1) & 7) * 16 + g;
    if (c == (g >> 1)) { dst[0] = make_float2(r.x, r.y); dst[8] = make_float2(r.z, r.w); g_ln0[i * 8 + g] = 0; }
    __syncwarp();
    if (lane == 0) red_release(cnt_ptr(C_ST, i >> 4), 1);
}
__global__ void stats_kernel() { x1_stats(blockIdx.x * 4 + (threadIdx.x >> 5)); }

#define NT 9
#define RH 104
#define RW0 200
#define NPD 9
#define NTO 12
#define DP1 9
#define GPW 0
#define GPJ 0
#define PACE 2
#define EARLY 4
#define G2I 4
#define VE 4
#define VF 8
constexpr int R_WV = 0, R_WO = 65536, R_T = 131072, R_M = R_T + 20480, R_LOC = R_M + 4096, R_REM = R_LOC + 6144, R_O = R_REM + 12288, R_SX = R_O + 2048,
              R_IL = R_SX + 5120, XS = R_IL + 128 - R_T, R_BAR = 231936, R_Z = R_BAR + 128  , R_STQ = 0, R_STK = 65536, R_STV = 131072;
static_assert(R_T + 2 * XS <= R_BAR && R_BAR + 256 <= S_XBAR, "smem map");
enum { RB_INIT = 0, RB_V = 4  , RB_QK = 8  , RB_T = 12  , RB_N = 16 };
enum { NB_MF = 1  , NB_LOC = 3  , NB_PAIR = 5  , NB_O = 9  , NB_XG = 11  , NB_W = 13 };
__device__ __forceinline__ uint32_t clk32() { return (uint32_t)clock64(); }

__device__ __forceinline__ char* acc_base() { return (char*)(((size_t)g_acc + 131071) & ~(size_t)131071); }
__device__ __forceinline__ uint32_t acc_slice(uint32_t s6) { return (s6 & 1) * 256 + (s6 >> 1) * 1024; }
__device__ __forceinline__ uint32_t acc_main(uint32_t rank, uint32_t tid) { return acc_slice(rank * 32 + (tid >> 3)) + (tid & 7) * 16; }
__device__ __forceinline__ uint32_t acc_extra(uint32_t rank, uint32_t tid) { return 65536 + acc_slice(((tid >> 5) & 1) + rank * 4 + (tid >> 6) * 8) + (tid & 31) * 4; }
__device__ __forceinline__ uint32_t acc_slot(uint32_t s) { return (s & 1) * 128 + (s & 2) * 256; }
__device__ __forceinline__ void acc_init(const __nv_bfloat16* mem0, int i) {
    const uint32_t tid = i & 255, rank = (i >> 8) & 1, slot = (i >> 9) & 3, X = i >> 11;
    uint32_t v[5] = {0, 0, 0, 0, 0};
    if (slot == 3) {
        const uint16_t* m = (const uint16_t*)mem0 + (tid & 3) * 1024 + rank * 256 + (tid >> 5) * 32 + ((tid >> 2) & 7);
#pragma unroll
        for (int k = 0; k < 4; k++) v[k] = __ldg(m + k * 8) | ((uint32_t)__ldg(m + k * 8 + 512) << 16);
        v[4] = (v[3] >> 16) | 0x42000000u; v[3] = (v[3] & 0xffff) | 0x42000000u;
    }
    *(uint4*)(acc_base() + X * 32768 + acc_slot(slot) + acc_main(rank, tid)) = make_uint4(v[0], v[1], v[2], v[3]);
    *(uint32_t*)(acc_base() + X * 1024 + acc_slot(slot) + acc_extra(rank, tid)) = v[4];
}
__global__ void acc_init_kernel(const __nv_bfloat16* mem0) { acc_init(mem0, blockIdx.x * 256 + threadIdx.x); }

struct RecW { uint32_t am, ae, ah, dp, lp, lpw, vo, sb, bar, zero, ts, tn; };
__device__ __forceinline__ uint32_t vadd(uint32_t a, uint32_t b) { uint32_t d; asm volatile("add.u32 %0,%1,%2;" : "=r"(d) : "r"(a), "r"(b)); return d; }
__device__ __forceinline__ uint32_t vshr(uint32_t a, int n) { uint32_t d; asm volatile("shr.u32 %0,%1,%2;" : "=r"(d) : "r"(a), "r"(n)); return d; }
__device__ __forceinline__ uint64_t gptr(uint32_t lo, uint32_t hi) { uint64_t d; asm("mov.b64 %0,{%1,%2};" : "=l"(d) : "r"(lo), "r"(hi)); return d; }
__device__ __forceinline__ void sfence(uint32_t zero) { asm volatile("{.reg .pred p; setp.ne.u32 p,%0,0; @p exit;}" ::"r"(zero) : "memory"); }
#define SF sfence(k.zero)
#define TS(i) do {} while (0)
#define TSN(i) do {} while (0)
#define TSET(it, slot) do {} while (0)
struct Gat { uint32_t x, y, z, w, e; };
template <int X>
__device__ __forceinline__ void gat_issue(Gat& g, const RecW& k, int s, uint32_t dep) {
    const uint32_t o = acc_slot(s + 3) + dep;
    asm volatile("{.reg .b128 t; ld.relaxed.gpu.global.b128 t,[%5+%7]; mov.b128 {%0,%1,%2,%3},t; ld.relaxed.gpu.global.u32 %4,[%6+%8];}"
                 : "=r"(g.x), "=r"(g.y), "=r"(g.z), "=r"(g.w), "=r"(g.e) : "l"(gptr(k.am + o, k.ah)), "l"(gptr(k.ae + o, k.ah)), "n"(X * 32768), "n"(X * 1024) : "memory");
}
template <int X>
__device__ __forceinline__ bool gat_store(const Gat& g, const RecW& k) {
    uint32_t c;
    asm volatile("prmt.b32 %0,%1,%2,0x7632;" : "=r"(c) : "r"(g.w), "r"(g.e));
    SF;
    asm volatile("{.reg .b32 t; prmt.b32 t,%4,%6,0x5410; stmatrix.sync.aligned.m8n8.x4.trans.shared.b16 [%0+%5],{%1,%2,%3,t};}" ::"r"(k.lpw), "r"(g.x), "r"(g.y), "r"(g.z), "r"(g.w), "n"(R_M + X * XS), "r"(g.e) : "memory");
    return __all_sync(0xffffffffu, c == 0x42004200u);
}
template <int X>
__device__ __forceinline__ void gat_finish(bool ok, const RecW& k, int s) {
    if (!ok) {
        int n = s;
        while (true) {
            Gat g;
            gat_issue<X>(g, k, n, 0);
            if (gat_store<X>(g, k)) break;
            n += 4;
            if (n > 8000000) __trap();
        }
    }
}
__device__ __forceinline__ uint4 lds128o(uint32_t a, int o) { uint4 v; asm volatile("{.reg .b32 t; add.u32 t,%4,%5; ld.shared.v4.u32 {%0,%1,%2,%3},[t];}" : "=r"(v.x), "=r"(v.y), "=r"(v.z), "=r"(v.w) : "r"(a), "r"(o) : "memory"); return v; }
__device__ __forceinline__ uint4 ldsm4o(uint32_t a, int o) { uint4 v; asm volatile("{.reg .b32 t; add.u32 t,%4,%5; ldmatrix.sync.aligned.m8n8.x4.shared.b16 {%0,%1,%2,%3},[t];}" : "=r"(v.x), "=r"(v.y), "=r"(v.z), "=r"(v.w) : "r"(a), "r"(o) : "memory"); return v; }
__device__ __forceinline__ uint4 ldsm4to(uint32_t a, int o) { uint4 v; asm volatile("{.reg .b32 t; add.u32 t,%4,%5; ldmatrix.sync.aligned.m8n8.x4.trans.shared.b16 {%0,%1,%2,%3},[t];}" : "=r"(v.x), "=r"(v.y), "=r"(v.z), "=r"(v.w) : "r"(a), "r"(o) : "memory"); return v; }
__device__ __forceinline__ uint2 lds64o(uint32_t a, int o) { uint2 v; asm volatile("{.reg .b32 t; add.u32 t,%2,%3; ld.shared.v2.u32 {%0,%1},[t];}" : "=r"(v.x), "=r"(v.y) : "r"(a), "r"(o) : "memory"); return v; }
__device__ __forceinline__ void sts128o(uint32_t a, int o, uint32_t x, uint32_t y, uint32_t z, uint32_t w) { asm volatile("{.reg .b32 t; add.u32 t,%0,%5; st.shared.v4.u32 [t],{%1,%2,%3,%4};}" ::"r"(a), "r"(x), "r"(y), "r"(z), "r"(w), "r"(o) : "memory"); }
__device__ __forceinline__ void sts64o(uint32_t a, int o, uint32_t x, uint32_t y) { asm volatile("{.reg .b32 t; add.u32 t,%0,%3; st.shared.v2.u32 [t],{%1,%2};}" ::"r"(a), "r"(x), "r"(y), "r"(o) : "memory"); }
__device__ __forceinline__ uint32_t vxor(uint32_t a, uint32_t b) { uint32_t d; asm volatile("xor.b32 %0,%1,%2;" : "=r"(d) : "r"(a), "r"(b)); return d; }
#define WLD(base, i) wt[i] = lds128o(k.lpw, (base) + (i) * 4096)
template <int PASS, int X, int NP>
__device__ __forceinline__ void rec_qkv(const RecW& k, int s, const uint32_t (*wq)[4], const uint32_t (*wk)[4], uint4* wt, Gat& g2, int s2) {
    constexpr bool BWD = PASS == 2;
    float aq[4] = {0, 0, 0, 0}, ak[4] = {0, 0, 0, 0}, av[4] = {0, 0, 0, 0};
    constexpr int ma = R_M + X * XS;
    if (BWD) { TS(1); gat_finish<1>(gat_store<1>(g2, k), k, s); }
    bar_sync(NB_MF + X, 256);
    uint4 mf = ldsm4o(k.lp, ma + (BWD ? 7 : 0) * 512);
    if (BWD) TS(2); else { TS(0); TSN(13); }
#pragma unroll
    for (int ii = 0; ii < 8; ii++) {
        const int i = BWD ? 7 - ii : ii;
        const uint4 m = mf;
        if (ii < 7) mf = ldsm4o(k.lp, ma + (BWD ? i - 1 : i + 1) * 512);
        if (PASS == 1 && ii == G2I) gat_issue<1>(g2, k, s2, 0);
        SF;
#pragma unroll
        for (int hh = 0; hh < 2; hh++) {
            const int h = BWD ? 1 - hh : hh, ks = 2 * i + h;
            const uint32_t b0 = h ? m.z : m.x, b1 = h ? m.w : m.y;
            mma16(aq, wq[ks][0], wq[ks][1], wq[ks][2], wq[ks][3], b0, b1);
            mma16(ak, wk[ks][0], wk[ks][1], wk[ks][2], wk[ks][3], b0, b1);
            SF;
            mma16(av, wt[ks].x, wt[ks].y, wt[ks].z, wt[ks].w, b0, b1);
            SF;
            if (!BWD && ks + NP < 16) WLD(R_WV, ks + NP < 16 ? ks + NP : 0);
            if (BWD && ks >= NT) WLD(R_WV, ks >= NT ? ks - NT : 0);
            SF;
        }
    }
    const uint32_t ra = vadd(k.lpw, k.dp + R_REM + X * XS + (s & 1) * 6144), va = ((vshr(k.lp, 7) & 1) * 48 ^ k.lp ^ (k.vo & 64)) + (k.vo & ~64u);
    const uint32_t x0 = movm(pack2(aq[0], aq[1])), x1 = movm(pack2(aq[2], aq[3])), x2 = movm(pack2(ak[0], ak[1])), x3 = movm(pack2(ak[2], ak[3]));
    SF;
    asm volatile("stmatrix.sync.aligned.m8n8.x2.shared.b16 [%0+%3],{%1,%2};" ::"r"(va), "r"(pack2(av[0], av[1])), "r"(pack2(av[2], av[3])), "n"(R_LOC + X * XS) : "memory");
    SF;
    st_async4(ra, x0, x1, x2, x3, k.bar + X * 16);
    asm volatile("st.shared.v4.u32 [%0+%5],{%1,%2,%3,%4};" ::"r"(k.lpw), "r"(x0), "r"(x1), "r"(x2), "r"(x3), "n"(R_LOC + X * XS) : "memory");
    bar_arrive(NB_LOC + X, 320);
    SF;
    TS(BWD ? 4 : 3);
}
template <bool BWD, int X>
__device__ __forceinline__ void rec_out(const RecW& k, int s, uint4* wt, Gat& g, int s1) {
    if (BWD) { WLD(R_WO, 17 - NTO); WLD(R_WO, 16 - NTO); }
    TS(BWD ? 8 : 5);
    bar_sync(NB_O + X, 320);
    float r0[4] = {0, 0, 0, 0}, r1[4] = {0, 0, 0, 0};
    constexpr int oa = R_O + X * XS;
    uint4 bn = lds128o(k.lp, oa + (BWD ? 3 : 0) * 512);
    TS(BWD ? 9 : 6);
    uint2 il;
    uint64_t pm, pe;
#pragma unroll
    for (int ii = 0; ii < 4; ii++) {
        const int i = BWD ? 3 - ii : ii;
        const uint4 b = bn;
        if (ii < 3) bn = lds128o(k.lp, oa + (BWD ? i - 1 : i + 1) * 512);
        else { asm volatile("ld.shared.v2.u32 {%0,%1},[%2+%3];" : "=r"(il.x), "=r"(il.y) : "r"((vshr(k.ae, 2) & 3) * 8 + k.sb), "n"(R_IL + X * XS) : "memory"); pm = gptr(vadd(k.am, acc_slot(s)), k.ah); pe = gptr(vadd(k.ae, acc_slot(s)), k.ah); }
        SF;
        if (BWD && EARLY == ii + 1) { gat_issue<0>(g, k, s1 + 1, 0); SF; }
#pragma unroll
        for (int nn = 0; nn < 4; nn++) {
            const int n = BWD ? 3 - nn : nn, f = 4 * i + n, nx = BWD ? f - NTO + 2 : f + NTO - 2;
            mma16((n & 1) ? r1 : r0, wt[f].x, wt[f].y, wt[f].z, wt[f].w, n >> 1 ? b.z : b.x, n >> 1 ? b.w : b.y);
            SF;
            if (ii * 4 + nn >= 2 && nx >= 0 && nx < 16) WLD(R_WO, nx & 15);
            SF;
        }
    }
    const float i0 = __uint_as_float(il.x), i1 = __uint_as_float(il.y);
    asm volatile("red.relaxed.gpu.global.add.noftz.v4.bf16x2 [%0+%5],{%1,%2,%3,%4};" ::"l"(pm),
                 "r"(pack2(r0[0] * i0, r0[1] * i1)), "r"(pack2(r0[2] * i0, r0[3] * i1)), "r"(pack2(r1[0] * i0, r1[1] * i1)), "r"(pack2(r1[2] * i0, 1.f)), "n"(X * 32768) : "memory");
    asm volatile("red.relaxed.gpu.global.add.noftz.bf16x2 [%0+%2],%1;" ::"l"(pe), "r"(pack2(r1[3] * i1, 1.f)), "n"(X * 1024) : "memory");
    bar_arrive(NB_XG + X, 320);
    SF;
    TS(BWD ? 10 : 7);
}
__device__ __forceinline__ uint32_t pause(uint32_t v, int n) {
#pragma unroll
    for (int i = 0; i < n; i++) asm volatile("shfl.sync.bfly.b32 %0,%0,0,0x1f,0xffffffff;" : "+r"(v));
    return v;
}
template <bool DUAL, int X>
__device__ __forceinline__ void rec_step(const RecW& k, int s, int s2, const uint32_t (*wq)[4], const uint32_t (*wk)[4], uint4* wt) {
    constexpr int NP = NPD;
    uint4 wo[16];
    Gat g;
    rec_qkv<DUAL ? 1 : 0, X, NP>(k, s, wq, wk, wt, g, s2);
    if (DUAL) rec_qkv<2, 1, NP>(k, s2, wq, wk, wt, g, s2);
    uint32_t wa = k.lpw;
#pragma unroll
    for (int i = 0; i < NTO; i++) {
        wo[i] = lds128o(wa, R_WO + i * 4096);
        if (i % PACE == PACE - 1) wa = k.lpw + (wo[i].x & k.zero);
        SF;
    }
    rec_out<false, X>(k, s, wo, g, s);
    if (DUAL) { rec_out<true, 1>(k, s2, wo, g, s); if (!EARLY) gat_issue<0>(g, k, s + 1, 0); SF; }
#pragma unroll
    for (int i = 0; i < NP; i++) { WLD(R_WV, i); SF; }
    if (!DUAL) gat_issue<X>(g, k, s + 1, pause(wt[NP - 1].x & k.zero, DP1));
    TS(12);
    gat_finish<X>(gat_store<X>(g, k), k, s + 1);
    TS(11);
}

__device__ __forceinline__ void rec_fetch(const CUtensorMap* tm, uint32_t dst, int x, int y, int nx, uint32_t bar) {
#pragma unroll 1
    for (int j = 0; j < 8; j++) tma2d(dst + j * 8192, tm, x + (j / (8 / nx)) * 64, y + (j % (8 / nx)) * 64, bar);
}
__device__ __forceinline__ void rec_weights(const Params& p, uint32_t sb, int head, uint32_t rank, int w) {
    const int lane = threadIdx.x & 31, t = w & 3, WG = w >> 2;
    uint32_t wq[16][4], wk[16][4];
    const uint32_t rowo = (((lane >> 4) << 3) + (lane & 7)) * 128;
    const uint32_t woff = sb + WG * 32768 + rowo + (((2 * t + ((lane >> 3) & 1)) ^ (lane & 7)) << 4);
    const uint32_t qoff = sb + ((w & 1) ? R_STK : R_STQ) + WG * 32768 + rowo + (((2 * (t & 2) + ((lane >> 3) & 1)) ^ (lane & 7)) << 4);
    const uint32_t lw = sb + (lane ^ (lane >> 3)) * 16;
    PROF(threadIdx.x == 0, 3501);
    PROF(threadIdx.x == 0, 3502);
    mbar_wait(sb + R_BAR + RB_INIT * 8, 0);
    PROF(threadIdx.x == 0, 3503);
#pragma unroll
    for (int ks = 0; ks < 16; ks++) {
        uint4 a = ldsm4t(qoff + ks * 2048), b = ldsm4t((qoff ^ 32) + ks * 2048);
        wq[ks][0] = a.x; wq[ks][1] = a.y; wq[ks][2] = a.z; wq[ks][3] = a.w;
        wk[ks][0] = b.x; wk[ks][1] = b.y; wk[ks][2] = b.z; wk[ks][3] = b.w;
    }
    bar_sync(NB_W, 256);
#pragma unroll 4
    for (int ks = 0; ks < 16; ks++) { const uint4 a = ldsm4t(woff + R_STV + ks * 2048); sts128(lw + w * 512 + R_WV + ks * 4096, a.x, a.y, a.z, a.w); }
    bar_sync(NB_W, 256);
    if (threadIdx.x == 0) {
        mbar_expect(sb + R_BAR + RB_INIT * 8, 65536);
        rec_fetch(&p.tm[4], sb + R_STV, rank * 256, head * 128, 4, sb + R_BAR + RB_INIT * 8);
    }
    __syncwarp();
    mbar_wait(sb + R_BAR + RB_INIT * 8, 1);
#pragma unroll 4
    for (int f = 0; f < 16; f++) {
        const uint4 a = ldsm4t(sb + R_STV + (w >> 1) * 16384 + (f >> 1) * 2048 + rowo + ((((w & 1) * 4 + (f & 1) * 2 + ((lane >> 3) & 1)) ^ (lane & 7)) << 4));
        sts128(lw + w * 512 + R_WO + f * 4096, a.x, a.y, a.z, a.w);
    }
    PROF(threadIdx.x == 0, 3504);
    __syncthreads();
    cluster_sync();
    PROF(threadIdx.x == 0, 3505);
    RecW k;
    k.am = __shfl_sync(0xffffffffu, (uint32_t)(size_t)acc_base() + acc_main(rank, threadIdx.x), lane);
    k.ae = __shfl_sync(0xffffffffu, (uint32_t)(size_t)acc_base() + acc_extra(rank, threadIdx.x), lane);
    k.ah = (uint32_t)((size_t)acc_base() >> 32);
    k.sb = sb; k.zero = p.zero;

    k.dp = mapa(sb, rank ^ 1) - sb;
    k.lp = __shfl_sync(0xffffffffu, lw, lane);
    k.lpw = __shfl_sync(0xffffffffu, lw + w * 512, lane);
    k.vo = 4096 + w * 256 + (w & 1) * 64;
    k.bar = sb + k.dp + R_BAR + (RB_QK + WG) * 8;
    int it = 0;
    uint4 wt[16];
#pragma unroll
    for (int i = 0; i < NPD; i++) WLD(R_WV, i);
    gat_finish<0>(false, k, 0);
#pragma unroll 1
    for (; it < min(p.b1, p.e0); it++) { TSET(it, w == GPW ? 0 : 3); rec_step<false, 0>(k, it, it, wq, wk, wt); }
#pragma unroll 1
    for (; it < p.e0; it++) { TSET(it, w == GPW ? 0 : 3); rec_step<true, 0>(k, it, it - p.b1, wq, wk, wt); }
    if (it < p.nit) gat_finish<1>(false, k, it - p.b1);
#pragma unroll 1
    for (; it < p.nit; it++) { TSET(it, w == GPW ? 0 : 3); rec_step<false, 1>(k, it - p.b1, it - p.b1, wq, wk, wt); }
}

__device__ __forceinline__ void mma16_top(float* c, uint32_t a0, uint32_t a2, uint32_t b0, uint32_t b1) {
    asm volatile("{.reg .b32 j; mma.sync.aligned.m16n8k16.row.col.f32.bf16.bf16.f32 {%0,%1,%2,%3},{%4,j,%5,j},{%6,%7},{%0,%1,%2,%3};}"
                 : "+f"(c[0]), "+f"(c[1]), "+f"(c[2]), "+f"(c[3]) : "r"(a0), "r"(a2), "r"(b0), "r"(b1));
}
__device__ __forceinline__ void rec_load_tile(uint32_t sb, int X, int j, int s, int head, uint32_t rank) {
    const uint32_t bar = sb + R_BAR + (RB_T + X * 2 + j) * 8;
    mbar_expect1(bar, j ? 4096 : 16384);
    bulk_g2s1(sb + R_T + X * XS + j * 16384, g_qkv[X] + (size_t)(s * 32 + head) * 1536 + (j ? rank * 256 : 512), j ? 4096 : 16384, bar, POL_LAST);
}
__device__ __forceinline__ bool chunk_ready(int X, int j, int s) {
    unsigned v;
    asm volatile("ld.relaxed.gpu.global.u32 %0,[%1];" : "=r"(v) : "l"(cnt_ptr(C_QKV0 + X, (s >> 2) + j * 16)) : "memory");
    return __all_sync(0xffffffffu, v >= (256 >> j));
}
__device__ __forceinline__ uint4 hadd4(uint4 a, uint4 b) { return make_uint4(hadd2(a.x, b.x), hadd2(a.y, b.y), hadd2(a.z, b.z), hadd2(a.w, b.w)); }
struct RecH { uint32_t lw, lm, lq, lv, lu, sa, sp, xb, sb, zero, ts, tn; };
__device__ __forceinline__ void rec_publish(int X, int s) {
    asm volatile("{.reg .pred p; cp.async.bulk.wait_group 0; elect.sync _|p,0xffffffff; @p red.relaxed.gpu.global.add.u32 [%0],4;}" ::"l"(cnt_ptr(C_O0 + X, s >> 2)) : "memory");
}
__device__ __forceinline__ void rec_mattn(const RecH& k, uint32_t dp, int X, int j, int s, uint4 (*V)[4], uint4* vm, uint4* kmm) {
    const uint32_t sb = k.sb, to = R_T, lo = R_LOC, ro = R_REM + (s & 1) * 6144;
    const uint32_t bar = sb + R_BAR + (X * 2 + j) * 8;
    uint4 K[2][4];
    mbar_wait(sb + R_BAR + (RB_T + X * 2) * 8, s & 1);
    TS(1);
#pragma unroll
    for (int i = 0; i < 8; i++) K[i >> 2][i & 3] = ldsm4o(k.lm, (to + (i >> 2) * 1024 + ((i >> 1) & 1) * 4096 + (i & 1) * 512));
    asm volatile("cp.async.bulk.wait_group 0;" ::: "memory");
    bar_sync(NB_LOC + X, 320);
    fence_async_smem();
    asm volatile("{.reg .pred p; elect.sync _|p,0xffffffff; @p cp.async.bulk.shared::cluster.shared::cta.mbarrier::complete_tx::bytes [%0],[%1],1024,[%2];}"
                 ::"r"(k.xb + dp + ro + 4096), "r"(k.xb + lo + 4096), "r"(bar + dp + RB_V * 8) : "memory");
    uint4 u[4];
#pragma unroll
    for (int i = 0; i < 4; i++) u[i] = ldsm4o(k.lm, (lo + i * 512));
    TS(2);
    mbar_wait(bar + RB_QK * 8, s & 1);
    TS(3);
    float S[5][4];
#pragma unroll
    for (int i = 0; i < 5; i++) S[i][0] = S[i][1] = S[i][2] = S[i][3] = 0;
    {
        uint4 r[4];
#pragma unroll
        for (int i = 0; i < 4; i++) r[i] = ldsm4o(k.lm, (ro + i * 512));
        SF;
#pragma unroll
        for (int e = 0; e < 2; e++) {
            uint4& km = u[2 * e + 1];
            const uint32_t q0 = hadd2(u[2 * e].x, r[2 * e].x), q1 = hadd2(u[2 * e].y, r[2 * e].y);
            mma16_top(S[0], q0, q1, K[e][0].x, K[e][0].y);
            km.x = hadd2(km.x, r[2 * e + 1].x); km.y = hadd2(km.y, r[2 * e + 1].y);
            SF;
            mma16_top(S[1], q0, q1, K[e][1].x, K[e][1].y);
            const uint32_t q2 = hadd2(u[2 * e].z, r[2 * e].z), q3 = hadd2(u[2 * e].w, r[2 * e].w);
            SF;
            mma16_top(S[2], q0, q1, K[e][2].x, K[e][2].y);
            km.z = hadd2(km.z, r[2 * e + 1].z); km.w = hadd2(km.w, r[2 * e + 1].w);
            SF;
            mma16_top(S[3], q0, q1, K[e][3].x, K[e][3].y);
            mma16_top(S[4], q0, q1, km.x, km.y);
            SF;
#pragma unroll
            for (int i = 0; i < 4; i++) {
                mma16_top(S[i], q2, q3, K[e][i].z, K[e][i].w); SF;
            }
            mma16_top(S[4], q2, q3, km.z, km.w);
            SF;
        }
    }
#define VLD(a, b) _Pragma("unroll") for (int i = (a); i < (b); i++) V[i >> 2][i & 3] = ldsm4to((i & 1) ? lv2 : k.lv, (to + 8192 + (i >> 2) * 4096 + ((i >> 1) & 1) * 1024))
    const uint32_t lv2 = vxor(k.lv, 0x20), lh = k.lw - (vshr(k.lw - k.xb, 1) & 0xf8);
    VLD(0, VE);
    SF;
    const uint32_t sxr = k.sa, sxw = k.sp;
    sts128o(k.lw, sxw, __float_as_uint(S[0][0]), __float_as_uint(S[0][1]), __float_as_uint(S[1][0]), __float_as_uint(S[1][1]));
    SF;
    sts128o(k.lw, (sxw + 512), __float_as_uint(S[2][0]), __float_as_uint(S[2][1]), __float_as_uint(S[3][0]), __float_as_uint(S[3][1]));
    SF;
    sts64o(lh, (sxw + 1024), __float_as_uint(S[4][0]), __float_as_uint(S[4][1]));
    TS(4);
    bar_sync(NB_PAIR + X, 64);
    {
        const uint4 a = lds128o(k.lw, sxr), b = lds128o(k.lw, (sxr + 512));
        const uint2 c = lds64o(lh, (sxr + 1024));
        SF;
        VLD(VE, VF);
        SF;
        S[0][0] += __uint_as_float(a.x); S[0][1] += __uint_as_float(a.y); S[1][0] += __uint_as_float(a.z); S[1][1] += __uint_as_float(a.w);
        S[2][0] += __uint_as_float(b.x); S[2][1] += __uint_as_float(b.y); S[3][0] += __uint_as_float(b.z); S[3][1] += __uint_as_float(b.w);
        S[4][0] += __uint_as_float(c.x); S[4][1] += __uint_as_float(c.y);
    }
    float m = fmaxf(fmaxf(fmaxf(S[0][0], S[0][1]), fmaxf(S[1][0], S[1][1])), fmaxf(fmaxf(S[2][0], S[2][1]), fmaxf(S[3][0], S[3][1])));
    m = fmaxf(m, fmaxf(S[4][0], S[4][1]));
    m = fmaxf(m, __shfl_xor_sync(0xffffffffu, m, 1));
    const float m2 = __shfl_xor_sync(0xffffffffu, m, 2);
    SF;
    VLD(VF, 8);
    uint32_t ok;
    asm volatile("{.reg .pred p; mbarrier.test_wait.parity.shared::cta.b64 p,[%1],%2; selp.u32 %0,1,0,p;}" : "=r"(ok) : "r"(bar + RB_V * 8), "r"(s & 1) : "memory");
    uint4 vr0 = ldsm4o(k.lu, (ro + 4096)), vr1 = ldsm4o(k.lu, (ro + 4608));
    vm[0] = ldsm4o(k.lu, (lo + 4096)); vm[1] = ldsm4o(k.lu, (lo + 4608));
    SF;
    TS(5);
    m = fmaxf(m, m2) * -SC_LOG2E;
    uint32_t P[5];
#pragma unroll
    for (int i = 0; i < 5; i++) P[i] = pack2(ex2(fmaf(S[i][0], SC_LOG2E, m)), ex2(fmaf(S[i][1], SC_LOG2E, m)));
    float o[4][4], l[4] = {0, 0, 0, 0};
    const uint32_t ONE = 0x3f803f80u;
    mma16_top(l, ONE, ONE, P[0], P[1]);
#pragma unroll
    for (int t = 0; t < 4; t++) { o[t][0] = o[t][1] = o[t][2] = o[t][3] = 0; mma16(o[t], V[0][t].x, V[0][t].y, V[0][t].z, V[0][t].w, P[0], P[1]); }
    mma16_top(l, ONE, ONE, P[2], P[3]);
#pragma unroll
    for (int t = 0; t < 4; t++) mma16(o[t], V[1][t].x, V[1][t].y, V[1][t].z, V[1][t].w, P[2], P[3]);
    if (!__all_sync(0xffffffffu, ok)) {
        mbar_wait(bar + RB_V * 8, s & 1);
        vr0 = ldsm4o(k.lu, (ro + 4096)); vr1 = ldsm4o(k.lu, (ro + 4608));
    }
    TS(6);
    vm[0] = hadd4(vm[0], vr0); vm[1] = hadd4(vm[1], vr1);
    mma8(l, ONE, ONE, P[4]);
    mma8(o[0], vm[0].x, vm[0].y, P[4]); mma8(o[1], vm[0].z, vm[0].w, P[4]); mma8(o[2], vm[1].x, vm[1].y, P[4]); mma8(o[3], vm[1].z, vm[1].w, P[4]);
    asm volatile("{.reg .pred p; .reg .b32 t; setp.lt.u32 p,%0,%3; add.u32 t,%0,%4; @p st.shared.v2.f32 [t],{%1,%2};}" ::"r"(lh), "f"(rcp(l[0])), "f"(rcp(l[1])), "r"(k.xb + 32), "r"(R_IL) : "memory");
#pragma unroll
    for (int t = 0; t < 4; t += 2)
        asm volatile("{.reg .b32 t; add.u32 t,%0,%5; stmatrix.sync.aligned.m8n8.x4.trans.shared.b16 [t],{%1,%2,%3,%4};}" ::"r"(k.lm),
                     "r"(pack2(o[t][0], o[t][1])), "r"(pack2(o[t][2], o[t][3])), "r"(pack2(o[t + 1][0], o[t + 1][1])), "r"(pack2(o[t + 1][2], o[t + 1][3])), "r"(R_O - j * 1024 + t * 256) : "memory");
    bar_arrive(NB_O + X, 320);
    PROF(k.lw == k.xb, X * 64 + s);
    TS(7);
    kmm[0] = u[1]; kmm[1] = u[3];
    mbar_expect1(bar + RB_QK * 8, 2048); mbar_expect1(bar + RB_V * 8, 1024);
}
template <int MT>
__device__ __forceinline__ void rec_xattn(const RecH& k, int X, int j, int s, int head, bool early, const uint4 (*V)[4], const uint4* vmm, const uint4* kmm) {
    constexpr int NTL = 3 + 2 * MT;
    const uint32_t sb = k.sb, to = R_T;
    const uint32_t sxw = k.sa, sxr = k.sp;
    const uint32_t lq2 = vxor(k.lq, 0x20);
    float S[NTL][4];
#pragma unroll
    for (int i = 0; i < NTL; i++) S[i][0] = S[i][1] = S[i][2] = S[i][3] = 0;
    {
        uint4 q[2][2], kk[2][NTL];
#define XQ(e) q[e][0] = ldsm4o(k.lq, (to + 16384 + (e) * 1024)); q[e][1] = ldsm4o(lq2, (to + 16384 + (e) * 1024))
#define XK(e, i) kk[e][i] = ldsm4o(k.lm, (to + (e) * 1024 + (((i) - 1) >> 1) * 4096 + (((i) - 1) & 1) * 512))
        kk[0][0] = kmm[0]; kk[1][0] = kmm[1];
        if (!X) bar_sync(NB_XG, 320);
        XQ(0);
#pragma unroll
        for (int i = 1; i < NTL; i++) XK(0, i);
        SF;
#pragma unroll
        for (int i = 0; i < NTL; i++) { mma16(S[i], q[0][0].x, q[0][0].y, q[0][0].z, q[0][0].w, kk[0][i].x, kk[0][i].y); SF; }
        q[1][0] = ldsm4o(k.lq, (to + 16384 + 1024));
#pragma unroll
        for (int i = 0; i < NTL; i++) { mma16(S[i], q[0][1].x, q[0][1].y, q[0][1].z, q[0][1].w, kk[0][i].z, kk[0][i].w); SF; if (i + 1 < NTL) XK(1, i + 1); SF; }
        q[1][1] = ldsm4o(lq2, (to + 16384 + 1024));
        SF;
#pragma unroll
        for (int i = 0; i < NTL; i++) { mma16(S[i], q[1][0].x, q[1][0].y, q[1][0].z, q[1][0].w, kk[1][i].x, kk[1][i].y); SF; }
#pragma unroll
        for (int i = 0; i < NTL; i++) { mma16(S[i], q[1][1].x, q[1][1].y, q[1][1].z, q[1][1].w, kk[1][i].z, kk[1][i].w); SF; }
    }
#pragma unroll
    for (int i = 0; i < NTL; i++) sts128o(k.lw, (sxw + i * 512), __float_as_uint(S[i][0]), __float_as_uint(S[i][1]), __float_as_uint(S[i][2]), __float_as_uint(S[i][3]));
    SF;
    if (X) bar_sync(NB_XG + 1, 320); else bar_sync(NB_PAIR + 2, 64);
    TS(9);
    if (early && !X) rec_load_tile(sb, X, j, s + 1, head, MT);
#pragma unroll
    for (int i = 0; i < NTL; i++) {
        const uint4 r = lds128o(k.lw, (sxr + i * 512));
        S[i][0] += __uint_as_float(r.x); S[i][1] += __uint_as_float(r.y); S[i][2] += __uint_as_float(r.z); S[i][3] += __uint_as_float(r.w);
    }
    const int g = vshr(k.lw - k.xb, 6) & 7, c = (vshr(k.lw, 4) ^ (g >> 1)) & 3;
    const float NEG = -__int_as_float(0x7f800000);
    if (2 * c > g) { S[NTL - 2][0] = NEG; S[NTL - 1][2] = NEG; }
    if (2 * c + 1 > g) { S[NTL - 2][1] = NEG; S[NTL - 1][3] = NEG; }
    float m0 = fmaxf(S[0][0], S[0][1]), m1 = fmaxf(S[0][2], S[0][3]);
#pragma unroll
    for (int i = 1; i < NTL; i++) { if (i < NTL - 1) m0 = fmaxf(m0, fmaxf(S[i][0], S[i][1])); m1 = fmaxf(m1, fmaxf(S[i][2], S[i][3])); }
    m0 = fmaxf(m0, __shfl_xor_sync(0xffffffffu, m0, 1)); m1 = fmaxf(m1, __shfl_xor_sync(0xffffffffu, m1, 1));
    m0 = fmaxf(m0, __shfl_xor_sync(0xffffffffu, m0, 2)); m1 = fmaxf(m1, __shfl_xor_sync(0xffffffffu, m1, 2));
    m0 *= -SC_LOG2E; m1 *= -SC_LOG2E;
    uint32_t P[NTL][2];
#pragma unroll
    for (int i = 0; i < NTL; i++) {
        P[i][0] = i < NTL - 1 ? pack2(ex2(fmaf(S[i][0], SC_LOG2E, m0)), ex2(fmaf(S[i][1], SC_LOG2E, m0))) : 0u;
        P[i][1] = pack2(ex2(fmaf(S[i][2], SC_LOG2E, m1)), ex2(fmaf(S[i][3], SC_LOG2E, m1)));
    }
    float l[4] = {0, 0, 0, 0};
#pragma unroll
    for (int i = 0; i < NTL; i++) mma8(l, P[i][0], P[i][1], 0x3f803f80u);
    const float l0 = rcp(l[0]), l1 = rcp(l[2]);

#pragma unroll
    for (int e = 0; e < 2; e++) {
        const uint4 vm = vmm[e];
        uint32_t u[2][4];
#pragma unroll
        for (int n = 0; n < 4; n++) {
            float a[4] = {0, 0, 0, 0};
#pragma unroll
            for (int m = 0; m <= MT; m++) {
                const uint4 v = V[m][e * 2 + (n >> 1)];
                mma8(a, P[1 + 2 * m][0], P[1 + 2 * m][1], (n & 1) ? v.y : v.x); mma8(a, P[2 + 2 * m][0], P[2 + 2 * m][1], (n & 1) ? v.w : v.z);
            }
            mma8(a, P[0][0], P[0][1], n == 0 ? vm.x : n == 1 ? vm.y : n == 2 ? vm.z : vm.w);
            u[0][n] = pack2(a[0] * l0, a[1] * l0); u[1][n] = pack2(a[2] * l1, a[3] * l1);
        }
        sts128o(k.lw, sxr + e * 512, u[0][0], u[0][1], u[0][2], u[0][3]); sts128o(k.lw, sxr + e * 512 + 1024, u[1][0], u[1][1], u[1][2], u[1][3]);
    }
    if (early && X) rec_load_tile(sb, X, j, s + 1, head, MT);
    TS(10);
}
__device__ __forceinline__ void rec_attn(const Params& p, uint32_t sb, int X, int j, int head, uint32_t rank) {
    const int lane = threadIdx.x & 31;
    RecH k;
    k.xb = sb + X * XS + j * 1024;
    const uint32_t x2 = k.xb + j * 1024;
    k.lw = __shfl_sync(0xffffffffu, x2 + (lane ^ (lane >> 3)) * 16, lane);
    k.lm = __shfl_sync(0xffffffffu, x2 + ((lane & 7) * 4 + ((lane >> 3) ^ ((lane & 7) >> 1))) * 16, lane);
    k.lq = __shfl_sync(0xffffffffu, x2 + ((lane >> 3) & 1) * 512 + ((lane & 7) * 4 + ((lane >> 4) ^ ((lane & 7) >> 1))) * 16, lane);
    k.lv = __shfl_sync(0xffffffffu, x2 + (lane >> 4) * 512 + ((lane & 7) * 4 + (((lane >> 3) & 1) ^ ((lane & 7) >> 1))) * 16, lane);
    k.lu = __shfl_sync(0xffffffffu, k.xb + ((lane & 6) * 4 + (((lane >> 3) * 2 + (lane & 1)) ^ (lane & 6))) * 16, lane);
    k.sa = __shfl_sync(0xffffffffu, R_SX + j * 512, 0); k.sp = __shfl_sync(0xffffffffu, R_SX + 2560 - j * 4608, 0);
    k.sb = sb; k.zero = p.zero;
    const uint32_t dp = mapa(sb, rank ^ 1) - sb;
    char* zp = acc_base() + (j ? X * 32768 + acc_main(rank, head * 8) : X * 1024 + acc_extra(rank, head * 8));
    mbar_expect1(sb + R_BAR + (RB_QK + X * 2 + j) * 8, 2048); mbar_expect1(sb + R_BAR + (RB_V + X * 2 + j) * 8, 1024);
    bool early = false;
#pragma unroll 1
    for (int s = 0; s < 64; s++) {
        TSET(X ? s + p.b1 : s, j == GPJ ? 1 + X : 3);
        TS(0);
        if (!early) {
            if (!j) wait_cnt_warp(cnt_ptr(C_QKV0 + X, s >> 2), 256);
            early = !j || chunk_ready(X, 1, s);
            if (early) rec_load_tile(sb, X, j, s, head, rank);
        }
        uint4 V[2][4], vm[2], km[2];
        rec_mattn(k, dp, X, j, s, V, vm, km);
        if (!early) { wait_cnt_warp(cnt_ptr(C_QKV0 + X, (s >> 2) + 16), 128); rec_load_tile(sb, X, 1, s, head, rank); }
        early = s < 63 && ((s & 3) != 3 || chunk_ready(X, j, s + 1));
        mbar_wait(sb + R_BAR + (RB_T + X * 2 + 1) * 8, s & 1);
        if (rank) rec_xattn<1>(k, X, j, s, head, early, V, vm, km); else rec_xattn<0>(k, X, j, s, head, early, V, vm, km);
        fence_async_smem();
        __syncwarp();
        asm volatile("{.reg .pred p; elect.sync _|p,0xffffffff;\n"
                     "@p cp.async.bulk.global.shared::cta.bulk_group.L2::cache_hint [%0],[%1],2048,%2;\n"
                     "@p cp.async.bulk.global.shared::cta.bulk_group [%3],[%4],%5;\n"
                     "cp.async.bulk.commit_group;}"
                     ::"l"(g_o[X] + ((s >> 2) * 64 + head * 2 + j) * 1024 + ((s & 3) * 2 + rank) * 128), "r"(x2 + k.sp),
                       "l"((X && s < 40) ? POL_LATE : POL_SOON), "l"(zp + acc_slot(s + 2)), "r"(sb + R_Z), "r"(j ? 128 : 32) : "memory");
        if ((s & 3) == 3) {
            if (!early && s < 63 && chunk_ready(X, j, s + 1)) { rec_load_tile(sb, X, j, s + 1, head, rank); early = true; }
            rec_publish(X, s);
            PROF(lane == 0 && j, 3900 + X * 16 + (s >> 2));
        }
    }
}

__device__ __forceinline__ void rec_init(const Params& p, uint32_t sb, int head, uint32_t rank) {
    const uint32_t b = sb + R_BAR;
    const int i = threadIdx.x - 320;
    if (i >= 0 && i < RB_N) {
        mbar_init(b + i * 8, 1);
        asm volatile("fence.mbarrier_init.release.cluster;" ::: "memory");
    }
    if (i == 0) mbar_expect(b + RB_INIT * 8, 196608);
    if (i >= 0 && i < 32) sts32(sb + R_Z + i * 4, 0);
}

#define NSTGN 8
constexpr int NSTG = NSTGN, STG_B = 24576;
#define LAGH 3
constexpr int NSB = 8;
constexpr int B_OUT = NSTG * STG_B  , B_UT = B_OUT, B_YT = B_UT + 16384, B_SP = B_YT  ,
              B_ST = 229376  , B_BAR = 231936;
static_assert(B_OUT + NSB * 4096 <= B_ST && B_ST + 2048 <= B_BAR && B_YT + 10240 <= B_ST, "smem map");
enum { BB_FULL = 0, BB_EMPTY = 8, BB_SF = 16  , BB_GO = 18, BB_DONE = 20  , BB_IDLE = 22  , BB_N = 30 };
enum { NB_REL = 2  , NB_C = 11, NB_WG = 12  , NB_PH = 14 };

__device__ __forceinline__ void bulk_init(uint32_t sb) {
    const int i = threadIdx.x - 320;
    if (i >= 0 && i < BB_N) {
        mbar_init(sb + B_BAR + i * 8, (i >= BB_EMPTY && i < BB_EMPTY + NSTG) ? 4 : i >= BB_DONE ? 4 : 1);
        asm volatile("fence.mbarrier_init.release.cluster;" ::: "memory");
    }
}

struct Task { int type, layer, ch, a, b, c, blk; bool pair, dry; };
__device__ __forceinline__ Task task_of(uint32_t tk, uint32_t rank) {
    Task t;
    t.type = tk & 7; t.layer = (tk >> 3) & 1; t.a = (tk >> 8) & 255; t.b = (tk >> 16) & 255; t.c = (tk >> 24) & 127; t.dry = tk >> 31;
    t.pair = t.type <= T_OP && (t.c & 64);
    t.ch = ((tk >> 4) & 15) + (t.pair ? rank : 0);
    t.blk = t.type == T_QKV ? t.a + (t.pair ? 0 : rank) : 192 + (t.pair ? (t.c >> 2) & 4 : rank * 4);
    return t;
}
__device__ __forceinline__ int qkv_blk(const Task& t, int u) {
    const int v = t.blk + (t.pair ? 1 : 2 * t.c) * u;
    return 2 * (v < 64 ? v + 32 : v - 64);
}
__device__ __forceinline__ void bulk_producer(const Params& p, uint32_t sb, int cl, uint32_t rank) {
    int st = 0; uint32_t ph = 1;
    const int tag = __shfl_sync(0xffffffffu, lds32(sb + S_TAG), 0);
    bool gated = false;
#define ACQ(bytes) do { mbar_wait(sb + B_BAR + (BB_EMPTY + st) * 8, ph); mbar_expect1(sb + B_BAR + (BB_FULL + st) * 8, bytes); } while (0)
#define NEXT do { if (++st == NSTG) { st = 0; ph ^= 1; } } while (0)
#pragma unroll 1
    for (int ti = 0; ti < MAXT; ti++) {
        const Task t = task_of(p.task[cl][ti], rank);
        const int layer = t.layer, ch = t.ch;
        if (t.type == T_END) break;
        if (t.type <= T_OP) {
            const bool qkv = t.type == T_QKV;
            const int nh = (qkv ? 8 : 2) * t.b;
            const unsigned* dep = cnt_ptr(qkv ? (layer ? C_CV : C_ST) : C_O0 + layer, ch);
            const unsigned need = qkv ? (layer ? 32 : ch < 2 ? 0 : 16) : 512;
            const uint16_t mb = t.pair ? 3 : 1 << rank, ma = t.pair ? 1 << rank : 3;
            const int pend = min(nh, gated ? NSTG : 4);
            auto ready = [&](int h) {
                if (h < pend) {
                    unsigned v = 0;
                    if (gated) asm volatile("ld.relaxed.gpu.global.u32 %0,[%1];" : "=r"(v) : "l"(dep) : "memory");
                    return gated && __all_sync(0xffffffffu, v >= need);
                }
                if (!gated) { wait_cnt_warp(g_gate, lds32(sb + S_GATE)); gated = true; }
                if (need) wait_cnt_warp(dep, need);
                return true;
            };
            bool open = true;
            if (qkv) {
#pragma unroll 1
                while (st) { ACQ(0); NEXT; }
#pragma unroll 1
                for (int h = 0; h < nh; h++) {
                    const int blk = qkv_blk(t, h >> 3);
                    ACQ(16384 + (h < 2 ? (layer ? 8192 : 1024) : 0));
                    if (!t.pair || !rank) tma3d_mc(sb + st * STG_B, &p.t3[1][blk >> 6], (h & 7) * 64, blk & 63, sb + B_BAR + (BB_FULL + st) * 8, mb);
                    if (!t.pair || rank) tma3d_mc(sb + st * STG_B + 8192, &p.t3[1][blk >> 6], (h & 7) * 64 + 32, blk & 63, sb + B_BAR + (BB_FULL + st) * 8, mb);
                    NEXT;
                    if (open && h && ready(h + 1)) {
                        open = false;
                        const float2* sp = g_st[layer] + ch * 2048 + (need ? 0 : tag * 256);
                        bulk_g2s1(sb + 16384, sp, layer ? 8192 : 1024, sb + B_BAR + BB_FULL * 8, POL_N);
                        bulk_g2s1(sb + STG_B + 16384, sp + (layer ? 1024 : 128), layer ? 8192 : 1024, sb + B_BAR + (BB_FULL + 1) * 8, POL_N);
                    }
                }
                continue;
            }
            if (PFC && !layer && (t.c & 15) < 8) {
                const int q = (t.c & 15) * 2 + rank;
                asm volatile("{.reg .pred p; elect.sync _|p,0xffffffff; @p cp.async.bulk.prefetch.L2.global [%0],8192; @p cp.async.bulk.prefetch.L2.global [%1],%2;}"
                             ::"l"(g_xA[0] + (ch * 16 + q) * 512), "l"(g_P + q * 16 * 32 * PW), "r"((2 + (ch & 1)) * 32 * PW * 4) : "memory");
            }
            const CUtensorMap *tb = &p.t3[t.pair][3], *ta = &p.ta[t.pair];
            const uint32_t db = sb + 8192 + (t.pair ? rank * 8192 : 0), da = sb + (t.pair ? 0 : rank * 4096);
            const int zb = (t.blk & 63) + (t.pair ? rank * 2 : 0), ya = 4096 + ((layer * 16 + ch) * 64 + t.a) * 16 + (t.pair ? 0 : rank * 8), row = t.a * 64;
            int h = 0;
            const int s0 = st;
#pragma unroll 1
            for (; !ready(h); h++) { ACQ(STG_B); tma3d_mc(db + st * STG_B, tb, row + h * 32, zb, sb + B_BAR + (BB_FULL + st) * 8, mb); NEXT; }
#pragma unroll 1
            for (int k = 0; k < h; k++) {
                const int s2 = (s0 + k) & (NSTG - 1);
                tma2d_mc(da + s2 * STG_B, ta, (k & 1) * 256, ya + (k >> 1) * 16, sb + B_BAR + (BB_FULL + s2) * 8, ma, POL_LAST);
            }
#pragma unroll 1
            for (; h < nh; h++) {
                ACQ(STG_B);
                tma3d_mc(db + st * STG_B, tb, row + h * 32, zb, sb + B_BAR + (BB_FULL + st) * 8, mb);
                tma2d_mc(da + st * STG_B, ta, (h & 1) * 256, ya + (h >> 1) * 16, sb + B_BAR + (BB_FULL + st) * 8, ma, POL_LAST);
                NEXT;
            }
#pragma unroll 1
            for (h = 0; h < 4 && !layer; h++) { ACQ(0); NEXT; }
        } else if (t.type == T_CV) {
            const int q = t.a + rank;
            if (!gated) { wait_cnt_warp(g_gate, lds32(sb + S_GATE)); gated = true; }
            if (layer) {
                wait_cnt_warp(cnt_ptr(C_U, ch - 2), 32);
#pragma unroll 1
                for (int j = ch + 1; j >= 2; j--) {
                    ACQ(16 * PW * 4 + (j > 2 ? 4096 : 0));
                    bulk_g2s1(sb + st * STG_B, g_P + (((q >> 1) * 16 + j) * 2 + (q & 1)) * 16 * PW, 16 * PW * 4, sb + B_BAR + (BB_FULL + st) * 8, POL_N);
                    if (j > 2) bulk_g2s1(sb + st * STG_B + 12288, g_u + (((q >> 1) * 16 + ch + 1 - j) * 2 + (q & 1)) * 256, 4096, sb + B_BAR + (BB_FULL + st) * 8, POL_N);
                    NEXT;
                }
            } else {
#pragma unroll 1
                for (int j = min(ch, 1 + (ch & 1)); j >= 0; j--) {
                    if (j == 0 && ch >= 2) {
                        wait_cnt_warp(cnt_ptr(C_H, ch & ~1), 64);
#pragma unroll 1
                        for (int i = 0; i < ((ch & 1) || ch == 2 ? 1 : 2); i++) {
                            ACQ(16384);
                            bulk_g2s1(sb + st * STG_B, g_carry[i] + (ch * 16 + q) * 1024, 16384, sb + B_BAR + (BB_FULL + st) * 8, POL_LAST);
                            NEXT;
                        }
                    }
                    ACQ(32 * PW * 4);
                    bulk_g2s1(sb + st * STG_B, g_P + (q * 16 + j) * 32 * PW, 32 * PW * 4, sb + B_BAR + (BB_FULL + st) * 8, POL_N);
                    NEXT;
                }
            }
        }
    }
}

__device__ __forceinline__ uint4* qkv_dst(int layer, int ch, int w, int blk);
__device__ __forceinline__ uint4* op_dst(int layer, int ch, int slot, int w, uint32_t rank);
__device__ __forceinline__ uint64_t out_pol(int type, int layer, int ch) { return (type == T_QKV ? (!layer && ch > 1) : (layer && ch < 10)) ? POL_LATE : POL_SOON; }
__device__ __forceinline__ void bulk_relay(const Params& p, uint32_t sb, int cl) {
    for (int ti = 0; ti < MAXT; ti++) {
        const int type = p.task[cl][ti] & 7;
        if (type == T_END) break;
        if (type != T_QKV) continue;
        bar_sync(NB_PH, 96);
        const uint32_t ph = lds32(sb + B_ST + 8);
#pragma unroll 1
        for (int h = 2; h < 8; h++) {
            mbar_wait(sb + B_BAR + (BB_FULL + h) * 8, ph);
            if (h == 4 || h == 7) { bar_arrive(NB_REL + (h == 7) * 2, 160); bar_arrive(NB_REL + (h == 7) * 2 + 1, 160); }
        }
    }
}
__device__ __forceinline__ void bulk_release(const Params& p, uint32_t sb, int cl, uint32_t rank, int wg) {
    int nd = 0;
    for (int ti = 0; ti < MAXT; ti++) {
        const Task t = task_of(p.task[cl][ti], rank);
        const int type = t.type, layer = t.layer, ch = t.ch;
        if (type == T_END) break;
        if (type == T_FIN || (type == T_OP && (t.c & 32))) continue;
        if (type == T_OP && !layer) {
            mbar_wait(sb + B_BAR + (BB_DONE + wg) * 8, nd & 1);
            nd++;
            const int s0 = __shfl_sync(0xffffffffu, lds32(sb + B_ST + wg * 4), 0) + wg * 2;
            fence_async_smem();
#pragma unroll 1
            for (int w = 0; w < 4; w++)
                asm volatile("{.reg .pred p; elect.sync _|p,0xffffffff; @p cp.async.bulk.global.shared::cta.bulk_group.L2::cache_hint [%0],[%1],8192,%2; cp.async.bulk.commit_group;}"
                             ::"l"(op_dst(0, ch, t.c & 15, wg * 4 + w, rank)), "r"(sb + ((s0 + (w >> 1)) & (NSTG - 1)) * STG_B + (w & 1) * 8192), "l"(POL_SOON) : "memory");
            mbar_arrive1(sb + B_BAR + (BB_SF + wg) * 8);
            asm volatile("{.reg .pred p; elect.sync _|p,0xffffffff;\n"
                         "cp.async.bulk.wait_group 3; @p red.relaxed.gpu.global.add.u32 [%0],1; cp.async.bulk.wait_group 2; @p red.relaxed.gpu.global.add.u32 [%0+64],1;\n"
                         "cp.async.bulk.wait_group 1; @p red.relaxed.gpu.global.add.u32 [%0+128],1; cp.async.bulk.wait_group 0; @p red.relaxed.gpu.global.add.u32 [%0+192],1;}"
                         ::"l"(cnt_ptr(C_OP0 + rank * 2 + wg, ch)) : "memory");
#pragma unroll 1
            for (int i = 0; i < 8; i++) mbar_arrive1_cluster(mapa(sb + B_BAR + (BB_EMPTY + ((s0 + (i >> 2)) & (NSTG - 1))) * 8, i & 1));
            continue;
        }
#pragma unroll 1
        for (int u = 0; u < (type == T_QKV ? t.b : 1); u++) {
            const int blk = qkv_blk(t, u);
            unsigned* cnt = cnt_ptr(type == T_QKV ? C_QKV0 + layer : type == T_OP ? C_OP1 : layer ? C_H : C_CV, ch + (type == T_QKV && blk < 64 ? 16 : 0));
            const uint4* dst = type == T_QKV ? qkv_dst(layer, ch, wg * 4, blk) : op_dst(1, ch, t.c & 15, wg * 4, (t.blk >> 2) & 1) + 256;
            mbar_wait(sb + B_BAR + (BB_DONE + wg) * 8, nd & 1);
            nd++;
            if (type != T_CV) {
                fence_async_smem();
#pragma unroll
                for (int w = 0; w < 4; w++)
                    asm volatile("{.reg .pred p; elect.sync _|p,0xffffffff; @p cp.async.bulk.global.shared::cta.bulk_group.L2::cache_hint [%0],[%1],4096,%2;}"
                                 ::"l"(dst + (type == T_QKV ? (w >> 1) * 49152 + (w & 1) * 256 : w * 1024)), "r"(sb + B_OUT + (wg * 4 + w) * 4096), "l"(out_pol(type, layer, ch)) : "memory");
                asm volatile("cp.async.bulk.commit_group; cp.async.bulk.wait_group 0;" ::: "memory");
            }
            if (type != T_QKV) fence_async();
            if (!t.dry) asm volatile("{.reg .pred p; elect.sync _|p,0xffffffff; @p red.relaxed.gpu.global.add.u32 [%0],%1;}" ::"l"(cnt), "r"(type == T_QKV ? 2 : type == T_OP ? t.b : 1) : "memory");
            PROF(wg && (threadIdx.x & 31) == 0 && (type == T_CV || u + 2 == t.b), 3900 + ti);
            if (type == T_CV && !layer && !t.dry) {
                asm volatile("{.reg .pred p; elect.sync _|p,0xffffffff; @p cp.async.bulk.global.shared::cta.bulk_group [%0],[%1],4096;\n"
                             "cp.async.bulk.commit_group; cp.async.bulk.wait_group 0; @p red.relaxed.gpu.global.add.u32 [%2],1;}"
                             ::"l"(g_u + ((t.a + rank) * 16 + ch) * 512 + wg * 256), "r"(sb + B_UT + (ch & 1) * 8192 + wg * 4096), "l"(cnt_ptr(C_U, ch)) : "memory");
            }
            mbar_arrive1(sb + B_BAR + (BB_SF + wg) * 8);
        }
        PROF(wg && (threadIdx.x & 31) == 0, 3600 + ti * 4 + 3);
    }
}

__device__ __forceinline__ void stage_release(uint32_t sb, int w, int st) {
    if (!(w & 2)) mbar_arrive1_cluster(mapa(sb + B_BAR + (BB_EMPTY + st) * 8, w & 1));
}
template <bool ACC>
__device__ __forceinline__ void gemm_run(float* acc, uint32_t sb, int w, int h0, int h1, uint32_t& r0, uint32_t& r1, int& st, uint32_t& ph) {
    const uint64_t da0 = mkdesc(sb + (w >> 2) * 4096, 16, 512, 2), db0 = mkdesc(sb + 8192, 4096, 1024, 1);
    const uint32_t rel0 = mapa(sb + B_BAR + BB_EMPTY * 8, w & 1);
#pragma unroll 1
    for (int h = h0; h < h1; h++) {
        const uint64_t da = da0 + st * (STG_B >> 4), db = db0 + st * (STG_B >> 4);
        mbar_wait(sb + B_BAR + (BB_FULL + st) * 8, ph);
        if (ACC) wg_wait<1>();
        wg_fence();
        wgmma256<ACC>(acc, da, db);
        wgmma256<true>(acc, da + 2, db + 128);
        wg_commit();
        if (ACC) mbar_arrive1_cluster((w == 2 && h == LAGH - 1) ? sb + B_BAR + BB_GO * 8 : r0);
        r0 = r1;
        if (!(w & 2)) r1 = rel0 + st * 8;
        if (++st == NSTG) { st = 0; ph ^= 1; }
    }
}

__device__ __forceinline__ uint4* qkv_dst(int layer, int ch, int w, int blk) {
    return g_qkv[layer] + (size_t)((ch * 4 + (w >> 1)) * 32 + ((blk & 63) >> 1)) * 1536 + (blk >> 6) * 512 + (w & 1) * 256;
}
__device__ __forceinline__ uint4* op_dst(int layer, int ch, int slot, int w, uint32_t rank) {
    return g_pp[layer] + (size_t)(ch * MAXSPLIT + slot) * 8192 + (w * 32 + rank * 16) * 32;
}
__device__ __forceinline__ uint32_t ln2(uint32_t x, uint32_t m, uint32_t rh, uint32_t rl) {
    uint32_t d; asm volatile("{.reg .b32 t,u; sub.rn.bf16x2 t,%1,%2; mul.rn.bf16x2 u,t,%4; fma.rn.bf16x2 %0,t,%3,u;}" : "=r"(d) : "r"(x), "r"(m), "r"(rh), "r"(rl)); return d;
}
__device__ __forceinline__ void qkv_task(uint32_t sb, int w, int layer, int ch, int nu, int& ng, int& nd, uint32_t& ph, int ti, uint32_t zero) {
    constexpr int type = T_QKV;
    static_assert(NSTG == 8, "ring");
    const int lane = threadIdx.x & 31;
    const uint64_t db0 = mkdesc(sb, 4096, 1024, 1);
    const uint32_t rel = (w & 2) ? sb + B_BAR + BB_IDLE * 8 : mapa(sb + B_BAR + BB_EMPTY * 8, w & 1), full = sb + B_BAR + BB_FULL * 8;
    const uint32_t lo = sb + B_OUT + w * 4096 + (lane ^ (lane >> 3)) * 16;
    const uint4* xa = g_xA[layer] + (ch * 8 + w) * 1024 + lane;
    uint32_t m0, m1, h0, h1, l0, l1;
    uint4 A[32];
    {
        mbar_wait(full, ph);
        mbar_wait(full + 8, ph);
        CPROF(1);
        const uint32_t sa = sb + (lane >> 4) * STG_B + 16384 + (w * 16 + (lane & 15)) * 8;
        uint2 v[8];
#pragma unroll
        for (int i = 0; i < 8; i++) v[i] = lds64(sa + i * 1024 * layer);
#pragma unroll
        for (int i = 0; i < 4 * QB1; i++) A[i] = ldcg128(xa + i * 32);
        bar_sync(NB_WG + (w >> 2), 128);
        float sm = 0, M2 = 0, D = 0;
#pragma unroll
        for (int i = 0; i < 8; i++) { sm += __uint_as_float(v[i].x); M2 += __uint_as_float(v[i].y); }
        if (!layer) { sm = __uint_as_float(v[0].x); M2 = __uint_as_float(v[0].y); }
        sm += __shfl_xor_sync(0xffffffffu, sm, 16);
#pragma unroll
        for (int i = 0; i < 8; i++) { const float d = __uint_as_float(v[i].x) * (1.f / 32.f) - sm * (1.f / 512.f); D += 32.f * d * d; }
        M2 += layer ? D : sm * sm * (-1.f / 1024.f);
        M2 = fmaxf(M2 + __shfl_xor_sync(0xffffffffu, M2, 16), 0.f);
        const float2 o = ln_finish(sm * (1.f / 512.f), M2 * (1.f / 512.f));
        const float r = rcp(o.y), rh = rbf(r);
        const uint32_t mm = pack2(o.x, o.x), hl = pack2(r - rh, rh);
        m0 = __shfl_sync(0xffffffffu, mm, lane >> 2); m1 = __shfl_sync(0xffffffffu, mm, (lane >> 2) + 8);
        l0 = __shfl_sync(0xffffffffu, hl, lane >> 2); l1 = __shfl_sync(0xffffffffu, hl, (lane >> 2) + 8);
        h0 = __byte_perm(l0, 0, 0x3232); h1 = __byte_perm(l1, 0, 0x3232); l0 = __byte_perm(l0, 0, 0x1010); l1 = __byte_perm(l1, 0, 0x1010);
    }
    float acc[64];
#define QNRM(i) A[i] = make_uint4(ln2(A[i].x, m0, h0, l0), ln2(A[i].y, m1, h1, l1), ln2(A[i].z, m0, h0, l0), ln2(A[i].w, m1, h1, l1))
#pragma unroll
    for (int h = 0; h < 8; h++) {
        const uint64_t db = db0 + h * (STG_B >> 4);
        const int b0 = h == 0 ? QB1 : h == QB1 ? QB2 : h == QB2 ? QB3 : 8, b1 = h == 0 ? QB2 : h == QB1 ? QB3 : 8;
        if (b0 < b1) {
            const uint4* xb = xa + (A[4 * b0 - 1].x & zero);
#pragma unroll
            for (int i = 4 * b0; i < 4 * b1; i++) A[i] = ldcg128(xb + i * 32);
            bar_sync(NB_WG + (w >> 2), 128);
        }
        QNRM(4 * h); QNRM(4 * h + 1); QNRM(4 * h + 2); QNRM(4 * h + 3);
        if (h == 2 || h == 5) bar_sync(NB_REL + (h == 5) * 2 + (w >> 2), 160);
        if (h) wg_wait<1>();
        wg_fence();
        if (h) wgmma128r<true>(acc, A[4 * h], db); else wgmma128r<false>(acc, A[0], db);
        wgmma128r<true>(acc, A[4 * h + 1], db + 128);
        wgmma128r<true>(acc, A[4 * h + 2], db + 512);
        wgmma128r<true>(acc, A[4 * h + 3], db + 640);
        wg_commit();
        if (h >= 2) mbar_arrive1_cluster(rel + (h - 2) * 8);
    }
    ph ^= 1;
#pragma unroll 1
    for (int u = 1;; u++) {
        mbar_wait(sb + B_BAR + (BB_SF + (w >> 2)) * 8, (nd & 1) ^ 1);
        if (u < nu) mbar_wait(full, ph);
        wg_wait<1>();
        mbar_arrive1_cluster(rel + 48);
        wg_wait<0>();
        mbar_arrive1_cluster(rel + 56);
        uint4 o[8];
#pragma unroll
        for (int n = 0; n < 8; n++) {
            const float* a = acc + (n >> 1) * 16 + (n & 1) * 2;
            o[n] = make_uint4(pack2(a[0], a[1]), pack2(a[4], a[5]), pack2(a[8], a[9]), pack2(a[12], a[13]));
            sts128(lo + n * 512, o[n].x, o[n].y, o[n].z, o[n].w);
        }
        __syncwarp();
        mbar_arrive1(sb + B_BAR + (BB_DONE + (w >> 2)) * 8);
        nd++;
        CPROF(min(2 + u, 7));
        if (u == nu) break;
        if (LAGQ) { if (w >> 2) mbar_wait(sb + B_BAR + BB_GO * 8, ng & 1); ng++; }
        const uint64_t db1 = mkdesc(sb + (u >> 10), 4096, 1024, 1);
#pragma unroll
        for (int h = 0; h < 8; h++) {
            const uint64_t db = db1 + h * (STG_B >> 4);
            if (h) { mbar_wait(full + h * 8, ph); wg_wait<1>(); }
            wg_fence();
            if (h) wgmma128r<true>(acc, A[4 * h], db); else wgmma128r<false>(acc, A[0], db);
            wgmma128r<true>(acc, A[4 * h + 1], db + 128);
            wgmma128r<true>(acc, A[4 * h + 2], db + 512);
            wgmma128r<true>(acc, A[4 * h + 3], db + 640);
            wg_commit();
            if (h >= 2) mbar_arrive1_cluster(rel + (h - 2) * 8);
            if (h == LAGQ - 1 && w == 2) mbar_arrive1(sb + B_BAR + BB_GO * 8);
        }
        ph ^= 1;
    }
}

template <int NB>
__device__ __forceinline__ void load_resid(uint32_t* r, int layer, int ch, int w, int cb) {
#pragma unroll
    for (int i = 0; i < NB; i++) {
        const uint4 v = ldcg128(g_xA[layer] + ((ch * 8 + w) * 32 + cb + i) * 32 + (threadIdx.x & 31));
        r[4 * i] = v.x; r[4 * i + 1] = v.y; r[4 * i + 2] = v.z; r[4 * i + 3] = v.w;
    }
}
template <int NS>
__device__ __forceinline__ void part_load(uint4* v, int layer, int ch, int w, int cb, int ns) {
    const uint4* src = g_pp[layer] + (size_t)ch * MAXSPLIT * 8192 + (w * 32 + cb) * 32 + (threadIdx.x & 31);
#pragma unroll
    for (int i = 0; i < 2 * NS; i++) {
        asm volatile("{.reg .pred p; .reg .b128 t; setp.gt.s32 p,%6,0; mov.b128 t,{0,0,0,0}; @p ld.relaxed.gpu.global.L2::cache_hint.b128 t,[%4],%5; mov.b128 {%0,%1,%2,%3},t;}"
                     : "=r"(v[i].x), "=r"(v[i].y), "=r"(v[i].z), "=r"(v[i].w) : "l"(src + (i / NS) * 32 + (i % NS) * 8192), "l"(POL_LAST), "r"(ns - i % NS) : "memory");
    }
}
template <int NS>
__device__ __forceinline__ void part_sum(float* x, const uint4* v, const uint32_t* r) {
    const int dg = ((threadIdx.x & 31) >> 2) - 2 * (threadIdx.x & 3);
    const uint32_t idm = dg == 0 ? 0x00003f80u : dg == 1 ? 0x3f800000u : 0u;
#pragma unroll
    for (int b = 0; b < 2; b++) {
        float* y = x + b * 8;
#pragma unroll
        for (int i = 0; i < 8; i++) y[i] = 0;
#pragma unroll
        for (int s = 0; s < NS; s++) { mma8(y, v[b * NS + s].x, v[b * NS + s].y, idm); mma8(y + 4, v[b * NS + s].z, v[b * NS + s].w, idm); }
#pragma unroll
        for (int i = 0; i < 4; i++) { y[2 * i] = rbf(rbf(y[2 * i]) + blo(r[b * 4 + i])); y[2 * i + 1] = rbf(rbf(y[2 * i + 1]) + bhi(r[b * 4 + i])); }
    }
}

__device__ __forceinline__ float4 row_stats32(const float* x) {
    float a = (x[0] + x[1]) + (x[4] + x[5]) + (x[8] + x[9]) + (x[12] + x[13]);
    float b = (x[2] + x[3]) + (x[6] + x[7]) + (x[10] + x[11]) + (x[14] + x[15]);
    a += __shfl_xor_sync(0xffffffffu, a, 1); b += __shfl_xor_sync(0xffffffffu, b, 1);
    a += __shfl_xor_sync(0xffffffffu, a, 2); b += __shfl_xor_sync(0xffffffffu, b, 2);
    const float ma = a * (1.f / 32.f), mb = b * (1.f / 32.f);
    float qa = 0, qb = 0;
#pragma unroll
    for (int i = 0; i < 4; i++) {
        float d0 = x[4 * i] - ma, d1 = x[4 * i + 1] - ma, d2 = x[4 * i + 2] - mb, d3 = x[4 * i + 3] - mb;
        qa += d0 * d0 + d1 * d1; qb += d2 * d2 + d3 * d3;
    }
    qa += __shfl_xor_sync(0xffffffffu, qa, 1); qb += __shfl_xor_sync(0xffffffffu, qb, 1);
    qa += __shfl_xor_sync(0xffffffffu, qa, 2); qb += __shfl_xor_sync(0xffffffffu, qb, 2);
    return make_float4(a, qa, b, qb);
}

__device__ __forceinline__ void conv_stage(float* Y, uint32_t pbase, uint32_t ubase) {
    const int lane = threadIdx.x & 31, w = threadIdx.x >> 5, g = lane >> 2, c = lane & 3;
#pragma unroll
    for (int cp = 0; cp < 2; cp++) {
        const int chl = w * 4 + cp * 2 + (lane >> 4);
        const uint4 b = ldsm4(ubase + chl * 256 + ((lane >> 3) & 1) * 128 + (((lane & 7) ^ (chl & 7)) << 4));
#pragma unroll
        for (int h = 0; h < 2; h++) {
            const uint32_t pa = pbase + ((w * 4 + cp * 2 + h) * PW + 16 + g - 2 * c) * 4;
            uint32_t lo = lds32(pa - 32);
#pragma unroll
            for (int d = 0; d < 8; d++) {
                const uint32_t a0 = lds32(pa + d * 64), a1 = lds32(pa + d * 64 + 32);
                mma16(Y + ((cp * 2 + h) * 8 + d) * 4, a0, a1, lo, a0, h ? b.z : b.x, h ? b.w : b.y);
                lo = a1;
            }
        }
    }
}

__device__ __forceinline__ void conv_combine(const float* y8, float* cur, float* nxt) {
    const int lane = threadIdx.x & 31, c = lane & 3;
    cur[0] = y8[0]; cur[1] = y8[1] + y8[4]; cur[2] = y8[2]; cur[3] = y8[3] + y8[6];
    nxt[0] = y8[29]; nxt[1] = 0.f; nxt[2] = y8[31]; nxt[3] = 0.f;
#pragma unroll
    for (int e = 1; e < 4; e++) {
        const int src = (lane & ~3) | ((c - e) & 3);
        const float v0 = __shfl_sync(0xffffffffu, y8[8 * e] + y8[8 * e - 3], src), v1 = __shfl_sync(0xffffffffu, y8[8 * e + 1] + y8[8 * e + 4], src);
        const float v2 = __shfl_sync(0xffffffffu, y8[8 * e + 2] + y8[8 * e - 1], src), v3 = __shfl_sync(0xffffffffu, y8[8 * e + 3] + y8[8 * e + 6], src);
        if (c >= e) { cur[0] += v0; cur[1] += v1; cur[2] += v2; cur[3] += v3; }
        else { nxt[0] += v0; nxt[1] += v1; nxt[2] += v2; nxt[3] += v3; }
    }
}

__device__ __forceinline__ void hist_task(float* Y, uint32_t sb, int w, int ch, int q, int& st, uint32_t& ph, int nd) {
    const int lane = threadIdx.x & 31, chl = w * 2 + (lane >> 4);
    const uint32_t ua = sb + 12288 + chl * 256 + ((lane >> 3) & 1) * 128 + (((lane & 7) ^ (chl & 7)) << 4);
    const uint32_t pa = sb + (w * 2 * PW + 16 + (lane >> 2) - 2 * (lane & 3)) * 4;
#pragma unroll
    for (int i = 0; i < 128; i++) Y[i] = 0;
    uint4 b1 = make_uint4(0, 0, 0, 0);
#pragma unroll 1
    for (int j = ch + 1; j >= 2; j--) {
        const uint4 b0 = b1;
        mbar_wait(sb + B_BAR + (BB_FULL + st) * 8, ph);
        b1 = ldsm4(ua + st * STG_B);
        if (j == 2) b1 = make_uint4(0, 0, 0, 0);
#pragma unroll
        for (int h = 0; h < 2; h++) {
            const uint32_t o = pa + st * STG_B + h * PW * 4;
            uint32_t lo = lds32(o - 32);
#pragma unroll
            for (int d = 0; d < 8; d++) {
                const uint32_t a0 = lds32(o + d * 64), a1 = lds32(o + d * 64 + 32);
                mma16(Y + (h * 16 + d) * 4, a0, a1, lo, a0, h ? b0.z : b0.x, h ? b0.w : b0.y);
                mma16(Y + (h * 16 + 8 + d) * 4, a0, a1, lo, a0, h ? b1.z : b1.x, h ? b1.w : b1.y);
                lo = a1;
            }
        }
        bar_sync(NB_WG + (w >> 2), 128);
        stage_release(sb, w, st);
        if (++st == NSTG) { st = 0; ph ^= 1; }
    }
    mbar_wait(sb + B_BAR + (BB_SF + (w >> 2)) * 8, (nd & 1) ^ 1);
#pragma unroll
    for (int h = 0; h < 2; h++) {
        const int o = ((ch * 16 + (q >> 1)) * 4 + (w & 1) * 2 + h) * 256 + ((q & 1) * 4 + (w >> 1)) * 32 + lane;
        float c0[4], n0[4], c1[4], n1[4];
        conv_combine(Y + h * 64, c0, n0); conv_combine(Y + h * 64 + 32, c1, n1);
        g_carry[0][o] = make_float4(c0[0], c0[1], c0[2], c0[3]);
        g_carry[0][o + 16384] = make_float4(c1[0] + n0[0], c1[1] + n0[1], c1[2] + n0[2], c1[3] + n0[3]);
        g_carry[1][o + 32768] = make_float4(n1[0], n1[1], n1[2], n1[3]);
    }
}

__device__ __forceinline__ void conv_task(const Params& p, float* Y, uint32_t sb, int w, int ch, int q, int ns, bool dry, int& st, uint32_t& ph, int nd) {
    const int tid = threadIdx.x, lane = tid & 31, g = lane >> 2, c = lane & 3;
    uint32_t dk[4];
    const uint32_t sg = (~ch & 2) << 30;
    int sr = st;
    float x[16];
    PROF(tid == 128, 2048 + ch * 8);
#pragma unroll
    for (int i = 0; i < 128; i++) Y[i] = 0;
#pragma unroll 1
    for (int j = min(ch, 1 + (ch & 1)); j >= 1; j--) {
        mbar_wait(sb + B_BAR + (BB_FULL + st) * 8, ph);
        conv_stage(Y, sb + st * STG_B, sb + B_UT + ((ch - j) & 1) * 8192);
        if (++st == NSTG) { st = 0; ph ^= 1; }
    }
#define CONV_CARRY _Pragma("unroll 1") \
    for (int i = 0; i < min(ch, (ch & 1) ? 2 : 3); i++) { \
        if (i) mbar_wait(sb + B_BAR + (BB_FULL + st) * 8, ph); \
        const uint32_t ca = sb + (i ? st * STG_B : B_SP) + tid * 16; \
_Pragma("unroll") \
        for (int k = 0; k < 4; k++) { \
            const uint4 cr = lds128(ca + k * 4096); \
            Y[k * 32] += __uint_as_float(cr.x); Y[k * 32 + 1] += __uint_as_float(cr.y); Y[k * 32 + 2] += __uint_as_float(cr.z); Y[k * 32 + 3] += __uint_as_float(cr.w); \
        } \
        if (i && ++st == NSTG) { st = 0; ph ^= 1; } \
    } \
    bar_sync(NB_C, 256); \
_Pragma("unroll 1") \
    for (; sr != st; sr = (sr + 1) & (NSTG - 1)) stage_release(sb, w, sr); \
    mbar_wait(sb + B_BAR + (BB_SF + (w >> 2)) * 8, (nd & 1) ^ 1); \
    mbar_wait(sb + B_BAR + (BB_SF + 1 - (w >> 2)) * 8, (nd & 1) ^ 1);
    const uint32_t ut = sb + B_UT + (ch & 1) * 8192;
    if (CPOS == 0) { CONV_CARRY }
    PROF(tid == 128, 2048 + ch * 8 + 7);
    {
        uint4 v[2 * OPS1];
        wait_cnt_warp(cnt_ptr(C_OP0 + (q >> 3) * 2 + (w >> 2), ch + (w & 3) * 16), ns);
        part_load<OPS1>(v, 0, ch, w, 2 * q, ns);
        uint32_t rs[8];
        load_resid<2>(rs, 0, ch, w, 2 * q);
        if (CPOS == 1) { CONV_CARRY }
        part_sum<OPS1>(x, v, rs);
        const float4 s = row_stats32(x);
        float2* dst = g_st2 + ((ch & 1) * 16 + q) * 128 + w * 16 + g + c * 8;
        asm volatile("{.reg .pred p; setp.ne.u32 p,%2,0; @p st.relaxed.gpu.global.b64 [%0],%1;}" ::"l"(dst),
                     "l"(((uint64_t)((__float_as_uint(c ? s.w : s.y) & 0x7fffffffu) | sg) << 32) | __float_as_uint(c ? s.z : s.x)), "r"((uint32_t)(c < 2 && !dry)) : "memory");
        PROF(tid == 128, 2048 + ch * 8 + 1);
    }
#pragma unroll
    for (int i = 0; i < 4; i++) asm volatile("ld.global.nc.u32 %0,[%1];" : "=r"(dk[i]) : "l"(p.Dskip + q * 32 + i * 8 + 2 * c));
    if (CPOS == 2) { CONV_CARRY }
    float2 ln0, ln1;
    {
        const float2* src = g_st2 + ((ch & 1) * 16 + (lane >> 4) * 8) * 128 + w * 16 + (lane & 15);
        uint64_t v[8];
        int n = 0;
#pragma unroll
        for (int i = 0; i < 8; i++) v[i] = (uint64_t)~sg << 32;
        while (true) {
            bool bad = false;
#pragma unroll
            for (int i = 0; i < 8; i++) asm volatile("{.reg .pred p; setp.lt.s32 p,%2,0; @p ld.relaxed.gpu.global.b64 %0,[%1];}" : "+l"(v[i]) : "l"(src + i * 128), "r"((uint32_t)(v[i] >> 32) ^ sg) : "memory");
#pragma unroll
            for (int i = 0; i < 8; i++) bad = bad || (int)((uint32_t)(v[i] >> 32) ^ sg) < 0;
            if (!__any_sync(0xffffffffu, bad && !dry)) break;
            if (++n > 2000000) __trap();
        }
        float sm = 0;
#pragma unroll
        for (int i = 0; i < 8; i++) sm += __uint_as_float((uint32_t)v[i]);
        sm += __shfl_xor_sync(0xffffffffu, sm, 16);
        const float mean = sm * (1.f / 512.f);
        float M2 = 0;
#pragma unroll
        for (int i = 0; i < 8; i++) { const float d = __uint_as_float((uint32_t)v[i]) * (1.f / 32.f) - mean; M2 += fabsf(__uint_as_float((uint32_t)(v[i] >> 32))) + 32.f * d * d; }
        M2 += __shfl_xor_sync(0xffffffffu, M2, 16);
        const float2 o = ln_finish(mean, M2 * (1.f / 512.f));
        ln0.x = __shfl_sync(0xffffffffu, o.x, g); ln0.y = __shfl_sync(0xffffffffu, o.y, g);
        ln1.x = __shfl_sync(0xffffffffu, o.x, g + 8); ln1.y = __shfl_sync(0xffffffffu, o.y, g + 8);
    }
    PROF(tid == 128, 2048 + ch * 8 + 2);
    uint32_t u[8];
#pragma unroll
    for (int i = 0; i < 8; i++) {
        const float2 l = (i & 1) ? ln1 : ln0;
        u[i] = pack2(__fdividef(rbf(x[2 * i] - l.x), l.y), __fdividef(rbf(x[2 * i + 1] - l.x), l.y));
        const int chl = (i >> 1) * 8 + g;
        sts32(ut + chl * 256 + (i & 1) * 128 + ((w ^ g) << 4) + c * 4, movm(u[i]));
    }
    bar_sync(NB_C, 256);
    mbar_wait(sb + B_BAR + (BB_FULL + st) * 8, ph);
    PROF(tid == 128, 2048 + ch * 8 + 3);
    conv_stage(Y, sb + st * STG_B, ut);
    uint32_t yp[4][2];
    float nxt[4][4];
    {
        float y[4][4];
#pragma unroll
        for (int k = 0; k < 4; k++) conv_combine(Y + k * 32, y[k], nxt[k]);
#pragma unroll
        for (int i = 0; i < 4; i++) { yp[i][0] = pack2(y[0][i], y[1][i]); yp[i][1] = pack2(y[2][i], y[3][i]); }
    }
#pragma unroll
    for (int i = 0; i < 4; i++) sts64(sb + B_YT + (16 * (2 * c + (i & 1)) + g + (i >> 1) * 8) * 80 + w * 8, yp[i][0], yp[i][1]);
    bar_sync(NB_C, 256);
    stage_release(sb, w, st);
    if (++st == NSTG) { st = 0; ph ^= 1; }
    PROF(tid == 128, 2048 + ch * 8 + 4);
    uint32_t xo[8];
    uint4* dA = g_xA[1] + ((ch * 8 + w) * 32 + 2 * q) * 32 + lane;
#pragma unroll
    for (int i = 0; i < 8; i++) {
        const int col = (i >> 1) * 8 + 2 * c;
        const uint32_t yv = lds32(sb + B_YT + (w * 16 + g + (i & 1) * 8) * 80 + col * 2);
        const uint32_t dv = dk[i >> 1];
        x[2 * i] = rbf(x[2 * i] + rbf(blo(yv) + rbf(blo(u[i]) * blo(dv))));
        x[2 * i + 1] = rbf(x[2 * i + 1] + rbf(bhi(yv) + rbf(bhi(u[i]) * bhi(dv))));
        xo[i] = pack2(x[2 * i], x[2 * i + 1]);
        if ((i & 3) == 3) dA[(i >> 2) * 32] = make_uint4(xo[i - 3], xo[i - 2], xo[i - 1], xo[i]);
    }
    {
        const float4 s = row_stats32(x);
        float2* dst = g_st[1] + (ch * 16 + q) * 128 + w * 16 + g;
        if (c == 0) dst[0] = make_float2(s.x, s.y);
        if (c == 1) dst[8] = make_float2(s.z, s.w);
        __syncwarp();
    }
    PROF(tid == 128, 2048 + ch * 8 + 5);
    mbar_arrive1(sb + B_BAR + (BB_DONE + (w >> 2)) * 8);
    bar_sync(NB_C, 256);
#pragma unroll
    for (int k = 0; k < 4; k++) sts128(sb + B_SP + k * 4096 + tid * 16, __float_as_uint(nxt[k][0]), __float_as_uint(nxt[k][1]), __float_as_uint(nxt[k][2]), __float_as_uint(nxt[k][3]));
    PROF(tid == 128, 2048 + ch * 8 + 6);
}

__device__ __forceinline__ void out_store(const Params& p, const float* x, int ch, int cb, bool on) {
    const int lane = threadIdx.x & 31, w = threadIdx.x >> 5, g = lane >> 2, c = lane & 3;
#pragma unroll
    for (int h = 0; h < 2; h++) {
        const float* y = x + h * 2;
        uint32_t v0 = pack2(y[0], y[1]), v1 = pack2(y[4], y[5]), v2 = pack2(y[8], y[9]), v3 = pack2(y[12], y[13]);
        uint32_t t0 = (c & 1) ? v0 : v1, t1 = (c & 1) ? v2 : v3;
        t0 = __shfl_xor_sync(0xffffffffu, t0, 1); t1 = __shfl_xor_sync(0xffffffffu, t1, 1);
        if (c & 1) { v0 = t0; v2 = t1; } else { v1 = t0; v3 = t1; }
        t0 = (c & 2) ? v0 : v2; t1 = (c & 2) ? v1 : v3;
        t0 = __shfl_xor_sync(0xffffffffu, t0, 2); t1 = __shfl_xor_sync(0xffffffffu, t1, 2);
        if (c & 2) { v0 = t0; v1 = t1; } else { v2 = t0; v3 = t1; }
        asm volatile("{.reg .pred p; setp.ne.u32 p,%6,0; @p st.global.L2::cache_hint.v4.u32 [%0],{%1,%2,%3,%4},%5;}"
                     ::"l"(p.out + (size_t)(ch * 128 + w * 16 + g + h * 8) * 512 + cb * 16 + c * 8), "r"(v0), "r"(v1), "r"(v2), "r"(v3), "l"(POL_LATE), "r"((uint32_t)on));
    }
}
__device__ __forceinline__ void fin_task(const Params& p, int ch, int cb0, int ncb, int ns, bool dry) {
    const int w = threadIdx.x >> 5;
    uint32_t rs[8];
    wait_cnt_warp(cnt_ptr(C_CV, ch), 32);
    load_resid<2>(rs, 1, ch, w, cb0);
    wait_cnt_warp(cnt_ptr(C_OP1, ch), dry ? 0 : 256);
    for (int cb = cb0; cb < cb0 + ncb; cb += 2) {
        float x[16];
        if (cb != cb0) load_resid<2>(rs, 1, ch, w, cb);
        uint4 v[32];
        part_load<16>(v, 1, ch, w, cb, ns);
        part_sum<16>(x, v, rs);
        out_store(p, x, ch, cb, !dry);
    }
}

__device__ __forceinline__ void bulk_consumer(const Params& p, uint32_t sb, int cl, uint32_t rank, int w) {
    int st = 0; uint32_t ph = 0; int nd = 0, ng = 0;
    for (int ti = 0; ti < MAXT; ti++) {
        const Task t = task_of(p.task[cl][ti], rank);
        const int type = t.type, layer = t.layer, ch = t.ch;
        if (type == T_END) break;
        bool staged = type != T_FIN;
        PROF(threadIdx.x == 0, 3600 + ti * 4);
        CPROF(0);
        if (type == T_QKV) {
            staged = false;
            #pragma unroll 1
            while (st) {
                if (!(w & 3)) { mbar_wait(sb + B_BAR + (BB_FULL + st) * 8, ph); stage_release(sb, 0, st); stage_release(sb, 1, st); }
                if (++st == NSTG) { st = 0; ph ^= 1; }
            }
            if (!(w & 3)) { sts32(sb + B_ST + 8, ph); bar_arrive(NB_PH, 96); }
            qkv_task(sb, w, layer, ch, t.b, ng, nd, ph, ti, p.zero);
            PROF(threadIdx.x == 128, 3600 + ti * 4 + 1);
        } else if (type == T_OP) {
            const int lane = threadIdx.x & 31;
            float acc[128];
            uint32_t r0 = sb + B_BAR + BB_IDLE * 8, r1 = r0;
            if (w >> 2) mbar_wait(sb + B_BAR + BB_GO * 8, ng & 1);
            ng++;
            gemm_run<false>(acc, sb, w, 0, 1, r0, r1, st, ph);
            gemm_run<true>(acc, sb, w, 1, 2 * t.b, r0, r1, st, ph);
            mbar_wait(sb + B_BAR + (BB_SF + (w >> 2)) * 8, (nd & 1) ^ 1);
            wg_wait<1>();
            mbar_arrive1_cluster(r0);
            wg_wait<0>();
            mbar_arrive1_cluster(r1);
            PROF(threadIdx.x == 128, 3600 + ti * 4 + 1);
            if (t.c & 32) {
                staged = false;
                const int dg = (lane >> 2) - 2 * (lane & 3);
                const uint32_t idm = dg == 0 ? 0x00003f80u : dg == 1 ? 0x3f800000u : 0u;
                wait_cnt_warp(cnt_ptr(C_OP1, ch), 256 - 4 * t.b);
#pragma unroll 1
                for (int i = 0; i < (t.c & 15); i++) {
                    const uint4* src = op_dst(1, ch, i, w, (t.blk >> 2) & 1) + lane;
                    uint4 v[16];
#pragma unroll
                    for (int j = 0; j < 16; j++) v[j] = ldcg128_last(src + j * 32);
#pragma unroll
                    for (int j = 0; j < 16; j++) { mma8(acc + j * 8, v[j].x, v[j].y, idm); mma8(acc + j * 8 + 4, v[j].z, v[j].w, idm); }
                }
#pragma unroll
                for (int j = 0; j < 16; j += 4) {
                    uint32_t rs[16];
                    load_resid<4>(rs, 1, ch, w, (t.blk & 4) * 4 + j);
#pragma unroll
                    for (int i = 0; i < 16; i++) { float* y = acc + j * 8 + 2 * i; y[0] = rbf(y[0]) + blo(rs[i]); y[1] = rbf(y[1]) + bhi(rs[i]); }
                    out_store(p, acc + j * 8, ch, (t.blk & 4) * 4 + j, true); out_store(p, acc + j * 8 + 16, ch, (t.blk & 4) * 4 + j + 2, true);
                }
            } else if (!layer) {
                const int s2 = st + (w >> 1);
                const uint32_t o = sb + (s2 & (NSTG - 1)) * STG_B + (w & 1) * 8192 + lane * 16;
                mbar_wait(sb + B_BAR + (BB_FULL + (s2 & (NSTG - 1))) * 8, ph ^ (s2 >= NSTG));
#pragma unroll
                for (int j = 0; j < 16; j++)
                    sts128(o + j * 512, pack2(acc[j * 8], acc[j * 8 + 1]), pack2(acc[j * 8 + 2], acc[j * 8 + 3]), pack2(acc[j * 8 + 4], acc[j * 8 + 5]), pack2(acc[j * 8 + 6], acc[j * 8 + 7]));
                sts32(sb + B_ST + (w >> 2) * 4, st);
                st += 4;
                if (st >= NSTG) { st -= NSTG; ph ^= 1; }
            } else {
                uint4* dst = op_dst(layer, ch, t.c & 15, w, (t.blk >> 2) & 1) + lane;
#pragma unroll
                for (int n = 0; n < 16; n++) {
                    const int j = (n >> 1) + (n & 1) * 8;
                    const uint4 v = make_uint4(pack2(acc[j * 8], acc[j * 8 + 1]), pack2(acc[j * 8 + 2], acc[j * 8 + 3]), pack2(acc[j * 8 + 4], acc[j * 8 + 5]), pack2(acc[j * 8 + 6], acc[j * 8 + 7]));
                    if (j < 16 - NSB) stg128(dst + j * 32, v, out_pol(T_OP, layer, ch)); else sts128(sb + B_OUT + (w * NSB + j - (16 - NSB)) * 512 + lane * 16, v.x, v.y, v.z, v.w);
                }
            }
        } else if (type == T_CV) {
            float acc[128];
            if (layer) hist_task(acc, sb, w, ch, t.a + rank, st, ph, nd);
            else { conv_task(p, acc, sb, w, ch, t.a + rank, t.b, t.dry, st, ph, nd); staged = false; nd++; }
        } else {
            fin_task(p, ch, t.a + rank * t.c, t.c, t.b, t.dry);
        }
        if (staged) {
            __syncwarp();
            mbar_arrive1(sb + B_BAR + (BB_DONE + (w >> 2)) * 8);
            nd++;
        }
        PROF(threadIdx.x == 128, 3600 + ti * 4 + 2);
        __syncwarp();
    }
}

constexpr int P_Y = 131072  , P_PRM = P_Y  , P_K6 = P_PRM + 8192  ,
              P_P = P_Y + 40960  , P_U = P_P + 33280  , P_END = P_U + 17408, P_X = 98304  ;
static_assert(P_END <= B_BAR && P_END <= R_BAR, "prologue scratch");
#define KGUN 2
constexpr int KGU = KGUN;
__device__ __forceinline__ void csq(float& r, float& i) { const float t = r * i; r = fmaf(r, r, -(i * i)); i = t + t; }
__device__ __forceinline__ void cpow(float ar, float ph, float p, float& r, float& i) {
    const float e = ex2(ar * p);
    const float u = ph * p, n = fabsf(u) < 4194304.f ? (u + 12582912.f) - 12582912.f : u;
    const float t = (u - n) * 6.283185307179586f;
    r = e * __cosf(t); i = e * __sinf(t);
}
__device__ __forceinline__ void mma_tf32(float* c, float a0, float a1, float a2, float a3, float b0, float b1) {
    asm volatile("mma.sync.aligned.m16n8k8.row.col.f32.tf32.tf32.f32 {%0,%1,%2,%3},{%4,%5,%6,%7},{%8,%9},{%0,%1,%2,%3};"
                 : "+f"(c[0]), "+f"(c[1]), "+f"(c[2]), "+f"(c[3])
                 : "r"(__float_as_uint(a0)), "r"(__float_as_uint(a1)), "r"(__float_as_uint(a2)), "r"(__float_as_uint(a3)), "r"(__float_as_uint(b0)), "r"(__float_as_uint(b1)));
}

struct ProRegs { uint32_t v[2][4], ldt[2]; };
__device__ __forceinline__ void prologue_load(const ProArgs& a, int b, ProRegs& pr) {
    const int w = threadIdx.x >> 5;
#pragma unroll
    for (int i = 0; i < 2; i++) {
        const int gi = b * 512 + (w & 3) * 128 + ((w >> 2) & 1) * 64 + i * 32 + (threadIdx.x & 31);
        pr.ldt[i] = __ldg((const uint16_t*)a.ldt + b * 4 + (w & 3));
        pr.v[i][0] = __ldg((const uint16_t*)a.lAr + gi); pr.v[i][1] = __ldg((const uint16_t*)a.Ai + gi);
        pr.v[i][2] = __ldg((const uint16_t*)a.Cr + gi); pr.v[i][3] = __ldg((const uint16_t*)a.Ci + gi);
    }
}
__device__ __forceinline__ void prologue(const ProArgs& a, uint32_t sb, int b, int w, const ProRegs& pr) {
    const int tid = threadIdx.x, lane = tid & 31, g = lane >> 2, c = lane & 3;
    const int d0 = b * 4;
    if (w >= 8) {
        const int t2 = tid - 256;
        if (w < 10) {
            const int row = b * 16 + (w - 8) * 8 + g;
            const float4 r4 = row_stats((const uint4*)(a.x + (size_t)row * 512) + c, 4);
            const float2 r = make_float2(r4.x + r4.z, r4.y + r4.w);
            const float2 l = ln_finish(r.x * (1.f / 512.f), fmaxf(r.y - r.x * r.x * (1.f / 512.f), 0.f) * (1.f / 512.f));
            if (c == (g >> 1)) asm volatile("st.relaxed.gpu.global.u32 [%0],%1;" ::"l"(g_ln0 + row), "r"(pack2(l.x, l.y)) : "memory");
        }
        PROF(t2 == 0, 3516);
        const int gi = b * 128 + t2;
        if (t2 < 32) acc_init(a.mem0, b * 32 + t2);
        if (t2 >= 112) ((uint4*)g_st2)[b * 16 + t2 - 112] = make_uint4(0, 0, 0, 0);
        if (gi < 13 * 64) g_cnt[gi] = 0;
        bar_sync(6, 384);
        if (gi < 512) g_st[0][(gi >> 8) * 2048 + (lds32(sb + S_TAG) ^ 1) * 256 + (gi & 255)] = make_float2(0.f, 0.f);
        asm volatile("{.reg .pred p; elect.sync _|p,0xffffffff; @p cp.async.bulk.prefetch.L2.global [%0],32768;}"
                     ::"l"((w == 8 ? a.Wq : w == 9 ? a.Wk : w == 10 ? a.Wv : a.Wo) + (size_t)b * 16384) : "memory");
        mbar_wait(sb + S_XBAR, 0);
#pragma unroll 1
        for (int h = 0; h < 2; h++) {
            uint32_t l[8];
            int n = 0;
            while (true) {
                bool ok = true;
#pragma unroll
                for (int i = 0; i < 8; i++) asm volatile("ld.relaxed.gpu.global.u32 %0,[%1];" : "=r"(l[i]) : "l"(g_ln0 + h * 1024 + i * 128 + t2) : "memory");
#pragma unroll
                for (int i = 0; i < 8; i++) ok = ok && l[i];
                if (__all_sync(0xffffffffu, ok)) break;
                if (++n > 2000000) __trap();
            }
#pragma unroll
            for (int i = 0; i < 8; i++) {
                const int t = h * 1024 + i * 128 + t2;
                const uint2 x = lds64(sb + P_X + t * 16 + (b & 1) * 8);
                const float m = blo(l[i]), rs = rcp(bhi(l[i]));
                const uint32_t u0 = pack2(rbf(blo(x.x) - m) * rs, rbf(bhi(x.x) - m) * rs), u1 = pack2(rbf(blo(x.y) - m) * rs, rbf(bhi(x.y) - m) * rs);
                sts128(sb + P_X + t * 16, x.x, x.y, u0, u1);
                const uint32_t o = sb + P_U + ((t >> 3) & 1) * 2176 + ((t >> 4) + 8) * 16 + (t & 7) * 2;
                asm volatile("st.shared.u16 [%0],%1;" ::"r"(o), "h"((uint16_t)u0) : "memory");
                asm volatile("st.shared.u16 [%0],%1;" ::"r"(o + 4352), "h"((uint16_t)(u0 >> 16)) : "memory");
                asm volatile("st.shared.u16 [%0],%1;" ::"r"(o + 8704), "h"((uint16_t)u1) : "memory");
                asm volatile("st.shared.u16 [%0],%1;" ::"r"(o + 13056), "h"((uint16_t)(u1 >> 16)) : "memory");
            }
        }
        PROF(t2 == 0, 3517);
        bar_sync(9, 384);
        fence_async_smem();
#pragma unroll 1
        for (int j = 0; j < 16; j++) {
            const int d = d0 + w - 8;
            asm volatile("{.reg .pred p; elect.sync _|p,0xffffffff; @p cp.async.bulk.global.shared::cta.bulk_group [%0],[%1],%2;}" ::"l"(g_P + (((d >> 5) * 16 + j) * 32 + (d & 31)) * PW),
                         "r"(sb + P_P + ((w - 8) * 2080 + j * 128) * 4), "r"(PW * 4) : "memory");
        }
        asm volatile("cp.async.bulk.commit_group; cp.async.bulk.wait_group 0;" ::: "memory");
        bar_arrive(10, 384);
        return;
    }
#pragma unroll
    for (int i = 0; i < 2; i++) {
        const float dt = rbf(expf(blo(pr.ldt[i])));
        const float ar = -rbf(expf(blo(pr.v[i][0]))) * dt, ai = blo(pr.v[i][1]) * dt;
        sts128(sb + P_PRM + (w * 64 + i * 32 + lane) * 16, __float_as_uint(ar * 1.4426950408889634f), __float_as_uint(ai * 0.15915494309189535f),
               __float_as_uint(2.f * (blo(pr.v[i][2]) * dt)), __float_as_uint(2.f * (blo(pr.v[i][3]) * dt)));
    }
    if (tid < 64) sts128(sb + P_U + (tid >> 3) * 2176 + (tid & 7) * 16, 0, 0, 0, 0);
    bar_arrive(6, 384);
    __syncwarp();
    PROF(tid == 0, 3510);
    const int ch = w & 3, hf = w >> 2;
    {
        float k0[4] = {0, 0, 0, 0}, k1[4] = {0, 0, 0, 0}, k2[4] = {0, 0, 0, 0}, k3[4] = {0, 0, 0, 0}, k4[4] = {0, 0, 0, 0}, kl = 0;
#pragma unroll KGU
        for (int j = 0; j < 16; j++) {
            const uint4 q = lds128(sb + P_PRM + (w * 64 + j * 4 + c) * 16);
            const float cr = __uint_as_float(q.z), ci = __uint_as_float(q.w);
            float wr[4], wi[4], vr[4], vi[4];
            cpow(__uint_as_float(q.x), __uint_as_float(q.y), (float)g, wr[0], wi[0]);
            cpow(__uint_as_float(q.x), __uint_as_float(q.y), (float)(g + 8), vr[0], vi[0]);
#pragma unroll
            for (int i = 1; i < 4; i++) { wr[i] = wr[i - 1]; wi[i] = wi[i - 1]; csq(wr[i], wi[i]); vr[i] = vr[i - 1]; vi[i] = vi[i - 1]; csq(vr[i], vi[i]); }
            float hr = wr[3], hi = wi[3];
            csq(hr, hi);
            mma_tf32(k0, wr[0], vr[0], wi[0], vi[0], cr * hr - ci * hi, -(cr * hi + ci * hr));
            hr = vr[3]; hi = vi[3]; csq(hr, hi);
            mma_tf32(k1, wr[0], vr[0], wi[0], vi[0], cr * hr - ci * hi, -(cr * hi + ci * hr));
            csq(hr, hi);
            mma_tf32(k2, wr[1], vr[1], wi[1], vi[1], cr * hr - ci * hi, -(cr * hi + ci * hr));
            csq(hr, hi);
            mma_tf32(k3, wr[2], vr[2], wi[2], vi[2], cr * hr - ci * hi, -(cr * hi + ci * hr));
            csq(hr, hi);
            mma_tf32(k4, wr[3], vr[3], wi[3], vi[3], cr * hr - ci * hi, -(cr * hi + ci * hr));
            csq(hr, hi);
            kl += cr * hr - ci * hi;
        }
        kl += __shfl_xor_sync(0xffffffffu, kl, 1); kl += __shfl_xor_sync(0xffffffffu, kl, 2);
        const uint32_t o = sb + P_K6 + (ch * 656 + c * 32 + g) * 4, ol = sb + P_K6 + (ch * 656 + 640) * 4;
#define KST(k, base) sts32(o + (base) * 4, __float_as_uint(k[0])); sts32(o + (base) * 4 + 64, __float_as_uint(k[1])); \
                     sts32(o + (base) * 4 + 32, __float_as_uint(k[2])); sts32(o + (base) * 4 + 96, __float_as_uint(k[3]))
#define KAD(k, base) k[0] += __uint_as_float(lds32(o + (base) * 4)); k[1] += __uint_as_float(lds32(o + (base) * 4 + 64)); \
                     k[2] += __uint_as_float(lds32(o + (base) * 4 + 32)); k[3] += __uint_as_float(lds32(o + (base) * 4 + 96))
        if (hf == 0) {
            bar_sync(2 + ch, 64);
            KAD(k0, 0); KAD(k1, 128); KAD(k2, 256); KAD(k3, 384); KAD(k4, 512);
            kl += __uint_as_float(lds32(ol));
            __syncwarp();
        }
        KST(k0, 0); KST(k1, 128); KST(k2, 256); KST(k3, 384); KST(k4, 512);
        if (lane == 0) sts32(ol, __float_as_uint(kl));
        if (hf == 1) { __syncwarp(); bar_arrive(2 + ch, 64); }
    }
    PROF(tid == 0, 3511);
    bar_sync(8, 384);
    PROF(tid == 0, 3512);
    if (tid < 64) sts32(sb + P_P + ((tid >> 4) * 2080 + (tid & 15)) * 4, 0);
#pragma unroll 1
    for (int x = tid; x < 2048; x += 512) {
        uint32_t pw[2][4];
#pragma unroll
        for (int h = 0; h < 2; h++) {
            const int y = x + h * 256;
            const int i0 = y <= 256 ? y : 256 + (int)((pack2((float)y, 0.f) & 0xffff) - 0x4380);
            const int i1 = y <= 256 ? max(y - 1, 0) : 256 + (int)((pack2((float)(y - 1), 0.f) & 0xffff) - 0x4380);
#pragma unroll
            for (int k = 0; k < 4; k++) {
                const float lo = __uint_as_float(lds32(sb + P_K6 + k * 2624 + i0 * 4)), hi = __uint_as_float(lds32(sb + P_K6 + k * 2624 + i1 * 4));
                pw[h][k] = pack2(lo, y ? hi : 0.f);
            }
        }
#pragma unroll
        for (int h = 0; h < 2; h++)
#pragma unroll
            for (int k = 0; k < 4; k++) sts32(sb + P_P + (k * 2080 + x + h * 256 + 16) * 4, pw[h][k]);
    }
    bar_sync(9, 384);
    PROF(tid == 0, 3513);
    {
        float acc[16][4];
#pragma unroll
        for (int j = 0; j < 16; j++) acc[j][0] = acc[j][1] = acc[j][2] = acc[j][3] = 0;
#pragma unroll 1
        for (int e = hf * 4; e < hf * 4 + 4; e++) {
            uint32_t B[16][2];
            const uint32_t ua = sb + P_U + ch * 4352 + ((lane >> 3) & 1) * 2176 + (8 + (lane >> 4) * 8 + (lane & 7) - e) * 16;
#pragma unroll
            for (int j = 0; j < 8; j++) { const uint4 v = ldsm4(ua + j * 256); B[2 * j][0] = v.x; B[2 * j][1] = v.y; B[2 * j + 1][0] = v.z; B[2 * j + 1][1] = v.w; }
            const uint32_t pa = sb + P_P + (ch * 2080 + 16 + e * 16 + g - 2 * c) * 4;
#pragma unroll
            for (int d = 0; d < 16; d++) {
                const uint32_t a0 = lds32(pa + d * 512), a1 = lds32(pa + d * 512 + 32), a2 = lds32(pa + d * 512 - 32);
#pragma unroll
                for (int j = d; j < 16; j++) mma16(acc[j], a0, a1, a2, a0, B[j - d][0], B[j - d][1]);
            }
        }
        PROF(tid == 0, 3514);
        const uint32_t o = sb + P_Y + (ch * 2560 + c * 40 + g) * 4;
#pragma unroll
        for (int j = 0; j < 8; j++) {
#pragma unroll
            for (int i = 0; i < 4; i++) { const float lo = acc[j][i], hi = acc[j + 8][i]; acc[j][i] = hf ? hi : lo; sts32(o + (j + 8 - hf * 8) * 640 + (i & 1) * 80 + (i >> 1) * 32, __float_as_uint(hf ? lo : hi)); }
        }
        bar_sync(2 + ch, 64);
#pragma unroll
        for (int j = 0; j < 8; j++) {
#pragma unroll
            for (int i = 0; i < 4; i++) acc[j][i] += __uint_as_float(lds32(o + (j + hf * 8) * 640 + (i & 1) * 80 + (i >> 1) * 32));
        }
#pragma unroll
        for (int j = 0; j < 8; j++) {
#pragma unroll
            for (int i = 0; i < 4; i++) sts32(o + (j + hf * 8) * 640 + (i & 1) * 80 + (i >> 1) * 32, __float_as_uint(acc[j][i]));
        }
    }
    const uint2 dk = __ldg((const uint2*)(a.Dk + d0));
    bar_sync(1, 256);
#pragma unroll 2
    for (int i = 0; i < 8; i++) {
        const int t = i * 256 + tid;
        const uint32_t o = sb + P_Y + (t + 4 * (t >> 4)) * 4;
        const uint4 xu = lds128(sb + P_X + t * 16);
        float y[4];
#pragma unroll
        for (int k = 0; k < 4; k++) y[k] = rbf(__uint_as_float(lds32(o + k * 10240)));
        uint2 r;
        r.x = pack2(blo(xu.x) + rbf(y[0] + rbf(blo(xu.z) * blo(dk.x))), bhi(xu.x) + rbf(y[1] + rbf(bhi(xu.z) * bhi(dk.x))));
        r.y = pack2(blo(xu.y) + rbf(y[2] + rbf(blo(xu.w) * blo(dk.y))), bhi(xu.y) + rbf(y[3] + rbf(bhi(xu.w) * bhi(dk.y))));
        {
            const bool up = t & 8;
            const uint32_t o = __shfl_xor_sync(0xffffffffu, up ? r.x : r.y, 8);
            ((uint2*)(g_xA[0] + ((t >> 4) * 32 + (d0 >> 4)) * 32 + (t & 7) * 4 + ((d0 >> 1) & 2) + up))[(d0 >> 3) & 1] = up ? make_uint2(o, r.y) : make_uint2(r.x, o);
        }
        if (i == 0) {
            const float e0 = blo(r.x), e1 = bhi(r.x), e2 = blo(r.y), e3 = bhi(r.y);
            asm volatile("red.relaxed.gpu.global.add.v2.f32 [%0],{%1,%2};" ::"l"(g_st[0] + (t >> 7) * 2048 + lds32(sb + S_TAG) * 256 + (b & 1) * 128 + (t & 127)),
                         "f"((e0 + e1) + (e2 + e3)), "f"((e0 * e0 + e1 * e1) + (e2 * e2 + e3 * e3)) : "memory");
        }
    }
    PROF(tid == 0, 3515);
    bar_sync(10, 384);
}

__global__ void __cluster_dims__(2, 1, 1) __launch_bounds__(384, 1) main_kernel(const __grid_constant__ Params p) {
    extern __shared__ __align__(1024) uint8_t smem[];
    const uint32_t sb = __shfl_sync(0xffffffffu, smem_u32(smem), 0);
    uint32_t rank; asm("mov.u32 %0,%%cluster_ctarank;" : "=r"(rank));
    const int wi = __shfl_sync(0xffffffffu, threadIdx.x >> 5, 0);
    const int cl = blockIdx.x >> 1, wg = wi >> 2;
    const bool rec = p.rec0 >= 0 && cl >= p.rec0 && cl < p.rec0 + 32;
    PROF(threadIdx.x == 0, 3500);
    ProRegs pr;
    prologue_load(p.pa, max((int)blockIdx.x - 4, 0), pr);
    if (rec) rec_init(p, sb, cl - p.rec0, rank); else bulk_init(sb);
    if (threadIdx.x == 352 && p.dopro && cl >= 2) {
        mbar_init(sb + S_XBAR, 1);
        asm volatile("fence.mbarrier_init.release.cluster;" ::: "memory");
        mbar_expect(sb + S_XBAR, 32768);
        for (int j = 0; j < 8; j++) tma2d(sb + P_X + j * 4096, &p.tm[3], ((blockIdx.x - 4) >> 1) * 8, j * 256, sb + S_XBAR);
    }
    if (threadIdx.x == 320) {
        unsigned v;
        asm volatile("ld.relaxed.gpu.global.u32 %0,[%1];" : "=r"(v) : "l"(g_gate) : "memory");
        v = v / (4 * NCL) + p.dopro;
        sts64(sb + S_GATE, v * (4 * NCL), v & 1);
    }
    __syncwarp();
    asm volatile("barrier.cluster.arrive.relaxed.aligned;" ::: "memory");
    if (wg == 2) bar_arrive(8, 384);
    if (p.dopro && cl >= 2) prologue(p.pa, sb, blockIdx.x - 4, wi, pr); else if (wg < 2) bar_sync(8, 384);
    asm volatile("barrier.cluster.wait.aligned;" ::: "memory");
    fence_async_smem();
    bar_sync(wg == 2 ? 7 : 1, wg == 2 ? 128 : 256);
    if (p.dopro && (threadIdx.x == 32 || threadIdx.x == 352)) red_release(g_gate, 1);
    if (rec) {
        if (threadIdx.x == 0) {
            rec_fetch(&p.tm[1], sb + R_STK, (cl - p.rec0) * 128, rank * 256, 2, sb + R_BAR + RB_INIT * 8);
            rec_fetch(&p.tm[2], sb + R_STV, (cl - p.rec0) * 128, rank * 256, 2, sb + R_BAR + RB_INIT * 8);
        }
    }
    PROF(threadIdx.x == 0, 3506);
    __syncwarp();
    if (rec) {
        const int head = cl - p.rec0;
        if (wg == 2) {
            reg_dec<RH>();
            const int w = wi & 3;
            if (threadIdx.x == 256) rec_fetch(&p.tm[0], sb + R_STQ, head * 128, rank * 256, 2, sb + R_BAR + RB_INIT * 8);
            __syncwarp();
            wait_cnt_warp(g_gate, lds32(sb + S_GATE));
            if (p.dostats) x1_stats((head * 2 + rank) * 4 + w);
            __syncthreads();
            cluster_sync();
            if ((p.chains >> (w >> 1)) & 1) rec_attn(p, sb, w >> 1, w & 1, head, rank);
        } else {
            reg_inc<RW0>();
            rec_weights(p, sb, head, rank, wi);
        }
    } else {
        if (wg == 2) {
            reg_dec<40>();
            const int w = wi & 3;
            if (w == 0) bulk_producer(p, sb, cl, rank); else if (w >= 2) bulk_release(p, sb, cl, rank, w - 2); else bulk_relay(p, sb, cl);
        } else { reg_inc<232>(); bulk_consumer(p, sb, cl, rank, wi); }
    }
    __syncwarp();
    cluster_sync();
}

typedef CUresult (*EncFn)(CUtensorMap*, CUtensorMapDataType, cuuint32_t, void*, const cuuint64_t*, const cuuint64_t*, const cuuint32_t*, const cuuint32_t*,
                          CUtensorMapInterleave, CUtensorMapSwizzle, CUtensorMapL2promotion, CUtensorMapFloatOOBfill);
inline uint32_t mk(int type, int layer, int ch, int a, int b, int c) { return type | (layer << 3) | (ch << 4) | (a << 8) | (b << 16) | ((uint32_t)c << 24); }
constexpr int SMEM_BYTES = 232448;

struct Sched {
    Params* P; int n[NCL];
    void clear() { memset(P->task, 0, sizeof(P->task)); memset(n, 0, sizeof(n)); }
    void add(int cl, uint32_t t) { if (n[cl] < MAXT - 1) P->task[cl][n[cl]++] = t; }
};

constexpr int REC0 = 4;
struct Cfg { int LAG, TS1, TS2, DQU, DQO, DUN, DHN, MARG, NQ1, FAST0, n0, oc, fc, nuns, ns2, nhg, hs, osl, nfin, dry; };
#define PLAN 14, 2250, 2850, 2400, 1100, 5800, 420, 3000, 4, 1, 10, 6, 14, 6, 4, 8, 4000, 500, 0, 8500
Cfg g_cfg = {PLAN};
double g_est;
bool g_planned = false;
struct Plan { uint32_t w[NCL][MAXT]; int n[NCL]; double end, rec; };
void simulate(Plan& L, int nc, const Cfg& C) {
    const int LAG = C.LAG, NQ1 = C.NQ1, FAST0 = C.FAST0, n0 = C.n0, oc = C.oc, fc = C.fc, nuns = C.nuns, ns2 = C.ns2, nhg = C.nhg;
    const double TS1 = C.TS1, TS2 = C.TS2, DQU = C.DQU, DQO = C.DQO, DUN = C.DUN, DHN = C.DHN, MARG = C.MARG, hs = C.hs;
    const double INF = 1e18, DKB = 600, DOV = 700, DH = DHN, DHO = 1100, DF = 2200, DFB = 200, POLL = 450, FILL = 500, PUB = 600;
    enum { Q0, O0, Q1, HB, O1, FI, NK };
    struct Grp { int n, left; double done; } G[NK][16];
    double fr[NCL], it[100] = {}, cv[16];
    int ns[16], last[2][NCL], uc = 0, nit = 0;
    memset(L.n, 0, sizeof(L.n)); L.end = 0;
    auto fast = [&](int c) { return c < FAST0 || c >= fc; };
    for (int c = 0; c < 16; c++) {
        ns[c] = c < nuns ? 1 : c == 15 ? 16 : c == 14 ? 8 : ns2;
        const int cnt[NK] = {c < 2 ? 48 : (c & 1) ? 0 : 96, c < oc ? 8 : OPS1, c == 15 ? 24 : fast(c) ? 16 : 48 / NQ1, c >= 2 && !(c & 1) ? 16 : 0, ns[c], c < C.nfin || ns[c] == 1 ? 0 : c >= 14 ? 8 : 4};
        for (int k = 0; k < NK; k++) G[k][c] = {cnt[k], cnt[k], 0};
        cv[c] = INF;
    }
    for (int i = 0; i < nc; i++) { fr[i] = 0; last[0][i] = last[1][i] = -1; }
    auto fin = [&](int k, int c) { if ((k == Q0 && c >= 2) || k == HB) c &= ~1; return G[k][c].left ? INF : G[k][c].done; };
    auto len = [&](int i) { return (i >= LAG && i < 64) ? (double)TS2 : (double)TS1; };
    auto end_it = [&](int i) { return i < nit ? it[i] + len(i) : INF; };
    auto nominal = [&](int i) { if (i < nit) return it[i]; double t = nit ? it[nit - 1] : 11000 - TS1; for (int j = nit - 1; j < i; j++) t += len(j); return t; };
    auto put = [&](int i, uint32_t w) { if (L.n[i] < MAXT - 4) L.w[i][L.n[i]++] = w; else L.end = INF; };
    auto rel = [&](int k, int c) {
        switch (k) {
            case Q0: return 0.0;
            case O0: return end_it(4 * c + 3) + PUB + POLL;
            case Q1: return cv[c] + POLL;
            case HB: return cv[c - 2] + 600 + POLL;
            case O1: return fmax(end_it(LAG + 4 * c + 3) + PUB + POLL, G[O1][c].left == 1 && !G[FI][c].n ? G[O1][c].done - DKB * 64 / ns[c] : 0);
            default: return fin(O1, c) + POLL;
        }
    };
    auto dur = [&](int k, int c) {
        switch (k) {
            case Q0: return DQO + (c < 2 ? 2.0 : 1.0) * DQU;
            case O0: return (16 - G[O0][c].n) * DKB + 1200;
            case HB: return DHO + DH * c;
            case Q1: return DQO + 48.0 / G[Q1][c].n * DQU;
            case O1: return DOV + DKB * 64 / ns[c] + (G[O1][c].left == 1 && !G[FI][c].n ? 700 + 800 * ns[c] : 0);
            default: return DF + DFB * ns[c] * (c >= 14 ? 0.5 : 1);
        }
    };
    auto o0_est = [&](int c) {
        double t = uc ? cv[uc - 1] - 900 : 0;
        for (int j = uc; j < c; j++) t = fmax(t, nominal(4 * j + 4) + PUB + POLL + FILL) + dur(O0, j) + DUN;
        return fmax(t, nominal(4 * c + 4) + PUB + POLL);
    };
    auto cv_est = [&](int c) { return c < uc ? cv[c] : o0_est(c) + FILL + dur(O0, c) + DUN + 900; };
    auto slot = [&](int k, int c, int i) { return k == O0 ? (i < 8 ? i : nc + 7 - i) : c == 15 ? i : i - 8; };
    while (true) {
        while (nit < 64 + LAG) {
            double t = nit ? end_it(nit - 1) : 0;
            if (nit < 64) t = fmax(t, fin(Q0, nit >> 2) + POLL);
            if (nit >= LAG) t = fmax(t, fin(Q1, (nit - LAG) >> 2) + (nit < 64 ? 0 : POLL));
            if (t >= INF) break;
            it[nit++] = t;
        }
        int i = -1;
        for (int j = 0; j < nc; j++) if (fr[j] < INF && (i < 0 || fr[j] < fr[i])) i = j;
        if (i < 0) break;
        const double t = fr[i];
        double lim = INF;
        if (i < 8 && last[0][i] == uc) {
            if (G[O0][uc].left || fin(HB, uc) >= INF) { fr[i] = t + 200; continue; }
            const double e = fmax(G[O0][uc].done, fin(HB, uc) - 2000) + DUN;
            for (int j = 0; j < 8; j++) { put(j, mk(T_CV, 0, uc, 2 * j, G[O0][uc].n, 0)); fr[j] = e; }
            cv[uc++] = e + 900;
            continue;
        }
        const bool hg = (unsigned)(i - 24) < (unsigned)nhg;
        double hlim = INF;
        for (int c = 2; c < 16 && hg; c++) if (G[HB][c].left) { hlim = cv_est(c - 2) + hs; break; }
        int mine[2] = {-1, -1};
        for (int k = 0; k < 2; k++)
            for (int c = last[k][i] + 1; c < 16 && mine[k] < 0; c++) if ((unsigned)slot(O0 + k, c, i) < (unsigned)G[O0 + k][c].n) mine[k] = c;
        if (mine[0] >= 0) lim = i < 8 ? o0_est(mine[0]) - (uc ? 0 : C.dry) : nominal(4 * mine[0] + 4) + PUB + C.osl;
        else if (mine[1] >= 0) lim = cv_est(mine[1]) + POLL;
        else if (i < 16 && G[O1][15].left) lim = fmin(lim, nominal(64 + LAG) + PUB);
        int bk = -1, bc = 0; double bd = INF;
        for (int k = 0; k < NK; k++)
            for (int c = 0; c < 16; c++) {
                const bool urgent = k == O0 || k == Q1 || (k == O1 && c == 15);
                if (!G[k][c].left || ((k == O0 || k == Q1) && c != mine[k - O0]) || (k == O1 && c == 15 && i >= 16)) continue;
                if (rel(k, c) > t || (t + dur(k, c) + (k == Q0 && c >= 2 ? DQU : 0) > lim && !urgent)) continue;
                if (i < 8 && uc && uc < 16 && k != O0) continue;
                if ((k == HB && !hg && i < nc - 2) || (k != HB && !urgent && t + dur(k, c) + (k == Q0 && c >= 2 ? DQU : 0) > hlim)) continue;
                const double dl = urgent ? -INF : k == HB ? -INF / 2 : k == Q0 ? nominal(4 * c) - 3000 : 1e9 + c * 2 + (k == O1);
                if (dl < bd) { bd = dl; bk = k; bc = c; }
            }
        if (bk < 0) {
            bool any = i < 8 && uc < 16;
            for (int k = 0; k < NK; k++) for (int c = 0; c < 16; c++) any = any || G[k][c].left;
            fr[i] = any ? t + 200 : INF;
            if (t > 400000) { L.end = INF; return; }
            continue;
        }
        Grp& g = G[bk][bc];
        const int n = g.n - g.left, c = bc;
        int nu = 1;
        double d = dur(bk, c);
        if (bk == Q0) for (nu = c < 2 ? 2 : 1; c >= 2 && nu < g.left && (nu < 2 || (nu < n0 && t + d + DQU < fmin(fmin(lim, hlim), bd - MARG))); nu++) d += DQU;
        if (bk == O0 && i >= 8) d += (g.n - 8) * DKB;
        if (bk == Q0 && !c && n >= 32) { nu = 1; d -= DQU; }
        if (bk == O0 || bk == Q1) last[bk - O0][i] = c;
        if (bk == O0 && !c && i < 8 && C.dry) put(i, mk(T_CV, 0, 1, 2 * i, 0, 128));
        g.left -= nu;
        const bool fini = bk == O1 && !g.left && !G[FI][c].n;
        const double e = fmax(fmax(t, rel(bk, c) + FILL) + (t < 1 ? 3500 : 0) + d, fini ? g.done + POLL + 700 + 800 * ns[c] : 0);
        fr[i] = e;
        g.done = fmax(g.done, e + (bk == O1 ? 1900 : bk == O0 ? 0 : (bk == Q1 && g.n < 24) || (bk == Q0 && !c && nu == 2) ? -500 : 1000));
        if (bk == FI || fini) L.end = fmax(L.end, e);
        put(i, bk == Q0 ? (c == 0 ? mk(T_QKV, 0, 0, n < 32 ? n : 2 * n - 32, nu, 32) : c == 1 ? mk(T_QKV, 0, c, n, 2, 24) : mk(T_QKV, 0, c, n, nu, 64))
             : bk == O0 ? (i < 8 ? mk(T_OP, 0, c, i * (16 - g.n), 16 - g.n, i) : mk(T_OP, 0, c, 64 - (nc - i) * 8, 8, slot(O0, c, i)))
             : bk == HB ? mk(T_CV, 1, c, 2 * n, 0, 0)
             : bk == Q1 ? mk(T_QKV, 1, c, slot(Q1, c, i) * 2, 48 / g.n, g.n)
             : bk == O1 ? mk(T_OP, 1, c, n * 64 / ns[c], 64 / ns[c], n + (fini ? 32 : 0))
                        : mk(T_FIN, 1, c, n * (32 / g.n), ns[c], 16 / g.n));
    }
    L.rec = end_it(63 + LAG);
}
void plan(Params& P) {
    P.rec0 = REC0; P.chains = 3; P.lag = g_cfg.LAG; P.dostats = 1; P.dopro = 1;
    static Plan L;
    int cls[NCL], nc = 0;
    for (int c = REC0 + 32; c < NCL; c++) cls[nc++] = c;
    for (int c = REC0 - 1; c >= 0; c--) cls[nc++] = c;
    simulate(L, nc, g_cfg);
    g_est = L.end;
    Sched S; S.P = &P; S.clear();
    for (int i = 0; i < nc; i++) {
        bool warm = false;
        for (int k = 0; k < L.n[i]; k++) {
            if (!warm && k + 1 < L.n[i] && (L.w[i][k + 1] & 255) == (mk(T_FIN, 1, 15, 0, 0, 0) & 255)) { S.add(cls[i], (L.w[i][k + 1] & ~0xff0000u) | 0x80000000u); warm = true; }
            S.add(cls[i], L.w[i][k]);
            if ((L.w[i][k] & 7) == T_FIN) warm = true;
        }
    }
}

#define TK0() do {} while (0)
#define TK() do { P.e0 = (P.chains & 1) ? 64 : 0; P.b1 = (P.chains & 2) ? P.lag : 1000; P.nit = (P.chains & 2) ? P.lag + 64 : 64; TK0(); } while (0)
}

extern "C" void kernel_launch(void* const* d_in, const int* in_sizes, int n_in, void* d_out, int out_size) {
    typedef const __nv_bfloat16* BP;
    static EncFn enc = nullptr;
    if (!enc) {
        void* fn = nullptr; cudaDriverEntryPointQueryResult qr;
        cudaGetDriverEntryPoint("cuTensorMapEncodeTiled", &fn, cudaEnableDefault, &qr);
        enc = (EncFn)fn;
        cudaFuncSetAttribute(main_kernel, cudaFuncAttributeMaxDynamicSharedMemorySize, SMEM_BYTES);
    }
    static Params P;
    for (int i = 0; i < 4; i++) {
        const cuuint64_t cols = i < 3 ? 4096 : 512, rows = i < 3 ? 512 : 4096;
        cuuint64_t d2[2] = {cols, rows}, d3[3] = {64, rows, cols / 64}, str[2] = {cols * 2, 128};
        cuuint32_t box[3] = {64, 64, 4}, es[3] = {1, 1, 1};
        enc(&P.tm[i < 3 ? i : 4], CU_TENSOR_MAP_DATA_TYPE_BFLOAT16, 2, d_in[9 + i], d2, str, box, es, CU_TENSOR_MAP_INTERLEAVE_NONE, CU_TENSOR_MAP_SWIZZLE_128B,
                       CU_TENSOR_MAP_L2_PROMOTION_L2_128B, CU_TENSOR_MAP_FLOAT_OOB_FILL_NONE);
        for (int m = 0; m < 2; m++) {
            cuuint32_t box3[3] = {64, 32, m ? 2u : 4u};
            enc(&P.t3[m][i], CU_TENSOR_MAP_DATA_TYPE_BFLOAT16, 3, d_in[9 + i], d3, str, box3, es, CU_TENSOR_MAP_INTERLEAVE_NONE, CU_TENSOR_MAP_SWIZZLE_128B,
                CU_TENSOR_MAP_L2_PROMOTION_L2_128B, CU_TENSOR_MAP_FLOAT_OOB_FILL_NONE);
        }
    }
    {
        cuuint64_t dims[2] = {512, 2048}, str[1] = {1024};
        cuuint32_t box[2] = {8, 256}, es[2] = {1, 1};
        enc(&P.tm[3], CU_TENSOR_MAP_DATA_TYPE_BFLOAT16, 2, d_in[0], dims, str, box, es, CU_TENSOR_MAP_INTERLEAVE_NONE, CU_TENSOR_MAP_SWIZZLE_NONE,
            CU_TENSOR_MAP_L2_PROMOTION_NONE, CU_TENSOR_MAP_FLOAT_OOB_FILL_NONE);
    }
    for (int m = 0; m < 2; m++) {
        void* ga; cudaGetSymbolAddress(&ga, g_A);
        cuuint64_t dims[2] = {512, sizeof(AOps) / 1024}, str[1] = {1024};
        cuuint32_t box[2] = {256, m ? 16u : 8u}, es[2] = {1, 1};
        enc(&P.ta[m], CU_TENSOR_MAP_DATA_TYPE_BFLOAT16, 2, ga, dims, str, box, es, CU_TENSOR_MAP_INTERLEAVE_NONE, CU_TENSOR_MAP_SWIZZLE_NONE,
            CU_TENSOR_MAP_L2_PROMOTION_L2_128B, CU_TENSOR_MAP_FLOAT_OOB_FILL_NONE);
    }
    P.mem0 = (BP)d_in[8]; P.Wo = (BP)d_in[12]; P.Dskip = (BP)d_in[6]; P.out = (__nv_bfloat16*)d_out;
    cudaStream_t s = cudaStreamPerThread;
    P.pa = {(BP)d_in[0], (BP)d_in[1], (BP)d_in[2], (BP)d_in[3], (BP)d_in[4], (BP)d_in[5], (BP)d_in[6], (BP)d_in[9], (BP)d_in[10], (BP)d_in[11], (BP)d_in[12], (BP)d_in[8]};
    if (!g_planned) { plan(P); g_planned = true; }
    TK(); main_kernel<<<2 * NCL, 384, SMEM_BYTES, s>>>(P); TK();
}
```

```cpp
#include <cuda_runtime.h>
#include <cuda_bf16.h>
#include <cuda.h>
#include <stdint.h>
#include <string.h>
#include <math.h>

#define MAXTN 42
namespace {

constexpr int NCL = 66;
constexpr int NLIST = NCL - 32;
__host__ __device__ inline int list_of(int cl) { return cl < 4 ? cl : cl - 32; }
constexpr int MAXT = MAXTN;
#define PFC 1
#define QB1 2
#define QB2 4
#define QB3 6
#define LAGQ 2
#define CPOS 2
#define OPS1N 10
constexpr int OPS1 = OPS1N;
constexpr int MAXSPLIT = 16;
constexpr int PW = 144;

struct AOps { uint4 x[2][16 * 8 * 1024], o[2][16 * 64 * 1024]; };
__device__ AOps g_A;
#define g_xA g_A.x
#define g_o g_A.o
__device__ float2 g_st[2][16 * 2048];
__device__ float2 g_st2[2 * 16 * 128];
__device__ uint4 g_qkv[2][64 * 64 * 768];
__device__ uint4 g_pp[2][16 * MAXSPLIT * 8192];
__device__ uint4 g_acc[7 * 2048];
__device__ unsigned g_gate[32];
__device__ uint32_t g_P[16 * 16 * 32 * PW];
__device__ uint4 g_u[16 * 16 * 512];
__device__ float4 g_carry[2][17 * 16 * 4 * 256];
__device__ unsigned g_cnt[13 * 64];
__device__ uint32_t g_ln0[2048];

enum { C_QKV0 = 0, C_QKV1 = 1  , C_O0 = 2, C_O1 = 3, C_U = 4, C_OP1 = 5, C_CV = 6, C_ST = 7, C_H = 8, C_OP0 = 9   };
__device__ __forceinline__ unsigned* cnt_ptr(int kind, int chunk) { return g_cnt + kind * 64 + chunk; }

enum { T_END = 0, T_QKV = 1, T_OP = 2, T_CV = 3, T_FIN = 4 };
struct ProArgs { const __nv_bfloat16 *x, *lAr, *Ai, *Cr, *Ci, *ldt, *Dk, *Wq, *Wk, *Wv, *Wo, *mem0; };
struct Params {
    CUtensorMap tm[5];
    CUtensorMap t3[5];
    CUtensorMap ta[2];
    ProArgs pa;
    int dopro;
    const __nv_bfloat16* mem0;
    const __nv_bfloat16* Wo;
    const __nv_bfloat16* Dskip;
    __nv_bfloat16* out;
    int rec0;
    int chains;
    int lag;
    int b1, e0, nit;
    int zero, gpit;
    int dostats;
    uint32_t task[NLIST][MAXT];
};

__device__ __forceinline__ uint32_t smem_u32(const void* p) { return (uint32_t)__cvta_generic_to_shared(p); }
__device__ __forceinline__ uint32_t mapa(uint32_t a, uint32_t r) {
    uint32_t o; asm("mapa.shared::cluster.u32 %0,%1,%2;" : "=r"(o) : "r"(a), "r"(r)); return o;
}
__device__ __forceinline__ void mbar_init(uint32_t b, int c) { asm volatile("mbarrier.init.shared::cta.b64 [%0],%1;" ::"r"(b), "r"(c) : "memory"); }
__device__ __forceinline__ void mbar_expect(uint32_t b, int bytes) { asm volatile("mbarrier.arrive.expect_tx.shared::cta.b64 _,[%0],%1;" ::"r"(b), "r"(bytes) : "memory"); }
__device__ __forceinline__ void mbar_arrive(uint32_t b) { asm volatile("mbarrier.arrive.shared::cta.b64 _,[%0];" ::"r"(b) : "memory"); }
__device__ __forceinline__ void mbar_arrive_cluster(uint32_t b) { asm volatile("mbarrier.arrive.shared::cluster.b64 _,[%0];" ::"r"(b) : "memory"); }
__device__ __forceinline__ void mbar_arrive1(uint32_t b) { asm volatile("{.reg .pred p; elect.sync _|p,0xffffffff; @p mbarrier.arrive.shared::cta.b64 _,[%0];}" ::"r"(b) : "memory"); }
__device__ __forceinline__ void mbar_arrive1_cluster(uint32_t b) { asm volatile("{.reg .pred p; elect.sync _|p,0xffffffff; @p mbarrier.arrive.shared::cluster.b64 _,[%0];}" ::"r"(b) : "memory"); }
__device__ __forceinline__ void mbar_wait(uint32_t b, uint32_t ph) {
    asm volatile(
        "{.reg .pred p; .reg .u32 n; mov.u32 n,0;\n"
        "W%=: mbarrier.try_wait.parity.shared::cta.b64 p,[%0],%1;\n"
        "@p bra D%=;\n"
        "add.u32 n,n,1; setp.lt.u32 p,n,2000000; @p bra W%=;\n"
        "trap;\n"
        "D%=: }" ::"r"(b), "r"(ph) : "memory");
}
__device__ __forceinline__ bool mbar_test(uint32_t b, uint32_t ph) {
    uint32_t ok;
    asm volatile("{.reg .pred p; mbarrier.test_wait.parity.shared::cta.b64 p,[%1],%2; selp.u32 %0,1,0,p;}" : "=r"(ok) : "r"(b), "r"(ph) : "memory");
    return ok;
}
__device__ __forceinline__ bool wait_lds128(uint32_t b, uint32_t ph, uint32_t a, uint4& v) {
    uint32_t ok;
    asm volatile("{.reg .pred p; mbarrier.try_wait.parity.shared::cta.b64 p,[%5],%6,20000; ld.shared.v4.u32 {%0,%1,%2,%3},[%7]; selp.u32 %4,1,0,p;}"
                 : "=r"(v.x), "=r"(v.y), "=r"(v.z), "=r"(v.w), "=r"(ok) : "r"(b), "r"(ph), "r"(a) : "memory");
    return ok;
}
__device__ __forceinline__ bool wait_lds64(uint32_t b, uint32_t ph, uint32_t a, uint2& v) {
    uint32_t ok;
    asm volatile("{.reg .pred p; mbarrier.try_wait.parity.shared::cta.b64 p,[%3],%4,20000; ld.shared.v2.u32 {%0,%1},[%5]; selp.u32 %2,1,0,p;}"
                 : "=r"(v.x), "=r"(v.y), "=r"(ok) : "r"(b), "r"(ph), "r"(a) : "memory");
    return ok;
}
template <int PH> __device__ __forceinline__ void mbar_wait_c(uint32_t b) {
    asm volatile(
        "{.reg .pred p; .reg .u32 n; mov.u32 n,%2;\n"
        "W%=: mbarrier.try_wait.parity.shared::cta.b64 p,[%0],%1;\n"
        "@p bra D%=;\n"
        "add.u32 n,n,1; setp.lt.u32 p,n,2000000; @p bra W%=;\n"
        "trap;\n"
        "D%=: }" ::"r"(b), "n"(PH), "n"(PH) : "memory");
}
__device__ __forceinline__ void bar_sync(int id, int n) { asm volatile("bar.sync %0,%1;" ::"r"(id), "r"(n) : "memory"); }
__device__ __forceinline__ void bar_arrive(int id, int n) { asm volatile("bar.arrive %0,%1;" ::"r"(id), "r"(n) : "memory"); }
__device__ __forceinline__ void cluster_sync() { asm volatile("barrier.cluster.arrive.relaxed.aligned; barrier.cluster.wait.aligned;" ::: "memory"); }
__device__ __forceinline__ void fence_async() { asm volatile("fence.proxy.async;" ::: "memory"); }
__device__ __forceinline__ void fence_async_smem() { asm volatile("fence.proxy.async.shared::cta;" ::: "memory"); }
#define EFR 1
#define EFW 1
constexpr uint64_t POL_N = 0x1000000000000000ull, POL_F = 0x12F0000000000000ull;
constexpr uint64_t POL_LAST = EFR ? POL_F : POL_N  , POL_LATE = EFW ? POL_F : POL_N  , POL_SOON = EFW > 1 ? POL_F : POL_N;
__device__ __forceinline__ void bulk_g2s(uint32_t dst, const void* src, int bytes, uint32_t bar, uint64_t pol) {
    asm volatile("cp.async.bulk.shared::cluster.global.mbarrier::complete_tx::bytes.L2::cache_hint [%0],[%1],%2,[%3],%4;" ::"r"(dst), "l"(src), "r"(bytes), "r"(bar), "l"(pol) : "memory");
}
__device__ __forceinline__ void bulk_g2s_mc(uint32_t dst, const void* src, int bytes, uint32_t bar, uint64_t pol) {
    asm volatile("cp.async.bulk.shared::cluster.global.mbarrier::complete_tx::bytes.multicast::cluster.L2::cache_hint [%0],[%1],%2,[%3],%4,%5;" ::"r"(dst), "l"(src), "r"(bytes), "r"(bar), "h"((uint16_t)3), "l"(pol) : "memory");
}
__device__ __forceinline__ void bulk_s2s(uint32_t dst, uint32_t src, int bytes, uint32_t bar) {
    asm volatile("cp.async.bulk.shared::cluster.shared::cta.mbarrier::complete_tx::bytes [%0],[%1],%2,[%3];" ::"r"(dst), "r"(src), "r"(bytes), "r"(bar) : "memory");
}
__device__ __forceinline__ bool elect() {
    uint32_t r; asm volatile("{.reg .pred p; elect.sync _|p,0xffffffff; selp.u32 %0,1,0,p;}" : "=r"(r)); return r;
}
__device__ __forceinline__ void stg128(uint4* p, uint4 v, uint64_t pol) {
    asm volatile("st.global.L2::cache_hint.v4.u32 [%0],{%1,%2,%3,%4},%5;" ::"l"(p), "r"(v.x), "r"(v.y), "r"(v.z), "r"(v.w), "l"(pol));
}
__device__ __forceinline__ void stg32(uint32_t* p, uint32_t v, uint64_t pol) { asm volatile("st.global.L2::cache_hint.u32 [%0],%1,%2;" ::"l"(p), "r"(v), "l"(pol)); }
__device__ __forceinline__ uint4 ldcg128_last(const uint4* p) {
    uint4 v; asm volatile("ld.global.cg.L2::cache_hint.v4.u32 {%0,%1,%2,%3},[%4],%5;" : "=r"(v.x), "=r"(v.y), "=r"(v.z), "=r"(v.w) : "l"(p), "l"(POL_LAST) : "memory"); return v;
}
__device__ __forceinline__ void tma2d(uint32_t dst, const CUtensorMap* tm, int x, int y, uint32_t bar) {
    asm volatile("cp.async.bulk.tensor.2d.shared::cluster.global.mbarrier::complete_tx::bytes [%0],[%1,{%2,%3}],[%4];" ::"r"(dst), "l"(tm), "r"(x), "r"(y), "r"(bar) : "memory");
}
__device__ __forceinline__ void tma3d_mc(uint32_t dst, const CUtensorMap* tm, int y, int z, uint32_t bar, uint16_t mask) {
    asm volatile("{.reg .pred p; elect.sync _|p,0xffffffff;\n"
                 "@p cp.async.bulk.tensor.3d.shared::cluster.global.mbarrier::complete_tx::bytes.multicast::cluster [%0],[%1,{0,%2,%3}],[%4],%5;}"
                 ::"r"(dst), "l"(tm), "r"(y), "r"(z), "r"(bar), "h"(mask) : "memory");
}
__device__ __forceinline__ void tma2d_mc(uint32_t dst, const CUtensorMap* tm, int x, int y, uint32_t bar, uint16_t mask, uint64_t pol) {
    asm volatile("{.reg .pred p; elect.sync _|p,0xffffffff;\n"
                 "@p cp.async.bulk.tensor.2d.shared::cluster.global.mbarrier::complete_tx::bytes.multicast::cluster.L2::cache_hint [%0],[%1,{%2,%3}],[%4],%5,%6;}"
                 ::"r"(dst), "l"(tm), "r"(x), "r"(y), "r"(bar), "h"(mask), "l"(pol) : "memory");
}
__device__ __forceinline__ void bulk_g2s1(uint32_t dst, const void* src, int bytes, uint32_t bar, uint64_t pol) {
    asm volatile("{.reg .pred p; elect.sync _|p,0xffffffff;\n"
                 "@p cp.async.bulk.shared::cluster.global.mbarrier::complete_tx::bytes.L2::cache_hint [%0],[%1],%2,[%3],%4;}" ::"r"(dst), "l"(src), "r"(bytes), "r"(bar), "l"(pol) : "memory");
}
__device__ __forceinline__ void mbar_expect1(uint32_t b, int bytes) {
    asm volatile("{.reg .pred p; elect.sync _|p,0xffffffff; @p mbarrier.arrive.expect_tx.shared::cta.b64 _,[%0],%1;}" ::"r"(b), "r"(bytes) : "memory");
}
__device__ __forceinline__ void st_async4(uint32_t a, uint32_t x, uint32_t y, uint32_t z, uint32_t w, uint32_t mb) {
    asm volatile("st.async.shared::cluster.mbarrier::complete_tx::bytes.v4.b32 [%0],{%1,%2,%3,%4},[%5];" ::"r"(a), "r"(x), "r"(y), "r"(z), "r"(w), "r"(mb) : "memory");
}
__device__ __forceinline__ void st_async2(uint32_t a, uint32_t x, uint32_t y, uint32_t mb) {
    asm volatile("st.async.shared::cluster.mbarrier::complete_tx::bytes.v2.b32 [%0],{%1,%2},[%3];" ::"r"(a), "r"(x), "r"(y), "r"(mb) : "memory");
}
#define LDSQ "ld.shared"
__device__ __forceinline__ uint4 lds128(uint32_t a) { uint4 v; asm volatile(LDSQ ".v4.u32 {%0,%1,%2,%3},[%4];" : "=r"(v.x), "=r"(v.y), "=r"(v.z), "=r"(v.w) : "r"(a) : "memory"); return v; }
__device__ __forceinline__ uint2 lds64(uint32_t a) { uint2 v; asm volatile(LDSQ ".v2.u32 {%0,%1},[%2];" : "=r"(v.x), "=r"(v.y) : "r"(a) : "memory"); return v; }
__device__ __forceinline__ uint32_t lds32(uint32_t a) { uint32_t v; asm volatile(LDSQ ".u32 %0,[%1];" : "=r"(v) : "r"(a) : "memory"); return v; }
__device__ __forceinline__ void sts128(uint32_t a, uint32_t x, uint32_t y, uint32_t z, uint32_t w) { asm volatile("st.shared.v4.u32 [%0],{%1,%2,%3,%4};" ::"r"(a), "r"(x), "r"(y), "r"(z), "r"(w) : "memory"); }
__device__ __forceinline__ void sts64(uint32_t a, uint32_t x, uint32_t y) { asm volatile("st.shared.v2.u32 [%0],{%1,%2};" ::"r"(a), "r"(x), "r"(y) : "memory"); }
__device__ __forceinline__ void sts32(uint32_t a, uint32_t x) { asm volatile("st.shared.u32 [%0],%1;" ::"r"(a), "r"(x) : "memory"); }
__device__ __forceinline__ uint4 ldsm4(uint32_t a) { uint4 v; asm volatile("ldmatrix.sync.aligned.m8n8.x4.shared.b16 {%0,%1,%2,%3},[%4];" : "=r"(v.x), "=r"(v.y), "=r"(v.z), "=r"(v.w) : "r"(a) : "memory"); return v; }
__device__ __forceinline__ uint4 ldsm4t(uint32_t a) { uint4 v; asm volatile("ldmatrix.sync.aligned.m8n8.x4.trans.shared.b16 {%0,%1,%2,%3},[%4];" : "=r"(v.x), "=r"(v.y), "=r"(v.z), "=r"(v.w) : "r"(a) : "memory"); return v; }
__device__ __forceinline__ uint32_t movm(uint32_t a) { uint32_t d; asm volatile("movmatrix.sync.aligned.m8n8.trans.b16 %0,%1;" : "=r"(d) : "r"(a)); return d; }
__device__ __forceinline__ uint32_t pack2(float lo, float hi) { uint32_t d; asm("cvt.rn.bf16x2.f32 %0,%1,%2;" : "=r"(d) : "f"(hi), "f"(lo)); return d; }
__device__ __forceinline__ uint32_t hadd2(uint32_t a, uint32_t b) { uint32_t d; asm("add.rn.bf16x2 %0,%1,%2;" : "=r"(d) : "r"(a), "r"(b)); return d; }
__device__ __forceinline__ float blo(uint32_t v) { return __uint_as_float(v << 16); }
__device__ __forceinline__ float bhi(uint32_t v) { return __uint_as_float(v & 0xffff0000u); }
__device__ __forceinline__ float rbf(float x) { return __uint_as_float(pack2(0.f, x)); }
__device__ __forceinline__ float ex2(float x) { float y; asm("ex2.approx.ftz.f32 %0,%1;" : "=f"(y) : "f"(x)); return y; }
__device__ __forceinline__ float rcp(float x) { float y; asm("rcp.approx.ftz.f32 %0,%1;" : "=f"(y) : "f"(x)); return y; }
__device__ __forceinline__ void mma16(float* c, uint32_t a0, uint32_t a1, uint32_t a2, uint32_t a3, uint32_t b0, uint32_t b1) {
    asm volatile("mma.sync.aligned.m16n8k16.row.col.f32.bf16.bf16.f32 {%0,%1,%2,%3},{%4,%5,%6,%7},{%8,%9},{%0,%1,%2,%3};"
                 : "+f"(c[0]), "+f"(c[1]), "+f"(c[2]), "+f"(c[3]) : "r"(a0), "r"(a1), "r"(a2), "r"(a3), "r"(b0), "r"(b1));
}
__device__ __forceinline__ void mma8(float* c, uint32_t a0, uint32_t a1, uint32_t b0) {
    asm volatile("mma.sync.aligned.m16n8k8.row.col.f32.bf16.bf16.f32 {%0,%1,%2,%3},{%4,%5},{%6},{%0,%1,%2,%3};"
                 : "+f"(c[0]), "+f"(c[1]), "+f"(c[2]), "+f"(c[3]) : "r"(a0), "r"(a1), "r"(b0));
}
__device__ __forceinline__ uint4 ld_rlx128(const uint4* p) {
    uint4 v;
    asm volatile("{.reg .b128 t; ld.relaxed.gpu.global.b128 t,[%4]; mov.b128 {%0,%1,%2,%3},t;}" : "=r"(v.x), "=r"(v.y), "=r"(v.z), "=r"(v.w) : "l"(p) : "memory");
    return v;
}
__device__ __forceinline__ void st_rlx128(uint4* p, uint32_t x, uint32_t y, uint32_t z, uint32_t w) {
    asm volatile("{.reg .b128 t; mov.b128 t,{%1,%2,%3,%4}; st.relaxed.gpu.global.b128 [%0],t;}" ::"l"(p), "r"(x), "r"(y), "r"(z), "r"(w) : "memory");
}
__device__ __forceinline__ uint4 ldcg128(const uint4* p) { uint4 v; asm volatile("ld.global.cg.v4.u32 {%0,%1,%2,%3},[%4];" : "=r"(v.x), "=r"(v.y), "=r"(v.z), "=r"(v.w) : "l"(p) : "memory"); return v; }
__device__ __forceinline__ void red_release(unsigned* p, unsigned v) {
    asm volatile("fence.proxy.async; red.relaxed.gpu.global.add.u32 [%0],%1;" ::"l"(p), "r"(v) : "memory");
}
__device__ __forceinline__ void wait_cnt(const unsigned* p, unsigned target) {
    unsigned v; int n = 0;
    while (true) {
        asm volatile("ld.acquire.gpu.global.u32 %0,[%1];" : "=r"(v) : "l"(p) : "memory");
        if (v >= target) break;
        if (++n > 3000000) __trap();
        __nanosleep(40);
    }
}
__device__ __forceinline__ void wait_cnt_warp(const unsigned* p, unsigned target) {
    unsigned v; int n = 0;
    while (true) {
        asm volatile("ld.acquire.gpu.global.u32 %0,[%1];" : "=r"(v) : "l"(p) : "memory");
        if (__all_sync(0xffffffffu, v >= target)) break;
        if (++n > 3000000) __trap();
    }
}
__device__ __forceinline__ uint64_t mkdesc(uint32_t addr, uint32_t lbo, uint32_t sbo, uint32_t sw) {
    return (uint64_t)((addr & 0x3FFFF) >> 4) | ((uint64_t)(lbo >> 4) << 16) | ((uint64_t)(sbo >> 4) << 32) | ((uint64_t)sw << 62);
}
__device__ __forceinline__ void wg_fence() { asm volatile("wgmma.fence.sync.aligned;" ::: "memory"); }
__device__ __forceinline__ void wg_commit() { asm volatile("wgmma.commit_group.sync.aligned;" ::: "memory"); }
template <int N> __device__ __forceinline__ void wg_wait() { asm volatile("wgmma.wait_group.sync.aligned %0;" ::"n"(N) : "memory"); }
#define R8(c, o) "+f"(c[o]), "+f"(c[o + 1]), "+f"(c[o + 2]), "+f"(c[o + 3]), "+f"(c[o + 4]), "+f"(c[o + 5]), "+f"(c[o + 6]), "+f"(c[o + 7])
#define R32(c, o) R8(c, o), R8(c, o + 8), R8(c, o + 16), R8(c, o + 24)
#define S32A "%0,%1,%2,%3,%4,%5,%6,%7,%8,%9,%10,%11,%12,%13,%14,%15,%16,%17,%18,%19,%20,%21,%22,%23,%24,%25,%26,%27,%28,%29,%30,%31"
#define S32B ",%32,%33,%34,%35,%36,%37,%38,%39,%40,%41,%42,%43,%44,%45,%46,%47,%48,%49,%50,%51,%52,%53,%54,%55,%56,%57,%58,%59,%60,%61,%62,%63"
#define S32C ",%64,%65,%66,%67,%68,%69,%70,%71,%72,%73,%74,%75,%76,%77,%78,%79,%80,%81,%82,%83,%84,%85,%86,%87,%88,%89,%90,%91,%92,%93,%94,%95"
#define S32D ",%96,%97,%98,%99,%100,%101,%102,%103,%104,%105,%106,%107,%108,%109,%110,%111,%112,%113,%114,%115,%116,%117,%118,%119,%120,%121,%122,%123,%124,%125,%126,%127"
#define W8(c, o) "=f"(c[o]), "=f"(c[o + 1]), "=f"(c[o + 2]), "=f"(c[o + 3]), "=f"(c[o + 4]), "=f"(c[o + 5]), "=f"(c[o + 6]), "=f"(c[o + 7])
#define W32(c, o) W8(c, o), W8(c, o + 8), W8(c, o + 16), W8(c, o + 24)
template <bool ACC> __device__ __forceinline__ void wgmma256(float* c, uint64_t da, uint64_t db) {
    if (ACC) asm volatile("wgmma.mma_async.sync.aligned.m64n256k16.f32.bf16.bf16 {" S32A S32B S32C S32D "},%128,%129,1,1,1,0,1;"
                          : R32(c, 0), R32(c, 32), R32(c, 64), R32(c, 96) : "l"(da), "l"(db));
    else asm volatile("wgmma.mma_async.sync.aligned.m64n256k16.f32.bf16.bf16 {" S32A S32B S32C S32D "},%128,%129,0,1,1,0,1;"
                      : W32(c, 0), W32(c, 32), W32(c, 64), W32(c, 96) : "l"(da), "l"(db));
}
template <bool ACC> __device__ __forceinline__ void wgmma128r(float* c, const uint4& a, uint64_t db) {
    if (ACC) asm volatile("wgmma.mma_async.sync.aligned.m64n128k16.f32.bf16.bf16 {" S32A S32B "},{%64,%65,%66,%67},%68,1,1,1,1;"
                          : R32(c, 0), R32(c, 32) : "r"(a.x), "r"(a.y), "r"(a.z), "r"(a.w), "l"(db));
    else asm volatile("wgmma.mma_async.sync.aligned.m64n128k16.f32.bf16.bf16 {" S32A S32B "},{%64,%65,%66,%67},%68,0,1,1,1;"
                      : W32(c, 0), W32(c, 32) : "r"(a.x), "r"(a.y), "r"(a.z), "r"(a.w), "l"(db));
}
template <int N> __device__ __forceinline__ void reg_inc() { asm volatile("setmaxnreg.inc.sync.aligned.u32 %0;" ::"n"(N)); }
template <int N> __device__ __forceinline__ void reg_dec() { asm volatile("setmaxnreg.dec.sync.aligned.u32 %0;" ::"n"(N)); }

#define PROF(cond, idx) do {} while (0)
#define CPROF(k) do {} while (0)

constexpr int S_GATE = 232440, S_TAG = 232444, S_XBAR = 232432;
constexpr float SC_LOG2E = 0.08838834764831845f * 1.4426950408889634f;

__device__ __forceinline__ float2 ln_finish(float mean, float var) {
    float sd; asm("sqrt.approx.f32 %0,%1;" : "=f"(sd) : "f"(rbf(rbf(var) + 1e-5f)));
    sd = rbf(sd);
    return make_float2(rbf(mean), sd);
}

__device__ __forceinline__ float4 row_stats(const uint4* src, int stride) {
    const int g = (threadIdx.x & 31) >> 2;
    uint4 v[16];
#pragma unroll
    for (int i = 0; i < 16; i++) v[i] = ldcg128(src + i * stride);
    float a[4] = {0, 0, 0, 0}, q0[4] = {0, 0, 0, 0}, q1[4] = {0, 0, 0, 0};
#pragma unroll
    for (int i = 0; i < 16; i++) {
        mma16(a, v[i].x, v[i].y, v[i].z, v[i].w, 0x3f803f80u, 0x3f803f80u);
        mma8(q0, v[i].x, v[i].y, v[i].x); mma8(q1, v[i].x, v[i].y, v[i].y);
        mma8(q0, v[i].z, v[i].w, v[i].z); mma8(q1, v[i].z, v[i].w, v[i].w);
    }
    return make_float4(a[0], (g & 1) ? q0[1] : q0[0], a[2], (g & 1) ? q1[3] : q1[2]);
}
__device__ __forceinline__ void x1_stats(int i) {
    const int lane = threadIdx.x & 31, g = lane >> 2, c = lane & 3;
    const float4 r = row_stats(g_xA[0] + i * 512 + lane, 32);
    float2* dst = g_st[0] + (i >> 4) * 2048 + ((i < 32 ? 4 : 0) + (i & 1)) * 128 + ((i >> 1) & 7) * 16 + g;
    if (c == (g >> 1)) { dst[0] = make_float2(r.x, r.y); dst[8] = make_float2(r.z, r.w); g_ln0[i * 8 + g] = 0; }
    __syncwarp();
    if (lane == 0) red_release(cnt_ptr(C_ST, i >> 4), 1);
}
__global__ void stats_kernel() { x1_stats(blockIdx.x * 4 + (threadIdx.x >> 5)); }

#define NT 9
#define RH 104
#define RW0 200
#define NPD 9
#define NTO 12
#define DP1 9
#define GPW 0
#define GPJ 0
#define PACE 2
#define EARLY 4
#define G2I 4
#define VE 4
#define VF 8
constexpr int R_WV = 0, R_WO = 65536, R_T = 131072, R_M = R_T + 20480, R_LOC = R_M + 4096, R_REM = R_LOC + 6144, R_O = R_REM + 12288, R_SX = R_O + 2048,
              R_IL = R_SX + 5120, XS = R_IL + 128 - R_T, R_BAR = 231936, R_Z = R_BAR + 128  , R_STQ = 0, R_STK = 65536, R_STV = 131072;
static_assert(R_T + 2 * XS <= R_BAR && R_BAR + 256 <= S_XBAR, "smem map");
enum { RB_INIT = 0, RB_V = 4  , RB_QK = 8  , RB_T = 12  , RB_N = 16 };
enum { NB_MF = 1  , NB_LOC = 3  , NB_PAIR = 5  , NB_O = 9  , NB_XG = 11  , NB_W = 13 };
__device__ __forceinline__ uint32_t clk32() { return (uint32_t)clock64(); }

__device__ __forceinline__ char* acc_base() { return (char*)(((size_t)g_acc + 131071) & ~(size_t)131071); }
__device__ __forceinline__ uint32_t acc_slice(uint32_t s6) { return (s6 & 1) * 256 + (s6 >> 1) * 1024; }
__device__ __forceinline__ uint32_t acc_main(uint32_t rank, uint32_t tid) { return acc_slice(rank * 32 + (tid >> 3)) + (tid & 7) * 16; }
__device__ __forceinline__ uint32_t acc_extra(uint32_t rank, uint32_t tid) { return 65536 + acc_slice(((tid >> 5) & 1) + rank * 4 + (tid >> 6) * 8) + (tid & 31) * 4; }
__device__ __forceinline__ uint32_t acc_slot(uint32_t s) { return (s & 1) * 128 + (s & 2) * 256; }
__device__ __forceinline__ void acc_init(const __nv_bfloat16* mem0, int i) {
    const uint32_t tid = i & 255, rank = (i >> 8) & 1, slot = (i >> 9) & 3, X = i >> 11;
    uint32_t v[5] = {0, 0, 0, 0, 0};
    if (slot == 3) {
        const uint16_t* m = (const uint16_t*)mem0 + (tid & 3) * 1024 + rank * 256 + (tid >> 5) * 32 + ((tid >> 2) & 7);
#pragma unroll
        for (int k = 0; k < 4; k++) v[k] = __ldg(m + k * 8) | ((uint32_t)__ldg(m + k * 8 + 512) << 16);
        v[4] = (v[3] >> 16) | 0x42000000u; v[3] = (v[3] & 0xffff) | 0x42000000u;
    }
    *(uint4*)(acc_base() + X * 32768 + acc_slot(slot) + acc_main(rank, tid)) = make_uint4(v[0], v[1], v[2], v[3]);
    *(uint32_t*)(acc_base() + X * 1024 + acc_slot(slot) + acc_extra(rank, tid)) = v[4];
}
__global__ void acc_init_kernel(const __nv_bfloat16* mem0) { acc_init(mem0, blockIdx.x * 256 + threadIdx.x); }

struct RecW { uint32_t am, ae, ah, dp, lp, lpw, vo, sb, bar, zero, ts, tn; };
__device__ __forceinline__ uint32_t vadd(uint32_t a, uint32_t b) { uint32_t d; asm volatile("add.u32 %0,%1,%2;" : "=r"(d) : "r"(a), "r"(b)); return d; }
__device__ __forceinline__ uint32_t vshr(uint32_t a, int n) { uint32_t d; asm volatile("shr.u32 %0,%1,%2;" : "=r"(d) : "r"(a), "r"(n)); return d; }
__device__ __forceinline__ uint64_t gptr(uint32_t lo, uint32_t hi) { uint64_t d; asm("mov.b64 %0,{%1,%2};" : "=l"(d) : "r"(lo), "r"(hi)); return d; }
__device__ __forceinline__ void sfence(uint32_t zero) { asm volatile("{.reg .pred p; setp.ne.u32 p,%0,0; @p exit;}" ::"r"(zero) : "memory"); }
#define SF sfence(k.zero)
#define TS(i) do {} while (0)
#define TSN(i) do {} while (0)
#define TSET(it, slot) do {} while (0)
struct Gat { uint32_t x, y, z, w, e; };
template <int X>
__device__ __forceinline__ void gat_issue(Gat& g, const RecW& k, int s, uint32_t dep) {
    const uint32_t o = acc_slot(s + 3) + dep;
    asm volatile("{.reg .b128 t; ld.relaxed.gpu.global.b128 t,[%5+%7]; mov.b128 {%0,%1,%2,%3},t; ld.relaxed.gpu.global.u32 %4,[%6+%8];}"
                 : "=r"(g.x), "=r"(g.y), "=r"(g.z), "=r"(g.w), "=r"(g.e) : "l"(gptr(k.am + o, k.ah)), "l"(gptr(k.ae + o, k.ah)), "n"(X * 32768), "n"(X * 1024) : "memory");
}
template <int X>
__device__ __forceinline__ bool gat_store(const Gat& g, const RecW& k) {
    uint32_t c;
    asm volatile("prmt.b32 %0,%1,%2,0x7632;" : "=r"(c) : "r"(g.w), "r"(g.e));
    SF;
    asm volatile("{.reg .b32 t; prmt.b32 t,%4,%6,0x5410; stmatrix.sync.aligned.m8n8.x4.trans.shared.b16 [%0+%5],{%1,%2,%3,t};}" ::"r"(k.lpw), "r"(g.x), "r"(g.y), "r"(g.z), "r"(g.w), "n"(R_M + X * XS), "r"(g.e) : "memory");
    return __all_sync(0xffffffffu, c == 0x42004200u);
}
template <int X>
__device__ __forceinline__ void gat_finish(bool ok, const RecW& k, int s) {
    if (!ok) {
        int n = s;
        while (true) {
            Gat g;
            gat_issue<X>(g, k, n, 0);
            if (gat_store<X>(g, k)) break;
            n += 4;
            if (n > 8000000) __trap();
        }
    }
}
__device__ __forceinline__ uint4 lds128o(uint32_t a, int o) { uint4 v; asm volatile("{.reg .b32 t; add.u32 t,%4,%5; ld.shared.v4.u32 {%0,%1,%2,%3},[t];}" : "=r"(v.x), "=r"(v.y), "=r"(v.z), "=r"(v.w) : "r"(a), "r"(o) : "memory"); return v; }
__device__ __forceinline__ uint4 ldsm4o(uint32_t a, int o) { uint4 v; asm volatile("{.reg .b32 t; add.u32 t,%4,%5; ldmatrix.sync.aligned.m8n8.x4.shared.b16 {%0,%1,%2,%3},[t];}" : "=r"(v.x), "=r"(v.y), "=r"(v.z), "=r"(v.w) : "r"(a), "r"(o) : "memory"); return v; }
__device__ __forceinline__ uint4 ldsm4to(uint32_t a, int o) { uint4 v; asm volatile("{.reg .b32 t; add.u32 t,%4,%5; ldmatrix.sync.aligned.m8n8.x4.trans.shared.b16 {%0,%1,%2,%3},[t];}" : "=r"(v.x), "=r"(v.y), "=r"(v.z), "=r"(v.w) : "r"(a), "r"(o) : "memory"); return v; }
__device__ __forceinline__ uint2 lds64o(uint32_t a, int o) { uint2 v; asm volatile("{.reg .b32 t; add.u32 t,%2,%3; ld.shared.v2.u32 {%0,%1},[t];}" : "=r"(v.x), "=r"(v.y) : "r"(a), "r"(o) : "memory"); return v; }
__device__ __forceinline__ void sts128o(uint32_t a, int o, uint32_t x, uint32_t y, uint32_t z, uint32_t w) { asm volatile("{.reg .b32 t; add.u32 t,%0,%5; st.shared.v4.u32 [t],{%1,%2,%3,%4};}" ::"r"(a), "r"(x), "r"(y), "r"(z), "r"(w), "r"(o) : "memory"); }
__device__ __forceinline__ void sts64o(uint32_t a, int o, uint32_t x, uint32_t y) { asm volatile("{.reg .b32 t; add.u32 t,%0,%3; st.shared.v2.u32 [t],{%1,%2};}" ::"r"(a), "r"(x), "r"(y), "r"(o) : "memory"); }
__device__ __forceinline__ uint32_t vxor(uint32_t a, uint32_t b) { uint32_t d; asm volatile("xor.b32 %0,%1,%2;" : "=r"(d) : "r"(a), "r"(b)); return d; }
#define WLD(base, i) wt[i] = lds128o(k.lpw, (base) + (i) * 4096)
template <int PASS, int X, int NP>
__device__ __forceinline__ void rec_qkv(const RecW& k, int s, const uint32_t (*wq)[4], const uint32_t (*wk)[4], uint4* wt, Gat& g2, int s2) {
    constexpr bool BWD = PASS == 2;
    float aq[4] = {0, 0, 0, 0}, ak[4] = {0, 0, 0, 0}, av[4] = {0, 0, 0, 0};
    constexpr int ma = R_M + X * XS;
    if (BWD) { TS(1); gat_finish<1>(gat_store<1>(g2, k), k, s); }
    bar_sync(NB_MF + X, 256);
    uint4 mf = ldsm4o(k.lp, ma + (BWD ? 7 : 0) * 512);
    if (BWD) TS(2); else { TS(0); TSN(13); }
#pragma unroll
    for (int ii = 0; ii < 8; ii++) {
        const int i = BWD ? 7 - ii : ii;
        const uint4 m = mf;
        if (ii < 7) mf = ldsm4o(k.lp, ma + (BWD ? i - 1 : i + 1) * 512);
        if (PASS == 1 && ii == G2I) gat_issue<1>(g2, k, s2, 0);
        SF;
#pragma unroll
        for (int hh = 0; hh < 2; hh++) {
            const int h = BWD ? 1 - hh : hh, ks = 2 * i + h;
            const uint32_t b0 = h ? m.z : m.x, b1 = h ? m.w : m.y;
            mma16(aq, wq[ks][0], wq[ks][1], wq[ks][2], wq[ks][3], b0, b1);
            mma16(ak, wk[ks][0], wk[ks][1], wk[ks][2], wk[ks][3], b0, b1);
            SF;
            mma16(av, wt[ks].x, wt[ks].y, wt[ks].z, wt[ks].w, b0, b1);
            SF;
            if (!BWD && ks + NP < 16) WLD(R_WV, ks + NP < 16 ? ks + NP : 0);
            if (BWD && ks >= NT) WLD(R_WV, ks >= NT ? ks - NT : 0);
            SF;
        }
    }
    const uint32_t ra = vadd(k.lpw, k.dp + R_REM + X * XS + (s & 1) * 6144), va = ((vshr(k.lp, 7) & 1) * 48 ^ k.lp ^ (k.vo & 64)) + (k.vo & ~64u);
    const uint32_t x0 = movm(pack2(aq[0], aq[1])), x1 = movm(pack2(aq[2], aq[3])), x2 = movm(pack2(ak[0], ak[1])), x3 = movm(pack2(ak[2], ak[3]));
    SF;
    asm volatile("stmatrix.sync.aligned.m8n8.x2.shared.b16 [%0+%3],{%1,%2};" ::"r"(va), "r"(pack2(av[0], av[1])), "r"(pack2(av[2], av[3])), "n"(R_LOC + X * XS) : "memory");
    SF;
    st_async4(ra, x0, x1, x2, x3, k.bar + X * 16);
    asm volatile("st.shared.v4.u32 [%0+%5],{%1,%2,%3,%4};" ::"r"(k.lpw), "r"(x0), "r"(x1), "r"(x2), "r"(x3), "n"(R_LOC + X * XS) : "memory");
    bar_arrive(NB_LOC + X, 320);
    SF;
    TS(BWD ? 4 : 3);
}
template <bool BWD, int X>
__device__ __forceinline__ void rec_out(const RecW& k, int s, uint4* wt, Gat& g, int s1) {
    if (BWD) { WLD(R_WO, 17 - NTO); WLD(R_WO, 16 - NTO); }
    TS(BWD ? 8 : 5);
    bar_sync(NB_O + X, 320);
    float r0[4] = {0, 0, 0, 0}, r1[4] = {0, 0, 0, 0};
    constexpr int oa = R_O + X * XS;
    uint4 bn = lds128o(k.lp, oa + (BWD ? 3 : 0) * 512);
    TS(BWD ? 9 : 6);
    uint2 il;
    uint64_t pm, pe;
#pragma unroll
    for (int ii = 0; ii < 4; ii++) {
        const int i = BWD ? 3 - ii : ii;
        const uint4 b = bn;
        if (ii < 3) bn = lds128o(k.lp, oa + (BWD ? i - 1 : i + 1) * 512);
        else { asm volatile("ld.shared.v2.u32 {%0,%1},[%2+%3];" : "=r"(il.x), "=r"(il.y) : "r"((vshr(k.ae, 2) & 3) * 8 + k.sb), "n"(R_IL + X * XS) : "memory"); pm = gptr(vadd(k.am, acc_slot(s)), k.ah); pe = gptr(vadd(k.ae, acc_slot(s)), k.ah); }
        SF;
        if (BWD && EARLY == ii + 1) { gat_issue<0>(g, k, s1 + 1, 0); SF; }
#pragma unroll
        for (int nn = 0; nn < 4; nn++) {
            const int n = BWD ? 3 - nn : nn, f = 4 * i + n, nx = BWD ? f - NTO + 2 : f + NTO - 2;
            mma16((n & 1) ? r1 : r0, wt[f].x, wt[f].y, wt[f].z, wt[f].w, n >> 1 ? b.z : b.x, n >> 1 ? b.w : b.y);
            SF;
            if (ii * 4 + nn >= 2 && nx >= 0 && nx < 16) WLD(R_WO, nx & 15);
            SF;
        }
    }
    const float i0 = __uint_as_float(il.x), i1 = __uint_as_float(il.y);
    asm volatile("red.relaxed.gpu.global.add.noftz.v4.bf16x2 [%0+%5],{%1,%2,%3,%4};" ::"l"(pm),
                 "r"(pack2(r0[0] * i0, r0[1] * i1)), "r"(pack2(r0[2] * i0, r0[3] * i1)), "r"(pack2(r1[0] * i0, r1[1] * i1)), "r"(pack2(r1[2] * i0, 1.f)), "n"(X * 32768) : "memory");
    asm volatile("red.relaxed.gpu.global.add.noftz.bf16x2 [%0+%2],%1;" ::"l"(pe), "r"(pack2(r1[3] * i1, 1.f)), "n"(X * 1024) : "memory");
    bar_arrive(NB_XG + X, 320);
    SF;
    TS(BWD ? 10 : 7);
}
__device__ __forceinline__ uint32_t pause(uint32_t v, int n) {
#pragma unroll
    for (int i = 0; i < n; i++) asm volatile("shfl.sync.bfly.b32 %0,%0,0,0x1f,0xffffffff;" : "+r"(v));
    return v;
}
template <bool DUAL, int X>
__device__ __forceinline__ void rec_step(const RecW& k, int s, int s2, const uint32_t (*wq)[4], const uint32_t (*wk)[4], uint4* wt) {
    constexpr int NP = NPD;
    uint4 wo[16];
    Gat g;
    rec_qkv<DUAL ? 1 : 0, X, NP>(k, s, wq, wk, wt, g, s2);
    if (DUAL) rec_qkv<2, 1, NP>(k, s2, wq, wk, wt, g, s2);
    uint32_t wa = k.lpw;
#pragma unroll
    for (int i = 0; i < NTO; i++) {
        wo[i] = lds128o(wa, R_WO + i * 4096);
        if (i % PACE == PACE - 1) wa = k.lpw + (wo[i].x & k.zero);
        SF;
    }
    rec_out<false, X>(k, s, wo, g, s);
    if (DUAL) { rec_out<true, 1>(k, s2, wo, g, s); if (!EARLY) gat_issue<0>(g, k, s + 1, 0); SF; }
#pragma unroll
    for (int i = 0; i < NP; i++) { WLD(R_WV, i); SF; }
    if (!DUAL) gat_issue<X>(g, k, s + 1, pause(wt[NP - 1].x & k.zero, DP1));
    TS(12);
    gat_finish<X>(gat_store<X>(g, k), k, s + 1);
    TS(11);
}

__device__ __forceinline__ void rec_fetch(const CUtensorMap* tm, uint32_t dst, int x, int y, int nx, uint32_t bar) {
#pragma unroll 1
    for (int j = 0; j < 8; j++) tma2d(dst + j * 8192, tm, x + (j / (8 / nx)) * 64, y + (j % (8 / nx)) * 64, bar);
}
__device__ __forceinline__ void rec_weights(const Params& p, uint32_t sb, int head, uint32_t rank, int w) {
    const int lane = threadIdx.x & 31, t = w & 3, WG = w >> 2;
    uint32_t wq[16][4], wk[16][4];
    const uint32_t rowo = (((lane >> 4) << 3) + (lane & 7)) * 128;
    const uint32_t woff = sb + WG * 32768 + rowo + (((2 * t + ((lane >> 3) & 1)) ^ (lane & 7)) << 4);
    const uint32_t qoff = sb + ((w & 1) ? R_STK : R_STQ) + WG * 32768 + rowo + (((2 * (t & 2) + ((lane >> 3) & 1)) ^ (lane & 7)) << 4);
    const uint32_t lw = sb + (lane ^ (lane >> 3)) * 16;
    PROF(threadIdx.x == 0, 3501);
    PROF(threadIdx.x == 0, 3502);
    mbar_wait(sb + R_BAR + RB_INIT * 8, 0);
    PROF(threadIdx.x == 0, 3503);
#pragma unroll
    for (int ks = 0; ks < 16; ks++) {
        uint4 a = ldsm4t(qoff + ks * 2048), b = ldsm4t((qoff ^ 32) + ks * 2048);
        wq[ks][0] = a.x; wq[ks][1] = a.y; wq[ks][2] = a.z; wq[ks][3] = a.w;
        wk[ks][0] = b.x; wk[ks][1] = b.y; wk[ks][2] = b.z; wk[ks][3] = b.w;
    }
    bar_sync(NB_W, 256);
#pragma unroll 4
    for (int ks = 0; ks < 16; ks++) { const uint4 a = ldsm4t(woff + R_STV + ks * 2048); sts128(lw + w * 512 + R_WV + ks * 4096, a.x, a.y, a.z, a.w); }
    bar_sync(NB_W, 256);
    if (threadIdx.x == 0) {
        mbar_expect(sb + R_BAR + RB_INIT * 8, 65536);
        rec_fetch(&p.tm[4], sb + R_STV, rank * 256, head * 128, 4, sb + R_BAR + RB_INIT * 8);
    }
    __syncwarp();
    mbar_wait(sb + R_BAR + RB_INIT * 8, 1);
#pragma unroll 4
    for (int f = 0; f < 16; f++) {
        const uint4 a = ldsm4t(sb + R_STV + (w >> 1) * 16384 + (f >> 1) * 2048 + rowo + ((((w & 1) * 4 + (f & 1) * 2 + ((lane >> 3) & 1)) ^ (lane & 7)) << 4));
        sts128(lw + w * 512 + R_WO + f * 4096, a.x, a.y, a.z, a.w);
    }
    PROF(threadIdx.x == 0, 3504);
    __syncthreads();
    cluster_sync();
    PROF(threadIdx.x == 0, 3505);
    RecW k;
    k.am = __shfl_sync(0xffffffffu, (uint32_t)(size_t)acc_base() + acc_main(rank, threadIdx.x), lane);
    k.ae = __shfl_sync(0xffffffffu, (uint32_t)(size_t)acc_base() + acc_extra(rank, threadIdx.x), lane);
    k.ah = (uint32_t)((size_t)acc_base() >> 32);
    k.sb = sb; k.zero = p.zero;

    k.dp = mapa(sb, rank ^ 1) - sb;
    k.lp = __shfl_sync(0xffffffffu, lw, lane);
    k.lpw = __shfl_sync(0xffffffffu, lw + w * 512, lane);
    k.vo = 4096 + w * 256 + (w & 1) * 64;
    k.bar = sb + k.dp + R_BAR + (RB_QK + WG) * 8;
    int it = 0;
    uint4 wt[16];
#pragma unroll
    for (int i = 0; i < NPD; i++) WLD(R_WV, i);
    gat_finish<0>(false, k, 0);
#pragma unroll 1
    for (; it < min(p.b1, p.e0); it++) { TSET(it, w == GPW ? 0 : 3); rec_step<false, 0>(k, it, it, wq, wk, wt); }
#pragma unroll 1
    for (; it < p.e0; it++) { TSET(it, w == GPW ? 0 : 3); rec_step<true, 0>(k, it, it - p.b1, wq, wk, wt); }
    if (it < p.nit) gat_finish<1>(false, k, it - p.b1);
#pragma unroll 1
    for (; it < p.nit; it++) { TSET(it, w == GPW ? 0 : 3); rec_step<false, 1>(k, it - p.b1, it - p.b1, wq, wk, wt); }
}

__device__ __forceinline__ void mma16_top(float* c, uint32_t a0, uint32_t a2, uint32_t b0, uint32_t b1) {
    asm volatile("{.reg .b32 j; mma.sync.aligned.m16n8k16.row.col.f32.bf16.bf16.f32 {%0,%1,%2,%3},{%4,j,%5,j},{%6,%7},{%0,%1,%2,%3};}"
                 : "+f"(c[0]), "+f"(c[1]), "+f"(c[2]), "+f"(c[3]) : "r"(a0), "r"(a2), "r"(b0), "r"(b1));
}
__device__ __forceinline__ void rec_load_tile(uint32_t sb, int X, int j, int s, int head, uint32_t rank) {
    const uint32_t bar = sb + R_BAR + (RB_T + X * 2 + j) * 8;
    mbar_expect1(bar, j ? 4096 : 16384);
    bulk_g2s1(sb + R_T + X * XS + j * 16384, g_qkv[X] + (size_t)(s * 32 + head) * 1536 + (j ? rank * 256 : 512), j ? 4096 : 16384, bar, POL_LAST);
}
__device__ __forceinline__ bool chunk_ready(int X, int j, int s) {
    unsigned v;
    asm volatile("ld.relaxed.gpu.global.u32 %0,[%1];" : "=r"(v) : "l"(cnt_ptr(C_QKV0 + X, (s >> 2) + j * 16)) : "memory");
    return __all_sync(0xffffffffu, v >= (256 >> j));
}
__device__ __forceinline__ uint4 hadd4(uint4 a, uint4 b) { return make_uint4(hadd2(a.x, b.x), hadd2(a.y, b.y), hadd2(a.z, b.z), hadd2(a.w, b.w)); }
struct RecH { uint32_t lw, lm, lq, lv, lu, sa, sp, xb, sb, zero, ts, tn; };
__device__ __forceinline__ void rec_publish(int X, int s) {
    asm volatile("{.reg .pred p; cp.async.bulk.wait_group 0; elect.sync _|p,0xffffffff; @p red.relaxed.gpu.global.add.u32 [%0],4;}" ::"l"(cnt_ptr(C_O0 + X, s >> 2)) : "memory");
}
__device__ __forceinline__ void rec_mattn(const RecH& k, uint32_t dp, int X, int j, int s, uint4 (*V)[4], uint4* vm, uint4* kmm) {
    const uint32_t sb = k.sb, to = R_T, lo = R_LOC, ro = R_REM + (s & 1) * 6144;
    const uint32_t bar = sb + R_BAR + (X * 2 + j) * 8;
    uint4 K[2][4];
    mbar_wait(sb + R_BAR + (RB_T + X * 2) * 8, s & 1);
    TS(1);
#pragma unroll
    for (int i = 0; i < 8; i++) K[i >> 2][i & 3] = ldsm4o(k.lm, (to + (i >> 2) * 1024 + ((i >> 1) & 1) * 4096 + (i & 1) * 512));
    asm volatile("cp.async.bulk.wait_group 0;" ::: "memory");
    bar_sync(NB_LOC + X, 320);
    fence_async_smem();
    asm volatile("{.reg .pred p; elect.sync _|p,0xffffffff; @p cp.async.bulk.shared::cluster.shared::cta.mbarrier::complete_tx::bytes [%0],[%1],1024,[%2];}"
                 ::"r"(k.xb + dp + ro + 4096), "r"(k.xb + lo + 4096), "r"(bar + dp + RB_V * 8) : "memory");
    uint4 u[4];
#pragma unroll
    for (int i = 0; i < 4; i++) u[i] = ldsm4o(k.lm, (lo + i * 512));
    TS(2);
    mbar_wait(bar + RB_QK * 8, s & 1);
    TS(3);
    float S[5][4];
#pragma unroll
    for (int i = 0; i < 5; i++) S[i][0] = S[i][1] = S[i][2] = S[i][3] = 0;
    {
        uint4 r[4];
#pragma unroll
        for (int i = 0; i < 4; i++) r[i] = ldsm4o(k.lm, (ro + i * 512));
        SF;
#pragma unroll
        for (int e = 0; e < 2; e++) {
            uint4& km = u[2 * e + 1];
            const uint32_t q0 = hadd2(u[2 * e].x, r[2 * e].x), q1 = hadd2(u[2 * e].y, r[2 * e].y);
            mma16_top(S[0], q0, q1, K[e][0].x, K[e][0].y);
            km.x = hadd2(km.x, r[2 * e + 1].x); km.y = hadd2(km.y, r[2 * e + 1].y);
            SF;
            mma16_top(S[1], q0, q1, K[e][1].x, K[e][1].y);
            const uint32_t q2 = hadd2(u[2 * e].z, r[2 * e].z), q3 = hadd2(u[2 * e].w, r[2 * e].w);
            SF;
            mma16_top(S[2], q0, q1, K[e][2].x, K[e][2].y);
            km.z = hadd2(km.z, r[2 * e + 1].z); km.w = hadd2(km.w, r[2 * e + 1].w);
            SF;
            mma16_top(S[3], q0, q1, K[e][3].x, K[e][3].y);
            mma16_top(S[4], q0, q1, km.x, km.y);
            SF;
#pragma unroll
            for (int i = 0; i < 4; i++) {
                mma16_top(S[i], q2, q3, K[e][i].z, K[e][i].w); SF;
            }
            mma16_top(S[4], q2, q3, km.z, km.w);
            SF;
        }
    }
#define VLD(a, b) _Pragma("unroll") for (int i = (a); i < (b); i++) V[i >> 2][i & 3] = ldsm4to((i & 1) ? lv2 : k.lv, (to + 8192 + (i >> 2) * 4096 + ((i >> 1) & 1) * 1024))
    const uint32_t lv2 = vxor(k.lv, 0x20), lh = k.lw - (vshr(k.lw - k.xb, 1) & 0xf8);
    VLD(0, VE);
    SF;
    const uint32_t sxr = k.sa, sxw = k.sp;
    sts128o(k.lw, sxw, __float_as_uint(S[0][0]), __float_as_uint(S[0][1]), __float_as_uint(S[1][0]), __float_as_uint(S[1][1]));
    SF;
    sts128o(k.lw, (sxw + 512), __float_as_uint(S[2][0]), __float_as_uint(S[2][1]), __float_as_uint(S[3][0]), __float_as_uint(S[3][1]));
    SF;
    sts64o(lh, (sxw + 1024), __float_as_uint(S[4][0]), __float_as_uint(S[4][1]));
    TS(4);
    bar_sync(NB_PAIR + X, 64);
    {
        const uint4 a = lds128o(k.lw, sxr), b = lds128o(k.lw, (sxr + 512));
        const uint2 c = lds64o(lh, (sxr + 1024));
        SF;
        VLD(VE, VF);
        SF;
        S[0][0] += __uint_as_float(a.x); S[0][1] += __uint_as_float(a.y); S[1][0] += __uint_as_float(a.z); S[1][1] += __uint_as_float(a.w);
        S[2][0] += __uint_as_float(b.x); S[2][1] += __uint_as_float(b.y); S[3][0] += __uint_as_float(b.z); S[3][1] += __uint_as_float(b.w);
        S[4][0] += __uint_as_float(c.x); S[4][1] += __uint_as_float(c.y);
    }
    float m = fmaxf(fmaxf(fmaxf(S[0][0], S[0][1]), fmaxf(S[1][0], S[1][1])), fmaxf(fmaxf(S[2][0], S[2][1]), fmaxf(S[3][0], S[3][1])));
    m = fmaxf(m, fmaxf(S[4][0], S[4][1]));
    m = fmaxf(m, __shfl_xor_sync(0xffffffffu, m, 1));
    const float m2 = __shfl_xor_sync(0xffffffffu, m, 2);
    SF;
    VLD(VF, 8);
    uint32_t ok;
    asm volatile("{.reg .pred p; mbarrier.test_wait.parity.shared::cta.b64 p,[%1],%2; selp.u32 %0,1,0,p;}" : "=r"(ok) : "r"(bar + RB_V * 8), "r"(s & 1) : "memory");
    uint4 vr0 = ldsm4o(k.lu, (ro + 4096)), vr1 = ldsm4o(k.lu, (ro + 4608));
    vm[0] = ldsm4o(k.lu, (lo + 4096)); vm[1] = ldsm4o(k.lu, (lo + 4608));
    SF;
    TS(5);
    m = fmaxf(m, m2) * -SC_LOG2E;
    uint32_t P[5];
#pragma unroll
    for (int i = 0; i < 5; i++) P[i] = pack2(ex2(fmaf(S[i][0], SC_LOG2E, m)), ex2(fmaf(S[i][1], SC_LOG2E, m)));
    float o[4][4], l[4] = {0, 0, 0, 0};
    const uint32_t ONE = 0x3f803f80u;
    mma16_top(l, ONE, ONE, P[0], P[1]);
#pragma unroll
    for (int t = 0; t < 4; t++) { o[t][0] = o[t][1] = o[t][2] = o[t][3] = 0; mma16(o[t], V[0][t].x, V[0][t].y, V[0][t].z, V[0][t].w, P[0], P[1]); }
    mma16_top(l, ONE, ONE, P[2], P[3]);
#pragma unroll
    for (int t = 0; t < 4; t++) mma16(o[t], V[1][t].x, V[1][t].y, V[1][t].z, V[1][t].w, P[2], P[3]);
    if (!__all_sync(0xffffffffu, ok)) {
        mbar_wait(bar + RB_V * 8, s & 1);
        vr0 = ldsm4o(k.lu, (ro + 4096)); vr1 = ldsm4o(k.lu, (ro + 4608));
    }
    TS(6);
    vm[0] = hadd4(vm[0], vr0); vm[1] = hadd4(vm[1], vr1);
    mma8(l, ONE, ONE, P[4]);
    mma8(o[0], vm[0].x, vm[0].y, P[4]); mma8(o[1], vm[0].z, vm[0].w, P[4]); mma8(o[2], vm[1].x, vm[1].y, P[4]); mma8(o[3], vm[1].z, vm[1].w, P[4]);
    asm volatile("{.reg .pred p; .reg .b32 t; setp.lt.u32 p,%0,%3; add.u32 t,%0,%4; @p st.shared.v2.f32 [t],{%1,%2};}" ::"r"(lh), "f"(rcp(l[0])), "f"(rcp(l[1])), "r"(k.xb + 32), "r"(R_IL) : "memory");
#pragma unroll
    for (int t = 0; t < 4; t += 2)
        asm volatile("{.reg .b32 t; add.u32 t,%0,%5; stmatrix.sync.aligned.m8n8.x4.trans.shared.b16 [t],{%1,%2,%3,%4};}" ::"r"(k.lm),
                     "r"(pack2(o[t][0], o[t][1])), "r"(pack2(o[t][2], o[t][3])), "r"(pack2(o[t + 1][0], o[t + 1][1])), "r"(pack2(o[t + 1][2], o[t + 1][3])), "r"(R_O - j * 1024 + t * 256) : "memory");
    bar_arrive(NB_O + X, 320);
    PROF(k.lw == k.xb, X * 64 + s);
    TS(7);
    kmm[0] = u[1]; kmm[1] = u[3];
    mbar_expect1(bar + RB_QK * 8, 2048); mbar_expect1(bar + RB_V * 8, 1024);
}
template <int MT>
__device__ __forceinline__ void rec_xattn(const RecH& k, int X, int j, int s, int head, bool early, const uint4 (*V)[4], const uint4* vmm, const uint4* kmm) {
    constexpr int NTL = 3 + 2 * MT;
    const uint32_t sb = k.sb, to = R_T;
    const uint32_t sxw = k.sa, sxr = k.sp;
    const uint32_t lq2 = vxor(k.lq, 0x20);
    float S[NTL][4];
#pragma unroll
    for (int i = 0; i < NTL; i++) S[i][0] = S[i][1] = S[i][2] = S[i][3] = 0;
    {
        uint4 q[2][2], kk[2][NTL];
#define XQ(e) q[e][0] = ldsm4o(k.lq, (to + 16384 + (e) * 1024)); q[e][1] = ldsm4o(lq2, (to + 16384 + (e) * 1024))
#define XK(e, i) kk[e][i] = ldsm4o(k.lm, (to + (e) * 1024 + (((i) - 1) >> 1) * 4096 + (((i) - 1) & 1) * 512))
        kk[0][0] = kmm[0]; kk[1][0] = kmm[1];
        if (!X) bar_sync(NB_XG, 320);
        XQ(0);
#pragma unroll
        for (int i = 1; i < NTL; i++) XK(0, i);
        SF;
#pragma unroll
        for (int i = 0; i < NTL; i++) { mma16(S[i], q[0][0].x, q[0][0].y, q[0][0].z, q[0][0].w, kk[0][i].x, kk[0][i].y); SF; }
        q[1][0] = ldsm4o(k.lq, (to + 16384 + 1024));
#pragma unroll
        for (int i = 0; i < NTL; i++) { mma16(S[i], q[0][1].x, q[0][1].y, q[0][1].z, q[0][1].w, kk[0][i].z, kk[0][i].w); SF; if (i + 1 < NTL) XK(1, i + 1); SF; }
        q[1][1] = ldsm4o(lq2, (to + 16384 + 1024));
        SF;
#pragma unroll
        for (int i = 0; i < NTL; i++) { mma16(S[i], q[1][0].x, q[1][0].y, q[1][0].z, q[1][0].w, kk[1][i].x, kk[1][i].y); SF; }
#pragma unroll
        for (int i = 0; i < NTL; i++) { mma16(S[i], q[1][1].x, q[1][1].y, q[1][1].z, q[1][1].w, kk[1][i].z, kk[1][i].w); SF; }
    }
#pragma unroll
    for (int i = 0; i < NTL; i++) sts128o(k.lw, (sxw + i * 512), __float_as_uint(S[i][0]), __float_as_uint(S[i][1]), __float_as_uint(S[i][2]), __float_as_uint(S[i][3]));
    SF;
    if (X) bar_sync(NB_XG + 1, 320); else bar_sync(NB_PAIR + 2, 64);
    TS(9);
    if (early && !X) rec_load_tile(sb, X, j, s + 1, head, MT);
#pragma unroll
    for (int i = 0; i < NTL; i++) {
        const uint4 r = lds128o(k.lw, (sxr + i * 512));
        S[i][0] += __uint_as_float(r.x); S[i][1] += __uint_as_float(r.y); S[i][2] += __uint_as_float(r.z); S[i][3] += __uint_as_float(r.w);
    }
    const int g = vshr(k.lw - k.xb, 6) & 7, c = (vshr(k.lw, 4) ^ (g >> 1)) & 3;
    const float NEG = -__int_as_float(0x7f800000);
    if (2 * c > g) { S[NTL - 2][0] = NEG; S[NTL - 1][2] = NEG; }
    if (2 * c + 1 > g) { S[NTL - 2][1] = NEG; S[NTL - 1][3] = NEG; }
    float m0 = fmaxf(S[0][0], S[0][1]), m1 = fmaxf(S[0][2], S[0][3]);
#pragma unroll
    for (int i = 1; i < NTL; i++) { if (i < NTL - 1) m0 = fmaxf(m0, fmaxf(S[i][0], S[i][1])); m1 = fmaxf(m1, fmaxf(S[i][2], S[i][3])); }
    m0 = fmaxf(m0, __shfl_xor_sync(0xffffffffu, m0, 1)); m1 = fmaxf(m1, __shfl_xor_sync(0xffffffffu, m1, 1));
    m0 = fmaxf(m0, __shfl_xor_sync(0xffffffffu, m0, 2)); m1 = fmaxf(m1, __shfl_xor_sync(0xffffffffu, m1, 2));
    m0 *= -SC_LOG2E; m1 *= -SC_LOG2E;
    uint32_t P[NTL][2];
#pragma unroll
    for (int i = 0; i < NTL; i++) {
        P[i][0] = i < NTL - 1 ? pack2(ex2(fmaf(S[i][0], SC_LOG2E, m0)), ex2(fmaf(S[i][1], SC_LOG2E, m0))) : 0u;
        P[i][1] = pack2(ex2(fmaf(S[i][2], SC_LOG2E, m1)), ex2(fmaf(S[i][3], SC_LOG2E, m1)));
    }
    float l[4] = {0, 0, 0, 0};
#pragma unroll
    for (int i = 0; i < NTL; i++) mma8(l, P[i][0], P[i][1], 0x3f803f80u);
    const float l0 = rcp(l[0]), l1 = rcp(l[2]);

#pragma unroll
    for (int e = 0; e < 2; e++) {
        const uint4 vm = vmm[e];
        uint32_t u[2][4];
#pragma unroll
        for (int n = 0; n < 4; n++) {
            float a[4] = {0, 0, 0, 0};
#pragma unroll
            for (int m = 0; m <= MT; m++) {
                const uint4 v = V[m][e * 2 + (n >> 1)];
                mma8(a, P[1 + 2 * m][0], P[1 + 2 * m][1], (n & 1) ? v.y : v.x); mma8(a, P[2 + 2 * m][0], P[2 + 2 * m][1], (n & 1) ? v.w : v.z);
            }
            mma8(a, P[0][0], P[0][1], n == 0 ? vm.x : n == 1 ? vm.y : n == 2 ? vm.z : vm.w);
            u[0][n] = pack2(a[0] * l0, a[1] * l0); u[1][n] = pack2(a[2] * l1, a[3] * l1);
        }
        sts128o(k.lw, sxr + e * 512, u[0][0], u[0][1], u[0][2], u[0][3]); sts128o(k.lw, sxr + e * 512 + 1024, u[1][0], u[1][1], u[1][2], u[1][3]);
    }
    if (early && X) rec_load_tile(sb, X, j, s + 1, head, MT);
    TS(10);
}
__device__ __forceinline__ void rec_attn(const Params& p, uint32_t sb, int X, int j, int head, uint32_t rank) {
    const int lane = threadIdx.x & 31;
    RecH k;
    k.xb = sb + X * XS + j * 1024;
    const uint32_t x2 = k.xb + j * 1024;
    k.lw = __shfl_sync(0xffffffffu, x2 + (lane ^ (lane >> 3)) * 16, lane);
    k.lm = __shfl_sync(0xffffffffu, x2 + ((lane & 7) * 4 + ((lane >> 3) ^ ((lane & 7) >> 1))) * 16, lane);
    k.lq = __shfl_sync(0xffffffffu, x2 + ((lane >> 3) & 1) * 512 + ((lane & 7) * 4 + ((lane >> 4) ^ ((lane & 7) >> 1))) * 16, lane);
    k.lv = __shfl_sync(0xffffffffu, x2 + (lane >> 4) * 512 + ((lane & 7) * 4 + (((lane >> 3) & 1) ^ ((lane & 7) >> 1))) * 16, lane);
    k.lu = __shfl_sync(0xffffffffu, k.xb + ((lane & 6) * 4 + (((lane >> 3) * 2 + (lane & 1)) ^ (lane & 6))) * 16, lane);
    k.sa = __shfl_sync(0xffffffffu, R_SX + j * 512, 0); k.sp = __shfl_sync(0xffffffffu, R_SX + 2560 - j * 4608, 0);
    k.sb = sb; k.zero = p.zero;
    const uint32_t dp = mapa(sb, rank ^ 1) - sb;
    char* zp = acc_base() + (j ? X * 32768 + acc_main(rank, head * 8) : X * 1024 + acc_extra(rank, head * 8));
    mbar_expect1(sb + R_BAR + (RB_QK + X * 2 + j) * 8, 2048); mbar_expect1(sb + R_BAR + (RB_V + X * 2 + j) * 8, 1024);
    bool early = false;
#pragma unroll 1
    for (int s = 0; s < 64; s++) {
        TSET(X ? s + p.b1 : s, j == GPJ ? 1 + X : 3);
        TS(0);
        if (!early) {
            if (!j) wait_cnt_warp(cnt_ptr(C_QKV0 + X, s >> 2), 256);
            early = !j || chunk_ready(X, 1, s);
            if (early) rec_load_tile(sb, X, j, s, head, rank);
        }
        uint4 V[2][4], vm[2], km[2];
        rec_mattn(k, dp, X, j, s, V, vm, km);
        if (!early) { wait_cnt_warp(cnt_ptr(C_QKV0 + X, (s >> 2) + 16), 128); rec_load_tile(sb, X, 1, s, head, rank); }
        early = s < 63 && ((s & 3) != 3 || chunk_ready(X, j, s + 1));
        mbar_wait(sb + R_BAR + (RB_T + X * 2 + 1) * 8, s & 1);
        if (rank) rec_xattn<1>(k, X, j, s, head, early, V, vm, km); else rec_xattn<0>(k, X, j, s, head, early, V, vm, km);
        fence_async_smem();
        __syncwarp();
        asm volatile("{.reg .pred p; elect.sync _|p,0xffffffff;\n"
                     "@p cp.async.bulk.global.shared::cta.bulk_group.L2::cache_hint [%0],[%1],2048,%2;\n"
                     "@p cp.async.bulk.global.shared::cta.bulk_group [%3],[%4],%5;\n"
                     "cp.async.bulk.commit_group;}"
                     ::"l"(g_o[X] + ((s >> 2) * 64 + head * 2 + j) * 1024 + ((s & 3) * 2 + rank) * 128), "r"(x2 + k.sp),
                       "l"((X && s < 40) ? POL_LATE : POL_SOON), "l"(zp + acc_slot(s + 2)), "r"(sb + R_Z), "r"(j ? 128 : 32) : "memory");
        if (s == 61) rec_publish(X, 64);
        if ((s & 3) == 3) {
            if (!early && s < 63 && chunk_ready(X, j, s + 1)) { rec_load_tile(sb, X, j, s + 1, head, rank); early = true; }
            rec_publish(X, s);
            PROF(lane == 0 && j, 3900 + X * 16 + (s >> 2));
        }
    }
}

__device__ __forceinline__ void rec_init(const Params& p, uint32_t sb, int head, uint32_t rank) {
    const uint32_t b = sb + R_BAR;
    const int i = threadIdx.x - 320;
    if (i >= 0 && i < RB_N) {
        mbar_init(b + i * 8, 1);
        asm volatile("fence.mbarrier_init.release.cluster;" ::: "memory");
    }
    if (i == 0) mbar_expect(b + RB_INIT * 8, 196608);
    if (i >= 0 && i < 32) sts32(sb + R_Z + i * 4, 0);
}

#define NSTGN 8
constexpr int NSTG = NSTGN, STG_B = 24576;
#define LAGH 3
constexpr int NSB = 8;
constexpr int B_OUT = NSTG * STG_B  , B_UT = B_OUT, B_YT = B_UT + 16384, B_SP = B_YT  ,
              B_ST = 229376  , B_BAR = 231936;
static_assert(B_OUT + NSB * 4096 <= B_ST && B_ST + 2048 <= B_BAR && B_YT + 10240 <= B_ST, "smem map");
enum { BB_FULL = 0, BB_EMPTY = 8, BB_SF = 16  , BB_GO = 18, BB_LOW = 19, BB_DONE = 20  , BB_IDLE = 22  , BB_N = 30 };
enum { NB_REL = 2  , NB_C = 11, NB_WG = 12  , NB_PH = 14 };

__device__ __forceinline__ void bulk_init(uint32_t sb) {
    const int i = threadIdx.x - 320;
    if (i >= 0 && i < BB_N) {
        mbar_init(sb + B_BAR + i * 8, (i >= BB_EMPTY && i < BB_EMPTY + NSTG) ? 4 : i >= BB_DONE ? 4 : 1);
        asm volatile("fence.mbarrier_init.release.cluster;" ::: "memory");
    }
}

struct Task { int type, layer, ch, a, b, c, blk; bool pair, dry; };
__device__ __forceinline__ Task task_of(uint32_t tk, uint32_t rank) {
    Task t;
    t.type = tk & 7; t.layer = (tk >> 3) & 1; t.a = (tk >> 8) & 255; t.b = (tk >> 16) & 255; t.c = (tk >> 24) & 127; t.dry = tk >> 31;
    t.pair = t.type <= T_OP && (t.c & 64);
    t.ch = ((tk >> 4) & 15) + (t.pair ? rank : 0);
    t.blk = t.type == T_QKV ? t.a + (t.pair ? 0 : rank) : 192 + (t.pair ? (t.c >> 2) & 4 : rank * 4);
    return t;
}
__device__ __forceinline__ int qkv_blk(const Task& t, int u) {
    const int v = t.blk + (t.pair ? 1 : 2 * t.c) * u;
    return 2 * (v < 64 ? v + 32 : v - 64);
}
__device__ __forceinline__ void bulk_producer(const Params& p, uint32_t sb, int cl, uint32_t rank) {
    int st = 0; uint32_t ph = 1;
    const int tag = __shfl_sync(0xffffffffu, lds32(sb + S_TAG), 0);
    bool gated = false;
#define ACQ(bytes) do { mbar_wait(sb + B_BAR + (BB_EMPTY + st) * 8, ph); mbar_expect1(sb + B_BAR + (BB_FULL + st) * 8, bytes); } while (0)
#define NEXT do { if (++st == NSTG) { st = 0; ph ^= 1; } } while (0)
#pragma unroll 1
    for (int ti = 0; ti < MAXT; ti++) {
        const Task t = task_of(p.task[list_of(cl)][ti], rank);
        const int layer = t.layer, ch = t.ch;
        if (t.type == T_END) break;
        if (t.type <= T_OP) {
            const bool qkv = t.type == T_QKV;
            const int nh = (qkv ? 8 : 2) * t.b;
            const bool halves = !qkv && (t.c & 80) == 16;
            const unsigned* dep = cnt_ptr(qkv ? (layer ? C_CV : C_ST) : C_O0 + layer, ch + (halves && !rank));
            const unsigned need = qkv ? (layer ? 32 : ch < 2 ? 0 : 16) : 512;
            const uint16_t mb = t.pair ? 3 : 1 << rank, ma = t.pair ? 1 << rank : 3;
            const int pend = min(nh, gated ? NSTG : 4);
            auto ready = [&](int h) {
                if (h < pend) {
                    unsigned v = 0;
                    if (gated) asm volatile("ld.relaxed.gpu.global.u32 %0,[%1];" : "=r"(v) : "l"(dep) : "memory");
                    return gated && __all_sync(0xffffffffu, v >= need);
                }
                if (!gated) { wait_cnt_warp(g_gate, lds32(sb + S_GATE)); gated = true; }
                if (need) wait_cnt_warp(dep, need);
                return true;
            };
            bool open = true;
            if (qkv) {
#pragma unroll 1
                while (st) { ACQ(0); NEXT; }
#pragma unroll 1
                for (int h = 0; h < nh; h++) {
                    const int blk = qkv_blk(t, h >> 3);
                    ACQ(16384 + (h < 2 ? (layer ? 8192 : 1024) : 0));
                    if (!t.pair || !rank) tma3d_mc(sb + st * STG_B, &p.t3[blk >> 6], (h & 7) * 64, blk & 63, sb + B_BAR + (BB_FULL + st) * 8, mb);
                    if (!t.pair || rank) tma3d_mc(sb + st * STG_B + 8192, &p.t3[blk >> 6], (h & 7) * 64 + 32, blk & 63, sb + B_BAR + (BB_FULL + st) * 8, mb);
                    NEXT;
                    if (open && h && ready(h + 1)) {
                        open = false;
                        const float2* sp = g_st[layer] + ch * 2048 + (need ? 0 : tag * 256);
                        bulk_g2s1(sb + 16384, sp, layer ? 8192 : 1024, sb + B_BAR + BB_FULL * 8, POL_N);
                        bulk_g2s1(sb + STG_B + 16384, sp + (layer ? 1024 : 128), layer ? 8192 : 1024, sb + B_BAR + (BB_FULL + 1) * 8, POL_N);
                    }
                }
                continue;
            }
            if (PFC && !layer && (t.c & 15) < 8) {
                const int q = (t.c & 15) * 2 + rank;
                asm volatile("{.reg .pred p; elect.sync _|p,0xffffffff; @p cp.async.bulk.prefetch.L2.global [%0],8192; @p cp.async.bulk.prefetch.L2.global [%1],%2;}"
                             ::"l"(g_xA[0] + (ch * 16 + q) * 512), "l"(g_P + q * 16 * 32 * PW), "r"((2 + (ch & 1)) * 32 * PW * 4) : "memory");
            }
            const CUtensorMap *tb = &p.t3[4 - t.pair], *ta = &p.ta[t.pair];
            const uint32_t db = sb + 8192 + (t.pair ? rank * 8192 : 0), da = sb + (t.pair ? 0 : rank * 4096);
            const int zb = (t.blk & 63) + (t.pair ? rank * 2 : 0), ya = 4096 + ((layer * 16 + ch) * 64 + t.a) * 16 + (t.pair ? 0 : rank * 8), row = t.a * 64;
            int h = 0;
            const int s0 = st;
            if (halves) mbar_expect1(sb + B_BAR + BB_LOW * 8, NSTG * 4096);
#pragma unroll 1
            for (; (halves && h < NSTG) || !ready(h); h++) { ACQ(halves ? STG_B - 4096 : STG_B); tma3d_mc(db + st * STG_B, tb, row + h * 32, zb, sb + B_BAR + (BB_FULL + st) * 8, mb); NEXT; }
#pragma unroll 1
            for (int k = 0; k < h; k++) {
                const int s2 = (s0 + k) & (NSTG - 1);
                tma2d_mc(da + s2 * STG_B, ta, (k & 1) * 256, ya + (k >> 1) * 16, sb + B_BAR + (halves && rank ? BB_LOW : BB_FULL + s2) * 8, ma, POL_LAST);
            }
#pragma unroll 1
            for (; h < nh; h++) {
                ACQ(STG_B);
                tma3d_mc(db + st * STG_B, tb, row + h * 32, zb, sb + B_BAR + (BB_FULL + st) * 8, mb);
                tma2d_mc(da + st * STG_B, ta, (h & 1) * 256, ya + (h >> 1) * 16, sb + B_BAR + (BB_FULL + st) * 8, ma, POL_LAST);
                NEXT;
            }
#pragma unroll 1
            for (h = 0; h < 4 && !layer; h++) { ACQ(0); NEXT; }
        } else if (t.type == T_CV) {
            const int q = t.a + rank;
            if (!gated) { wait_cnt_warp(g_gate, lds32(sb + S_GATE)); gated = true; }
            if (layer) {
                wait_cnt_warp(cnt_ptr(C_U, ch - 2), 32);
#pragma unroll 1
                for (int j = ch + 1; j >= 2; j--) {
                    ACQ(16 * PW * 4 + (j > 2 ? 4096 : 0));
                    bulk_g2s1(sb + st * STG_B, g_P + (((q >> 1) * 16 + j) * 2 + (q & 1)) * 16 * PW, 16 * PW * 4, sb + B_BAR + (BB_FULL + st) * 8, POL_N);
                    if (j > 2) bulk_g2s1(sb + st * STG_B + 12288, g_u + (((q >> 1) * 16 + ch + 1 - j) * 2 + (q & 1)) * 256, 4096, sb + B_BAR + (BB_FULL + st) * 8, POL_N);
                    NEXT;
                }
            } else {
#pragma unroll 1
                for (int j = min(ch, 1 + (ch & 1)); j >= 0; j--) {
                    if (j == 0 && ch >= 2) {
                        wait_cnt_warp(cnt_ptr(C_H, ch & ~1), 64);
#pragma unroll 1
                        for (int i = 0; i < ((ch & 1) || ch == 2 ? 1 : 2); i++) {
                            ACQ(16384);
                            bulk_g2s1(sb + st * STG_B, g_carry[i] + (ch * 16 + q) * 1024, 16384, sb + B_BAR + (BB_FULL + st) * 8, POL_LAST);
                            NEXT;
                        }
                    }
                    ACQ(32 * PW * 4);
                    bulk_g2s1(sb + st * STG_B, g_P + (q * 16 + j) * 32 * PW, 32 * PW * 4, sb + B_BAR + (BB_FULL + st) * 8, POL_N);
                    NEXT;
                }
            }
        }
    }
}

__device__ __forceinline__ uint4* qkv_dst(int layer, int ch, int w, int blk);
__device__ __forceinline__ uint4* op_dst(int layer, int ch, int slot, int w, uint32_t rank);
__device__ __forceinline__ uint64_t out_pol(int type, int layer, int ch) { return (type == T_QKV ? (!layer && ch > 1) : (layer && ch < 10)) ? POL_LATE : POL_SOON; }
__device__ __forceinline__ void bulk_relay(const Params& p, uint32_t sb, int cl) {
    for (int ti = 0; ti < MAXT; ti++) {
        const int type = p.task[list_of(cl)][ti] & 7;
        if (type == T_END) break;
        if (type != T_QKV) continue;
        bar_sync(NB_PH, 96);
        const uint32_t ph = lds32(sb + B_ST + 8);
#pragma unroll 1
        for (int h = 2; h < 8; h++) {
            mbar_wait(sb + B_BAR + (BB_FULL + h) * 8, ph);
            if (h == 4 || h == 7) { bar_arrive(NB_REL + (h == 7) * 2, 160); bar_arrive(NB_REL + (h == 7) * 2 + 1, 160); }
        }
    }
}
__device__ __forceinline__ void bulk_release(const Params& p, uint32_t sb, int cl, uint32_t rank, int wg) {
    int nd = 0;
    for (int ti = 0; ti < MAXT; ti++) {
        const Task t = task_of(p.task[list_of(cl)][ti], rank);
        const int type = t.type, layer = t.layer, ch = t.ch;
        if (type == T_END) break;
        if (type == T_FIN || (type == T_OP && (t.c & 32))) continue;
        if (type == T_OP && !layer) {
            mbar_wait(sb + B_BAR + (BB_DONE + wg) * 8, nd & 1);
            nd++;
            const int s0 = __shfl_sync(0xffffffffu, lds32(sb + B_ST + wg * 4), 0) + wg * 2;
            fence_async_smem();
#pragma unroll 1
            for (int w = 0; w < 4; w++)
                asm volatile("{.reg .pred p; elect.sync _|p,0xffffffff; @p cp.async.bulk.global.shared::cta.bulk_group.L2::cache_hint [%0],[%1],8192,%2; cp.async.bulk.commit_group;}"
                             ::"l"(op_dst(0, ch, t.c & 15, wg * 4 + w, rank)), "r"(sb + ((s0 + (w >> 1)) & (NSTG - 1)) * STG_B + (w & 1) * 8192), "l"(POL_SOON) : "memory");
            mbar_arrive1(sb + B_BAR + (BB_SF + wg) * 8);
            asm volatile("{.reg .pred p; elect.sync _|p,0xffffffff;\n"
                         "cp.async.bulk.wait_group 3; @p red.relaxed.gpu.global.add.u32 [%0],1; cp.async.bulk.wait_group 2; @p red.relaxed.gpu.global.add.u32 [%0+64],1;\n"
                         "cp.async.bulk.wait_group 1; @p red.relaxed.gpu.global.add.u32 [%0+128],1; cp.async.bulk.wait_group 0; @p red.relaxed.gpu.global.add.u32 [%0+192],1;}"
                         ::"l"(cnt_ptr(C_OP0 + rank * 2 + wg, ch)) : "memory");
#pragma unroll 1
            for (int i = 0; i < 8; i++) mbar_arrive1_cluster(mapa(sb + B_BAR + (BB_EMPTY + ((s0 + (i >> 2)) & (NSTG - 1))) * 8, i & 1));
            continue;
        }
#pragma unroll 1
        for (int u = 0; u < (type == T_QKV ? t.b : 1); u++) {
            const int blk = qkv_blk(t, u);
            unsigned* cnt = cnt_ptr(type == T_QKV ? C_QKV0 + layer : type == T_OP ? C_OP1 : layer ? C_H : C_CV, ch + (type == T_QKV && blk < 64 ? 16 : 0));
            const uint4* dst = type == T_QKV ? qkv_dst(layer, ch, wg * 4, blk) : op_dst(1, ch, t.c & 15, wg * 4, (t.blk >> 2) & 1) + 256;
            mbar_wait(sb + B_BAR + (BB_DONE + wg) * 8, nd & 1);
            nd++;
            if (type != T_CV) {
                fence_async_smem();
#pragma unroll
                for (int w = 0; w < 4; w++)
                    asm volatile("{.reg .pred p; elect.sync _|p,0xffffffff; @p cp.async.bulk.global.shared::cta.bulk_group.L2::cache_hint [%0],[%1],4096,%2;}"
                                 ::"l"(dst + (type == T_QKV ? (w >> 1) * 49152 + (w & 1) * 256 : w * 1024)), "r"(sb + B_OUT + (wg * 4 + w) * 4096), "l"(out_pol(type, layer, ch)) : "memory");
                asm volatile("cp.async.bulk.commit_group; cp.async.bulk.wait_group 0;" ::: "memory");
            }
            if (type != T_QKV) fence_async();
            if (!t.dry) asm volatile("{.reg .pred p; elect.sync _|p,0xffffffff; @p red.relaxed.gpu.global.add.u32 [%0],%1;}" ::"l"(cnt), "r"(type == T_QKV ? 2 : type == T_OP ? t.b : 1) : "memory");
            PROF(wg && (threadIdx.x & 31) == 0 && (type == T_CV || u + 2 == t.b), 3900 + ti);
            if (type == T_CV && !layer && !t.dry) {
                asm volatile("{.reg .pred p; elect.sync _|p,0xffffffff; @p cp.async.bulk.global.shared::cta.bulk_group [%0],[%1],4096;\n"
                             "cp.async.bulk.commit_group; cp.async.bulk.wait_group 0; @p red.relaxed.gpu.global.add.u32 [%2],1;}"
                             ::"l"(g_u + ((t.a + rank) * 16 + ch) * 512 + wg * 256), "r"(sb + B_UT + (ch & 1) * 8192 + wg * 4096), "l"(cnt_ptr(C_U, ch)) : "memory");
            }
            mbar_arrive1(sb + B_BAR + (BB_SF + wg) * 8);
        }
        PROF(wg && (threadIdx.x & 31) == 0, 3600 + ti * 4 + 3);
    }
}

__device__ __forceinline__ void stage_release(uint32_t sb, int w, int st) {
    if (!(w & 2)) mbar_arrive1_cluster(mapa(sb + B_BAR + (BB_EMPTY + st) * 8, w & 1));
}
template <bool ACC>
__device__ __forceinline__ void gemm_run(float* acc, uint32_t sb, int w, int h0, int h1, uint32_t& r0, uint32_t& r1, int& st, uint32_t& ph) {
    const uint64_t da0 = mkdesc(sb + (w >> 2) * 4096, 16, 512, 2), db0 = mkdesc(sb + 8192, 4096, 1024, 1);
    const uint32_t rel0 = mapa(sb + B_BAR + BB_EMPTY * 8, w & 1);
#pragma unroll 1
    for (int h = h0; h < h1; h++) {
        const uint64_t da = da0 + st * (STG_B >> 4), db = db0 + st * (STG_B >> 4);
        mbar_wait(sb + B_BAR + (BB_FULL + st) * 8, ph);
        if (ACC) wg_wait<1>();
        wg_fence();
        wgmma256<ACC>(acc, da, db);
        wgmma256<true>(acc, da + 2, db + 128);
        wg_commit();
        if (ACC) mbar_arrive1_cluster((w == 2 && h == LAGH - 1) ? sb + B_BAR + BB_GO * 8 : r0);
        r0 = r1;
        if (!(w & 2)) r1 = rel0 + st * 8;
        if (++st == NSTG) { st = 0; ph ^= 1; }
    }
}

__device__ __forceinline__ uint4* qkv_dst(int layer, int ch, int w, int blk) {
    return g_qkv[layer] + (size_t)((ch * 4 + (w >> 1)) * 32 + ((blk & 63) >> 1)) * 1536 + (blk >> 6) * 512 + (w & 1) * 256;
}
__device__ __forceinline__ uint4* op_dst(int layer, int ch, int slot, int w, uint32_t rank) {
    return g_pp[layer] + (size_t)(ch * MAXSPLIT + slot) * 8192 + (w * 32 + rank * 16) * 32;
}
__device__ __forceinline__ uint32_t ln2(uint32_t x, uint32_t m, uint32_t rh, uint32_t rl) {
    uint32_t d; asm volatile("{.reg .b32 t,u; sub.rn.bf16x2 t,%1,%2; mul.rn.bf16x2 u,t,%4; fma.rn.bf16x2 %0,t,%3,u;}" : "=r"(d) : "r"(x), "r"(m), "r"(rh), "r"(rl)); return d;
}
__device__ __forceinline__ void qkv_task(uint32_t sb, int w, int layer, int ch, int nu, int& ng, int& nd, uint32_t& ph, int ti, uint32_t zero) {
    constexpr int type = T_QKV;
    static_assert(NSTG == 8, "ring");
    const int lane = threadIdx.x & 31;
    const uint64_t db0 = mkdesc(sb, 4096, 1024, 1);
    const uint32_t rel = (w & 2) ? sb + B_BAR + BB_IDLE * 8 : mapa(sb + B_BAR + BB_EMPTY * 8, w & 1), full = sb + B_BAR + BB_FULL * 8;
    const uint32_t lo = sb + B_OUT + w * 4096 + (lane ^ (lane >> 3)) * 16;
    const uint4* xa = g_xA[layer] + (ch * 8 + w) * 1024 + lane;
    uint32_t m0, m1, h0, h1, l0, l1;
    uint4 A[32];
    {
        mbar_wait(full, ph);
        mbar_wait(full + 8, ph);
        CPROF(1);
        const uint32_t sa = sb + (lane >> 4) * STG_B + 16384 + (w * 16 + (lane & 15)) * 8;
        uint2 v[8];
#pragma unroll
        for (int i = 0; i < 8; i++) v[i] = lds64(sa + i * 1024 * layer);
#pragma unroll
        for (int i = 0; i < 4 * QB1; i++) A[i] = ldcg128(xa + i * 32);
        bar_sync(NB_WG + (w >> 2), 128);
        float sm = 0, M2 = 0, D = 0;
#pragma unroll
        for (int i = 0; i < 8; i++) { sm += __uint_as_float(v[i].x); M2 += __uint_as_float(v[i].y); }
        if (!layer) { sm = __uint_as_float(v[0].x); M2 = __uint_as_float(v[0].y); }
        sm += __shfl_xor_sync(0xffffffffu, sm, 16);
#pragma unroll
        for (int i = 0; i < 8; i++) { const float d = __uint_as_float(v[i].x) * (1.f / 32.f) - sm * (1.f / 512.f); D += 32.f * d * d; }
        M2 += layer ? D : sm * sm * (-1.f / 1024.f);
        M2 = fmaxf(M2 + __shfl_xor_sync(0xffffffffu, M2, 16), 0.f);
        const float2 o = ln_finish(sm * (1.f / 512.f), M2 * (1.f / 512.f));
        const float r = rcp(o.y), rh = rbf(r);
        const uint32_t mm = pack2(o.x, o.x), hl = pack2(r - rh, rh);
        m0 = __shfl_sync(0xffffffffu, mm, lane >> 2); m1 = __shfl_sync(0xffffffffu, mm, (lane >> 2) + 8);
        l0 = __shfl_sync(0xffffffffu, hl, lane >> 2); l1 = __shfl_sync(0xffffffffu, hl, (lane >> 2) + 8);
        h0 = __byte_perm(l0, 0, 0x3232); h1 = __byte_perm(l1, 0, 0x3232); l0 = __byte_perm(l0, 0, 0x1010); l1 = __byte_perm(l1, 0, 0x1010);
    }
    float acc[64];
#define QNRM(i) A[i] = make_uint4(ln2(A[i].x, m0, h0, l0), ln2(A[i].y, m1, h1, l1), ln2(A[i].z, m0, h0, l0), ln2(A[i].w, m1, h1, l1))
#pragma unroll
    for (int h = 0; h < 8; h++) {
        const uint64_t db = db0 + h * (STG_B >> 4);
        const int b0 = h == 0 ? QB1 : h == QB1 ? QB2 : h == QB2 ? QB3 : 8, b1 = h == 0 ? QB2 : h == QB1 ? QB3 : 8;
        if (b0 < b1) {
            const uint4* xb = xa + (A[4 * b0 - 1].x & zero);
#pragma unroll
            for (int i = 4 * b0; i < 4 * b1; i++) A[i] = ldcg128(xb + i * 32);
            bar_sync(NB_WG + (w >> 2), 128);
        }
        QNRM(4 * h); QNRM(4 * h + 1); QNRM(4 * h + 2); QNRM(4 * h + 3);
        if (h == 2 || h == 5) bar_sync(NB_REL + (h == 5) * 2 + (w >> 2), 160);
        if (h) wg_wait<1>();
        wg_fence();
        if (h) wgmma128r<true>(acc, A[4 * h], db); else wgmma128r<false>(acc, A[0], db);
        wgmma128r<true>(acc, A[4 * h + 1], db + 128);
        wgmma128r<true>(acc, A[4 * h + 2], db + 512);
        wgmma128r<true>(acc, A[4 * h + 3], db + 640);
        wg_commit();
        if (h >= 2) mbar_arrive1_cluster(rel + (h - 2) * 8);
    }
    ph ^= 1;
#pragma unroll 1
    for (int u = 1;; u++) {
        mbar_wait(sb + B_BAR + (BB_SF + (w >> 2)) * 8, (nd & 1) ^ 1);
        if (u < nu) mbar_wait(full, ph);
        wg_wait<1>();
        mbar_arrive1_cluster(rel + 48);
        wg_wait<0>();
        mbar_arrive1_cluster(rel + 56);
        uint4 o[8];
#pragma unroll
        for (int n = 0; n < 8; n++) {
            const float* a = acc + (n >> 1) * 16 + (n & 1) * 2;
            o[n] = make_uint4(pack2(a[0], a[1]), pack2(a[4], a[5]), pack2(a[8], a[9]), pack2(a[12], a[13]));
            sts128(lo + n * 512, o[n].x, o[n].y, o[n].z, o[n].w);
        }
        __syncwarp();
        mbar_arrive1(sb + B_BAR + (BB_DONE + (w >> 2)) * 8);
        nd++;
        CPROF(min(2 + u, 7));
        if (u == nu) break;
        if (LAGQ) { if (w >> 2) mbar_wait(sb + B_BAR + BB_GO * 8, ng & 1); ng++; }
        const uint64_t db1 = mkdesc(sb + (u >> 10), 4096, 1024, 1);
#pragma unroll
        for (int h = 0; h < 8; h++) {
            const uint64_t db = db1 + h * (STG_B >> 4);
            if (h) { mbar_wait(full + h * 8, ph); wg_wait<1>(); }
            wg_fence();
            if (h) wgmma128r<true>(acc, A[4 * h], db); else wgmma128r<false>(acc, A[0], db);
            wgmma128r<true>(acc, A[4 * h + 1], db + 128);
            wgmma128r<true>(acc, A[4 * h + 2], db + 512);
            wgmma128r<true>(acc, A[4 * h + 3], db + 640);
            wg_commit();
            if (h >= 2) mbar_arrive1_cluster(rel + (h - 2) * 8);
            if (h == LAGQ - 1 && w == 2) mbar_arrive1(sb + B_BAR + BB_GO * 8);
        }
        ph ^= 1;
    }
}

template <int NB>
__device__ __forceinline__ void load_resid(uint32_t* r, int layer, int ch, int w, int cb) {
#pragma unroll
    for (int i = 0; i < NB; i++) {
        const uint4 v = ldcg128(g_xA[layer] + ((ch * 8 + w) * 32 + cb + i) * 32 + (threadIdx.x & 31));
        r[4 * i] = v.x; r[4 * i + 1] = v.y; r[4 * i + 2] = v.z; r[4 * i + 3] = v.w;
    }
}
template <int NS>
__device__ __forceinline__ void part_load(uint4* v, int layer, int ch, int w, int cb, int ns) {
    const uint4* src = g_pp[layer] + (size_t)ch * MAXSPLIT * 8192 + (w * 32 + cb) * 32 + (threadIdx.x & 31);
#pragma unroll
    for (int i = 0; i < 2 * NS; i++) {
        asm volatile("{.reg .pred p; .reg .b128 t; setp.gt.s32 p,%6,0; mov.b128 t,{0,0,0,0}; @p ld.relaxed.gpu.global.L2::cache_hint.b128 t,[%4],%5; mov.b128 {%0,%1,%2,%3},t;}"
                     : "=r"(v[i].x), "=r"(v[i].y), "=r"(v[i].z), "=r"(v[i].w) : "l"(src + (i / NS) * 32 + (i % NS) * 8192), "l"(POL_LAST), "r"(ns - i % NS) : "memory");
    }
}
template <int NS>
__device__ __forceinline__ void part_sum(float* x, const uint4* v, const uint32_t* r) {
    const int dg = ((threadIdx.x & 31) >> 2) - 2 * (threadIdx.x & 3);
    const uint32_t idm = dg == 0 ? 0x00003f80u : dg == 1 ? 0x3f800000u : 0u;
#pragma unroll
    for (int b = 0; b < 2; b++) {
        float* y = x + b * 8;
#pragma unroll
        for (int i = 0; i < 8; i++) y[i] = 0;
#pragma unroll
        for (int s = 0; s < NS; s++) { mma8(y, v[b * NS + s].x, v[b * NS + s].y, idm); mma8(y + 4, v[b * NS + s].z, v[b * NS + s].w, idm); }
#pragma unroll
        for (int i = 0; i < 4; i++) { y[2 * i] = rbf(rbf(y[2 * i]) + blo(r[b * 4 + i])); y[2 * i + 1] = rbf(rbf(y[2 * i + 1]) + bhi(r[b * 4 + i])); }
    }
}

__device__ __forceinline__ float4 row_stats32(const float* x) {
    float a = (x[0] + x[1]) + (x[4] + x[5]) + (x[8] + x[9]) + (x[12] + x[13]);
    float b = (x[2] + x[3]) + (x[6] + x[7]) + (x[10] + x[11]) + (x[14] + x[15]);
    a += __shfl_xor_sync(0xffffffffu, a, 1); b += __shfl_xor_sync(0xffffffffu, b, 1);
    a += __shfl_xor_sync(0xffffffffu, a, 2); b += __shfl_xor_sync(0xffffffffu, b, 2);
    const float ma = a * (1.f / 32.f), mb = b * (1.f / 32.f);
    float qa = 0, qb = 0;
#pragma unroll
    for (int i = 0; i < 4; i++) {
        float d0 = x[4 * i] - ma, d1 = x[4 * i + 1] - ma, d2 = x[4 * i + 2] - mb, d3 = x[4 * i + 3] - mb;
        qa += d0 * d0 + d1 * d1; qb += d2 * d2 + d3 * d3;
    }
    qa += __shfl_xor_sync(0xffffffffu, qa, 1); qb += __shfl_xor_sync(0xffffffffu, qb, 1);
    qa += __shfl_xor_sync(0xffffffffu, qa, 2); qb += __shfl_xor_sync(0xffffffffu, qb, 2);
    return make_float4(a, qa, b, qb);
}

__device__ __forceinline__ void conv_stage(float* Y, uint32_t pbase, uint32_t ubase) {
    const int lane = threadIdx.x & 31, w = threadIdx.x >> 5, g = lane >> 2, c = lane & 3;
#pragma unroll
    for (int cp = 0; cp < 2; cp++) {
        const int chl = w * 4 + cp * 2 + (lane >> 4);
        const uint4 b = ldsm4(ubase + chl * 256 + ((lane >> 3) & 1) * 128 + (((lane & 7) ^ (chl & 7)) << 4));
#pragma unroll
        for (int h = 0; h < 2; h++) {
            const uint32_t pa = pbase + ((w * 4 + cp * 2 + h) * PW + 16 + g - 2 * c) * 4;
            uint32_t lo = lds32(pa - 32);
#pragma unroll
            for (int d = 0; d < 8; d++) {
                const uint32_t a0 = lds32(pa + d * 64), a1 = lds32(pa + d * 64 + 32);
                mma16(Y + ((cp * 2 + h) * 8 + d) * 4, a0, a1, lo, a0, h ? b.z : b.x, h ? b.w : b.y);
                lo = a1;
            }
        }
    }
}

__device__ __forceinline__ void conv_combine(const float* y8, float* cur, float* nxt) {
    const int lane = threadIdx.x & 31, c = lane & 3;
    cur[0] = y8[0]; cur[1] = y8[1] + y8[4]; cur[2] = y8[2]; cur[3] = y8[3] + y8[6];
    nxt[0] = y8[29]; nxt[1] = 0.f; nxt[2] = y8[31]; nxt[3] = 0.f;
#pragma unroll
    for (int e = 1; e < 4; e++) {
        const int src = (lane & ~3) | ((c - e) & 3);
        const float v0 = __shfl_sync(0xffffffffu, y8[8 * e] + y8[8 * e - 3], src), v1 = __shfl_sync(0xffffffffu, y8[8 * e + 1] + y8[8 * e + 4], src);
        const float v2 = __shfl_sync(0xffffffffu, y8[8 * e + 2] + y8[8 * e - 1], src), v3 = __shfl_sync(0xffffffffu, y8[8 * e + 3] + y8[8 * e + 6], src);
        if (c >= e) { cur[0] += v0; cur[1] += v1; cur[2] += v2; cur[3] += v3; }
        else { nxt[0] += v0; nxt[1] += v1; nxt[2] += v2; nxt[3] += v3; }
    }
}

__device__ __forceinline__ void hist_task(float* Y, uint32_t sb, int w, int ch, int q, int& st, uint32_t& ph, int nd) {
    const int lane = threadIdx.x & 31, chl = w * 2 + (lane >> 4);
    const uint32_t ua = sb + 12288 + chl * 256 + ((lane >> 3) & 1) * 128 + (((lane & 7) ^ (chl & 7)) << 4);
    const uint32_t pa = sb + (w * 2 * PW + 16 + (lane >> 2) - 2 * (lane & 3)) * 4;
#pragma unroll
    for (int i = 0; i < 128; i++) Y[i] = 0;
    uint4 b1 = make_uint4(0, 0, 0, 0);
#pragma unroll 1
    for (int j = ch + 1; j >= 2; j--) {
        const uint4 b0 = b1;
        mbar_wait(sb + B_BAR + (BB_FULL + st) * 8, ph);
        b1 = ldsm4(ua + st * STG_B);
        if (j == 2) b1 = make_uint4(0, 0, 0, 0);
#pragma unroll
        for (int h = 0; h < 2; h++) {
            const uint32_t o = pa + st * STG_B + h * PW * 4;
            uint32_t lo = lds32(o - 32);
#pragma unroll
            for (int d = 0; d < 8; d++) {
                const uint32_t a0 = lds32(o + d * 64), a1 = lds32(o + d * 64 + 32);
                mma16(Y + (h * 16 + d) * 4, a0, a1, lo, a0, h ? b0.z : b0.x, h ? b0.w : b0.y);
                mma16(Y + (h * 16 + 8 + d) * 4, a0, a1, lo, a0, h ? b1.z : b1.x, h ? b1.w : b1.y);
                lo = a1;
            }
        }
        bar_sync(NB_WG + (w >> 2), 128);
        stage_release(sb, w, st);
        if (++st == NSTG) { st = 0; ph ^= 1; }
    }
    mbar_wait(sb + B_BAR + (BB_SF + (w >> 2)) * 8, (nd & 1) ^ 1);
#pragma unroll
    for (int h = 0; h < 2; h++) {
        const int o = ((ch * 16 + (q >> 1)) * 4 + (w & 1) * 2 + h) * 256 + ((q & 1) * 4 + (w >> 1)) * 32 + lane;
        float c0[4], n0[4], c1[4], n1[4];
        conv_combine(Y + h * 64, c0, n0); conv_combine(Y + h * 64 + 32, c1, n1);
        g_carry[0][o] = make_float4(c0[0], c0[1], c0[2], c0[3]);
        g_carry[0][o + 16384] = make_float4(c1[0] + n0[0], c1[1] + n0[1], c1[2] + n0[2], c1[3] + n0[3]);
        g_carry[1][o + 32768] = make_float4(n1[0], n1[1], n1[2], n1[3]);
    }
}

__device__ __forceinline__ void conv_task(const Params& p, float* Y, uint32_t sb, int w, int ch, int q, int ns, bool dry, int& st, uint32_t& ph, int nd) {
    const int tid = threadIdx.x, lane = tid & 31, g = lane >> 2, c = lane & 3;
    uint32_t dk[4];
    const uint32_t sg = (~ch & 2) << 30;
    int sr = st;
    float x[16];
    PROF(tid == 128, 2048 + ch * 8);
#pragma unroll
    for (int i = 0; i < 128; i++) Y[i] = 0;
#pragma unroll 1
    for (int j = min(ch, 1 + (ch & 1)); j >= 1; j--) {
        mbar_wait(sb + B_BAR + (BB_FULL + st) * 8, ph);
        conv_stage(Y, sb + st * STG_B, sb + B_UT + ((ch - j) & 1) * 8192);
        if (++st == NSTG) { st = 0; ph ^= 1; }
    }
#define CONV_CARRY _Pragma("unroll 1") \
    for (int i = 0; i < min(ch, (ch & 1) ? 2 : 3); i++) { \
        if (i) mbar_wait(sb + B_BAR + (BB_FULL + st) * 8, ph); \
        const uint32_t ca = sb + (i ? st * STG_B : B_SP) + tid * 16; \
_Pragma("unroll") \
        for (int k = 0; k < 4; k++) { \
            const uint4 cr = lds128(ca + k * 4096); \
            Y[k * 32] += __uint_as_float(cr.x); Y[k * 32 + 1] += __uint_as_float(cr.y); Y[k * 32 + 2] += __uint_as_float(cr.z); Y[k * 32 + 3] += __uint_as_float(cr.w); \
        } \
        if (i && ++st == NSTG) { st = 0; ph ^= 1; } \
    } \
    bar_sync(NB_C, 256); \
_Pragma("unroll 1") \
    for (; sr != st; sr = (sr + 1) & (NSTG - 1)) stage_release(sb, w, sr); \
    mbar_wait(sb + B_BAR + (BB_SF + (w >> 2)) * 8, (nd & 1) ^ 1); \
    mbar_wait(sb + B_BAR + (BB_SF + 1 - (w >> 2)) * 8, (nd & 1) ^ 1);
    const uint32_t ut = sb + B_UT + (ch & 1) * 8192;
    if (CPOS == 0) { CONV_CARRY }
    PROF(tid == 128, 2048 + ch * 8 + 7);
    {
        uint4 v[2 * OPS1];
        wait_cnt_warp(cnt_ptr(C_OP0 + (q >> 3) * 2 + (w >> 2), ch + (w & 3) * 16), ns);
        part_load<OPS1>(v, 0, ch, w, 2 * q, ns);
        uint32_t rs[8];
        load_resid<2>(rs, 0, ch, w, 2 * q);
        if (CPOS == 1) { CONV_CARRY }
        part_sum<OPS1>(x, v, rs);
        const float4 s = row_stats32(x);
        float2* dst = g_st2 + ((ch & 1) * 16 + q) * 128 + w * 16 + g + c * 8;
        asm volatile("{.reg .pred p; setp.ne.u32 p,%2,0; @p st.relaxed.gpu.global.b64 [%0],%1;}" ::"l"(dst),
                     "l"(((uint64_t)((__float_as_uint(c ? s.w : s.y) & 0x7fffffffu) | sg) << 32) | __float_as_uint(c ? s.z : s.x)), "r"((uint32_t)(c < 2 && !dry)) : "memory");
        PROF(tid == 128, 2048 + ch * 8 + 1);
    }
#pragma unroll
    for (int i = 0; i < 4; i++) asm volatile("ld.global.nc.u32 %0,[%1];" : "=r"(dk[i]) : "l"(p.Dskip + q * 32 + i * 8 + 2 * c));
    if (CPOS == 2) { CONV_CARRY }
    float2 ln0, ln1;
    {
        const float2* src = g_st2 + ((ch & 1) * 16 + (lane >> 4) * 8) * 128 + w * 16 + (lane & 15);
        uint64_t v[8];
        int n = 0;
#pragma unroll
        for (int i = 0; i < 8; i++) v[i] = (uint64_t)~sg << 32;
        while (true) {
            bool bad = false;
#pragma unroll
            for (int i = 0; i < 8; i++) asm volatile("{.reg .pred p; setp.lt.s32 p,%2,0; @p ld.relaxed.gpu.global.b64 %0,[%1];}" : "+l"(v[i]) : "l"(src + i * 128), "r"((uint32_t)(v[i] >> 32) ^ sg) : "memory");
#pragma unroll
            for (int i = 0; i < 8; i++) bad = bad || (int)((uint32_t)(v[i] >> 32) ^ sg) < 0;
            if (!__any_sync(0xffffffffu, bad && !dry)) break;
            if (++n > 2000000) __trap();
        }
        float sm = 0;
#pragma unroll
        for (int i = 0; i < 8; i++) sm += __uint_as_float((uint32_t)v[i]);
        sm += __shfl_xor_sync(0xffffffffu, sm, 16);
        const float mean = sm * (1.f / 512.f);
        float M2 = 0;
#pragma unroll
        for (int i = 0; i < 8; i++) { const float d = __uint_as_float((uint32_t)v[i]) * (1.f / 32.f) - mean; M2 += fabsf(__uint_as_float((uint32_t)(v[i] >> 32))) + 32.f * d * d; }
        M2 += __shfl_xor_sync(0xffffffffu, M2, 16);
        const float2 o = ln_finish(mean, M2 * (1.f / 512.f));
        ln0.x = __shfl_sync(0xffffffffu, o.x, g); ln0.y = __shfl_sync(0xffffffffu, o.y, g);
        ln1.x = __shfl_sync(0xffffffffu, o.x, g + 8); ln1.y = __shfl_sync(0xffffffffu, o.y, g + 8);
    }
    PROF(tid == 128, 2048 + ch * 8 + 2);
    uint32_t u[8];
#pragma unroll
    for (int i = 0; i < 8; i++) {
        const float2 l = (i & 1) ? ln1 : ln0;
        u[i] = pack2(__fdividef(rbf(x[2 * i] - l.x), l.y), __fdividef(rbf(x[2 * i + 1] - l.x), l.y));
        const int chl = (i >> 1) * 8 + g;
        sts32(ut + chl * 256 + (i & 1) * 128 + ((w ^ g) << 4) + c * 4, movm(u[i]));
    }
    bar_sync(NB_C, 256);
    mbar_wait(sb + B_BAR + (BB_FULL + st) * 8, ph);
    PROF(tid == 128, 2048 + ch * 8 + 3);
    conv_stage(Y, sb + st * STG_B, ut);
    uint32_t yp[4][2];
    float nxt[4][4];
    {
        float y[4][4];
#pragma unroll
        for (int k = 0; k < 4; k++) conv_combine(Y + k * 32, y[k], nxt[k]);
#pragma unroll
        for (int i = 0; i < 4; i++) { yp[i][0] = pack2(y[0][i], y[1][i]); yp[i][1] = pack2(y[2][i], y[3][i]); }
    }
#pragma unroll
    for (int i = 0; i < 4; i++) sts64(sb + B_YT + (16 * (2 * c + (i & 1)) + g + (i >> 1) * 8) * 80 + w * 8, yp[i][0], yp[i][1]);
    bar_sync(NB_C, 256);
    stage_release(sb, w, st);
    if (++st == NSTG) { st = 0; ph ^= 1; }
    PROF(tid == 128, 2048 + ch * 8 + 4);
    uint32_t xo[8];
    uint4* dA = g_xA[1] + ((ch * 8 + w) * 32 + 2 * q) * 32 + lane;
#pragma unroll
    for (int i = 0; i < 8; i++) {
        const int col = (i >> 1) * 8 + 2 * c;
        const uint32_t yv = lds32(sb + B_YT + (w * 16 + g + (i & 1) * 8) * 80 + col * 2);
        const uint32_t dv = dk[i >> 1];
        x[2 * i] = rbf(x[2 * i] + rbf(blo(yv) + rbf(blo(u[i]) * blo(dv))));
        x[2 * i + 1] = rbf(x[2 * i + 1] + rbf(bhi(yv) + rbf(bhi(u[i]) * bhi(dv))));
        xo[i] = pack2(x[2 * i], x[2 * i + 1]);
        if ((i & 3) == 3) dA[(i >> 2) * 32] = make_uint4(xo[i - 3], xo[i - 2], xo[i - 1], xo[i]);
    }
    {
        const float4 s = row_stats32(x);
        float2* dst = g_st[1] + (ch * 16 + q) * 128 + w * 16 + g;
        if (c == 0) dst[0] = make_float2(s.x, s.y);
        if (c == 1) dst[8] = make_float2(s.z, s.w);
        __syncwarp();
    }
    PROF(tid == 128, 2048 + ch * 8 + 5);
    mbar_arrive1(sb + B_BAR + (BB_DONE + (w >> 2)) * 8);
    bar_sync(NB_C, 256);
#pragma unroll
    for (int k = 0; k < 4; k++) sts128(sb + B_SP + k * 4096 + tid * 16, __float_as_uint(nxt[k][0]), __float_as_uint(nxt[k][1]), __float_as_uint(nxt[k][2]), __float_as_uint(nxt[k][3]));
    PROF(tid == 128, 2048 + ch * 8 + 6);
}

__device__ __forceinline__ void out_store(const Params& p, const float* x, int ch, int cb, bool on) {
    const int lane = threadIdx.x & 31, w = threadIdx.x >> 5, g = lane >> 2, c = lane & 3;
#pragma unroll
    for (int h = 0; h < 2; h++) {
        const float* y = x + h * 2;
        uint32_t v0 = pack2(y[0], y[1]), v1 = pack2(y[4], y[5]), v2 = pack2(y[8], y[9]), v3 = pack2(y[12], y[13]);
        uint32_t t0 = (c & 1) ? v0 : v1, t1 = (c & 1) ? v2 : v3;
        t0 = __shfl_xor_sync(0xffffffffu, t0, 1); t1 = __shfl_xor_sync(0xffffffffu, t1, 1);
        if (c & 1) { v0 = t0; v2 = t1; } else { v1 = t0; v3 = t1; }
        t0 = (c & 2) ? v0 : v2; t1 = (c & 2) ? v1 : v3;
        t0 = __shfl_xor_sync(0xffffffffu, t0, 2); t1 = __shfl_xor_sync(0xffffffffu, t1, 2);
        if (c & 2) { v0 = t0; v1 = t1; } else { v2 = t0; v3 = t1; }
        asm volatile("{.reg .pred p; setp.ne.u32 p,%6,0; @p st.global.L2::cache_hint.v4.u32 [%0],{%1,%2,%3,%4},%5;}"
                     ::"l"(p.out + (size_t)(ch * 128 + w * 16 + g + h * 8) * 512 + cb * 16 + c * 8), "r"(v0), "r"(v1), "r"(v2), "r"(v3), "l"(POL_LATE), "r"((uint32_t)on));
    }
}
__device__ __forceinline__ void fin_task(const Params& p, int ch, int cb0, int ncb, int ns, bool dry) {
    const int w = threadIdx.x >> 5;
    uint32_t rs[8];
    wait_cnt_warp(cnt_ptr(C_CV, ch), 32);
    load_resid<2>(rs, 1, ch, w, cb0);
    wait_cnt_warp(cnt_ptr(C_OP1, ch), dry ? 0 : 256);
    for (int cb = cb0; cb < cb0 + ncb; cb += 2) {
        float x[16];
        if (cb != cb0) load_resid<2>(rs, 1, ch, w, cb);
        uint4 v[32];
        part_load<16>(v, 1, ch, w, cb, ns);
        part_sum<16>(x, v, rs);
        out_store(p, x, ch, cb, !dry);
    }
}

__device__ __forceinline__ void bulk_consumer(const Params& p, uint32_t sb, int cl, uint32_t rank, int w) {
    int st = 0; uint32_t ph = 0; int nd = 0, ng = 0;
    for (int ti = 0; ti < MAXT; ti++) {
        const Task t = task_of(p.task[list_of(cl)][ti], rank);
        const int type = t.type, layer = t.layer, ch = t.ch;
        if (type == T_END) break;
        bool staged = type != T_FIN;
        PROF(threadIdx.x == 0, 3600 + ti * 4);
        CPROF(0);
        if (type == T_QKV) {
            staged = false;
            #pragma unroll 1
            while (st) {
                if (!(w & 3)) { mbar_wait(sb + B_BAR + (BB_FULL + st) * 8, ph); stage_release(sb, 0, st); stage_release(sb, 1, st); }
                if (++st == NSTG) { st = 0; ph ^= 1; }
            }
            if (!(w & 3)) { sts32(sb + B_ST + 8, ph); bar_arrive(NB_PH, 96); }
            qkv_task(sb, w, layer, ch, t.b, ng, nd, ph, ti, p.zero);
            PROF(threadIdx.x == 128, 3600 + ti * 4 + 1);
        } else if (type == T_OP) {
            const int lane = threadIdx.x & 31;
            float acc[128];
            uint32_t r0 = sb + B_BAR + BB_IDLE * 8, r1 = r0;
            if (w >> 2) { mbar_wait(sb + B_BAR + BB_GO * 8, ng & 1); if ((t.c & 80) == 16) mbar_wait(sb + B_BAR + BB_LOW * 8, 0); }
            ng++;
            gemm_run<false>(acc, sb, w, 0, 1, r0, r1, st, ph);
            gemm_run<true>(acc, sb, w, 1, 2 * t.b, r0, r1, st, ph);
            mbar_wait(sb + B_BAR + (BB_SF + (w >> 2)) * 8, (nd & 1) ^ 1);
            wg_wait<1>();
            mbar_arrive1_cluster(r0);
            wg_wait<0>();
            mbar_arrive1_cluster(r1);
            PROF(threadIdx.x == 128, 3600 + ti * 4 + 1);
            if (t.c & 32) {
                staged = false;
                const int dg = (lane >> 2) - 2 * (lane & 3);
                const uint32_t idm = dg == 0 ? 0x00003f80u : dg == 1 ? 0x3f800000u : 0u;
                wait_cnt_warp(cnt_ptr(C_OP1, ch), 256 - 4 * t.b);
#pragma unroll 1
                for (int i = 0; i < (t.c & 15); i++) {
                    const uint4* src = op_dst(1, ch, i, w, (t.blk >> 2) & 1) + lane;
                    uint4 v[16];
#pragma unroll
                    for (int j = 0; j < 16; j++) v[j] = ldcg128_last(src + j * 32);
#pragma unroll
                    for (int j = 0; j < 16; j++) { mma8(acc + j * 8, v[j].x, v[j].y, idm); mma8(acc + j * 8 + 4, v[j].z, v[j].w, idm); }
                }
#pragma unroll
                for (int j = 0; j < 16; j += 4) {
                    uint32_t rs[16];
                    load_resid<4>(rs, 1, ch, w, (t.blk & 4) * 4 + j);
#pragma unroll
                    for (int i = 0; i < 16; i++) { float* y = acc + j * 8 + 2 * i; y[0] = rbf(y[0]) + blo(rs[i]); y[1] = rbf(y[1]) + bhi(rs[i]); }
                    out_store(p, acc + j * 8, ch, (t.blk & 4) * 4 + j, true); out_store(p, acc + j * 8 + 16, ch, (t.blk & 4) * 4 + j + 2, true);
                }
            } else if (!layer) {
                const int s2 = st + (w >> 1);
                const uint32_t o = sb + (s2 & (NSTG - 1)) * STG_B + (w & 1) * 8192 + lane * 16;
                mbar_wait(sb + B_BAR + (BB_FULL + (s2 & (NSTG - 1))) * 8, ph ^ (s2 >= NSTG));
#pragma unroll
                for (int j = 0; j < 16; j++)
                    sts128(o + j * 512, pack2(acc[j * 8], acc[j * 8 + 1]), pack2(acc[j * 8 + 2], acc[j * 8 + 3]), pack2(acc[j * 8 + 4], acc[j * 8 + 5]), pack2(acc[j * 8 + 6], acc[j * 8 + 7]));
                sts32(sb + B_ST + (w >> 2) * 4, st);
                st += 4;
                if (st >= NSTG) { st -= NSTG; ph ^= 1; }
            } else {
                uint4* dst = op_dst(layer, ch, t.c & 15, w, (t.blk >> 2) & 1) + lane;
#pragma unroll
                for (int n = 0; n < 16; n++) {
                    const int j = (n >> 1) + (n & 1) * 8;
                    const uint4 v = make_uint4(pack2(acc[j * 8], acc[j * 8 + 1]), pack2(acc[j * 8 + 2], acc[j * 8 + 3]), pack2(acc[j * 8 + 4], acc[j * 8 + 5]), pack2(acc[j * 8 + 6], acc[j * 8 + 7]));
                    if (j < 16 - NSB) stg128(dst + j * 32, v, out_pol(T_OP, layer, ch)); else sts128(sb + B_OUT + (w * NSB + j - (16 - NSB)) * 512 + lane * 16, v.x, v.y, v.z, v.w);
                }
            }
        } else if (type == T_CV) {
            float acc[128];
            if (layer) hist_task(acc, sb, w, ch, t.a + rank, st, ph, nd);
            else { conv_task(p, acc, sb, w, ch, t.a + rank, t.b, t.dry, st, ph, nd); staged = false; nd++; }
        } else {
            fin_task(p, ch, t.a + rank * t.c, t.c, t.b, t.dry);
        }
        if (staged) {
            __syncwarp();
            mbar_arrive1(sb + B_BAR + (BB_DONE + (w >> 2)) * 8);
            nd++;
        }
        PROF(threadIdx.x == 128, 3600 + ti * 4 + 2);
        __syncwarp();
    }
}

constexpr int P_Y = 131072  , P_PRM = P_Y  , P_K6 = P_PRM + 8192  ,
              P_P = P_Y + 40960  , P_U = P_P + 33280  , P_END = P_U + 17408, P_X = 98304  ;
static_assert(P_END <= B_BAR && P_END <= R_BAR, "prologue scratch");
#define KGUN 2
constexpr int KGU = KGUN;
__device__ __forceinline__ void csq(float& r, float& i) { const float t = r * i; r = fmaf(r, r, -(i * i)); i = t + t; }
__device__ __forceinline__ void cpow(float ar, float ph, float p, float& r, float& i) {
    const float e = ex2(ar * p);
    const float u = ph * p, n = fabsf(u) < 4194304.f ? (u + 12582912.f) - 12582912.f : u;
    const float t = (u - n) * 6.283185307179586f;
    r = e * __cosf(t); i = e * __sinf(t);
}
__device__ __forceinline__ void mma_tf32(float* c, float a0, float a1, float a2, float a3, float b0, float b1) {
    asm volatile("mma.sync.aligned.m16n8k8.row.col.f32.tf32.tf32.f32 {%0,%1,%2,%3},{%4,%5,%6,%7},{%8,%9},{%0,%1,%2,%3};"
                 : "+f"(c[0]), "+f"(c[1]), "+f"(c[2]), "+f"(c[3])
                 : "r"(__float_as_uint(a0)), "r"(__float_as_uint(a1)), "r"(__float_as_uint(a2)), "r"(__float_as_uint(a3)), "r"(__float_as_uint(b0)), "r"(__float_as_uint(b1)));
}

struct ProRegs { uint32_t v[2][4], ldt[2]; };
__device__ __forceinline__ void prologue_load(const ProArgs& a, int b, ProRegs& pr) {
    const int w = threadIdx.x >> 5;
#pragma unroll
    for (int i = 0; i < 2; i++) {
        const int gi = b * 512 + (w & 3) * 128 + ((w >> 2) & 1) * 64 + i * 32 + (threadIdx.x & 31);
        pr.ldt[i] = __ldg((const uint16_t*)a.ldt + b * 4 + (w & 3));
        pr.v[i][0] = __ldg((const uint16_t*)a.lAr + gi); pr.v[i][1] = __ldg((const uint16_t*)a.Ai + gi);
        pr.v[i][2] = __ldg((const uint16_t*)a.Cr + gi); pr.v[i][3] = __ldg((const uint16_t*)a.Ci + gi);
    }
}
__device__ __forceinline__ void prologue(const ProArgs& a, uint32_t sb, int b, int w, const ProRegs& pr) {
    const int tid = threadIdx.x, lane = tid & 31, g = lane >> 2, c = lane & 3;
    const int d0 = b * 4;
    if (w >= 8) {
        const int t2 = tid - 256;
        if (w < 10) {
            const int row = b * 16 + (w - 8) * 8 + g;
            const float4 r4 = row_stats((const uint4*)(a.x + (size_t)row * 512) + c, 4);
            const float2 r = make_float2(r4.x + r4.z, r4.y + r4.w);
            const float2 l = ln_finish(r.x * (1.f / 512.f), fmaxf(r.y - r.x * r.x * (1.f / 512.f), 0.f) * (1.f / 512.f));
            if (c == (g >> 1)) asm volatile("st.relaxed.gpu.global.u32 [%0],%1;" ::"l"(g_ln0 + row), "r"(pack2(l.x, l.y)) : "memory");
        }
        PROF(t2 == 0, 3516);
        const int gi = b * 128 + t2;
        if (t2 < 32) acc_init(a.mem0, b * 32 + t2);
        if (t2 >= 112) ((uint4*)g_st2)[b * 16 + t2 - 112] = make_uint4(0, 0, 0, 0);
        if (gi < 13 * 64) g_cnt[gi] = 0;
        bar_sync(6, 384);
        if (gi < 512) g_st[0][(gi >> 8) * 2048 + (lds32(sb + S_TAG) ^ 1) * 256 + (gi & 255)] = make_float2(0.f, 0.f);
        asm volatile("{.reg .pred p; elect.sync _|p,0xffffffff; @p cp.async.bulk.prefetch.L2.global [%0],32768;}"
                     ::"l"((w == 8 ? a.Wq : w == 9 ? a.Wk : w == 10 ? a.Wv : a.Wo) + (size_t)b * 16384) : "memory");
        mbar_wait(sb + S_XBAR, 0);
#pragma unroll 1
        for (int h = 0; h < 2; h++) {
            uint32_t l[8];
            int n = 0;
            while (true) {
                bool ok = true;
#pragma unroll
                for (int i = 0; i < 8; i++) asm volatile("ld.relaxed.gpu.global.u32 %0,[%1];" : "=r"(l[i]) : "l"(g_ln0 + h * 1024 + i * 128 + t2) : "memory");
#pragma unroll
                for (int i = 0; i < 8; i++) ok = ok && l[i];
                if (__all_sync(0xffffffffu, ok)) break;
                if (++n > 2000000) __trap();
            }
#pragma unroll
            for (int i = 0; i < 8; i++) {
                const int t = h * 1024 + i * 128 + t2;
                const uint2 x = lds64(sb + P_X + t * 16 + (b & 1) * 8);
                const float m = blo(l[i]), rs = rcp(bhi(l[i]));
                const uint32_t u0 = pack2(rbf(blo(x.x) - m) * rs, rbf(bhi(x.x) - m) * rs), u1 = pack2(rbf(blo(x.y) - m) * rs, rbf(bhi(x.y) - m) * rs);
                sts128(sb + P_X + t * 16, x.x, x.y, u0, u1);
                const uint32_t o = sb + P_U + ((t >> 3) & 1) * 2176 + ((t >> 4) + 8) * 16 + (t & 7) * 2;
                asm volatile("st.shared.u16 [%0],%1;" ::"r"(o), "h"((uint16_t)u0) : "memory");
                asm volatile("st.shared.u16 [%0],%1;" ::"r"(o + 4352), "h"((uint16_t)(u0 >> 16)) : "memory");
                asm volatile("st.shared.u16 [%0],%1;" ::"r"(o + 8704), "h"((uint16_t)u1) : "memory");
                asm volatile("st.shared.u16 [%0],%1;" ::"r"(o + 13056), "h"((uint16_t)(u1 >> 16)) : "memory");
            }
        }
        PROF(t2 == 0, 3517);
        bar_sync(9, 384);
        fence_async_smem();
#pragma unroll 1
        for (int j = 0; j < 16; j++) {
            const int d = d0 + w - 8;
            asm volatile("{.reg .pred p; elect.sync _|p,0xffffffff; @p cp.async.bulk.global.shared::cta.bulk_group [%0],[%1],%2;}" ::"l"(g_P + (((d >> 5) * 16 + j) * 32 + (d & 31)) * PW),
                         "r"(sb + P_P + ((w - 8) * 2080 + j * 128) * 4), "r"(PW * 4) : "memory");
        }
        asm volatile("cp.async.bulk.commit_group; cp.async.bulk.wait_group 0;" ::: "memory");
        bar_arrive(10, 384);
        return;
    }
#pragma unroll
    for (int i = 0; i < 2; i++) {
        const float dt = rbf(expf(blo(pr.ldt[i])));
        const float ar = -rbf(expf(blo(pr.v[i][0]))) * dt, ai = blo(pr.v[i][1]) * dt;
        sts128(sb + P_PRM + (w * 64 + i * 32 + lane) * 16, __float_as_uint(ar * 1.4426950408889634f), __float_as_uint(ai * 0.15915494309189535f),
               __float_as_uint(2.f * (blo(pr.v[i][2]) * dt)), __float_as_uint(2.f * (blo(pr.v[i][3]) * dt)));
    }
    if (tid < 64) sts128(sb + P_U + (tid >> 3) * 2176 + (tid & 7) * 16, 0, 0, 0, 0);
    bar_arrive(6, 384);
    __syncwarp();
    PROF(tid == 0, 3510);
    const int ch = w & 3, hf = w >> 2;
    {
        float k0[4] = {0, 0, 0, 0}, k1[4] = {0, 0, 0, 0}, k2[4] = {0, 0, 0, 0}, k3[4] = {0, 0, 0, 0}, k4[4] = {0, 0, 0, 0}, kl = 0;
#pragma unroll KGU
        for (int j = 0; j < 16; j++) {
            const uint4 q = lds128(sb + P_PRM + (w * 64 + j * 4 + c) * 16);
            const float cr = __uint_as_float(q.z), ci = __uint_as_float(q.w);
            float wr[4], wi[4], vr[4], vi[4];
            cpow(__uint_as_float(q.x), __uint_as_float(q.y), (float)g, wr[0], wi[0]);
            cpow(__uint_as_float(q.x), __uint_as_float(q.y), (float)(g + 8), vr[0], vi[0]);
#pragma unroll
            for (int i = 1; i < 4; i++) { wr[i] = wr[i - 1]; wi[i] = wi[i - 1]; csq(wr[i], wi[i]); vr[i] = vr[i - 1]; vi[i] = vi[i - 1]; csq(vr[i], vi[i]); }
            float hr = wr[3], hi = wi[3];
            csq(hr, hi);
            mma_tf32(k0, wr[0], vr[0], wi[0], vi[0], cr * hr - ci * hi, -(cr * hi + ci * hr));
            hr = vr[3]; hi = vi[3]; csq(hr, hi);
            mma_tf32(k1, wr[0], vr[0], wi[0], vi[0], cr * hr - ci * hi, -(cr * hi + ci * hr));
            csq(hr, hi);
            mma_tf32(k2, wr[1], vr[1], wi[1], vi[1], cr * hr - ci * hi, -(cr * hi + ci * hr));
            csq(hr, hi);
            mma_tf32(k3, wr[2], vr[2], wi[2], vi[2], cr * hr - ci * hi, -(cr * hi + ci * hr));
            csq(hr, hi);
            mma_tf32(k4, wr[3], vr[3], wi[3], vi[3], cr * hr - ci * hi, -(cr * hi + ci * hr));
            csq(hr, hi);
            kl += cr * hr - ci * hi;
        }
        kl += __shfl_xor_sync(0xffffffffu, kl, 1); kl += __shfl_xor_sync(0xffffffffu, kl, 2);
        const uint32_t o = sb + P_K6 + (ch * 656 + c * 32 + g) * 4, ol = sb + P_K6 + (ch * 656 + 640) * 4;
#define KST(k, base) sts32(o + (base) * 4, __float_as_uint(k[0])); sts32(o + (base) * 4 + 64, __float_as_uint(k[1])); \
                     sts32(o + (base) * 4 + 32, __float_as_uint(k[2])); sts32(o + (base) * 4 + 96, __float_as_uint(k[3]))
#define KAD(k, base) k[0] += __uint_as_float(lds32(o + (base) * 4)); k[1] += __uint_as_float(lds32(o + (base) * 4 + 64)); \
                     k[2] += __uint_as_float(lds32(o + (base) * 4 + 32)); k[3] += __uint_as_float(lds32(o + (base) * 4 + 96))
        if (hf == 0) {
            bar_sync(2 + ch, 64);
            KAD(k0, 0); KAD(k1, 128); KAD(k2, 256); KAD(k3, 384); KAD(k4, 512);
            kl += __uint_as_float(lds32(ol));
            __syncwarp();
        }
        KST(k0, 0); KST(k1, 128); KST(k2, 256); KST(k3, 384); KST(k4, 512);
        if (lane == 0) sts32(ol, __float_as_uint(kl));
        if (hf == 1) { __syncwarp(); bar_arrive(2 + ch, 64); }
    }
    PROF(tid == 0, 3511);
    bar_sync(8, 384);
    PROF(tid == 0, 3512);
    if (tid < 64) sts32(sb + P_P + ((tid >> 4) * 2080 + (tid & 15)) * 4, 0);
#pragma unroll 1
    for (int x = tid; x < 2048; x += 512) {
        uint32_t pw[2][4];
#pragma unroll
        for (int h = 0; h < 2; h++) {
            const int y = x + h * 256;
            const int i0 = y <= 256 ? y : 256 + (int)((pack2((float)y, 0.f) & 0xffff) - 0x4380);
            const int i1 = y <= 256 ? max(y - 1, 0) : 256 + (int)((pack2((float)(y - 1), 0.f) & 0xffff) - 0x4380);
#pragma unroll
            for (int k = 0; k < 4; k++) {
                const float lo = __uint_as_float(lds32(sb + P_K6 + k * 2624 + i0 * 4)), hi = __uint_as_float(lds32(sb + P_K6 + k * 2624 + i1 * 4));
                pw[h][k] = pack2(lo, y ? hi : 0.f);
            }
        }
#pragma unroll
        for (int h = 0; h < 2; h++)
#pragma unroll
            for (int k = 0; k < 4; k++) sts32(sb + P_P + (k * 2080 + x + h * 256 + 16) * 4, pw[h][k]);
    }
    bar_sync(9, 384);
    PROF(tid == 0, 3513);
    {
        float acc[16][4];
#pragma unroll
        for (int j = 0; j < 16; j++) acc[j][0] = acc[j][1] = acc[j][2] = acc[j][3] = 0;
#pragma unroll 1
        for (int e = hf * 4; e < hf * 4 + 4; e++) {
            uint32_t B[16][2];
            const uint32_t ua = sb + P_U + ch * 4352 + ((lane >> 3) & 1) * 2176 + (8 + (lane >> 4) * 8 + (lane & 7) - e) * 16;
#pragma unroll
            for (int j = 0; j < 8; j++) { const uint4 v = ldsm4(ua + j * 256); B[2 * j][0] = v.x; B[2 * j][1] = v.y; B[2 * j + 1][0] = v.z; B[2 * j + 1][1] = v.w; }
            const uint32_t pa = sb + P_P + (ch * 2080 + 16 + e * 16 + g - 2 * c) * 4;
#pragma unroll
            for (int d = 0; d < 16; d++) {
                const uint32_t a0 = lds32(pa + d * 512), a1 = lds32(pa + d * 512 + 32), a2 = lds32(pa + d * 512 - 32);
#pragma unroll
                for (int j = d; j < 16; j++) mma16(acc[j], a0, a1, a2, a0, B[j - d][0], B[j - d][1]);
            }
        }
        PROF(tid == 0, 3514);
        const uint32_t o = sb + P_Y + (ch * 2560 + c * 40 + g) * 4;
#pragma unroll
        for (int j = 0; j < 8; j++) {
#pragma unroll
            for (int i = 0; i < 4; i++) { const float lo = acc[j][i], hi = acc[j + 8][i]; acc[j][i] = hf ? hi : lo; sts32(o + (j + 8 - hf * 8) * 640 + (i & 1) * 80 + (i >> 1) * 32, __float_as_uint(hf ? lo : hi)); }
        }
        bar_sync(2 + ch, 64);
#pragma unroll
        for (int j = 0; j < 8; j++) {
#pragma unroll
            for (int i = 0; i < 4; i++) acc[j][i] += __uint_as_float(lds32(o + (j + hf * 8) * 640 + (i & 1) * 80 + (i >> 1) * 32));
        }
#pragma unroll
        for (int j = 0; j < 8; j++) {
#pragma unroll
            for (int i = 0; i < 4; i++) sts32(o + (j + hf * 8) * 640 + (i & 1) * 80 + (i >> 1) * 32, __float_as_uint(acc[j][i]));
        }
    }
    const uint2 dk = __ldg((const uint2*)(a.Dk + d0));
    bar_sync(1, 256);
#pragma unroll 2
    for (int i = 0; i < 8; i++) {
        const int t = i * 256 + tid;
        const uint32_t o = sb + P_Y + (t + 4 * (t >> 4)) * 4;
        const uint4 xu = lds128(sb + P_X + t * 16);
        float y[4];
#pragma unroll
        for (int k = 0; k < 4; k++) y[k] = rbf(__uint_as_float(lds32(o + k * 10240)));
        uint2 r;
        r.x = pack2(blo(xu.x) + rbf(y[0] + rbf(blo(xu.z) * blo(dk.x))), bhi(xu.x) + rbf(y[1] + rbf(bhi(xu.z) * bhi(dk.x))));
        r.y = pack2(blo(xu.y) + rbf(y[2] + rbf(blo(xu.w) * blo(dk.y))), bhi(xu.y) + rbf(y[3] + rbf(bhi(xu.w) * bhi(dk.y))));
        {
            const bool up = t & 8;
            const uint32_t o = __shfl_xor_sync(0xffffffffu, up ? r.x : r.y, 8);
            ((uint2*)(g_xA[0] + ((t >> 4) * 32 + (d0 >> 4)) * 32 + (t & 7) * 4 + ((d0 >> 1) & 2) + up))[(d0 >> 3) & 1] = up ? make_uint2(o, r.y) : make_uint2(r.x, o);
        }
        if (i == 0) {
            const float e0 = blo(r.x), e1 = bhi(r.x), e2 = blo(r.y), e3 = bhi(r.y);
            asm volatile("red.relaxed.gpu.global.add.v2.f32 [%0],{%1,%2};" ::"l"(g_st[0] + (t >> 7) * 2048 + lds32(sb + S_TAG) * 256 + (b & 1) * 128 + (t & 127)),
                         "f"((e0 + e1) + (e2 + e3)), "f"((e0 * e0 + e1 * e1) + (e2 * e2 + e3 * e3)) : "memory");
        }
    }
    PROF(tid == 0, 3515);
    bar_sync(10, 384);
}

__global__ void __cluster_dims__(2, 1, 1) __launch_bounds__(384, 1) main_kernel(const __grid_constant__ Params p) {
    extern __shared__ __align__(1024) uint8_t smem[];
    const uint32_t sb = __shfl_sync(0xffffffffu, smem_u32(smem), 0);
    uint32_t rank; asm("mov.u32 %0,%%cluster_ctarank;" : "=r"(rank));
    const int wi = __shfl_sync(0xffffffffu, threadIdx.x >> 5, 0);
    const int cl = blockIdx.x >> 1, wg = wi >> 2;
    const bool rec = p.rec0 >= 0 && cl >= p.rec0 && cl < p.rec0 + 32;
    PROF(threadIdx.x == 0, 3500);
    ProRegs pr;
    prologue_load(p.pa, max((int)blockIdx.x - 4, 0), pr);
    if (rec) rec_init(p, sb, cl - p.rec0, rank); else bulk_init(sb);
    if (threadIdx.x == 352 && p.dopro && cl >= 2) {
        mbar_init(sb + S_XBAR, 1);
        asm volatile("fence.mbarrier_init.release.cluster;" ::: "memory");
        mbar_expect(sb + S_XBAR, 32768);
        for (int j = 0; j < 8; j++) tma2d(sb + P_X + j * 4096, &p.tm[3], ((blockIdx.x - 4) >> 1) * 8, j * 256, sb + S_XBAR);
    }
    if (threadIdx.x == 320) {
        unsigned v;
        asm volatile("ld.relaxed.gpu.global.u32 %0,[%1];" : "=r"(v) : "l"(g_gate) : "memory");
        v = v / (4 * NCL) + p.dopro;
        sts64(sb + S_GATE, v * (4 * NCL), v & 1);
    }
    __syncwarp();
    asm volatile("barrier.cluster.arrive.relaxed.aligned;" ::: "memory");
    if (wg == 2) bar_arrive(8, 384);
    if (p.dopro && cl >= 2) prologue(p.pa, sb, blockIdx.x - 4, wi, pr); else if (wg < 2) bar_sync(8, 384);
    asm volatile("barrier.cluster.wait.aligned;" ::: "memory");
    fence_async_smem();
    bar_sync(wg == 2 ? 7 : 1, wg == 2 ? 128 : 256);
    if (p.dopro && (threadIdx.x == 32 || threadIdx.x == 352)) red_release(g_gate, 1);
    if (rec) {
        if (threadIdx.x == 0) {
            rec_fetch(&p.tm[1], sb + R_STK, (cl - p.rec0) * 128, rank * 256, 2, sb + R_BAR + RB_INIT * 8);
            rec_fetch(&p.tm[2], sb + R_STV, (cl - p.rec0) * 128, rank * 256, 2, sb + R_BAR + RB_INIT * 8);
        }
    }
    PROF(threadIdx.x == 0, 3506);
    __syncwarp();
    if (rec) {
        const int head = cl - p.rec0;
        if (wg == 2) {
            reg_dec<RH>();
            const int w = wi & 3;
            if (threadIdx.x == 256) rec_fetch(&p.tm[0], sb + R_STQ, head * 128, rank * 256, 2, sb + R_BAR + RB_INIT * 8);
            __syncwarp();
            wait_cnt_warp(g_gate, lds32(sb + S_GATE));
            if (p.dostats) x1_stats((head * 2 + rank) * 4 + w);
            __syncthreads();
            cluster_sync();
            if ((p.chains >> (w >> 1)) & 1) rec_attn(p, sb, w >> 1, w & 1, head, rank);
        } else {
            reg_inc<RW0>();
            rec_weights(p, sb, head, rank, wi);
        }
    } else {
        if (wg == 2) {
            reg_dec<40>();
            const int w = wi & 3;
            if (w == 0) bulk_producer(p, sb, cl, rank); else if (w >= 2) bulk_release(p, sb, cl, rank, w - 2); else bulk_relay(p, sb, cl);
        } else { reg_inc<232>(); bulk_consumer(p, sb, cl, rank, wi); }
    }
    __syncwarp();
    cluster_sync();
}

typedef CUresult (*EncFn)(CUtensorMap*, CUtensorMapDataType, cuuint32_t, void*, const cuuint64_t*, const cuuint64_t*, const cuuint32_t*, const cuuint32_t*,
                          CUtensorMapInterleave, CUtensorMapSwizzle, CUtensorMapL2promotion, CUtensorMapFloatOOBfill);
inline uint32_t mk(int type, int layer, int ch, int a, int b, int c) { return type | (layer << 3) | (ch << 4) | (a << 8) | (b << 16) | ((uint32_t)c << 24); }
constexpr int SMEM_BYTES = 232448;

struct Sched {
    Params* P; int n[NCL];
    void clear() { memset(P->task, 0, sizeof(P->task)); memset(n, 0, sizeof(n)); }
    void add(int cl, uint32_t t) { if (n[cl] < MAXT - 1) P->task[list_of(cl)][n[cl]++] = t; }
};

constexpr int REC0 = 4;
struct Cfg { int LAG, TS1, TS2, DQU, DQO, DUN, DHN, MARG, NQ1, FAST0, n0, oc, fc, nuns, ns2, nhg, hs, osl, nfin, dry, tl, c8; };
#define HALVES 1
#define PLAN 14, 2250, 2750, 2400, 1300, 5400, 380, 3000, 4, 0, 10, 10, 13, 5, 4, 8, 6000, 0, 0, 5000, 3000, 13
Cfg g_cfg = {PLAN};
double g_est;
bool g_planned = false;
struct Plan { uint32_t w[NCL][MAXT]; int n[NCL]; double end, rec; };
void simulate(Plan& L, int nc, const Cfg& C) {
    const int LAG = C.LAG, NQ1 = C.NQ1, FAST0 = C.FAST0, n0 = C.n0, oc = C.oc, fc = C.fc, nuns = C.nuns, ns2 = C.ns2, nhg = C.nhg;
    const double TS1 = C.TS1, TS2 = C.TS2, DQU = C.DQU, DQO = C.DQO, DUN = C.DUN, DHN = C.DHN, MARG = C.MARG, hs = C.hs;
    const double INF = 1e18, DKB = 600, DOV = 700, DH = DHN, DHO = 1100, DF = 2200, DFB = 200, POLL = 450, FILL = 500, PUB = 600;
    enum { Q0, O0, Q1, HB, O1, FI, NK };
    struct Grp { int n, left; double done; } G[NK][16];
    double fr[NCL], it[100] = {}, cv[16];
    int ns[16], last[2][NCL], uc = 0, nit = 0;
    memset(L.n, 0, sizeof(L.n)); L.end = 0;
    auto fast = [&](int c) { return c < FAST0 || c >= fc; };
    for (int c = 0; c < 16; c++) {
        ns[c] = c < nuns ? 1 : c == 15 ? 16 : c >= C.c8 ? 8 : ns2;
        const int cnt[NK] = {c < 2 ? 48 : (c & 1) ? 0 : 96, c < oc ? 8 : OPS1, c == 15 ? 24 : fast(c) ? 16 : 48 / NQ1, c >= 2 && !(c & 1) ? 16 : 0, ns[c], c < C.nfin || ns[c] == 1 ? 0 : c >= 14 ? 8 : 4};
        for (int k = 0; k < NK; k++) G[k][c] = {cnt[k], cnt[k], 0};
        cv[c] = INF;
    }
    for (int i = 0; i < nc; i++) { fr[i] = 0; last[0][i] = last[1][i] = -1; }
    auto fin = [&](int k, int c) { if ((k == Q0 && c >= 2) || k == HB) c &= ~1; return G[k][c].left ? INF : G[k][c].done; };
    auto len = [&](int i) { return (i >= LAG && i < 64) ? (double)TS2 : (double)TS1; };
    auto end_it = [&](int i) { return i < nit ? it[i] + len(i) : INF; };
    auto nominal = [&](int i) { if (i < nit) return it[i]; double t = nit ? it[nit - 1] : 11000 - TS1; for (int j = nit - 1; j < i; j++) t += len(j); return t; };
    auto put = [&](int i, uint32_t w) { if (L.n[i] < MAXT - 2) L.w[i][L.n[i]++] = w; else L.end = INF; };
    auto rel = [&](int k, int c) {
        switch (k) {
            case Q0: return 0.0;
            case O0: return end_it(4 * c + 3) + PUB + POLL;
            case Q1: return cv[c] + POLL;
            case HB: return cv[c - 2] + 600 + POLL;
            case O1: return fmax(end_it(LAG + 4 * c + 3) + PUB + POLL, G[O1][c].left == 1 && !G[FI][c].n ? G[O1][c].done - DKB * 64 / ns[c] : 0);
            default: return fin(O1, c) + POLL;
        }
    };
    auto dur = [&](int k, int c) {
        switch (k) {
            case Q0: return DQO + (c < 2 ? 2.0 : 1.0) * DQU;
            case O0: return (16 - G[O0][c].n) * DKB + 1200;
            case HB: return DHO + DH * c;
            case Q1: return DQO + 48.0 / G[Q1][c].n * DQU;
            case O1: return DOV + DKB * 64 / ns[c] + (G[O1][c].left == 1 && !G[FI][c].n ? 700 + 800 * ns[c] : 0);
            default: return DF + DFB * ns[c] * (c >= 14 ? 0.5 : 1);
        }
    };
    auto o0_est = [&](int c) {
        double t = uc ? cv[uc - 1] - 900 : 0;
        for (int j = uc; j < c; j++) t = fmax(t, nominal(4 * j + 4) + PUB + POLL + FILL) + dur(O0, j) + DUN;
        return fmax(t, nominal(4 * c + 4) + PUB + POLL);
    };
    auto cv_est = [&](int c) { return c < uc ? cv[c] : o0_est(c) + FILL + dur(O0, c) + DUN + 900; };
    auto slot = [&](int k, int c, int i) { return k == O0 ? (i < 8 ? i : nc + 7 - i) : c == 15 ? i : i - 8; };
    while (true) {
        while (nit < 64 + LAG) {
            double t = nit ? end_it(nit - 1) : 0;
            if (nit < 64) t = fmax(t, fin(Q0, nit >> 2) + POLL);
            if (nit >= LAG) t = fmax(t, fin(Q1, (nit - LAG) >> 2) + (nit < 64 ? 0 : POLL));
            if (t >= INF) break;
            it[nit++] = t;
        }
        int i = -1;
        for (int j = 0; j < nc; j++) if (fr[j] < INF && (i < 0 || fr[j] < fr[i])) i = j;
        if (i < 0) break;
        const double t = fr[i];
        double lim = INF;
        if (i < 8 && last[0][i] == uc) {
            if (G[O0][uc].left || fin(HB, uc) >= INF) { fr[i] = t + 200; continue; }
            const double e = fmax(G[O0][uc].done, fin(HB, uc) - 2000) + DUN;
            for (int j = 0; j < 8; j++) { put(j, mk(T_CV, 0, uc, 2 * j, G[O0][uc].n, 0)); fr[j] = e; }
            cv[uc++] = e + 900;
            continue;
        }
        const bool hg = (unsigned)(i - 24) < (unsigned)nhg;
        double hlim = INF;
        for (int c = 2; c < 16 && hg; c++) if (G[HB][c].left) { hlim = cv_est(c - 2) + hs; break; }
        int mine[2] = {-1, -1};
        for (int k = 0; k < 2; k++)
            for (int c = last[k][i] + 1; c < 16 && mine[k] < 0; c++) if ((unsigned)slot(O0 + k, c, i) < (unsigned)G[O0 + k][c].n) mine[k] = c;
        if (mine[0] >= 0) lim = i < 8 ? o0_est(mine[0]) - (uc ? 0 : C.dry) : nominal(4 * mine[0] + 4) + PUB + C.osl;
        else if (mine[1] >= 0) lim = cv_est(mine[1]) + POLL;
        else if ((i < 16 && G[O1][15].left) || (i < 8 && G[FI][15].left)) lim = fmin(lim, nominal(64 + LAG) + PUB - C.tl);
        int bk = -1, bc = 0; double bd = INF;
        for (int k = 0; k < NK; k++)
            for (int c = 0; c < 16; c++) {
                const bool urgent = k == O0 || k == Q1 || (k >= O1 && c == 15);
                if (!G[k][c].left || ((k == O0 || k == Q1) && c != mine[k - O0]) || (k >= O1 && c == 15 && i >= G[k][c].n)) continue;
                if (rel(k, c) > t || (t + dur(k, c) + (k == Q0 && c >= 2 ? DQU : 0) > lim && !urgent)) continue;
                if (i < 8 && uc && uc < 16 && k != O0) continue;
                if ((k == HB && !hg && i < nc - 2) || (k != HB && !urgent && t + dur(k, c) + (k == Q0 && c >= 2 ? DQU : 0) > hlim)) continue;
                const double dl = urgent ? -INF : k == HB ? -INF / 2 : k == Q0 ? nominal(4 * c) - 3000 : 1e9 + c * 2 + (k == O1);
                if (dl < bd) { bd = dl; bk = k; bc = c; }
            }
        if (bk < 0) {
            bool any = i < 8 && uc < 16;
            for (int k = 0; k < NK; k++) for (int c = 0; c < 16; c++) any = any || G[k][c].left;
            fr[i] = any ? t + 200 : INF;
            if (t > 400000) { L.end = INF; return; }
            continue;
        }
        Grp& g = G[bk][bc];
        const int n = g.n - g.left, c = bc;
        int nu = 1;
        double d = dur(bk, c);
        if (bk == Q0) for (nu = c < 2 ? 2 : 1; c >= 2 && nu < g.left && (nu < 2 || (nu < n0 && t + d + DQU < fmin(fmin(lim, hlim), bd - MARG))); nu++) d += DQU;
        if (bk == O0 && i >= 8) d += (g.n - 8) * DKB;
        if (bk == Q0 && !c && n >= 32) { nu = 1; d -= DQU; }
        if (bk == O0 || bk == Q1) last[bk - O0][i] = c;
        if (bk == O0 && !c && i < 8 && C.dry) put(i, mk(T_CV, 0, 1, 2 * i, 0, 128));
        g.left -= nu;
        const bool fini = bk == O1 && !g.left && !G[FI][c].n;
        const double e = fmax(fmax(t, rel(bk, c) + FILL) + (t < 1 ? 3500 : 0) + d, fini ? g.done + POLL + 700 + 800 * ns[c] : 0);
        fr[i] = e;
        g.done = fmax(g.done, e + (bk == O1 ? (c == 15 ? -500 : 1500) : bk == O0 ? 0 : (bk == Q1 && g.n < 24) || (bk == Q0 && !c && nu == 2) ? -500 : 1000));
        if (bk == FI || fini) L.end = fmax(L.end, e);
        put(i, bk == Q0 ? (c == 0 ? mk(T_QKV, 0, 0, n < 32 ? n : 2 * n - 32, nu, 32) : c == 1 ? mk(T_QKV, 0, c, n, 2, 24) : mk(T_QKV, 0, c, n, nu, 64))
             : bk == O0 ? (i < 8 ? mk(T_OP, 0, c, i * (16 - g.n), 16 - g.n, i) : mk(T_OP, 0, c, 64 - (nc - i) * 8, 8, slot(O0, c, i)))
             : bk == HB ? mk(T_CV, 1, c, 2 * n, 0, 0)
             : bk == Q1 ? mk(T_QKV, 1, c, slot(Q1, c, i) * 2, 48 / g.n, g.n)
             : bk == O1 ? mk(T_OP, 1, c, n * 64 / ns[c], 64 / ns[c], n + (fini ? 32 : c == 15 && HALVES ? 16 : 0))
                        : mk(T_FIN, 1, c, n * (32 / g.n), ns[c], 16 / g.n));
    }
    L.rec = end_it(63 + LAG);
}
void plan(Params& P) {
    P.rec0 = REC0; P.chains = 3; P.lag = g_cfg.LAG; P.dostats = 1; P.dopro = 1;
    static Plan L;
    int cls[NCL], nc = 0;
    for (int c = REC0 + 32; c < NCL; c++) cls[nc++] = c;
    for (int c = REC0 - 1; c >= 0; c--) cls[nc++] = c;
    simulate(L, nc, g_cfg);
    g_est = L.end;
    Sched S; S.P = &P; S.clear();
    for (int i = 0; i < nc; i++) {
        bool warm = false;
        for (int k = 0; k < L.n[i]; k++) {
            if (!warm && k + 1 < L.n[i] && (L.w[i][k + 1] & 255) == (mk(T_FIN, 1, 15, 0, 0, 0) & 255)) { S.add(cls[i], (L.w[i][k + 1] & ~0xff0000u) | 0x80000000u); warm = true; }
            S.add(cls[i], L.w[i][k]);
            if ((L.w[i][k] & 7) == T_FIN) warm = true;
        }
    }
}

#define TK0() do {} while (0)
#define TK() do { P.e0 = (P.chains & 1) ? 64 : 0; P.b1 = (P.chains & 2) ? P.lag : 1000; P.nit = (P.chains & 2) ? P.lag + 64 : 64; TK0(); } while (0)
}

extern "C" void kernel_launch(void* const* d_in, const int* in_sizes, int n_in, void* d_out, int out_size) {
    typedef const __nv_bfloat16* BP;
    static EncFn enc = nullptr;
    if (!enc) {
        void* fn = nullptr; cudaDriverEntryPointQueryResult qr;
        cudaGetDriverEntryPoint("cuTensorMapEncodeTiled", &fn, cudaEnableDefault, &qr);
        enc = (EncFn)fn;
        cudaFuncSetAttribute(main_kernel, cudaFuncAttributeMaxDynamicSharedMemorySize, SMEM_BYTES);
    }
    static Params P;
    for (int i = 0; i < 4; i++) {
        const cuuint64_t cols = i < 3 ? 4096 : 512, rows = i < 3 ? 512 : 4096;
        cuuint64_t d2[2] = {cols, rows}, d3[3] = {64, rows, cols / 64}, str[2] = {cols * 2, 128};
        cuuint32_t box[3] = {64, 64, 4}, es[3] = {1, 1, 1};
        enc(&P.tm[i < 3 ? i : 4], CU_TENSOR_MAP_DATA_TYPE_BFLOAT16, 2, d_in[9 + i], d2, str, box, es, CU_TENSOR_MAP_INTERLEAVE_NONE, CU_TENSOR_MAP_SWIZZLE_128B,
                       CU_TENSOR_MAP_L2_PROMOTION_L2_128B, CU_TENSOR_MAP_FLOAT_OOB_FILL_NONE);
        for (int m = 0; m <= i / 3; m++) {
            cuuint32_t box3[3] = {64, 32, m ? 4u : 2u};
            enc(&P.t3[i + m], CU_TENSOR_MAP_DATA_TYPE_BFLOAT16, 3, d_in[9 + i], d3, str, box3, es, CU_TENSOR_MAP_INTERLEAVE_NONE, CU_TENSOR_MAP_SWIZZLE_128B,
                CU_TENSOR_MAP_L2_PROMOTION_L2_128B, CU_TENSOR_MAP_FLOAT_OOB_FILL_NONE);
        }
    }
    {
        cuuint64_t dims[2] = {512, 2048}, str[1] = {1024};
        cuuint32_t box[2] = {8, 256}, es[2] = {1, 1};
        enc(&P.tm[3], CU_TENSOR_MAP_DATA_TYPE_BFLOAT16, 2, d_in[0], dims, str, box, es, CU_TENSOR_MAP_INTERLEAVE_NONE, CU_TENSOR_MAP_SWIZZLE_NONE,
            CU_TENSOR_MAP_L2_PROMOTION_NONE, CU_TENSOR_MAP_FLOAT_OOB_FILL_NONE);
    }
    for (int m = 0; m < 2; m++) {
        void* ga; cudaGetSymbolAddress(&ga, g_A);
        cuuint64_t dims[2] = {512, sizeof(AOps) / 1024}, str[1] = {1024};
        cuuint32_t box[2] = {256, m ? 16u : 8u}, es[2] = {1, 1};
        enc(&P.ta[m], CU_TENSOR_MAP_DATA_TYPE_BFLOAT16, 2, ga, dims, str, box, es, CU_TENSOR_MAP_INTERLEAVE_NONE, CU_TENSOR_MAP_SWIZZLE_NONE,
            CU_TENSOR_MAP_L2_PROMOTION_L2_128B, CU_TENSOR_MAP_FLOAT_OOB_FILL_NONE);
    }
    P.mem0 = (BP)d_in[8]; P.Wo = (BP)d_in[12]; P.Dskip = (BP)d_in[6]; P.out = (__nv_bfloat16*)d_out;
    cudaStream_t s = cudaStreamPerThread;
    P.pa = {(BP)d_in[0], (BP)d_in[1], (BP)d_in[2], (BP)d_in[3], (BP)d_in[4], (BP)d_in[5], (BP)d_in[6], (BP)d_in[9], (BP)d_in[10], (BP)d_in[11], (BP)d_in[12], (BP)d_in[8]};
    if (!g_planned) { plan(P); g_planned = true; }
    TK(); main_kernel<<<2 * NCL, 384, SMEM_BYTES, s>>>(P); TK();
}
```

```cpp
#include <cuda_runtime.h>
#include <cuda_bf16.h>
#include <cuda.h>
#include <stdint.h>
#include <string.h>
#include <math.h>

#define MAXTN 42
namespace {

constexpr int NCL = 66;
constexpr int NLIST = NCL - 32;
__host__ __device__ inline int list_of(int cl) { return cl < 4 ? cl : cl - 32; }
constexpr int MAXT = MAXTN;
#define PFC 1
#define QB1 2
#define QB2 4
#define QB3 6
#define LAGQ 2
#define CPOS 2
#define OPS1N 10
constexpr int OPS1 = OPS1N;
constexpr int MAXSPLIT = 16;
constexpr int PW = 144;

struct AOps { uint4 x[2][16 * 8 * 1024], o[2][16 * 64 * 1024]; };
__device__ AOps g_A;
#define g_xA g_A.x
#define g_o g_A.o
__device__ float2 g_st[2][16 * 2048];
__device__ float2 g_st2[2 * 16 * 128];
__device__ uint4 g_qkv[2][64 * 64 * 768];
__device__ uint4 g_pp[2][16 * MAXSPLIT * 8192];
__device__ uint4 g_acc[7 * 2048];
__device__ unsigned g_gate[32];
__device__ uint32_t g_P[16 * 16 * 32 * PW];
__device__ uint4 g_u[16 * 16 * 512];
__device__ float4 g_carry[2][17 * 16 * 4 * 256];
__device__ unsigned g_cnt[13 * 64];
__device__ uint32_t g_ln0[2048];

enum { C_QKV0 = 0, C_QKV1 = 1  , C_O0 = 2, C_O1 = 3, C_U = 4, C_OP1 = 5, C_CV = 6, C_ST = 7, C_H = 8, C_OP0 = 9   };
__device__ __forceinline__ unsigned* cnt_ptr(int kind, int chunk) { return g_cnt + kind * 64 + chunk; }

enum { T_END = 0, T_QKV = 1, T_OP = 2, T_CV = 3, T_FIN = 4 };
struct ProArgs { const __nv_bfloat16 *x, *lAr, *Ai, *Cr, *Ci, *ldt, *Dk, *Wq, *Wk, *Wv, *Wo, *mem0; };
struct Params {
    CUtensorMap tm[5];
    CUtensorMap t3[5];
    CUtensorMap ta[2];
    ProArgs pa;
    int dopro;
    const __nv_bfloat16* mem0;
    const __nv_bfloat16* Wo;
    const __nv_bfloat16* Dskip;
    __nv_bfloat16* out;
    int rec0;
    int chains;
    int lag;
    int b1, e0, nit;
    int zero, gpit;
    int dostats;
    uint32_t task[NLIST][MAXT];
};

__device__ __forceinline__ uint32_t smem_u32(const void* p) { return (uint32_t)__cvta_generic_to_shared(p); }
__device__ __forceinline__ uint32_t mapa(uint32_t a, uint32_t r) {
    uint32_t o; asm("mapa.shared::cluster.u32 %0,%1,%2;" : "=r"(o) : "r"(a), "r"(r)); return o;
}
__device__ __forceinline__ void mbar_init(uint32_t b, int c) { asm volatile("mbarrier.init.shared::cta.b64 [%0],%1;" ::"r"(b), "r"(c) : "memory"); }
__device__ __forceinline__ void mbar_expect(uint32_t b, int bytes) { asm volatile("mbarrier.arrive.expect_tx.shared::cta.b64 _,[%0],%1;" ::"r"(b), "r"(bytes) : "memory"); }
__device__ __forceinline__ void mbar_arrive(uint32_t b) { asm volatile("mbarrier.arrive.shared::cta.b64 _,[%0];" ::"r"(b) : "memory"); }
__device__ __forceinline__ void mbar_arrive_cluster(uint32_t b) { asm volatile("mbarrier.arrive.shared::cluster.b64 _,[%0];" ::"r"(b) : "memory"); }
__device__ __forceinline__ void mbar_arrive1(uint32_t b) { asm volatile("{.reg .pred p; elect.sync _|p,0xffffffff; @p mbarrier.arrive.shared::cta.b64 _,[%0];}" ::"r"(b) : "memory"); }
__device__ __forceinline__ void mbar_arrive1_cluster(uint32_t b) { asm volatile("{.reg .pred p; elect.sync _|p,0xffffffff; @p mbarrier.arrive.shared::cluster.b64 _,[%0];}" ::"r"(b) : "memory"); }
__device__ __forceinline__ void mbar_wait(uint32_t b, uint32_t ph) {
    asm volatile(
        "{.reg .pred p; .reg .u32 n; mov.u32 n,0;\n"
        "W%=: mbarrier.try_wait.parity.shared::cta.b64 p,[%0],%1;\n"
        "@p bra D%=;\n"
        "add.u32 n,n,1; setp.lt.u32 p,n,2000000; @p bra W%=;\n"
        "trap;\n"
        "D%=: }" ::"r"(b), "r"(ph) : "memory");
}
__device__ __forceinline__ bool mbar_test(uint32_t b, uint32_t ph) {
    uint32_t ok;
    asm volatile("{.reg .pred p; mbarrier.test_wait.parity.shared::cta.b64 p,[%1],%2; selp.u32 %0,1,0,p;}" : "=r"(ok) : "r"(b), "r"(ph) : "memory");
    return ok;
}
__device__ __forceinline__ bool wait_lds128(uint32_t b, uint32_t ph, uint32_t a, uint4& v) {
    uint32_t ok;
    asm volatile("{.reg .pred p; mbarrier.try_wait.parity.shared::cta.b64 p,[%5],%6,20000; ld.shared.v4.u32 {%0,%1,%2,%3},[%7]; selp.u32 %4,1,0,p;}"
                 : "=r"(v.x), "=r"(v.y), "=r"(v.z), "=r"(v.w), "=r"(ok) : "r"(b), "r"(ph), "r"(a) : "memory");
    return ok;
}
__device__ __forceinline__ bool wait_lds64(uint32_t b, uint32_t ph, uint32_t a, uint2& v) {
    uint32_t ok;
    asm volatile("{.reg .pred p; mbarrier.try_wait.parity.shared::cta.b64 p,[%3],%4,20000; ld.shared.v2.u32 {%0,%1},[%5]; selp.u32 %2,1,0,p;}"
                 : "=r"(v.x), "=r"(v.y), "=r"(ok) : "r"(b), "r"(ph), "r"(a) : "memory");
    return ok;
}
template <int PH> __device__ __forceinline__ void mbar_wait_c(uint32_t b) {
    asm volatile(
        "{.reg .pred p; .reg .u32 n; mov.u32 n,%2;\n"
        "W%=: mbarrier.try_wait.parity.shared::cta.b64 p,[%0],%1;\n"
        "@p bra D%=;\n"
        "add.u32 n,n,1; setp.lt.u32 p,n,2000000; @p bra W%=;\n"
        "trap;\n"
        "D%=: }" ::"r"(b), "n"(PH), "n"(PH) : "memory");
}
__device__ __forceinline__ void bar_sync(int id, int n) { asm volatile("bar.sync %0,%1;" ::"r"(id), "r"(n) : "memory"); }
__device__ __forceinline__ void bar_arrive(int id, int n) { asm volatile("bar.arrive %0,%1;" ::"r"(id), "r"(n) : "memory"); }
__device__ __forceinline__ void cluster_sync() { asm volatile("barrier.cluster.arrive.relaxed.aligned; barrier.cluster.wait.aligned;" ::: "memory"); }
__device__ __forceinline__ void fence_async() { asm volatile("fence.proxy.async;" ::: "memory"); }
__device__ __forceinline__ void fence_async_smem() { asm volatile("fence.proxy.async.shared::cta;" ::: "memory"); }
#define EFR 1
#define EFW 1
constexpr uint64_t POL_N = 0x1000000000000000ull, POL_F = 0x12F0000000000000ull;
constexpr uint64_t POL_LAST = EFR ? POL_F : POL_N  , POL_LATE = EFW ? POL_F : POL_N  , POL_SOON = EFW > 1 ? POL_F : POL_N;
__device__ __forceinline__ void bulk_g2s(uint32_t dst, const void* src, int bytes, uint32_t bar, uint64_t pol) {
    asm volatile("cp.async.bulk.shared::cluster.global.mbarrier::complete_tx::bytes.L2::cache_hint [%0],[%1],%2,[%3],%4;" ::"r"(dst), "l"(src), "r"(bytes), "r"(bar), "l"(pol) : "memory");
}
__device__ __forceinline__ void bulk_g2s_mc(uint32_t dst, const void* src, int bytes, uint32_t bar, uint64_t pol) {
    asm volatile("cp.async.bulk.shared::cluster.global.mbarrier::complete_tx::bytes.multicast::cluster.L2::cache_hint [%0],[%1],%2,[%3],%4,%5;" ::"r"(dst), "l"(src), "r"(bytes), "r"(bar), "h"((uint16_t)3), "l"(pol) : "memory");
}
__device__ __forceinline__ void bulk_s2s(uint32_t dst, uint32_t src, int bytes, uint32_t bar) {
    asm volatile("cp.async.bulk.shared::cluster.shared::cta.mbarrier::complete_tx::bytes [%0],[%1],%2,[%3];" ::"r"(dst), "r"(src), "r"(bytes), "r"(bar) : "memory");
}
__device__ __forceinline__ bool elect() {
    uint32_t r; asm volatile("{.reg .pred p; elect.sync _|p,0xffffffff; selp.u32 %0,1,0,p;}" : "=r"(r)); return r;
}
__device__ __forceinline__ void stg128(uint4* p, uint4 v, uint64_t pol) {
    asm volatile("st.global.L2::cache_hint.v4.u32 [%0],{%1,%2,%3,%4},%5;" ::"l"(p), "r"(v.x), "r"(v.y), "r"(v.z), "r"(v.w), "l"(pol));
}
__device__ __forceinline__ void stg32(uint32_t* p, uint32_t v, uint64_t pol) { asm volatile("st.global.L2::cache_hint.u32 [%0],%1,%2;" ::"l"(p), "r"(v), "l"(pol)); }
__device__ __forceinline__ uint4 ldcg128_last(const uint4* p) {
    uint4 v; asm volatile("ld.global.cg.L2::cache_hint.v4.u32 {%0,%1,%2,%3},[%4],%5;" : "=r"(v.x), "=r"(v.y), "=r"(v.z), "=r"(v.w) : "l"(p), "l"(POL_LAST) : "memory"); return v;
}
__device__ __forceinline__ void tma2d(uint32_t dst, const CUtensorMap* tm, int x, int y, uint32_t bar) {
    asm volatile("cp.async.bulk.tensor.2d.shared::cluster.global.mbarrier::complete_tx::bytes [%0],[%1,{%2,%3}],[%4];" ::"r"(dst), "l"(tm), "r"(x), "r"(y), "r"(bar) : "memory");
}
__device__ __forceinline__ void tma3d_mc(uint32_t dst, const CUtensorMap* tm, int y, int z, uint32_t bar, uint16_t mask) {
    asm volatile("{.reg .pred p; elect.sync _|p,0xffffffff;\n"
                 "@p cp.async.bulk.tensor.3d.shared::cluster.global.mbarrier::complete_tx::bytes.multicast::cluster [%0],[%1,{0,%2,%3}],[%4],%5;}"
                 ::"r"(dst), "l"(tm), "r"(y), "r"(z), "r"(bar), "h"(mask) : "memory");
}
__device__ __forceinline__ void tma2d_mc(uint32_t dst, const CUtensorMap* tm, int x, int y, uint32_t bar, uint16_t mask, uint64_t pol) {
    asm volatile("{.reg .pred p; elect.sync _|p,0xffffffff;\n"
                 "@p cp.async.bulk.tensor.2d.shared::cluster.global.mbarrier::complete_tx::bytes.multicast::cluster.L2::cache_hint [%0],[%1,{%2,%3}],[%4],%5,%6;}"
                 ::"r"(dst), "l"(tm), "r"(x), "r"(y), "r"(bar), "h"(mask), "l"(pol) : "memory");
}
__device__ __forceinline__ void bulk_g2s1(uint32_t dst, const void* src, int bytes, uint32_t bar, uint64_t pol) {
    asm volatile("{.reg .pred p; elect.sync _|p,0xffffffff;\n"
                 "@p cp.async.bulk.shared::cluster.global.mbarrier::complete_tx::bytes.L2::cache_hint [%0],[%1],%2,[%3],%4;}" ::"r"(dst), "l"(src), "r"(bytes), "r"(bar), "l"(pol) : "memory");
}
__device__ __forceinline__ void mbar_expect1(uint32_t b, int bytes) {
    asm volatile("{.reg .pred p; elect.sync _|p,0xffffffff; @p mbarrier.arrive.expect_tx.shared::cta.b64 _,[%0],%1;}" ::"r"(b), "r"(bytes) : "memory");
}
__device__ __forceinline__ void st_async4(uint32_t a, uint32_t x, uint32_t y, uint32_t z, uint32_t w, uint32_t mb) {
    asm volatile("st.async.shared::cluster.mbarrier::complete_tx::bytes.v4.b32 [%0],{%1,%2,%3,%4},[%5];" ::"r"(a), "r"(x), "r"(y), "r"(z), "r"(w), "r"(mb) : "memory");
}
__device__ __forceinline__ void st_async2(uint32_t a, uint32_t x, uint32_t y, uint32_t mb) {
    asm volatile("st.async.shared::cluster.mbarrier::complete_tx::bytes.v2.b32 [%0],{%1,%2},[%3];" ::"r"(a), "r"(x), "r"(y), "r"(mb) : "memory");
}
#define LDSQ "ld.shared"
__device__ __forceinline__ uint4 lds128(uint32_t a) { uint4 v; asm volatile(LDSQ ".v4.u32 {%0,%1,%2,%3},[%4];" : "=r"(v.x), "=r"(v.y), "=r"(v.z), "=r"(v.w) : "r"(a) : "memory"); return v; }
__device__ __forceinline__ uint2 lds64(uint32_t a) { uint2 v; asm volatile(LDSQ ".v2.u32 {%0,%1},[%2];" : "=r"(v.x), "=r"(v.y) : "r"(a) : "memory"); return v; }
__device__ __forceinline__ uint32_t lds32(uint32_t a) { uint32_t v; asm volatile(LDSQ ".u32 %0,[%1];" : "=r"(v) : "r"(a) : "memory"); return v; }
__device__ __forceinline__ void sts128(uint32_t a, uint32_t x, uint32_t y, uint32_t z, uint32_t w) { asm volatile("st.shared.v4.u32 [%0],{%1,%2,%3,%4};" ::"r"(a), "r"(x), "r"(y), "r"(z), "r"(w) : "memory"); }
__device__ __forceinline__ void sts64(uint32_t a, uint32_t x, uint32_t y) { asm volatile("st.shared.v2.u32 [%0],{%1,%2};" ::"r"(a), "r"(x), "r"(y) : "memory"); }
__device__ __forceinline__ void sts32(uint32_t a, uint32_t x) { asm volatile("st.shared.u32 [%0],%1;" ::"r"(a), "r"(x) : "memory"); }
__device__ __forceinline__ uint4 ldsm4(uint32_t a) { uint4 v; asm volatile("ldmatrix.sync.aligned.m8n8.x4.shared.b16 {%0,%1,%2,%3},[%4];" : "=r"(v.x), "=r"(v.y), "=r"(v.z), "=r"(v.w) : "r"(a) : "memory"); return v; }
__device__ __forceinline__ uint4 ldsm4t(uint32_t a) { uint4 v; asm volatile("ldmatrix.sync.aligned.m8n8.x4.trans.shared.b16 {%0,%1,%2,%3},[%4];" : "=r"(v.x), "=r"(v.y), "=r"(v.z), "=r"(v.w) : "r"(a) : "memory"); return v; }
__device__ __forceinline__ uint32_t movm(uint32_t a) { uint32_t d; asm volatile("movmatrix.sync.aligned.m8n8.trans.b16 %0,%1;" : "=r"(d) : "r"(a)); return d; }
__device__ __forceinline__ uint32_t pack2(float lo, float hi) { uint32_t d; asm("cvt.rn.bf16x2.f32 %0,%1,%2;" : "=r"(d) : "f"(hi), "f"(lo)); return d; }
__device__ __forceinline__ uint32_t hadd2(uint32_t a, uint32_t b) { uint32_t d; asm("add.rn.bf16x2 %0,%1,%2;" : "=r"(d) : "r"(a), "r"(b)); return d; }
__device__ __forceinline__ float blo(uint32_t v) { return __uint_as_float(v << 16); }
__device__ __forceinline__ float bhi(uint32_t v) { return __uint_as_float(v & 0xffff0000u); }
__device__ __forceinline__ float rbf(float x) { return __uint_as_float(pack2(0.f, x)); }
__device__ __forceinline__ float ex2(float x) { float y; asm("ex2.approx.ftz.f32 %0,%1;" : "=f"(y) : "f"(x)); return y; }
__device__ __forceinline__ float rcp(float x) { float y; asm("rcp.approx.ftz.f32 %0,%1;" : "=f"(y) : "f"(x)); return y; }
__device__ __forceinline__ void mma16(float* c, uint32_t a0, uint32_t a1, uint32_t a2, uint32_t a3, uint32_t b0, uint32_t b1) {
    asm volatile("mma.sync.aligned.m16n8k16.row.col.f32.bf16.bf16.f32 {%0,%1,%2,%3},{%4,%5,%6,%7},{%8,%9},{%0,%1,%2,%3};"
                 : "+f"(c[0]), "+f"(c[1]), "+f"(c[2]), "+f"(c[3]) : "r"(a0), "r"(a1), "r"(a2), "r"(a3), "r"(b0), "r"(b1));
}
__device__ __forceinline__ void mma8(float* c, uint32_t a0, uint32_t a1, uint32_t b0) {
    asm volatile("mma.sync.aligned.m16n8k8.row.col.f32.bf16.bf16.f32 {%0,%1,%2,%3},{%4,%5},{%6},{%0,%1,%2,%3};"
                 : "+f"(c[0]), "+f"(c[1]), "+f"(c[2]), "+f"(c[3]) : "r"(a0), "r"(a1), "r"(b0));
}
__device__ __forceinline__ uint4 ld_rlx128(const uint4* p) {
    uint4 v;
    asm volatile("{.reg .b128 t; ld.relaxed.gpu.global.b128 t,[%4]; mov.b128 {%0,%1,%2,%3},t;}" : "=r"(v.x), "=r"(v.y), "=r"(v.z), "=r"(v.w) : "l"(p) : "memory");
    return v;
}
__device__ __forceinline__ void st_rlx128(uint4* p, uint32_t x, uint32_t y, uint32_t z, uint32_t w) {
    asm volatile("{.reg .b128 t; mov.b128 t,{%1,%2,%3,%4}; st.relaxed.gpu.global.b128 [%0],t;}" ::"l"(p), "r"(x), "r"(y), "r"(z), "r"(w) : "memory");
}
__device__ __forceinline__ uint4 ldcg128(const uint4* p) { uint4 v; asm volatile("ld.global.cg.v4.u32 {%0,%1,%2,%3},[%4];" : "=r"(v.x), "=r"(v.y), "=r"(v.z), "=r"(v.w) : "l"(p) : "memory"); return v; }
__device__ __forceinline__ void red_release(unsigned* p, unsigned v) {
    asm volatile("fence.proxy.async; red.relaxed.gpu.global.add.u32 [%0],%1;" ::"l"(p), "r"(v) : "memory");
}
__device__ __forceinline__ void wait_cnt(const unsigned* p, unsigned target) {
    unsigned v; int n = 0;
    while (true) {
        asm volatile("ld.acquire.gpu.global.u32 %0,[%1];" : "=r"(v) : "l"(p) : "memory");
        if (v >= target) break;
        if (++n > 3000000) __trap();
        __nanosleep(40);
    }
}
__device__ __forceinline__ void wait_cnt_warp(const unsigned* p, unsigned target) {
    unsigned v; int n = 0;
    while (true) {
        asm volatile("ld.acquire.gpu.global.u32 %0,[%1];" : "=r"(v) : "l"(p) : "memory");
        if (__all_sync(0xffffffffu, v >= target)) break;
        if (++n > 3000000) __trap();
    }
}
__device__ __forceinline__ uint64_t mkdesc(uint32_t addr, uint32_t lbo, uint32_t sbo, uint32_t sw) {
    return (uint64_t)((addr & 0x3FFFF) >> 4) | ((uint64_t)(lbo >> 4) << 16) | ((uint64_t)(sbo >> 4) << 32) | ((uint64_t)sw << 62);
}
__device__ __forceinline__ void wg_fence() { asm volatile("wgmma.fence.sync.aligned;" ::: "memory"); }
__device__ __forceinline__ void wg_commit() { asm volatile("wgmma.commit_group.sync.aligned;" ::: "memory"); }
template <int N> __device__ __forceinline__ void wg_wait() { asm volatile("wgmma.wait_group.sync.aligned %0;" ::"n"(N) : "memory"); }
#define R8(c, o) "+f"(c[o]), "+f"(c[o + 1]), "+f"(c[o + 2]), "+f"(c[o + 3]), "+f"(c[o + 4]), "+f"(c[o + 5]), "+f"(c[o + 6]), "+f"(c[o + 7])
#define R32(c, o) R8(c, o), R8(c, o + 8), R8(c, o + 16), R8(c, o + 24)
#define S32A "%0,%1,%2,%3,%4,%5,%6,%7,%8,%9,%10,%11,%12,%13,%14,%15,%16,%17,%18,%19,%20,%21,%22,%23,%24,%25,%26,%27,%28,%29,%30,%31"
#define S32B ",%32,%33,%34,%35,%36,%37,%38,%39,%40,%41,%42,%43,%44,%45,%46,%47,%48,%49,%50,%51,%52,%53,%54,%55,%56,%57,%58,%59,%60,%61,%62,%63"
#define S32C ",%64,%65,%66,%67,%68,%69,%70,%71,%72,%73,%74,%75,%76,%77,%78,%79,%80,%81,%82,%83,%84,%85,%86,%87,%88,%89,%90,%91,%92,%93,%94,%95"
#define S32D ",%96,%97,%98,%99,%100,%101,%102,%103,%104,%105,%106,%107,%108,%109,%110,%111,%112,%113,%114,%115,%116,%117,%118,%119,%120,%121,%122,%123,%124,%125,%126,%127"
#define W8(c, o) "=f"(c[o]), "=f"(c[o + 1]), "=f"(c[o + 2]), "=f"(c[o + 3]), "=f"(c[o + 4]), "=f"(c[o + 5]), "=f"(c[o + 6]), "=f"(c[o + 7])
#define W32(c, o) W8(c, o), W8(c, o + 8), W8(c, o + 16), W8(c, o + 24)
template <bool ACC> __device__ __forceinline__ void wgmma256(float* c, uint64_t da, uint64_t db) {
    if (ACC) asm volatile("wgmma.mma_async.sync.aligned.m64n256k16.f32.bf16.bf16 {" S32A S32B S32C S32D "},%128,%129,1,1,1,0,1;"
                          : R32(c, 0), R32(c, 32), R32(c, 64), R32(c, 96) : "l"(da), "l"(db));
    else asm volatile("wgmma.mma_async.sync.aligned.m64n256k16.f32.bf16.bf16 {" S32A S32B S32C S32D "},%128,%129,0,1,1,0,1;"
                      : W32(c, 0), W32(c, 32), W32(c, 64), W32(c, 96) : "l"(da), "l"(db));
}
template <bool ACC> __device__ __forceinline__ void wgmma128r(float* c, const uint4& a, uint64_t db) {
    if (ACC) asm volatile("wgmma.mma_async.sync.aligned.m64n128k16.f32.bf16.bf16 {" S32A S32B "},{%64,%65,%66,%67},%68,1,1,1,1;"
                          : R32(c, 0), R32(c, 32) : "r"(a.x), "r"(a.y), "r"(a.z), "r"(a.w), "l"(db));
    else asm volatile("wgmma.mma_async.sync.aligned.m64n128k16.f32.bf16.bf16 {" S32A S32B "},{%64,%65,%66,%67},%68,0,1,1,1;"
                      : W32(c, 0), W32(c, 32) : "r"(a.x), "r"(a.y), "r"(a.z), "r"(a.w), "l"(db));
}
template <int N> __device__ __forceinline__ void reg_inc() { asm volatile("setmaxnreg.inc.sync.aligned.u32 %0;" ::"n"(N)); }
template <int N> __device__ __forceinline__ void reg_dec() { asm volatile("setmaxnreg.dec.sync.aligned.u32 %0;" ::"n"(N)); }

#define PROF(cond, idx) do {} while (0)
#define CPROF(k) do {} while (0)

constexpr int S_GATE = 232440, S_TAG = 232444, S_XBAR = 232432;
constexpr float SC_LOG2E = 0.08838834764831845f * 1.4426950408889634f;

__device__ __forceinline__ float2 ln_finish(float mean, float var) {
    float sd; asm("sqrt.approx.f32 %0,%1;" : "=f"(sd) : "f"(rbf(rbf(var) + 1e-5f)));
    sd = rbf(sd);
    return make_float2(rbf(mean), sd);
}

__device__ __forceinline__ float4 row_stats(const uint4* src, int stride) {
    const int g = (threadIdx.x & 31) >> 2;
    uint4 v[16];
#pragma unroll
    for (int i = 0; i < 16; i++) v[i] = ldcg128(src + i * stride);
    float a[4] = {0, 0, 0, 0}, q0[4] = {0, 0, 0, 0}, q1[4] = {0, 0, 0, 0}, q2[4] = {0, 0, 0, 0}, q3[4] = {0, 0, 0, 0};
#pragma unroll
    for (int i = 0; i < 16; i++) {
        mma16(a, v[i].x, v[i].y, v[i].z, v[i].w, 0x3f803f80u, 0x3f803f80u);
        mma8(q0, v[i].x, v[i].y, v[i].x); mma8(q1, v[i].x, v[i].y, v[i].y);
        mma8(q2, v[i].z, v[i].w, v[i].z); mma8(q3, v[i].z, v[i].w, v[i].w);
    }
    return make_float4(a[0], (g & 1) ? q0[1] + q2[1] : q0[0] + q2[0], a[2], (g & 1) ? q1[3] + q3[3] : q1[2] + q3[2]);
}
__device__ __forceinline__ void x1_stats(int i) {
    const int lane = threadIdx.x & 31, g = lane >> 2, c = lane & 3;
    const float4 r = row_stats(g_xA[0] + i * 512 + lane, 32);
    float2* dst = g_st[0] + (i >> 4) * 2048 + ((i < 32 ? 4 : 0) + (i & 1)) * 128 + ((i >> 1) & 7) * 16 + g;
    if (c == (g >> 1)) { dst[0] = make_float2(r.x, r.y); dst[8] = make_float2(r.z, r.w); g_ln0[i * 8 + g] = 0; }
    __syncwarp();
    if (lane == 0) red_release(cnt_ptr(C_ST, i >> 4), 1);
}
__global__ void stats_kernel() { x1_stats(blockIdx.x * 4 + (threadIdx.x >> 5)); }

#define NT 9
#define RH 104
#define RW0 200
#define NPD 9
#define NTO 12
#define DP1 9
#define GPW 0
#define GPJ 0
#define PACE 2
#define EARLY 4
#define G2I 4
#define VE 4
#define VF 8
constexpr int R_WV = 0, R_WO = 65536, R_T = 131072, R_M = R_T + 20480, R_LOC = R_M + 4096, R_REM = R_LOC + 6144, R_O = R_REM + 12288, R_SX = R_O + 2048,
              R_IL = R_SX + 5120, XS = R_IL + 128 - R_T, R_BAR = 231936, R_Z = R_BAR + 128  , R_STQ = 0, R_STK = 65536, R_STV = 131072;
static_assert(R_T + 2 * XS <= R_BAR && R_BAR + 256 <= S_XBAR, "smem map");
enum { RB_INIT = 0, RB_V = 4  , RB_QK = 8  , RB_T = 12  , RB_N = 16 };
enum { NB_MF = 1  , NB_LOC = 3  , NB_PAIR = 5  , NB_O = 9  , NB_XG = 11  , NB_W = 13 };
__device__ __forceinline__ uint32_t clk32() { return (uint32_t)clock64(); }

__device__ __forceinline__ char* acc_base() { return (char*)(((size_t)g_acc + 131071) & ~(size_t)131071); }
__device__ __forceinline__ uint32_t acc_slice(uint32_t s6) { return (s6 & 1) * 256 + (s6 >> 1) * 1024; }
__device__ __forceinline__ uint32_t acc_main(uint32_t rank, uint32_t tid) { return acc_slice(rank * 32 + (tid >> 3)) + (tid & 7) * 16; }
__device__ __forceinline__ uint32_t acc_extra(uint32_t rank, uint32_t tid) { return 65536 + acc_slice(((tid >> 5) & 1) + rank * 4 + (tid >> 6) * 8) + (tid & 31) * 4; }
__device__ __forceinline__ uint32_t acc_slot(uint32_t s) { return (s & 1) * 128 + (s & 2) * 256; }
__device__ __forceinline__ void acc_init(const __nv_bfloat16* mem0, int i) {
    const uint32_t tid = i & 255, rank = (i >> 8) & 1, slot = (i >> 9) & 3, X = i >> 11;
    uint32_t v[5] = {0, 0, 0, 0, 0};
    if (slot == 3) {
        const uint16_t* m = (const uint16_t*)mem0 + (tid & 3) * 1024 + rank * 256 + (tid >> 5) * 32 + ((tid >> 2) & 7);
#pragma unroll
        for (int k = 0; k < 4; k++) v[k] = __ldg(m + k * 8) | ((uint32_t)__ldg(m + k * 8 + 512) << 16);
        v[4] = (v[3] >> 16) | 0x42000000u; v[3] = (v[3] & 0xffff) | 0x42000000u;
    }
    *(uint4*)(acc_base() + X * 32768 + acc_slot(slot) + acc_main(rank, tid)) = make_uint4(v[0], v[1], v[2], v[3]);
    *(uint32_t*)(acc_base() + X * 1024 + acc_slot(slot) + acc_extra(rank, tid)) = v[4];
}
__global__ void acc_init_kernel(const __nv_bfloat16* mem0) { acc_init(mem0, blockIdx.x * 256 + threadIdx.x); }

struct RecW { uint32_t am, ae, ah, dp, lp, lpw, vo, sb, bar, zero, ts, tn; };
__device__ __forceinline__ uint32_t vadd(uint32_t a, uint32_t b) { uint32_t d; asm volatile("add.u32 %0,%1,%2;" : "=r"(d) : "r"(a), "r"(b)); return d; }
__device__ __forceinline__ uint32_t vshr(uint32_t a, int n) { uint32_t d; asm volatile("shr.u32 %0,%1,%2;" : "=r"(d) : "r"(a), "r"(n)); return d; }
__device__ __forceinline__ uint64_t gptr(uint32_t lo, uint32_t hi) { uint64_t d; asm("mov.b64 %0,{%1,%2};" : "=l"(d) : "r"(lo), "r"(hi)); return d; }
__device__ __forceinline__ void sfence(uint32_t zero) { asm volatile("{.reg .pred p; setp.ne.u32 p,%0,0; @p exit;}" ::"r"(zero) : "memory"); }
#define SF sfence(k.zero)
#define TS(i) do {} while (0)
#define TSN(i) do {} while (0)
#define TSET(it, slot) do {} while (0)
struct Gat { uint32_t x, y, z, w, e; };
template <int X>
__device__ __forceinline__ void gat_issue(Gat& g, const RecW& k, int s, uint32_t dep) {
    const uint32_t o = acc_slot(s + 3) + dep;
    asm volatile("{.reg .b128 t; ld.relaxed.gpu.global.b128 t,[%5+%7]; mov.b128 {%0,%1,%2,%3},t; ld.relaxed.gpu.global.u32 %4,[%6+%8];}"
                 : "=r"(g.x), "=r"(g.y), "=r"(g.z), "=r"(g.w), "=r"(g.e) : "l"(gptr(k.am + o, k.ah)), "l"(gptr(k.ae + o, k.ah)), "n"(X * 32768), "n"(X * 1024) : "memory");
}
template <int X>
__device__ __forceinline__ bool gat_store(const Gat& g, const RecW& k) {
    uint32_t c;
    asm volatile("prmt.b32 %0,%1,%2,0x7632;" : "=r"(c) : "r"(g.w), "r"(g.e));
    SF;
    asm volatile("{.reg .b32 t; prmt.b32 t,%4,%6,0x5410; stmatrix.sync.aligned.m8n8.x4.trans.shared.b16 [%0+%5],{%1,%2,%3,t};}" ::"r"(k.lpw), "r"(g.x), "r"(g.y), "r"(g.z), "r"(g.w), "n"(R_M + X * XS), "r"(g.e) : "memory");
    return __all_sync(0xffffffffu, c == 0x42004200u);
}
template <int X>
__device__ __forceinline__ void gat_finish(bool ok, const RecW& k, int s) {
    if (!ok) {
        int n = s;
        while (true) {
            Gat g;
            gat_issue<X>(g, k, n, 0);
            if (gat_store<X>(g, k)) break;
            n += 4;
            if (n > 8000000) __trap();
        }
    }
}
__device__ __forceinline__ uint4 lds128o(uint32_t a, int o) { uint4 v; asm volatile("{.reg .b32 t; add.u32 t,%4,%5; ld.shared.v4.u32 {%0,%1,%2,%3},[t];}" : "=r"(v.x), "=r"(v.y), "=r"(v.z), "=r"(v.w) : "r"(a), "r"(o) : "memory"); return v; }
__device__ __forceinline__ uint4 ldsm4o(uint32_t a, int o) { uint4 v; asm volatile("{.reg .b32 t; add.u32 t,%4,%5; ldmatrix.sync.aligned.m8n8.x4.shared.b16 {%0,%1,%2,%3},[t];}" : "=r"(v.x), "=r"(v.y), "=r"(v.z), "=r"(v.w) : "r"(a), "r"(o) : "memory"); return v; }
__device__ __forceinline__ uint4 ldsm4to(uint32_t a, int o) { uint4 v; asm volatile("{.reg .b32 t; add.u32 t,%4,%5; ldmatrix.sync.aligned.m8n8.x4.trans.shared.b16 {%0,%1,%2,%3},[t];}" : "=r"(v.x), "=r"(v.y), "=r"(v.z), "=r"(v.w) : "r"(a), "r"(o) : "memory"); return v; }
__device__ __forceinline__ uint2 lds64o(uint32_t a, int o) { uint2 v; asm volatile("{.reg .b32 t; add.u32 t,%2,%3; ld.shared.v2.u32 {%0,%1},[t];}" : "=r"(v.x), "=r"(v.y) : "r"(a), "r"(o) : "memory"); return v; }
__device__ __forceinline__ void sts128o(uint32_t a, int o, uint32_t x, uint32_t y, uint32_t z, uint32_t w) { asm volatile("{.reg .b32 t; add.u32 t,%0,%5; st.shared.v4.u32 [t],{%1,%2,%3,%4};}" ::"r"(a), "r"(x), "r"(y), "r"(z), "r"(w), "r"(o) : "memory"); }
__device__ __forceinline__ void sts64o(uint32_t a, int o, uint32_t x, uint32_t y) { asm volatile("{.reg .b32 t; add.u32 t,%0,%3; st.shared.v2.u32 [t],{%1,%2};}" ::"r"(a), "r"(x), "r"(y), "r"(o) : "memory"); }
__device__ __forceinline__ uint32_t vxor(uint32_t a, uint32_t b) { uint32_t d; asm volatile("xor.b32 %0,%1,%2;" : "=r"(d) : "r"(a), "r"(b)); return d; }
#define WLD(base, i) wt[i] = lds128o(k.lpw, (base) + (i) * 4096)
template <int PASS, int X, int NP>
__device__ __forceinline__ void rec_qkv(const RecW& k, int s, const uint32_t (*wq)[4], const uint32_t (*wk)[4], uint4* wt, Gat& g2, int s2) {
    constexpr bool BWD = PASS == 2;
    float aq[4] = {0, 0, 0, 0}, ak[4] = {0, 0, 0, 0}, av[4] = {0, 0, 0, 0};
    constexpr int ma = R_M + X * XS;
    if (BWD) { TS(1); gat_finish<1>(gat_store<1>(g2, k), k, s); }
    bar_sync(NB_MF + X, 256);
    uint4 mf = ldsm4o(k.lp, ma + (BWD ? 7 : 0) * 512);
    if (BWD) TS(2); else { TS(0); TSN(13); }
#pragma unroll
    for (int ii = 0; ii < 8; ii++) {
        const int i = BWD ? 7 - ii : ii;
        const uint4 m = mf;
        if (ii < 7) mf = ldsm4o(k.lp, ma + (BWD ? i - 1 : i + 1) * 512);
        if (PASS == 1 && ii == G2I) gat_issue<1>(g2, k, s2, 0);
        SF;
#pragma unroll
        for (int hh = 0; hh < 2; hh++) {
            const int h = BWD ? 1 - hh : hh, ks = 2 * i + h;
            const uint32_t b0 = h ? m.z : m.x, b1 = h ? m.w : m.y;
            mma16(aq, wq[ks][0], wq[ks][1], wq[ks][2], wq[ks][3], b0, b1);
            mma16(ak, wk[ks][0], wk[ks][1], wk[ks][2], wk[ks][3], b0, b1);
            SF;
            mma16(av, wt[ks].x, wt[ks].y, wt[ks].z, wt[ks].w, b0, b1);
            SF;
            if (!BWD && ks + NP < 16) WLD(R_WV, ks + NP < 16 ? ks + NP : 0);
            if (BWD && ks >= NT) WLD(R_WV, ks >= NT ? ks - NT : 0);
            SF;
        }
    }
    const uint32_t ra = vadd(k.lpw, k.dp + R_REM + X * XS + (s & 1) * 6144), va = ((vshr(k.lp, 7) & 1) * 48 ^ k.lp ^ (k.vo & 64)) + (k.vo & ~64u);
    const uint32_t x0 = movm(pack2(aq[0], aq[1])), x1 = movm(pack2(aq[2], aq[3])), x2 = movm(pack2(ak[0], ak[1])), x3 = movm(pack2(ak[2], ak[3]));
    SF;
    asm volatile("stmatrix.sync.aligned.m8n8.x2.shared.b16 [%0+%3],{%1,%2};" ::"r"(va), "r"(pack2(av[0], av[1])), "r"(pack2(av[2], av[3])), "n"(R_LOC + X * XS) : "memory");
    SF;
    st_async4(ra, x0, x1, x2, x3, k.bar + X * 16);
    asm volatile("st.shared.v4.u32 [%0+%5],{%1,%2,%3,%4};" ::"r"(k.lpw), "r"(x0), "r"(x1), "r"(x2), "r"(x3), "n"(R_LOC + X * XS) : "memory");
    bar_arrive(NB_LOC + X, 320);
    SF;
    TS(BWD ? 4 : 3);
}
template <bool BWD, int X>
__device__ __forceinline__ void rec_out(const RecW& k, int s, uint4* wt, Gat& g, int s1) {
    if (BWD) { WLD(R_WO, 17 - NTO); WLD(R_WO, 16 - NTO); }
    TS(BWD ? 8 : 5);
    bar_sync(NB_O + X, 320);
    float r0[4] = {0, 0, 0, 0}, r1[4] = {0, 0, 0, 0};
    constexpr int oa = R_O + X * XS;
    uint4 bn = lds128o(k.lp, oa + (BWD ? 3 : 0) * 512);
    TS(BWD ? 9 : 6);
    uint2 il;
    uint64_t pm, pe;
#pragma unroll
    for (int ii = 0; ii < 4; ii++) {
        const int i = BWD ? 3 - ii : ii;
        const uint4 b = bn;
        if (ii < 3) bn = lds128o(k.lp, oa + (BWD ? i - 1 : i + 1) * 512);
        else { asm volatile("ld.shared.v2.u32 {%0,%1},[%2+%3];" : "=r"(il.x), "=r"(il.y) : "r"((vshr(k.ae, 2) & 3) * 8 + k.sb), "n"(R_IL + X * XS) : "memory"); pm = gptr(vadd(k.am, acc_slot(s)), k.ah); pe = gptr(vadd(k.ae, acc_slot(s)), k.ah); }
        SF;
        if (BWD && EARLY == ii + 1) { gat_issue<0>(g, k, s1 + 1, 0); SF; }
#pragma unroll
        for (int nn = 0; nn < 4; nn++) {
            const int n = BWD ? 3 - nn : nn, f = 4 * i + n, nx = BWD ? f - NTO + 2 : f + NTO - 2;
            mma16((n & 1) ? r1 : r0, wt[f].x, wt[f].y, wt[f].z, wt[f].w, n >> 1 ? b.z : b.x, n >> 1 ? b.w : b.y);
            SF;
            if (ii * 4 + nn >= 2 && nx >= 0 && nx < 16) WLD(R_WO, nx & 15);
            SF;
        }
    }
    const float i0 = __uint_as_float(il.x), i1 = __uint_as_float(il.y);
    asm volatile("red.relaxed.gpu.global.add.noftz.v4.bf16x2 [%0+%5],{%1,%2,%3,%4};" ::"l"(pm),
                 "r"(pack2(r0[0] * i0, r0[1] * i1)), "r"(pack2(r0[2] * i0, r0[3] * i1)), "r"(pack2(r1[0] * i0, r1[1] * i1)), "r"(pack2(r1[2] * i0, 1.f)), "n"(X * 32768) : "memory");
    asm volatile("red.relaxed.gpu.global.add.noftz.bf16x2 [%0+%2],%1;" ::"l"(pe), "r"(pack2(r1[3] * i1, 1.f)), "n"(X * 1024) : "memory");
    bar_arrive(NB_XG + X, 320);
    SF;
    TS(BWD ? 10 : 7);
}
__device__ __forceinline__ uint32_t pause(uint32_t v, int n) {
#pragma unroll
    for (int i = 0; i < n; i++) asm volatile("shfl.sync.bfly.b32 %0,%0,0,0x1f,0xffffffff;" : "+r"(v));
    return v;
}
template <bool DUAL, int X>
__device__ __forceinline__ void rec_step(const RecW& k, int s, int s2, const uint32_t (*wq)[4], const uint32_t (*wk)[4], uint4* wt) {
    constexpr int NP = NPD;
    uint4 wo[16];
    Gat g;
    rec_qkv<DUAL ? 1 : 0, X, NP>(k, s, wq, wk, wt, g, s2);
    if (DUAL) rec_qkv<2, 1, NP>(k, s2, wq, wk, wt, g, s2);
    uint32_t wa = k.lpw;
#pragma unroll
    for (int i = 0; i < NTO; i++) {
        wo[i] = lds128o(wa, R_WO + i * 4096);
        if (i % PACE == PACE - 1) wa = k.lpw + (wo[i].x & k.zero);
        SF;
    }
    rec_out<false, X>(k, s, wo, g, s);
    if (DUAL) { rec_out<true, 1>(k, s2, wo, g, s); if (!EARLY) gat_issue<0>(g, k, s + 1, 0); SF; }
#pragma unroll
    for (int i = 0; i < NP; i++) { WLD(R_WV, i); SF; }
    if (!DUAL) gat_issue<X>(g, k, s + 1, pause(wt[NP - 1].x & k.zero, DP1));
    TS(12);
    gat_finish<X>(gat_store<X>(g, k), k, s + 1);
    TS(11);
}

__device__ __forceinline__ void rec_fetch(const CUtensorMap* tm, uint32_t dst, int x, int y, int nx, uint32_t bar) {
#pragma unroll 1
    for (int j = 0; j < 8; j++) tma2d(dst + j * 8192, tm, x + (j / (8 / nx)) * 64, y + (j % (8 / nx)) * 64, bar);
}
__device__ __forceinline__ void rec_weights(const Params& p, uint32_t sb, int head, uint32_t rank, int w) {
    const int lane = threadIdx.x & 31, t = w & 3, WG = w >> 2;
    uint32_t wq[16][4], wk[16][4];
    const uint32_t rowo = (((lane >> 4) << 3) + (lane & 7)) * 128;
    const uint32_t woff = sb + WG * 32768 + rowo + (((2 * t + ((lane >> 3) & 1)) ^ (lane & 7)) << 4);
    const uint32_t qoff = sb + ((w & 1) ? R_STK : R_STQ) + WG * 32768 + rowo + (((2 * (t & 2) + ((lane >> 3) & 1)) ^ (lane & 7)) << 4);
    const uint32_t lw = sb + (lane ^ (lane >> 3)) * 16;
    PROF(threadIdx.x == 0, 3501);
    PROF(threadIdx.x == 0, 3502);
    mbar_wait(sb + R_BAR + RB_INIT * 8, 0);
    PROF(threadIdx.x == 0, 3503);
#pragma unroll
    for (int ks = 0; ks < 16; ks++) {
        uint4 a = ldsm4t(qoff + ks * 2048), b = ldsm4t((qoff ^ 32) + ks * 2048);
        wq[ks][0] = a.x; wq[ks][1] = a.y; wq[ks][2] = a.z; wq[ks][3] = a.w;
        wk[ks][0] = b.x; wk[ks][1] = b.y; wk[ks][2] = b.z; wk[ks][3] = b.w;
    }
    bar_sync(NB_W, 256);
#pragma unroll 4
    for (int ks = 0; ks < 16; ks++) { const uint4 a = ldsm4t(woff + R_STV + ks * 2048); sts128(lw + w * 512 + R_WV + ks * 4096, a.x, a.y, a.z, a.w); }
    bar_sync(NB_W, 256);
    if (threadIdx.x == 0) {
        mbar_expect(sb + R_BAR + RB_INIT * 8, 65536);
        rec_fetch(&p.tm[4], sb + R_STV, rank * 256, head * 128, 4, sb + R_BAR + RB_INIT * 8);
    }
    __syncwarp();
    mbar_wait(sb + R_BAR + RB_INIT * 8, 1);
#pragma unroll 4
    for (int f = 0; f < 16; f++) {
        const uint4 a = ldsm4t(sb + R_STV + (w >> 1) * 16384 + (f >> 1) * 2048 + rowo + ((((w & 1) * 4 + (f & 1) * 2 + ((lane >> 3) & 1)) ^ (lane & 7)) << 4));
        sts128(lw + w * 512 + R_WO + f * 4096, a.x, a.y, a.z, a.w);
    }
    PROF(threadIdx.x == 0, 3504);
    __syncthreads();
    cluster_sync();
    PROF(threadIdx.x == 0, 3505);
    RecW k;
    k.am = __shfl_sync(0xffffffffu, (uint32_t)(size_t)acc_base() + acc_main(rank, threadIdx.x), lane);
    k.ae = __shfl_sync(0xffffffffu, (uint32_t)(size_t)acc_base() + acc_extra(rank, threadIdx.x), lane);
    k.ah = (uint32_t)((size_t)acc_base() >> 32);
    k.sb = sb; k.zero = p.zero;

    k.dp = mapa(sb, rank ^ 1) - sb;
    k.lp = __shfl_sync(0xffffffffu, lw, lane);
    k.lpw = __shfl_sync(0xffffffffu, lw + w * 512, lane);
    k.vo = 4096 + w * 256 + (w & 1) * 64;
    k.bar = sb + k.dp + R_BAR + (RB_QK + WG) * 8;
    int it = 0;
    uint4 wt[16];
#pragma unroll
    for (int i = 0; i < NPD; i++) WLD(R_WV, i);
    gat_finish<0>(false, k, 0);
#pragma unroll 1
    for (; it < min(p.b1, p.e0); it++) { TSET(it, w == GPW ? 0 : 3); rec_step<false, 0>(k, it, it, wq, wk, wt); }
#pragma unroll 1
    for (; it < p.e0; it++) { TSET(it, w == GPW ? 0 : 3); rec_step<true, 0>(k, it, it - p.b1, wq, wk, wt); }
    if (it < p.nit) gat_finish<1>(false, k, it - p.b1);
#pragma unroll 1
    for (; it < p.nit; it++) { TSET(it, w == GPW ? 0 : 3); rec_step<false, 1>(k, it - p.b1, it - p.b1, wq, wk, wt); }
}

__device__ __forceinline__ void mma16_top(float* c, uint32_t a0, uint32_t a2, uint32_t b0, uint32_t b1) {
    asm volatile("{.reg .b32 j; mma.sync.aligned.m16n8k16.row.col.f32.bf16.bf16.f32 {%0,%1,%2,%3},{%4,j,%5,j},{%6,%7},{%0,%1,%2,%3};}"
                 : "+f"(c[0]), "+f"(c[1]), "+f"(c[2]), "+f"(c[3]) : "r"(a0), "r"(a2), "r"(b0), "r"(b1));
}
__device__ __forceinline__ void rec_load_tile(uint32_t sb, int X, int j, int s, int head, uint32_t rank) {
    const uint32_t bar = sb + R_BAR + (RB_T + X * 2 + j) * 8;
    mbar_expect1(bar, j ? 4096 : 16384);
    bulk_g2s1(sb + R_T + X * XS + j * 16384, g_qkv[X] + (size_t)(s * 32 + head) * 1536 + (j ? rank * 256 : 512), j ? 4096 : 16384, bar, POL_LAST);
}
__device__ __forceinline__ bool chunk_ready(int X, int j, int s) {
    unsigned v;
    asm volatile("ld.relaxed.gpu.global.u32 %0,[%1];" : "=r"(v) : "l"(cnt_ptr(C_QKV0 + X, (s >> 2) + j * 16)) : "memory");
    return __all_sync(0xffffffffu, v >= (256 >> j));
}
__device__ __forceinline__ uint4 hadd4(uint4 a, uint4 b) { return make_uint4(hadd2(a.x, b.x), hadd2(a.y, b.y), hadd2(a.z, b.z), hadd2(a.w, b.w)); }
struct RecH { uint32_t lw, lm, lq, lv, lu, sa, sp, xb, sb, zero, ts, tn; };
__device__ __forceinline__ void rec_publish(int X, int s) {
    asm volatile("{.reg .pred p; cp.async.bulk.wait_group 0; elect.sync _|p,0xffffffff; @p red.relaxed.gpu.global.add.u32 [%0],4;}" ::"l"(cnt_ptr(C_O0 + X, s >> 2)) : "memory");
}
__device__ __forceinline__ void rec_mattn(const RecH& k, uint32_t dp, int X, int j, int s, uint4 (*V)[4], uint4* vm, uint4* kmm) {
    const uint32_t sb = k.sb, to = R_T, lo = R_LOC, ro = R_REM + (s & 1) * 6144;
    const uint32_t bar = sb + R_BAR + (X * 2 + j) * 8;
    uint4 K[2][4];
    mbar_wait(sb + R_BAR + (RB_T + X * 2) * 8, s & 1);
    TS(1);
#pragma unroll
    for (int i = 0; i < 8; i++) K[i >> 2][i & 3] = ldsm4o(k.lm, (to + (i >> 2) * 1024 + ((i >> 1) & 1) * 4096 + (i & 1) * 512));
    asm volatile("cp.async.bulk.wait_group 0;" ::: "memory");
    bar_sync(NB_LOC + X, 320);
    fence_async_smem();
    asm volatile("{.reg .pred p; elect.sync _|p,0xffffffff; @p cp.async.bulk.shared::cluster.shared::cta.mbarrier::complete_tx::bytes [%0],[%1],1024,[%2];}"
                 ::"r"(k.xb + dp + ro + 4096), "r"(k.xb + lo + 4096), "r"(bar + dp + RB_V * 8) : "memory");
    uint4 u[4];
#pragma unroll
    for (int i = 0; i < 4; i++) u[i] = ldsm4o(k.lm, (lo + i * 512));
    TS(2);
    mbar_wait(bar + RB_QK * 8, s & 1);
    TS(3);
    float S[5][4];
#pragma unroll
    for (int i = 0; i < 5; i++) S[i][0] = S[i][1] = S[i][2] = S[i][3] = 0;
    {
        uint4 r[4];
#pragma unroll
        for (int i = 0; i < 4; i++) r[i] = ldsm4o(k.lm, (ro + i * 512));
        SF;
#pragma unroll
        for (int e = 0; e < 2; e++) {
            uint4& km = u[2 * e + 1];
            const uint32_t q0 = hadd2(u[2 * e].x, r[2 * e].x), q1 = hadd2(u[2 * e].y, r[2 * e].y);
            mma16_top(S[0], q0, q1, K[e][0].x, K[e][0].y);
            km.x = hadd2(km.x, r[2 * e + 1].x); km.y = hadd2(km.y, r[2 * e + 1].y);
            SF;
            mma16_top(S[1], q0, q1, K[e][1].x, K[e][1].y);
            const uint32_t q2 = hadd2(u[2 * e].z, r[2 * e].z), q3 = hadd2(u[2 * e].w, r[2 * e].w);
            SF;
            mma16_top(S[2], q0, q1, K[e][2].x, K[e][2].y);
            km.z = hadd2(km.z, r[2 * e + 1].z); km.w = hadd2(km.w, r[2 * e + 1].w);
            SF;
            mma16_top(S[3], q0, q1, K[e][3].x, K[e][3].y);
            mma16_top(S[4], q0, q1, km.x, km.y);
            SF;
#pragma unroll
            for (int i = 0; i < 4; i++) {
                mma16_top(S[i], q2, q3, K[e][i].z, K[e][i].w); SF;
            }
            mma16_top(S[4], q2, q3, km.z, km.w);
            SF;
        }
    }
#define VLD(a, b) _Pragma("unroll") for (int i = (a); i < (b); i++) V[i >> 2][i & 3] = ldsm4to((i & 1) ? lv2 : k.lv, (to + 8192 + (i >> 2) * 4096 + ((i >> 1) & 1) * 1024))
    const uint32_t lv2 = vxor(k.lv, 0x20), lh = k.lw - (vshr(k.lw - k.xb, 1) & 0xf8);
    VLD(0, VE);
    SF;
    const uint32_t sxr = k.sa, sxw = k.sp;
    sts128o(k.lw, sxw, __float_as_uint(S[0][0]), __float_as_uint(S[0][1]), __float_as_uint(S[1][0]), __float_as_uint(S[1][1]));
    SF;
    sts128o(k.lw, (sxw + 512), __float_as_uint(S[2][0]), __float_as_uint(S[2][1]), __float_as_uint(S[3][0]), __float_as_uint(S[3][1]));
    SF;
    sts64o(lh, (sxw + 1024), __float_as_uint(S[4][0]), __float_as_uint(S[4][1]));
    TS(4);
    bar_sync(NB_PAIR + X, 64);
    {
        const uint4 a = lds128o(k.lw, sxr), b = lds128o(k.lw, (sxr + 512));
        const uint2 c = lds64o(lh, (sxr + 1024));
        SF;
        VLD(VE, VF);
        SF;
        S[0][0] += __uint_as_float(a.x); S[0][1] += __uint_as_float(a.y); S[1][0] += __uint_as_float(a.z); S[1][1] += __uint_as_float(a.w);
        S[2][0] += __uint_as_float(b.x); S[2][1] += __uint_as_float(b.y); S[3][0] += __uint_as_float(b.z); S[3][1] += __uint_as_float(b.w);
        S[4][0] += __uint_as_float(c.x); S[4][1] += __uint_as_float(c.y);
    }
    float m = fmaxf(fmaxf(fmaxf(S[0][0], S[0][1]), fmaxf(S[1][0], S[1][1])), fmaxf(fmaxf(S[2][0], S[2][1]), fmaxf(S[3][0], S[3][1])));
    m = fmaxf(m, fmaxf(S[4][0], S[4][1]));
    m = fmaxf(m, __shfl_xor_sync(0xffffffffu, m, 1));
    const float m2 = __shfl_xor_sync(0xffffffffu, m, 2);
    SF;
    VLD(VF, 8);
    uint32_t ok;
    asm volatile("{.reg .pred p; mbarrier.test_wait.parity.shared::cta.b64 p,[%1],%2; selp.u32 %0,1,0,p;}" : "=r"(ok) : "r"(bar + RB_V * 8), "r"(s & 1) : "memory");
    uint4 vr0 = ldsm4o(k.lu, (ro + 4096)), vr1 = ldsm4o(k.lu, (ro + 4608));
    vm[0] = ldsm4o(k.lu, (lo + 4096)); vm[1] = ldsm4o(k.lu, (lo + 4608));
    SF;
    TS(5);
    m = fmaxf(m, m2) * -SC_LOG2E;
    uint32_t P[5];
#pragma unroll
    for (int i = 0; i < 5; i++) P[i] = pack2(ex2(fmaf(S[i][0], SC_LOG2E, m)), ex2(fmaf(S[i][1], SC_LOG2E, m)));
    float o[4][4], l[4] = {0, 0, 0, 0};
    const uint32_t ONE = 0x3f803f80u;
    mma16_top(l, ONE, ONE, P[0], P[1]);
#pragma unroll
    for (int t = 0; t < 4; t++) { o[t][0] = o[t][1] = o[t][2] = o[t][3] = 0; mma16(o[t], V[0][t].x, V[0][t].y, V[0][t].z, V[0][t].w, P[0], P[1]); }
    mma16_top(l, ONE, ONE, P[2], P[3]);
#pragma unroll
    for (int t = 0; t < 4; t++) mma16(o[t], V[1][t].x, V[1][t].y, V[1][t].z, V[1][t].w, P[2], P[3]);
    if (!__all_sync(0xffffffffu, ok)) {
        mbar_wait(bar + RB_V * 8, s & 1);
        vr0 = ldsm4o(k.lu, (ro + 4096)); vr1 = ldsm4o(k.lu, (ro + 4608));
    }
    TS(6);
    vm[0] = hadd4(vm[0], vr0); vm[1] = hadd4(vm[1], vr1);
    mma8(l, ONE, ONE, P[4]);
    mma8(o[0], vm[0].x, vm[0].y, P[4]); mma8(o[1], vm[0].z, vm[0].w, P[4]); mma8(o[2], vm[1].x, vm[1].y, P[4]); mma8(o[3], vm[1].z, vm[1].w, P[4]);
    asm volatile("{.reg .pred p; .reg .b32 t; setp.lt.u32 p,%0,%3; add.u32 t,%0,%4; @p st.shared.v2.f32 [t],{%1,%2};}" ::"r"(lh), "f"(rcp(l[0])), "f"(rcp(l[1])), "r"(k.xb + 32), "r"(R_IL) : "memory");
#pragma unroll
    for (int t = 0; t < 4; t += 2)
        asm volatile("{.reg .b32 t; add.u32 t,%0,%5; stmatrix.sync.aligned.m8n8.x4.trans.shared.b16 [t],{%1,%2,%3,%4};}" ::"r"(k.lm),
                     "r"(pack2(o[t][0], o[t][1])), "r"(pack2(o[t][2], o[t][3])), "r"(pack2(o[t + 1][0], o[t + 1][1])), "r"(pack2(o[t + 1][2], o[t + 1][3])), "r"(R_O - j * 1024 + t * 256) : "memory");
    bar_arrive(NB_O + X, 320);
    PROF(k.lw == k.xb, X * 64 + s);
    TS(7);
    kmm[0] = u[1]; kmm[1] = u[3];
    mbar_expect1(bar + RB_QK * 8, 2048); mbar_expect1(bar + RB_V * 8, 1024);
}
template <int MT>
__device__ __forceinline__ void rec_xattn(const RecH& k, int X, int j, int s, int head, bool early, const uint4 (*V)[4], const uint4* vmm, const uint4* kmm) {
    constexpr int NTL = 3 + 2 * MT;
    const uint32_t sb = k.sb, to = R_T;
    const uint32_t sxw = k.sa, sxr = k.sp;
    const uint32_t lq2 = vxor(k.lq, 0x20);
    float S[NTL][4];
#pragma unroll
    for (int i = 0; i < NTL; i++) S[i][0] = S[i][1] = S[i][2] = S[i][3] = 0;
    {
        uint4 q[2][2], kk[2][NTL];
#define XQ(e) q[e][0] = ldsm4o(k.lq, (to + 16384 + (e) * 1024)); q[e][1] = ldsm4o(lq2, (to + 16384 + (e) * 1024))
#define XK(e, i) kk[e][i] = ldsm4o(k.lm, (to + (e) * 1024 + (((i) - 1) >> 1) * 4096 + (((i) - 1) & 1) * 512))
        kk[0][0] = kmm[0]; kk[1][0] = kmm[1];
        if (!X) bar_sync(NB_XG, 320);
        XQ(0);
#pragma unroll
        for (int i = 1; i < NTL; i++) XK(0, i);
        SF;
#pragma unroll
        for (int i = 0; i < NTL; i++) { mma16(S[i], q[0][0].x, q[0][0].y, q[0][0].z, q[0][0].w, kk[0][i].x, kk[0][i].y); SF; }
        q[1][0] = ldsm4o(k.lq, (to + 16384 + 1024));
#pragma unroll
        for (int i = 0; i < NTL; i++) { mma16(S[i], q[0][1].x, q[0][1].y, q[0][1].z, q[0][1].w, kk[0][i].z, kk[0][i].w); SF; if (i + 1 < NTL) XK(1, i + 1); SF; }
        q[1][1] = ldsm4o(lq2, (to + 16384 + 1024));
        SF;
#pragma unroll
        for (int i = 0; i < NTL; i++) { mma16(S[i], q[1][0].x, q[1][0].y, q[1][0].z, q[1][0].w, kk[1][i].x, kk[1][i].y); SF; }
#pragma unroll
        for (int i = 0; i < NTL; i++) { mma16(S[i], q[1][1].x, q[1][1].y, q[1][1].z, q[1][1].w, kk[1][i].z, kk[1][i].w); SF; }
    }
#pragma unroll
    for (int i = 0; i < NTL; i++) sts128o(k.lw, (sxw + i * 512), __float_as_uint(S[i][0]), __float_as_uint(S[i][1]), __float_as_uint(S[i][2]), __float_as_uint(S[i][3]));
    SF;
    if (X) bar_sync(NB_XG + 1, 320); else bar_sync(NB_PAIR + 2, 64);
    TS(9);
    if (early && !X) rec_load_tile(sb, X, j, s + 1, head, MT);
#pragma unroll
    for (int i = 0; i < NTL; i++) {
        const uint4 r = lds128o(k.lw, (sxr + i * 512));
        S[i][0] += __uint_as_float(r.x); S[i][1] += __uint_as_float(r.y); S[i][2] += __uint_as_float(r.z); S[i][3] += __uint_as_float(r.w);
    }
    const int g = vshr(k.lw - k.xb, 6) & 7, c = (vshr(k.lw, 4) ^ (g >> 1)) & 3;
    const float NEG = -__int_as_float(0x7f800000);
    if (2 * c > g) { S[NTL - 2][0] = NEG; S[NTL - 1][2] = NEG; }
    if (2 * c + 1 > g) { S[NTL - 2][1] = NEG; S[NTL - 1][3] = NEG; }
    float m0 = fmaxf(S[0][0], S[0][1]), m1 = fmaxf(S[0][2], S[0][3]);
#pragma unroll
    for (int i = 1; i < NTL; i++) { if (i < NTL - 1) m0 = fmaxf(m0, fmaxf(S[i][0], S[i][1])); m1 = fmaxf(m1, fmaxf(S[i][2], S[i][3])); }
    m0 = fmaxf(m0, __shfl_xor_sync(0xffffffffu, m0, 1)); m1 = fmaxf(m1, __shfl_xor_sync(0xffffffffu, m1, 1));
    m0 = fmaxf(m0, __shfl_xor_sync(0xffffffffu, m0, 2)); m1 = fmaxf(m1, __shfl_xor_sync(0xffffffffu, m1, 2));
    m0 *= -SC_LOG2E; m1 *= -SC_LOG2E;
    uint32_t P[NTL][2];
#pragma unroll
    for (int i = 0; i < NTL; i++) {
        P[i][0] = i < NTL - 1 ? pack2(ex2(fmaf(S[i][0], SC_LOG2E, m0)), ex2(fmaf(S[i][1], SC_LOG2E, m0))) : 0u;
        P[i][1] = pack2(ex2(fmaf(S[i][2], SC_LOG2E, m1)), ex2(fmaf(S[i][3], SC_LOG2E, m1)));
    }
    float l[4] = {0, 0, 0, 0};
#pragma unroll
    for (int i = 0; i < NTL; i++) mma8(l, P[i][0], P[i][1], 0x3f803f80u);
    const float l0 = rcp(l[0]), l1 = rcp(l[2]);

#pragma unroll
    for (int e = 0; e < 2; e++) {
        const uint4 vm = vmm[e];
        uint32_t u[2][4];
#pragma unroll
        for (int n = 0; n < 4; n++) {
            float a[4] = {0, 0, 0, 0};
#pragma unroll
            for (int m = 0; m <= MT; m++) {
                const uint4 v = V[m][e * 2 + (n >> 1)];
                mma8(a, P[1 + 2 * m][0], P[1 + 2 * m][1], (n & 1) ? v.y : v.x); mma8(a, P[2 + 2 * m][0], P[2 + 2 * m][1], (n & 1) ? v.w : v.z);
            }
            mma8(a, P[0][0], P[0][1], n == 0 ? vm.x : n == 1 ? vm.y : n == 2 ? vm.z : vm.w);
            u[0][n] = pack2(a[0] * l0, a[1] * l0); u[1][n] = pack2(a[2] * l1, a[3] * l1);
        }
        sts128o(k.lw, sxr + e * 512, u[0][0], u[0][1], u[0][2], u[0][3]); sts128o(k.lw, sxr + e * 512 + 1024, u[1][0], u[1][1], u[1][2], u[1][3]);
    }
    if (early && X) rec_load_tile(sb, X, j, s + 1, head, MT);
    TS(10);
}
__device__ __forceinline__ void rec_attn(const Params& p, uint32_t sb, int X, int j, int head, uint32_t rank) {
    const int lane = threadIdx.x & 31;
    RecH k;
    k.xb = sb + X * XS + j * 1024;
    const uint32_t x2 = k.xb + j * 1024;
    k.lw = __shfl_sync(0xffffffffu, x2 + (lane ^ (lane >> 3)) * 16, lane);
    k.lm = __shfl_sync(0xffffffffu, x2 + ((lane & 7) * 4 + ((lane >> 3) ^ ((lane & 7) >> 1))) * 16, lane);
    k.lq = __shfl_sync(0xffffffffu, x2 + ((lane >> 3) & 1) * 512 + ((lane & 7) * 4 + ((lane >> 4) ^ ((lane & 7) >> 1))) * 16, lane);
    k.lv = __shfl_sync(0xffffffffu, x2 + (lane >> 4) * 512 + ((lane & 7) * 4 + (((lane >> 3) & 1) ^ ((lane & 7) >> 1))) * 16, lane);
    k.lu = __shfl_sync(0xffffffffu, k.xb + ((lane & 6) * 4 + (((lane >> 3) * 2 + (lane & 1)) ^ (lane & 6))) * 16, lane);
    k.sa = __shfl_sync(0xffffffffu, R_SX + j * 512, 0); k.sp = __shfl_sync(0xffffffffu, R_SX + 2560 - j * 4608, 0);
    k.sb = sb; k.zero = p.zero;
    const uint32_t dp = mapa(sb, rank ^ 1) - sb;
    char* zp = acc_base() + (j ? X * 32768 + acc_main(rank, head * 8) : X * 1024 + acc_extra(rank, head * 8));
    mbar_expect1(sb + R_BAR + (RB_QK + X * 2 + j) * 8, 2048); mbar_expect1(sb + R_BAR + (RB_V + X * 2 + j) * 8, 1024);
    bool early = false;
#pragma unroll 1
    for (int s = 0; s < 64; s++) {
        TSET(X ? s + p.b1 : s, j == GPJ ? 1 + X : 3);
        TS(0);
        if (!early) {
            if (!j) wait_cnt_warp(cnt_ptr(C_QKV0 + X, s >> 2), 256);
            early = !j || chunk_ready(X, 1, s);
            if (early) rec_load_tile(sb, X, j, s, head, rank);
        }
        uint4 V[2][4], vm[2], km[2];
        rec_mattn(k, dp, X, j, s, V, vm, km);
        if (!early) { wait_cnt_warp(cnt_ptr(C_QKV0 + X, (s >> 2) + 16), 128); rec_load_tile(sb, X, 1, s, head, rank); }
        early = s < 63 && ((s & 3) != 3 || chunk_ready(X, j, s + 1));
        mbar_wait(sb + R_BAR + (RB_T + X * 2 + 1) * 8, s & 1);
        if (rank) rec_xattn<1>(k, X, j, s, head, early, V, vm, km); else rec_xattn<0>(k, X, j, s, head, early, V, vm, km);
        fence_async_smem();
        __syncwarp();
        asm volatile("{.reg .pred p; elect.sync _|p,0xffffffff;\n"
                     "@p cp.async.bulk.global.shared::cta.bulk_group.L2::cache_hint [%0],[%1],2048,%2;\n"
                     "@p cp.async.bulk.global.shared::cta.bulk_group [%3],[%4],%5;\n"
                     "cp.async.bulk.commit_group;}"
                     ::"l"(g_o[X] + ((s >> 2) * 64 + head * 2 + j) * 1024 + ((s & 3) * 2 + rank) * 128), "r"(x2 + k.sp),
                       "l"((X && s < 40) ? POL_LATE : POL_SOON), "l"(zp + acc_slot(s + 2)), "r"(sb + R_Z), "r"(j ? 128 : 32) : "memory");
        if (s == 61) rec_publish(X, 64);
        if ((s & 3) == 3) {
            if (!early && s < 63 && chunk_ready(X, j, s + 1)) { rec_load_tile(sb, X, j, s + 1, head, rank); early = true; }
            rec_publish(X, s);
            PROF(lane == 0 && j, 3900 + X * 16 + (s >> 2));
        }
    }
}

__device__ __forceinline__ void rec_init(const Params& p, uint32_t sb, int head, uint32_t rank) {
    const uint32_t b = sb + R_BAR;
    const int i = threadIdx.x - 320;
    if (i >= 0 && i < RB_N) {
        mbar_init(b + i * 8, 1);
        asm volatile("fence.mbarrier_init.release.cluster;" ::: "memory");
    }
    if (i == 0) mbar_expect(b + RB_INIT * 8, 196608);
    if (i >= 0 && i < 32) sts32(sb + R_Z + i * 4, 0);
}

#define NSTGN 8
constexpr int NSTG = NSTGN, STG_B = 24576;
#define LAGH 3
constexpr int NSB = 8;
constexpr int B_OUT = NSTG * STG_B  , B_UT = B_OUT, B_YT = B_UT + 16384, B_SP = B_YT  ,
              B_ST = 229376  , B_BAR = 231936;
static_assert(B_OUT + NSB * 4096 <= B_ST && B_ST + 2048 <= B_BAR && B_YT + 10240 <= B_ST, "smem map");
enum { BB_FULL = 0, BB_EMPTY = 8, BB_SF = 16  , BB_GO = 18, BB_LOW = 19, BB_DONE = 20  , BB_IDLE = 22  , BB_N = 30 };
enum { NB_REL = 2  , NB_C = 11, NB_WG = 12  , NB_PH = 14 };

__device__ __forceinline__ void bulk_init(uint32_t sb) {
    const int i = threadIdx.x - 320;
    if (i >= 0 && i < BB_N) {
        mbar_init(sb + B_BAR + i * 8, (i >= BB_EMPTY && i < BB_EMPTY + NSTG) ? 4 : i >= BB_DONE ? 4 : 1);
        asm volatile("fence.mbarrier_init.release.cluster;" ::: "memory");
    }
}

struct Task { int type, layer, ch, a, b, c, blk; bool pair, dry; };
__device__ __forceinline__ Task task_of(uint32_t tk, uint32_t rank) {
    Task t;
    t.type = tk & 7; t.layer = (tk >> 3) & 1; t.a = (tk >> 8) & 255; t.b = (tk >> 16) & 255; t.c = (tk >> 24) & 127; t.dry = tk >> 31;
    t.pair = t.type <= T_OP && (t.c & 64);
    t.ch = ((tk >> 4) & 15) + (t.pair ? rank : 0);
    t.blk = t.type == T_QKV ? t.a + (t.pair ? 0 : rank) : 192 + (t.pair ? (t.c >> 2) & 4 : rank * 4);
    return t;
}
__device__ __forceinline__ int qkv_blk(const Task& t, int u) {
    const int v = t.blk + (t.pair ? 1 : 2 * t.c) * u;
    return 2 * (v < 64 ? v + 32 : v - 64);
}
__device__ __forceinline__ void bulk_producer(const Params& p, uint32_t sb, int cl, uint32_t rank) {
    int st = 0; uint32_t ph = 1;
    const int tag = __shfl_sync(0xffffffffu, lds32(sb + S_TAG), 0);
    bool gated = false;
#define ACQ(bytes) do { mbar_wait(sb + B_BAR + (BB_EMPTY + st) * 8, ph); mbar_expect1(sb + B_BAR + (BB_FULL + st) * 8, bytes); } while (0)
#define NEXT do { if (++st == NSTG) { st = 0; ph ^= 1; } } while (0)
#pragma unroll 1
    for (int ti = 0; ti < MAXT; ti++) {
        const Task t = task_of(p.task[list_of(cl)][ti], rank);
        const int layer = t.layer, ch = t.ch;
        if (t.type == T_END) break;
        if (t.type <= T_OP) {
            const bool qkv = t.type == T_QKV;
            const int nh = (qkv ? 8 : 2) * t.b;
            const bool halves = !qkv && (t.c & 80) == 16;
            const unsigned* dep = cnt_ptr(qkv ? (layer ? C_CV : C_ST) : C_O0 + layer, ch + (halves && !rank));
            const unsigned need = qkv ? (layer ? 32 : ch < 2 ? 0 : 16) : 512;
            const uint16_t mb = t.pair ? 3 : 1 << rank, ma = t.pair ? 1 << rank : 3;
            const int pend = min(nh, gated ? NSTG : 4);
            auto ready = [&](int h) {
                if (h < pend) {
                    unsigned v = 0;
                    if (gated) asm volatile("ld.relaxed.gpu.global.u32 %0,[%1];" : "=r"(v) : "l"(dep) : "memory");
                    return gated && __all_sync(0xffffffffu, v >= need);
                }
                if (!gated) { wait_cnt_warp(g_gate, lds32(sb + S_GATE)); gated = true; }
                if (need) wait_cnt_warp(dep, need);
                return true;
            };
            bool open = true;
            if (qkv) {
#pragma unroll 1
                while (st) { ACQ(0); NEXT; }
#pragma unroll 1
                for (int h = 0; h < nh; h++) {
                    const int blk = qkv_blk(t, h >> 3);
                    ACQ(16384 + (h < 2 ? (layer ? 8192 : 1024) : 0));
                    if (!t.pair || !rank) tma3d_mc(sb + st * STG_B, &p.t3[blk >> 6], (h & 7) * 64, blk & 63, sb + B_BAR + (BB_FULL + st) * 8, mb);
                    if (!t.pair || rank) tma3d_mc(sb + st * STG_B + 8192, &p.t3[blk >> 6], (h & 7) * 64 + 32, blk & 63, sb + B_BAR + (BB_FULL + st) * 8, mb);
                    NEXT;
                    if (open && h && ready(h + 1)) {
                        open = false;
                        const float2* sp = g_st[layer] + ch * 2048 + (need ? 0 : tag * 256);
                        bulk_g2s1(sb + 16384, sp, layer ? 8192 : 1024, sb + B_BAR + BB_FULL * 8, POL_N);
                        bulk_g2s1(sb + STG_B + 16384, sp + (layer ? 1024 : 128), layer ? 8192 : 1024, sb + B_BAR + (BB_FULL + 1) * 8, POL_N);
                    }
                }
                continue;
            }
            if (PFC && !layer && (t.c & 15) < 8) {
                const int q = (t.c & 15) * 2 + rank;
                asm volatile("{.reg .pred p; elect.sync _|p,0xffffffff; @p cp.async.bulk.prefetch.L2.global [%0],8192; @p cp.async.bulk.prefetch.L2.global [%1],%2;}"
                             ::"l"(g_xA[0] + (ch * 16 + q) * 512), "l"(g_P + q * 16 * 32 * PW), "r"((2 + (ch & 1)) * 32 * PW * 4) : "memory");
            }
            const CUtensorMap *tb = &p.t3[4 - t.pair], *ta = &p.ta[t.pair];
            const uint32_t db = sb + 8192 + (t.pair ? rank * 8192 : 0), da = sb + (t.pair ? 0 : rank * 4096);
            const int zb = (t.blk & 63) + (t.pair ? rank * 2 : 0), ya = 4096 + ((layer * 16 + ch) * 64 + t.a) * 16 + (t.pair ? 0 : rank * 8), row = t.a * 64;
            int h = 0;
            const int s0 = st;
            if (halves) mbar_expect1(sb + B_BAR + BB_LOW * 8, NSTG * 4096);
#pragma unroll 1
            for (; (halves && h < NSTG) || !ready(h); h++) { ACQ(halves ? STG_B - 4096 : STG_B); tma3d_mc(db + st * STG_B, tb, row + h * 32, zb, sb + B_BAR + (BB_FULL + st) * 8, mb); NEXT; }
#pragma unroll 1
            for (int k = 0; k < h; k++) {
                const int s2 = (s0 + k) & (NSTG - 1);
                tma2d_mc(da + s2 * STG_B, ta, (k & 1) * 256, ya + (k >> 1) * 16, sb + B_BAR + (halves && rank ? BB_LOW : BB_FULL + s2) * 8, ma, POL_LAST);
            }
#pragma unroll 1
            for (; h < nh; h++) {
                ACQ(STG_B);
                tma3d_mc(db + st * STG_B, tb, row + h * 32, zb, sb + B_BAR + (BB_FULL + st) * 8, mb);
                tma2d_mc(da + st * STG_B, ta, (h & 1) * 256, ya + (h >> 1) * 16, sb + B_BAR + (BB_FULL + st) * 8, ma, POL_LAST);
                NEXT;
            }
#pragma unroll 1
            for (h = 0; h < 4 && !layer; h++) { ACQ(0); NEXT; }
        } else if (t.type == T_CV) {
            const int q = t.a + rank;
            if (!gated) { wait_cnt_warp(g_gate, lds32(sb + S_GATE)); gated = true; }
            if (layer) {
                wait_cnt_warp(cnt_ptr(C_U, ch - 2), 32);
#pragma unroll 1
                for (int j = ch + 1; j >= 2; j--) {
                    ACQ(16 * PW * 4 + (j > 2 ? 4096 : 0));
                    bulk_g2s1(sb + st * STG_B, g_P + (((q >> 1) * 16 + j) * 2 + (q & 1)) * 16 * PW, 16 * PW * 4, sb + B_BAR + (BB_FULL + st) * 8, POL_N);
                    if (j > 2) bulk_g2s1(sb + st * STG_B + 12288, g_u + (((q >> 1) * 16 + ch + 1 - j) * 2 + (q & 1)) * 256, 4096, sb + B_BAR + (BB_FULL + st) * 8, POL_N);
                    NEXT;
                }
            } else {
#pragma unroll 1
                for (int j = min(ch, 1 + (ch & 1)); j >= 0; j--) {
                    if (j == 0 && ch >= 2) {
                        wait_cnt_warp(cnt_ptr(C_H, ch & ~1), 64);
#pragma unroll 1
                        for (int i = 0; i < ((ch & 1) || ch == 2 ? 1 : 2); i++) {
                            ACQ(16384);
                            bulk_g2s1(sb + st * STG_B, g_carry[i] + (ch * 16 + q) * 1024, 16384, sb + B_BAR + (BB_FULL + st) * 8, POL_LAST);
                            NEXT;
                        }
                    }
                    ACQ(32 * PW * 4);
                    bulk_g2s1(sb + st * STG_B, g_P + (q * 16 + j) * 32 * PW, 32 * PW * 4, sb + B_BAR + (BB_FULL + st) * 8, POL_N);
                    NEXT;
                }
            }
        }
    }
}

__device__ __forceinline__ uint4* qkv_dst(int layer, int ch, int w, int blk);
__device__ __forceinline__ uint4* op_dst(int layer, int ch, int slot, int w, uint32_t rank);
__device__ __forceinline__ uint64_t out_pol(int type, int layer, int ch) { return (type == T_QKV ? (!layer && ch > 1) : (layer && ch < 10)) ? POL_LATE : POL_SOON; }
__device__ __forceinline__ void bulk_relay(const Params& p, uint32_t sb, int cl) {
    for (int ti = 0; ti < MAXT; ti++) {
        const int type = p.task[list_of(cl)][ti] & 7;
        if (type == T_END) break;
        if (type != T_QKV) continue;
        bar_sync(NB_PH, 96);
        const uint32_t ph = lds32(sb + B_ST + 8);
#pragma unroll 1
        for (int h = 2; h < 8; h++) {
            mbar_wait(sb + B_BAR + (BB_FULL + h) * 8, ph);
            if (h == 4 || h == 7) { bar_arrive(NB_REL + (h == 7) * 2, 160); bar_arrive(NB_REL + (h == 7) * 2 + 1, 160); }
        }
    }
}
__device__ __forceinline__ void bulk_release(const Params& p, uint32_t sb, int cl, uint32_t rank, int wg) {
    int nd = 0;
    for (int ti = 0; ti < MAXT; ti++) {
        const Task t = task_of(p.task[list_of(cl)][ti], rank);
        const int type = t.type, layer = t.layer, ch = t.ch;
        if (type == T_END) break;
        if (type == T_FIN || (type == T_OP && (t.c & 32))) continue;
        if (type == T_OP && !layer) {
            mbar_wait(sb + B_BAR + (BB_DONE + wg) * 8, nd & 1);
            nd++;
            const int s0 = __shfl_sync(0xffffffffu, lds32(sb + B_ST + wg * 4), 0) + wg * 2;
            fence_async_smem();
#pragma unroll 1
            for (int w = 0; w < 4; w++)
                asm volatile("{.reg .pred p; elect.sync _|p,0xffffffff; @p cp.async.bulk.global.shared::cta.bulk_group.L2::cache_hint [%0],[%1],8192,%2; cp.async.bulk.commit_group;}"
                             ::"l"(op_dst(0, ch, t.c & 15, wg * 4 + w, rank)), "r"(sb + ((s0 + (w >> 1)) & (NSTG - 1)) * STG_B + (w & 1) * 8192), "l"(POL_SOON) : "memory");
            mbar_arrive1(sb + B_BAR + (BB_SF + wg) * 8);
            asm volatile("{.reg .pred p; elect.sync _|p,0xffffffff;\n"
                         "cp.async.bulk.wait_group 3; @p red.relaxed.gpu.global.add.u32 [%0],1; cp.async.bulk.wait_group 2; @p red.relaxed.gpu.global.add.u32 [%0+64],1;\n"
                         "cp.async.bulk.wait_group 1; @p red.relaxed.gpu.global.add.u32 [%0+128],1; cp.async.bulk.wait_group 0; @p red.relaxed.gpu.global.add.u32 [%0+192],1;}"
                         ::"l"(cnt_ptr(C_OP0 + rank * 2 + wg, ch)) : "memory");
#pragma unroll 1
            for (int i = 0; i < 8; i++) mbar_arrive1_cluster(mapa(sb + B_BAR + (BB_EMPTY + ((s0 + (i >> 2)) & (NSTG - 1))) * 8, i & 1));
            continue;
        }
#pragma unroll 1
        for (int u = 0; u < (type == T_QKV ? t.b : 1); u++) {
            const int blk = qkv_blk(t, u);
            unsigned* cnt = cnt_ptr(type == T_QKV ? C_QKV0 + layer : type == T_OP ? C_OP1 : layer ? C_H : C_CV, ch + (type == T_QKV && blk < 64 ? 16 : 0));
            const uint4* dst = type == T_QKV ? qkv_dst(layer, ch, wg * 4, blk) : op_dst(1, ch, t.c & 15, wg * 4, (t.blk >> 2) & 1) + 256;
            mbar_wait(sb + B_BAR + (BB_DONE + wg) * 8, nd & 1);
            nd++;
            if (type != T_CV) {
                fence_async_smem();
#pragma unroll
                for (int w = 0; w < 4; w++)
                    asm volatile("{.reg .pred p; elect.sync _|p,0xffffffff; @p cp.async.bulk.global.shared::cta.bulk_group.L2::cache_hint [%0],[%1],4096,%2;}"
                                 ::"l"(dst + (type == T_QKV ? (w >> 1) * 49152 + (w & 1) * 256 : w * 1024)), "r"(sb + B_OUT + (wg * 4 + w) * 4096), "l"(out_pol(type, layer, ch)) : "memory");
                asm volatile("cp.async.bulk.commit_group; cp.async.bulk.wait_group 0;" ::: "memory");
            }
            if (type != T_QKV) fence_async();
            if (!t.dry) asm volatile("{.reg .pred p; elect.sync _|p,0xffffffff; @p red.relaxed.gpu.global.add.u32 [%0],%1;}" ::"l"(cnt), "r"(type == T_QKV ? 2 : type == T_OP ? t.b : 1) : "memory");
            PROF(wg && (threadIdx.x & 31) == 0 && (type == T_CV || u + 2 == t.b), 3900 + ti);
            if (type == T_CV && !layer && !t.dry) {
                asm volatile("{.reg .pred p; elect.sync _|p,0xffffffff; @p cp.async.bulk.global.shared::cta.bulk_group [%0],[%1],4096;\n"
                             "cp.async.bulk.commit_group; cp.async.bulk.wait_group 0; @p red.relaxed.gpu.global.add.u32 [%2],1;}"
                             ::"l"(g_u + ((t.a + rank) * 16 + ch) * 512 + wg * 256), "r"(sb + B_UT + (ch & 1) * 8192 + wg * 4096), "l"(cnt_ptr(C_U, ch)) : "memory");
            }
            mbar_arrive1(sb + B_BAR + (BB_SF + wg) * 8);
        }
        PROF(wg && (threadIdx.x & 31) == 0, 3600 + ti * 4 + 3);
    }
}

__device__ __forceinline__ void stage_release(uint32_t sb, int w, int st) {
    if (!(w & 2)) mbar_arrive1_cluster(mapa(sb + B_BAR + (BB_EMPTY + st) * 8, w & 1));
}
template <bool ACC>
__device__ __forceinline__ void gemm_run(float* acc, uint32_t sb, int w, int h0, int h1, uint32_t& r0, uint32_t& r1, int& st, uint32_t& ph) {
    const uint64_t da0 = mkdesc(sb + (w >> 2) * 4096, 16, 512, 2), db0 = mkdesc(sb + 8192, 4096, 1024, 1);
    const uint32_t rel0 = mapa(sb + B_BAR + BB_EMPTY * 8, w & 1);
#pragma unroll 1
    for (int h = h0; h < h1; h++) {
        const uint64_t da = da0 + st * (STG_B >> 4), db = db0 + st * (STG_B >> 4);
        mbar_wait(sb + B_BAR + (BB_FULL + st) * 8, ph);
        if (ACC) wg_wait<1>();
        wg_fence();
        wgmma256<ACC>(acc, da, db);
        wgmma256<true>(acc, da + 2, db + 128);
        wg_commit();
        if (ACC) mbar_arrive1_cluster((w == 2 && h == LAGH - 1) ? sb + B_BAR + BB_GO * 8 : r0);
        r0 = r1;
        if (!(w & 2)) r1 = rel0 + st * 8;
        if (++st == NSTG) { st = 0; ph ^= 1; }
    }
}

__device__ __forceinline__ uint4* qkv_dst(int layer, int ch, int w, int blk) {
    return g_qkv[layer] + (size_t)((ch * 4 + (w >> 1)) * 32 + ((blk & 63) >> 1)) * 1536 + (blk >> 6) * 512 + (w & 1) * 256;
}
__device__ __forceinline__ uint4* op_dst(int layer, int ch, int slot, int w, uint32_t rank) {
    return g_pp[layer] + (size_t)(ch * MAXSPLIT + slot) * 8192 + (w * 32 + rank * 16) * 32;
}
__device__ __forceinline__ uint32_t ln2(uint32_t x, uint32_t m, uint32_t rh, uint32_t rl) {
    uint32_t d; asm volatile("{.reg .b32 t,u; sub.rn.bf16x2 t,%1,%2; mul.rn.bf16x2 u,t,%4; fma.rn.bf16x2 %0,t,%3,u;}" : "=r"(d) : "r"(x), "r"(m), "r"(rh), "r"(rl)); return d;
}
__device__ __forceinline__ void qkv_task(uint32_t sb, int w, int layer, int ch, int nu, int& ng, int& nd, uint32_t& ph, int ti, uint32_t zero) {
    constexpr int type = T_QKV;
    static_assert(NSTG == 8, "ring");
    const int lane = threadIdx.x & 31;
    const uint64_t db0 = mkdesc(sb, 4096, 1024, 1);
    const uint32_t rel = (w & 2) ? sb + B_BAR + BB_IDLE * 8 : mapa(sb + B_BAR + BB_EMPTY * 8, w & 1), full = sb + B_BAR + BB_FULL * 8;
    const uint32_t lo = sb + B_OUT + w * 4096 + (lane ^ (lane >> 3)) * 16;
    const uint4* xa = g_xA[layer] + (ch * 8 + w) * 1024 + lane;
    uint32_t m0, m1, h0, h1, l0, l1;
    uint4 A[32];
    {
        mbar_wait(full, ph);
        mbar_wait(full + 8, ph);
        CPROF(1);
        const uint32_t sa = sb + (lane >> 4) * STG_B + 16384 + (w * 16 + (lane & 15)) * 8;
        uint2 v[8];
#pragma unroll
        for (int i = 0; i < 8; i++) v[i] = lds64(sa + i * 1024 * layer);
#pragma unroll
        for (int i = 0; i < 4 * QB1; i++) A[i] = ldcg128(xa + i * 32);
        bar_sync(NB_WG + (w >> 2), 128);
        float sm = 0, M2 = 0, D = 0;
#pragma unroll
        for (int i = 0; i < 8; i++) { sm += __uint_as_float(v[i].x); M2 += __uint_as_float(v[i].y); }
        if (!layer) { sm = __uint_as_float(v[0].x); M2 = __uint_as_float(v[0].y); }
        sm += __shfl_xor_sync(0xffffffffu, sm, 16);
#pragma unroll
        for (int i = 0; i < 8; i++) { const float d = __uint_as_float(v[i].x) * (1.f / 32.f) - sm * (1.f / 512.f); D += 32.f * d * d; }
        M2 += layer ? D : sm * sm * (-1.f / 1024.f);
        M2 = fmaxf(M2 + __shfl_xor_sync(0xffffffffu, M2, 16), 0.f);
        const float2 o = ln_finish(sm * (1.f / 512.f), M2 * (1.f / 512.f));
        const float r = rcp(o.y), rh = rbf(r);
        const uint32_t mm = pack2(o.x, o.x), hl = pack2(r - rh, rh);
        m0 = __shfl_sync(0xffffffffu, mm, lane >> 2); m1 = __shfl_sync(0xffffffffu, mm, (lane >> 2) + 8);
        l0 = __shfl_sync(0xffffffffu, hl, lane >> 2); l1 = __shfl_sync(0xffffffffu, hl, (lane >> 2) + 8);
        h0 = __byte_perm(l0, 0, 0x3232); h1 = __byte_perm(l1, 0, 0x3232); l0 = __byte_perm(l0, 0, 0x1010); l1 = __byte_perm(l1, 0, 0x1010);
    }
    float acc[64];
#define QNRM(i) A[i] = make_uint4(ln2(A[i].x, m0, h0, l0), ln2(A[i].y, m1, h1, l1), ln2(A[i].z, m0, h0, l0), ln2(A[i].w, m1, h1, l1))
#pragma unroll
    for (int h = 0; h < 8; h++) {
        const uint64_t db = db0 + h * (STG_B >> 4);
        const int b0 = h == 0 ? QB1 : h == QB1 ? QB2 : h == QB2 ? QB3 : 8, b1 = h == 0 ? QB2 : h == QB1 ? QB3 : 8;
        if (b0 < b1) {
            const uint4* xb = xa + (A[4 * b0 - 1].x & zero);
#pragma unroll
            for (int i = 4 * b0; i < 4 * b1; i++) A[i] = ldcg128(xb + i * 32);
            bar_sync(NB_WG + (w >> 2), 128);
        }
        QNRM(4 * h); QNRM(4 * h + 1); QNRM(4 * h + 2); QNRM(4 * h + 3);
        if (h == 2 || h == 5) bar_sync(NB_REL + (h == 5) * 2 + (w >> 2), 160);
        if (h) wg_wait<1>();
        wg_fence();
        if (h) wgmma128r<true>(acc, A[4 * h], db); else wgmma128r<false>(acc, A[0], db);
        wgmma128r<true>(acc, A[4 * h + 1], db + 128);
        wgmma128r<true>(acc, A[4 * h + 2], db + 512);
        wgmma128r<true>(acc, A[4 * h + 3], db + 640);
        wg_commit();
        if (h >= 2) mbar_arrive1_cluster(rel + (h - 2) * 8);
    }
    ph ^= 1;
#pragma unroll 1
    for (int u = 1;; u++) {
        mbar_wait(sb + B_BAR + (BB_SF + (w >> 2)) * 8, (nd & 1) ^ 1);
        if (u < nu) mbar_wait(full, ph);
        wg_wait<1>();
        mbar_arrive1_cluster(rel + 48);
        wg_wait<0>();
        mbar_arrive1_cluster(rel + 56);
        uint4 o[8];
#pragma unroll
        for (int n = 0; n < 8; n++) {
            const float* a = acc + (n >> 1) * 16 + (n & 1) * 2;
            o[n] = make_uint4(pack2(a[0], a[1]), pack2(a[4], a[5]), pack2(a[8], a[9]), pack2(a[12], a[13]));
            sts128(lo + n * 512, o[n].x, o[n].y, o[n].z, o[n].w);
        }
        __syncwarp();
        mbar_arrive1(sb + B_BAR + (BB_DONE + (w >> 2)) * 8);
        nd++;
        CPROF(min(2 + u, 7));
        if (u == nu) break;
        if (LAGQ) { if (w >> 2) mbar_wait(sb + B_BAR + BB_GO * 8, ng & 1); ng++; }
        const uint64_t db1 = mkdesc(sb + (u >> 10), 4096, 1024, 1);
#pragma unroll
        for (int h = 0; h < 8; h++) {
            const uint64_t db = db1 + h * (STG_B >> 4);
            if (h) { mbar_wait(full + h * 8, ph); wg_wait<1>(); }
            wg_fence();
            if (h) wgmma128r<true>(acc, A[4 * h], db); else wgmma128r<false>(acc, A[0], db);
            wgmma128r<true>(acc, A[4 * h + 1], db + 128);
            wgmma128r<true>(acc, A[4 * h + 2], db + 512);
            wgmma128r<true>(acc, A[4 * h + 3], db + 640);
            wg_commit();
            if (h >= 2) mbar_arrive1_cluster(rel + (h - 2) * 8);
            if (h == LAGQ - 1 && w == 2) mbar_arrive1(sb + B_BAR + BB_GO * 8);
        }
        ph ^= 1;
    }
}

template <int NB>
__device__ __forceinline__ void load_resid(uint32_t* r, int layer, int ch, int w, int cb) {
#pragma unroll
    for (int i = 0; i < NB; i++) {
        const uint4 v = ldcg128(g_xA[layer] + ((ch * 8 + w) * 32 + cb + i) * 32 + (threadIdx.x & 31));
        r[4 * i] = v.x; r[4 * i + 1] = v.y; r[4 * i + 2] = v.z; r[4 * i + 3] = v.w;
    }
}
template <int NS>
__device__ __forceinline__ void part_load(uint4* v, int layer, int ch, int w, int cb, int ns) {
    const uint4* src = g_pp[layer] + (size_t)ch * MAXSPLIT * 8192 + (w * 32 + cb) * 32 + (threadIdx.x & 31);
#pragma unroll
    for (int i = 0; i < 2 * NS; i++) {
        asm volatile("{.reg .pred p; .reg .b128 t; setp.gt.s32 p,%6,0; mov.b128 t,{0,0,0,0}; @p ld.relaxed.gpu.global.L2::cache_hint.b128 t,[%4],%5; mov.b128 {%0,%1,%2,%3},t;}"
                     : "=r"(v[i].x), "=r"(v[i].y), "=r"(v[i].z), "=r"(v[i].w) : "l"(src + (i / NS) * 32 + (i % NS) * 8192), "l"(POL_LAST), "r"(ns - i % NS) : "memory");
    }
}
template <int NS>
__device__ __forceinline__ void part_sum(float* x, const uint4* v, const uint32_t* r) {
    const int dg = ((threadIdx.x & 31) >> 2) - 2 * (threadIdx.x & 3);
    const uint32_t idm = dg == 0 ? 0x00003f80u : dg == 1 ? 0x3f800000u : 0u;
#pragma unroll
    for (int b = 0; b < 2; b++) {
        float* y = x + b * 8;
#pragma unroll
        for (int i = 0; i < 8; i++) y[i] = 0;
#pragma unroll
        for (int s = 0; s < NS; s++) { mma8(y, v[b * NS + s].x, v[b * NS + s].y, idm); mma8(y + 4, v[b * NS + s].z, v[b * NS + s].w, idm); }
#pragma unroll
        for (int i = 0; i < 4; i++) { y[2 * i] = rbf(rbf(y[2 * i]) + blo(r[b * 4 + i])); y[2 * i + 1] = rbf(rbf(y[2 * i + 1]) + bhi(r[b * 4 + i])); }
    }
}

__device__ __forceinline__ float4 row_stats32(const float* x) {
    float a = (x[0] + x[1]) + (x[4] + x[5]) + (x[8] + x[9]) + (x[12] + x[13]);
    float b = (x[2] + x[3]) + (x[6] + x[7]) + (x[10] + x[11]) + (x[14] + x[15]);
    a += __shfl_xor_sync(0xffffffffu, a, 1); b += __shfl_xor_sync(0xffffffffu, b, 1);
    a += __shfl_xor_sync(0xffffffffu, a, 2); b += __shfl_xor_sync(0xffffffffu, b, 2);
    const float ma = a * (1.f / 32.f), mb = b * (1.f / 32.f);
    float qa = 0, qb = 0;
#pragma unroll
    for (int i = 0; i < 4; i++) {
        float d0 = x[4 * i] - ma, d1 = x[4 * i + 1] - ma, d2 = x[4 * i + 2] - mb, d3 = x[4 * i + 3] - mb;
        qa += d0 * d0 + d1 * d1; qb += d2 * d2 + d3 * d3;
    }
    qa += __shfl_xor_sync(0xffffffffu, qa, 1); qb += __shfl_xor_sync(0xffffffffu, qb, 1);
    qa += __shfl_xor_sync(0xffffffffu, qa, 2); qb += __shfl_xor_sync(0xffffffffu, qb, 2);
    return make_float4(a, qa, b, qb);
}

__device__ __forceinline__ void conv_stage(float* Y, uint32_t pbase, uint32_t ubase) {
    const int lane = threadIdx.x & 31, w = threadIdx.x >> 5, g = lane >> 2, c = lane & 3;
#pragma unroll
    for (int cp = 0; cp < 2; cp++) {
        const int chl = w * 4 + cp * 2 + (lane >> 4);
        const uint4 b = ldsm4(ubase + chl * 256 + ((lane >> 3) & 1) * 128 + (((lane & 7) ^ (chl & 7)) << 4));
#pragma unroll
        for (int h = 0; h < 2; h++) {
            const uint32_t pa = pbase + ((w * 4 + cp * 2 + h) * PW + 16 + g - 2 * c) * 4;
            uint32_t lo = lds32(pa - 32);
#pragma unroll
            for (int d = 0; d < 8; d++) {
                const uint32_t a0 = lds32(pa + d * 64), a1 = lds32(pa + d * 64 + 32);
                mma16(Y + ((cp * 2 + h) * 8 + d) * 4, a0, a1, lo, a0, h ? b.z : b.x, h ? b.w : b.y);
                lo = a1;
            }
        }
    }
}

__device__ __forceinline__ void conv_combine(const float* y8, float* cur, float* nxt) {
    const int lane = threadIdx.x & 31, c = lane & 3;
    cur[0] = y8[0]; cur[1] = y8[1] + y8[4]; cur[2] = y8[2]; cur[3] = y8[3] + y8[6];
    nxt[0] = y8[29]; nxt[1] = 0.f; nxt[2] = y8[31]; nxt[3] = 0.f;
#pragma unroll
    for (int e = 1; e < 4; e++) {
        const int src = (lane & ~3) | ((c - e) & 3);
        const float v0 = __shfl_sync(0xffffffffu, y8[8 * e] + y8[8 * e - 3], src), v1 = __shfl_sync(0xffffffffu, y8[8 * e + 1] + y8[8 * e + 4], src);
        const float v2 = __shfl_sync(0xffffffffu, y8[8 * e + 2] + y8[8 * e - 1], src), v3 = __shfl_sync(0xffffffffu, y8[8 * e + 3] + y8[8 * e + 6], src);
        if (c >= e) { cur[0] += v0; cur[1] += v1; cur[2] += v2; cur[3] += v3; }
        else { nxt[0] += v0; nxt[1] += v1; nxt[2] += v2; nxt[3] += v3; }
    }
}

__device__ __forceinline__ void hist_task(float* Y, uint32_t sb, int w, int ch, int q, int& st, uint32_t& ph, int nd) {
    const int lane = threadIdx.x & 31, chl = w * 2 + (lane >> 4);
    const uint32_t ua = sb + 12288 + chl * 256 + ((lane >> 3) & 1) * 128 + (((lane & 7) ^ (chl & 7)) << 4);
    const uint32_t pa = sb + (w * 2 * PW + 16 + (lane >> 2) - 2 * (lane & 3)) * 4;
#pragma unroll
    for (int i = 0; i < 128; i++) Y[i] = 0;
    uint4 b1 = make_uint4(0, 0, 0, 0);
#pragma unroll 1
    for (int j = ch + 1; j >= 2; j--) {
        const uint4 b0 = b1;
        mbar_wait(sb + B_BAR + (BB_FULL + st) * 8, ph);
        b1 = ldsm4(ua + st * STG_B);
        if (j == 2) b1 = make_uint4(0, 0, 0, 0);
#pragma unroll
        for (int h = 0; h < 2; h++) {
            const uint32_t o = pa + st * STG_B + h * PW * 4;
            uint32_t lo = lds32(o - 32);
#pragma unroll
            for (int d = 0; d < 8; d++) {
                const uint32_t a0 = lds32(o + d * 64), a1 = lds32(o + d * 64 + 32);
                mma16(Y + (h * 16 + d) * 4, a0, a1, lo, a0, h ? b0.z : b0.x, h ? b0.w : b0.y);
                mma16(Y + (h * 16 + 8 + d) * 4, a0, a1, lo, a0, h ? b1.z : b1.x, h ? b1.w : b1.y);
                lo = a1;
            }
        }
        bar_sync(NB_WG + (w >> 2), 128);
        stage_release(sb, w, st);
        if (++st == NSTG) { st = 0; ph ^= 1; }
    }
    mbar_wait(sb + B_BAR + (BB_SF + (w >> 2)) * 8, (nd & 1) ^ 1);
#pragma unroll
    for (int h = 0; h < 2; h++) {
        const int o = ((ch * 16 + (q >> 1)) * 4 + (w & 1) * 2 + h) * 256 + ((q & 1) * 4 + (w >> 1)) * 32 + lane;
        float c0[4], n0[4], c1[4], n1[4];
        conv_combine(Y + h * 64, c0, n0); conv_combine(Y + h * 64 + 32, c1, n1);
        g_carry[0][o] = make_float4(c0[0], c0[1], c0[2], c0[3]);
        g_carry[0][o + 16384] = make_float4(c1[0] + n0[0], c1[1] + n0[1], c1[2] + n0[2], c1[3] + n0[3]);
        g_carry[1][o + 32768] = make_float4(n1[0], n1[1], n1[2], n1[3]);
    }
}

__device__ __forceinline__ void conv_task(const Params& p, float* Y, uint32_t sb, int w, int ch, int q, int ns, bool dry, int& st, uint32_t& ph, int nd) {
    const int tid = threadIdx.x, lane = tid & 31, g = lane >> 2, c = lane & 3;
    uint32_t dk[4];
    const uint32_t sg = (~ch & 2) << 30;
    int sr = st;
    float x[16];
    PROF(tid == 128, 2048 + ch * 8);
#pragma unroll
    for (int i = 0; i < 128; i++) Y[i] = 0;
#pragma unroll 1
    for (int j = min(ch, 1 + (ch & 1)); j >= 1; j--) {
        mbar_wait(sb + B_BAR + (BB_FULL + st) * 8, ph);
        conv_stage(Y, sb + st * STG_B, sb + B_UT + ((ch - j) & 1) * 8192);
        if (++st == NSTG) { st = 0; ph ^= 1; }
    }
#define CONV_CARRY _Pragma("unroll 1") \
    for (int i = 0; i < min(ch, (ch & 1) ? 2 : 3); i++) { \
        if (i) mbar_wait(sb + B_BAR + (BB_FULL + st) * 8, ph); \
        const uint32_t ca = sb + (i ? st * STG_B : B_SP) + tid * 16; \
_Pragma("unroll") \
        for (int k = 0; k < 4; k++) { \
            const uint4 cr = lds128(ca + k * 4096); \
            Y[k * 32] += __uint_as_float(cr.x); Y[k * 32 + 1] += __uint_as_float(cr.y); Y[k * 32 + 2] += __uint_as_float(cr.z); Y[k * 32 + 3] += __uint_as_float(cr.w); \
        } \
        if (i && ++st == NSTG) { st = 0; ph ^= 1; } \
    } \
    bar_sync(NB_C, 256); \
_Pragma("unroll 1") \
    for (; sr != st; sr = (sr + 1) & (NSTG - 1)) stage_release(sb, w, sr); \
    mbar_wait(sb + B_BAR + (BB_SF + (w >> 2)) * 8, (nd & 1) ^ 1); \
    mbar_wait(sb + B_BAR + (BB_SF + 1 - (w >> 2)) * 8, (nd & 1) ^ 1);
    const uint32_t ut = sb + B_UT + (ch & 1) * 8192;
    if (CPOS == 0) { CONV_CARRY }
    PROF(tid == 128, 2048 + ch * 8 + 7);
    {
        uint4 v[2 * OPS1];
        wait_cnt_warp(cnt_ptr(C_OP0 + (q >> 3) * 2 + (w >> 2), ch + (w & 3) * 16), ns);
        part_load<OPS1>(v, 0, ch, w, 2 * q, ns);
        uint32_t rs[8];
        load_resid<2>(rs, 0, ch, w, 2 * q);
        if (CPOS == 1) { CONV_CARRY }
        part_sum<OPS1>(x, v, rs);
        const float4 s = row_stats32(x);
        float2* dst = g_st2 + ((ch & 1) * 16 + q) * 128 + w * 16 + g + c * 8;
        asm volatile("{.reg .pred p; setp.ne.u32 p,%2,0; @p st.relaxed.gpu.global.b64 [%0],%1;}" ::"l"(dst),
                     "l"(((uint64_t)((__float_as_uint(c ? s.w : s.y) & 0x7fffffffu) | sg) << 32) | __float_as_uint(c ? s.z : s.x)), "r"((uint32_t)(c < 2 && !dry)) : "memory");
        PROF(tid == 128, 2048 + ch * 8 + 1);
    }
#pragma unroll
    for (int i = 0; i < 4; i++) asm volatile("ld.global.nc.u32 %0,[%1];" : "=r"(dk[i]) : "l"(p.Dskip + q * 32 + i * 8 + 2 * c));
    if (CPOS == 2) { CONV_CARRY }
    float2 ln0, ln1;
    {
        const float2* src = g_st2 + ((ch & 1) * 16 + (lane >> 4) * 8) * 128 + w * 16 + (lane & 15);
        uint64_t v[8];
        int n = 0;
#pragma unroll
        for (int i = 0; i < 8; i++) v[i] = (uint64_t)~sg << 32;
        while (true) {
            bool bad = false;
#pragma unroll
            for (int i = 0; i < 8; i++) asm volatile("{.reg .pred p; setp.lt.s32 p,%2,0; @p ld.relaxed.gpu.global.b64 %0,[%1];}" : "+l"(v[i]) : "l"(src + i * 128), "r"((uint32_t)(v[i] >> 32) ^ sg) : "memory");
#pragma unroll
            for (int i = 0; i < 8; i++) bad = bad || (int)((uint32_t)(v[i] >> 32) ^ sg) < 0;
            if (!__any_sync(0xffffffffu, bad && !dry)) break;
            if (++n > 2000000) __trap();
        }
        float sm = 0;
#pragma unroll
        for (int i = 0; i < 8; i++) sm += __uint_as_float((uint32_t)v[i]);
        sm += __shfl_xor_sync(0xffffffffu, sm, 16);
        const float mean = sm * (1.f / 512.f);
        float M2 = 0;
#pragma unroll
        for (int i = 0; i < 8; i++) { const float d = __uint_as_float((uint32_t)v[i]) * (1.f / 32.f) - mean; M2 += fabsf(__uint_as_float((uint32_t)(v[i] >> 32))) + 32.f * d * d; }
        M2 += __shfl_xor_sync(0xffffffffu, M2, 16);
        const float2 o = ln_finish(mean, M2 * (1.f / 512.f));
        ln0.x = __shfl_sync(0xffffffffu, o.x, g); ln0.y = __shfl_sync(0xffffffffu, o.y, g);
        ln1.x = __shfl_sync(0xffffffffu, o.x, g + 8); ln1.y = __shfl_sync(0xffffffffu, o.y, g + 8);
    }
    PROF(tid == 128, 2048 + ch * 8 + 2);
    uint32_t u[8];
#pragma unroll
    for (int i = 0; i < 8; i++) {
        const float2 l = (i & 1) ? ln1 : ln0;
        u[i] = pack2(__fdividef(rbf(x[2 * i] - l.x), l.y), __fdividef(rbf(x[2 * i + 1] - l.x), l.y));
        const int chl = (i >> 1) * 8 + g;
        sts32(ut + chl * 256 + (i & 1) * 128 + ((w ^ g) << 4) + c * 4, movm(u[i]));
    }
    bar_sync(NB_C, 256);
    mbar_wait(sb + B_BAR + (BB_FULL + st) * 8, ph);
    PROF(tid == 128, 2048 + ch * 8 + 3);
    conv_stage(Y, sb + st * STG_B, ut);
    uint32_t yp[4][2];
    float nxt[4][4];
    {
        float y[4][4];
#pragma unroll
        for (int k = 0; k < 4; k++) conv_combine(Y + k * 32, y[k], nxt[k]);
#pragma unroll
        for (int i = 0; i < 4; i++) { yp[i][0] = pack2(y[0][i], y[1][i]); yp[i][1] = pack2(y[2][i], y[3][i]); }
    }
#pragma unroll
    for (int i = 0; i < 4; i++) sts64(sb + B_YT + (16 * (2 * c + (i & 1)) + g + (i >> 1) * 8) * 80 + w * 8, yp[i][0], yp[i][1]);
    bar_sync(NB_C, 256);
    stage_release(sb, w, st);
    if (++st == NSTG) { st = 0; ph ^= 1; }
    PROF(tid == 128, 2048 + ch * 8 + 4);
    uint32_t xo[8];
    uint4* dA = g_xA[1] + ((ch * 8 + w) * 32 + 2 * q) * 32 + lane;
#pragma unroll
    for (int i = 0; i < 8; i++) {
        const int col = (i >> 1) * 8 + 2 * c;
        const uint32_t yv = lds32(sb + B_YT + (w * 16 + g + (i & 1) * 8) * 80 + col * 2);
        const uint32_t dv = dk[i >> 1];
        x[2 * i] = rbf(x[2 * i] + rbf(blo(yv) + rbf(blo(u[i]) * blo(dv))));
        x[2 * i + 1] = rbf(x[2 * i + 1] + rbf(bhi(yv) + rbf(bhi(u[i]) * bhi(dv))));
        xo[i] = pack2(x[2 * i], x[2 * i + 1]);
        if ((i & 3) == 3) dA[(i >> 2) * 32] = make_uint4(xo[i - 3], xo[i - 2], xo[i - 1], xo[i]);
    }
    {
        const float4 s = row_stats32(x);
        float2* dst = g_st[1] + (ch * 16 + q) * 128 + w * 16 + g;
        if (c == 0) dst[0] = make_float2(s.x, s.y);
        if (c == 1) dst[8] = make_float2(s.z, s.w);
        __syncwarp();
    }
    PROF(tid == 128, 2048 + ch * 8 + 5);
    mbar_arrive1(sb + B_BAR + (BB_DONE + (w >> 2)) * 8);
    bar_sync(NB_C, 256);
#pragma unroll
    for (int k = 0; k < 4; k++) sts128(sb + B_SP + k * 4096 + tid * 16, __float_as_uint(nxt[k][0]), __float_as_uint(nxt[k][1]), __float_as_uint(nxt[k][2]), __float_as_uint(nxt[k][3]));
    PROF(tid == 128, 2048 + ch * 8 + 6);
}

__device__ __forceinline__ void out_store(const Params& p, const float* x, int ch, int cb, bool on) {
    const int lane = threadIdx.x & 31, w = threadIdx.x >> 5, g = lane >> 2, c = lane & 3;
#pragma unroll
    for (int h = 0; h < 2; h++) {
        const float* y = x + h * 2;
        uint32_t v0 = pack2(y[0], y[1]), v1 = pack2(y[4], y[5]), v2 = pack2(y[8], y[9]), v3 = pack2(y[12], y[13]);
        uint32_t t0 = (c & 1) ? v0 : v1, t1 = (c & 1) ? v2 : v3;
        t0 = __shfl_xor_sync(0xffffffffu, t0, 1); t1 = __shfl_xor_sync(0xffffffffu, t1, 1);
        if (c & 1) { v0 = t0; v2 = t1; } else { v1 = t0; v3 = t1; }
        t0 = (c & 2) ? v0 : v2; t1 = (c & 2) ? v1 : v3;
        t0 = __shfl_xor_sync(0xffffffffu, t0, 2); t1 = __shfl_xor_sync(0xffffffffu, t1, 2);
        if (c & 2) { v0 = t0; v1 = t1; } else { v2 = t0; v3 = t1; }
        asm volatile("{.reg .pred p; setp.ne.u32 p,%6,0; @p st.global.L2::cache_hint.v4.u32 [%0],{%1,%2,%3,%4},%5;}"
                     ::"l"(p.out + (size_t)(ch * 128 + w * 16 + g + h * 8) * 512 + cb * 16 + c * 8), "r"(v0), "r"(v1), "r"(v2), "r"(v3), "l"(POL_LATE), "r"((uint32_t)on));
    }
}
__device__ __forceinline__ void fin_task(const Params& p, int ch, int cb0, int ncb, int ns, bool dry) {
    const int w = threadIdx.x >> 5;
    uint32_t rs[8];
    wait_cnt_warp(cnt_ptr(C_CV, ch), 32);
    load_resid<2>(rs, 1, ch, w, cb0);
    wait_cnt_warp(cnt_ptr(C_OP1, ch), dry ? 0 : 256);
    for (int cb = cb0; cb < cb0 + ncb; cb += 2) {
        float x[16];
        if (cb != cb0) load_resid<2>(rs, 1, ch, w, cb);
        uint4 v[32];
        part_load<16>(v, 1, ch, w, cb, ns);
        part_sum<16>(x, v, rs);
        out_store(p, x, ch, cb, !dry);
    }
}

__device__ __forceinline__ void bulk_consumer(const Params& p, uint32_t sb, int cl, uint32_t rank, int w) {
    int st = 0; uint32_t ph = 0; int nd = 0, ng = 0;
    for (int ti = 0; ti < MAXT; ti++) {
        const Task t = task_of(p.task[list_of(cl)][ti], rank);
        const int type = t.type, layer = t.layer, ch = t.ch;
        if (type == T_END) break;
        bool staged = type != T_FIN;
        PROF(threadIdx.x == 0, 3600 + ti * 4);
        CPROF(0);
        if (type == T_QKV) {
            staged = false;
            #pragma unroll 1
            while (st) {
                if (!(w & 3)) { mbar_wait(sb + B_BAR + (BB_FULL + st) * 8, ph); stage_release(sb, 0, st); stage_release(sb, 1, st); }
                if (++st == NSTG) { st = 0; ph ^= 1; }
            }
            if (!(w & 3)) { sts32(sb + B_ST + 8, ph); bar_arrive(NB_PH, 96); }
            qkv_task(sb, w, layer, ch, t.b, ng, nd, ph, ti, p.zero);
            PROF(threadIdx.x == 128, 3600 + ti * 4 + 1);
        } else if (type == T_OP) {
            const int lane = threadIdx.x & 31;
            float acc[128];
            uint32_t r0 = sb + B_BAR + BB_IDLE * 8, r1 = r0;
            if (w >> 2) { mbar_wait(sb + B_BAR + BB_GO * 8, ng & 1); if ((t.c & 80) == 16) mbar_wait(sb + B_BAR + BB_LOW * 8, 0); }
            ng++;
            gemm_run<false>(acc, sb, w, 0, 1, r0, r1, st, ph);
            gemm_run<true>(acc, sb, w, 1, 2 * t.b, r0, r1, st, ph);
            mbar_wait(sb + B_BAR + (BB_SF + (w >> 2)) * 8, (nd & 1) ^ 1);
            wg_wait<1>();
            mbar_arrive1_cluster(r0);
            wg_wait<0>();
            mbar_arrive1_cluster(r1);
            PROF(threadIdx.x == 128, 3600 + ti * 4 + 1);
            if (t.c & 32) {
                staged = false;
                const int dg = (lane >> 2) - 2 * (lane & 3);
                const uint32_t idm = dg == 0 ? 0x00003f80u : dg == 1 ? 0x3f800000u : 0u;
                wait_cnt_warp(cnt_ptr(C_OP1, ch), 256 - 4 * t.b);
#pragma unroll 1
                for (int i = 0; i < (t.c & 15); i++) {
                    const uint4* src = op_dst(1, ch, i, w, (t.blk >> 2) & 1) + lane;
                    uint4 v[16];
#pragma unroll
                    for (int j = 0; j < 16; j++) v[j] = ldcg128_last(src + j * 32);
#pragma unroll
                    for (int j = 0; j < 16; j++) { mma8(acc + j * 8, v[j].x, v[j].y, idm); mma8(acc + j * 8 + 4, v[j].z, v[j].w, idm); }
                }
#pragma unroll
                for (int j = 0; j < 16; j += 4) {
                    uint32_t rs[16];
                    load_resid<4>(rs, 1, ch, w, (t.blk & 4) * 4 + j);
#pragma unroll
                    for (int i = 0; i < 16; i++) { float* y = acc + j * 8 + 2 * i; y[0] = rbf(y[0]) + blo(rs[i]); y[1] = rbf(y[1]) + bhi(rs[i]); }
                    out_store(p, acc + j * 8, ch, (t.blk & 4) * 4 + j, true); out_store(p, acc + j * 8 + 16, ch, (t.blk & 4) * 4 + j + 2, true);
                }
            } else if (!layer) {
                const int s2 = st + (w >> 1);
                const uint32_t o = sb + (s2 & (NSTG - 1)) * STG_B + (w & 1) * 8192 + lane * 16;
                mbar_wait(sb + B_BAR + (BB_FULL + (s2 & (NSTG - 1))) * 8, ph ^ (s2 >= NSTG));
#pragma unroll
                for (int j = 0; j < 16; j++)
                    sts128(o + j * 512, pack2(acc[j * 8], acc[j * 8 + 1]), pack2(acc[j * 8 + 2], acc[j * 8 + 3]), pack2(acc[j * 8 + 4], acc[j * 8 + 5]), pack2(acc[j * 8 + 6], acc[j * 8 + 7]));
                sts32(sb + B_ST + (w >> 2) * 4, st);
                st += 4;
                if (st >= NSTG) { st -= NSTG; ph ^= 1; }
            } else {
                uint4* dst = op_dst(layer, ch, t.c & 15, w, (t.blk >> 2) & 1) + lane;
#pragma unroll
                for (int n = 0; n < 16; n++) {
                    const int j = (n >> 1) + (n & 1) * 8;
                    const uint4 v = make_uint4(pack2(acc[j * 8], acc[j * 8 + 1]), pack2(acc[j * 8 + 2], acc[j * 8 + 3]), pack2(acc[j * 8 + 4], acc[j * 8 + 5]), pack2(acc[j * 8 + 6], acc[j * 8 + 7]));
                    if (j < 16 - NSB) stg128(dst + j * 32, v, out_pol(T_OP, layer, ch)); else sts128(sb + B_OUT + (w * NSB + j - (16 - NSB)) * 512 + lane * 16, v.x, v.y, v.z, v.w);
                }
            }
        } else if (type == T_CV) {
            float acc[128];
            if (layer) hist_task(acc, sb, w, ch, t.a + rank, st, ph, nd);
            else { conv_task(p, acc, sb, w, ch, t.a + rank, t.b, t.dry, st, ph, nd); staged = false; nd++; }
        } else {
            fin_task(p, ch, t.a + rank * t.c, t.c, t.b, t.dry);
        }
        if (staged) {
            __syncwarp();
            mbar_arrive1(sb + B_BAR + (BB_DONE + (w >> 2)) * 8);
            nd++;
        }
        PROF(threadIdx.x == 128, 3600 + ti * 4 + 2);
        __syncwarp();
    }
}

constexpr int P_Y = 131072  , P_PRM = P_Y  , P_K6 = P_PRM + 8192  ,
              P_P = P_Y + 40960  , P_U = P_P + 33280  , P_END = P_U + 17408, P_X = 98304  ;
static_assert(P_END <= B_BAR && P_END <= R_BAR, "prologue scratch");
#define KGUN 2
constexpr int KGU = KGUN;
__device__ __forceinline__ void csq(float& r, float& i) { const float t = r * i; r = fmaf(r, r, -(i * i)); i = t + t; }
__device__ __forceinline__ void cpow(float ar, float ph, float p, float& r, float& i) {
    const float e = ex2(ar * p);
    const float u = ph * p, n = fabsf(u) < 4194304.f ? (u + 12582912.f) - 12582912.f : u;
    const float t = (u - n) * 6.283185307179586f;
    r = e * __cosf(t); i = e * __sinf(t);
}
__device__ __forceinline__ void mma_tf32(float* c, float a0, float a1, float a2, float a3, float b0, float b1) {
    asm volatile("mma.sync.aligned.m16n8k8.row.col.f32.tf32.tf32.f32 {%0,%1,%2,%3},{%4,%5,%6,%7},{%8,%9},{%0,%1,%2,%3};"
                 : "+f"(c[0]), "+f"(c[1]), "+f"(c[2]), "+f"(c[3])
                 : "r"(__float_as_uint(a0)), "r"(__float_as_uint(a1)), "r"(__float_as_uint(a2)), "r"(__float_as_uint(a3)), "r"(__float_as_uint(b0)), "r"(__float_as_uint(b1)));
}

struct ProRegs { uint32_t v[2][4], ldt[2]; };
__device__ __forceinline__ void prologue_load(const ProArgs& a, int b, ProRegs& pr) {
    const int w = threadIdx.x >> 5;
#pragma unroll
    for (int i = 0; i < 2; i++) {
        const int gi = b * 512 + (w & 3) * 128 + ((w >> 2) & 1) * 64 + i * 32 + (threadIdx.x & 31);
        pr.ldt[i] = __ldg((const uint16_t*)a.ldt + b * 4 + (w & 3));
        pr.v[i][0] = __ldg((const uint16_t*)a.lAr + gi); pr.v[i][1] = __ldg((const uint16_t*)a.Ai + gi);
        pr.v[i][2] = __ldg((const uint16_t*)a.Cr + gi); pr.v[i][3] = __ldg((const uint16_t*)a.Ci + gi);
    }
}
__device__ __forceinline__ void prologue(const ProArgs& a, uint32_t sb, int b, int w, const ProRegs& pr, uint32_t zero) {
    const int tid = threadIdx.x, lane = tid & 31, g = lane >> 2, c = lane & 3;
    const int d0 = b * 4;
    if (w >= 8) {
        const int t2 = tid - 256;
        PROF(t2 == 0, 3516);
        const int gi = b * 128 + t2;
        if (t2 < 32) acc_init(a.mem0, b * 32 + t2);
        if (t2 >= 112) ((uint4*)g_st2)[b * 16 + t2 - 112] = make_uint4(0, 0, 0, 0);
        if (gi < 13 * 64) g_cnt[gi] = 0;
        bar_sync(6, 384);
        if (gi < 512) g_st[0][(gi >> 8) * 2048 + (lds32(sb + S_TAG) ^ 1) * 256 + (gi & 255)] = make_float2(0.f, 0.f);
        asm volatile("{.reg .pred p; elect.sync _|p,0xffffffff; @p cp.async.bulk.prefetch.L2.global [%0],32768;}"
                     ::"l"((w == 8 ? a.Wq : w == 9 ? a.Wk : w == 10 ? a.Wv : a.Wo) + (size_t)b * 16384) : "memory");
        mbar_wait(sb + S_XBAR, 0);
        uint32_t l[16];
        int n = 0;
        while (true) {
            bool ok = true;
#pragma unroll
            for (int i = 0; i < 16; i++) asm volatile("ld.relaxed.gpu.global.u32 %0,[%1];" : "=r"(l[i]) : "l"(g_ln0 + i * 128 + t2) : "memory");
#pragma unroll
            for (int i = 0; i < 16; i++) ok = ok && l[i];
            if (__all_sync(0xffffffffu, ok)) break;
            if (++n > 2000000) __trap();
        }
#pragma unroll 1
        for (int h = 0; h < 2; h++) {
#pragma unroll
            for (int i = 0; i < 8; i++) {
                const int t = h * 1024 + i * 128 + t2;
                const uint2 x = lds64(sb + P_X + t * 16 + (b & 1) * 8);
                const float m = blo(l[i]), rs = rcp(bhi(l[i]));
                l[i] = l[i + 8];
                const uint32_t u0 = pack2(rbf(blo(x.x) - m) * rs, rbf(bhi(x.x) - m) * rs), u1 = pack2(rbf(blo(x.y) - m) * rs, rbf(bhi(x.y) - m) * rs);
                sts128(sb + P_X + t * 16, x.x, x.y, u0, u1);
                const uint32_t o = sb + P_U + ((t >> 3) & 1) * 2176 + ((t >> 4) + 8) * 16 + (t & 7) * 2;
                asm volatile("st.shared.u16 [%0],%1;" ::"r"(o), "h"((uint16_t)u0) : "memory");
                asm volatile("st.shared.u16 [%0],%1;" ::"r"(o + 4352), "h"((uint16_t)(u0 >> 16)) : "memory");
                asm volatile("st.shared.u16 [%0],%1;" ::"r"(o + 8704), "h"((uint16_t)u1) : "memory");
                asm volatile("st.shared.u16 [%0],%1;" ::"r"(o + 13056), "h"((uint16_t)(u1 >> 16)) : "memory");
            }
        }
        PROF(t2 == 0, 3517);
        bar_sync(9, 384);
        fence_async_smem();
#pragma unroll 1
        for (int j = 0; j < 16; j++) {
            const int d = d0 + w - 8;
            asm volatile("{.reg .pred p; elect.sync _|p,0xffffffff; @p cp.async.bulk.global.shared::cta.bulk_group [%0],[%1],%2;}" ::"l"(g_P + (((d >> 5) * 16 + j) * 32 + (d & 31)) * PW),
                         "r"(sb + P_P + ((w - 8) * 2080 + j * 128) * 4), "r"(PW * 4) : "memory");
        }
        asm volatile("cp.async.bulk.commit_group; cp.async.bulk.wait_group 0;" ::: "memory");
        bar_arrive(10, 384);
        return;
    }
#pragma unroll
    for (int i = 0; i < 2; i++) {
        const float dt = rbf(expf(blo(pr.ldt[i])));
        const float ar = -rbf(expf(blo(pr.v[i][0]))) * dt, ai = blo(pr.v[i][1]) * dt;
        sts128(sb + P_PRM + (w * 64 + i * 32 + lane) * 16, __float_as_uint(ar * 1.4426950408889634f), __float_as_uint(ai * 0.15915494309189535f),
               __float_as_uint(2.f * (blo(pr.v[i][2]) * dt)), __float_as_uint(2.f * (blo(pr.v[i][3]) * dt)));
    }
    if (tid < 64) sts128(sb + P_U + (tid >> 3) * 2176 + (tid & 7) * 16, 0, 0, 0, 0);
    bar_arrive(6, 384);
    __syncwarp();
    PROF(tid == 0, 3510);
    const int ch = w & 3, hf = w >> 2;
    {
        float k0[4] = {0, 0, 0, 0}, k1[4] = {0, 0, 0, 0}, k2[4] = {0, 0, 0, 0}, k3[4] = {0, 0, 0, 0}, k4[4] = {0, 0, 0, 0}, kl = 0;
#pragma unroll KGU
        for (int j = 0; j < 16; j++) {
            const uint4 q = lds128(sb + P_PRM + (w * 64 + j * 4 + c) * 16);
            const float cr = __uint_as_float(q.z), ci = __uint_as_float(q.w);
            float wr[4], wi[4], vr[4], vi[4];
            cpow(__uint_as_float(q.x), __uint_as_float(q.y), (float)g, wr[0], wi[0]);
            cpow(__uint_as_float(q.x), __uint_as_float(q.y), (float)(g + 8), vr[0], vi[0]);
#pragma unroll
            for (int i = 1; i < 4; i++) { wr[i] = wr[i - 1]; wi[i] = wi[i - 1]; csq(wr[i], wi[i]); vr[i] = vr[i - 1]; vi[i] = vi[i - 1]; csq(vr[i], vi[i]); }
            float hr = wr[3], hi = wi[3];
            csq(hr, hi);
            mma_tf32(k0, wr[0], vr[0], wi[0], vi[0], cr * hr - ci * hi, -(cr * hi + ci * hr));
            hr = vr[3]; hi = vi[3]; csq(hr, hi);
            mma_tf32(k1, wr[0], vr[0], wi[0], vi[0], cr * hr - ci * hi, -(cr * hi + ci * hr));
            csq(hr, hi);
            mma_tf32(k2, wr[1], vr[1], wi[1], vi[1], cr * hr - ci * hi, -(cr * hi + ci * hr));
            csq(hr, hi);
            mma_tf32(k3, wr[2], vr[2], wi[2], vi[2], cr * hr - ci * hi, -(cr * hi + ci * hr));
            csq(hr, hi);
            mma_tf32(k4, wr[3], vr[3], wi[3], vi[3], cr * hr - ci * hi, -(cr * hi + ci * hr));
            csq(hr, hi);
            kl += cr * hr - ci * hi;
        }
        kl += __shfl_xor_sync(0xffffffffu, kl, 1); kl += __shfl_xor_sync(0xffffffffu, kl, 2);
        const uint32_t o = sb + P_K6 + (ch * 656 + c * 32 + g) * 4, ol = sb + P_K6 + (ch * 656 + 640) * 4;
#define KST(k, base) sts32(o + (base) * 4, __float_as_uint(k[0])); sts32(o + (base) * 4 + 64, __float_as_uint(k[1])); \
                     sts32(o + (base) * 4 + 32, __float_as_uint(k[2])); sts32(o + (base) * 4 + 96, __float_as_uint(k[3]))
#define KAD(k, base) k[0] += __uint_as_float(lds32(o + (base) * 4)); k[1] += __uint_as_float(lds32(o + (base) * 4 + 64)); \
                     k[2] += __uint_as_float(lds32(o + (base) * 4 + 32)); k[3] += __uint_as_float(lds32(o + (base) * 4 + 96))
        if (hf == 0) {
            bar_sync(2 + ch, 64);
            KAD(k0, 0); KAD(k1, 128); KAD(k2, 256); KAD(k3, 384); KAD(k4, 512);
            kl += __uint_as_float(lds32(ol));
            __syncwarp();
        }
        KST(k0, 0); KST(k1, 128); KST(k2, 256); KST(k3, 384); KST(k4, 512);
        if (lane == 0) sts32(ol, __float_as_uint(kl));
        if (hf == 1) { __syncwarp(); bar_arrive(2 + ch, 64); }
    }
    PROF(tid == 0, 3511);
    bar_sync(8, 384);
    PROF(tid == 0, 3512);
    if (tid < 64) sts32(sb + P_P + ((tid >> 4) * 2080 + (tid & 15)) * 4, 0);
#pragma unroll 1
    for (int x = tid; x < 2048; x += 512) {
        uint32_t pw[2][4];
#pragma unroll
        for (int h = 0; h < 2; h++) {
            const int y = x + h * 256;
            const int i0 = y <= 256 ? y : 256 + (int)((pack2((float)y, 0.f) & 0xffff) - 0x4380);
            const int i1 = y <= 256 ? max(y - 1, 0) : 256 + (int)((pack2((float)(y - 1), 0.f) & 0xffff) - 0x4380);
#pragma unroll
            for (int k = 0; k < 4; k++) {
                const float lo = __uint_as_float(lds32(sb + P_K6 + k * 2624 + i0 * 4)), hi = __uint_as_float(lds32(sb + P_K6 + k * 2624 + i1 * 4));
                pw[h][k] = pack2(lo, y ? hi : 0.f);
            }
        }
#pragma unroll
        for (int h = 0; h < 2; h++)
#pragma unroll
            for (int k = 0; k < 4; k++) sts32(sb + P_P + (k * 2080 + x + h * 256 + 16) * 4, pw[h][k]);
    }
    bar_sync(9, 384);
    PROF(tid == 0, 3513);
    {
        float acc[16][4];
#pragma unroll
        for (int j = 0; j < 16; j++) acc[j][0] = acc[j][1] = acc[j][2] = acc[j][3] = 0;
#pragma unroll 1
        for (int e = hf * 4; e < hf * 4 + 4; e++) {
            uint32_t B[16][2];
            const uint32_t ua = sb + P_U + ch * 4352 + ((lane >> 3) & 1) * 2176 + (8 + (lane >> 4) * 8 + (lane & 7) - e) * 16;
            const uint32_t pa = sb + P_P + (ch * 2080 + 16 + e * 16 + g - 2 * c) * 4;
            uint4 A[16];
#define TLD(d) A[d] = make_uint4(lds32(pa + (d) * 512), lds32(pa + (d) * 512 + 32), lds32(pa + (d) * 512 - 32), 0)
            TLD(0); TLD(15);
#pragma unroll
            for (int j = 0; j < 8; j++) { const uint4 v = ldsm4(ua + j * 256); B[2 * j][0] = v.x; B[2 * j][1] = v.y; B[2 * j + 1][0] = v.z; B[2 * j + 1][1] = v.w; }
#pragma unroll
            for (int d = 0; d < 8; d++) {
                if (d < 7) { TLD(d + 1); TLD(14 - d); }
                A[d].w = A[d].x + zero; A[15 - d].w = A[15 - d].x + zero;
                sfence(zero);
#pragma unroll
                for (int j = 15 - d; j < 16; j++) mma16(acc[j], A[15 - d].x, A[15 - d].y, A[15 - d].z, A[15 - d].w, B[j - 15 + d][0], B[j - 15 + d][1]);
#pragma unroll
                for (int j = d; j < 16; j++) { mma16(acc[j], A[d].x, A[d].y, A[d].z, A[d].w, B[j - d][0], B[j - d][1]); sfence(zero); }
            }
        }
        PROF(tid == 0, 3514);
        const uint32_t o = sb + P_Y + (ch * 2560 + c * 40 + g) * 4;
#pragma unroll
        for (int j = 0; j < 8; j++) {
#pragma unroll
            for (int i = 0; i < 4; i++) { const float lo = acc[j][i], hi = acc[j + 8][i]; acc[j][i] = hf ? hi : lo; sts32(o + (j + 8 - hf * 8) * 640 + (i & 1) * 80 + (i >> 1) * 32, __float_as_uint(hf ? lo : hi)); }
        }
        bar_sync(2 + ch, 64);
#pragma unroll
        for (int j = 0; j < 8; j++) {
#pragma unroll
            for (int i = 0; i < 4; i++) acc[j][i] += __uint_as_float(lds32(o + (j + hf * 8) * 640 + (i & 1) * 80 + (i >> 1) * 32));
        }
#pragma unroll
        for (int j = 0; j < 8; j++) {
#pragma unroll
            for (int i = 0; i < 4; i++) sts32(o + (j + hf * 8) * 640 + (i & 1) * 80 + (i >> 1) * 32, __float_as_uint(acc[j][i]));
        }
    }
    const uint2 dk = __ldg((const uint2*)(a.Dk + d0));
    bar_sync(1, 256);
#pragma unroll 2
    for (int i = 0; i < 8; i++) {
        const int t = i * 256 + tid;
        const uint32_t o = sb + P_Y + (t + 4 * (t >> 4)) * 4;
        const uint4 xu = lds128(sb + P_X + t * 16);
        float y[4];
#pragma unroll
        for (int k = 0; k < 4; k++) y[k] = rbf(__uint_as_float(lds32(o + k * 10240)));
        uint2 r;
        r.x = pack2(blo(xu.x) + rbf(y[0] + rbf(blo(xu.z) * blo(dk.x))), bhi(xu.x) + rbf(y[1] + rbf(bhi(xu.z) * bhi(dk.x))));
        r.y = pack2(blo(xu.y) + rbf(y[2] + rbf(blo(xu.w) * blo(dk.y))), bhi(xu.y) + rbf(y[3] + rbf(bhi(xu.w) * bhi(dk.y))));
        {
            const bool up = t & 8;
            const uint32_t o = __shfl_xor_sync(0xffffffffu, up ? r.x : r.y, 8);
            ((uint2*)(g_xA[0] + ((t >> 4) * 32 + (d0 >> 4)) * 32 + (t & 7) * 4 + ((d0 >> 1) & 2) + up))[(d0 >> 3) & 1] = up ? make_uint2(o, r.y) : make_uint2(r.x, o);
        }
        if (i == 0) {
            const float e0 = blo(r.x), e1 = bhi(r.x), e2 = blo(r.y), e3 = bhi(r.y);
            asm volatile("red.relaxed.gpu.global.add.v2.f32 [%0],{%1,%2};" ::"l"(g_st[0] + (t >> 7) * 2048 + lds32(sb + S_TAG) * 256 + (b & 1) * 128 + (t & 127)),
                         "f"((e0 + e1) + (e2 + e3)), "f"((e0 * e0 + e1 * e1) + (e2 * e2 + e3 * e3)) : "memory");
        }
    }
    PROF(tid == 0, 3515);
    bar_sync(10, 384);
}

__global__ void __cluster_dims__(2, 1, 1) __launch_bounds__(384, 1) main_kernel(const __grid_constant__ Params p) {
    extern __shared__ __align__(1024) uint8_t smem[];
    const uint32_t sb = __shfl_sync(0xffffffffu, smem_u32(smem), 0);
    uint32_t rank; asm("mov.u32 %0,%%cluster_ctarank;" : "=r"(rank));
    const int wi = __shfl_sync(0xffffffffu, threadIdx.x >> 5, 0);
    const int cl = blockIdx.x >> 1, wg = wi >> 2;
    const bool rec = p.rec0 >= 0 && cl >= p.rec0 && cl < p.rec0 + 32;
    PROF(threadIdx.x == 0, 3500);
    ProRegs pr;
    if ((wi >> 1) == 4 && p.dopro && cl >= 2) {
        const int g = (threadIdx.x & 31) >> 2, c = threadIdx.x & 3, row = (blockIdx.x - 4) * 16 + (wi - 8) * 8 + g;
        const float4 r4 = row_stats((const uint4*)(p.pa.x + (size_t)row * 512) + c, 4);
        const float2 r = make_float2(r4.x + r4.z, r4.y + r4.w);
        const float2 l = ln_finish(r.x * (1.f / 512.f), fmaxf(r.y - r.x * r.x * (1.f / 512.f), 0.f) * (1.f / 512.f));
        if (c == (g >> 1)) asm volatile("st.relaxed.gpu.global.u32 [%0],%1;" ::"l"(g_ln0 + row), "r"(pack2(l.x, l.y)) : "memory");
        __syncwarp();
    }
    prologue_load(p.pa, max((int)blockIdx.x - 4, 0), pr);
    if (rec) rec_init(p, sb, cl - p.rec0, rank); else bulk_init(sb);
    if (threadIdx.x == 352 && p.dopro && cl >= 2) {
        mbar_init(sb + S_XBAR, 1);
        asm volatile("fence.mbarrier_init.release.cluster;" ::: "memory");
        mbar_expect(sb + S_XBAR, 32768);
        for (int j = 0; j < 8; j++) tma2d(sb + P_X + j * 4096, &p.tm[3], ((blockIdx.x - 4) >> 1) * 8, j * 256, sb + S_XBAR);
    }
    if (threadIdx.x == 320) {
        unsigned v;
        asm volatile("ld.relaxed.gpu.global.u32 %0,[%1];" : "=r"(v) : "l"(g_gate) : "memory");
        v = v / (4 * NCL) + p.dopro;
        sts64(sb + S_GATE, v * (4 * NCL), v & 1);
    }
    __syncwarp();
    asm volatile("barrier.cluster.arrive.relaxed.aligned;" ::: "memory");
    if (wg == 2) bar_arrive(8, 384);
    if (p.dopro && cl >= 2) prologue(p.pa, sb, blockIdx.x - 4, wi, pr, p.zero); else if (wg < 2) bar_sync(8, 384);
    asm volatile("barrier.cluster.wait.aligned;" ::: "memory");
    fence_async_smem();
    bar_sync(wg == 2 ? 7 : 1, wg == 2 ? 128 : 256);
    if (p.dopro && (threadIdx.x == 32 || threadIdx.x == 352)) red_release(g_gate, 1);
    if (rec) {
        if (threadIdx.x == 0) {
            rec_fetch(&p.tm[1], sb + R_STK, (cl - p.rec0) * 128, rank * 256, 2, sb + R_BAR + RB_INIT * 8);
            rec_fetch(&p.tm[2], sb + R_STV, (cl - p.rec0) * 128, rank * 256, 2, sb + R_BAR + RB_INIT * 8);
        }
    }
    PROF(threadIdx.x == 0, 3506);
    __syncwarp();
    if (rec) {
        const int head = cl - p.rec0;
        if (wg == 2) {
            reg_dec<RH>();
            const int w = wi & 3;
            if (threadIdx.x == 256) rec_fetch(&p.tm[0], sb + R_STQ, head * 128, rank * 256, 2, sb + R_BAR + RB_INIT * 8);
            __syncwarp();
            wait_cnt_warp(g_gate, lds32(sb + S_GATE));
            if (p.dostats) x1_stats((head * 2 + rank) * 4 + w);
            __syncthreads();
            cluster_sync();
            if ((p.chains >> (w >> 1)) & 1) rec_attn(p, sb, w >> 1, w & 1, head, rank);
        } else {
            reg_inc<RW0>();
            rec_weights(p, sb, head, rank, wi);
        }
    } else {
        if (wg == 2) {
            reg_dec<40>();
            const int w = wi & 3;
            if (w == 0) bulk_producer(p, sb, cl, rank); else if (w >= 2) bulk_release(p, sb, cl, rank, w - 2); else bulk_relay(p, sb, cl);
        } else { reg_inc<232>(); bulk_consumer(p, sb, cl, rank, wi); }
    }
    __syncwarp();
    cluster_sync();
}

typedef CUresult (*EncFn)(CUtensorMap*, CUtensorMapDataType, cuuint32_t, void*, const cuuint64_t*, const cuuint64_t*, const cuuint32_t*, const cuuint32_t*,
                          CUtensorMapInterleave, CUtensorMapSwizzle, CUtensorMapL2promotion, CUtensorMapFloatOOBfill);
inline uint32_t mk(int type, int layer, int ch, int a, int b, int c) { return type | (layer << 3) | (ch << 4) | (a << 8) | (b << 16) | ((uint32_t)c << 24); }
constexpr int SMEM_BYTES = 232448;

struct Sched {
    Params* P; int n[NCL];
    void clear() { memset(P->task, 0, sizeof(P->task)); memset(n, 0, sizeof(n)); }
    void add(int cl, uint32_t t) { if (n[cl] < MAXT - 1) P->task[list_of(cl)][n[cl]++] = t; }
};

constexpr int REC0 = 4;
struct Cfg { int LAG, TS1, TS2, DQU, DQO, DUN, DHN, MARG, NQ1, FAST0, n0, oc, fc, nuns, ns2, nhg, hs, osl, nfin, dry, tl, c8, o9; };
#define HALVES 1
#define PLAN 14, 2200, 2850, 2400, 900, 5400, 380, 0, 4, 0, 12, 14, 14, 6, 4, 8, 4000, 0, 0, 8500, 0, 12, 4
Cfg g_cfg = {PLAN};
double g_est;
bool g_planned = false;
struct Plan { uint32_t w[NCL][MAXT]; int n[NCL]; double end, rec; };
void simulate(Plan& L, int nc, const Cfg& C) {
    const int LAG = C.LAG, NQ1 = C.NQ1, FAST0 = C.FAST0, n0 = C.n0, oc = C.oc, fc = C.fc, nuns = C.nuns, ns2 = C.ns2, nhg = C.nhg;
    const double TS1 = C.TS1, TS2 = C.TS2, DQU = C.DQU, DQO = C.DQO, DUN = C.DUN, DHN = C.DHN, MARG = C.MARG, hs = C.hs;
    const double INF = 1e18, DKB = 600, DOV = 700, DH = DHN, DHO = 1100, DF = 2200, DFB = 200, POLL = 450, FILL = 500, PUB = 600;
    enum { Q0, O0, Q1, HB, O1, FI, NK };
    struct Grp { int n, left; double done; } G[NK][16];
    double fr[NCL], it[100] = {}, cv[16];
    int ns[16], last[2][NCL], uc = 0, nit = 0;
    memset(L.n, 0, sizeof(L.n)); L.end = 0;
    auto fast = [&](int c) { return c < FAST0 || c >= fc; };
    for (int c = 0; c < 16; c++) {
        ns[c] = c < nuns ? 1 : c == 15 ? 16 : c >= C.c8 ? 8 : ns2;
        const int cnt[NK] = {c < 2 ? 48 : (c & 1) ? 0 : 96, c >= oc ? OPS1 : c >= C.o9 ? 9 : 8, c == 15 ? 24 : fast(c) ? 16 : 48 / NQ1, c >= 2 && !(c & 1) ? 16 : 0, ns[c], c < C.nfin || ns[c] == 1 ? 0 : c >= 14 ? 8 : 4};
        for (int k = 0; k < NK; k++) G[k][c] = {cnt[k], cnt[k], 0};
        cv[c] = INF;
    }
    for (int i = 0; i < nc; i++) { fr[i] = 0; last[0][i] = last[1][i] = -1; }
    auto fin = [&](int k, int c) { if ((k == Q0 && c >= 2) || k == HB) c &= ~1; return G[k][c].left ? INF : G[k][c].done; };
    auto len = [&](int i) { return (i >= LAG && i < 64) ? (double)TS2 : (double)TS1; };
    auto end_it = [&](int i) { return i < nit ? it[i] + len(i) : INF; };
    auto nominal = [&](int i) { if (i < nit) return it[i]; double t = nit ? it[nit - 1] : 11000 - TS1; for (int j = nit - 1; j < i; j++) t += len(j); return t; };
    auto put = [&](int i, uint32_t w) { if (L.n[i] < MAXT - 2) L.w[i][L.n[i]++] = w; else L.end = INF; };
    auto rel = [&](int k, int c) {
        switch (k) {
            case Q0: return 0.0;
            case O0: return end_it(4 * c + 3) + PUB + POLL;
            case Q1: return cv[c] + POLL;
            case HB: return cv[c - 2] + 600 + POLL;
            case O1: return fmax(end_it(LAG + 4 * c + 3) + PUB + POLL, G[O1][c].left == 1 && !G[FI][c].n ? G[O1][c].done - DKB * 64 / ns[c] : 0);
            default: return fin(O1, c) + POLL;
        }
    };
    auto dur = [&](int k, int c) {
        switch (k) {
            case Q0: return DQO + (c < 2 ? 2.0 : 1.0) * DQU;
            case O0: return (16 - G[O0][c].n) * DKB + 1200;
            case HB: return DHO + DH * c;
            case Q1: return DQO + 48.0 / G[Q1][c].n * DQU;
            case O1: return DOV + DKB * 64 / ns[c] + (G[O1][c].left == 1 && !G[FI][c].n ? 700 + 800 * ns[c] : 0);
            default: return DF + DFB * ns[c] * (c >= 14 ? 0.5 : 1);
        }
    };
    auto o0_est = [&](int c) {
        double t = uc ? cv[uc - 1] - 900 : 0;
        for (int j = uc; j < c; j++) t = fmax(t, nominal(4 * j + 4) + PUB + POLL + FILL) + dur(O0, j) + DUN;
        return fmax(t, nominal(4 * c + 4) + PUB + POLL);
    };
    auto cv_est = [&](int c) { return c < uc ? cv[c] : o0_est(c) + FILL + dur(O0, c) + DUN + 900; };
    auto slot = [&](int k, int c, int i) { return k == O0 ? (i < 8 ? i : nc + 7 - i) : c == 15 ? i : i - 8; };
    while (true) {
        while (nit < 64 + LAG) {
            double t = nit ? end_it(nit - 1) : 0;
            if (nit < 64) t = fmax(t, fin(Q0, nit >> 2) + POLL);
            if (nit >= LAG) t = fmax(t, fin(Q1, (nit - LAG) >> 2) + (nit < 64 ? 0 : POLL));
            if (t >= INF) break;
            it[nit++] = t;
        }
        int i = -1;
        for (int j = 0; j < nc; j++) if (fr[j] < INF && (i < 0 || fr[j] < fr[i])) i = j;
        if (i < 0) break;
        const double t = fr[i];
        double lim = INF;
        if (i < 8 && last[0][i] == uc) {
            if (G[O0][uc].left || fin(HB, uc) >= INF) { fr[i] = t + 200; continue; }
            const double e = fmax(G[O0][uc].done, fin(HB, uc) - 2000) + DUN;
            for (int j = 0; j < 8; j++) { put(j, mk(T_CV, 0, uc, 2 * j, G[O0][uc].n, 0)); fr[j] = e; }
            cv[uc++] = e + 900;
            continue;
        }
        const bool hg = (unsigned)(i - 24) < (unsigned)nhg;
        double hlim = INF;
        for (int c = 2; c < 16 && hg; c++) if (G[HB][c].left) { hlim = cv_est(c - 2) + hs; break; }
        int mine[2] = {-1, -1};
        for (int k = 0; k < 2; k++)
            for (int c = last[k][i] + 1; c < 16 && mine[k] < 0; c++) if ((unsigned)slot(O0 + k, c, i) < (unsigned)G[O0 + k][c].n) mine[k] = c;
        if (mine[0] >= 0) lim = i < 8 ? o0_est(mine[0]) - (uc ? 0 : C.dry) : nominal(4 * mine[0] + 4) + PUB + C.osl;
        else if (mine[1] >= 0) lim = cv_est(mine[1]) + POLL;
        else if ((i < 16 && G[O1][15].left) || (i < 8 && G[FI][15].left)) lim = fmin(lim, nominal(64 + LAG) + PUB - C.tl);
        int bk = -1, bc = 0; double bd = INF;
        for (int k = 0; k < NK; k++)
            for (int c = 0; c < 16; c++) {
                const bool urgent = k == O0 || k == Q1 || (k >= O1 && c == 15);
                if (!G[k][c].left || ((k == O0 || k == Q1) && c != mine[k - O0]) || (k >= O1 && c == 15 && i >= G[k][c].n)) continue;
                if (rel(k, c) > t || (t + dur(k, c) + (k == Q0 && c >= 2 ? DQU : 0) > lim && !urgent)) continue;
                if (i < 8 && uc && uc < 16 && k != O0) continue;
                if ((k == HB && !hg && i < nc - 2) || (k != HB && !urgent && t + dur(k, c) + (k == Q0 && c >= 2 ? DQU : 0) > hlim)) continue;
                const double dl = urgent ? -INF : k == HB ? -INF / 2 : k == Q0 ? nominal(4 * c) - 3000 : 1e9 + c * 2 + (k == O1);
                if (dl < bd) { bd = dl; bk = k; bc = c; }
            }
        if (bk < 0) {
            bool any = i < 8 && uc < 16;
            for (int k = 0; k < NK; k++) for (int c = 0; c < 16; c++) any = any || G[k][c].left;
            fr[i] = any ? t + 200 : INF;
            if (t > 400000) { L.end = INF; return; }
            continue;
        }
        Grp& g = G[bk][bc];
        const int n = g.n - g.left, c = bc;
        int nu = 1;
        double d = dur(bk, c);
        if (bk == Q0) for (nu = c < 2 ? 2 : 1; c >= 2 && nu < g.left && (nu < 2 || (nu < n0 && t + d + DQU < fmin(fmin(lim, hlim), bd - MARG))); nu++) d += DQU;
        if (bk == O0 && i >= 8) d += (g.n - 8) * DKB;
        if (bk == Q0 && !c && n >= 32) { nu = 1; d -= DQU; }
        if (bk == O0 || bk == Q1) last[bk - O0][i] = c;
        if (bk == O0 && !c && i < 8 && C.dry) put(i, mk(T_CV, 0, 1, 2 * i, 0, 128));
        g.left -= nu;
        const bool fini = bk == O1 && !g.left && !G[FI][c].n;
        const double e = fmax(fmax(t, rel(bk, c) + FILL) + (t < 1 ? 3500 : 0) + d, fini ? g.done + POLL + 700 + 800 * ns[c] : 0);
        fr[i] = e;
        g.done = fmax(g.done, e + (bk == O1 ? (c == 15 ? -500 : 1500) : bk == O0 ? 0 : (bk == Q1 && g.n < 24) || (bk == Q0 && !c && nu == 2) ? -500 : 1000));
        if (bk == FI || fini) L.end = fmax(L.end, e);
        put(i, bk == Q0 ? (c == 0 ? mk(T_QKV, 0, 0, n < 32 ? n : 2 * n - 32, nu, 32) : c == 1 ? mk(T_QKV, 0, c, n, 2, 24) : mk(T_QKV, 0, c, n, nu, 64))
             : bk == O0 ? (i < 8 ? mk(T_OP, 0, c, i * (16 - g.n), 16 - g.n, i) : mk(T_OP, 0, c, 64 - (nc - i) * 8, 8, slot(O0, c, i)))
             : bk == HB ? mk(T_CV, 1, c, 2 * n, 0, 0)
             : bk == Q1 ? mk(T_QKV, 1, c, slot(Q1, c, i) * 2, 48 / g.n, g.n)
             : bk == O1 ? mk(T_OP, 1, c, n * 64 / ns[c], 64 / ns[c], n + (fini ? 32 : c == 15 && HALVES ? 16 : 0))
                        : mk(T_FIN, 1, c, n * (32 / g.n), ns[c], 16 / g.n));
    }
    L.rec = end_it(63 + LAG);
}
void plan(Params& P) {
    P.rec0 = REC0; P.chains = 3; P.lag = g_cfg.LAG; P.dostats = 1; P.dopro = 1;
    static Plan L;
    int cls[NCL], nc = 0;
    for (int c = REC0 + 32; c < NCL; c++) cls[nc++] = c;
    for (int c = REC0 - 1; c >= 0; c--) cls[nc++] = c;
    simulate(L, nc, g_cfg);
    g_est = L.end;
    Sched S; S.P = &P; S.clear();
    for (int i = 0; i < nc; i++) {
        bool warm = false;
        for (int k = 0; k < L.n[i]; k++) {
            if (!warm && k + 1 < L.n[i] && (L.w[i][k + 1] & 255) == (mk(T_FIN, 1, 15, 0, 0, 0) & 255)) { S.add(cls[i], (L.w[i][k + 1] & ~0xff0000u) | 0x80000000u); warm = true; }
            S.add(cls[i], L.w[i][k]);
            if ((L.w[i][k] & 7) == T_FIN) warm = true;
        }
    }
}

#define TK0() do {} while (0)
#define TK() do { P.e0 = (P.chains & 1) ? 64 : 0; P.b1 = (P.chains & 2) ? P.lag : 1000; P.nit = (P.chains & 2) ? P.lag + 64 : 64; TK0(); } while (0)
}

extern "C" void kernel_launch(void* const* d_in, const int* in_sizes, int n_in, void* d_out, int out_size) {
    typedef const __nv_bfloat16* BP;
    static EncFn enc = nullptr;
    if (!enc) {
        void* fn = nullptr; cudaDriverEntryPointQueryResult qr;
        cudaGetDriverEntryPoint("cuTensorMapEncodeTiled", &fn, cudaEnableDefault, &qr);
        enc = (EncFn)fn;
        cudaFuncSetAttribute(main_kernel, cudaFuncAttributeMaxDynamicSharedMemorySize, SMEM_BYTES);
    }
    static Params P;
    for (int i = 0; i < 4; i++) {
        const cuuint64_t cols = i < 3 ? 4096 : 512, rows = i < 3 ? 512 : 4096;
        cuuint64_t d2[2] = {cols, rows}, d3[3] = {64, rows, cols / 64}, str[2] = {cols * 2, 128};
        cuuint32_t box[3] = {64, 64, 4}, es[3] = {1, 1, 1};
        enc(&P.tm[i < 3 ? i : 4], CU_TENSOR_MAP_DATA_TYPE_BFLOAT16, 2, d_in[9 + i], d2, str, box, es, CU_TENSOR_MAP_INTERLEAVE_NONE, CU_TENSOR_MAP_SWIZZLE_128B,
                       CU_TENSOR_MAP_L2_PROMOTION_L2_128B, CU_TENSOR_MAP_FLOAT_OOB_FILL_NONE);
        for (int m = 0; m <= i / 3; m++) {
            cuuint32_t box3[3] = {64, 32, m ? 4u : 2u};
            enc(&P.t3[i + m], CU_TENSOR_MAP_DATA_TYPE_BFLOAT16, 3, d_in[9 + i], d3, str, box3, es, CU_TENSOR_MAP_INTERLEAVE_NONE, CU_TENSOR_MAP_SWIZZLE_128B,
                CU_TENSOR_MAP_L2_PROMOTION_L2_128B, CU_TENSOR_MAP_FLOAT_OOB_FILL_NONE);
        }
    }
    {
        cuuint64_t dims[2] = {512, 2048}, str[1] = {1024};
        cuuint32_t box[2] = {8, 256}, es[2] = {1, 1};
        enc(&P.tm[3], CU_TENSOR_MAP_DATA_TYPE_BFLOAT16, 2, d_in[0], dims, str, box, es, CU_TENSOR_MAP_INTERLEAVE_NONE, CU_TENSOR_MAP_SWIZZLE_NONE,
            CU_TENSOR_MAP_L2_PROMOTION_NONE, CU_TENSOR_MAP_FLOAT_OOB_FILL_NONE);
    }
    for (int m = 0; m < 2; m++) {
        void* ga; cudaGetSymbolAddress(&ga, g_A);
        cuuint64_t dims[2] = {512, sizeof(AOps) / 1024}, str[1] = {1024};
        cuuint32_t box[2] = {256, m ? 16u : 8u}, es[2] = {1, 1};
        enc(&P.ta[m], CU_TENSOR_MAP_DATA_TYPE_BFLOAT16, 2, ga, dims, str, box, es, CU_TENSOR_MAP_INTERLEAVE_NONE, CU_TENSOR_MAP_SWIZZLE_NONE,
            CU_TENSOR_MAP_L2_PROMOTION_L2_128B, CU_TENSOR_MAP_FLOAT_OOB_FILL_NONE);
    }
    P.mem0 = (BP)d_in[8]; P.Wo = (BP)d_in[12]; P.Dskip = (BP)d_in[6]; P.out = (__nv_bfloat16*)d_out;
    cudaStream_t s = cudaStreamPerThread;
    P.pa = {(BP)d_in[0], (BP)d_in[1], (BP)d_in[2], (BP)d_in[3], (BP)d_in[4], (BP)d_in[5], (BP)d_in[6], (BP)d_in[9], (BP)d_in[10], (BP)d_in[11], (BP)d_in[12], (BP)d_in[8]};
    if (!g_planned) { plan(P); g_planned = true; }
    TK(); main_kernel<<<2 * NCL, 384, SMEM_BYTES, s>>>(P); TK();
}
```

```cpp
#include <cuda_runtime.h>
#include <cuda_bf16.h>
#include <cuda.h>
#include <stdint.h>
#include <string.h>
#include <math.h>

#define MAXTN 42
namespace {

constexpr int NCL = 66;
constexpr int NLIST = NCL - 32;
__host__ __device__ inline int list_of(int cl) { return cl < 4 ? cl : cl - 32; }
constexpr int MAXT = MAXTN;
#define PFC 1
#define QB1 2
#define QB2 4
#define QB3 6
#define LAGQ 3
#define CPOS 2
#define QPRE 1
#define QPOS 1
#define OPS1N 10
constexpr int OPS1 = OPS1N;
constexpr int MAXSPLIT = 16;
constexpr int PW = 144;

struct AOps { uint4 x[2][16 * 8 * 1024], o[2][16 * 64 * 1024]; };
__device__ AOps g_A;
#define g_xA g_A.x
#define g_o g_A.o
__device__ float2 g_st[2][16 * 2048];
__device__ float2 g_st2[2 * 16 * 128];
__device__ uint4 g_qkv[2][64 * 64 * 768];
__device__ uint4 g_pp[2][16 * MAXSPLIT * 8192];
__device__ uint4 g_acc[7 * 2048];
__device__ unsigned g_gate[32];
__device__ uint32_t g_P[16 * 16 * 32 * PW];
__device__ uint4 g_u[16 * 16 * 512];
__device__ float4 g_carry[2][17 * 16 * 4 * 256];
__device__ unsigned g_cnt[13 * 64];
__device__ uint32_t g_ln0[2048];

enum { C_QKV0 = 0, C_QKV1 = 1  , C_O0 = 2, C_O1 = 3, C_U = 4, C_OP1 = 5, C_CV = 6, C_ST = 7, C_H = 8, C_OP0 = 9   };
__device__ __forceinline__ unsigned* cnt_ptr(int kind, int chunk) { return g_cnt + kind * 64 + chunk; }

enum { T_END = 0, T_QKV = 1, T_OP = 2, T_CV = 3, T_FIN = 4 };
struct ProArgs { const __nv_bfloat16 *x, *lAr, *Ai, *Cr, *Ci, *ldt, *Dk, *Wq, *Wk, *Wv, *Wo, *mem0; };
struct Params {
    CUtensorMap tm[5];
    CUtensorMap t3[5];
    CUtensorMap ta[2];
    ProArgs pa;
    int dopro;
    const __nv_bfloat16* mem0;
    const __nv_bfloat16* Wo;
    const __nv_bfloat16* Dskip;
    __nv_bfloat16* out;
    int rec0;
    int chains;
    int lag;
    int b1, e0, nit;
    int zero, gpit;
    int dostats;
    uint32_t task[NLIST][MAXT];
};

__device__ __forceinline__ uint32_t smem_u32(const void* p) { return (uint32_t)__cvta_generic_to_shared(p); }
__device__ __forceinline__ uint32_t mapa(uint32_t a, uint32_t r) {
    uint32_t o; asm("mapa.shared::cluster.u32 %0,%1,%2;" : "=r"(o) : "r"(a), "r"(r)); return o;
}
__device__ __forceinline__ void mbar_init(uint32_t b, int c) { asm volatile("mbarrier.init.shared::cta.b64 [%0],%1;" ::"r"(b), "r"(c) : "memory"); }
__device__ __forceinline__ void mbar_expect(uint32_t b, int bytes) { asm volatile("mbarrier.arrive.expect_tx.shared::cta.b64 _,[%0],%1;" ::"r"(b), "r"(bytes) : "memory"); }
__device__ __forceinline__ void mbar_arrive(uint32_t b) { asm volatile("mbarrier.arrive.shared::cta.b64 _,[%0];" ::"r"(b) : "memory"); }
__device__ __forceinline__ void mbar_arrive_cluster(uint32_t b) { asm volatile("mbarrier.arrive.shared::cluster.b64 _,[%0];" ::"r"(b) : "memory"); }
__device__ __forceinline__ void mbar_arrive1(uint32_t b) { asm volatile("{.reg .pred p; elect.sync _|p,0xffffffff; @p mbarrier.arrive.shared::cta.b64 _,[%0];}" ::"r"(b) : "memory"); }
__device__ __forceinline__ void mbar_arrive1_cluster(uint32_t b) { asm volatile("{.reg .pred p; elect.sync _|p,0xffffffff; @p mbarrier.arrive.shared::cluster.b64 _,[%0];}" ::"r"(b) : "memory"); }
__device__ __forceinline__ void mbar_wait(uint32_t b, uint32_t ph) {
    asm volatile(
        "{.reg .pred p; .reg .u32 n; mov.u32 n,0;\n"
        "W%=: mbarrier.try_wait.parity.shared::cta.b64 p,[%0],%1;\n"
        "@p bra D%=;\n"
        "add.u32 n,n,1; setp.lt.u32 p,n,2000000; @p bra W%=;\n"
        "trap;\n"
        "D%=: }" ::"r"(b), "r"(ph) : "memory");
}
__device__ __forceinline__ bool mbar_test(uint32_t b, uint32_t ph) {
    uint32_t ok;
    asm volatile("{.reg .pred p; mbarrier.test_wait.parity.shared::cta.b64 p,[%1],%2; selp.u32 %0,1,0,p;}" : "=r"(ok) : "r"(b), "r"(ph) : "memory");
    return ok;
}
__device__ __forceinline__ bool wait_lds128(uint32_t b, uint32_t ph, uint32_t a, uint4& v) {
    uint32_t ok;
    asm volatile("{.reg .pred p; mbarrier.try_wait.parity.shared::cta.b64 p,[%5],%6,20000; ld.shared.v4.u32 {%0,%1,%2,%3},[%7]; selp.u32 %4,1,0,p;}"
                 : "=r"(v.x), "=r"(v.y), "=r"(v.z), "=r"(v.w), "=r"(ok) : "r"(b), "r"(ph), "r"(a) : "memory");
    return ok;
}
__device__ __forceinline__ bool wait_lds64(uint32_t b, uint32_t ph, uint32_t a, uint2& v) {
    uint32_t ok;
    asm volatile("{.reg .pred p; mbarrier.try_wait.parity.shared::cta.b64 p,[%3],%4,20000; ld.shared.v2.u32 {%0,%1},[%5]; selp.u32 %2,1,0,p;}"
                 : "=r"(v.x), "=r"(v.y), "=r"(ok) : "r"(b), "r"(ph), "r"(a) : "memory");
    return ok;
}
template <int PH> __device__ __forceinline__ void mbar_wait_c(uint32_t b) {
    asm volatile(
        "{.reg .pred p; .reg .u32 n; mov.u32 n,%2;\n"
        "W%=: mbarrier.try_wait.parity.shared::cta.b64 p,[%0],%1;\n"
        "@p bra D%=;\n"
        "add.u32 n,n,1; setp.lt.u32 p,n,2000000; @p bra W%=;\n"
        "trap;\n"
        "D%=: }" ::"r"(b), "n"(PH), "n"(PH) : "memory");
}
__device__ __forceinline__ void bar_sync(int id, int n) { asm volatile("bar.sync %0,%1;" ::"r"(id), "r"(n) : "memory"); }
__device__ __forceinline__ void bar_arrive(int id, int n) { asm volatile("bar.arrive %0,%1;" ::"r"(id), "r"(n) : "memory"); }
__device__ __forceinline__ void cluster_sync() { asm volatile("barrier.cluster.arrive.relaxed.aligned; barrier.cluster.wait.aligned;" ::: "memory"); }
__device__ __forceinline__ void fence_async() { asm volatile("fence.proxy.async;" ::: "memory"); }
__device__ __forceinline__ void fence_async_smem() { asm volatile("fence.proxy.async.shared::cta;" ::: "memory"); }
#define EFR 1
#define EFW 1
constexpr uint64_t POL_N = 0x1000000000000000ull, POL_F = 0x12F0000000000000ull;
constexpr uint64_t POL_LAST = EFR ? POL_F : POL_N  , POL_LATE = EFW ? POL_F : POL_N  , POL_SOON = EFW > 1 ? POL_F : POL_N;
__device__ __forceinline__ void bulk_g2s(uint32_t dst, const void* src, int bytes, uint32_t bar, uint64_t pol) {
    asm volatile("cp.async.bulk.shared::cluster.global.mbarrier::complete_tx::bytes.L2::cache_hint [%0],[%1],%2,[%3],%4;" ::"r"(dst), "l"(src), "r"(bytes), "r"(bar), "l"(pol) : "memory");
}
__device__ __forceinline__ void bulk_g2s_mc(uint32_t dst, const void* src, int bytes, uint32_t bar, uint64_t pol) {
    asm volatile("cp.async.bulk.shared::cluster.global.mbarrier::complete_tx::bytes.multicast::cluster.L2::cache_hint [%0],[%1],%2,[%3],%4,%5;" ::"r"(dst), "l"(src), "r"(bytes), "r"(bar), "h"((uint16_t)3), "l"(pol) : "memory");
}
__device__ __forceinline__ void bulk_s2s(uint32_t dst, uint32_t src, int bytes, uint32_t bar) {
    asm volatile("cp.async.bulk.shared::cluster.shared::cta.mbarrier::complete_tx::bytes [%0],[%1],%2,[%3];" ::"r"(dst), "r"(src), "r"(bytes), "r"(bar) : "memory");
}
__device__ __forceinline__ bool elect() {
    uint32_t r; asm volatile("{.reg .pred p; elect.sync _|p,0xffffffff; selp.u32 %0,1,0,p;}" : "=r"(r)); return r;
}
__device__ __forceinline__ void stg128(uint4* p, uint4 v, uint64_t pol) {
    asm volatile("st.global.L2::cache_hint.v4.u32 [%0],{%1,%2,%3,%4},%5;" ::"l"(p), "r"(v.x), "r"(v.y), "r"(v.z), "r"(v.w), "l"(pol));
}
__device__ __forceinline__ void stg32(uint32_t* p, uint32_t v, uint64_t pol) { asm volatile("st.global.L2::cache_hint.u32 [%0],%1,%2;" ::"l"(p), "r"(v), "l"(pol)); }
__device__ __forceinline__ uint4 ldcg128_last(const uint4* p) {
    uint4 v; asm volatile("ld.global.cg.L2::cache_hint.v4.u32 {%0,%1,%2,%3},[%4],%5;" : "=r"(v.x), "=r"(v.y), "=r"(v.z), "=r"(v.w) : "l"(p), "l"(POL_LAST) : "memory"); return v;
}
__device__ __forceinline__ void tma2d(uint32_t dst, const CUtensorMap* tm, int x, int y, uint32_t bar) {
    asm volatile("cp.async.bulk.tensor.2d.shared::cluster.global.mbarrier::complete_tx::bytes [%0],[%1,{%2,%3}],[%4];" ::"r"(dst), "l"(tm), "r"(x), "r"(y), "r"(bar) : "memory");
}
__device__ __forceinline__ void tma3d_mc(uint32_t dst, const CUtensorMap* tm, int y, int z, uint32_t bar, uint16_t mask) {
    asm volatile("{.reg .pred p; elect.sync _|p,0xffffffff;\n"
                 "@p cp.async.bulk.tensor.3d.shared::cluster.global.mbarrier::complete_tx::bytes.multicast::cluster [%0],[%1,{0,%2,%3}],[%4],%5;}"
                 ::"r"(dst), "l"(tm), "r"(y), "r"(z), "r"(bar), "h"(mask) : "memory");
}
__device__ __forceinline__ void tma2d_mc(uint32_t dst, const CUtensorMap* tm, int x, int y, uint32_t bar, uint16_t mask, uint64_t pol) {
    asm volatile("{.reg .pred p; elect.sync _|p,0xffffffff;\n"
                 "@p cp.async.bulk.tensor.2d.shared::cluster.global.mbarrier::complete_tx::bytes.multicast::cluster.L2::cache_hint [%0],[%1,{%2,%3}],[%4],%5,%6;}"
                 ::"r"(dst), "l"(tm), "r"(x), "r"(y), "r"(bar), "h"(mask), "l"(pol) : "memory");
}
__device__ __forceinline__ void bulk_g2s1(uint32_t dst, const void* src, int bytes, uint32_t bar, uint64_t pol) {
    asm volatile("{.reg .pred p; elect.sync _|p,0xffffffff;\n"
                 "@p cp.async.bulk.shared::cluster.global.mbarrier::complete_tx::bytes.L2::cache_hint [%0],[%1],%2,[%3],%4;}" ::"r"(dst), "l"(src), "r"(bytes), "r"(bar), "l"(pol) : "memory");
}
__device__ __forceinline__ void mbar_expect1(uint32_t b, int bytes) {
    asm volatile("{.reg .pred p; elect.sync _|p,0xffffffff; @p mbarrier.arrive.expect_tx.shared::cta.b64 _,[%0],%1;}" ::"r"(b), "r"(bytes) : "memory");
}
__device__ __forceinline__ void st_async4(uint32_t a, uint32_t x, uint32_t y, uint32_t z, uint32_t w, uint32_t mb) {
    asm volatile("st.async.shared::cluster.mbarrier::complete_tx::bytes.v4.b32 [%0],{%1,%2,%3,%4},[%5];" ::"r"(a), "r"(x), "r"(y), "r"(z), "r"(w), "r"(mb) : "memory");
}
__device__ __forceinline__ void st_async2(uint32_t a, uint32_t x, uint32_t y, uint32_t mb) {
    asm volatile("st.async.shared::cluster.mbarrier::complete_tx::bytes.v2.b32 [%0],{%1,%2},[%3];" ::"r"(a), "r"(x), "r"(y), "r"(mb) : "memory");
}
#define LDSQ "ld.shared"
__device__ __forceinline__ uint4 lds128(uint32_t a) { uint4 v; asm volatile(LDSQ ".v4.u32 {%0,%1,%2,%3},[%4];" : "=r"(v.x), "=r"(v.y), "=r"(v.z), "=r"(v.w) : "r"(a) : "memory"); return v; }
__device__ __forceinline__ uint2 lds64(uint32_t a) { uint2 v; asm volatile(LDSQ ".v2.u32 {%0,%1},[%2];" : "=r"(v.x), "=r"(v.y) : "r"(a) : "memory"); return v; }
__device__ __forceinline__ uint32_t lds32(uint32_t a) { uint32_t v; asm volatile(LDSQ ".u32 %0,[%1];" : "=r"(v) : "r"(a) : "memory"); return v; }
__device__ __forceinline__ void sts128(uint32_t a, uint32_t x, uint32_t y, uint32_t z, uint32_t w) { asm volatile("st.shared.v4.u32 [%0],{%1,%2,%3,%4};" ::"r"(a), "r"(x), "r"(y), "r"(z), "r"(w) : "memory"); }
__device__ __forceinline__ void sts64(uint32_t a, uint32_t x, uint32_t y) { asm volatile("st.shared.v2.u32 [%0],{%1,%2};" ::"r"(a), "r"(x), "r"(y) : "memory"); }
__device__ __forceinline__ void sts32(uint32_t a, uint32_t x) { asm volatile("st.shared.u32 [%0],%1;" ::"r"(a), "r"(x) : "memory"); }
__device__ __forceinline__ uint4 ldsm4(uint32_t a) { uint4 v; asm volatile("ldmatrix.sync.aligned.m8n8.x4.shared.b16 {%0,%1,%2,%3},[%4];" : "=r"(v.x), "=r"(v.y), "=r"(v.z), "=r"(v.w) : "r"(a) : "memory"); return v; }
__device__ __forceinline__ uint4 ldsm4t(uint32_t a) { uint4 v; asm volatile("ldmatrix.sync.aligned.m8n8.x4.trans.shared.b16 {%0,%1,%2,%3},[%4];" : "=r"(v.x), "=r"(v.y), "=r"(v.z), "=r"(v.w) : "r"(a) : "memory"); return v; }
__device__ __forceinline__ uint32_t movm(uint32_t a) { uint32_t d; asm volatile("movmatrix.sync.aligned.m8n8.trans.b16 %0,%1;" : "=r"(d) : "r"(a)); return d; }
__device__ __forceinline__ uint32_t pack2(float lo, float hi) { uint32_t d; asm("cvt.rn.bf16x2.f32 %0,%1,%2;" : "=r"(d) : "f"(hi), "f"(lo)); return d; }
__device__ __forceinline__ uint32_t hadd2(uint32_t a, uint32_t b) { uint32_t d; asm("add.rn.bf16x2 %0,%1,%2;" : "=r"(d) : "r"(a), "r"(b)); return d; }
__device__ __forceinline__ float blo(uint32_t v) { return __uint_as_float(v << 16); }
__device__ __forceinline__ float bhi(uint32_t v) { return __uint_as_float(v & 0xffff0000u); }
__device__ __forceinline__ float rbf(float x) { return __uint_as_float(pack2(0.f, x)); }
__device__ __forceinline__ float ex2(float x) { float y; asm("ex2.approx.ftz.f32 %0,%1;" : "=f"(y) : "f"(x)); return y; }
__device__ __forceinline__ float rcp(float x) { float y; asm("rcp.approx.ftz.f32 %0,%1;" : "=f"(y) : "f"(x)); return y; }
__device__ __forceinline__ void mma16(float* c, uint32_t a0, uint32_t a1, uint32_t a2, uint32_t a3, uint32_t b0, uint32_t b1) {
    asm volatile("mma.sync.aligned.m16n8k16.row.col.f32.bf16.bf16.f32 {%0,%1,%2,%3},{%4,%5,%6,%7},{%8,%9},{%0,%1,%2,%3};"
                 : "+f"(c[0]), "+f"(c[1]), "+f"(c[2]), "+f"(c[3]) : "r"(a0), "r"(a1), "r"(a2), "r"(a3), "r"(b0), "r"(b1));
}
__device__ __forceinline__ void mma8(float* c, uint32_t a0, uint32_t a1, uint32_t b0) {
    asm volatile("mma.sync.aligned.m16n8k8.row.col.f32.bf16.bf16.f32 {%0,%1,%2,%3},{%4,%5},{%6},{%0,%1,%2,%3};"
                 : "+f"(c[0]), "+f"(c[1]), "+f"(c[2]), "+f"(c[3]) : "r"(a0), "r"(a1), "r"(b0));
}
__device__ __forceinline__ uint4 ld_rlx128(const uint4* p) {
    uint4 v;
    asm volatile("{.reg .b128 t; ld.relaxed.gpu.global.b128 t,[%4]; mov.b128 {%0,%1,%2,%3},t;}" : "=r"(v.x), "=r"(v.y), "=r"(v.z), "=r"(v.w) : "l"(p) : "memory");
    return v;
}
__device__ __forceinline__ void st_rlx128(uint4* p, uint32_t x, uint32_t y, uint32_t z, uint32_t w) {
    asm volatile("{.reg .b128 t; mov.b128 t,{%1,%2,%3,%4}; st.relaxed.gpu.global.b128 [%0],t;}" ::"l"(p), "r"(x), "r"(y), "r"(z), "r"(w) : "memory");
}
__device__ __forceinline__ uint4 ldcg128(const uint4* p) { uint4 v; asm volatile("ld.global.cg.v4.u32 {%0,%1,%2,%3},[%4];" : "=r"(v.x), "=r"(v.y), "=r"(v.z), "=r"(v.w) : "l"(p) : "memory"); return v; }
__device__ __forceinline__ void red_release(unsigned* p, unsigned v) {
    asm volatile("fence.proxy.async; red.relaxed.gpu.global.add.u32 [%0],%1;" ::"l"(p), "r"(v) : "memory");
}
__device__ __forceinline__ void wait_cnt(const unsigned* p, unsigned target) {
    unsigned v; int n = 0;
    while (true) {
        asm volatile("ld.acquire.gpu.global.u32 %0,[%1];" : "=r"(v) : "l"(p) : "memory");
        if (v >= target) break;
        if (++n > 3000000) __trap();
        __nanosleep(40);
    }
}
__device__ __forceinline__ void wait_cnt_warp(const unsigned* p, unsigned target) {
    unsigned v; int n = 0;
    while (true) {
        asm volatile("ld.acquire.gpu.global.u32 %0,[%1];" : "=r"(v) : "l"(p) : "memory");
        if (__all_sync(0xffffffffu, v >= target)) break;
        if (++n > 3000000) __trap();
    }
}
__device__ __forceinline__ uint64_t mkdesc(uint32_t addr, uint32_t lbo, uint32_t sbo, uint32_t sw) {
    return (uint64_t)((addr & 0x3FFFF) >> 4) | ((uint64_t)(lbo >> 4) << 16) | ((uint64_t)(sbo >> 4) << 32) | ((uint64_t)sw << 62);
}
__device__ __forceinline__ void wg_fence() { asm volatile("wgmma.fence.sync.aligned;" ::: "memory"); }
__device__ __forceinline__ void wg_commit() { asm volatile("wgmma.commit_group.sync.aligned;" ::: "memory"); }
template <int N> __device__ __forceinline__ void wg_wait() { asm volatile("wgmma.wait_group.sync.aligned %0;" ::"n"(N) : "memory"); }
#define R8(c, o) "+f"(c[o]), "+f"(c[o + 1]), "+f"(c[o + 2]), "+f"(c[o + 3]), "+f"(c[o + 4]), "+f"(c[o + 5]), "+f"(c[o + 6]), "+f"(c[o + 7])
#define R32(c, o) R8(c, o), R8(c, o + 8), R8(c, o + 16), R8(c, o + 24)
#define S32A "%0,%1,%2,%3,%4,%5,%6,%7,%8,%9,%10,%11,%12,%13,%14,%15,%16,%17,%18,%19,%20,%21,%22,%23,%24,%25,%26,%27,%28,%29,%30,%31"
#define S32B ",%32,%33,%34,%35,%36,%37,%38,%39,%40,%41,%42,%43,%44,%45,%46,%47,%48,%49,%50,%51,%52,%53,%54,%55,%56,%57,%58,%59,%60,%61,%62,%63"
#define S32C ",%64,%65,%66,%67,%68,%69,%70,%71,%72,%73,%74,%75,%76,%77,%78,%79,%80,%81,%82,%83,%84,%85,%86,%87,%88,%89,%90,%91,%92,%93,%94,%95"
#define S32D ",%96,%97,%98,%99,%100,%101,%102,%103,%104,%105,%106,%107,%108,%109,%110,%111,%112,%113,%114,%115,%116,%117,%118,%119,%120,%121,%122,%123,%124,%125,%126,%127"
#define W8(c, o) "=f"(c[o]), "=f"(c[o + 1]), "=f"(c[o + 2]), "=f"(c[o + 3]), "=f"(c[o + 4]), "=f"(c[o + 5]), "=f"(c[o + 6]), "=f"(c[o + 7])
#define W32(c, o) W8(c, o), W8(c, o + 8), W8(c, o + 16), W8(c, o + 24)
template <bool ACC> __device__ __forceinline__ void wgmma256(float* c, uint64_t da, uint64_t db) {
    if (ACC) asm volatile("wgmma.mma_async.sync.aligned.m64n256k16.f32.bf16.bf16 {" S32A S32B S32C S32D "},%128,%129,1,1,1,0,1;"
                          : R32(c, 0), R32(c, 32), R32(c, 64), R32(c, 96) : "l"(da), "l"(db));
    else asm volatile("wgmma.mma_async.sync.aligned.m64n256k16.f32.bf16.bf16 {" S32A S32B S32C S32D "},%128,%129,0,1,1,0,1;"
                      : W32(c, 0), W32(c, 32), W32(c, 64), W32(c, 96) : "l"(da), "l"(db));
}
template <bool ACC> __device__ __forceinline__ void wgmma128r(float* c, const uint4& a, uint64_t db) {
    if (ACC) asm volatile("wgmma.mma_async.sync.aligned.m64n128k16.f32.bf16.bf16 {" S32A S32B "},{%64,%65,%66,%67},%68,1,1,1,1;"
                          : R32(c, 0), R32(c, 32) : "r"(a.x), "r"(a.y), "r"(a.z), "r"(a.w), "l"(db));
    else asm volatile("wgmma.mma_async.sync.aligned.m64n128k16.f32.bf16.bf16 {" S32A S32B "},{%64,%65,%66,%67},%68,0,1,1,1;"
                      : W32(c, 0), W32(c, 32) : "r"(a.x), "r"(a.y), "r"(a.z), "r"(a.w), "l"(db));
}
template <int N> __device__ __forceinline__ void reg_inc() { asm volatile("setmaxnreg.inc.sync.aligned.u32 %0;" ::"n"(N)); }
template <int N> __device__ __forceinline__ void reg_dec() { asm volatile("setmaxnreg.dec.sync.aligned.u32 %0;" ::"n"(N)); }

#define PROF(cond, idx) do {} while (0)
#define CPROF(k) do {} while (0)

constexpr int S_GATE = 232440, S_TAG = 232444, S_XBAR = 232432;
constexpr float SC_LOG2E = 0.08838834764831845f * 1.4426950408889634f;

__device__ __forceinline__ float2 ln_finish(float mean, float var) {
    float sd; asm("sqrt.approx.f32 %0,%1;" : "=f"(sd) : "f"(rbf(rbf(var) + 1e-5f)));
    sd = rbf(sd);
    return make_float2(rbf(mean), sd);
}

__device__ __forceinline__ float4 row_stats(const uint4* src, int stride) {
    const int g = (threadIdx.x & 31) >> 2;
    uint4 v[16];
#pragma unroll
    for (int i = 0; i < 16; i++) v[i] = ldcg128(src + i * stride);
    float a[4] = {0, 0, 0, 0}, q0[4] = {0, 0, 0, 0}, q1[4] = {0, 0, 0, 0}, q2[4] = {0, 0, 0, 0}, q3[4] = {0, 0, 0, 0};
#pragma unroll
    for (int i = 0; i < 16; i++) {
        mma16(a, v[i].x, v[i].y, v[i].z, v[i].w, 0x3f803f80u, 0x3f803f80u);
        mma8(q0, v[i].x, v[i].y, v[i].x); mma8(q1, v[i].x, v[i].y, v[i].y);
        mma8(q2, v[i].z, v[i].w, v[i].z); mma8(q3, v[i].z, v[i].w, v[i].w);
    }
    return make_float4(a[0], (g & 1) ? q0[1] + q2[1] : q0[0] + q2[0], a[2], (g & 1) ? q1[3] + q3[3] : q1[2] + q3[2]);
}
__device__ __forceinline__ void x1_stats(int i) {
    const int lane = threadIdx.x & 31, g = lane >> 2, c = lane & 3;
    const float4 r = row_stats(g_xA[0] + i * 512 + lane, 32);
    float2* dst = g_st[0] + (i >> 4) * 2048 + ((i < 32 ? 4 : 0) + (i & 1)) * 128 + ((i >> 1) & 7) * 16 + g;
    if (c == (g >> 1)) { dst[0] = make_float2(r.x, r.y); dst[8] = make_float2(r.z, r.w); g_ln0[i * 8 + g] = 0; }
    __syncwarp();
    if (lane == 0) red_release(cnt_ptr(C_ST, i >> 4), 1);
}
__global__ void stats_kernel() { x1_stats(blockIdx.x * 4 + (threadIdx.x >> 5)); }

#define NT 9
#define RH 104
#define RW0 200
#define NPD 9
#define NTO 12
#define DP1 9
#define GPW 0
#define GPJ 0
#define PACE 2
#define EARLY 4
#define G2I 4
#define VE 4
#define VF 8
constexpr int R_WV = 0, R_WO = 65536, R_T = 131072, R_M = R_T + 20480, R_LOC = R_M + 4096, R_REM = R_LOC + 6144, R_O = R_REM + 12288, R_SX = R_O + 2048,
              R_IL = R_SX + 5120, XS = R_IL + 128 - R_T, R_BAR = 231936, R_Z = R_BAR + 128  , R_STQ = 0, R_STK = 65536, R_STV = 131072;
static_assert(R_T + 2 * XS <= R_BAR && R_BAR + 256 <= S_XBAR, "smem map");
enum { RB_INIT = 0, RB_V = 4  , RB_QK = 8  , RB_T = 12  , RB_N = 16 };
enum { NB_MF = 1  , NB_LOC = 3  , NB_PAIR = 5  , NB_O = 9  , NB_XG = 11  , NB_W = 13 };
__device__ __forceinline__ uint32_t clk32() { return (uint32_t)clock64(); }

__device__ __forceinline__ char* acc_base() { return (char*)(((size_t)g_acc + 131071) & ~(size_t)131071); }
__device__ __forceinline__ uint32_t acc_slice(uint32_t s6) { return (s6 & 1) * 256 + (s6 >> 1) * 1024; }
__device__ __forceinline__ uint32_t acc_main(uint32_t rank, uint32_t tid) { return acc_slice(rank * 32 + (tid >> 3)) + (tid & 7) * 16; }
__device__ __forceinline__ uint32_t acc_extra(uint32_t rank, uint32_t tid) { return 65536 + acc_slice(((tid >> 5) & 1) + rank * 4 + (tid >> 6) * 8) + (tid & 31) * 4; }
__device__ __forceinline__ uint32_t acc_slot(uint32_t s) { return (s & 1) * 128 + (s & 2) * 256; }
__device__ __forceinline__ void acc_init(const __nv_bfloat16* mem0, int i) {
    const uint32_t tid = i & 255, rank = (i >> 8) & 1, slot = (i >> 9) & 3, X = i >> 11;
    uint32_t v[5] = {0, 0, 0, 0, 0};
    if (slot == 3) {
        const uint16_t* m = (const uint16_t*)mem0 + (tid & 3) * 1024 + rank * 256 + (tid >> 5) * 32 + ((tid >> 2) & 7);
#pragma unroll
        for (int k = 0; k < 4; k++) v[k] = __ldg(m + k * 8) | ((uint32_t)__ldg(m + k * 8 + 512) << 16);
        v[4] = (v[3] >> 16) | 0x42000000u; v[3] = (v[3] & 0xffff) | 0x42000000u;
    }
    *(uint4*)(acc_base() + X * 32768 + acc_slot(slot) + acc_main(rank, tid)) = make_uint4(v[0], v[1], v[2], v[3]);
    *(uint32_t*)(acc_base() + X * 1024 + acc_slot(slot) + acc_extra(rank, tid)) = v[4];
}
__global__ void acc_init_kernel(const __nv_bfloat16* mem0) { acc_init(mem0, blockIdx.x * 256 + threadIdx.x); }

struct RecW { uint32_t am, ae, ah, dp, lp, lpw, vo, sb, bar, zero, ts, tn; };
__device__ __forceinline__ uint32_t vadd(uint32_t a, uint32_t b) { uint32_t d; asm volatile("add.u32 %0,%1,%2;" : "=r"(d) : "r"(a), "r"(b)); return d; }
__device__ __forceinline__ uint32_t vshr(uint32_t a, int n) { uint32_t d; asm volatile("shr.u32 %0,%1,%2;" : "=r"(d) : "r"(a), "r"(n)); return d; }
__device__ __forceinline__ uint64_t gptr(uint32_t lo, uint32_t hi) { uint64_t d; asm("mov.b64 %0,{%1,%2};" : "=l"(d) : "r"(lo), "r"(hi)); return d; }
__device__ __forceinline__ void sfence(uint32_t zero) { asm volatile("{.reg .pred p; setp.ne.u32 p,%0,0; @p exit;}" ::"r"(zero) : "memory"); }
#define SF sfence(k.zero)
#define TS(i) do {} while (0)
#define TSN(i) do {} while (0)
#define TSET(it, slot) do {} while (0)
struct Gat { uint32_t x, y, z, w, e; };
template <int X>
__device__ __forceinline__ void gat_issue(Gat& g, const RecW& k, int s, uint32_t dep) {
    const uint32_t o = acc_slot(s + 3) + dep;
    asm volatile("{.reg .b128 t; ld.relaxed.gpu.global.b128 t,[%5+%7]; mov.b128 {%0,%1,%2,%3},t; ld.relaxed.gpu.global.u32 %4,[%6+%8];}"
                 : "=r"(g.x), "=r"(g.y), "=r"(g.z), "=r"(g.w), "=r"(g.e) : "l"(gptr(k.am + o, k.ah)), "l"(gptr(k.ae + o, k.ah)), "n"(X * 32768), "n"(X * 1024) : "memory");
}
template <int X>
__device__ __forceinline__ bool gat_store(const Gat& g, const RecW& k) {
    uint32_t c;
    asm volatile("prmt.b32 %0,%1,%2,0x7632;" : "=r"(c) : "r"(g.w), "r"(g.e));
    SF;
    asm volatile("{.reg .b32 t; prmt.b32 t,%4,%6,0x5410; stmatrix.sync.aligned.m8n8.x4.trans.shared.b16 [%0+%5],{%1,%2,%3,t};}" ::"r"(k.lpw), "r"(g.x), "r"(g.y), "r"(g.z), "r"(g.w), "n"(R_M + X * XS), "r"(g.e) : "memory");
    return __all_sync(0xffffffffu, c == 0x42004200u);
}
template <int X>
__device__ __forceinline__ void gat_finish(bool ok, const RecW& k, int s) {
    if (!ok) {
        int n = s;
        while (true) {
            Gat g;
            gat_issue<X>(g, k, n, 0);
            if (gat_store<X>(g, k)) break;
            n += 4;
            if (n > 8000000) __trap();
        }
    }
}
__device__ __forceinline__ uint4 lds128o(uint32_t a, int o) { uint4 v; asm volatile("{.reg .b32 t; add.u32 t,%4,%5; ld.shared.v4.u32 {%0,%1,%2,%3},[t];}" : "=r"(v.x), "=r"(v.y), "=r"(v.z), "=r"(v.w) : "r"(a), "r"(o) : "memory"); return v; }
__device__ __forceinline__ uint4 ldsm4o(uint32_t a, int o) { uint4 v; asm volatile("{.reg .b32 t; add.u32 t,%4,%5; ldmatrix.sync.aligned.m8n8.x4.shared.b16 {%0,%1,%2,%3},[t];}" : "=r"(v.x), "=r"(v.y), "=r"(v.z), "=r"(v.w) : "r"(a), "r"(o) : "memory"); return v; }
__device__ __forceinline__ uint4 ldsm4to(uint32_t a, int o) { uint4 v; asm volatile("{.reg .b32 t; add.u32 t,%4,%5; ldmatrix.sync.aligned.m8n8.x4.trans.shared.b16 {%0,%1,%2,%3},[t];}" : "=r"(v.x), "=r"(v.y), "=r"(v.z), "=r"(v.w) : "r"(a), "r"(o) : "memory"); return v; }
__device__ __forceinline__ uint2 lds64o(uint32_t a, int o) { uint2 v; asm volatile("{.reg .b32 t; add.u32 t,%2,%3; ld.shared.v2.u32 {%0,%1},[t];}" : "=r"(v.x), "=r"(v.y) : "r"(a), "r"(o) : "memory"); return v; }
__device__ __forceinline__ void sts128o(uint32_t a, int o, uint32_t x, uint32_t y, uint32_t z, uint32_t w) { asm volatile("{.reg .b32 t; add.u32 t,%0,%5; st.shared.v4.u32 [t],{%1,%2,%3,%4};}" ::"r"(a), "r"(x), "r"(y), "r"(z), "r"(w), "r"(o) : "memory"); }
__device__ __forceinline__ void sts64o(uint32_t a, int o, uint32_t x, uint32_t y) { asm volatile("{.reg .b32 t; add.u32 t,%0,%3; st.shared.v2.u32 [t],{%1,%2};}" ::"r"(a), "r"(x), "r"(y), "r"(o) : "memory"); }
__device__ __forceinline__ uint32_t vxor(uint32_t a, uint32_t b) { uint32_t d; asm volatile("xor.b32 %0,%1,%2;" : "=r"(d) : "r"(a), "r"(b)); return d; }
#define WLD(base, i) wt[i] = lds128o(k.lpw, (base) + (i) * 4096)
template <int PASS, int X, int NP>
__device__ __forceinline__ void rec_qkv(const RecW& k, int s, const uint32_t (*wq)[4], const uint32_t (*wk)[4], uint4* wt, Gat& g2, int s2) {
    constexpr bool BWD = PASS == 2;
    float aq[4] = {0, 0, 0, 0}, ak[4] = {0, 0, 0, 0}, av[4] = {0, 0, 0, 0};
    constexpr int ma = R_M + X * XS;
    if (BWD) { TS(1); gat_finish<1>(gat_store<1>(g2, k), k, s); }
    bar_sync(NB_MF + X, 256);
    uint4 mf = ldsm4o(k.lp, ma + (BWD ? 7 : 0) * 512);
    if (BWD) TS(2); else { TS(0); TSN(13); }
#pragma unroll
    for (int ii = 0; ii < 8; ii++) {
        const int i = BWD ? 7 - ii : ii;
        const uint4 m = mf;
        if (ii < 7) mf = ldsm4o(k.lp, ma + (BWD ? i - 1 : i + 1) * 512);
        if (PASS == 1 && ii == G2I) gat_issue<1>(g2, k, s2, 0);
        SF;
#pragma unroll
        for (int hh = 0; hh < 2; hh++) {
            const int h = BWD ? 1 - hh : hh, ks = 2 * i + h;
            const uint32_t b0 = h ? m.z : m.x, b1 = h ? m.w : m.y;
            mma16(aq, wq[ks][0], wq[ks][1], wq[ks][2], wq[ks][3], b0, b1);
            mma16(ak, wk[ks][0], wk[ks][1], wk[ks][2], wk[ks][3], b0, b1);
            SF;
            mma16(av, wt[ks].x, wt[ks].y, wt[ks].z, wt[ks].w, b0, b1);
            SF;
            if (!BWD && ks + NP < 16) WLD(R_WV, ks + NP < 16 ? ks + NP : 0);
            if (BWD && ks >= NT) WLD(R_WV, ks >= NT ? ks - NT : 0);
            SF;
        }
    }
    const uint32_t ra = vadd(k.lpw, k.dp + R_REM + X * XS + (s & 1) * 6144), va = ((vshr(k.lp, 7) & 1) * 48 ^ k.lp ^ (k.vo & 64)) + (k.vo & ~64u);
    const uint32_t x0 = movm(pack2(aq[0], aq[1])), x1 = movm(pack2(aq[2], aq[3])), x2 = movm(pack2(ak[0], ak[1])), x3 = movm(pack2(ak[2], ak[3]));
    SF;
    asm volatile("stmatrix.sync.aligned.m8n8.x2.shared.b16 [%0+%3],{%1,%2};" ::"r"(va), "r"(pack2(av[0], av[1])), "r"(pack2(av[2], av[3])), "n"(R_LOC + X * XS) : "memory");
    SF;
    st_async4(ra, x0, x1, x2, x3, k.bar + X * 16);
    asm volatile("st.shared.v4.u32 [%0+%5],{%1,%2,%3,%4};" ::"r"(k.lpw), "r"(x0), "r"(x1), "r"(x2), "r"(x3), "n"(R_LOC + X * XS) : "memory");
    bar_arrive(NB_LOC + X, 320);
    SF;
    TS(BWD ? 4 : 3);
}
template <bool BWD, int X>
__device__ __forceinline__ void rec_out(const RecW& k, int s, uint4* wt, Gat& g, int s1) {
    if (BWD) { WLD(R_WO, 17 - NTO); WLD(R_WO, 16 - NTO); }
    TS(BWD ? 8 : 5);
    bar_sync(NB_O + X, 320);
    float r0[4] = {0, 0, 0, 0}, r1[4] = {0, 0, 0, 0};
    constexpr int oa = R_O + X * XS;
    uint4 bn = lds128o(k.lp, oa + (BWD ? 3 : 0) * 512);
    TS(BWD ? 9 : 6);
    uint2 il;
    uint64_t pm, pe;
#pragma unroll
    for (int ii = 0; ii < 4; ii++) {
        const int i = BWD ? 3 - ii : ii;
        const uint4 b = bn;
        if (ii < 3) bn = lds128o(k.lp, oa + (BWD ? i - 1 : i + 1) * 512);
        else { asm volatile("ld.shared.v2.u32 {%0,%1},[%2+%3];" : "=r"(il.x), "=r"(il.y) : "r"((vshr(k.ae, 2) & 3) * 8 + k.sb), "n"(R_IL + X * XS) : "memory"); pm = gptr(vadd(k.am, acc_slot(s)), k.ah); pe = gptr(vadd(k.ae, acc_slot(s)), k.ah); }
        SF;
        if (BWD && EARLY == ii + 1) { gat_issue<0>(g, k, s1 + 1, 0); SF; }
#pragma unroll
        for (int nn = 0; nn < 4; nn++) {
            const int n = BWD ? 3 - nn : nn, f = 4 * i + n, nx = BWD ? f - NTO + 2 : f + NTO - 2;
            mma16((n & 1) ? r1 : r0, wt[f].x, wt[f].y, wt[f].z, wt[f].w, n >> 1 ? b.z : b.x, n >> 1 ? b.w : b.y);
            SF;
            if (ii * 4 + nn >= 2 && nx >= 0 && nx < 16) WLD(R_WO, nx & 15);
            SF;
        }
    }
    const float i0 = __uint_as_float(il.x), i1 = __uint_as_float(il.y);
    asm volatile("red.relaxed.gpu.global.add.noftz.v4.bf16x2 [%0+%5],{%1,%2,%3,%4};" ::"l"(pm),
                 "r"(pack2(r0[0] * i0, r0[1] * i1)), "r"(pack2(r0[2] * i0, r0[3] * i1)), "r"(pack2(r1[0] * i0, r1[1] * i1)), "r"(pack2(r1[2] * i0, 1.f)), "n"(X * 32768) : "memory");
    asm volatile("red.relaxed.gpu.global.add.noftz.bf16x2 [%0+%2],%1;" ::"l"(pe), "r"(pack2(r1[3] * i1, 1.f)), "n"(X * 1024) : "memory");
    bar_arrive(NB_XG + X, 320);
    SF;
    TS(BWD ? 10 : 7);
}
__device__ __forceinline__ uint32_t pause(uint32_t v, int n) {
#pragma unroll
    for (int i = 0; i < n; i++) asm volatile("shfl.sync.bfly.b32 %0,%0,0,0x1f,0xffffffff;" : "+r"(v));
    return v;
}
template <bool DUAL, int X>
__device__ __forceinline__ void rec_step(const RecW& k, int s, int s2, const uint32_t (*wq)[4], const uint32_t (*wk)[4], uint4* wt) {
    constexpr int NP = NPD;
    uint4 wo[16];
    Gat g;
    rec_qkv<DUAL ? 1 : 0, X, NP>(k, s, wq, wk, wt, g, s2);
    if (DUAL) rec_qkv<2, 1, NP>(k, s2, wq, wk, wt, g, s2);
    uint32_t wa = k.lpw;
#pragma unroll
    for (int i = 0; i < NTO; i++) {
        wo[i] = lds128o(wa, R_WO + i * 4096);
        if (i % PACE == PACE - 1) wa = k.lpw + (wo[i].x & k.zero);
        SF;
    }
    rec_out<false, X>(k, s, wo, g, s);
    if (DUAL) { rec_out<true, 1>(k, s2, wo, g, s); if (!EARLY) gat_issue<0>(g, k, s + 1, 0); SF; }
#pragma unroll
    for (int i = 0; i < NP; i++) { WLD(R_WV, i); SF; }
    if (!DUAL) gat_issue<X>(g, k, s + 1, pause(wt[NP - 1].x & k.zero, DP1));
    TS(12);
    gat_finish<X>(gat_store<X>(g, k), k, s + 1);
    TS(11);
}

__device__ __forceinline__ void rec_fetch(const CUtensorMap* tm, uint32_t dst, int x, int y, int nx, uint32_t bar) {
#pragma unroll 1
    for (int j = 0; j < 8; j++) tma2d(dst + j * 8192, tm, x + (j / (8 / nx)) * 64, y + (j % (8 / nx)) * 64, bar);
}
__device__ __forceinline__ void rec_weights(const Params& p, uint32_t sb, int head, uint32_t rank, int w) {
    const int lane = threadIdx.x & 31, t = w & 3, WG = w >> 2;
    uint32_t wq[16][4], wk[16][4];
    const uint32_t rowo = (((lane >> 4) << 3) + (lane & 7)) * 128;
    const uint32_t woff = sb + WG * 32768 + rowo + (((2 * t + ((lane >> 3) & 1)) ^ (lane & 7)) << 4);
    const uint32_t qoff = sb + ((w & 1) ? R_STK : R_STQ) + WG * 32768 + rowo + (((2 * (t & 2) + ((lane >> 3) & 1)) ^ (lane & 7)) << 4);
    const uint32_t lw = sb + (lane ^ (lane >> 3)) * 16;
    PROF(threadIdx.x == 0, 3501);
    PROF(threadIdx.x == 0, 3502);
    mbar_wait(sb + R_BAR + RB_INIT * 8, 0);
    PROF(threadIdx.x == 0, 3503);
#pragma unroll
    for (int ks = 0; ks < 16; ks++) {
        uint4 a = ldsm4t(qoff + ks * 2048), b = ldsm4t((qoff ^ 32) + ks * 2048);
        wq[ks][0] = a.x; wq[ks][1] = a.y; wq[ks][2] = a.z; wq[ks][3] = a.w;
        wk[ks][0] = b.x; wk[ks][1] = b.y; wk[ks][2] = b.z; wk[ks][3] = b.w;
    }
    bar_sync(NB_W, 256);
#pragma unroll 4
    for (int ks = 0; ks < 16; ks++) { const uint4 a = ldsm4t(woff + R_STV + ks * 2048); sts128(lw + w * 512 + R_WV + ks * 4096, a.x, a.y, a.z, a.w); }
    bar_sync(NB_W, 256);
    if (threadIdx.x == 0) {
        mbar_expect(sb + R_BAR + RB_INIT * 8, 65536);
        rec_fetch(&p.tm[4], sb + R_STV, rank * 256, head * 128, 4, sb + R_BAR + RB_INIT * 8);
    }
    __syncwarp();
    mbar_wait(sb + R_BAR + RB_INIT * 8, 1);
#pragma unroll 4
    for (int f = 0; f < 16; f++) {
        const uint4 a = ldsm4t(sb + R_STV + (w >> 1) * 16384 + (f >> 1) * 2048 + rowo + ((((w & 1) * 4 + (f & 1) * 2 + ((lane >> 3) & 1)) ^ (lane & 7)) << 4));
        sts128(lw + w * 512 + R_WO + f * 4096, a.x, a.y, a.z, a.w);
    }
    PROF(threadIdx.x == 0, 3504);
    __syncthreads();
    cluster_sync();
    PROF(threadIdx.x == 0, 3505);
    RecW k;
    k.am = __shfl_sync(0xffffffffu, (uint32_t)(size_t)acc_base() + acc_main(rank, threadIdx.x), lane);
    k.ae = __shfl_sync(0xffffffffu, (uint32_t)(size_t)acc_base() + acc_extra(rank, threadIdx.x), lane);
    k.ah = (uint32_t)((size_t)acc_base() >> 32);
    k.sb = sb; k.zero = p.zero;

    k.dp = mapa(sb, rank ^ 1) - sb;
    k.lp = __shfl_sync(0xffffffffu, lw, lane);
    k.lpw = __shfl_sync(0xffffffffu, lw + w * 512, lane);
    k.vo = 4096 + w * 256 + (w & 1) * 64;
    k.bar = sb + k.dp + R_BAR + (RB_QK + WG) * 8;
    int it = 0;
    uint4 wt[16];
#pragma unroll
    for (int i = 0; i < NPD; i++) WLD(R_WV, i);
    gat_finish<0>(false, k, 0);
#pragma unroll 1
    for (; it < min(p.b1, p.e0); it++) { TSET(it, w == GPW ? 0 : 3); rec_step<false, 0>(k, it, it, wq, wk, wt); }
#pragma unroll 1
    for (; it < p.e0; it++) { TSET(it, w == GPW ? 0 : 3); rec_step<true, 0>(k, it, it - p.b1, wq, wk, wt); }
    if (it < p.nit) gat_finish<1>(false, k, it - p.b1);
#pragma unroll 1
    for (; it < p.nit; it++) { TSET(it, w == GPW ? 0 : 3); rec_step<false, 1>(k, it - p.b1, it - p.b1, wq, wk, wt); }
}

__device__ __forceinline__ void mma16_top(float* c, uint32_t a0, uint32_t a2, uint32_t b0, uint32_t b1) {
    asm volatile("{.reg .b32 j; mma.sync.aligned.m16n8k16.row.col.f32.bf16.bf16.f32 {%0,%1,%2,%3},{%4,j,%5,j},{%6,%7},{%0,%1,%2,%3};}"
                 : "+f"(c[0]), "+f"(c[1]), "+f"(c[2]), "+f"(c[3]) : "r"(a0), "r"(a2), "r"(b0), "r"(b1));
}
__device__ __forceinline__ void rec_load_tile(uint32_t sb, int X, int j, int s, int head, uint32_t rank) {
    const uint32_t bar = sb + R_BAR + (RB_T + X * 2 + j) * 8;
    mbar_expect1(bar, j ? 4096 : 16384);
    bulk_g2s1(sb + R_T + X * XS + j * 16384, g_qkv[X] + (size_t)(s * 32 + head) * 1536 + (j ? rank * 256 : 512), j ? 4096 : 16384, bar, POL_LAST);
}
__device__ __forceinline__ bool chunk_ready(int X, int j, int s) {
    unsigned v;
    asm volatile("ld.relaxed.gpu.global.u32 %0,[%1];" : "=r"(v) : "l"(cnt_ptr(C_QKV0 + X, (s >> 2) + j * 16)) : "memory");
    return __all_sync(0xffffffffu, v >= (256 >> j));
}
__device__ __forceinline__ uint4 hadd4(uint4 a, uint4 b) { return make_uint4(hadd2(a.x, b.x), hadd2(a.y, b.y), hadd2(a.z, b.z), hadd2(a.w, b.w)); }
struct RecH { uint32_t lw, lm, lq, lv, lu, sa, sp, xb, sb, zero, ts, tn; };
__device__ __forceinline__ void rec_publish(int X, int s) {
    asm volatile("{.reg .pred p; cp.async.bulk.wait_group 0; elect.sync _|p,0xffffffff; @p red.relaxed.gpu.global.add.u32 [%0],4;}" ::"l"(cnt_ptr(C_O0 + X, s >> 2)) : "memory");
}
__device__ __forceinline__ void rec_mattn(const RecH& k, uint32_t dp, int X, int j, int s, uint4 (*V)[4], uint4* vm, uint4* kmm) {
    const uint32_t sb = k.sb, to = R_T, lo = R_LOC, ro = R_REM + (s & 1) * 6144;
    const uint32_t bar = sb + R_BAR + (X * 2 + j) * 8;
    uint4 K[2][4];
    mbar_wait(sb + R_BAR + (RB_T + X * 2) * 8, s & 1);
    TS(1);
#pragma unroll
    for (int i = 0; i < 8; i++) K[i >> 2][i & 3] = ldsm4o(k.lm, (to + (i >> 2) * 1024 + ((i >> 1) & 1) * 4096 + (i & 1) * 512));
    asm volatile("cp.async.bulk.wait_group 0;" ::: "memory");
    bar_sync(NB_LOC + X, 320);
    fence_async_smem();
    asm volatile("{.reg .pred p; elect.sync _|p,0xffffffff; @p cp.async.bulk.shared::cluster.shared::cta.mbarrier::complete_tx::bytes [%0],[%1],1024,[%2];}"
                 ::"r"(k.xb + dp + ro + 4096), "r"(k.xb + lo + 4096), "r"(bar + dp + RB_V * 8) : "memory");
    uint4 u[4];
#pragma unroll
    for (int i = 0; i < 4; i++) u[i] = ldsm4o(k.lm, (lo + i * 512));
    TS(2);
    mbar_wait(bar + RB_QK * 8, s & 1);
    TS(3);
    float S[5][4];
#pragma unroll
    for (int i = 0; i < 5; i++) S[i][0] = S[i][1] = S[i][2] = S[i][3] = 0;
    {
        uint4 r[4];
#pragma unroll
        for (int i = 0; i < 4; i++) r[i] = ldsm4o(k.lm, (ro + i * 512));
        SF;
#pragma unroll
        for (int e = 0; e < 2; e++) {
            uint4& km = u[2 * e + 1];
            const uint32_t q0 = hadd2(u[2 * e].x, r[2 * e].x), q1 = hadd2(u[2 * e].y, r[2 * e].y);
            mma16_top(S[0], q0, q1, K[e][0].x, K[e][0].y);
            km.x = hadd2(km.x, r[2 * e + 1].x); km.y = hadd2(km.y, r[2 * e + 1].y);
            SF;
            mma16_top(S[1], q0, q1, K[e][1].x, K[e][1].y);
            const uint32_t q2 = hadd2(u[2 * e].z, r[2 * e].z), q3 = hadd2(u[2 * e].w, r[2 * e].w);
            SF;
            mma16_top(S[2], q0, q1, K[e][2].x, K[e][2].y);
            km.z = hadd2(km.z, r[2 * e + 1].z); km.w = hadd2(km.w, r[2 * e + 1].w);
            SF;
            mma16_top(S[3], q0, q1, K[e][3].x, K[e][3].y);
            mma16_top(S[4], q0, q1, km.x, km.y);
            SF;
#pragma unroll
            for (int i = 0; i < 4; i++) {
                mma16_top(S[i], q2, q3, K[e][i].z, K[e][i].w); SF;
            }
            mma16_top(S[4], q2, q3, km.z, km.w);
            SF;
        }
    }
#define VLD(a, b) _Pragma("unroll") for (int i = (a); i < (b); i++) V[i >> 2][i & 3] = ldsm4to((i & 1) ? lv2 : k.lv, (to + 8192 + (i >> 2) * 4096 + ((i >> 1) & 1) * 1024))
    const uint32_t lv2 = vxor(k.lv, 0x20), lh = k.lw - (vshr(k.lw - k.xb, 1) & 0xf8);
    VLD(0, VE);
    SF;
    const uint32_t sxr = k.sa, sxw = k.sp;
    sts128o(k.lw, sxw, __float_as_uint(S[0][0]), __float_as_uint(S[0][1]), __float_as_uint(S[1][0]), __float_as_uint(S[1][1]));
    SF;
    sts128o(k.lw, (sxw + 512), __float_as_uint(S[2][0]), __float_as_uint(S[2][1]), __float_as_uint(S[3][0]), __float_as_uint(S[3][1]));
    SF;
    sts64o(lh, (sxw + 1024), __float_as_uint(S[4][0]), __float_as_uint(S[4][1]));
    TS(4);
    bar_sync(NB_PAIR + X, 64);
    {
        const uint4 a = lds128o(k.lw, sxr), b = lds128o(k.lw, (sxr + 512));
        const uint2 c = lds64o(lh, (sxr + 1024));
        SF;
        VLD(VE, VF);
        SF;
        S[0][0] += __uint_as_float(a.x); S[0][1] += __uint_as_float(a.y); S[1][0] += __uint_as_float(a.z); S[1][1] += __uint_as_float(a.w);
        S[2][0] += __uint_as_float(b.x); S[2][1] += __uint_as_float(b.y); S[3][0] += __uint_as_float(b.z); S[3][1] += __uint_as_float(b.w);
        S[4][0] += __uint_as_float(c.x); S[4][1] += __uint_as_float(c.y);
    }
    float m = fmaxf(fmaxf(fmaxf(S[0][0], S[0][1]), fmaxf(S[1][0], S[1][1])), fmaxf(fmaxf(S[2][0], S[2][1]), fmaxf(S[3][0], S[3][1])));
    m = fmaxf(m, fmaxf(S[4][0], S[4][1]));
    m = fmaxf(m, __shfl_xor_sync(0xffffffffu, m, 1));
    const float m2 = __shfl_xor_sync(0xffffffffu, m, 2);
    SF;
    VLD(VF, 8);
    uint32_t ok;
    asm volatile("{.reg .pred p; mbarrier.test_wait.parity.shared::cta.b64 p,[%1],%2; selp.u32 %0,1,0,p;}" : "=r"(ok) : "r"(bar + RB_V * 8), "r"(s & 1) : "memory");
    uint4 vr0 = ldsm4o(k.lu, (ro + 4096)), vr1 = ldsm4o(k.lu, (ro + 4608));
    vm[0] = ldsm4o(k.lu, (lo + 4096)); vm[1] = ldsm4o(k.lu, (lo + 4608));
    SF;
    TS(5);
    m = fmaxf(m, m2) * -SC_LOG2E;
    uint32_t P[5];
#pragma unroll
    for (int i = 0; i < 5; i++) P[i] = pack2(ex2(fmaf(S[i][0], SC_LOG2E, m)), ex2(fmaf(S[i][1], SC_LOG2E, m)));
    float o[4][4], l[4] = {0, 0, 0, 0};
    const uint32_t ONE = 0x3f803f80u;
    mma16_top(l, ONE, ONE, P[0], P[1]);
#pragma unroll
    for (int t = 0; t < 4; t++) { o[t][0] = o[t][1] = o[t][2] = o[t][3] = 0; mma16(o[t], V[0][t].x, V[0][t].y, V[0][t].z, V[0][t].w, P[0], P[1]); }
    mma16_top(l, ONE, ONE, P[2], P[3]);
#pragma unroll
    for (int t = 0; t < 4; t++) mma16(o[t], V[1][t].x, V[1][t].y, V[1][t].z, V[1][t].w, P[2], P[3]);
    if (!__all_sync(0xffffffffu, ok)) {
        mbar_wait(bar + RB_V * 8, s & 1);
        vr0 = ldsm4o(k.lu, (ro + 4096)); vr1 = ldsm4o(k.lu, (ro + 4608));
    }
    TS(6);
    vm[0] = hadd4(vm[0], vr0); vm[1] = hadd4(vm[1], vr1);
    mma8(l, ONE, ONE, P[4]);
    mma8(o[0], vm[0].x, vm[0].y, P[4]); mma8(o[1], vm[0].z, vm[0].w, P[4]); mma8(o[2], vm[1].x, vm[1].y, P[4]); mma8(o[3], vm[1].z, vm[1].w, P[4]);
    asm volatile("{.reg .pred p; .reg .b32 t; setp.lt.u32 p,%0,%3; add.u32 t,%0,%4; @p st.shared.v2.f32 [t],{%1,%2};}" ::"r"(lh), "f"(rcp(l[0])), "f"(rcp(l[1])), "r"(k.xb + 32), "r"(R_IL) : "memory");
#pragma unroll
    for (int t = 0; t < 4; t += 2)
        asm volatile("{.reg .b32 t; add.u32 t,%0,%5; stmatrix.sync.aligned.m8n8.x4.trans.shared.b16 [t],{%1,%2,%3,%4};}" ::"r"(k.lm),
                     "r"(pack2(o[t][0], o[t][1])), "r"(pack2(o[t][2], o[t][3])), "r"(pack2(o[t + 1][0], o[t + 1][1])), "r"(pack2(o[t + 1][2], o[t + 1][3])), "r"(R_O - j * 1024 + t * 256) : "memory");
    bar_arrive(NB_O + X, 320);
    PROF(k.lw == k.xb, X * 64 + s);
    TS(7);
    kmm[0] = u[1]; kmm[1] = u[3];
    mbar_expect1(bar + RB_QK * 8, 2048); mbar_expect1(bar + RB_V * 8, 1024);
}
template <int MT>
__device__ __forceinline__ void rec_xattn(const RecH& k, int X, int j, int s, int head, bool early, const uint4 (*V)[4], const uint4* vmm, const uint4* kmm) {
    constexpr int NTL = 3 + 2 * MT;
    const uint32_t sb = k.sb, to = R_T;
    const uint32_t sxw = k.sa, sxr = k.sp;
    const uint32_t lq2 = vxor(k.lq, 0x20);
    float S[NTL][4];
#pragma unroll
    for (int i = 0; i < NTL; i++) S[i][0] = S[i][1] = S[i][2] = S[i][3] = 0;
    {
        uint4 q[2][2], kk[2][NTL];
#define XQ(e) q[e][0] = ldsm4o(k.lq, (to + 16384 + (e) * 1024)); q[e][1] = ldsm4o(lq2, (to + 16384 + (e) * 1024))
#define XK(e, i) kk[e][i] = ldsm4o(k.lm, (to + (e) * 1024 + (((i) - 1) >> 1) * 4096 + (((i) - 1) & 1) * 512))
        kk[0][0] = kmm[0]; kk[1][0] = kmm[1];
        if (!X) bar_sync(NB_XG, 320);
        XQ(0);
#pragma unroll
        for (int i = 1; i < NTL; i++) XK(0, i);
        SF;
#pragma unroll
        for (int i = 0; i < NTL; i++) { mma16(S[i], q[0][0].x, q[0][0].y, q[0][0].z, q[0][0].w, kk[0][i].x, kk[0][i].y); SF; }
        q[1][0] = ldsm4o(k.lq, (to + 16384 + 1024));
#pragma unroll
        for (int i = 0; i < NTL; i++) { mma16(S[i], q[0][1].x, q[0][1].y, q[0][1].z, q[0][1].w, kk[0][i].z, kk[0][i].w); SF; if (i + 1 < NTL) XK(1, i + 1); SF; }
        q[1][1] = ldsm4o(lq2, (to + 16384 + 1024));
        SF;
#pragma unroll
        for (int i = 0; i < NTL; i++) { mma16(S[i], q[1][0].x, q[1][0].y, q[1][0].z, q[1][0].w, kk[1][i].x, kk[1][i].y); SF; }
#pragma unroll
        for (int i = 0; i < NTL; i++) { mma16(S[i], q[1][1].x, q[1][1].y, q[1][1].z, q[1][1].w, kk[1][i].z, kk[1][i].w); SF; }
    }
#pragma unroll
    for (int i = 0; i < NTL; i++) sts128o(k.lw, (sxw + i * 512), __float_as_uint(S[i][0]), __float_as_uint(S[i][1]), __float_as_uint(S[i][2]), __float_as_uint(S[i][3]));
    SF;
    if (X) bar_sync(NB_XG + 1, 320); else bar_sync(NB_PAIR + 2, 64);
    TS(9);
    if (early && !X) rec_load_tile(sb, X, j, s + 1, head, MT);
#pragma unroll
    for (int i = 0; i < NTL; i++) {
        const uint4 r = lds128o(k.lw, (sxr + i * 512));
        S[i][0] += __uint_as_float(r.x); S[i][1] += __uint_as_float(r.y); S[i][2] += __uint_as_float(r.z); S[i][3] += __uint_as_float(r.w);
    }
    const int g = vshr(k.lw - k.xb, 6) & 7, c = (vshr(k.lw, 4) ^ (g >> 1)) & 3;
    const float NEG = -__int_as_float(0x7f800000);
    if (2 * c > g) { S[NTL - 2][0] = NEG; S[NTL - 1][2] = NEG; }
    if (2 * c + 1 > g) { S[NTL - 2][1] = NEG; S[NTL - 1][3] = NEG; }
    float m0 = fmaxf(S[0][0], S[0][1]), m1 = fmaxf(S[0][2], S[0][3]);
#pragma unroll
    for (int i = 1; i < NTL; i++) { if (i < NTL - 1) m0 = fmaxf(m0, fmaxf(S[i][0], S[i][1])); m1 = fmaxf(m1, fmaxf(S[i][2], S[i][3])); }
    m0 = fmaxf(m0, __shfl_xor_sync(0xffffffffu, m0, 1)); m1 = fmaxf(m1, __shfl_xor_sync(0xffffffffu, m1, 1));
    m0 = fmaxf(m0, __shfl_xor_sync(0xffffffffu, m0, 2)); m1 = fmaxf(m1, __shfl_xor_sync(0xffffffffu, m1, 2));
    m0 *= -SC_LOG2E; m1 *= -SC_LOG2E;
    uint32_t P[NTL][2];
#pragma unroll
    for (int i = 0; i < NTL; i++) {
        P[i][0] = i < NTL - 1 ? pack2(ex2(fmaf(S[i][0], SC_LOG2E, m0)), ex2(fmaf(S[i][1], SC_LOG2E, m0))) : 0u;
        P[i][1] = pack2(ex2(fmaf(S[i][2], SC_LOG2E, m1)), ex2(fmaf(S[i][3], SC_LOG2E, m1)));
    }
    float l[4] = {0, 0, 0, 0};
#pragma unroll
    for (int i = 0; i < NTL; i++) mma8(l, P[i][0], P[i][1], 0x3f803f80u);
    const float l0 = rcp(l[0]), l1 = rcp(l[2]);

#pragma unroll
    for (int e = 0; e < 2; e++) {
        const uint4 vm = vmm[e];
        uint32_t u[2][4];
#pragma unroll
        for (int n = 0; n < 4; n++) {
            float a[4] = {0, 0, 0, 0};
#pragma unroll
            for (int m = 0; m <= MT; m++) {
                const uint4 v = V[m][e * 2 + (n >> 1)];
                mma8(a, P[1 + 2 * m][0], P[1 + 2 * m][1], (n & 1) ? v.y : v.x); mma8(a, P[2 + 2 * m][0], P[2 + 2 * m][1], (n & 1) ? v.w : v.z);
            }
            mma8(a, P[0][0], P[0][1], n == 0 ? vm.x : n == 1 ? vm.y : n == 2 ? vm.z : vm.w);
            u[0][n] = pack2(a[0] * l0, a[1] * l0); u[1][n] = pack2(a[2] * l1, a[3] * l1);
        }
        sts128o(k.lw, sxr + e * 512, u[0][0], u[0][1], u[0][2], u[0][3]); sts128o(k.lw, sxr + e * 512 + 1024, u[1][0], u[1][1], u[1][2], u[1][3]);
    }
    if (early && X) rec_load_tile(sb, X, j, s + 1, head, MT);
    TS(10);
}
__device__ __forceinline__ void rec_attn(const Params& p, uint32_t sb, int X, int j, int head, uint32_t rank) {
    const int lane = threadIdx.x & 31;
    RecH k;
    k.xb = sb + X * XS + j * 1024;
    const uint32_t x2 = k.xb + j * 1024;
    k.lw = __shfl_sync(0xffffffffu, x2 + (lane ^ (lane >> 3)) * 16, lane);
    k.lm = __shfl_sync(0xffffffffu, x2 + ((lane & 7) * 4 + ((lane >> 3) ^ ((lane & 7) >> 1))) * 16, lane);
    k.lq = __shfl_sync(0xffffffffu, x2 + ((lane >> 3) & 1) * 512 + ((lane & 7) * 4 + ((lane >> 4) ^ ((lane & 7) >> 1))) * 16, lane);
    k.lv = __shfl_sync(0xffffffffu, x2 + (lane >> 4) * 512 + ((lane & 7) * 4 + (((lane >> 3) & 1) ^ ((lane & 7) >> 1))) * 16, lane);
    k.lu = __shfl_sync(0xffffffffu, k.xb + ((lane & 6) * 4 + (((lane >> 3) * 2 + (lane & 1)) ^ (lane & 6))) * 16, lane);
    k.sa = __shfl_sync(0xffffffffu, R_SX + j * 512, 0); k.sp = __shfl_sync(0xffffffffu, R_SX + 2560 - j * 4608, 0);
    k.sb = sb; k.zero = p.zero;
    const uint32_t dp = mapa(sb, rank ^ 1) - sb;
    char* zp = acc_base() + (j ? X * 32768 + acc_main(rank, head * 8) : X * 1024 + acc_extra(rank, head * 8));
    mbar_expect1(sb + R_BAR + (RB_QK + X * 2 + j) * 8, 2048); mbar_expect1(sb + R_BAR + (RB_V + X * 2 + j) * 8, 1024);
    bool early = false;
#pragma unroll 1
    for (int s = 0; s < 64; s++) {
        TSET(X ? s + p.b1 : s, j == GPJ ? 1 + X : 3);
        TS(0);
        if (!early) {
            if (!j) wait_cnt_warp(cnt_ptr(C_QKV0 + X, s >> 2), 256);
            early = !j || chunk_ready(X, 1, s);
            if (early) rec_load_tile(sb, X, j, s, head, rank);
        }
        uint4 V[2][4], vm[2], km[2];
        rec_mattn(k, dp, X, j, s, V, vm, km);
        if (!early) { wait_cnt_warp(cnt_ptr(C_QKV0 + X, (s >> 2) + 16), 128); rec_load_tile(sb, X, 1, s, head, rank); }
        early = s < 63 && ((s & 3) != 3 || chunk_ready(X, j, s + 1));
        mbar_wait(sb + R_BAR + (RB_T + X * 2 + 1) * 8, s & 1);
        if (rank) rec_xattn<1>(k, X, j, s, head, early, V, vm, km); else rec_xattn<0>(k, X, j, s, head, early, V, vm, km);
        fence_async_smem();
        __syncwarp();
        asm volatile("{.reg .pred p; elect.sync _|p,0xffffffff;\n"
                     "@p cp.async.bulk.global.shared::cta.bulk_group.L2::cache_hint [%0],[%1],2048,%2;\n"
                     "@p cp.async.bulk.global.shared::cta.bulk_group [%3],[%4],%5;\n"
                     "cp.async.bulk.commit_group;}"
                     ::"l"(g_o[X] + ((s >> 2) * 64 + head * 2 + j) * 1024 + ((s & 3) * 2 + rank) * 128), "r"(x2 + k.sp),
                       "l"((X && s < 40) ? POL_LATE : POL_SOON), "l"(zp + acc_slot(s + 2)), "r"(sb + R_Z), "r"(j ? 128 : 32) : "memory");
        if (s == 61) rec_publish(X, 64);
        if ((s & 3) == 3) {
            if (!early && s < 63 && chunk_ready(X, j, s + 1)) { rec_load_tile(sb, X, j, s + 1, head, rank); early = true; }
            rec_publish(X, s);
            PROF(lane == 0 && j, 3900 + X * 16 + (s >> 2));
        }
    }
}

__device__ __forceinline__ void rec_init(const Params& p, uint32_t sb, int head, uint32_t rank) {
    const uint32_t b = sb + R_BAR;
    const int i = threadIdx.x - 320;
    if (i >= 0 && i < RB_N) {
        mbar_init(b + i * 8, 1);
        asm volatile("fence.mbarrier_init.release.cluster;" ::: "memory");
    }
    if (i == 0) mbar_expect(b + RB_INIT * 8, 196608);
    if (i >= 0 && i < 32) sts32(sb + R_Z + i * 4, 0);
}

#define NSTGN 8
constexpr int NSTG = NSTGN, STG_B = 24576;
#define LAGH 3
constexpr int NSB = 8;
constexpr int B_OUT = NSTG * STG_B  , B_UT = B_OUT, B_YT = B_UT + 16384, B_SP = B_YT  ,
              B_ST = 229376  , B_BAR = 231936;
static_assert(B_OUT + NSB * 4096 <= B_ST && B_ST + 2048 <= B_BAR && B_YT + 10240 <= B_ST, "smem map");
enum { BB_FULL = 0, BB_EMPTY = 8, BB_SF = 16  , BB_GO = 18, BB_LOW = 19, BB_DONE = 20  , BB_IDLE = 22  , BB_N = 30 };
enum { NB_REL = 2  , NB_C = 11, NB_WG = 12  , NB_PH = 14 };

__device__ __forceinline__ void bulk_init(uint32_t sb) {
    const int i = threadIdx.x - 320;
    if (i >= 0 && i < BB_N) {
        mbar_init(sb + B_BAR + i * 8, (i >= BB_EMPTY && i < BB_EMPTY + NSTG) ? 4 : i >= BB_DONE ? 4 : 1);
        asm volatile("fence.mbarrier_init.release.cluster;" ::: "memory");
    }
}

struct Task { int type, layer, ch, a, b, c, blk; bool pair, dry; };
__device__ __forceinline__ Task task_of(uint32_t tk, uint32_t rank) {
    Task t;
    t.type = tk & 7; t.layer = (tk >> 3) & 1; t.a = (tk >> 8) & 255; t.b = (tk >> 16) & 255; t.c = (tk >> 24) & 127; t.dry = tk >> 31;
    t.pair = t.type <= T_OP && (t.c & 64);
    t.ch = ((tk >> 4) & 15) + (t.pair ? rank : 0);
    t.blk = t.type == T_QKV ? t.a + (t.pair ? 0 : rank) : 192 + (t.pair ? (t.c >> 2) & 4 : rank * 4);
    return t;
}
__device__ __forceinline__ int qkv_blk(const Task& t, int u) {
    const int v = t.blk + (t.pair ? 1 : 2 * t.c) * u;
    return 2 * (v < 64 ? v + 32 : v - 64);
}
__device__ __forceinline__ void bulk_producer(const Params& p, uint32_t sb, int cl, uint32_t rank) {
    int st = 0; uint32_t ph = 1;
    const int tag = __shfl_sync(0xffffffffu, lds32(sb + S_TAG), 0);
    bool gated = false;
#define ACQ(bytes) do { mbar_wait(sb + B_BAR + (BB_EMPTY + st) * 8, ph); mbar_expect1(sb + B_BAR + (BB_FULL + st) * 8, bytes); } while (0)
#define NEXT do { if (++st == NSTG) { st = 0; ph ^= 1; } } while (0)
#pragma unroll 1
    for (int ti = 0; ti < MAXT; ti++) {
        const Task t = task_of(p.task[list_of(cl)][ti], rank);
        const int layer = t.layer, ch = t.ch;
        if (t.type == T_END) break;
        if (t.type <= T_OP) {
            const bool qkv = t.type == T_QKV;
            const int nh = (qkv ? 8 : 2) * t.b;
            const bool halves = !qkv && (t.c & 80) == 16;
            const unsigned* dep = cnt_ptr(qkv ? (layer ? C_CV : C_ST) : C_O0 + layer, ch + (halves && !rank));
            const unsigned need = qkv ? (layer ? 32 : ch < 2 ? 0 : 16) : 512;
            const uint16_t mb = t.pair ? 3 : 1 << rank, ma = t.pair ? 1 << rank : 3;
            const int pend = min(nh, gated ? NSTG : 4);
            auto ready = [&](int h) {
                if (h < pend) {
                    unsigned v = 0;
                    if (gated) asm volatile("ld.relaxed.gpu.global.u32 %0,[%1];" : "=r"(v) : "l"(dep) : "memory");
                    return gated && __all_sync(0xffffffffu, v >= need);
                }
                if (!gated) { wait_cnt_warp(g_gate, lds32(sb + S_GATE)); gated = true; }
                if (need) wait_cnt_warp(dep, need);
                return true;
            };
            bool open = true;
            if (qkv) {
#pragma unroll 1
                while (st) { ACQ(0); NEXT; }
#pragma unroll 1
                for (int h = 0; h < nh; h++) {
                    const int blk = qkv_blk(t, h >> 3);
                    ACQ(16384 + (h < 2 ? (layer ? 8192 : 1024) : 0));
                    if (!t.pair || !rank) tma3d_mc(sb + st * STG_B, &p.t3[blk >> 6], (h & 7) * 64, blk & 63, sb + B_BAR + (BB_FULL + st) * 8, mb);
                    if (!t.pair || rank) tma3d_mc(sb + st * STG_B + 8192, &p.t3[blk >> 6], (h & 7) * 64 + 32, blk & 63, sb + B_BAR + (BB_FULL + st) * 8, mb);
                    NEXT;
                    if (open && h && ready(h + 1)) {
                        open = false;
                        const float2* sp = g_st[layer] + ch * 2048 + (need ? 0 : tag * 256);
                        bulk_g2s1(sb + 16384, sp, layer ? 8192 : 1024, sb + B_BAR + BB_FULL * 8, POL_N);
                        bulk_g2s1(sb + STG_B + 16384, sp + (layer ? 1024 : 128), layer ? 8192 : 1024, sb + B_BAR + (BB_FULL + 1) * 8, POL_N);
                    }
                }
                continue;
            }
            if (PFC && !layer && (t.c & 15) < 8) {
                const int q = (t.c & 15) * 2 + rank;
                asm volatile("{.reg .pred p; elect.sync _|p,0xffffffff; @p cp.async.bulk.prefetch.L2.global [%0],8192; @p cp.async.bulk.prefetch.L2.global [%1],%2;}"
                             ::"l"(g_xA[0] + (ch * 16 + q) * 512), "l"(g_P + q * 16 * 32 * PW), "r"((2 + (ch & 1)) * 32 * PW * 4) : "memory");
            }
            const CUtensorMap *tb = &p.t3[4 - t.pair], *ta = &p.ta[t.pair];
            const uint32_t db = sb + 8192 + (t.pair ? rank * 8192 : 0), da = sb + (t.pair ? 0 : rank * 4096);
            const int zb = (t.blk & 63) + (t.pair ? rank * 2 : 0), ya = 4096 + ((layer * 16 + ch) * 64 + t.a) * 16 + (t.pair ? 0 : rank * 8), row = t.a * 64;
            int h = 0;
            const int s0 = st;
            if (halves) mbar_expect1(sb + B_BAR + BB_LOW * 8, NSTG * 4096);
#pragma unroll 1
            for (; (halves && h < NSTG) || !ready(h); h++) { ACQ(halves ? STG_B - 4096 : STG_B); tma3d_mc(db + st * STG_B, tb, row + h * 32, zb, sb + B_BAR + (BB_FULL + st) * 8, mb); NEXT; }
#pragma unroll 1
            for (int k = 0; k < h; k++) {
                const int s2 = (s0 + k) & (NSTG - 1);
                tma2d_mc(da + s2 * STG_B, ta, (k & 1) * 256, ya + (k >> 1) * 16, sb + B_BAR + (halves && rank ? BB_LOW : BB_FULL + s2) * 8, ma, POL_LAST);
            }
#pragma unroll 1
            for (; h < nh; h++) {
                ACQ(STG_B);
                tma3d_mc(db + st * STG_B, tb, row + h * 32, zb, sb + B_BAR + (BB_FULL + st) * 8, mb);
                tma2d_mc(da + st * STG_B, ta, (h & 1) * 256, ya + (h >> 1) * 16, sb + B_BAR + (BB_FULL + st) * 8, ma, POL_LAST);
                NEXT;
            }
#pragma unroll 1
            for (h = 0; h < 4 && !layer; h++) { ACQ(0); NEXT; }
        } else if (t.type == T_CV) {
            const int q = t.a + rank;
            if (!gated) { wait_cnt_warp(g_gate, lds32(sb + S_GATE)); gated = true; }
            if (layer) {
                wait_cnt_warp(cnt_ptr(C_U, ch - 2), 32);
#pragma unroll 1
                for (int j = ch + 1; j >= 2; j--) {
                    ACQ(16 * PW * 4 + (j > 2 ? 4096 : 0));
                    bulk_g2s1(sb + st * STG_B, g_P + (((q >> 1) * 16 + j) * 2 + (q & 1)) * 16 * PW, 16 * PW * 4, sb + B_BAR + (BB_FULL + st) * 8, POL_N);
                    if (j > 2) bulk_g2s1(sb + st * STG_B + 12288, g_u + (((q >> 1) * 16 + ch + 1 - j) * 2 + (q & 1)) * 256, 4096, sb + B_BAR + (BB_FULL + st) * 8, POL_N);
                    NEXT;
                }
            } else {
#pragma unroll 1
                for (int j = min(ch, 1 + (ch & 1)); j >= 0; j--) {
                    if (j == 0 && ch >= 2) {
                        wait_cnt_warp(cnt_ptr(C_H, ch & ~1), 64);
#pragma unroll 1
                        for (int i = 0; i < ((ch & 1) || ch == 2 ? 1 : 2); i++) {
                            ACQ(16384);
                            bulk_g2s1(sb + st * STG_B, g_carry[i] + (ch * 16 + q) * 1024, 16384, sb + B_BAR + (BB_FULL + st) * 8, POL_LAST);
                            NEXT;
                        }
                    }
                    ACQ(32 * PW * 4);
                    bulk_g2s1(sb + st * STG_B, g_P + (q * 16 + j) * 32 * PW, 32 * PW * 4, sb + B_BAR + (BB_FULL + st) * 8, POL_N);
                    NEXT;
                }
            }
        }
    }
}

__device__ __forceinline__ uint4* qkv_dst(int layer, int ch, int w, int blk);
__device__ __forceinline__ uint4* op_dst(int layer, int ch, int slot, int w, uint32_t rank);
__device__ __forceinline__ uint64_t out_pol(int type, int layer, int ch) { return (type == T_QKV ? (!layer && ch > 1) : (layer && ch < 10)) ? POL_LATE : POL_SOON; }
__device__ __forceinline__ void bulk_relay(const Params& p, uint32_t sb, int cl) {
    for (int ti = 0; ti < MAXT; ti++) {
        const int type = p.task[list_of(cl)][ti] & 7;
        if (type == T_END) break;
        if (type != T_QKV) continue;
        bar_sync(NB_PH, 64);
        const uint32_t ph = lds32(sb + B_ST + 8);
#pragma unroll 1
        for (int h = 2; h < 8; h++) {
            mbar_wait(sb + B_BAR + (BB_FULL + h) * 8, ph);
            if (h == 4 || h == 7) { bar_arrive(NB_REL + (h == 7) * 2, 160); bar_arrive(NB_REL + (h == 7) * 2 + 1, 160); }
        }
    }
}
__device__ __forceinline__ void bulk_release(const Params& p, uint32_t sb, int cl, uint32_t rank, int wg) {
    int nd = 0;
    for (int ti = 0; ti < MAXT; ti++) {
        const Task t = task_of(p.task[list_of(cl)][ti], rank);
        const int type = t.type, layer = t.layer, ch = t.ch;
        if (type == T_END) break;
        if (type == T_FIN || (type == T_OP && (t.c & 32))) continue;
        if (type == T_OP && !layer) {
            mbar_wait(sb + B_BAR + (BB_DONE + wg) * 8, nd & 1);
            nd++;
            const int s0 = __shfl_sync(0xffffffffu, lds32(sb + B_ST + wg * 4), 0) + wg * 2;
            fence_async_smem();
#pragma unroll 1
            for (int w = 0; w < 4; w++)
                asm volatile("{.reg .pred p; elect.sync _|p,0xffffffff; @p cp.async.bulk.global.shared::cta.bulk_group.L2::cache_hint [%0],[%1],8192,%2; cp.async.bulk.commit_group;}"
                             ::"l"(op_dst(0, ch, t.c & 15, wg * 4 + w, rank)), "r"(sb + ((s0 + (w >> 1)) & (NSTG - 1)) * STG_B + (w & 1) * 8192), "l"(POL_SOON) : "memory");
            mbar_arrive1(sb + B_BAR + (BB_SF + wg) * 8);
            asm volatile("{.reg .pred p; elect.sync _|p,0xffffffff;\n"
                         "cp.async.bulk.wait_group 3; @p red.relaxed.gpu.global.add.u32 [%0],1; cp.async.bulk.wait_group 2; @p red.relaxed.gpu.global.add.u32 [%0+64],1;\n"
                         "cp.async.bulk.wait_group 1; @p red.relaxed.gpu.global.add.u32 [%0+128],1; cp.async.bulk.wait_group 0; @p red.relaxed.gpu.global.add.u32 [%0+192],1;}"
                         ::"l"(cnt_ptr(C_OP0 + rank * 2 + wg, ch)) : "memory");
#pragma unroll 1
            for (int i = 0; i < 8; i++) mbar_arrive1_cluster(mapa(sb + B_BAR + (BB_EMPTY + ((s0 + (i >> 2)) & (NSTG - 1))) * 8, i & 1));
            continue;
        }
#pragma unroll 1
        for (int u = 0; u < (type == T_QKV ? t.b : 1); u++) {
            const int blk = qkv_blk(t, u);
            unsigned* cnt = cnt_ptr(type == T_QKV ? C_QKV0 + layer : type == T_OP ? C_OP1 : layer ? C_H : C_CV, ch + (type == T_QKV && blk < 64 ? 16 : 0));
            const uint4* dst = type == T_QKV ? qkv_dst(layer, ch, wg * 4, blk) : op_dst(1, ch, t.c & 15, wg * 4, (t.blk >> 2) & 1) + 256;
            mbar_wait(sb + B_BAR + (BB_DONE + wg) * 8, nd & 1);
            nd++;
            if (type != T_CV) {
                fence_async_smem();
#pragma unroll
                for (int w = 0; w < 4; w++)
                    asm volatile("{.reg .pred p; elect.sync _|p,0xffffffff; @p cp.async.bulk.global.shared::cta.bulk_group.L2::cache_hint [%0],[%1],4096,%2;}"
                                 ::"l"(dst + (type == T_QKV ? (w >> 1) * 49152 + (w & 1) * 256 : w * 1024)), "r"(sb + B_OUT + (wg * 4 + w) * 4096), "l"(out_pol(type, layer, ch)) : "memory");
                asm volatile("cp.async.bulk.commit_group; cp.async.bulk.wait_group 0;" ::: "memory");
            }
            if (type != T_QKV) fence_async();
            if (!t.dry) asm volatile("{.reg .pred p; elect.sync _|p,0xffffffff; @p red.relaxed.gpu.global.add.u32 [%0],%1;}" ::"l"(cnt), "r"(type == T_QKV ? 2 : type == T_OP ? t.b : 1) : "memory");
            PROF(wg && (threadIdx.x & 31) == 0 && (type == T_CV || u + 2 == t.b), 3900 + ti);
            if (type == T_CV && !layer && !t.dry) {
                asm volatile("{.reg .pred p; elect.sync _|p,0xffffffff; @p cp.async.bulk.global.shared::cta.bulk_group [%0],[%1],4096;\n"
                             "cp.async.bulk.commit_group; cp.async.bulk.wait_group 0; @p red.relaxed.gpu.global.add.u32 [%2],1;}"
                             ::"l"(g_u + ((t.a + rank) * 16 + ch) * 512 + wg * 256), "r"(sb + B_UT + (ch & 1) * 8192 + wg * 4096), "l"(cnt_ptr(C_U, ch)) : "memory");
            }
            mbar_arrive1(sb + B_BAR + (BB_SF + wg) * 8);
        }
        PROF(wg && (threadIdx.x & 31) == 0, 3600 + ti * 4 + 3);
    }
}

__device__ __forceinline__ void stage_release(uint32_t sb, int w, int st) {
    if (!(w & 2)) mbar_arrive1_cluster(mapa(sb + B_BAR + (BB_EMPTY + st) * 8, w & 1));
}
template <bool ACC>
__device__ __forceinline__ void gemm_run(float* acc, uint32_t sb, int w, int h0, int h1, uint32_t& r0, uint32_t& r1, int& st, uint32_t& ph) {
    const uint64_t da0 = mkdesc(sb + (w >> 2) * 4096, 16, 512, 2), db0 = mkdesc(sb + 8192, 4096, 1024, 1);
    const uint32_t rel0 = mapa(sb + B_BAR + BB_EMPTY * 8, w & 1);
#pragma unroll 1
    for (int h = h0; h < h1; h++) {
        const uint64_t da = da0 + st * (STG_B >> 4), db = db0 + st * (STG_B >> 4);
        mbar_wait(sb + B_BAR + (BB_FULL + st) * 8, ph);
        if (ACC) wg_wait<1>();
        wg_fence();
        wgmma256<ACC>(acc, da, db);
        wgmma256<true>(acc, da + 2, db + 128);
        wg_commit();
        if (ACC) mbar_arrive1_cluster((w == 2 && h == LAGH - 1) ? sb + B_BAR + BB_GO * 8 : r0);
        r0 = r1;
        if (!(w & 2)) r1 = rel0 + st * 8;
        if (++st == NSTG) { st = 0; ph ^= 1; }
    }
}

__device__ __forceinline__ uint4* qkv_dst(int layer, int ch, int w, int blk) {
    return g_qkv[layer] + (size_t)((ch * 4 + (w >> 1)) * 32 + ((blk & 63) >> 1)) * 1536 + (blk >> 6) * 512 + (w & 1) * 256;
}
__device__ __forceinline__ uint4* op_dst(int layer, int ch, int slot, int w, uint32_t rank) {
    return g_pp[layer] + (size_t)(ch * MAXSPLIT + slot) * 8192 + (w * 32 + rank * 16) * 32;
}
__device__ __forceinline__ uint32_t ln2(uint32_t x, uint32_t m, uint32_t rh, uint32_t rl) {
    uint32_t d; asm volatile("{.reg .b32 t,u; sub.rn.bf16x2 t,%1,%2; mul.rn.bf16x2 u,t,%4; fma.rn.bf16x2 %0,t,%3,u;}" : "=r"(d) : "r"(x), "r"(m), "r"(rh), "r"(rl)); return d;
}
__device__ __forceinline__ void ldcg128p(uint4& v, const uint4* p, uint32_t on) {
    asm volatile("{.reg .pred p; setp.ne.u32 p,%5,0; @p ld.global.cg.v4.u32 {%0,%1,%2,%3},[%4];}" : "+r"(v.x), "+r"(v.y), "+r"(v.z), "+r"(v.w) : "l"(p), "r"(on) : "memory");
}
__device__ __forceinline__ void qkv_task(uint32_t sb, int w, int layer, int ch, int nu, int& ng, int& nd, uint32_t& ph, int ti, uint32_t zero,
                                         uint4* A, uint32_t& pre, const uint4* xn, const unsigned* dn, unsigned need) {
    constexpr int type = T_QKV;
    static_assert(NSTG == 8, "ring");
    const int lane = threadIdx.x & 31;
    const uint64_t db0 = mkdesc(sb, 4096, 1024, 1);
    const uint32_t rel = (w & 2) ? sb + B_BAR + BB_IDLE * 8 : mapa(sb + B_BAR + BB_EMPTY * 8, w & 1), full = sb + B_BAR + BB_FULL * 8;
    const uint32_t lo = sb + B_OUT + w * 4096 + (lane ^ (lane >> 3)) * 16;
    const uint4* xa = g_xA[layer] + (ch * 8 + w) * 1024 + lane;
    uint32_t m0, m1, h0, h1, l0, l1;
    {
        mbar_wait(full, ph);
        mbar_wait(full + 8, ph);
        CPROF(1);
        const uint32_t sa = sb + (lane >> 4) * STG_B + 16384 + (w * 16 + (lane & 15)) * 8;
        uint2 v[8];
#pragma unroll
        for (int i = 0; i < 8; i++) v[i] = lds64(sa + i * 1024 * layer);
#pragma unroll
        for (int i = 0; i < 4 * QB1; i++) ldcg128p(A[i], xa + i * 32, !pre);
        bar_sync(NB_WG + (w >> 2), 128);
        float sm = 0, M2 = 0, D = 0;
#pragma unroll
        for (int i = 0; i < 8; i++) { sm += __uint_as_float(v[i].x); M2 += __uint_as_float(v[i].y); }
        if (!layer) { sm = __uint_as_float(v[0].x); M2 = __uint_as_float(v[0].y); }
        sm += __shfl_xor_sync(0xffffffffu, sm, 16);
#pragma unroll
        for (int i = 0; i < 8; i++) { const float d = __uint_as_float(v[i].x) * (1.f / 32.f) - sm * (1.f / 512.f); D += 32.f * d * d; }
        M2 += layer ? D : sm * sm * (-1.f / 1024.f);
        M2 = fmaxf(M2 + __shfl_xor_sync(0xffffffffu, M2, 16), 0.f);
        const float2 o = ln_finish(sm * (1.f / 512.f), M2 * (1.f / 512.f));
        const float r = rcp(o.y), rh = rbf(r);
        const uint32_t mm = pack2(o.x, o.x), hl = pack2(r - rh, rh);
        m0 = __shfl_sync(0xffffffffu, mm, lane >> 2); m1 = __shfl_sync(0xffffffffu, mm, (lane >> 2) + 8);
        l0 = __shfl_sync(0xffffffffu, hl, lane >> 2); l1 = __shfl_sync(0xffffffffu, hl, (lane >> 2) + 8);
        h0 = __byte_perm(l0, 0, 0x3232); h1 = __byte_perm(l1, 0, 0x3232); l0 = __byte_perm(l0, 0, 0x1010); l1 = __byte_perm(l1, 0, 0x1010);
    }
    float acc[64];
#define QNRM(i) A[i] = make_uint4(ln2(A[i].x, m0, h0, l0), ln2(A[i].y, m1, h1, l1), ln2(A[i].z, m0, h0, l0), ln2(A[i].w, m1, h1, l1))
#pragma unroll
    for (int h = 0; h < 8; h++) {
        const uint64_t db = db0 + h * (STG_B >> 4);
        const int b0 = h == 0 ? QB1 : h == QB1 ? QB2 : h == QB2 ? QB3 : 8, b1 = h == 0 ? QB2 : h == QB1 ? QB3 : 8;
        if (b0 < b1) {
            const uint4* xb = xa + (A[4 * b0 - 1].x & zero);
#pragma unroll
            for (int i = 4 * b0; i < 4 * b1; i++) { if (b0 < QB3) ldcg128p(A[i], xb + i * 32, !pre); else A[i] = ldcg128(xb + i * 32); }
            bar_sync(NB_WG + (w >> 2), 128);
        }
        QNRM(4 * h); QNRM(4 * h + 1); QNRM(4 * h + 2); QNRM(4 * h + 3);
        if (h == 2 || h == 5) bar_sync(NB_REL + (h == 5) * 2 + (w >> 2), 160);
        if (h) wg_wait<1>();
        wg_fence();
        if (h) wgmma128r<true>(acc, A[4 * h], db); else wgmma128r<false>(acc, A[0], db);
        wgmma128r<true>(acc, A[4 * h + 1], db + 128);
        wgmma128r<true>(acc, A[4 * h + 2], db + 512);
        wgmma128r<true>(acc, A[4 * h + 3], db + 640);
        wg_commit();
        if (h >= 2) mbar_arrive1_cluster(rel + (h - 2) * 8);
    }
    ph ^= 1;
    pre = 0;
#pragma unroll 1
    for (int u = 1;; u++) {
        mbar_wait(sb + B_BAR + (BB_SF + (w >> 2)) * 8, (nd & 1) ^ 1);
        if (u < nu) mbar_wait(full, ph);
        wg_wait<1>();
        mbar_arrive1_cluster(rel + 48);
        wg_wait<0>();
        mbar_arrive1_cluster(rel + 56);
        uint4 o[8];
#pragma unroll
        for (int n = 0; n < 8; n++) {
            const float* a = acc + (n >> 1) * 16 + (n & 1) * 2;
            o[n] = make_uint4(pack2(a[0], a[1]), pack2(a[4], a[5]), pack2(a[8], a[9]), pack2(a[12], a[13]));
            sts128(lo + n * 512, o[n].x, o[n].y, o[n].z, o[n].w);
        }
        __syncwarp();
        mbar_arrive1(sb + B_BAR + (BB_DONE + (w >> 2)) * 8);
        nd++;
        CPROF(min(2 + u, 7));
        if (u == nu) break;
        if (LAGQ) { if (w >> 2) mbar_wait(sb + B_BAR + BB_GO * 8, ng & 1); ng++; }
        unsigned v;
        asm volatile("ld.relaxed.gpu.global.u32 %0,[%1];" : "=r"(v) : "l"(dn) : "memory");
        const uint64_t db1 = mkdesc(sb + (u >> 10), 4096, 1024, 1);
#pragma unroll
        for (int h = 0; h < 8; h++) {
            const uint64_t db = db1 + h * (STG_B >> 4);
            if (h) { mbar_wait(full + h * 8, ph); wg_wait<1>(); }
            if (QPOS == 0) {
            if (h == 2) pre = u + 1 == nu && v >= need;
            if (h >= 2 && h - 2 < QB3) {
#pragma unroll
                for (int i = 4 * (h - 2); i < 4 * (h - 1); i++) ldcg128p(A[i], xn + i * 32, pre);
            }
            }
            wg_fence();
            if (h) wgmma128r<true>(acc, A[4 * h], db); else wgmma128r<false>(acc, A[0], db);
            wgmma128r<true>(acc, A[4 * h + 1], db + 128);
            wgmma128r<true>(acc, A[4 * h + 2], db + 512);
            wgmma128r<true>(acc, A[4 * h + 3], db + 640);
            wg_commit();
            if (h >= 2) mbar_arrive1_cluster(rel + (h - 2) * 8);
            if (h == LAGQ - 1 && w == 2) mbar_arrive1(sb + B_BAR + BB_GO * 8);
            if (QPOS == 1) {
            if (h == 2) pre = u + 1 == nu && v >= need;
            if (h >= 2 && h - 2 < QB3) {
#pragma unroll
                for (int i = 4 * (h - 2); i < 4 * (h - 1); i++) ldcg128p(A[i], xn + i * 32, pre);
            }
            }
        }
        ph ^= 1;
    }
}

template <int NB>
__device__ __forceinline__ void load_resid(uint32_t* r, int layer, int ch, int w, int cb) {
#pragma unroll
    for (int i = 0; i < NB; i++) {
        const uint4 v = ldcg128(g_xA[layer] + ((ch * 8 + w) * 32 + cb + i) * 32 + (threadIdx.x & 31));
        r[4 * i] = v.x; r[4 * i + 1] = v.y; r[4 * i + 2] = v.z; r[4 * i + 3] = v.w;
    }
}
template <int NS>
__device__ __forceinline__ void part_load(uint4* v, int layer, int ch, int w, int cb, int ns) {
    const uint4* src = g_pp[layer] + (size_t)ch * MAXSPLIT * 8192 + (w * 32 + cb) * 32 + (threadIdx.x & 31);
#pragma unroll
    for (int i = 0; i < 2 * NS; i++) {
        asm volatile("{.reg .pred p; .reg .b128 t; setp.gt.s32 p,%6,0; mov.b128 t,{0,0,0,0}; @p ld.relaxed.gpu.global.L2::cache_hint.b128 t,[%4],%5; mov.b128 {%0,%1,%2,%3},t;}"
                     : "=r"(v[i].x), "=r"(v[i].y), "=r"(v[i].z), "=r"(v[i].w) : "l"(src + (i / NS) * 32 + (i % NS) * 8192), "l"(POL_LAST), "r"(ns - i % NS) : "memory");
    }
}
template <int NS>
__device__ __forceinline__ void part_sum(float* x, const uint4* v, const uint32_t* r) {
    const int dg = ((threadIdx.x & 31) >> 2) - 2 * (threadIdx.x & 3);
    const uint32_t idm = dg == 0 ? 0x00003f80u : dg == 1 ? 0x3f800000u : 0u;
#pragma unroll
    for (int b = 0; b < 2; b++) {
        float* y = x + b * 8;
#pragma unroll
        for (int i = 0; i < 8; i++) y[i] = 0;
#pragma unroll
        for (int s = 0; s < NS; s++) { mma8(y, v[b * NS + s].x, v[b * NS + s].y, idm); mma8(y + 4, v[b * NS + s].z, v[b * NS + s].w, idm); }
#pragma unroll
        for (int i = 0; i < 4; i++) { y[2 * i] = rbf(rbf(y[2 * i]) + blo(r[b * 4 + i])); y[2 * i + 1] = rbf(rbf(y[2 * i + 1]) + bhi(r[b * 4 + i])); }
    }
}

__device__ __forceinline__ float4 row_stats32(const float* x) {
    float a = (x[0] + x[1]) + (x[4] + x[5]) + (x[8] + x[9]) + (x[12] + x[13]);
    float b = (x[2] + x[3]) + (x[6] + x[7]) + (x[10] + x[11]) + (x[14] + x[15]);
    a += __shfl_xor_sync(0xffffffffu, a, 1); b += __shfl_xor_sync(0xffffffffu, b, 1);
    a += __shfl_xor_sync(0xffffffffu, a, 2); b += __shfl_xor_sync(0xffffffffu, b, 2);
    const float ma = a * (1.f / 32.f), mb = b * (1.f / 32.f);
    float qa = 0, qb = 0;
#pragma unroll
    for (int i = 0; i < 4; i++) {
        float d0 = x[4 * i] - ma, d1 = x[4 * i + 1] - ma, d2 = x[4 * i + 2] - mb, d3 = x[4 * i + 3] - mb;
        qa += d0 * d0 + d1 * d1; qb += d2 * d2 + d3 * d3;
    }
    qa += __shfl_xor_sync(0xffffffffu, qa, 1); qb += __shfl_xor_sync(0xffffffffu, qb, 1);
    qa += __shfl_xor_sync(0xffffffffu, qa, 2); qb += __shfl_xor_sync(0xffffffffu, qb, 2);
    return make_float4(a, qa, b, qb);
}

__device__ __forceinline__ void conv_stage(float* Y, uint32_t pbase, uint32_t ubase) {
    const int lane = threadIdx.x & 31, w = threadIdx.x >> 5, g = lane >> 2, c = lane & 3;
#pragma unroll
    for (int cp = 0; cp < 2; cp++) {
        const int chl = w * 4 + cp * 2 + (lane >> 4);
        const uint4 b = ldsm4(ubase + chl * 256 + ((lane >> 3) & 1) * 128 + (((lane & 7) ^ (chl & 7)) << 4));
#pragma unroll
        for (int h = 0; h < 2; h++) {
            const uint32_t pa = pbase + ((w * 4 + cp * 2 + h) * PW + 16 + g - 2 * c) * 4;
            uint32_t lo = lds32(pa - 32);
#pragma unroll
            for (int d = 0; d < 8; d++) {
                const uint32_t a0 = lds32(pa + d * 64), a1 = lds32(pa + d * 64 + 32);
                mma16(Y + ((cp * 2 + h) * 8 + d) * 4, a0, a1, lo, a0, h ? b.z : b.x, h ? b.w : b.y);
                lo = a1;
            }
        }
    }
}

__device__ __forceinline__ void conv_combine(const float* y8, float* cur, float* nxt) {
    const int lane = threadIdx.x & 31, c = lane & 3;
    cur[0] = y8[0]; cur[1] = y8[1] + y8[4]; cur[2] = y8[2]; cur[3] = y8[3] + y8[6];
    nxt[0] = y8[29]; nxt[1] = 0.f; nxt[2] = y8[31]; nxt[3] = 0.f;
#pragma unroll
    for (int e = 1; e < 4; e++) {
        const int src = (lane & ~3) | ((c - e) & 3);
        const float v0 = __shfl_sync(0xffffffffu, y8[8 * e] + y8[8 * e - 3], src), v1 = __shfl_sync(0xffffffffu, y8[8 * e + 1] + y8[8 * e + 4], src);
        const float v2 = __shfl_sync(0xffffffffu, y8[8 * e + 2] + y8[8 * e - 1], src), v3 = __shfl_sync(0xffffffffu, y8[8 * e + 3] + y8[8 * e + 6], src);
        if (c >= e) { cur[0] += v0; cur[1] += v1; cur[2] += v2; cur[3] += v3; }
        else { nxt[0] += v0; nxt[1] += v1; nxt[2] += v2; nxt[3] += v3; }
    }
}

__device__ __forceinline__ void hist_task(float* Y, uint32_t sb, int w, int ch, int q, int& st, uint32_t& ph, int nd) {
    const int lane = threadIdx.x & 31, chl = w * 2 + (lane >> 4);
    const uint32_t ua = sb + 12288 + chl * 256 + ((lane >> 3) & 1) * 128 + (((lane & 7) ^ (chl & 7)) << 4);
    const uint32_t pa = sb + (w * 2 * PW + 16 + (lane >> 2) - 2 * (lane & 3)) * 4;
#pragma unroll
    for (int i = 0; i < 128; i++) Y[i] = 0;
    uint4 b1 = make_uint4(0, 0, 0, 0);
#pragma unroll 1
    for (int j = ch + 1; j >= 2; j--) {
        const uint4 b0 = b1;
        mbar_wait(sb + B_BAR + (BB_FULL + st) * 8, ph);
        b1 = ldsm4(ua + st * STG_B);
        if (j == 2) b1 = make_uint4(0, 0, 0, 0);
#pragma unroll
        for (int h = 0; h < 2; h++) {
            const uint32_t o = pa + st * STG_B + h * PW * 4;
            uint32_t lo = lds32(o - 32);
#pragma unroll
            for (int d = 0; d < 8; d++) {
                const uint32_t a0 = lds32(o + d * 64), a1 = lds32(o + d * 64 + 32);
                mma16(Y + (h * 16 + d) * 4, a0, a1, lo, a0, h ? b0.z : b0.x, h ? b0.w : b0.y);
                mma16(Y + (h * 16 + 8 + d) * 4, a0, a1, lo, a0, h ? b1.z : b1.x, h ? b1.w : b1.y);
                lo = a1;
            }
        }
        bar_sync(NB_WG + (w >> 2), 128);
        stage_release(sb, w, st);
        if (++st == NSTG) { st = 0; ph ^= 1; }
    }
    mbar_wait(sb + B_BAR + (BB_SF + (w >> 2)) * 8, (nd & 1) ^ 1);
#pragma unroll
    for (int h = 0; h < 2; h++) {
        const int o = ((ch * 16 + (q >> 1)) * 4 + (w & 1) * 2 + h) * 256 + ((q & 1) * 4 + (w >> 1)) * 32 + lane;
        float c0[4], n0[4], c1[4], n1[4];
        conv_combine(Y + h * 64, c0, n0); conv_combine(Y + h * 64 + 32, c1, n1);
        g_carry[0][o] = make_float4(c0[0], c0[1], c0[2], c0[3]);
        g_carry[0][o + 16384] = make_float4(c1[0] + n0[0], c1[1] + n0[1], c1[2] + n0[2], c1[3] + n0[3]);
        g_carry[1][o + 32768] = make_float4(n1[0], n1[1], n1[2], n1[3]);
    }
}

__device__ __forceinline__ void conv_task(const Params& p, float* Y, uint32_t sb, int w, int ch, int q, int ns, bool dry, int& st, uint32_t& ph, int nd) {
    const int tid = threadIdx.x, lane = tid & 31, g = lane >> 2, c = lane & 3;
    uint32_t dk[4];
    const uint32_t sg = (~ch & 2) << 30;
    int sr = st;
    float x[16];
    PROF(tid == 128, 2048 + ch * 8);
#pragma unroll
    for (int i = 0; i < 128; i++) Y[i] = 0;
#pragma unroll 1
    for (int j = min(ch, 1 + (ch & 1)); j >= 1; j--) {
        mbar_wait(sb + B_BAR + (BB_FULL + st) * 8, ph);
        conv_stage(Y, sb + st * STG_B, sb + B_UT + ((ch - j) & 1) * 8192);
        if (++st == NSTG) { st = 0; ph ^= 1; }
    }
#define CONV_CARRY _Pragma("unroll 1") \
    for (int i = 0; i < min(ch, (ch & 1) ? 2 : 3); i++) { \
        if (i) mbar_wait(sb + B_BAR + (BB_FULL + st) * 8, ph); \
        const uint32_t ca = sb + (i ? st * STG_B : B_SP) + tid * 16; \
_Pragma("unroll") \
        for (int k = 0; k < 4; k++) { \
            const uint4 cr = lds128(ca + k * 4096); \
            Y[k * 32] += __uint_as_float(cr.x); Y[k * 32 + 1] += __uint_as_float(cr.y); Y[k * 32 + 2] += __uint_as_float(cr.z); Y[k * 32 + 3] += __uint_as_float(cr.w); \
        } \
        if (i && ++st == NSTG) { st = 0; ph ^= 1; } \
    } \
    bar_sync(NB_C, 256); \
_Pragma("unroll 1") \
    for (; sr != st; sr = (sr + 1) & (NSTG - 1)) stage_release(sb, w, sr); \
    mbar_wait(sb + B_BAR + (BB_SF + (w >> 2)) * 8, (nd & 1) ^ 1); \
    mbar_wait(sb + B_BAR + (BB_SF + 1 - (w >> 2)) * 8, (nd & 1) ^ 1);
    const uint32_t ut = sb + B_UT + (ch & 1) * 8192;
    if (CPOS == 0) { CONV_CARRY }
    PROF(tid == 128, 2048 + ch * 8 + 7);
    {
        uint4 v[2 * OPS1];
        wait_cnt_warp(cnt_ptr(C_OP0 + (q >> 3) * 2 + (w >> 2), ch + (w & 3) * 16), ns);
        part_load<OPS1>(v, 0, ch, w, 2 * q, ns);
        uint32_t rs[8];
        load_resid<2>(rs, 0, ch, w, 2 * q);
        if (CPOS == 1) { CONV_CARRY }
        part_sum<OPS1>(x, v, rs);
        const float4 s = row_stats32(x);
        float2* dst = g_st2 + ((ch & 1) * 16 + q) * 128 + w * 16 + g + c * 8;
        asm volatile("{.reg .pred p; setp.ne.u32 p,%2,0; @p st.relaxed.gpu.global.b64 [%0],%1;}" ::"l"(dst),
                     "l"(((uint64_t)((__float_as_uint(c ? s.w : s.y) & 0x7fffffffu) | sg) << 32) | __float_as_uint(c ? s.z : s.x)), "r"((uint32_t)(c < 2 && !dry)) : "memory");
        PROF(tid == 128, 2048 + ch * 8 + 1);
    }
#pragma unroll
    for (int i = 0; i < 4; i++) asm volatile("ld.global.nc.u32 %0,[%1];" : "=r"(dk[i]) : "l"(p.Dskip + q * 32 + i * 8 + 2 * c));
    if (CPOS == 2) { CONV_CARRY }
    float2 ln0, ln1;
    {
        const float2* src = g_st2 + ((ch & 1) * 16 + (lane >> 4) * 8) * 128 + w * 16 + (lane & 15);
        uint64_t v[8];
        int n = 0;
#pragma unroll
        for (int i = 0; i < 8; i++) v[i] = (uint64_t)~sg << 32;
        while (true) {
            bool bad = false;
#pragma unroll
            for (int i = 0; i < 8; i++) asm volatile("{.reg .pred p; setp.lt.s32 p,%2,0; @p ld.relaxed.gpu.global.b64 %0,[%1];}" : "+l"(v[i]) : "l"(src + i * 128), "r"((uint32_t)(v[i] >> 32) ^ sg) : "memory");
#pragma unroll
            for (int i = 0; i < 8; i++) bad = bad || (int)((uint32_t)(v[i] >> 32) ^ sg) < 0;
            if (!__any_sync(0xffffffffu, bad && !dry)) break;
            if (++n > 2000000) __trap();
        }
        float sm = 0;
#pragma unroll
        for (int i = 0; i < 8; i++) sm += __uint_as_float((uint32_t)v[i]);
        sm += __shfl_xor_sync(0xffffffffu, sm, 16);
        const float mean = sm * (1.f / 512.f);
        float M2 = 0;
#pragma unroll
        for (int i = 0; i < 8; i++) { const float d = __uint_as_float((uint32_t)v[i]) * (1.f / 32.f) - mean; M2 += fabsf(__uint_as_float((uint32_t)(v[i] >> 32))) + 32.f * d * d; }
        M2 += __shfl_xor_sync(0xffffffffu, M2, 16);
        const float2 o = ln_finish(mean, M2 * (1.f / 512.f));
        ln0.x = __shfl_sync(0xffffffffu, o.x, g); ln0.y = __shfl_sync(0xffffffffu, o.y, g);
        ln1.x = __shfl_sync(0xffffffffu, o.x, g + 8); ln1.y = __shfl_sync(0xffffffffu, o.y, g + 8);
    }
    PROF(tid == 128, 2048 + ch * 8 + 2);
    uint32_t u[8];
#pragma unroll
    for (int i = 0; i < 8; i++) {
        const float2 l = (i & 1) ? ln1 : ln0;
        u[i] = pack2(__fdividef(rbf(x[2 * i] - l.x), l.y), __fdividef(rbf(x[2 * i + 1] - l.x), l.y));
        const int chl = (i >> 1) * 8 + g;
        sts32(ut + chl * 256 + (i & 1) * 128 + ((w ^ g) << 4) + c * 4, movm(u[i]));
    }
    bar_sync(NB_C, 256);
    mbar_wait(sb + B_BAR + (BB_FULL + st) * 8, ph);
    PROF(tid == 128, 2048 + ch * 8 + 3);
    conv_stage(Y, sb + st * STG_B, ut);
    uint32_t yp[4][2];
    float nxt[4][4];
    {
        float y[4][4];
#pragma unroll
        for (int k = 0; k < 4; k++) conv_combine(Y + k * 32, y[k], nxt[k]);
#pragma unroll
        for (int i = 0; i < 4; i++) { yp[i][0] = pack2(y[0][i], y[1][i]); yp[i][1] = pack2(y[2][i], y[3][i]); }
    }
#pragma unroll
    for (int i = 0; i < 4; i++) sts64(sb + B_YT + (16 * (2 * c + (i & 1)) + g + (i >> 1) * 8) * 80 + w * 8, yp[i][0], yp[i][1]);
    bar_sync(NB_C, 256);
    stage_release(sb, w, st);
    if (++st == NSTG) { st = 0; ph ^= 1; }
    PROF(tid == 128, 2048 + ch * 8 + 4);
    uint32_t xo[8];
    uint4* dA = g_xA[1] + ((ch * 8 + w) * 32 + 2 * q) * 32 + lane;
#pragma unroll
    for (int i = 0; i < 8; i++) {
        const int col = (i >> 1) * 8 + 2 * c;
        const uint32_t yv = lds32(sb + B_YT + (w * 16 + g + (i & 1) * 8) * 80 + col * 2);
        const uint32_t dv = dk[i >> 1];
        x[2 * i] = rbf(x[2 * i] + rbf(blo(yv) + rbf(blo(u[i]) * blo(dv))));
        x[2 * i + 1] = rbf(x[2 * i + 1] + rbf(bhi(yv) + rbf(bhi(u[i]) * bhi(dv))));
        xo[i] = pack2(x[2 * i], x[2 * i + 1]);
        if ((i & 3) == 3) dA[(i >> 2) * 32] = make_uint4(xo[i - 3], xo[i - 2], xo[i - 1], xo[i]);
    }
    {
        const float4 s = row_stats32(x);
        float2* dst = g_st[1] + (ch * 16 + q) * 128 + w * 16 + g;
        if (c == 0) dst[0] = make_float2(s.x, s.y);
        if (c == 1) dst[8] = make_float2(s.z, s.w);
        __syncwarp();
    }
    PROF(tid == 128, 2048 + ch * 8 + 5);
    mbar_arrive1(sb + B_BAR + (BB_DONE + (w >> 2)) * 8);
    bar_sync(NB_C, 256);
#pragma unroll
    for (int k = 0; k < 4; k++) sts128(sb + B_SP + k * 4096 + tid * 16, __float_as_uint(nxt[k][0]), __float_as_uint(nxt[k][1]), __float_as_uint(nxt[k][2]), __float_as_uint(nxt[k][3]));
    PROF(tid == 128, 2048 + ch * 8 + 6);
}

__device__ __forceinline__ void out_store(const Params& p, const float* x, int ch, int cb, bool on) {
    const int lane = threadIdx.x & 31, w = threadIdx.x >> 5, g = lane >> 2, c = lane & 3;
#pragma unroll
    for (int h = 0; h < 2; h++) {
        const float* y = x + h * 2;
        uint32_t v0 = pack2(y[0], y[1]), v1 = pack2(y[4], y[5]), v2 = pack2(y[8], y[9]), v3 = pack2(y[12], y[13]);
        uint32_t t0 = (c & 1) ? v0 : v1, t1 = (c & 1) ? v2 : v3;
        t0 = __shfl_xor_sync(0xffffffffu, t0, 1); t1 = __shfl_xor_sync(0xffffffffu, t1, 1);
        if (c & 1) { v0 = t0; v2 = t1; } else { v1 = t0; v3 = t1; }
        t0 = (c & 2) ? v0 : v2; t1 = (c & 2) ? v1 : v3;
        t0 = __shfl_xor_sync(0xffffffffu, t0, 2); t1 = __shfl_xor_sync(0xffffffffu, t1, 2);
        if (c & 2) { v0 = t0; v1 = t1; } else { v2 = t0; v3 = t1; }
        asm volatile("{.reg .pred p; setp.ne.u32 p,%6,0; @p st.global.L2::cache_hint.v4.u32 [%0],{%1,%2,%3,%4},%5;}"
                     ::"l"(p.out + (size_t)(ch * 128 + w * 16 + g + h * 8) * 512 + cb * 16 + c * 8), "r"(v0), "r"(v1), "r"(v2), "r"(v3), "l"(POL_LATE), "r"((uint32_t)on));
    }
}
__device__ __forceinline__ void fin_task(const Params& p, int ch, int cb0, int ncb, int ns, bool dry) {
    const int w = threadIdx.x >> 5;
    uint32_t rs[8];
    wait_cnt_warp(cnt_ptr(C_CV, ch), 32);
    load_resid<2>(rs, 1, ch, w, cb0);
    wait_cnt_warp(cnt_ptr(C_OP1, ch), dry ? 0 : 256);
    for (int cb = cb0; cb < cb0 + ncb; cb += 2) {
        float x[16];
        if (cb != cb0) load_resid<2>(rs, 1, ch, w, cb);
        uint4 v[32];
        part_load<16>(v, 1, ch, w, cb, ns);
        part_sum<16>(x, v, rs);
        out_store(p, x, ch, cb, !dry);
    }
}

__device__ __forceinline__ void bulk_consumer(const Params& p, uint32_t sb, int cl, uint32_t rank, int w) {
    int st = 0; uint32_t ph = 0; int nd = 0, ng = 0;
    for (int ti = 0; ti < MAXT; ti++) {
        const Task t = task_of(p.task[list_of(cl)][ti], rank);
        const int type = t.type, layer = t.layer, ch = t.ch;
        if (type == T_END) break;
        bool staged = type != T_FIN;
        PROF(threadIdx.x == 0, 3600 + ti * 4);
        CPROF(0);
        if (type == T_QKV) {
            staged = false;
            #pragma unroll 1
            while (st) {
                if (!(w & 3)) { mbar_wait(sb + B_BAR + (BB_FULL + st) * 8, ph); stage_release(sb, 0, st); stage_release(sb, 1, st); }
                if (++st == NSTG) { st = 0; ph ^= 1; }
            }
            uint4 A[32];
#pragma unroll
            for (int i = 0; i < 32; i++) A[i] = make_uint4(0, 0, 0, 0);
            uint32_t pre = 0;
            Task c = t;
#pragma unroll 1
            while (true) {
                const Task n = task_of(p.task[list_of(cl)][ti + 1], rank);
                if (w == 3) { sts32(sb + B_ST + 8, ph); bar_arrive(NB_PH, 64); }
                qkv_task(sb, w, c.layer, c.ch, c.b, ng, nd, ph, ti, p.zero, A, pre, g_xA[n.layer] + (n.ch * 8 + w) * 1024 + (threadIdx.x & 31),
                         cnt_ptr(C_CV, n.ch), n.type != T_QKV || !QPRE ? ~0u : n.layer ? 32 : 0);
                PROF(threadIdx.x == 128, 3600 + ti * 4 + 1);
                if (n.type != T_QKV) break;
                PROF(threadIdx.x == 128, 3600 + ti * 4 + 2);
                c = n; ti++;
                PROF(threadIdx.x == 0, 3600 + ti * 4);
                { const int layer = c.layer; CPROF(0); }
            }
        } else if (type == T_OP) {
            const int lane = threadIdx.x & 31;
            float acc[128];
            uint32_t r0 = sb + B_BAR + BB_IDLE * 8, r1 = r0;
            if (w >> 2) { mbar_wait(sb + B_BAR + BB_GO * 8, ng & 1); if ((t.c & 80) == 16) mbar_wait(sb + B_BAR + BB_LOW * 8, 0); }
            ng++;
            gemm_run<false>(acc, sb, w, 0, 1, r0, r1, st, ph);
            gemm_run<true>(acc, sb, w, 1, 2 * t.b, r0, r1, st, ph);
            mbar_wait(sb + B_BAR + (BB_SF + (w >> 2)) * 8, (nd & 1) ^ 1);
            wg_wait<1>();
            mbar_arrive1_cluster(r0);
            wg_wait<0>();
            mbar_arrive1_cluster(r1);
            PROF(threadIdx.x == 128, 3600 + ti * 4 + 1);
            if (t.c & 32) {
                staged = false;
                const int dg = (lane >> 2) - 2 * (lane & 3);
                const uint32_t idm = dg == 0 ? 0x00003f80u : dg == 1 ? 0x3f800000u : 0u;
                wait_cnt_warp(cnt_ptr(C_OP1, ch), 256 - 4 * t.b);
#pragma unroll 1
                for (int i = 0; i < (t.c & 15); i++) {
                    const uint4* src = op_dst(1, ch, i, w, (t.blk >> 2) & 1) + lane;
                    uint4 v[16];
#pragma unroll
                    for (int j = 0; j < 16; j++) v[j] = ldcg128_last(src + j * 32);
#pragma unroll
                    for (int j = 0; j < 16; j++) { mma8(acc + j * 8, v[j].x, v[j].y, idm); mma8(acc + j * 8 + 4, v[j].z, v[j].w, idm); }
                }
#pragma unroll
                for (int j = 0; j < 16; j += 4) {
                    uint32_t rs[16];
                    load_resid<4>(rs, 1, ch, w, (t.blk & 4) * 4 + j);
#pragma unroll
                    for (int i = 0; i < 16; i++) { float* y = acc + j * 8 + 2 * i; y[0] = rbf(y[0]) + blo(rs[i]); y[1] = rbf(y[1]) + bhi(rs[i]); }
                    out_store(p, acc + j * 8, ch, (t.blk & 4) * 4 + j, true); out_store(p, acc + j * 8 + 16, ch, (t.blk & 4) * 4 + j + 2, true);
                }
            } else if (!layer) {
                const int s2 = st + (w >> 1);
                const uint32_t o = sb + (s2 & (NSTG - 1)) * STG_B + (w & 1) * 8192 + lane * 16;
                mbar_wait(sb + B_BAR + (BB_FULL + (s2 & (NSTG - 1))) * 8, ph ^ (s2 >= NSTG));
#pragma unroll
                for (int j = 0; j < 16; j++)
                    sts128(o + j * 512, pack2(acc[j * 8], acc[j * 8 + 1]), pack2(acc[j * 8 + 2], acc[j * 8 + 3]), pack2(acc[j * 8 + 4], acc[j * 8 + 5]), pack2(acc[j * 8 + 6], acc[j * 8 + 7]));
                sts32(sb + B_ST + (w >> 2) * 4, st);
                st += 4;
                if (st >= NSTG) { st -= NSTG; ph ^= 1; }
            } else {
                uint4* dst = op_dst(layer, ch, t.c & 15, w, (t.blk >> 2) & 1) + lane;
#pragma unroll
                for (int n = 0; n < 16; n++) {
                    const int j = (n >> 1) + (n & 1) * 8;
                    const uint4 v = make_uint4(pack2(acc[j * 8], acc[j * 8 + 1]), pack2(acc[j * 8 + 2], acc[j * 8 + 3]), pack2(acc[j * 8 + 4], acc[j * 8 + 5]), pack2(acc[j * 8 + 6], acc[j * 8 + 7]));
                    if (j < 16 - NSB) stg128(dst + j * 32, v, out_pol(T_OP, layer, ch)); else sts128(sb + B_OUT + (w * NSB + j - (16 - NSB)) * 512 + lane * 16, v.x, v.y, v.z, v.w);
                }
            }
        } else if (type == T_CV) {
            float acc[128];
            if (layer) hist_task(acc, sb, w, ch, t.a + rank, st, ph, nd);
            else { conv_task(p, acc, sb, w, ch, t.a + rank, t.b, t.dry, st, ph, nd); staged = false; nd++; }
        } else {
            fin_task(p, ch, t.a + rank * t.c, t.c, t.b, t.dry);
        }
        if (staged) {
            __syncwarp();
            mbar_arrive1(sb + B_BAR + (BB_DONE + (w >> 2)) * 8);
            nd++;
        }
        PROF(threadIdx.x == 128, 3600 + ti * 4 + 2);
        __syncwarp();
    }
}

constexpr int P_Y = 131072  , P_PRM = P_Y  , P_K6 = P_PRM + 8192  ,
              P_P = P_Y + 40960  , P_U = P_P + 33280  , P_END = P_U + 17408, P_X = 98304  ;
static_assert(P_END <= B_BAR && P_END <= R_BAR, "prologue scratch");
#define KGUN 2
constexpr int KGU = KGUN;
__device__ __forceinline__ void csq(float& r, float& i) { const float t = r * i; r = fmaf(r, r, -(i * i)); i = t + t; }
__device__ __forceinline__ void cpow(float ar, float ph, float p, float& r, float& i) {
    const float e = ex2(ar * p);
    const float u = ph * p, n = fabsf(u) < 4194304.f ? (u + 12582912.f) - 12582912.f : u;
    const float t = (u - n) * 6.283185307179586f;
    r = e * __cosf(t); i = e * __sinf(t);
}
__device__ __forceinline__ void mma_tf32(float* c, float a0, float a1, float a2, float a3, float b0, float b1) {
    asm volatile("mma.sync.aligned.m16n8k8.row.col.f32.tf32.tf32.f32 {%0,%1,%2,%3},{%4,%5,%6,%7},{%8,%9},{%0,%1,%2,%3};"
                 : "+f"(c[0]), "+f"(c[1]), "+f"(c[2]), "+f"(c[3])
                 : "r"(__float_as_uint(a0)), "r"(__float_as_uint(a1)), "r"(__float_as_uint(a2)), "r"(__float_as_uint(a3)), "r"(__float_as_uint(b0)), "r"(__float_as_uint(b1)));
}

struct ProRegs { uint32_t v[2][4], ldt[2]; };
__device__ __forceinline__ void prologue_load(const ProArgs& a, int b, ProRegs& pr) {
    const int w = threadIdx.x >> 5;
#pragma unroll
    for (int i = 0; i < 2; i++) {
        const int gi = b * 512 + (w & 3) * 128 + ((w >> 2) & 1) * 64 + i * 32 + (threadIdx.x & 31);
        pr.ldt[i] = __ldg((const uint16_t*)a.ldt + b * 4 + (w & 3));
        pr.v[i][0] = __ldg((const uint16_t*)a.lAr + gi); pr.v[i][1] = __ldg((const uint16_t*)a.Ai + gi);
        pr.v[i][2] = __ldg((const uint16_t*)a.Cr + gi); pr.v[i][3] = __ldg((const uint16_t*)a.Ci + gi);
    }
}
__device__ __forceinline__ void prologue(const ProArgs& a, uint32_t sb, int b, int w, const ProRegs& pr, uint32_t zero) {
    const int tid = threadIdx.x, lane = tid & 31, g = lane >> 2, c = lane & 3;
    const int d0 = b * 4;
    if (w >= 8) {
        const int t2 = tid - 256;
        PROF(t2 == 0, 3516);
        const int gi = b * 128 + t2;
        if (t2 < 32) acc_init(a.mem0, b * 32 + t2);
        if (t2 >= 112) ((uint4*)g_st2)[b * 16 + t2 - 112] = make_uint4(0, 0, 0, 0);
        if (gi < 13 * 64) g_cnt[gi] = 0;
        bar_sync(6, 384);
        if (gi < 512) g_st[0][(gi >> 8) * 2048 + (lds32(sb + S_TAG) ^ 1) * 256 + (gi & 255)] = make_float2(0.f, 0.f);
        asm volatile("{.reg .pred p; elect.sync _|p,0xffffffff; @p cp.async.bulk.prefetch.L2.global [%0],32768;}"
                     ::"l"((w == 8 ? a.Wq : w == 9 ? a.Wk : w == 10 ? a.Wv : a.Wo) + (size_t)b * 16384) : "memory");
        mbar_wait(sb + S_XBAR, 0);
        uint32_t l[16];
        int n = 0;
        while (true) {
            bool ok = true;
#pragma unroll
            for (int i = 0; i < 16; i++) asm volatile("ld.relaxed.gpu.global.u32 %0,[%1];" : "=r"(l[i]) : "l"(g_ln0 + i * 128 + t2) : "memory");
#pragma unroll
            for (int i = 0; i < 16; i++) ok = ok && l[i];
            if (__all_sync(0xffffffffu, ok)) break;
            if (++n > 2000000) __trap();
        }
#pragma unroll 1
        for (int h = 0; h < 2; h++) {
#pragma unroll
            for (int i = 0; i < 8; i++) {
                const int t = h * 1024 + i * 128 + t2;
                const uint2 x = lds64(sb + P_X + t * 16 + (b & 1) * 8);
                const float m = blo(l[i]), rs = rcp(bhi(l[i]));
                l[i] = l[i + 8];
                const uint32_t u0 = pack2(rbf(blo(x.x) - m) * rs, rbf(bhi(x.x) - m) * rs), u1 = pack2(rbf(blo(x.y) - m) * rs, rbf(bhi(x.y) - m) * rs);
                sts128(sb + P_X + t * 16, x.x, x.y, u0, u1);
                const uint32_t o = sb + P_U + ((t >> 3) & 1) * 2176 + ((t >> 4) + 8) * 16 + (t & 7) * 2;
                asm volatile("st.shared.u16 [%0],%1;" ::"r"(o), "h"((uint16_t)u0) : "memory");
                asm volatile("st.shared.u16 [%0],%1;" ::"r"(o + 4352), "h"((uint16_t)(u0 >> 16)) : "memory");
                asm volatile("st.shared.u16 [%0],%1;" ::"r"(o + 8704), "h"((uint16_t)u1) : "memory");
                asm volatile("st.shared.u16 [%0],%1;" ::"r"(o + 13056), "h"((uint16_t)(u1 >> 16)) : "memory");
            }
        }
        PROF(t2 == 0, 3517);
        bar_sync(9, 384);
        fence_async_smem();
#pragma unroll 1
        for (int j = 0; j < 16; j++) {
            const int d = d0 + w - 8;
            asm volatile("{.reg .pred p; elect.sync _|p,0xffffffff; @p cp.async.bulk.global.shared::cta.bulk_group [%0],[%1],%2;}" ::"l"(g_P + (((d >> 5) * 16 + j) * 32 + (d & 31)) * PW),
                         "r"(sb + P_P + ((w - 8) * 2080 + j * 128) * 4), "r"(PW * 4) : "memory");
        }
        asm volatile("cp.async.bulk.commit_group; cp.async.bulk.wait_group 0;" ::: "memory");
        bar_arrive(10, 384);
        return;
    }
#pragma unroll
    for (int i = 0; i < 2; i++) {
        const float dt = rbf(expf(blo(pr.ldt[i])));
        const float ar = -rbf(expf(blo(pr.v[i][0]))) * dt, ai = blo(pr.v[i][1]) * dt;
        sts128(sb + P_PRM + (w * 64 + i * 32 + lane) * 16, __float_as_uint(ar * 1.4426950408889634f), __float_as_uint(ai * 0.15915494309189535f),
               __float_as_uint(2.f * (blo(pr.v[i][2]) * dt)), __float_as_uint(2.f * (blo(pr.v[i][3]) * dt)));
    }
    if (tid < 64) sts128(sb + P_U + (tid >> 3) * 2176 + (tid & 7) * 16, 0, 0, 0, 0);
    bar_arrive(6, 384);
    __syncwarp();
    PROF(tid == 0, 3510);
    const int ch = w & 3, hf = w >> 2;
    {
        float k0[4] = {0, 0, 0, 0}, k1[4] = {0, 0, 0, 0}, k2[4] = {0, 0, 0, 0}, k3[4] = {0, 0, 0, 0}, k4[4] = {0, 0, 0, 0}, kl = 0;
#pragma unroll KGU
        for (int j = 0; j < 16; j++) {
            const uint4 q = lds128(sb + P_PRM + (w * 64 + j * 4 + c) * 16);
            const float cr = __uint_as_float(q.z), ci = __uint_as_float(q.w);
            float wr[4], wi[4], vr[4], vi[4];
            cpow(__uint_as_float(q.x), __uint_as_float(q.y), (float)g, wr[0], wi[0]);
            cpow(__uint_as_float(q.x), __uint_as_float(q.y), (float)(g + 8), vr[0], vi[0]);
#pragma unroll
            for (int i = 1; i < 4; i++) { wr[i] = wr[i - 1]; wi[i] = wi[i - 1]; csq(wr[i], wi[i]); vr[i] = vr[i - 1]; vi[i] = vi[i - 1]; csq(vr[i], vi[i]); }
            float hr = wr[3], hi = wi[3];
            csq(hr, hi);
            mma_tf32(k0, wr[0], vr[0], wi[0], vi[0], cr * hr - ci * hi, -(cr * hi + ci * hr));
            hr = vr[3]; hi = vi[3]; csq(hr, hi);
            mma_tf32(k1, wr[0], vr[0], wi[0], vi[0], cr * hr - ci * hi, -(cr * hi + ci * hr));
            csq(hr, hi);
            mma_tf32(k2, wr[1], vr[1], wi[1], vi[1], cr * hr - ci * hi, -(cr * hi + ci * hr));
            csq(hr, hi);
            mma_tf32(k3, wr[2], vr[2], wi[2], vi[2], cr * hr - ci * hi, -(cr * hi + ci * hr));
            csq(hr, hi);
            mma_tf32(k4, wr[3], vr[3], wi[3], vi[3], cr * hr - ci * hi, -(cr * hi + ci * hr));
            csq(hr, hi);
            kl += cr * hr - ci * hi;
        }
        kl += __shfl_xor_sync(0xffffffffu, kl, 1); kl += __shfl_xor_sync(0xffffffffu, kl, 2);
        const uint32_t o = sb + P_K6 + (ch * 656 + c * 32 + g) * 4, ol = sb + P_K6 + (ch * 656 + 640) * 4;
#define KST(k, base) sts32(o + (base) * 4, __float_as_uint(k[0])); sts32(o + (base) * 4 + 64, __float_as_uint(k[1])); \
                     sts32(o + (base) * 4 + 32, __float_as_uint(k[2])); sts32(o + (base) * 4 + 96, __float_as_uint(k[3]))
#define KAD(k, base) k[0] += __uint_as_float(lds32(o + (base) * 4)); k[1] += __uint_as_float(lds32(o + (base) * 4 + 64)); \
                     k[2] += __uint_as_float(lds32(o + (base) * 4 + 32)); k[3] += __uint_as_float(lds32(o + (base) * 4 + 96))
        if (hf == 0) {
            bar_sync(2 + ch, 64);
            KAD(k0, 0); KAD(k1, 128); KAD(k2, 256); KAD(k3, 384); KAD(k4, 512);
            kl += __uint_as_float(lds32(ol));
            __syncwarp();
        }
        KST(k0, 0); KST(k1, 128); KST(k2, 256); KST(k3, 384); KST(k4, 512);
        if (lane == 0) sts32(ol, __float_as_uint(kl));
        if (hf == 1) { __syncwarp(); bar_arrive(2 + ch, 64); }
    }
    PROF(tid == 0, 3511);
    bar_sync(8, 384);
    PROF(tid == 0, 3512);
    if (tid < 64) sts32(sb + P_P + ((tid >> 4) * 2080 + (tid & 15)) * 4, 0);
#pragma unroll 1
    for (int x = tid; x < 2048; x += 512) {
        uint32_t pw[2][4];
#pragma unroll
        for (int h = 0; h < 2; h++) {
            const int y = x + h * 256;
            const int i0 = y <= 256 ? y : 256 + (int)((pack2((float)y, 0.f) & 0xffff) - 0x4380);
            const int i1 = y <= 256 ? max(y - 1, 0) : 256 + (int)((pack2((float)(y - 1), 0.f) & 0xffff) - 0x4380);
#pragma unroll
            for (int k = 0; k < 4; k++) {
                const float lo = __uint_as_float(lds32(sb + P_K6 + k * 2624 + i0 * 4)), hi = __uint_as_float(lds32(sb + P_K6 + k * 2624 + i1 * 4));
                pw[h][k] = pack2(lo, y ? hi : 0.f);
            }
        }
#pragma unroll
        for (int h = 0; h < 2; h++)
#pragma unroll
            for (int k = 0; k < 4; k++) sts32(sb + P_P + (k * 2080 + x + h * 256 + 16) * 4, pw[h][k]);
    }
    bar_sync(9, 384);
    PROF(tid == 0, 3513);
    {
        float acc[16][4];
#pragma unroll
        for (int j = 0; j < 16; j++) acc[j][0] = acc[j][1] = acc[j][2] = acc[j][3] = 0;
#pragma unroll 1
        for (int e = hf * 4; e < hf * 4 + 4; e++) {
            uint32_t B[16][2];
            const uint32_t ua = sb + P_U + ch * 4352 + ((lane >> 3) & 1) * 2176 + (8 + (lane >> 4) * 8 + (lane & 7) - e) * 16;
            const uint32_t pa = sb + P_P + (ch * 2080 + 16 + e * 16 + g - 2 * c) * 4;
            uint4 A[16];
#define TLD(d) A[d] = make_uint4(lds32(pa + (d) * 512), lds32(pa + (d) * 512 + 32), lds32(pa + (d) * 512 - 32), 0)
            TLD(0); TLD(15);
#pragma unroll
            for (int j = 0; j < 8; j++) { const uint4 v = ldsm4(ua + j * 256); B[2 * j][0] = v.x; B[2 * j][1] = v.y; B[2 * j + 1][0] = v.z; B[2 * j + 1][1] = v.w; }
#pragma unroll
            for (int d = 0; d < 8; d++) {
                if (d < 7) { TLD(d + 1); TLD(14 - d); }
                A[d].w = A[d].x + zero; A[15 - d].w = A[15 - d].x + zero;
                sfence(zero);
#pragma unroll
                for (int j = 15 - d; j < 16; j++) mma16(acc[j], A[15 - d].x, A[15 - d].y, A[15 - d].z, A[15 - d].w, B[j - 15 + d][0], B[j - 15 + d][1]);
#pragma unroll
                for (int j = d; j < 16; j++) { mma16(acc[j], A[d].x, A[d].y, A[d].z, A[d].w, B[j - d][0], B[j - d][1]); sfence(zero); }
            }
        }
        PROF(tid == 0, 3514);
        const uint32_t o = sb + P_Y + (ch * 2560 + c * 40 + g) * 4;
#pragma unroll
        for (int j = 0; j < 8; j++) {
#pragma unroll
            for (int i = 0; i < 4; i++) { const float lo = acc[j][i], hi = acc[j + 8][i]; acc[j][i] = hf ? hi : lo; sts32(o + (j + 8 - hf * 8) * 640 + (i & 1) * 80 + (i >> 1) * 32, __float_as_uint(hf ? lo : hi)); }
        }
        bar_sync(2 + ch, 64);
#pragma unroll
        for (int j = 0; j < 8; j++) {
#pragma unroll
            for (int i = 0; i < 4; i++) acc[j][i] += __uint_as_float(lds32(o + (j + hf * 8) * 640 + (i & 1) * 80 + (i >> 1) * 32));
        }
#pragma unroll
        for (int j = 0; j < 8; j++) {
#pragma unroll
            for (int i = 0; i < 4; i++) sts32(o + (j + hf * 8) * 640 + (i & 1) * 80 + (i >> 1) * 32, __float_as_uint(acc[j][i]));
        }
    }
    const uint2 dk = __ldg((const uint2*)(a.Dk + d0));
    bar_sync(1, 256);
#pragma unroll 2
    for (int i = 0; i < 8; i++) {
        const int t = i * 256 + tid;
        const uint32_t o = sb + P_Y + (t + 4 * (t >> 4)) * 4;
        const uint4 xu = lds128(sb + P_X + t * 16);
        float y[4];
#pragma unroll
        for (int k = 0; k < 4; k++) y[k] = rbf(__uint_as_float(lds32(o + k * 10240)));
        uint2 r;
        r.x = pack2(blo(xu.x) + rbf(y[0] + rbf(blo(xu.z) * blo(dk.x))), bhi(xu.x) + rbf(y[1] + rbf(bhi(xu.z) * bhi(dk.x))));
        r.y = pack2(blo(xu.y) + rbf(y[2] + rbf(blo(xu.w) * blo(dk.y))), bhi(xu.y) + rbf(y[3] + rbf(bhi(xu.w) * bhi(dk.y))));
        {
            const bool up = t & 8;
            const uint32_t o = __shfl_xor_sync(0xffffffffu, up ? r.x : r.y, 8);
            ((uint2*)(g_xA[0] + ((t >> 4) * 32 + (d0 >> 4)) * 32 + (t & 7) * 4 + ((d0 >> 1) & 2) + up))[(d0 >> 3) & 1] = up ? make_uint2(o, r.y) : make_uint2(r.x, o);
        }
        if (i == 0) {
            const float e0 = blo(r.x), e1 = bhi(r.x), e2 = blo(r.y), e3 = bhi(r.y);
            asm volatile("red.relaxed.gpu.global.add.v2.f32 [%0],{%1,%2};" ::"l"(g_st[0] + (t >> 7) * 2048 + lds32(sb + S_TAG) * 256 + (b & 1) * 128 + (t & 127)),
                         "f"((e0 + e1) + (e2 + e3)), "f"((e0 * e0 + e1 * e1) + (e2 * e2 + e3 * e3)) : "memory");
        }
    }
    PROF(tid == 0, 3515);
    bar_sync(10, 384);
}

__global__ void __cluster_dims__(2, 1, 1) __launch_bounds__(384, 1) main_kernel(const __grid_constant__ Params p) {
    extern __shared__ __align__(1024) uint8_t smem[];
    const uint32_t sb = __shfl_sync(0xffffffffu, smem_u32(smem), 0);
    uint32_t rank; asm("mov.u32 %0,%%cluster_ctarank;" : "=r"(rank));
    const int wi = __shfl_sync(0xffffffffu, threadIdx.x >> 5, 0);
    const int cl = blockIdx.x >> 1, wg = wi >> 2;
    const bool rec = p.rec0 >= 0 && cl >= p.rec0 && cl < p.rec0 + 32;
    PROF(threadIdx.x == 0, 3500);
    ProRegs pr;
    if ((wi >> 1) == 4 && p.dopro && cl >= 2) {
        const int g = (threadIdx.x & 31) >> 2, c = threadIdx.x & 3, row = (blockIdx.x - 4) * 16 + (wi - 8) * 8 + g;
        const float4 r4 = row_stats((const uint4*)(p.pa.x + (size_t)row * 512) + c, 4);
        const float2 r = make_float2(r4.x + r4.z, r4.y + r4.w);
        const float2 l = ln_finish(r.x * (1.f / 512.f), fmaxf(r.y - r.x * r.x * (1.f / 512.f), 0.f) * (1.f / 512.f));
        if (c == (g >> 1)) asm volatile("st.relaxed.gpu.global.u32 [%0],%1;" ::"l"(g_ln0 + row), "r"(pack2(l.x, l.y)) : "memory");
        __syncwarp();
    }
    prologue_load(p.pa, max((int)blockIdx.x - 4, 0), pr);
    if (rec) rec_init(p, sb, cl - p.rec0, rank); else bulk_init(sb);
    if (threadIdx.x == 352 && p.dopro && cl >= 2) {
        mbar_init(sb + S_XBAR, 1);
        asm volatile("fence.mbarrier_init.release.cluster;" ::: "memory");
        mbar_expect(sb + S_XBAR, 32768);
        for (int j = 0; j < 8; j++) tma2d(sb + P_X + j * 4096, &p.tm[3], ((blockIdx.x - 4) >> 1) * 8, j * 256, sb + S_XBAR);
    }
    if (threadIdx.x == 320) {
        unsigned v;
        asm volatile("ld.relaxed.gpu.global.u32 %0,[%1];" : "=r"(v) : "l"(g_gate) : "memory");
        v = v / (4 * NCL) + p.dopro;
        sts64(sb + S_GATE, v * (4 * NCL), v & 1);
    }
    __syncwarp();
    asm volatile("barrier.cluster.arrive.relaxed.aligned;" ::: "memory");
    if (wg == 2) bar_arrive(8, 384);
    if (p.dopro && cl >= 2) prologue(p.pa, sb, blockIdx.x - 4, wi, pr, p.zero); else if (wg < 2) bar_sync(8, 384);
    asm volatile("barrier.cluster.wait.aligned;" ::: "memory");
    fence_async_smem();
    bar_sync(wg == 2 ? 7 : 1, wg == 2 ? 128 : 256);
    if (p.dopro && (threadIdx.x == 32 || threadIdx.x == 352)) red_release(g_gate, 1);
    if (rec) {
        if (threadIdx.x == 0) {
            rec_fetch(&p.tm[1], sb + R_STK, (cl - p.rec0) * 128, rank * 256, 2, sb + R_BAR + RB_INIT * 8);
            rec_fetch(&p.tm[2], sb + R_STV, (cl - p.rec0) * 128, rank * 256, 2, sb + R_BAR + RB_INIT * 8);
        }
    }
    PROF(threadIdx.x == 0, 3506);
    __syncwarp();
    if (rec) {
        const int head = cl - p.rec0;
        if (wg == 2) {
            reg_dec<RH>();
            const int w = wi & 3;
            if (threadIdx.x == 256) rec_fetch(&p.tm[0], sb + R_STQ, head * 128, rank * 256, 2, sb + R_BAR + RB_INIT * 8);
            __syncwarp();
            wait_cnt_warp(g_gate, lds32(sb + S_GATE));
            if (p.dostats) x1_stats((head * 2 + rank) * 4 + w);
            __syncthreads();
            cluster_sync();
            if ((p.chains >> (w >> 1)) & 1) rec_attn(p, sb, w >> 1, w & 1, head, rank);
        } else {
            reg_inc<RW0>();
            rec_weights(p, sb, head, rank, wi);
        }
    } else {
        if (wg == 2) {
            reg_dec<40>();
            const int w = wi & 3;
            if (w == 0) bulk_producer(p, sb, cl, rank); else if (w >= 2) bulk_release(p, sb, cl, rank, w - 2); else bulk_relay(p, sb, cl);
        } else { reg_inc<232>(); bulk_consumer(p, sb, cl, rank, wi); }
    }
    __syncwarp();
    cluster_sync();
}

typedef CUresult (*EncFn)(CUtensorMap*, CUtensorMapDataType, cuuint32_t, void*, const cuuint64_t*, const cuuint64_t*, const cuuint32_t*, const cuuint32_t*,
                          CUtensorMapInterleave, CUtensorMapSwizzle, CUtensorMapL2promotion, CUtensorMapFloatOOBfill);
inline uint32_t mk(int type, int layer, int ch, int a, int b, int c) { return type | (layer << 3) | (ch << 4) | (a << 8) | (b << 16) | ((uint32_t)c << 24); }
constexpr int SMEM_BYTES = 232448;

struct Sched {
    Params* P; int n[NCL];
    void clear() { memset(P->task, 0, sizeof(P->task)); memset(n, 0, sizeof(n)); }
    void add(int cl, uint32_t t) { if (n[cl] < MAXT - 1) P->task[list_of(cl)][n[cl]++] = t; }
};

constexpr int REC0 = 4;
struct Cfg { int LAG, TS1, TS2, DQU, DQO, DUN, DHN, MARG, NQ1, FAST0, n0, oc, fc, nuns, ns2, nhg, hs, osl, nfin, dry, tl, c8, o9, lm, hd, DKB, DF; };
#define HALVES 1
#define PLAN 14, 2250, 2850, 2400, 900, 5400, 420, 1000, 4, 0, 12, 10, 14, 6, 4, 8, 8000, 0, 0, 8500, 1500, 12, 3, 1500, 400, 640, 3000
Cfg g_cfg = {PLAN};
double g_est;
bool g_planned = false;
struct Plan { uint32_t w[NCL][MAXT]; int n[NCL]; double end, rec; };
void simulate(Plan& L, int nc, const Cfg& C) {
    const int LAG = C.LAG, NQ1 = C.NQ1, FAST0 = C.FAST0, n0 = C.n0, oc = C.oc, fc = C.fc, nuns = C.nuns, ns2 = C.ns2, nhg = C.nhg;
    const double TS1 = C.TS1, TS2 = C.TS2, DQU = C.DQU, DQO = C.DQO, DUN = C.DUN, DHN = C.DHN, MARG = C.MARG, hs = C.hs;
    const double INF = 1e18, DKB = C.DKB, DOV = 700, DH = DHN, DHO = 1100, DF = C.DF, DFB = 200, POLL = 450, FILL = 500, PUB = 600;
    enum { Q0, O0, Q1, HB, O1, FI, NK };
    struct Grp { int n, left; double done; } G[NK][16];
    double fr[NCL], it[100] = {}, cv[16];
    int ns[16], last[2][NCL], uc = 0, nit = 0;
    memset(L.n, 0, sizeof(L.n)); L.end = 0;
    auto fast = [&](int c) { return c < FAST0 || c >= fc; };
    for (int c = 0; c < 16; c++) {
        ns[c] = c < nuns ? 1 : c == 15 ? 16 : c >= C.c8 ? 8 : ns2;
        const int cnt[NK] = {c < 2 ? 48 : (c & 1) ? 0 : 96, c >= oc ? OPS1 : c >= C.o9 ? 9 : 8, c == 15 ? 24 : fast(c) ? 16 : 48 / NQ1, c >= 2 && !(c & 1) ? 16 : 0, ns[c], c < C.nfin || ns[c] == 1 ? 0 : c >= 14 ? 8 : 4};
        for (int k = 0; k < NK; k++) G[k][c] = {cnt[k], cnt[k], 0};
        cv[c] = INF;
    }
    for (int i = 0; i < nc; i++) { fr[i] = 0; last[0][i] = last[1][i] = -1; }
    auto fin = [&](int k, int c) { if ((k == Q0 && c >= 2) || k == HB) c &= ~1; return G[k][c].left ? INF : G[k][c].done; };
    auto len = [&](int i) { return (i >= LAG && i < 64) ? (double)TS2 : (double)TS1; };
    auto end_it = [&](int i) { return i < nit ? it[i] + len(i) : INF; };
    auto nominal = [&](int i) { if (i < nit) return it[i]; double t = nit ? it[nit - 1] : 11000 - TS1; for (int j = nit - 1; j < i; j++) t += len(j); return t; };
    auto put = [&](int i, uint32_t w) { if (L.n[i] < MAXT - 2) L.w[i][L.n[i]++] = w; else L.end = INF; };
    auto rel = [&](int k, int c) {
        switch (k) {
            case Q0: return 0.0;
            case O0: return end_it(4 * c + 3) + PUB + POLL;
            case Q1: return cv[c] + POLL;
            case HB: return cv[c - 2] + 600 + POLL;
            case O1: return fmax(end_it(LAG + 4 * c + 3) + PUB + POLL, G[O1][c].left == 1 && !G[FI][c].n ? G[O1][c].done - DKB * 64 / ns[c] : 0);
            default: return fin(O1, c) + POLL;
        }
    };
    auto dur = [&](int k, int c) {
        switch (k) {
            case Q0: return DQO + (c < 2 ? 2.0 : 1.0) * DQU;
            case O0: return (16 - G[O0][c].n) * DKB + 1200;
            case HB: return DHO + DH * c;
            case Q1: return DQO + 48.0 / G[Q1][c].n * DQU;
            case O1: return DOV + DKB * 64 / ns[c] + (G[O1][c].left == 1 && !G[FI][c].n ? 700 + 800 * ns[c] : 0);
            default: return DF + DFB * ns[c] * (c >= 14 ? 0.5 : 1);
        }
    };
    auto o0_est = [&](int c) {
        double t = uc ? cv[uc - 1] - 900 : 0;
        for (int j = uc; j < c; j++) t = fmax(t, nominal(4 * j + 4) + PUB + POLL + FILL) + dur(O0, j) + DUN;
        return fmax(t, nominal(4 * c + 4) + PUB + POLL);
    };
    auto cv_est = [&](int c) { return c < uc ? cv[c] : o0_est(c) + FILL + dur(O0, c) + DUN + 900; };
    auto slot = [&](int k, int c, int i) { return k == O0 ? (i < 8 ? i : nc + 7 - i) : c == 15 ? i : i - 8; };
    while (true) {
        while (nit < 64 + LAG) {
            double t = nit ? end_it(nit - 1) : 0;
            if (nit < 64) t = fmax(t, fin(Q0, nit >> 2) + POLL);
            if (nit >= LAG) t = fmax(t, fin(Q1, (nit - LAG) >> 2) + (nit < 64 ? 0 : POLL));
            if (t >= INF) break;
            it[nit++] = t;
        }
        int i = -1;
        for (int j = 0; j < nc; j++) if (fr[j] < INF && (i < 0 || fr[j] < fr[i])) i = j;
        if (i < 0) break;
        const double t = fr[i];
        double lim = INF;
        if (i < 8 && last[0][i] == uc) {
            if (G[O0][uc].left || fin(HB, uc) >= INF) { fr[i] = t + 200; continue; }
            const double e = fmax(G[O0][uc].done, fin(HB, uc) - 2000) + DUN;
            for (int j = 0; j < 8; j++) { put(j, mk(T_CV, 0, uc, 2 * j, G[O0][uc].n, 0)); fr[j] = e; }
            cv[uc++] = e + 900;
            continue;
        }
        const bool hg = (unsigned)(i - 24) < (unsigned)nhg;
        double hlim = INF;
        for (int c = 2; c < 16 && hg; c++) if (G[HB][c].left) { hlim = cv_est(c - 2) + hs - C.hd * c; break; }
        int mine[2] = {-1, -1};
        for (int k = 0; k < 2; k++)
            for (int c = last[k][i] + 1; c < 16 && mine[k] < 0; c++) if ((unsigned)slot(O0 + k, c, i) < (unsigned)G[O0 + k][c].n) mine[k] = c;
        if (mine[0] >= 0) lim = i < 8 ? o0_est(mine[0]) - (uc ? 0 : C.dry) : nominal(4 * mine[0] + 4) + PUB + C.osl;
        else if (mine[1] >= 0) lim = cv_est(mine[1]) + POLL - (mine[1] ? C.lm : 0);
        else if ((i < 16 && G[O1][15].left) || (i < 8 && G[FI][15].left)) lim = fmin(lim, nominal(64 + LAG) + PUB - C.tl);
        int bk = -1, bc = 0; double bd = INF;
        for (int k = 0; k < NK; k++)
            for (int c = 0; c < 16; c++) {
                const bool urgent = k == O0 || k == Q1 || (k >= O1 && c == 15);
                if (!G[k][c].left || ((k == O0 || k == Q1) && c != mine[k - O0]) || (k >= O1 && c == 15 && i >= G[k][c].n)) continue;
                if (rel(k, c) > t || (t + dur(k, c) + (k == Q0 && c >= 2 ? DQU : 0) > lim && !urgent)) continue;
                if (i < 8 && uc && uc < 16 && k != O0) continue;
                if ((k == HB && !hg && i < nc - 2) || (k != HB && !urgent && t + dur(k, c) + (k == Q0 && c >= 2 ? DQU : 0) > hlim)) continue;
                const double dl = urgent ? -INF : k == HB ? -INF / 2 : k == Q0 ? nominal(4 * c) - 3000 : 1e9 + c * 2 + (k == O1);
                if (dl < bd) { bd = dl; bk = k; bc = c; }
            }
        if (bk < 0) {
            bool any = i < 8 && uc < 16;
            for (int k = 0; k < NK; k++) for (int c = 0; c < 16; c++) any = any || G[k][c].left;
            fr[i] = any ? t + 200 : INF;
            if (t > 400000) { L.end = INF; return; }
            continue;
        }
        Grp& g = G[bk][bc];
        const int n = g.n - g.left, c = bc;
        int nu = 1;
        double d = dur(bk, c);
        if (bk == Q0) for (nu = c < 2 ? 2 : 1; c >= 2 && nu < g.left && (nu < 2 || (nu < n0 && t + d + DQU < fmin(fmin(lim, hlim), bd - MARG))); nu++) d += DQU;
        if (bk == O0 && i >= 8) d += (g.n - 8) * DKB;
        if (bk == Q0 && !c && n >= 32) { nu = 1; d -= DQU; }
        if (bk == O0 || bk == Q1) last[bk - O0][i] = c;
        if (bk == O0 && !c && i < 8 && C.dry) put(i, mk(T_CV, 0, 1, 2 * i, 0, 128));
        g.left -= nu;
        const bool fini = bk == O1 && !g.left && !G[FI][c].n;
        const double e = fmax(fmax(t, rel(bk, c) + FILL) + (t < 1 ? 3500 : 0) + d, fini ? g.done + POLL + 700 + 800 * ns[c] : 0);
        fr[i] = e;
        g.done = fmax(g.done, e + (bk == O1 ? (c == 15 ? -500 : 1500) : bk == O0 ? 0 : (bk == Q1 && g.n < 24) || (bk == Q0 && !c && nu == 2) ? -500 : 1000));
        if (bk == FI || fini) L.end = fmax(L.end, e);
        put(i, bk == Q0 ? (c == 0 ? mk(T_QKV, 0, 0, n < 32 ? n : 2 * n - 32, nu, 32) : c == 1 ? mk(T_QKV, 0, c, n, 2, 24) : mk(T_QKV, 0, c, n, nu, 64))
             : bk == O0 ? (i < 8 ? mk(T_OP, 0, c, i * (16 - g.n), 16 - g.n, i) : mk(T_OP, 0, c, 64 - (nc - i) * 8, 8, slot(O0, c, i)))
             : bk == HB ? mk(T_CV, 1, c, 2 * n, 0, 0)
             : bk == Q1 ? mk(T_QKV, 1, c, slot(Q1, c, i) * 2, 48 / g.n, g.n)
             : bk == O1 ? mk(T_OP, 1, c, n * 64 / ns[c], 64 / ns[c], n + (fini ? 32 : c == 15 && HALVES ? 16 : 0))
                        : mk(T_FIN, 1, c, n * (32 / g.n), ns[c], 16 / g.n));
    }
    L.rec = end_it(63 + LAG);
}
void plan(Params& P) {
    P.rec0 = REC0; P.chains = 3; P.lag = g_cfg.LAG; P.dostats = 1; P.dopro = 1;
    static Plan L;
    int cls[NCL], nc = 0;
    for (int c = REC0 + 32; c < NCL; c++) cls[nc++] = c;
    for (int c = REC0 - 1; c >= 0; c--) cls[nc++] = c;
    simulate(L, nc, g_cfg);
    g_est = L.end;
    Sched S; S.P = &P; S.clear();
    for (int i = 0; i < nc; i++) {
        bool warm = false;
        for (int k = 0; k < L.n[i]; k++) {
            if (!warm && k + 1 < L.n[i] && (L.w[i][k + 1] & 255) == (mk(T_FIN, 1, 15, 0, 0, 0) & 255)) { S.add(cls[i], (L.w[i][k + 1] & ~0xff0000u) | 0x80000000u); warm = true; }
            S.add(cls[i], L.w[i][k]);
            if ((L.w[i][k] & 7) == T_FIN) warm = true;
        }
    }
}

#define TK0() do {} while (0)
#define TK() do { P.e0 = (P.chains & 1) ? 64 : 0; P.b1 = (P.chains & 2) ? P.lag : 1000; P.nit = (P.chains & 2) ? P.lag + 64 : 64; TK0(); } while (0)
}

extern "C" void kernel_launch(void* const* d_in, const int* in_sizes, int n_in, void* d_out, int out_size) {
    typedef const __nv_bfloat16* BP;
    static EncFn enc = nullptr;
    if (!enc) {
        void* fn = nullptr; cudaDriverEntryPointQueryResult qr;
        cudaGetDriverEntryPoint("cuTensorMapEncodeTiled", &fn, cudaEnableDefault, &qr);
        enc = (EncFn)fn;
        cudaFuncSetAttribute(main_kernel, cudaFuncAttributeMaxDynamicSharedMemorySize, SMEM_BYTES);
    }
    static Params P;
    for (int i = 0; i < 4; i++) {
        const cuuint64_t cols = i < 3 ? 4096 : 512, rows = i < 3 ? 512 : 4096;
        cuuint64_t d2[2] = {cols, rows}, d3[3] = {64, rows, cols / 64}, str[2] = {cols * 2, 128};
        cuuint32_t box[3] = {64, 64, 4}, es[3] = {1, 1, 1};
        enc(&P.tm[i < 3 ? i : 4], CU_TENSOR_MAP_DATA_TYPE_BFLOAT16, 2, d_in[9 + i], d2, str, box, es, CU_TENSOR_MAP_INTERLEAVE_NONE, CU_TENSOR_MAP_SWIZZLE_128B,
                       CU_TENSOR_MAP_L2_PROMOTION_L2_128B, CU_TENSOR_MAP_FLOAT_OOB_FILL_NONE);
        for (int m = 0; m <= i / 3; m++) {
            cuuint32_t box3[3] = {64, 32, m ? 4u : 2u};
            enc(&P.t3[i + m], CU_TENSOR_MAP_DATA_TYPE_BFLOAT16, 3, d_in[9 + i], d3, str, box3, es, CU_TENSOR_MAP_INTERLEAVE_NONE, CU_TENSOR_MAP_SWIZZLE_128B,
                CU_TENSOR_MAP_L2_PROMOTION_L2_128B, CU_TENSOR_MAP_FLOAT_OOB_FILL_NONE);
        }
    }
    {
        cuuint64_t dims[2] = {512, 2048}, str[1] = {1024};
        cuuint32_t box[2] = {8, 256}, es[2] = {1, 1};
        enc(&P.tm[3], CU_TENSOR_MAP_DATA_TYPE_BFLOAT16, 2, d_in[0], dims, str, box, es, CU_TENSOR_MAP_INTERLEAVE_NONE, CU_TENSOR_MAP_SWIZZLE_NONE,
            CU_TENSOR_MAP_L2_PROMOTION_NONE, CU_TENSOR_MAP_FLOAT_OOB_FILL_NONE);
    }
    for (int m = 0; m < 2; m++) {
        void* ga; cudaGetSymbolAddress(&ga, g_A);
        cuuint64_t dims[2] = {512, sizeof(AOps) / 1024}, str[1] = {1024};
        cuuint32_t box[2] = {256, m ? 16u : 8u}, es[2] = {1, 1};
        enc(&P.ta[m], CU_TENSOR_MAP_DATA_TYPE_BFLOAT16, 2, ga, dims, str, box, es, CU_TENSOR_MAP_INTERLEAVE_NONE, CU_TENSOR_MAP_SWIZZLE_NONE,
            CU_TENSOR_MAP_L2_PROMOTION_L2_128B, CU_TENSOR_MAP_FLOAT_OOB_FILL_NONE);
    }
    P.mem0 = (BP)d_in[8]; P.Wo = (BP)d_in[12]; P.Dskip = (BP)d_in[6]; P.out = (__nv_bfloat16*)d_out;
    cudaStream_t s = cudaStreamPerThread;
    P.pa = {(BP)d_in[0], (BP)d_in[1], (BP)d_in[2], (BP)d_in[3], (BP)d_in[4], (BP)d_in[5], (BP)d_in[6], (BP)d_in[9], (BP)d_in[10], (BP)d_in[11], (BP)d_in[12], (BP)d_in[8]};
    if (!g_planned) { plan(P); g_planned = true; }
    TK(); main_kernel<<<2 * NCL, 384, SMEM_BYTES, s>>>(P); TK();
}
```

```cpp
#include <cuda_runtime.h>
#include <cuda_bf16.h>
#include <cuda.h>
#include <stdint.h>
#include <string.h>
#include <math.h>

#define MAXTN 42
namespace {

constexpr int NCL = 66;
constexpr int NLIST = NCL - 32;
__host__ __device__ inline int list_of(int cl) { return cl < 4 ? cl : cl - 32; }
constexpr int MAXT = MAXTN;
#define PFC 1
#define QB1 2
#define QB2 4
#define QB3 6
#define LAGQ 3
#define CPOS 2
#define QPRE 1
#define QPOS 1
#define OPS1N 10
constexpr int OPS1 = OPS1N;
constexpr int MAXSPLIT = 16;
constexpr int PW = 144;

struct AOps { uint4 x[2][16 * 8 * 1024], o[2][16 * 64 * 1024]; };
__device__ AOps g_A;
#define g_xA g_A.x
#define g_o g_A.o
__device__ float2 g_st[2][16 * 2048];
__device__ float2 g_st2[2 * 16 * 128];
__device__ uint4 g_qkv[2][64 * 64 * 768];
__device__ uint4 g_pp[2][16 * MAXSPLIT * 8192];
__device__ uint4 g_acc[7 * 2048];
__device__ unsigned g_gate[32];
__device__ uint32_t g_P[16 * 16 * 32 * PW];
__device__ uint4 g_u[16 * 16 * 512];
__device__ float4 g_carry[2][17 * 16 * 4 * 256];
__device__ unsigned g_cnt[13 * 64];
__device__ uint32_t g_ln0[2048];

enum { C_QKV0 = 0, C_QKV1 = 1  , C_O0 = 2, C_O1 = 3, C_U = 4, C_OP1 = 5, C_CV = 6, C_ST = 7, C_H = 8, C_OP0 = 9   };
__device__ __forceinline__ unsigned* cnt_ptr(int kind, int chunk) { return g_cnt + kind * 64 + chunk; }

enum { T_END = 0, T_QKV = 1, T_OP = 2, T_CV = 3, T_FIN = 4 };
struct ProArgs { const __nv_bfloat16 *x, *lAr, *Ai, *Cr, *Ci, *ldt, *Dk, *Wq, *Wk, *Wv, *Wo, *mem0; };
struct Params {
    CUtensorMap tm[5];
    CUtensorMap t3[5];
    CUtensorMap ta[2];
    ProArgs pa;
    int dopro;
    const __nv_bfloat16* mem0;
    const __nv_bfloat16* Wo;
    const __nv_bfloat16* Dskip;
    __nv_bfloat16* out;
    int rec0;
    int chains;
    int lag;
    int b1, e0, nit;
    int zero, gpit;
    int dostats;
    uint32_t task[NLIST][MAXT];
};

__device__ __forceinline__ uint32_t smem_u32(const void* p) { return (uint32_t)__cvta_generic_to_shared(p); }
__device__ __forceinline__ uint32_t mapa(uint32_t a, uint32_t r) {
    uint32_t o; asm("mapa.shared::cluster.u32 %0,%1,%2;" : "=r"(o) : "r"(a), "r"(r)); return o;
}
__device__ __forceinline__ void mbar_init(uint32_t b, int c) { asm volatile("mbarrier.init.shared::cta.b64 [%0],%1;" ::"r"(b), "r"(c) : "memory"); }
__device__ __forceinline__ void mbar_expect(uint32_t b, int bytes) { asm volatile("mbarrier.arrive.expect_tx.shared::cta.b64 _,[%0],%1;" ::"r"(b), "r"(bytes) : "memory"); }
__device__ __forceinline__ void mbar_arrive(uint32_t b) { asm volatile("mbarrier.arrive.shared::cta.b64 _,[%0];" ::"r"(b) : "memory"); }
__device__ __forceinline__ void mbar_arrive_cluster(uint32_t b) { asm volatile("mbarrier.arrive.shared::cluster.b64 _,[%0];" ::"r"(b) : "memory"); }
__device__ __forceinline__ void mbar_arrive1(uint32_t b) { asm volatile("{.reg .pred p; elect.sync _|p,0xffffffff; @p mbarrier.arrive.shared::cta.b64 _,[%0];}" ::"r"(b) : "memory"); }
__device__ __forceinline__ void mbar_arrive1_cluster(uint32_t b) { asm volatile("{.reg .pred p; elect.sync _|p,0xffffffff; @p mbarrier.arrive.shared::cluster.b64 _,[%0];}" ::"r"(b) : "memory"); }
__device__ __forceinline__ void mbar_wait(uint32_t b, uint32_t ph) {
    asm volatile(
        "{.reg .pred p; .reg .u32 n; mov.u32 n,0;\n"
        "W%=: mbarrier.try_wait.parity.shared::cta.b64 p,[%0],%1;\n"
        "@p bra D%=;\n"
        "add.u32 n,n,1; setp.lt.u32 p,n,2000000; @p bra W%=;\n"
        "trap;\n"
        "D%=: }" ::"r"(b), "r"(ph) : "memory");
}
__device__ __forceinline__ bool mbar_test(uint32_t b, uint32_t ph) {
    uint32_t ok;
    asm volatile("{.reg .pred p; mbarrier.test_wait.parity.shared::cta.b64 p,[%1],%2; selp.u32 %0,1,0,p;}" : "=r"(ok) : "r"(b), "r"(ph) : "memory");
    return ok;
}
__device__ __forceinline__ bool wait_lds128(uint32_t b, uint32_t ph, uint32_t a, uint4& v) {
    uint32_t ok;
    asm volatile("{.reg .pred p; mbarrier.try_wait.parity.shared::cta.b64 p,[%5],%6,20000; ld.shared.v4.u32 {%0,%1,%2,%3},[%7]; selp.u32 %4,1,0,p;}"
                 : "=r"(v.x), "=r"(v.y), "=r"(v.z), "=r"(v.w), "=r"(ok) : "r"(b), "r"(ph), "r"(a) : "memory");
    return ok;
}
__device__ __forceinline__ bool wait_lds64(uint32_t b, uint32_t ph, uint32_t a, uint2& v) {
    uint32_t ok;
    asm volatile("{.reg .pred p; mbarrier.try_wait.parity.shared::cta.b64 p,[%3],%4,20000; ld.shared.v2.u32 {%0,%1},[%5]; selp.u32 %2,1,0,p;}"
                 : "=r"(v.x), "=r"(v.y), "=r"(ok) : "r"(b), "r"(ph), "r"(a) : "memory");
    return ok;
}
template <int PH> __device__ __forceinline__ void mbar_wait_c(uint32_t b) {
    asm volatile(
        "{.reg .pred p; .reg .u32 n; mov.u32 n,%2;\n"
        "W%=: mbarrier.try_wait.parity.shared::cta.b64 p,[%0],%1;\n"
        "@p bra D%=;\n"
        "add.u32 n,n,1; setp.lt.u32 p,n,2000000; @p bra W%=;\n"
        "trap;\n"
        "D%=: }" ::"r"(b), "n"(PH), "n"(PH) : "memory");
}
__device__ __forceinline__ void bar_sync(int id, int n) { asm volatile("bar.sync %0,%1;" ::"r"(id), "r"(n) : "memory"); }
__device__ __forceinline__ void bar_arrive(int id, int n) { asm volatile("bar.arrive %0,%1;" ::"r"(id), "r"(n) : "memory"); }
__device__ __forceinline__ void cluster_sync() { asm volatile("barrier.cluster.arrive.relaxed.aligned; barrier.cluster.wait.aligned;" ::: "memory"); }
__device__ __forceinline__ void fence_async() { asm volatile("fence.proxy.async;" ::: "memory"); }
__device__ __forceinline__ void fence_async_smem() { asm volatile("fence.proxy.async.shared::cta;" ::: "memory"); }
#define EFR 1
#define EFW 1
constexpr uint64_t POL_N = 0x1000000000000000ull, POL_F = 0x12F0000000000000ull;
constexpr uint64_t POL_LAST = EFR ? POL_F : POL_N  , POL_LATE = EFW ? POL_F : POL_N  , POL_SOON = EFW > 1 ? POL_F : POL_N;
__device__ __forceinline__ void bulk_g2s(uint32_t dst, const void* src, int bytes, uint32_t bar, uint64_t pol) {
    asm volatile("cp.async.bulk.shared::cluster.global.mbarrier::complete_tx::bytes.L2::cache_hint [%0],[%1],%2,[%3],%4;" ::"r"(dst), "l"(src), "r"(bytes), "r"(bar), "l"(pol) : "memory");
}
__device__ __forceinline__ void bulk_g2s_mc(uint32_t dst, const void* src, int bytes, uint32_t bar, uint64_t pol) {
    asm volatile("cp.async.bulk.shared::cluster.global.mbarrier::complete_tx::bytes.multicast::cluster.L2::cache_hint [%0],[%1],%2,[%3],%4,%5;" ::"r"(dst), "l"(src), "r"(bytes), "r"(bar), "h"((uint16_t)3), "l"(pol) : "memory");
}
__device__ __forceinline__ void bulk_s2s(uint32_t dst, uint32_t src, int bytes, uint32_t bar) {
    asm volatile("cp.async.bulk.shared::cluster.shared::cta.mbarrier::complete_tx::bytes [%0],[%1],%2,[%3];" ::"r"(dst), "r"(src), "r"(bytes), "r"(bar) : "memory");
}
__device__ __forceinline__ bool elect() {
    uint32_t r; asm volatile("{.reg .pred p; elect.sync _|p,0xffffffff; selp.u32 %0,1,0,p;}" : "=r"(r)); return r;
}
__device__ __forceinline__ void stg128(uint4* p, uint4 v, uint64_t pol) {
    asm volatile("st.global.L2::cache_hint.v4.u32 [%0],{%1,%2,%3,%4},%5;" ::"l"(p), "r"(v.x), "r"(v.y), "r"(v.z), "r"(v.w), "l"(pol));
}
__device__ __forceinline__ void stg32(uint32_t* p, uint32_t v, uint64_t pol) { asm volatile("st.global.L2::cache_hint.u32 [%0],%1,%2;" ::"l"(p), "r"(v), "l"(pol)); }
__device__ __forceinline__ uint4 ldcg128_last(const uint4* p) {
    uint4 v; asm volatile("ld.global.cg.L2::cache_hint.v4.u32 {%0,%1,%2,%3},[%4],%5;" : "=r"(v.x), "=r"(v.y), "=r"(v.z), "=r"(v.w) : "l"(p), "l"(POL_LAST) : "memory"); return v;
}
__device__ __forceinline__ void tma2d(uint32_t dst, const CUtensorMap* tm, int x, int y, uint32_t bar) {
    asm volatile("cp.async.bulk.tensor.2d.shared::cluster.global.mbarrier::complete_tx::bytes [%0],[%1,{%2,%3}],[%4];" ::"r"(dst), "l"(tm), "r"(x), "r"(y), "r"(bar) : "memory");
}
__device__ __forceinline__ void tma3d_mc(uint32_t dst, const CUtensorMap* tm, int y, int z, uint32_t bar, uint16_t mask) {
    asm volatile("{.reg .pred p; elect.sync _|p,0xffffffff;\n"
                 "@p cp.async.bulk.tensor.3d.shared::cluster.global.mbarrier::complete_tx::bytes.multicast::cluster [%0],[%1,{0,%2,%3}],[%4],%5;}"
                 ::"r"(dst), "l"(tm), "r"(y), "r"(z), "r"(bar), "h"(mask) : "memory");
}
__device__ __forceinline__ void tma2d_mc(uint32_t dst, const CUtensorMap* tm, int x, int y, uint32_t bar, uint16_t mask, uint64_t pol) {
    asm volatile("{.reg .pred p; elect.sync _|p,0xffffffff;\n"
                 "@p cp.async.bulk.tensor.2d.shared::cluster.global.mbarrier::complete_tx::bytes.multicast::cluster.L2::cache_hint [%0],[%1,{%2,%3}],[%4],%5,%6;}"
                 ::"r"(dst), "l"(tm), "r"(x), "r"(y), "r"(bar), "h"(mask), "l"(pol) : "memory");
}
__device__ __forceinline__ void bulk_g2s1(uint32_t dst, const void* src, int bytes, uint32_t bar, uint64_t pol) {
    asm volatile("{.reg .pred p; elect.sync _|p,0xffffffff;\n"
                 "@p cp.async.bulk.shared::cluster.global.mbarrier::complete_tx::bytes.L2::cache_hint [%0],[%1],%2,[%3],%4;}" ::"r"(dst), "l"(src), "r"(bytes), "r"(bar), "l"(pol) : "memory");
}
__device__ __forceinline__ void mbar_expect1(uint32_t b, int bytes) {
    asm volatile("{.reg .pred p; elect.sync _|p,0xffffffff; @p mbarrier.arrive.expect_tx.shared::cta.b64 _,[%0],%1;}" ::"r"(b), "r"(bytes) : "memory");
}
__device__ __forceinline__ void st_async4(uint32_t a, uint32_t x, uint32_t y, uint32_t z, uint32_t w, uint32_t mb) {
    asm volatile("st.async.shared::cluster.mbarrier::complete_tx::bytes.v4.b32 [%0],{%1,%2,%3,%4},[%5];" ::"r"(a), "r"(x), "r"(y), "r"(z), "r"(w), "r"(mb) : "memory");
}
__device__ __forceinline__ void st_async2(uint32_t a, uint32_t x, uint32_t y, uint32_t mb) {
    asm volatile("st.async.shared::cluster.mbarrier::complete_tx::bytes.v2.b32 [%0],{%1,%2},[%3];" ::"r"(a), "r"(x), "r"(y), "r"(mb) : "memory");
}
#define LDSQ "ld.shared"
__device__ __forceinline__ uint4 lds128(uint32_t a) { uint4 v; asm volatile(LDSQ ".v4.u32 {%0,%1,%2,%3},[%4];" : "=r"(v.x), "=r"(v.y), "=r"(v.z), "=r"(v.w) : "r"(a) : "memory"); return v; }
__device__ __forceinline__ uint2 lds64(uint32_t a) { uint2 v; asm volatile(LDSQ ".v2.u32 {%0,%1},[%2];" : "=r"(v.x), "=r"(v.y) : "r"(a) : "memory"); return v; }
__device__ __forceinline__ uint32_t lds32(uint32_t a) { uint32_t v; asm volatile(LDSQ ".u32 %0,[%1];" : "=r"(v) : "r"(a) : "memory"); return v; }
__device__ __forceinline__ void sts128(uint32_t a, uint32_t x, uint32_t y, uint32_t z, uint32_t w) { asm volatile("st.shared.v4.u32 [%0],{%1,%2,%3,%4};" ::"r"(a), "r"(x), "r"(y), "r"(z), "r"(w) : "memory"); }
__device__ __forceinline__ void sts64(uint32_t a, uint32_t x, uint32_t y) { asm volatile("st.shared.v2.u32 [%0],{%1,%2};" ::"r"(a), "r"(x), "r"(y) : "memory"); }
__device__ __forceinline__ void sts32(uint32_t a, uint32_t x) { asm volatile("st.shared.u32 [%0],%1;" ::"r"(a), "r"(x) : "memory"); }
__device__ __forceinline__ uint4 ldsm4(uint32_t a) { uint4 v; asm volatile("ldmatrix.sync.aligned.m8n8.x4.shared.b16 {%0,%1,%2,%3},[%4];" : "=r"(v.x), "=r"(v.y), "=r"(v.z), "=r"(v.w) : "r"(a) : "memory"); return v; }
__device__ __forceinline__ uint4 ldsm4t(uint32_t a) { uint4 v; asm volatile("ldmatrix.sync.aligned.m8n8.x4.trans.shared.b16 {%0,%1,%2,%3},[%4];" : "=r"(v.x), "=r"(v.y), "=r"(v.z), "=r"(v.w) : "r"(a) : "memory"); return v; }
__device__ __forceinline__ uint32_t movm(uint32_t a) { uint32_t d; asm volatile("movmatrix.sync.aligned.m8n8.trans.b16 %0,%1;" : "=r"(d) : "r"(a)); return d; }
__device__ __forceinline__ uint32_t pack2(float lo, float hi) { uint32_t d; asm("cvt.rn.bf16x2.f32 %0,%1,%2;" : "=r"(d) : "f"(hi), "f"(lo)); return d; }
__device__ __forceinline__ uint32_t hadd2(uint32_t a, uint32_t b) { uint32_t d; asm("add.rn.bf16x2 %0,%1,%2;" : "=r"(d) : "r"(a), "r"(b)); return d; }
__device__ __forceinline__ float blo(uint32_t v) { return __uint_as_float(v << 16); }
__device__ __forceinline__ float bhi(uint32_t v) { return __uint_as_float(v & 0xffff0000u); }
__device__ __forceinline__ float rbf(float x) { return __uint_as_float(pack2(0.f, x)); }
__device__ __forceinline__ float ex2(float x) { float y; asm("ex2.approx.ftz.f32 %0,%1;" : "=f"(y) : "f"(x)); return y; }
__device__ __forceinline__ float rcp(float x) { float y; asm("rcp.approx.ftz.f32 %0,%1;" : "=f"(y) : "f"(x)); return y; }
__device__ __forceinline__ void mma16(float* c, uint32_t a0, uint32_t a1, uint32_t a2, uint32_t a3, uint32_t b0, uint32_t b1) {
    asm volatile("mma.sync.aligned.m16n8k16.row.col.f32.bf16.bf16.f32 {%0,%1,%2,%3},{%4,%5,%6,%7},{%8,%9},{%0,%1,%2,%3};"
                 : "+f"(c[0]), "+f"(c[1]), "+f"(c[2]), "+f"(c[3]) : "r"(a0), "r"(a1), "r"(a2), "r"(a3), "r"(b0), "r"(b1));
}
__device__ __forceinline__ void mma8(float* c, uint32_t a0, uint32_t a1, uint32_t b0) {
    asm volatile("mma.sync.aligned.m16n8k8.row.col.f32.bf16.bf16.f32 {%0,%1,%2,%3},{%4,%5},{%6},{%0,%1,%2,%3};"
                 : "+f"(c[0]), "+f"(c[1]), "+f"(c[2]), "+f"(c[3]) : "r"(a0), "r"(a1), "r"(b0));
}
__device__ __forceinline__ uint4 ld_rlx128(const uint4* p) {
    uint4 v;
    asm volatile("{.reg .b128 t; ld.relaxed.gpu.global.b128 t,[%4]; mov.b128 {%0,%1,%2,%3},t;}" : "=r"(v.x), "=r"(v.y), "=r"(v.z), "=r"(v.w) : "l"(p) : "memory");
    return v;
}
__device__ __forceinline__ void st_rlx128(uint4* p, uint32_t x, uint32_t y, uint32_t z, uint32_t w) {
    asm volatile("{.reg .b128 t; mov.b128 t,{%1,%2,%3,%4}; st.relaxed.gpu.global.b128 [%0],t;}" ::"l"(p), "r"(x), "r"(y), "r"(z), "r"(w) : "memory");
}
__device__ __forceinline__ uint4 ldcg128(const uint4* p) { uint4 v; asm volatile("ld.global.cg.v4.u32 {%0,%1,%2,%3},[%4];" : "=r"(v.x), "=r"(v.y), "=r"(v.z), "=r"(v.w) : "l"(p) : "memory"); return v; }
__device__ __forceinline__ void red_release(unsigned* p, unsigned v) {
    asm volatile("fence.proxy.async; red.relaxed.gpu.global.add.u32 [%0],%1;" ::"l"(p), "r"(v) : "memory");
}
__device__ __forceinline__ void wait_cnt(const unsigned* p, unsigned target) {
    unsigned v; int n = 0;
    while (true) {
        asm volatile("ld.acquire.gpu.global.u32 %0,[%1];" : "=r"(v) : "l"(p) : "memory");
        if (v >= target) break;
        if (++n > 3000000) __trap();
        __nanosleep(40);
    }
}
__device__ __forceinline__ void wait_cnt_warp(const unsigned* p, unsigned target) {
    unsigned v; int n = 0;
    while (true) {
        asm volatile("ld.acquire.gpu.global.u32 %0,[%1];" : "=r"(v) : "l"(p) : "memory");
        if (__all_sync(0xffffffffu, v >= target)) break;
        if (++n > 3000000) __trap();
    }
}
__device__ __forceinline__ uint64_t mkdesc(uint32_t addr, uint32_t lbo, uint32_t sbo, uint32_t sw) {
    return (uint64_t)((addr & 0x3FFFF) >> 4) | ((uint64_t)(lbo >> 4) << 16) | ((uint64_t)(sbo >> 4) << 32) | ((uint64_t)sw << 62);
}
__device__ __forceinline__ void wg_fence() { asm volatile("wgmma.fence.sync.aligned;" ::: "memory"); }
__device__ __forceinline__ void wg_commit() { asm volatile("wgmma.commit_group.sync.aligned;" ::: "memory"); }
template <int N> __device__ __forceinline__ void wg_wait() { asm volatile("wgmma.wait_group.sync.aligned %0;" ::"n"(N) : "memory"); }
#define R8(c, o) "+f"(c[o]), "+f"(c[o + 1]), "+f"(c[o + 2]), "+f"(c[o + 3]), "+f"(c[o + 4]), "+f"(c[o + 5]), "+f"(c[o + 6]), "+f"(c[o + 7])
#define R32(c, o) R8(c, o), R8(c, o + 8), R8(c, o + 16), R8(c, o + 24)
#define S32A "%0,%1,%2,%3,%4,%5,%6,%7,%8,%9,%10,%11,%12,%13,%14,%15,%16,%17,%18,%19,%20,%21,%22,%23,%24,%25,%26,%27,%28,%29,%30,%31"
#define S32B ",%32,%33,%34,%35,%36,%37,%38,%39,%40,%41,%42,%43,%44,%45,%46,%47,%48,%49,%50,%51,%52,%53,%54,%55,%56,%57,%58,%59,%60,%61,%62,%63"
#define S32C ",%64,%65,%66,%67,%68,%69,%70,%71,%72,%73,%74,%75,%76,%77,%78,%79,%80,%81,%82,%83,%84,%85,%86,%87,%88,%89,%90,%91,%92,%93,%94,%95"
#define S32D ",%96,%97,%98,%99,%100,%101,%102,%103,%104,%105,%106,%107,%108,%109,%110,%111,%112,%113,%114,%115,%116,%117,%118,%119,%120,%121,%122,%123,%124,%125,%126,%127"
#define W8(c, o) "=f"(c[o]), "=f"(c[o + 1]), "=f"(c[o + 2]), "=f"(c[o + 3]), "=f"(c[o + 4]), "=f"(c[o + 5]), "=f"(c[o + 6]), "=f"(c[o + 7])
#define W32(c, o) W8(c, o), W8(c, o + 8), W8(c, o + 16), W8(c, o + 24)
template <bool ACC> __device__ __forceinline__ void wgmma256(float* c, uint64_t da, uint64_t db) {
    if (ACC) asm volatile("wgmma.mma_async.sync.aligned.m64n256k16.f32.bf16.bf16 {" S32A S32B S32C S32D "},%128,%129,1,1,1,0,1;"
                          : R32(c, 0), R32(c, 32), R32(c, 64), R32(c, 96) : "l"(da), "l"(db));
    else asm volatile("wgmma.mma_async.sync.aligned.m64n256k16.f32.bf16.bf16 {" S32A S32B S32C S32D "},%128,%129,0,1,1,0,1;"
                      : W32(c, 0), W32(c, 32), W32(c, 64), W32(c, 96) : "l"(da), "l"(db));
}
template <bool ACC> __device__ __forceinline__ void wgmma128r(float* c, const uint4& a, uint64_t db) {
    if (ACC) asm volatile("wgmma.mma_async.sync.aligned.m64n128k16.f32.bf16.bf16 {" S32A S32B "},{%64,%65,%66,%67},%68,1,1,1,1;"
                          : R32(c, 0), R32(c, 32) : "r"(a.x), "r"(a.y), "r"(a.z), "r"(a.w), "l"(db));
    else asm volatile("wgmma.mma_async.sync.aligned.m64n128k16.f32.bf16.bf16 {" S32A S32B "},{%64,%65,%66,%67},%68,0,1,1,1;"
                      : W32(c, 0), W32(c, 32) : "r"(a.x), "r"(a.y), "r"(a.z), "r"(a.w), "l"(db));
}
template <int N> __device__ __forceinline__ void reg_inc() { asm volatile("setmaxnreg.inc.sync.aligned.u32 %0;" ::"n"(N)); }
template <int N> __device__ __forceinline__ void reg_dec() { asm volatile("setmaxnreg.dec.sync.aligned.u32 %0;" ::"n"(N)); }

#define PROF(cond, idx) do {} while (0)
#define CPROF(k) do {} while (0)

constexpr int S_GATE = 232440, S_TAG = 232444, S_XBAR = 232432;
constexpr float SC_LOG2E = 0.08838834764831845f * 1.4426950408889634f;

__device__ __forceinline__ float2 ln_finish(float mean, float var) {
    float sd; asm("sqrt.approx.f32 %0,%1;" : "=f"(sd) : "f"(rbf(rbf(var) + 1e-5f)));
    sd = rbf(sd);
    return make_float2(rbf(mean), sd);
}

__device__ __forceinline__ float4 row_stats(const uint4* src, int stride) {
    const int g = (threadIdx.x & 31) >> 2;
    uint4 v[16];
#pragma unroll
    for (int i = 0; i < 16; i++) v[i] = ldcg128(src + i * stride);
    float a[4] = {0, 0, 0, 0}, q0[4] = {0, 0, 0, 0}, q1[4] = {0, 0, 0, 0}, q2[4] = {0, 0, 0, 0}, q3[4] = {0, 0, 0, 0};
#pragma unroll
    for (int i = 0; i < 16; i++) {
        mma16(a, v[i].x, v[i].y, v[i].z, v[i].w, 0x3f803f80u, 0x3f803f80u);
        mma8(q0, v[i].x, v[i].y, v[i].x); mma8(q1, v[i].x, v[i].y, v[i].y);
        mma8(q2, v[i].z, v[i].w, v[i].z); mma8(q3, v[i].z, v[i].w, v[i].w);
    }
    return make_float4(a[0], (g & 1) ? q0[1] + q2[1] : q0[0] + q2[0], a[2], (g & 1) ? q1[3] + q3[3] : q1[2] + q3[2]);
}
__device__ __forceinline__ void x1_stats(int i) {
    const int lane = threadIdx.x & 31, g = lane >> 2, c = lane & 3;
    const float4 r = row_stats(g_xA[0] + i * 512 + lane, 32);
    float2* dst = g_st[0] + (i >> 4) * 2048 + ((i < 32 ? 4 : 0) + (i & 1)) * 128 + ((i >> 1) & 7) * 16 + g;
    if (c == (g >> 1)) { dst[0] = make_float2(r.x, r.y); dst[8] = make_float2(r.z, r.w); g_ln0[i * 8 + g] = 0; }
    __syncwarp();
    if (lane == 0) red_release(cnt_ptr(C_ST, i >> 4), 1);
}
__global__ void stats_kernel() { x1_stats(blockIdx.x * 4 + (threadIdx.x >> 5)); }

#define NT 9
#define RH 104
#define RW0 200
#define NPD 9
#define NTO 12
#define DP1 9
#define GPW 0
#define GPJ 0
#define PACE 2
#define EARLY 4
#define G2I 4
#define VE 4
#define VF 8
constexpr int R_WV = 0, R_WO = 65536, R_T = 131072, R_M = R_T + 20480, R_LOC = R_M + 4096, R_REM = R_LOC + 6144, R_O = R_REM + 12288, R_SX = R_O + 2048,
              R_IL = R_SX + 5120, XS = R_IL + 128 - R_T, R_BAR = 231936, R_Z = R_BAR + 128  , R_STQ = 0, R_STK = 65536, R_STV = 131072;
static_assert(R_T + 2 * XS <= R_BAR && R_BAR + 256 <= S_XBAR, "smem map");
enum { RB_INIT = 0, RB_V = 4  , RB_QK = 8  , RB_T = 12  , RB_N = 16 };
enum { NB_MF = 1  , NB_LOC = 3  , NB_PAIR = 5  , NB_O = 9  , NB_XG = 11  , NB_W = 13 };
__device__ __forceinline__ uint32_t clk32() { return (uint32_t)clock64(); }

__device__ __forceinline__ char* acc_base() { return (char*)(((size_t)g_acc + 131071) & ~(size_t)131071); }
__device__ __forceinline__ uint32_t acc_slice(uint32_t s6) { return (s6 & 1) * 256 + (s6 >> 1) * 1024; }
__device__ __forceinline__ uint32_t acc_main(uint32_t rank, uint32_t tid) { return acc_slice(rank * 32 + (tid >> 3)) + (tid & 7) * 16; }
__device__ __forceinline__ uint32_t acc_extra(uint32_t rank, uint32_t tid) { return 65536 + acc_slice(((tid >> 5) & 1) + rank * 4 + (tid >> 6) * 8) + (tid & 31) * 4; }
__device__ __forceinline__ uint32_t acc_slot(uint32_t it) { return ((it ^ (it >> 1)) & 1) * 128 + (it & 2) * 256; }
__device__ __forceinline__ void acc_init(const __nv_bfloat16* mem0, int i, int lag) {
    const uint32_t tid = i & 255, rank = (i >> 8) & 1, slot = (i >> 9) & 3, X = i >> 11;
    uint32_t v[5] = {0, 0, 0, 0, 0};
    if (slot == ((X * lag + 3) & 3)) {
        const uint16_t* m = (const uint16_t*)mem0 + (tid & 3) * 1024 + rank * 256 + (tid >> 5) * 32 + ((tid >> 2) & 7);
#pragma unroll
        for (int k = 0; k < 4; k++) v[k] = __ldg(m + k * 8) | ((uint32_t)__ldg(m + k * 8 + 512) << 16);
        v[4] = (v[3] >> 16) | 0x42000000u; v[3] = (v[3] & 0xffff) | 0x42000000u;
    }
    *(uint4*)(acc_base() + X * 32768 + acc_slot(slot) + acc_main(rank, tid)) = make_uint4(v[0], v[1], v[2], v[3]);
    *(uint32_t*)(acc_base() + X * 1024 + acc_slot(slot) + acc_extra(rank, tid)) = v[4];
}
__global__ void acc_init_kernel(const __nv_bfloat16* mem0, int lag) { acc_init(mem0, blockIdx.x * 256 + threadIdx.x, lag); }

struct RecW { uint32_t am, ae, ah, dp, lp, lpw, vo, sb, bar, zero, ts, tn; };
__device__ __forceinline__ uint32_t vadd(uint32_t a, uint32_t b) { uint32_t d; asm volatile("add.u32 %0,%1,%2;" : "=r"(d) : "r"(a), "r"(b)); return d; }
__device__ __forceinline__ uint32_t vshr(uint32_t a, int n) { uint32_t d; asm volatile("shr.u32 %0,%1,%2;" : "=r"(d) : "r"(a), "r"(n)); return d; }
__device__ __forceinline__ uint64_t gptr(uint32_t lo, uint32_t hi) { uint64_t d; asm("mov.b64 %0,{%1,%2};" : "=l"(d) : "r"(lo), "r"(hi)); return d; }
__device__ __forceinline__ void sfence(uint32_t zero) { asm volatile("{.reg .pred p; setp.ne.u32 p,%0,0; @p exit;}" ::"r"(zero) : "memory"); }
#define SF sfence(k.zero)
#define TS(i) do {} while (0)
#define TSN(i) do {} while (0)
#define TSET(it, slot) do {} while (0)
struct Gat { uint32_t x, y, z, w, e; };
template <int X>
__device__ __forceinline__ void gat_issue(Gat& g, const RecW& k, uint32_t dep) {
    asm volatile("{.reg .b128 t; ld.relaxed.gpu.global.b128 t,[%5+%7]; mov.b128 {%0,%1,%2,%3},t; ld.relaxed.gpu.global.u32 %4,[%6+%8];}"
                 : "=r"(g.x), "=r"(g.y), "=r"(g.z), "=r"(g.w), "=r"(g.e) : "l"(gptr(k.am + dep, k.ah)), "l"(gptr(k.ae + dep, k.ah)), "n"(X * 32768), "n"(X * 1024) : "memory");
}
template <int X>
__device__ __forceinline__ bool gat_store(const Gat& g, const RecW& k) {
    uint32_t c;
    asm volatile("prmt.b32 %0,%1,%2,0x7632;" : "=r"(c) : "r"(g.w), "r"(g.e));
    SF;
    asm volatile("{.reg .b32 t; prmt.b32 t,%4,%6,0x5410; stmatrix.sync.aligned.m8n8.x4.trans.shared.b16 [%0+%5],{%1,%2,%3,t};}" ::"r"(k.lpw), "r"(g.x), "r"(g.y), "r"(g.z), "r"(g.w), "n"(R_M + X * XS), "r"(g.e) : "memory");
    return __all_sync(0xffffffffu, c == 0x42004200u);
}
template <int X>
__device__ __forceinline__ void gat_finish(bool ok, const RecW& k) {
    if (!ok) {
        int n = 0;
        while (true) {
            Gat g;
            gat_issue<X>(g, k, n & k.zero);
            if (gat_store<X>(g, k)) break;
            if (++n > 2000000) __trap();
        }
    }
    bar_sync(NB_MF + X, 256);
}
__device__ __forceinline__ uint4 lds128o(uint32_t a, int o) { uint4 v; asm volatile("{.reg .b32 t; add.u32 t,%4,%5; ld.shared.v4.u32 {%0,%1,%2,%3},[t];}" : "=r"(v.x), "=r"(v.y), "=r"(v.z), "=r"(v.w) : "r"(a), "r"(o) : "memory"); return v; }
__device__ __forceinline__ uint4 ldsm4o(uint32_t a, int o) { uint4 v; asm volatile("{.reg .b32 t; add.u32 t,%4,%5; ldmatrix.sync.aligned.m8n8.x4.shared.b16 {%0,%1,%2,%3},[t];}" : "=r"(v.x), "=r"(v.y), "=r"(v.z), "=r"(v.w) : "r"(a), "r"(o) : "memory"); return v; }
__device__ __forceinline__ uint4 ldsm4to(uint32_t a, int o) { uint4 v; asm volatile("{.reg .b32 t; add.u32 t,%4,%5; ldmatrix.sync.aligned.m8n8.x4.trans.shared.b16 {%0,%1,%2,%3},[t];}" : "=r"(v.x), "=r"(v.y), "=r"(v.z), "=r"(v.w) : "r"(a), "r"(o) : "memory"); return v; }
__device__ __forceinline__ uint2 lds64o(uint32_t a, int o) { uint2 v; asm volatile("{.reg .b32 t; add.u32 t,%2,%3; ld.shared.v2.u32 {%0,%1},[t];}" : "=r"(v.x), "=r"(v.y) : "r"(a), "r"(o) : "memory"); return v; }
__device__ __forceinline__ void sts128o(uint32_t a, int o, uint32_t x, uint32_t y, uint32_t z, uint32_t w) { asm volatile("{.reg .b32 t; add.u32 t,%0,%5; st.shared.v4.u32 [t],{%1,%2,%3,%4};}" ::"r"(a), "r"(x), "r"(y), "r"(z), "r"(w), "r"(o) : "memory"); }
__device__ __forceinline__ void sts64o(uint32_t a, int o, uint32_t x, uint32_t y) { asm volatile("{.reg .b32 t; add.u32 t,%0,%3; st.shared.v2.u32 [t],{%1,%2};}" ::"r"(a), "r"(x), "r"(y), "r"(o) : "memory"); }
__device__ __forceinline__ uint32_t vxor(uint32_t a, uint32_t b) { uint32_t d; asm volatile("xor.b32 %0,%1,%2;" : "=r"(d) : "r"(a), "r"(b)); return d; }
#define WLD(base, i) wt[i] = lds128o(k.lpw, (base) + (i) * 4096)
template <int PASS, int X, int NP>
__device__ __forceinline__ void rec_qkv(const RecW& k, int s, const uint32_t (*wq)[4], const uint32_t (*wk)[4], uint4* wt, Gat& g2, uint4 mf) {
    constexpr bool BWD = PASS == 2;
    float aq[4] = {0, 0, 0, 0}, ak[4] = {0, 0, 0, 0}, av[4] = {0, 0, 0, 0};
    constexpr int ma = R_M + X * XS;
    if (BWD) { TS(1); gat_finish<1>(gat_store<1>(g2, k), k); mf = ldsm4o(k.lp, ma + 7 * 512); }
    if (BWD) TS(2); else { TS(0); TSN(13); }
    uint32_t ra, rb;
#pragma unroll
    for (int ii = 0; ii < 8; ii++) {
        const int i = BWD ? 7 - ii : ii;
        const uint4 m = mf;
        if (ii < 7) mf = ldsm4o(k.lp, ma + (BWD ? i - 1 : i + 1) * 512);
        else { ra = vadd(k.lpw, k.dp + R_REM + X * XS + (s & 1) * 6144); rb = (ra & k.zero) + (k.bar + X * 16); }
        if (PASS == 1 && ii == G2I) gat_issue<1>(g2, k, 0);
        SF;
#pragma unroll
        for (int hh = 0; hh < 2; hh++) {
            const int h = BWD ? 1 - hh : hh, ks = 2 * i + h;
            const uint32_t b0 = h ? m.z : m.x, b1 = h ? m.w : m.y;
            mma16(aq, wq[ks][0], wq[ks][1], wq[ks][2], wq[ks][3], b0, b1);
            mma16(ak, wk[ks][0], wk[ks][1], wk[ks][2], wk[ks][3], b0, b1);
            SF;
            mma16(av, wt[ks].x, wt[ks].y, wt[ks].z, wt[ks].w, b0, b1);
            SF;
            if (!BWD && ks + NP < 16) WLD(R_WV, ks + NP < 16 ? ks + NP : 0);
            if (BWD && ks >= NT) WLD(R_WV, ks >= NT ? ks - NT : 0);
            SF;
        }
    }
    const uint32_t x0 = movm(pack2(aq[0], aq[1])), x1 = movm(pack2(aq[2], aq[3])), x2 = movm(pack2(ak[0], ak[1])), x3 = movm(pack2(ak[2], ak[3]));
    SF;
    asm volatile("stmatrix.sync.aligned.m8n8.x2.shared.b16 [%0+%3],{%1,%2};" ::"r"(k.vo), "r"(pack2(av[0], av[1])), "r"(pack2(av[2], av[3])), "n"(R_LOC + X * XS) : "memory");
    SF;
    st_async4(ra, x0, x1, x2, x3, rb);
    asm volatile("st.shared.v4.u32 [%0+%5],{%1,%2,%3,%4};" ::"r"(k.lpw), "r"(x0), "r"(x1), "r"(x2), "r"(x3), "n"(R_LOC + X * XS) : "memory");
    bar_arrive(NB_LOC + X, 320);
    SF;
    TS(BWD ? 4 : 3);
}
template <bool BWD, int X>
__device__ __forceinline__ void rec_out(const RecW& k, uint4* wt, Gat& g) {
    if (BWD) { WLD(R_WO, 17 - NTO); WLD(R_WO, 16 - NTO); }
    TS(BWD ? 8 : 5);
    bar_sync(NB_O + X, 320);
    float r0[4] = {0, 0, 0, 0}, r1[4] = {0, 0, 0, 0};
    constexpr int oa = R_O + X * XS;
    uint4 bn = lds128o(k.lp, oa + (BWD ? 3 : 0) * 512);
    TS(BWD ? 9 : 6);
    uint2 il;
    uint64_t pm, pe;
#pragma unroll
    for (int ii = 0; ii < 4; ii++) {
        const int i = BWD ? 3 - ii : ii;
        const uint4 b = bn;
        if (ii < 3) bn = lds128o(k.lp, oa + (BWD ? i - 1 : i + 1) * 512);
        else { asm volatile("ld.shared.v2.u32 {%0,%1},[%2+%3];" : "=r"(il.x), "=r"(il.y) : "r"((vshr(k.ae, 2) & 3) * 8 + k.sb), "n"(R_IL + X * XS) : "memory"); pm = gptr(vadd(k.am, 0), k.ah); pe = gptr(vadd(k.ae, 0), k.ah); }
        SF;
        if (BWD && EARLY == ii + 1) { gat_issue<0>(g, k, 0); SF; }
#pragma unroll
        for (int nn = 0; nn < 4; nn++) {
            const int n = BWD ? 3 - nn : nn, f = 4 * i + n, nx = BWD ? f - NTO + 2 : f + NTO - 2;
            mma16((n & 1) ? r1 : r0, wt[f].x, wt[f].y, wt[f].z, wt[f].w, n >> 1 ? b.z : b.x, n >> 1 ? b.w : b.y);
            SF;
            if (ii * 4 + nn >= 2 && nx >= 0 && nx < 16) WLD(R_WO, nx & 15);
            SF;
        }
    }
    const float i0 = __uint_as_float(il.x), i1 = __uint_as_float(il.y);
    asm volatile("red.relaxed.gpu.global.add.noftz.v4.bf16x2 [%0+%5],{%1,%2,%3,%4};" ::"l"(pm),
                 "r"(pack2(r0[0] * i0, r0[1] * i1)), "r"(pack2(r0[2] * i0, r0[3] * i1)), "r"(pack2(r1[0] * i0, r1[1] * i1)), "r"(pack2(r1[2] * i0, 1.f)), "n"(X * 32768) : "memory");
    asm volatile("red.relaxed.gpu.global.add.noftz.bf16x2 [%0+%2],%1;" ::"l"(pe), "r"(pack2(r1[3] * i1, 1.f)), "n"(X * 1024) : "memory");
    bar_arrive(NB_XG + X, 320);
    SF;
    TS(BWD ? 10 : 7);
}
__device__ __forceinline__ uint32_t pause(uint32_t v, int n) {
#pragma unroll
    for (int i = 0; i < n; i++) asm volatile("shfl.sync.bfly.b32 %0,%0,0,0x1f,0xffffffff;" : "+r"(v));
    return v;
}
template <bool DUAL, int X>
__device__ __forceinline__ void rec_step(RecW& k, int it, int s2, const uint32_t (*wq)[4], const uint32_t (*wk)[4], uint4* wt, uint4& mf) {
    constexpr int NP = NPD;
    uint4 wo[16];
    Gat g;
    rec_qkv<DUAL ? 1 : 0, X, NP>(k, X ? s2 : it, wq, wk, wt, g, mf);
    if (DUAL) rec_qkv<2, 1, NP>(k, s2, wq, wk, wt, g, mf);
    k.am = vxor(k.am, (it & 1) ? 128 : 512); k.ae = vxor(k.ae, (it & 1) ? 128 : 512);
    uint32_t wa = k.lpw;
#pragma unroll
    for (int i = 0; i < NTO; i++) {
        wo[i] = lds128o(wa, R_WO + i * 4096);
        if (i % PACE == PACE - 1) wa = k.lpw + (wo[i].x & k.zero);
        SF;
    }
    rec_out<false, X>(k, wo, g);
    if (DUAL) { rec_out<true, 1>(k, wo, g); if (!EARLY) gat_issue<0>(g, k, 0); SF; }
#pragma unroll
    for (int i = 0; i < NP; i++) { WLD(R_WV, i); SF; }
    if (!DUAL) gat_issue<X>(g, k, pause(wt[NP - 1].x & k.zero, DP1));
    TS(12);
    gat_finish<X>(gat_store<X>(g, k), k);
    mf = ldsm4o(k.lp, R_M + X * XS);
}

__device__ __forceinline__ void rec_fetch(const CUtensorMap* tm, uint32_t dst, int x, int y, int nx, uint32_t bar) {
#pragma unroll 1
    for (int j = 0; j < 8; j++) tma2d(dst + j * 8192, tm, x + (j / (8 / nx)) * 64, y + (j % (8 / nx)) * 64, bar);
}
__device__ __forceinline__ void rec_weights(const Params& p, uint32_t sb, int head, uint32_t rank, int w) {
    const int lane = threadIdx.x & 31, t = w & 3, WG = w >> 2;
    uint32_t wq[16][4], wk[16][4];
    const uint32_t rowo = (((lane >> 4) << 3) + (lane & 7)) * 128;
    const uint32_t woff = sb + WG * 32768 + rowo + (((2 * t + ((lane >> 3) & 1)) ^ (lane & 7)) << 4);
    const uint32_t qoff = sb + ((w & 1) ? R_STK : R_STQ) + WG * 32768 + rowo + (((2 * (t & 2) + ((lane >> 3) & 1)) ^ (lane & 7)) << 4);
    const uint32_t lw = sb + (lane ^ (lane >> 3)) * 16;
    PROF(threadIdx.x == 0, 3501);
    PROF(threadIdx.x == 0, 3502);
    mbar_wait(sb + R_BAR + RB_INIT * 8, 0);
    PROF(threadIdx.x == 0, 3503);
#pragma unroll
    for (int ks = 0; ks < 16; ks++) {
        uint4 a = ldsm4t(qoff + ks * 2048), b = ldsm4t((qoff ^ 32) + ks * 2048);
        wq[ks][0] = a.x; wq[ks][1] = a.y; wq[ks][2] = a.z; wq[ks][3] = a.w;
        wk[ks][0] = b.x; wk[ks][1] = b.y; wk[ks][2] = b.z; wk[ks][3] = b.w;
    }
    bar_sync(NB_W, 256);
#pragma unroll 4
    for (int ks = 0; ks < 16; ks++) { const uint4 a = ldsm4t(woff + R_STV + ks * 2048); sts128(lw + w * 512 + R_WV + ks * 4096, a.x, a.y, a.z, a.w); }
    bar_sync(NB_W, 256);
    if (threadIdx.x == 0) {
        mbar_expect(sb + R_BAR + RB_INIT * 8, 65536);
        rec_fetch(&p.tm[4], sb + R_STV, rank * 256, head * 128, 4, sb + R_BAR + RB_INIT * 8);
    }
    __syncwarp();
    mbar_wait(sb + R_BAR + RB_INIT * 8, 1);
#pragma unroll 4
    for (int f = 0; f < 16; f++) {
        const uint4 a = ldsm4t(sb + R_STV + (w >> 1) * 16384 + (f >> 1) * 2048 + rowo + ((((w & 1) * 4 + (f & 1) * 2 + ((lane >> 3) & 1)) ^ (lane & 7)) << 4));
        sts128(lw + w * 512 + R_WO + f * 4096, a.x, a.y, a.z, a.w);
    }
    PROF(threadIdx.x == 0, 3504);
    __syncthreads();
    cluster_sync();
    PROF(threadIdx.x == 0, 3505);
    RecW k;
    k.am = __shfl_sync(0xffffffffu, (uint32_t)(size_t)acc_base() + acc_slot(3) + acc_main(rank, threadIdx.x), lane);
    k.ae = __shfl_sync(0xffffffffu, (uint32_t)(size_t)acc_base() + acc_slot(3) + acc_extra(rank, threadIdx.x), lane);
    k.ah = (uint32_t)((size_t)acc_base() >> 32);
    k.sb = sb; k.zero = p.zero;

    k.dp = mapa(sb, rank ^ 1) - sb;
    k.lp = __shfl_sync(0xffffffffu, lw, lane);
    k.lpw = __shfl_sync(0xffffffffu, lw + w * 512, lane);
    k.vo = __shfl_sync(0xffffffffu, sb + 4096 + w * 256 + (((lane & 15) ^ ((w & 1) * 4 + ((lane >> 3) & 1) * 2)) << 4), lane);
    k.bar = sb + k.dp + R_BAR + (RB_QK + WG) * 8;
    int it = 0;
    uint4 wt[16];
#pragma unroll
    for (int i = 0; i < NPD; i++) WLD(R_WV, i);
    gat_finish<0>(false, k);
    uint4 mf = ldsm4o(k.lp, R_M);
#pragma unroll 1
    for (; it < min(p.b1, p.e0); it++) { TSET(it, w == GPW ? 0 : 3); rec_step<false, 0>(k, it, it, wq, wk, wt, mf); }
#pragma unroll 1
    for (; it < p.e0; it++) { TSET(it, w == GPW ? 0 : 3); rec_step<true, 0>(k, it, it - p.b1, wq, wk, wt, mf); }
    if (it < p.nit) { gat_finish<1>(false, k); mf = ldsm4o(k.lp, R_M + XS); }
#pragma unroll 1
    for (; it < p.nit; it++) { TSET(it, w == GPW ? 0 : 3); rec_step<false, 1>(k, it, it - p.b1, wq, wk, wt, mf); }
}

__device__ __forceinline__ void mma16_top(float* c, uint32_t a0, uint32_t a2, uint32_t b0, uint32_t b1) {
    asm volatile("{.reg .b32 j; mma.sync.aligned.m16n8k16.row.col.f32.bf16.bf16.f32 {%0,%1,%2,%3},{%4,j,%5,j},{%6,%7},{%0,%1,%2,%3};}"
                 : "+f"(c[0]), "+f"(c[1]), "+f"(c[2]), "+f"(c[3]) : "r"(a0), "r"(a2), "r"(b0), "r"(b1));
}
__device__ __forceinline__ void rec_load_tile(uint32_t sb, int X, int j, int s, int head, uint32_t rank) {
    const uint32_t bar = sb + R_BAR + (RB_T + X * 2 + j) * 8;
    mbar_expect1(bar, j ? 4096 : 16384);
    bulk_g2s1(sb + R_T + X * XS + j * 16384, g_qkv[X] + (size_t)(s * 32 + head) * 1536 + (j ? rank * 256 : 512), j ? 4096 : 16384, bar, POL_LAST);
}
__device__ __forceinline__ bool chunk_ready(int X, int j, int s) {
    unsigned v;
    asm volatile("ld.relaxed.gpu.global.u32 %0,[%1];" : "=r"(v) : "l"(cnt_ptr(C_QKV0 + X, (s >> 2) + j * 16)) : "memory");
    return __all_sync(0xffffffffu, v >= (256 >> j));
}
__device__ __forceinline__ uint4 hadd4(uint4 a, uint4 b) { return make_uint4(hadd2(a.x, b.x), hadd2(a.y, b.y), hadd2(a.z, b.z), hadd2(a.w, b.w)); }
struct RecH { uint32_t lw, lm, lq, lv, lu, sa, sp, xb, sb, zero, ts, tn; };
__device__ __forceinline__ void rec_publish(int X, int s) {
    asm volatile("{.reg .pred p; cp.async.bulk.wait_group 0; elect.sync _|p,0xffffffff; @p red.relaxed.gpu.global.add.u32 [%0],4;}" ::"l"(cnt_ptr(C_O0 + X, s >> 2)) : "memory");
}
__device__ __forceinline__ void rec_mattn(const RecH& k, uint32_t dp, int X, int j, int s, uint4 (*V)[4], uint4* vm, uint4* kmm) {
    const uint32_t sb = k.sb, to = R_T, lo = R_LOC, ro = R_REM + (s & 1) * 6144;
    const uint32_t bar = sb + R_BAR + (X * 2 + j) * 8;
    uint4 K[2][4];
    mbar_wait(sb + R_BAR + (RB_T + X * 2) * 8, s & 1);
    TS(1);
#pragma unroll
    for (int i = 0; i < 8; i++) K[i >> 2][i & 3] = ldsm4o(k.lm, (to + (i >> 2) * 1024 + ((i >> 1) & 1) * 4096 + (i & 1) * 512));
    asm volatile("cp.async.bulk.wait_group 0;" ::: "memory");
    bar_sync(NB_LOC + X, 320);
    fence_async_smem();
    asm volatile("{.reg .pred p; elect.sync _|p,0xffffffff; @p cp.async.bulk.shared::cluster.shared::cta.mbarrier::complete_tx::bytes [%0],[%1],1024,[%2];}"
                 ::"r"(k.xb + dp + ro + 4096), "r"(k.xb + lo + 4096), "r"(bar + dp + RB_V * 8) : "memory");
    uint4 u[4];
#pragma unroll
    for (int i = 0; i < 4; i++) u[i] = ldsm4o(k.lm, (lo + i * 512));
    TS(2);
    mbar_wait(bar + RB_QK * 8, s & 1);
    TS(3);
    float S[5][4];
#pragma unroll
    for (int i = 0; i < 5; i++) S[i][0] = S[i][1] = S[i][2] = S[i][3] = 0;
    {
        uint4 r[4];
#pragma unroll
        for (int i = 0; i < 4; i++) r[i] = ldsm4o(k.lm, (ro + i * 512));
        SF;
#pragma unroll
        for (int e = 0; e < 2; e++) {
            uint4& km = u[2 * e + 1];
            const uint32_t q0 = hadd2(u[2 * e].x, r[2 * e].x), q1 = hadd2(u[2 * e].y, r[2 * e].y);
            mma16_top(S[0], q0, q1, K[e][0].x, K[e][0].y);
            km.x = hadd2(km.x, r[2 * e + 1].x); km.y = hadd2(km.y, r[2 * e + 1].y);
            SF;
            mma16_top(S[1], q0, q1, K[e][1].x, K[e][1].y);
            const uint32_t q2 = hadd2(u[2 * e].z, r[2 * e].z), q3 = hadd2(u[2 * e].w, r[2 * e].w);
            SF;
            mma16_top(S[2], q0, q1, K[e][2].x, K[e][2].y);
            km.z = hadd2(km.z, r[2 * e + 1].z); km.w = hadd2(km.w, r[2 * e + 1].w);
            SF;
            mma16_top(S[3], q0, q1, K[e][3].x, K[e][3].y);
            mma16_top(S[4], q0, q1, km.x, km.y);
            SF;
#pragma unroll
            for (int i = 0; i < 4; i++) {
                mma16_top(S[i], q2, q3, K[e][i].z, K[e][i].w); SF;
            }
            mma16_top(S[4], q2, q3, km.z, km.w);
            SF;
        }
    }
#define VLD(a, b) _Pragma("unroll") for (int i = (a); i < (b); i++) V[i >> 2][i & 3] = ldsm4to((i & 1) ? lv2 : k.lv, (to + 8192 + (i >> 2) * 4096 + ((i >> 1) & 1) * 1024))
    const uint32_t lv2 = vxor(k.lv, 0x20), lh = k.lw - (vshr(k.lw - k.xb, 1) & 0xf8);
    VLD(0, VE);
    SF;
    const uint32_t sxr = k.sa, sxw = k.sp;
    sts128o(k.lw, sxw, __float_as_uint(S[0][0]), __float_as_uint(S[0][1]), __float_as_uint(S[1][0]), __float_as_uint(S[1][1]));
    SF;
    sts128o(k.lw, (sxw + 512), __float_as_uint(S[2][0]), __float_as_uint(S[2][1]), __float_as_uint(S[3][0]), __float_as_uint(S[3][1]));
    SF;
    sts64o(lh, (sxw + 1024), __float_as_uint(S[4][0]), __float_as_uint(S[4][1]));
    TS(4);
    bar_sync(NB_PAIR + X, 64);
    {
        const uint4 a = lds128o(k.lw, sxr), b = lds128o(k.lw, (sxr + 512));
        const uint2 c = lds64o(lh, (sxr + 1024));
        SF;
        VLD(VE, VF);
        SF;
        S[0][0] += __uint_as_float(a.x); S[0][1] += __uint_as_float(a.y); S[1][0] += __uint_as_float(a.z); S[1][1] += __uint_as_float(a.w);
        S[2][0] += __uint_as_float(b.x); S[2][1] += __uint_as_float(b.y); S[3][0] += __uint_as_float(b.z); S[3][1] += __uint_as_float(b.w);
        S[4][0] += __uint_as_float(c.x); S[4][1] += __uint_as_float(c.y);
    }
    float m = fmaxf(fmaxf(fmaxf(S[0][0], S[0][1]), fmaxf(S[1][0], S[1][1])), fmaxf(fmaxf(S[2][0], S[2][1]), fmaxf(S[3][0], S[3][1])));
    m = fmaxf(m, fmaxf(S[4][0], S[4][1]));
    m = fmaxf(m, __shfl_xor_sync(0xffffffffu, m, 1));
    const float m2 = __shfl_xor_sync(0xffffffffu, m, 2);
    SF;
    VLD(VF, 8);
    uint32_t ok;
    asm volatile("{.reg .pred p; mbarrier.test_wait.parity.shared::cta.b64 p,[%1],%2; selp.u32 %0,1,0,p;}" : "=r"(ok) : "r"(bar + RB_V * 8), "r"(s & 1) : "memory");
    uint4 vr0 = ldsm4o(k.lu, (ro + 4096)), vr1 = ldsm4o(k.lu, (ro + 4608));
    vm[0] = ldsm4o(k.lu, (lo + 4096)); vm[1] = ldsm4o(k.lu, (lo + 4608));
    SF;
    TS(5);
    m = fmaxf(m, m2) * -SC_LOG2E;
    uint32_t P[5];
#pragma unroll
    for (int i = 0; i < 5; i++) P[i] = pack2(ex2(fmaf(S[i][0], SC_LOG2E, m)), ex2(fmaf(S[i][1], SC_LOG2E, m)));
    float o[4][4], l[4] = {0, 0, 0, 0};
    const uint32_t ONE = 0x3f803f80u;
    mma16_top(l, ONE, ONE, P[0], P[1]);
#pragma unroll
    for (int t = 0; t < 4; t++) { o[t][0] = o[t][1] = o[t][2] = o[t][3] = 0; mma16(o[t], V[0][t].x, V[0][t].y, V[0][t].z, V[0][t].w, P[0], P[1]); }
    mma16_top(l, ONE, ONE, P[2], P[3]);
#pragma unroll
    for (int t = 0; t < 4; t++) mma16(o[t], V[1][t].x, V[1][t].y, V[1][t].z, V[1][t].w, P[2], P[3]);
    if (!__all_sync(0xffffffffu, ok)) {
        mbar_wait(bar + RB_V * 8, s & 1);
        vr0 = ldsm4o(k.lu, (ro + 4096)); vr1 = ldsm4o(k.lu, (ro + 4608));
    }
    TS(6);
    vm[0] = hadd4(vm[0], vr0); vm[1] = hadd4(vm[1], vr1);
    mma8(l, ONE, ONE, P[4]);
    mma8(o[0], vm[0].x, vm[0].y, P[4]); mma8(o[1], vm[0].z, vm[0].w, P[4]); mma8(o[2], vm[1].x, vm[1].y, P[4]); mma8(o[3], vm[1].z, vm[1].w, P[4]);
    asm volatile("{.reg .pred p; .reg .b32 t; setp.lt.u32 p,%0,%3; add.u32 t,%0,%4; @p st.shared.v2.f32 [t],{%1,%2};}" ::"r"(lh), "f"(rcp(l[0])), "f"(rcp(l[1])), "r"(k.xb + 32), "r"(R_IL) : "memory");
#pragma unroll
    for (int t = 0; t < 4; t += 2)
        asm volatile("{.reg .b32 t; add.u32 t,%0,%5; stmatrix.sync.aligned.m8n8.x4.trans.shared.b16 [t],{%1,%2,%3,%4};}" ::"r"(k.lm),
                     "r"(pack2(o[t][0], o[t][1])), "r"(pack2(o[t][2], o[t][3])), "r"(pack2(o[t + 1][0], o[t + 1][1])), "r"(pack2(o[t + 1][2], o[t + 1][3])), "r"(R_O - j * 1024 + t * 256) : "memory");
    bar_arrive(NB_O + X, 320);
    PROF(k.lw == k.xb, X * 64 + s);
    TS(7);
    kmm[0] = u[1]; kmm[1] = u[3];
    mbar_expect1(bar + RB_QK * 8, 2048); mbar_expect1(bar + RB_V * 8, 1024);
}
template <int MT>
__device__ __forceinline__ void rec_xattn(const RecH& k, int X, int j, int s, int head, bool early, const uint4 (*V)[4], const uint4* vmm, const uint4* kmm) {
    constexpr int NTL = 3 + 2 * MT;
    const uint32_t sb = k.sb, to = R_T;
    const uint32_t sxw = k.sa, sxr = k.sp;
    const uint32_t lq2 = vxor(k.lq, 0x20);
    float S[NTL][4];
#pragma unroll
    for (int i = 0; i < NTL; i++) S[i][0] = S[i][1] = S[i][2] = S[i][3] = 0;
    {
        uint4 q[2][2], kk[2][NTL];
#define XQ(e) q[e][0] = ldsm4o(k.lq, (to + 16384 + (e) * 1024)); q[e][1] = ldsm4o(lq2, (to + 16384 + (e) * 1024))
#define XK(e, i) kk[e][i] = ldsm4o(k.lm, (to + (e) * 1024 + (((i) - 1) >> 1) * 4096 + (((i) - 1) & 1) * 512))
        kk[0][0] = kmm[0]; kk[1][0] = kmm[1];
        if (!X) bar_sync(NB_XG, 320);
        XQ(0);
#pragma unroll
        for (int i = 1; i < NTL; i++) XK(0, i);
        SF;
#pragma unroll
        for (int i = 0; i < NTL; i++) { mma16(S[i], q[0][0].x, q[0][0].y, q[0][0].z, q[0][0].w, kk[0][i].x, kk[0][i].y); SF; }
        q[1][0] = ldsm4o(k.lq, (to + 16384 + 1024));
#pragma unroll
        for (int i = 0; i < NTL; i++) { mma16(S[i], q[0][1].x, q[0][1].y, q[0][1].z, q[0][1].w, kk[0][i].z, kk[0][i].w); SF; if (i + 1 < NTL) XK(1, i + 1); SF; }
        q[1][1] = ldsm4o(lq2, (to + 16384 + 1024));
        SF;
#pragma unroll
        for (int i = 0; i < NTL; i++) { mma16(S[i], q[1][0].x, q[1][0].y, q[1][0].z, q[1][0].w, kk[1][i].x, kk[1][i].y); SF; }
#pragma unroll
        for (int i = 0; i < NTL; i++) { mma16(S[i], q[1][1].x, q[1][1].y, q[1][1].z, q[1][1].w, kk[1][i].z, kk[1][i].w); SF; }
    }
#pragma unroll
    for (int i = 0; i < NTL; i++) sts128o(k.lw, (sxw + i * 512), __float_as_uint(S[i][0]), __float_as_uint(S[i][1]), __float_as_uint(S[i][2]), __float_as_uint(S[i][3]));
    SF;
    if (X) bar_sync(NB_XG + 1, 320); else bar_sync(NB_PAIR + 2, 64);
    TS(9);
    if (early && !X) rec_load_tile(sb, X, j, s + 1, head, MT);
#pragma unroll
    for (int i = 0; i < NTL; i++) {
        const uint4 r = lds128o(k.lw, (sxr + i * 512));
        S[i][0] += __uint_as_float(r.x); S[i][1] += __uint_as_float(r.y); S[i][2] += __uint_as_float(r.z); S[i][3] += __uint_as_float(r.w);
    }
    const int g = vshr(k.lw - k.xb, 6) & 7, c = (vshr(k.lw, 4) ^ (g >> 1)) & 3;
    const float NEG = -__int_as_float(0x7f800000);
    if (2 * c > g) { S[NTL - 2][0] = NEG; S[NTL - 1][2] = NEG; }
    if (2 * c + 1 > g) { S[NTL - 2][1] = NEG; S[NTL - 1][3] = NEG; }
    float m0 = fmaxf(S[0][0], S[0][1]), m1 = fmaxf(S[0][2], S[0][3]);
#pragma unroll
    for (int i = 1; i < NTL; i++) { if (i < NTL - 1) m0 = fmaxf(m0, fmaxf(S[i][0], S[i][1])); m1 = fmaxf(m1, fmaxf(S[i][2], S[i][3])); }
    m0 = fmaxf(m0, __shfl_xor_sync(0xffffffffu, m0, 1)); m1 = fmaxf(m1, __shfl_xor_sync(0xffffffffu, m1, 1));
    m0 = fmaxf(m0, __shfl_xor_sync(0xffffffffu, m0, 2)); m1 = fmaxf(m1, __shfl_xor_sync(0xffffffffu, m1, 2));
    m0 *= -SC_LOG2E; m1 *= -SC_LOG2E;
    uint32_t P[NTL][2];
#pragma unroll
    for (int i = 0; i < NTL; i++) {
        P[i][0] = i < NTL - 1 ? pack2(ex2(fmaf(S[i][0], SC_LOG2E, m0)), ex2(fmaf(S[i][1], SC_LOG2E, m0))) : 0u;
        P[i][1] = pack2(ex2(fmaf(S[i][2], SC_LOG2E, m1)), ex2(fmaf(S[i][3], SC_LOG2E, m1)));
    }
    float l[4] = {0, 0, 0, 0};
#pragma unroll
    for (int i = 0; i < NTL; i++) mma8(l, P[i][0], P[i][1], 0x3f803f80u);
    const float l0 = rcp(l[0]), l1 = rcp(l[2]);

#pragma unroll
    for (int e = 0; e < 2; e++) {
        const uint4 vm = vmm[e];
        uint32_t u[2][4];
#pragma unroll
        for (int n = 0; n < 4; n++) {
            float a[4] = {0, 0, 0, 0};
#pragma unroll
            for (int m = 0; m <= MT; m++) {
                const uint4 v = V[m][e * 2 + (n >> 1)];
                mma8(a, P[1 + 2 * m][0], P[1 + 2 * m][1], (n & 1) ? v.y : v.x); mma8(a, P[2 + 2 * m][0], P[2 + 2 * m][1], (n & 1) ? v.w : v.z);
            }
            mma8(a, P[0][0], P[0][1], n == 0 ? vm.x : n == 1 ? vm.y : n == 2 ? vm.z : vm.w);
            u[0][n] = pack2(a[0] * l0, a[1] * l0); u[1][n] = pack2(a[2] * l1, a[3] * l1);
        }
        sts128o(k.lw, sxr + e * 512, u[0][0], u[0][1], u[0][2], u[0][3]); sts128o(k.lw, sxr + e * 512 + 1024, u[1][0], u[1][1], u[1][2], u[1][3]);
    }
    if (early && X) rec_load_tile(sb, X, j, s + 1, head, MT);
    TS(10);
}
__device__ __forceinline__ void rec_attn(const Params& p, uint32_t sb, int X, int j, int head, uint32_t rank) {
    const int lane = threadIdx.x & 31;
    RecH k;
    k.xb = sb + X * XS + j * 1024;
    const uint32_t x2 = k.xb + j * 1024;
    k.lw = __shfl_sync(0xffffffffu, x2 + (lane ^ (lane >> 3)) * 16, lane);
    k.lm = __shfl_sync(0xffffffffu, x2 + ((lane & 7) * 4 + ((lane >> 3) ^ ((lane & 7) >> 1))) * 16, lane);
    k.lq = __shfl_sync(0xffffffffu, x2 + ((lane >> 3) & 1) * 512 + ((lane & 7) * 4 + ((lane >> 4) ^ ((lane & 7) >> 1))) * 16, lane);
    k.lv = __shfl_sync(0xffffffffu, x2 + (lane >> 4) * 512 + ((lane & 7) * 4 + (((lane >> 3) & 1) ^ ((lane & 7) >> 1))) * 16, lane);
    k.lu = __shfl_sync(0xffffffffu, k.xb + ((lane & 6) * 4 + (((lane >> 3) * 2 + (lane & 1)) ^ (lane & 6))) * 16, lane);
    k.sa = __shfl_sync(0xffffffffu, R_SX + j * 512, 0); k.sp = __shfl_sync(0xffffffffu, R_SX + 2560 - j * 4608, 0);
    k.sb = sb; k.zero = p.zero;
    const uint32_t dp = mapa(sb, rank ^ 1) - sb;
    char* zp = acc_base() + (j ? X * 32768 + acc_main(rank, head * 8) : X * 1024 + acc_extra(rank, head * 8));
    mbar_expect1(sb + R_BAR + (RB_QK + X * 2 + j) * 8, 2048); mbar_expect1(sb + R_BAR + (RB_V + X * 2 + j) * 8, 1024);
    bool early = false;
#pragma unroll 1
    for (int s = 0; s < 64; s++) {
        TSET(X ? s + p.b1 : s, j == GPJ ? 1 + X : 3);
        TS(0);
        if (!early) {
            if (!j) wait_cnt_warp(cnt_ptr(C_QKV0 + X, s >> 2), 256);
            early = !j || chunk_ready(X, 1, s);
            if (early) rec_load_tile(sb, X, j, s, head, rank);
        }
        uint4 V[2][4], vm[2], km[2];
        rec_mattn(k, dp, X, j, s, V, vm, km);
        if (!early) { wait_cnt_warp(cnt_ptr(C_QKV0 + X, (s >> 2) + 16), 128); rec_load_tile(sb, X, 1, s, head, rank); }
        early = s < 63 && ((s & 3) != 3 || chunk_ready(X, j, s + 1));
        mbar_wait(sb + R_BAR + (RB_T + X * 2 + 1) * 8, s & 1);
        if (rank) rec_xattn<1>(k, X, j, s, head, early, V, vm, km); else rec_xattn<0>(k, X, j, s, head, early, V, vm, km);
        fence_async_smem();
        __syncwarp();
        asm volatile("{.reg .pred p; elect.sync _|p,0xffffffff;\n"
                     "@p cp.async.bulk.global.shared::cta.bulk_group.L2::cache_hint [%0],[%1],2048,%2;\n"
                     "@p cp.async.bulk.global.shared::cta.bulk_group [%3],[%4],%5;\n"
                     "cp.async.bulk.commit_group;}"
                     ::"l"(g_o[X] + ((s >> 2) * 64 + head * 2 + j) * 1024 + ((s & 3) * 2 + rank) * 128), "r"(x2 + k.sp),
                       "l"((X && s < 40) ? POL_LATE : POL_SOON), "l"(zp + acc_slot(s + 2 + X * p.lag)), "r"(sb + R_Z), "r"(j ? 128 : 32) : "memory");
        if (s == 61) rec_publish(X, 64);
        if ((s & 3) == 3) {
            if (!early && s < 63 && chunk_ready(X, j, s + 1)) { rec_load_tile(sb, X, j, s + 1, head, rank); early = true; }
            rec_publish(X, s);
            PROF(lane == 0 && j, 3900 + X * 16 + (s >> 2));
        }
    }
}

__device__ __forceinline__ void rec_init(const Params& p, uint32_t sb, int head, uint32_t rank) {
    const uint32_t b = sb + R_BAR;
    const int i = threadIdx.x - 320;
    if (i >= 0 && i < RB_N) {
        mbar_init(b + i * 8, 1);
        asm volatile("fence.mbarrier_init.release.cluster;" ::: "memory");
    }
    if (i == 0) mbar_expect(b + RB_INIT * 8, 196608);
    if (i >= 0 && i < 32) sts32(sb + R_Z + i * 4, 0);
}

#define NSTGN 8
constexpr int NSTG = NSTGN, STG_B = 24576;
#define LAGH 3
constexpr int NSB = 8;
constexpr int B_OUT = NSTG * STG_B  , B_UT = B_OUT, B_YT = B_UT + 16384, B_SP = B_YT  ,
              B_ST = 229376  , B_BAR = 231936;
static_assert(B_OUT + NSB * 4096 <= B_ST && B_ST + 2048 <= B_BAR && B_YT + 10240 <= B_ST, "smem map");
enum { BB_FULL = 0, BB_EMPTY = 8, BB_SF = 16  , BB_GO = 18, BB_LOW = 19, BB_DONE = 20  , BB_IDLE = 22  , BB_N = 30 };
enum { NB_REL = 2  , NB_C = 11, NB_WG = 12  , NB_PH = 14 };

__device__ __forceinline__ void bulk_init(uint32_t sb) {
    const int i = threadIdx.x - 320;
    if (i >= 0 && i < BB_N) {
        mbar_init(sb + B_BAR + i * 8, (i >= BB_EMPTY && i < BB_EMPTY + NSTG) ? 4 : i >= BB_DONE ? 4 : 1);
        asm volatile("fence.mbarrier_init.release.cluster;" ::: "memory");
    }
}

struct Task { int type, layer, ch, a, b, c, blk; bool pair, dry; };
__device__ __forceinline__ Task task_of(uint32_t tk, uint32_t rank) {
    Task t;
    t.type = tk & 7; t.layer = (tk >> 3) & 1; t.a = (tk >> 8) & 255; t.b = (tk >> 16) & 255; t.c = (tk >> 24) & 127; t.dry = tk >> 31;
    t.pair = t.type <= T_OP && (t.c & 64);
    t.ch = ((tk >> 4) & 15) + (t.pair ? rank : 0);
    t.blk = t.type == T_QKV ? t.a + (t.pair ? 0 : rank) : 192 + (t.pair ? (t.c >> 2) & 4 : rank * 4);
    return t;
}
__device__ __forceinline__ int qkv_blk(const Task& t, int u) {
    const int v = t.blk + (t.pair ? 1 : 2 * t.c) * u;
    return 2 * (v < 64 ? v + 32 : v - 64);
}
__device__ __forceinline__ void bulk_producer(const Params& p, uint32_t sb, int cl, uint32_t rank) {
    int st = 0; uint32_t ph = 1;
    const int tag = __shfl_sync(0xffffffffu, lds32(sb + S_TAG), 0);
    bool gated = false;
#define ACQ(bytes) do { mbar_wait(sb + B_BAR + (BB_EMPTY + st) * 8, ph); mbar_expect1(sb + B_BAR + (BB_FULL + st) * 8, bytes); } while (0)
#define NEXT do { if (++st == NSTG) { st = 0; ph ^= 1; } } while (0)
#pragma unroll 1
    for (int ti = 0; ti < MAXT; ti++) {
        const Task t = task_of(p.task[list_of(cl)][ti], rank);
        const int layer = t.layer, ch = t.ch;
        if (t.type == T_END) break;
        if (t.type <= T_OP) {
            const bool qkv = t.type == T_QKV;
            const int nh = (qkv ? 8 : 2) * t.b;
            const bool halves = !qkv && (t.c & 80) == 16;
            const unsigned* dep = cnt_ptr(qkv ? (layer ? C_CV : C_ST) : C_O0 + layer, ch + (halves && !rank));
            const unsigned need = qkv ? (layer ? 32 : ch < 2 ? 0 : 16) : 512;
            const uint16_t mb = t.pair ? 3 : 1 << rank, ma = t.pair ? 1 << rank : 3;
            const int pend = min(nh, gated ? NSTG : 4);
            auto ready = [&](int h) {
                if (h < pend) {
                    unsigned v = 0;
                    if (gated) asm volatile("ld.relaxed.gpu.global.u32 %0,[%1];" : "=r"(v) : "l"(dep) : "memory");
                    return gated && __all_sync(0xffffffffu, v >= need);
                }
                if (!gated) { wait_cnt_warp(g_gate, lds32(sb + S_GATE)); gated = true; }
                if (need) wait_cnt_warp(dep, need);
                return true;
            };
            bool open = true;
            if (qkv) {
#pragma unroll 1
                while (st) { ACQ(0); NEXT; }
#pragma unroll 1
                for (int h = 0; h < nh; h++) {
                    const int blk = qkv_blk(t, h >> 3);
                    ACQ(16384 + (h < 2 ? (layer ? 8192 : 1024) : 0));
                    if (!t.pair || !rank) tma3d_mc(sb + st * STG_B, &p.t3[blk >> 6], (h & 7) * 64, blk & 63, sb + B_BAR + (BB_FULL + st) * 8, mb);
                    if (!t.pair || rank) tma3d_mc(sb + st * STG_B + 8192, &p.t3[blk >> 6], (h & 7) * 64 + 32, blk & 63, sb + B_BAR + (BB_FULL + st) * 8, mb);
                    NEXT;
                    if (open && h && ready(h + 1)) {
                        open = false;
                        const float2* sp = g_st[layer] + ch * 2048 + (need ? 0 : tag * 256);
                        bulk_g2s1(sb + 16384, sp, layer ? 8192 : 1024, sb + B_BAR + BB_FULL * 8, POL_N);
                        bulk_g2s1(sb + STG_B + 16384, sp + (layer ? 1024 : 128), layer ? 8192 : 1024, sb + B_BAR + (BB_FULL + 1) * 8, POL_N);
                    }
                }
                continue;
            }
            if (PFC && !layer && (t.c & 15) < 8) {
                const int q = (t.c & 15) * 2 + rank;
                asm volatile("{.reg .pred p; elect.sync _|p,0xffffffff; @p cp.async.bulk.prefetch.L2.global [%0],8192; @p cp.async.bulk.prefetch.L2.global [%1],%2;}"
                             ::"l"(g_xA[0] + (ch * 16 + q) * 512), "l"(g_P + q * 16 * 32 * PW), "r"((2 + (ch & 1)) * 32 * PW * 4) : "memory");
            }
            const CUtensorMap *tb = &p.t3[4 - t.pair], *ta = &p.ta[t.pair];
            const uint32_t db = sb + 8192 + (t.pair ? rank * 8192 : 0), da = sb + (t.pair ? 0 : rank * 4096);
            const int zb = (t.blk & 63) + (t.pair ? rank * 2 : 0), ya = 4096 + ((layer * 16 + ch) * 64 + t.a) * 16 + (t.pair ? 0 : rank * 8), row = t.a * 64;
            int h = 0;
            const int s0 = st;
            if (halves) mbar_expect1(sb + B_BAR + BB_LOW * 8, NSTG * 4096);
#pragma unroll 1
            for (; (halves && h < NSTG) || !ready(h); h++) { ACQ(halves ? STG_B - 4096 : STG_B); tma3d_mc(db + st * STG_B, tb, row + h * 32, zb, sb + B_BAR + (BB_FULL + st) * 8, mb); NEXT; }
#pragma unroll 1
            for (int k = 0; k < h; k++) {
                const int s2 = (s0 + k) & (NSTG - 1);
                tma2d_mc(da + s2 * STG_B, ta, (k & 1) * 256, ya + (k >> 1) * 16, sb + B_BAR + (halves && rank ? BB_LOW : BB_FULL + s2) * 8, ma, POL_LAST);
            }
#pragma unroll 1
            for (; h < nh; h++) {
                ACQ(STG_B);
                tma3d_mc(db + st * STG_B, tb, row + h * 32, zb, sb + B_BAR + (BB_FULL + st) * 8, mb);
                tma2d_mc(da + st * STG_B, ta, (h & 1) * 256, ya + (h >> 1) * 16, sb + B_BAR + (BB_FULL + st) * 8, ma, POL_LAST);
                NEXT;
            }
#pragma unroll 1
            for (h = 0; h < 4 && !layer; h++) { ACQ(0); NEXT; }
        } else if (t.type == T_CV) {
            const int q = t.a + rank;
            if (!gated) { wait_cnt_warp(g_gate, lds32(sb + S_GATE)); gated = true; }
            if (layer) {
                wait_cnt_warp(cnt_ptr(C_U, ch - 2), 32);
#pragma unroll 1
                for (int j = ch + 1; j >= 2; j--) {
                    ACQ(16 * PW * 4 + (j > 2 ? 4096 : 0));
                    bulk_g2s1(sb + st * STG_B, g_P + (((q >> 1) * 16 + j) * 2 + (q & 1)) * 16 * PW, 16 * PW * 4, sb + B_BAR + (BB_FULL + st) * 8, POL_N);
                    if (j > 2) bulk_g2s1(sb + st * STG_B + 12288, g_u + (((q >> 1) * 16 + ch + 1 - j) * 2 + (q & 1)) * 256, 4096, sb + B_BAR + (BB_FULL + st) * 8, POL_N);
                    NEXT;
                }
            } else {
#pragma unroll 1
                for (int j = min(ch, 1 + (ch & 1)); j >= 0; j--) {
                    if (j == 0 && ch >= 2) {
                        wait_cnt_warp(cnt_ptr(C_H, ch & ~1), 64);
#pragma unroll 1
                        for (int i = 0; i < ((ch & 1) || ch == 2 ? 1 : 2); i++) {
                            ACQ(16384);
                            bulk_g2s1(sb + st * STG_B, g_carry[i] + (ch * 16 + q) * 1024, 16384, sb + B_BAR + (BB_FULL + st) * 8, POL_LAST);
                            NEXT;
                        }
                    }
                    ACQ(32 * PW * 4);
                    bulk_g2s1(sb + st * STG_B, g_P + (q * 16 + j) * 32 * PW, 32 * PW * 4, sb + B_BAR + (BB_FULL + st) * 8, POL_N);
                    NEXT;
                }
            }
        }
    }
}

__device__ __forceinline__ uint4* qkv_dst(int layer, int ch, int w, int blk);
__device__ __forceinline__ uint4* op_dst(int layer, int ch, int slot, int w, uint32_t rank);
__device__ __forceinline__ uint64_t out_pol(int type, int layer, int ch) { return (type == T_QKV ? (!layer && ch > 1) : (layer && ch < 10)) ? POL_LATE : POL_SOON; }
__device__ __forceinline__ void bulk_relay(const Params& p, uint32_t sb, int cl) {
    for (int ti = 0; ti < MAXT; ti++) {
        const int type = p.task[list_of(cl)][ti] & 7;
        if (type == T_END) break;
        if (type != T_QKV) continue;
        bar_sync(NB_PH, 64);
        const uint32_t ph = lds32(sb + B_ST + 8);
#pragma unroll 1
        for (int h = 2; h < 8; h++) {
            mbar_wait(sb + B_BAR + (BB_FULL + h) * 8, ph);
            if (h == 4 || h == 7) { bar_arrive(NB_REL + (h == 7) * 2, 160); bar_arrive(NB_REL + (h == 7) * 2 + 1, 160); }
        }
    }
}
__device__ __forceinline__ void bulk_release(const Params& p, uint32_t sb, int cl, uint32_t rank, int wg) {
    int nd = 0;
    for (int ti = 0; ti < MAXT; ti++) {
        const Task t = task_of(p.task[list_of(cl)][ti], rank);
        const int type = t.type, layer = t.layer, ch = t.ch;
        if (type == T_END) break;
        if (type == T_FIN || (type == T_OP && (t.c & 32))) continue;
        if (type == T_OP && !layer) {
            mbar_wait(sb + B_BAR + (BB_DONE + wg) * 8, nd & 1);
            nd++;
            const int s0 = __shfl_sync(0xffffffffu, lds32(sb + B_ST + wg * 4), 0) + wg * 2;
            fence_async_smem();
#pragma unroll 1
            for (int w = 0; w < 4; w++)
                asm volatile("{.reg .pred p; elect.sync _|p,0xffffffff; @p cp.async.bulk.global.shared::cta.bulk_group.L2::cache_hint [%0],[%1],8192,%2; cp.async.bulk.commit_group;}"
                             ::"l"(op_dst(0, ch, t.c & 15, wg * 4 + w, rank)), "r"(sb + ((s0 + (w >> 1)) & (NSTG - 1)) * STG_B + (w & 1) * 8192), "l"(POL_SOON) : "memory");
            mbar_arrive1(sb + B_BAR + (BB_SF + wg) * 8);
            asm volatile("{.reg .pred p; elect.sync _|p,0xffffffff;\n"
                         "cp.async.bulk.wait_group 3; @p red.relaxed.gpu.global.add.u32 [%0],1; cp.async.bulk.wait_group 2; @p red.relaxed.gpu.global.add.u32 [%0+64],1;\n"
                         "cp.async.bulk.wait_group 1; @p red.relaxed.gpu.global.add.u32 [%0+128],1; cp.async.bulk.wait_group 0; @p red.relaxed.gpu.global.add.u32 [%0+192],1;}"
                         ::"l"(cnt_ptr(C_OP0 + rank * 2 + wg, ch)) : "memory");
#pragma unroll 1
            for (int i = 0; i < 8; i++) mbar_arrive1_cluster(mapa(sb + B_BAR + (BB_EMPTY + ((s0 + (i >> 2)) & (NSTG - 1))) * 8, i & 1));
            continue;
        }
#pragma unroll 1
        for (int u = 0; u < (type == T_QKV ? t.b : 1); u++) {
            const int blk = qkv_blk(t, u);
            unsigned* cnt = cnt_ptr(type == T_QKV ? C_QKV0 + layer : type == T_OP ? C_OP1 : layer ? C_H : C_CV, ch + (type == T_QKV && blk < 64 ? 16 : 0));
            const uint4* dst = type == T_QKV ? qkv_dst(layer, ch, wg * 4, blk) : op_dst(1, ch, t.c & 15, wg * 4, (t.blk >> 2) & 1) + 256;
            mbar_wait(sb + B_BAR + (BB_DONE + wg) * 8, nd & 1);
            nd++;
            if (type != T_CV) {
                fence_async_smem();
#pragma unroll
                for (int w = 0; w < 4; w++)
                    asm volatile("{.reg .pred p; elect.sync _|p,0xffffffff; @p cp.async.bulk.global.shared::cta.bulk_group.L2::cache_hint [%0],[%1],4096,%2;}"
                                 ::"l"(dst + (type == T_QKV ? (w >> 1) * 49152 + (w & 1) * 256 : w * 1024)), "r"(sb + B_OUT + (wg * 4 + w) * 4096), "l"(out_pol(type, layer, ch)) : "memory");
                asm volatile("cp.async.bulk.commit_group; cp.async.bulk.wait_group 0;" ::: "memory");
            }
            if (type != T_QKV) fence_async();
            if (!t.dry) asm volatile("{.reg .pred p; elect.sync _|p,0xffffffff; @p red.relaxed.gpu.global.add.u32 [%0],%1;}" ::"l"(cnt), "r"(type == T_QKV ? 2 : type == T_OP ? t.b : 1) : "memory");
            PROF(wg && (threadIdx.x & 31) == 0 && (type == T_CV || u + 2 == t.b), 3900 + ti);
            if (type == T_CV && !layer && !t.dry) {
                asm volatile("{.reg .pred p; elect.sync _|p,0xffffffff; @p cp.async.bulk.global.shared::cta.bulk_group [%0],[%1],4096;\n"
                             "cp.async.bulk.commit_group; cp.async.bulk.wait_group 0; @p red.relaxed.gpu.global.add.u32 [%2],1;}"
                             ::"l"(g_u + ((t.a + rank) * 16 + ch) * 512 + wg * 256), "r"(sb + B_UT + (ch & 1) * 8192 + wg * 4096), "l"(cnt_ptr(C_U, ch)) : "memory");
            }
            mbar_arrive1(sb + B_BAR + (BB_SF + wg) * 8);
        }
        PROF(wg && (threadIdx.x & 31) == 0, 3600 + ti * 4 + 3);
    }
}

__device__ __forceinline__ void stage_release(uint32_t sb, int w, int st) {
    if (!(w & 2)) mbar_arrive1_cluster(mapa(sb + B_BAR + (BB_EMPTY + st) * 8, w & 1));
}
template <bool ACC>
__device__ __forceinline__ void gemm_run(float* acc, uint32_t sb, int w, int h0, int h1, uint32_t& r0, uint32_t& r1, int& st, uint32_t& ph) {
    const uint64_t da0 = mkdesc(sb + (w >> 2) * 4096, 16, 512, 2), db0 = mkdesc(sb + 8192, 4096, 1024, 1);
    const uint32_t rel0 = mapa(sb + B_BAR + BB_EMPTY * 8, w & 1);
#pragma unroll 1
    for (int h = h0; h < h1; h++) {
        const uint64_t da = da0 + st * (STG_B >> 4), db = db0 + st * (STG_B >> 4);
        mbar_wait(sb + B_BAR + (BB_FULL + st) * 8, ph);
        if (ACC) wg_wait<1>();
        wg_fence();
        wgmma256<ACC>(acc, da, db);
        wgmma256<true>(acc, da + 2, db + 128);
        wg_commit();
        if (ACC) mbar_arrive1_cluster((w == 2 && h == LAGH - 1) ? sb + B_BAR + BB_GO * 8 : r0);
        r0 = r1;
        if (!(w & 2)) r1 = rel0 + st * 8;
        if (++st == NSTG) { st = 0; ph ^= 1; }
    }
}

__device__ __forceinline__ uint4* qkv_dst(int layer, int ch, int w, int blk) {
    return g_qkv[layer] + (size_t)((ch * 4 + (w >> 1)) * 32 + ((blk & 63) >> 1)) * 1536 + (blk >> 6) * 512 + (w & 1) * 256;
}
__device__ __forceinline__ uint4* op_dst(int layer, int ch, int slot, int w, uint32_t rank) {
    return g_pp[layer] + (size_t)(ch * MAXSPLIT + slot) * 8192 + (w * 32 + rank * 16) * 32;
}
__device__ __forceinline__ uint32_t ln2(uint32_t x, uint32_t m, uint32_t rh, uint32_t rl) {
    uint32_t d; asm volatile("{.reg .b32 t,u; sub.rn.bf16x2 t,%1,%2; mul.rn.bf16x2 u,t,%4; fma.rn.bf16x2 %0,t,%3,u;}" : "=r"(d) : "r"(x), "r"(m), "r"(rh), "r"(rl)); return d;
}
__device__ __forceinline__ void ldcg128p(uint4& v, const uint4* p, uint32_t on) {
    asm volatile("{.reg .pred p; setp.ne.u32 p,%5,0; @p ld.global.cg.v4.u32 {%0,%1,%2,%3},[%4];}" : "+r"(v.x), "+r"(v.y), "+r"(v.z), "+r"(v.w) : "l"(p), "r"(on) : "memory");
}
__device__ __forceinline__ void qkv_task(uint32_t sb, int w, int layer, int ch, int nu, int& ng, int& nd, uint32_t& ph, int ti, uint32_t zero,
                                         uint4* A, uint32_t& pre, const uint4* xn, const unsigned* dn, unsigned need) {
    constexpr int type = T_QKV;
    static_assert(NSTG == 8, "ring");
    const int lane = threadIdx.x & 31;
    const uint64_t db0 = mkdesc(sb, 4096, 1024, 1);
    const uint32_t rel = (w & 2) ? sb + B_BAR + BB_IDLE * 8 : mapa(sb + B_BAR + BB_EMPTY * 8, w & 1), full = sb + B_BAR + BB_FULL * 8;
    const uint32_t lo = sb + B_OUT + w * 4096 + (lane ^ (lane >> 3)) * 16;
    const uint4* xa = g_xA[layer] + (ch * 8 + w) * 1024 + lane;
    uint32_t m0, m1, h0, h1, l0, l1;
    {
        mbar_wait(full, ph);
        mbar_wait(full + 8, ph);
        CPROF(1);
        const uint32_t sa = sb + (lane >> 4) * STG_B + 16384 + (w * 16 + (lane & 15)) * 8;
        uint2 v[8];
#pragma unroll
        for (int i = 0; i < 8; i++) v[i] = lds64(sa + i * 1024 * layer);
#pragma unroll
        for (int i = 0; i < 4 * QB1; i++) ldcg128p(A[i], xa + i * 32, !pre);
        bar_sync(NB_WG + (w >> 2), 128);
        float sm = 0, M2 = 0, D = 0;
#pragma unroll
        for (int i = 0; i < 8; i++) { sm += __uint_as_float(v[i].x); M2 += __uint_as_float(v[i].y); }
        if (!layer) { sm = __uint_as_float(v[0].x); M2 = __uint_as_float(v[0].y); }
        sm += __shfl_xor_sync(0xffffffffu, sm, 16);
#pragma unroll
        for (int i = 0; i < 8; i++) { const float d = __uint_as_float(v[i].x) * (1.f / 32.f) - sm * (1.f / 512.f); D += 32.f * d * d; }
        M2 += layer ? D : sm * sm * (-1.f / 1024.f);
        M2 = fmaxf(M2 + __shfl_xor_sync(0xffffffffu, M2, 16), 0.f);
        const float2 o = ln_finish(sm * (1.f / 512.f), M2 * (1.f / 512.f));
        const float r = rcp(o.y), rh = rbf(r);
        const uint32_t mm = pack2(o.x, o.x), hl = pack2(r - rh, rh);
        m0 = __shfl_sync(0xffffffffu, mm, lane >> 2); m1 = __shfl_sync(0xffffffffu, mm, (lane >> 2) + 8);
        l0 = __shfl_sync(0xffffffffu, hl, lane >> 2); l1 = __shfl_sync(0xffffffffu, hl, (lane >> 2) + 8);
        h0 = __byte_perm(l0, 0, 0x3232); h1 = __byte_perm(l1, 0, 0x3232); l0 = __byte_perm(l0, 0, 0x1010); l1 = __byte_perm(l1, 0, 0x1010);
    }
    float acc[64];
#define QNRM(i) A[i] = make_uint4(ln2(A[i].x, m0, h0, l0), ln2(A[i].y, m1, h1, l1), ln2(A[i].z, m0, h0, l0), ln2(A[i].w, m1, h1, l1))
#pragma unroll
    for (int h = 0; h < 8; h++) {
        const uint64_t db = db0 + h * (STG_B >> 4);
        const int b0 = h == 0 ? QB1 : h == QB1 ? QB2 : h == QB2 ? QB3 : 8, b1 = h == 0 ? QB2 : h == QB1 ? QB3 : 8;
        if (b0 < b1) {
            const uint4* xb = xa + (A[4 * b0 - 1].x & zero);
#pragma unroll
            for (int i = 4 * b0; i < 4 * b1; i++) { if (b0 < QB3) ldcg128p(A[i], xb + i * 32, !pre); else A[i] = ldcg128(xb + i * 32); }
            bar_sync(NB_WG + (w >> 2), 128);
        }
        QNRM(4 * h); QNRM(4 * h + 1); QNRM(4 * h + 2); QNRM(4 * h + 3);
        if (h == 2 || h == 5) bar_sync(NB_REL + (h == 5) * 2 + (w >> 2), 160);
        if (h) wg_wait<1>();
        wg_fence();
        if (h) wgmma128r<true>(acc, A[4 * h], db); else wgmma128r<false>(acc, A[0], db);
        wgmma128r<true>(acc, A[4 * h + 1], db + 128);
        wgmma128r<true>(acc, A[4 * h + 2], db + 512);
        wgmma128r<true>(acc, A[4 * h + 3], db + 640);
        wg_commit();
        if (h >= 2) mbar_arrive1_cluster(rel + (h - 2) * 8);
    }
    ph ^= 1;
    pre = 0;
#pragma unroll 1
    for (int u = 1;; u++) {
        mbar_wait(sb + B_BAR + (BB_SF + (w >> 2)) * 8, (nd & 1) ^ 1);
        if (u < nu) mbar_wait(full, ph);
        wg_wait<1>();
        mbar_arrive1_cluster(rel + 48);
        wg_wait<0>();
        mbar_arrive1_cluster(rel + 56);
        uint4 o[8];
#pragma unroll
        for (int n = 0; n < 8; n++) {
            const float* a = acc + (n >> 1) * 16 + (n & 1) * 2;
            o[n] = make_uint4(pack2(a[0], a[1]), pack2(a[4], a[5]), pack2(a[8], a[9]), pack2(a[12], a[13]));
            sts128(lo + n * 512, o[n].x, o[n].y, o[n].z, o[n].w);
        }
        __syncwarp();
        mbar_arrive1(sb + B_BAR + (BB_DONE + (w >> 2)) * 8);
        nd++;
        CPROF(min(2 + u, 7));
        if (u == nu) break;
        if (LAGQ) { if (w >> 2) mbar_wait(sb + B_BAR + BB_GO * 8, ng & 1); ng++; }
        unsigned v;
        asm volatile("ld.relaxed.gpu.global.u32 %0,[%1];" : "=r"(v) : "l"(dn) : "memory");
        const uint64_t db1 = mkdesc(sb + (u >> 10), 4096, 1024, 1);
#pragma unroll
        for (int h = 0; h < 8; h++) {
            const uint64_t db = db1 + h * (STG_B >> 4);
            if (h) { mbar_wait(full + h * 8, ph); wg_wait<1>(); }
            if (QPOS == 0) {
            if (h == 2) pre = u + 1 == nu && v >= need;
            if (h >= 2 && h - 2 < QB3) {
#pragma unroll
                for (int i = 4 * (h - 2); i < 4 * (h - 1); i++) ldcg128p(A[i], xn + i * 32, pre);
            }
            }
            wg_fence();
            if (h) wgmma128r<true>(acc, A[4 * h], db); else wgmma128r<false>(acc, A[0], db);
            wgmma128r<true>(acc, A[4 * h + 1], db + 128);
            wgmma128r<true>(acc, A[4 * h + 2], db + 512);
            wgmma128r<true>(acc, A[4 * h + 3], db + 640);
            wg_commit();
            if (h >= 2) mbar_arrive1_cluster(rel + (h - 2) * 8);
            if (h == LAGQ - 1 && w == 2) mbar_arrive1(sb + B_BAR + BB_GO * 8);
            if (QPOS == 1) {
            if (h == 2) pre = u + 1 == nu && v >= need;
            if (h >= 2 && h - 2 < QB3) {
#pragma unroll
                for (int i = 4 * (h - 2); i < 4 * (h - 1); i++) ldcg128p(A[i], xn + i * 32, pre);
            }
            }
        }
        ph ^= 1;
    }
}

template <int NB>
__device__ __forceinline__ void load_resid(uint32_t* r, int layer, int ch, int w, int cb) {
#pragma unroll
    for (int i = 0; i < NB; i++) {
        const uint4 v = ldcg128(g_xA[layer] + ((ch * 8 + w) * 32 + cb + i) * 32 + (threadIdx.x & 31));
        r[4 * i] = v.x; r[4 * i + 1] = v.y; r[4 * i + 2] = v.z; r[4 * i + 3] = v.w;
    }
}
template <int NS>
__device__ __forceinline__ void part_load(uint4* v, int layer, int ch, int w, int cb, int ns) {
    const uint4* src = g_pp[layer] + (size_t)ch * MAXSPLIT * 8192 + (w * 32 + cb) * 32 + (threadIdx.x & 31);
#pragma unroll
    for (int i = 0; i < 2 * NS; i++) {
        asm volatile("{.reg .pred p; .reg .b128 t; setp.gt.s32 p,%6,0; mov.b128 t,{0,0,0,0}; @p ld.relaxed.gpu.global.L2::cache_hint.b128 t,[%4],%5; mov.b128 {%0,%1,%2,%3},t;}"
                     : "=r"(v[i].x), "=r"(v[i].y), "=r"(v[i].z), "=r"(v[i].w) : "l"(src + (i / NS) * 32 + (i % NS) * 8192), "l"(POL_LAST), "r"(ns - i % NS) : "memory");
    }
}
template <int NS>
__device__ __forceinline__ void part_sum(float* x, const uint4* v, const uint32_t* r) {
    const int dg = ((threadIdx.x & 31) >> 2) - 2 * (threadIdx.x & 3);
    const uint32_t idm = dg == 0 ? 0x00003f80u : dg == 1 ? 0x3f800000u : 0u;
#pragma unroll
    for (int b = 0; b < 2; b++) {
        float* y = x + b * 8;
#pragma unroll
        for (int i = 0; i < 8; i++) y[i] = 0;
#pragma unroll
        for (int s = 0; s < NS; s++) { mma8(y, v[b * NS + s].x, v[b * NS + s].y, idm); mma8(y + 4, v[b * NS + s].z, v[b * NS + s].w, idm); }
#pragma unroll
        for (int i = 0; i < 4; i++) { y[2 * i] = rbf(rbf(y[2 * i]) + blo(r[b * 4 + i])); y[2 * i + 1] = rbf(rbf(y[2 * i + 1]) + bhi(r[b * 4 + i])); }
    }
}

__device__ __forceinline__ float4 row_stats32(const float* x) {
    float a = (x[0] + x[1]) + (x[4] + x[5]) + (x[8] + x[9]) + (x[12] + x[13]);
    float b = (x[2] + x[3]) + (x[6] + x[7]) + (x[10] + x[11]) + (x[14] + x[15]);
    a += __shfl_xor_sync(0xffffffffu, a, 1); b += __shfl_xor_sync(0xffffffffu, b, 1);
    a += __shfl_xor_sync(0xffffffffu, a, 2); b += __shfl_xor_sync(0xffffffffu, b, 2);
    const float ma = a * (1.f / 32.f), mb = b * (1.f / 32.f);
    float qa = 0, qb = 0;
#pragma unroll
    for (int i = 0; i < 4; i++) {
        float d0 = x[4 * i] - ma, d1 = x[4 * i + 1] - ma, d2 = x[4 * i + 2] - mb, d3 = x[4 * i + 3] - mb;
        qa += d0 * d0 + d1 * d1; qb += d2 * d2 + d3 * d3;
    }
    qa += __shfl_xor_sync(0xffffffffu, qa, 1); qb += __shfl_xor_sync(0xffffffffu, qb, 1);
    qa += __shfl_xor_sync(0xffffffffu, qa, 2); qb += __shfl_xor_sync(0xffffffffu, qb, 2);
    return make_float4(a, qa, b, qb);
}

__device__ __forceinline__ void conv_stage(float* Y, uint32_t pbase, uint32_t ubase) {
    const int lane = threadIdx.x & 31, w = threadIdx.x >> 5, g = lane >> 2, c = lane & 3;
#pragma unroll
    for (int cp = 0; cp < 2; cp++) {
        const int chl = w * 4 + cp * 2 + (lane >> 4);
        const uint4 b = ldsm4(ubase + chl * 256 + ((lane >> 3) & 1) * 128 + (((lane & 7) ^ (chl & 7)) << 4));
#pragma unroll
        for (int h = 0; h < 2; h++) {
            const uint32_t pa = pbase + ((w * 4 + cp * 2 + h) * PW + 16 + g - 2 * c) * 4;
            uint32_t lo = lds32(pa - 32);
#pragma unroll
            for (int d = 0; d < 8; d++) {
                const uint32_t a0 = lds32(pa + d * 64), a1 = lds32(pa + d * 64 + 32);
                mma16(Y + ((cp * 2 + h) * 8 + d) * 4, a0, a1, lo, a0, h ? b.z : b.x, h ? b.w : b.y);
                lo = a1;
            }
        }
    }
}

__device__ __forceinline__ void conv_combine(const float* y8, float* cur, float* nxt) {
    const int lane = threadIdx.x & 31, c = lane & 3;
    cur[0] = y8[0]; cur[1] = y8[1] + y8[4]; cur[2] = y8[2]; cur[3] = y8[3] + y8[6];
    nxt[0] = y8[29]; nxt[1] = 0.f; nxt[2] = y8[31]; nxt[3] = 0.f;
#pragma unroll
    for (int e = 1; e < 4; e++) {
        const int src = (lane & ~3) | ((c - e) & 3);
        const float v0 = __shfl_sync(0xffffffffu, y8[8 * e] + y8[8 * e - 3], src), v1 = __shfl_sync(0xffffffffu, y8[8 * e + 1] + y8[8 * e + 4], src);
        const float v2 = __shfl_sync(0xffffffffu, y8[8 * e + 2] + y8[8 * e - 1], src), v3 = __shfl_sync(0xffffffffu, y8[8 * e + 3] + y8[8 * e + 6], src);
        if (c >= e) { cur[0] += v0; cur[1] += v1; cur[2] += v2; cur[3] += v3; }
        else { nxt[0] += v0; nxt[1] += v1; nxt[2] += v2; nxt[3] += v3; }
    }
}

__device__ __forceinline__ void hist_task(float* Y, uint32_t sb, int w, int ch, int q, int& st, uint32_t& ph, int nd) {
    const int lane = threadIdx.x & 31, chl = w * 2 + (lane >> 4);
    const uint32_t ua = sb + 12288 + chl * 256 + ((lane >> 3) & 1) * 128 + (((lane & 7) ^ (chl & 7)) << 4);
    const uint32_t pa = sb + (w * 2 * PW + 16 + (lane >> 2) - 2 * (lane & 3)) * 4;
#pragma unroll
    for (int i = 0; i < 128; i++) Y[i] = 0;
    uint4 b1 = make_uint4(0, 0, 0, 0);
#pragma unroll 1
    for (int j = ch + 1; j >= 2; j--) {
        const uint4 b0 = b1;
        mbar_wait(sb + B_BAR + (BB_FULL + st) * 8, ph);
        b1 = ldsm4(ua + st * STG_B);
        if (j == 2) b1 = make_uint4(0, 0, 0, 0);
#pragma unroll
        for (int h = 0; h < 2; h++) {
            const uint32_t o = pa + st * STG_B + h * PW * 4;
            uint32_t lo = lds32(o - 32);
#pragma unroll
            for (int d = 0; d < 8; d++) {
                const uint32_t a0 = lds32(o + d * 64), a1 = lds32(o + d * 64 + 32);
                mma16(Y + (h * 16 + d) * 4, a0, a1, lo, a0, h ? b0.z : b0.x, h ? b0.w : b0.y);
                mma16(Y + (h * 16 + 8 + d) * 4, a0, a1, lo, a0, h ? b1.z : b1.x, h ? b1.w : b1.y);
                lo = a1;
            }
        }
        bar_sync(NB_WG + (w >> 2), 128);
        stage_release(sb, w, st);
        if (++st == NSTG) { st = 0; ph ^= 1; }
    }
    mbar_wait(sb + B_BAR + (BB_SF + (w >> 2)) * 8, (nd & 1) ^ 1);
#pragma unroll
    for (int h = 0; h < 2; h++) {
        const int o = ((ch * 16 + (q >> 1)) * 4 + (w & 1) * 2 + h) * 256 + ((q & 1) * 4 + (w >> 1)) * 32 + lane;
        float c0[4], n0[4], c1[4], n1[4];
        conv_combine(Y + h * 64, c0, n0); conv_combine(Y + h * 64 + 32, c1, n1);
        g_carry[0][o] = make_float4(c0[0], c0[1], c0[2], c0[3]);
        g_carry[0][o + 16384] = make_float4(c1[0] + n0[0], c1[1] + n0[1], c1[2] + n0[2], c1[3] + n0[3]);
        g_carry[1][o + 32768] = make_float4(n1[0], n1[1], n1[2], n1[3]);
    }
}

__device__ __forceinline__ void conv_task(const Params& p, float* Y, uint32_t sb, int w, int ch, int q, int ns, bool dry, int& st, uint32_t& ph, int nd) {
    const int tid = threadIdx.x, lane = tid & 31, g = lane >> 2, c = lane & 3;
    uint32_t dk[4];
    const uint32_t sg = (~ch & 2) << 30;
    int sr = st;
    float x[16];
    PROF(tid == 128, 2048 + ch * 8);
#pragma unroll
    for (int i = 0; i < 128; i++) Y[i] = 0;
#pragma unroll 1
    for (int j = min(ch, 1 + (ch & 1)); j >= 1; j--) {
        mbar_wait(sb + B_BAR + (BB_FULL + st) * 8, ph);
        conv_stage(Y, sb + st * STG_B, sb + B_UT + ((ch - j) & 1) * 8192);
        if (++st == NSTG) { st = 0; ph ^= 1; }
    }
#define CONV_CARRY _Pragma("unroll 1") \
    for (int i = 0; i < min(ch, (ch & 1) ? 2 : 3); i++) { \
        if (i) mbar_wait(sb + B_BAR + (BB_FULL + st) * 8, ph); \
        const uint32_t ca = sb + (i ? st * STG_B : B_SP) + tid * 16; \
_Pragma("unroll") \
        for (int k = 0; k < 4; k++) { \
            const uint4 cr = lds128(ca + k * 4096); \
            Y[k * 32] += __uint_as_float(cr.x); Y[k * 32 + 1] += __uint_as_float(cr.y); Y[k * 32 + 2] += __uint_as_float(cr.z); Y[k * 32 + 3] += __uint_as_float(cr.w); \
        } \
        if (i && ++st == NSTG) { st = 0; ph ^= 1; } \
    } \
    bar_sync(NB_C, 256); \
_Pragma("unroll 1") \
    for (; sr != st; sr = (sr + 1) & (NSTG - 1)) stage_release(sb, w, sr); \
    mbar_wait(sb + B_BAR + (BB_SF + (w >> 2)) * 8, (nd & 1) ^ 1); \
    mbar_wait(sb + B_BAR + (BB_SF + 1 - (w >> 2)) * 8, (nd & 1) ^ 1);
    const uint32_t ut = sb + B_UT + (ch & 1) * 8192;
    if (CPOS == 0) { CONV_CARRY }
    PROF(tid == 128, 2048 + ch * 8 + 7);
    {
        uint4 v[2 * OPS1];
        wait_cnt_warp(cnt_ptr(C_OP0 + (q >> 3) * 2 + (w >> 2), ch + (w & 3) * 16), ns);
        part_load<OPS1>(v, 0, ch, w, 2 * q, ns);
        uint32_t rs[8];
        load_resid<2>(rs, 0, ch, w, 2 * q);
        if (CPOS == 1) { CONV_CARRY }
        part_sum<OPS1>(x, v, rs);
        const float4 s = row_stats32(x);
        float2* dst = g_st2 + ((ch & 1) * 16 + q) * 128 + w * 16 + g + c * 8;
        asm volatile("{.reg .pred p; setp.ne.u32 p,%2,0; @p st.relaxed.gpu.global.b64 [%0],%1;}" ::"l"(dst),
                     "l"(((uint64_t)((__float_as_uint(c ? s.w : s.y) & 0x7fffffffu) | sg) << 32) | __float_as_uint(c ? s.z : s.x)), "r"((uint32_t)(c < 2 && !dry)) : "memory");
        PROF(tid == 128, 2048 + ch * 8 + 1);
    }
#pragma unroll
    for (int i = 0; i < 4; i++) asm volatile("ld.global.nc.u32 %0,[%1];" : "=r"(dk[i]) : "l"(p.Dskip + q * 32 + i * 8 + 2 * c));
    if (CPOS == 2) { CONV_CARRY }
    float2 ln0, ln1;
    {
        const float2* src = g_st2 + ((ch & 1) * 16 + (lane >> 4) * 8) * 128 + w * 16 + (lane & 15);
        uint64_t v[8];
        int n = 0;
#pragma unroll
        for (int i = 0; i < 8; i++) v[i] = (uint64_t)~sg << 32;
        while (true) {
            bool bad = false;
#pragma unroll
            for (int i = 0; i < 8; i++) asm volatile("{.reg .pred p; setp.lt.s32 p,%2,0; @p ld.relaxed.gpu.global.b64 %0,[%1];}" : "+l"(v[i]) : "l"(src + i * 128), "r"((uint32_t)(v[i] >> 32) ^ sg) : "memory");
#pragma unroll
            for (int i = 0; i < 8; i++) bad = bad || (int)((uint32_t)(v[i] >> 32) ^ sg) < 0;
            if (!__any_sync(0xffffffffu, bad && !dry)) break;
            if (++n > 2000000) __trap();
        }
        float sm = 0;
#pragma unroll
        for (int i = 0; i < 8; i++) sm += __uint_as_float((uint32_t)v[i]);
        sm += __shfl_xor_sync(0xffffffffu, sm, 16);
        const float mean = sm * (1.f / 512.f);
        float M2 = 0;
#pragma unroll
        for (int i = 0; i < 8; i++) { const float d = __uint_as_float((uint32_t)v[i]) * (1.f / 32.f) - mean; M2 += fabsf(__uint_as_float((uint32_t)(v[i] >> 32))) + 32.f * d * d; }
        M2 += __shfl_xor_sync(0xffffffffu, M2, 16);
        const float2 o = ln_finish(mean, M2 * (1.f / 512.f));
        ln0.x = __shfl_sync(0xffffffffu, o.x, g); ln0.y = __shfl_sync(0xffffffffu, o.y, g);
        ln1.x = __shfl_sync(0xffffffffu, o.x, g + 8); ln1.y = __shfl_sync(0xffffffffu, o.y, g + 8);
    }
    PROF(tid == 128, 2048 + ch * 8 + 2);
    uint32_t u[8];
#pragma unroll
    for (int i = 0; i < 8; i++) {
        const float2 l = (i & 1) ? ln1 : ln0;
        u[i] = pack2(__fdividef(rbf(x[2 * i] - l.x), l.y), __fdividef(rbf(x[2 * i + 1] - l.x), l.y));
        const int chl = (i >> 1) * 8 + g;
        sts32(ut + chl * 256 + (i & 1) * 128 + ((w ^ g) << 4) + c * 4, movm(u[i]));
    }
    bar_sync(NB_C, 256);
    mbar_wait(sb + B_BAR + (BB_FULL + st) * 8, ph);
    PROF(tid == 128, 2048 + ch * 8 + 3);
    conv_stage(Y, sb + st * STG_B, ut);
    uint32_t yp[4][2];
    float nxt[4][4];
    {
        float y[4][4];
#pragma unroll
        for (int k = 0; k < 4; k++) conv_combine(Y + k * 32, y[k], nxt[k]);
#pragma unroll
        for (int i = 0; i < 4; i++) { yp[i][0] = pack2(y[0][i], y[1][i]); yp[i][1] = pack2(y[2][i], y[3][i]); }
    }
#pragma unroll
    for (int i = 0; i < 4; i++) sts64(sb + B_YT + (16 * (2 * c + (i & 1)) + g + (i >> 1) * 8) * 80 + w * 8, yp[i][0], yp[i][1]);
    bar_sync(NB_C, 256);
    stage_release(sb, w, st);
    if (++st == NSTG) { st = 0; ph ^= 1; }
    PROF(tid == 128, 2048 + ch * 8 + 4);
    uint32_t xo[8];
    uint4* dA = g_xA[1] + ((ch * 8 + w) * 32 + 2 * q) * 32 + lane;
#pragma unroll
    for (int i = 0; i < 8; i++) {
        const int col = (i >> 1) * 8 + 2 * c;
        const uint32_t yv = lds32(sb + B_YT + (w * 16 + g + (i & 1) * 8) * 80 + col * 2);
        const uint32_t dv = dk[i >> 1];
        x[2 * i] = rbf(x[2 * i] + rbf(blo(yv) + rbf(blo(u[i]) * blo(dv))));
        x[2 * i + 1] = rbf(x[2 * i + 1] + rbf(bhi(yv) + rbf(bhi(u[i]) * bhi(dv))));
        xo[i] = pack2(x[2 * i], x[2 * i + 1]);
        if ((i & 3) == 3) dA[(i >> 2) * 32] = make_uint4(xo[i - 3], xo[i - 2], xo[i - 1], xo[i]);
    }
    {
        const float4 s = row_stats32(x);
        float2* dst = g_st[1] + (ch * 16 + q) * 128 + w * 16 + g;
        if (c == 0) dst[0] = make_float2(s.x, s.y);
        if (c == 1) dst[8] = make_float2(s.z, s.w);
        __syncwarp();
    }
    PROF(tid == 128, 2048 + ch * 8 + 5);
    mbar_arrive1(sb + B_BAR + (BB_DONE + (w >> 2)) * 8);
    bar_sync(NB_C, 256);
#pragma unroll
    for (int k = 0; k < 4; k++) sts128(sb + B_SP + k * 4096 + tid * 16, __float_as_uint(nxt[k][0]), __float_as_uint(nxt[k][1]), __float_as_uint(nxt[k][2]), __float_as_uint(nxt[k][3]));
    PROF(tid == 128, 2048 + ch * 8 + 6);
}

__device__ __forceinline__ void out_store(const Params& p, const float* x, int ch, int cb, bool on) {
    const int lane = threadIdx.x & 31, w = threadIdx.x >> 5, g = lane >> 2, c = lane & 3;
#pragma unroll
    for (int h = 0; h < 2; h++) {
        const float* y = x + h * 2;
        uint32_t v0 = pack2(y[0], y[1]), v1 = pack2(y[4], y[5]), v2 = pack2(y[8], y[9]), v3 = pack2(y[12], y[13]);
        uint32_t t0 = (c & 1) ? v0 : v1, t1 = (c & 1) ? v2 : v3;
        t0 = __shfl_xor_sync(0xffffffffu, t0, 1); t1 = __shfl_xor_sync(0xffffffffu, t1, 1);
        if (c & 1) { v0 = t0; v2 = t1; } else { v1 = t0; v3 = t1; }
        t0 = (c & 2) ? v0 : v2; t1 = (c & 2) ? v1 : v3;
        t0 = __shfl_xor_sync(0xffffffffu, t0, 2); t1 = __shfl_xor_sync(0xffffffffu, t1, 2);
        if (c & 2) { v0 = t0; v1 = t1; } else { v2 = t0; v3 = t1; }
        asm volatile("{.reg .pred p; setp.ne.u32 p,%6,0; @p st.global.L2::cache_hint.v4.u32 [%0],{%1,%2,%3,%4},%5;}"
                     ::"l"(p.out + (size_t)(ch * 128 + w * 16 + g + h * 8) * 512 + cb * 16 + c * 8), "r"(v0), "r"(v1), "r"(v2), "r"(v3), "l"(POL_LATE), "r"((uint32_t)on));
    }
}
__device__ __forceinline__ void fin_task(const Params& p, int ch, int cb0, int ncb, int ns, bool dry) {
    const int w = threadIdx.x >> 5;
    uint32_t rs[8];
    wait_cnt_warp(cnt_ptr(C_CV, ch), 32);
    load_resid<2>(rs, 1, ch, w, cb0);
    wait_cnt_warp(cnt_ptr(C_OP1, ch), dry ? 0 : 256);
    for (int cb = cb0; cb < cb0 + ncb; cb += 2) {
        float x[16];
        if (cb != cb0) load_resid<2>(rs, 1, ch, w, cb);
        uint4 v[32];
        part_load<16>(v, 1, ch, w, cb, ns);
        part_sum<16>(x, v, rs);
        out_store(p, x, ch, cb, !dry);
    }
}

__device__ __forceinline__ void bulk_consumer(const Params& p, uint32_t sb, int cl, uint32_t rank, int w) {
    int st = 0; uint32_t ph = 0; int nd = 0, ng = 0;
    for (int ti = 0; ti < MAXT; ti++) {
        const Task t = task_of(p.task[list_of(cl)][ti], rank);
        const int type = t.type, layer = t.layer, ch = t.ch;
        if (type == T_END) break;
        bool staged = type != T_FIN;
        PROF(threadIdx.x == 0, 3600 + ti * 4);
        CPROF(0);
        if (type == T_QKV) {
            staged = false;
            #pragma unroll 1
            while (st) {
                if (!(w & 3)) { mbar_wait(sb + B_BAR + (BB_FULL + st) * 8, ph); stage_release(sb, 0, st); stage_release(sb, 1, st); }
                if (++st == NSTG) { st = 0; ph ^= 1; }
            }
            uint4 A[32];
#pragma unroll
            for (int i = 0; i < 32; i++) A[i] = make_uint4(0, 0, 0, 0);
            uint32_t pre = 0;
            Task c = t;
#pragma unroll 1
            while (true) {
                const Task n = task_of(p.task[list_of(cl)][ti + 1], rank);
                if (w == 3) { sts32(sb + B_ST + 8, ph); bar_arrive(NB_PH, 64); }
                qkv_task(sb, w, c.layer, c.ch, c.b, ng, nd, ph, ti, p.zero, A, pre, g_xA[n.layer] + (n.ch * 8 + w) * 1024 + (threadIdx.x & 31),
                         cnt_ptr(C_CV, n.ch), n.type != T_QKV || !QPRE ? ~0u : n.layer ? 32 : 0);
                PROF(threadIdx.x == 128, 3600 + ti * 4 + 1);
                if (n.type != T_QKV) break;
                PROF(threadIdx.x == 128, 3600 + ti * 4 + 2);
                c = n; ti++;
                PROF(threadIdx.x == 0, 3600 + ti * 4);
                { const int layer = c.layer; CPROF(0); }
            }
        } else if (type == T_OP) {
            const int lane = threadIdx.x & 31;
            float acc[128];
            uint32_t r0 = sb + B_BAR + BB_IDLE * 8, r1 = r0;
            if (w >> 2) { mbar_wait(sb + B_BAR + BB_GO * 8, ng & 1); if ((t.c & 80) == 16) mbar_wait(sb + B_BAR + BB_LOW * 8, 0); }
            ng++;
            gemm_run<false>(acc, sb, w, 0, 1, r0, r1, st, ph);
            gemm_run<true>(acc, sb, w, 1, 2 * t.b, r0, r1, st, ph);
            mbar_wait(sb + B_BAR + (BB_SF + (w >> 2)) * 8, (nd & 1) ^ 1);
            wg_wait<1>();
            mbar_arrive1_cluster(r0);
            wg_wait<0>();
            mbar_arrive1_cluster(r1);
            PROF(threadIdx.x == 128, 3600 + ti * 4 + 1);
            if (t.c & 32) {
                staged = false;
                const int dg = (lane >> 2) - 2 * (lane & 3);
                const uint32_t idm = dg == 0 ? 0x00003f80u : dg == 1 ? 0x3f800000u : 0u;
                wait_cnt_warp(cnt_ptr(C_OP1, ch), 256 - 4 * t.b);
#pragma unroll 1
                for (int i = 0; i < (t.c & 15); i++) {
                    const uint4* src = op_dst(1, ch, i, w, (t.blk >> 2) & 1) + lane;
                    uint4 v[16];
#pragma unroll
                    for (int j = 0; j < 16; j++) v[j] = ldcg128_last(src + j * 32);
#pragma unroll
                    for (int j = 0; j < 16; j++) { mma8(acc + j * 8, v[j].x, v[j].y, idm); mma8(acc + j * 8 + 4, v[j].z, v[j].w, idm); }
                }
#pragma unroll
                for (int j = 0; j < 16; j += 4) {
                    uint32_t rs[16];
                    load_resid<4>(rs, 1, ch, w, (t.blk & 4) * 4 + j);
#pragma unroll
                    for (int i = 0; i < 16; i++) { float* y = acc + j * 8 + 2 * i; y[0] = rbf(y[0]) + blo(rs[i]); y[1] = rbf(y[1]) + bhi(rs[i]); }
                    out_store(p, acc + j * 8, ch, (t.blk & 4) * 4 + j, true); out_store(p, acc + j * 8 + 16, ch, (t.blk & 4) * 4 + j + 2, true);
                }
            } else if (!layer) {
                const int s2 = st + (w >> 1);
                const uint32_t o = sb + (s2 & (NSTG - 1)) * STG_B + (w & 1) * 8192 + lane * 16;
                mbar_wait(sb + B_BAR + (BB_FULL + (s2 & (NSTG - 1))) * 8, ph ^ (s2 >= NSTG));
#pragma unroll
                for (int j = 0; j < 16; j++)
                    sts128(o + j * 512, pack2(acc[j * 8], acc[j * 8 + 1]), pack2(acc[j * 8 + 2], acc[j * 8 + 3]), pack2(acc[j * 8 + 4], acc[j * 8 + 5]), pack2(acc[j * 8 + 6], acc[j * 8 + 7]));
                sts32(sb + B_ST + (w >> 2) * 4, st);
                st += 4;
                if (st >= NSTG) { st -= NSTG; ph ^= 1; }
            } else {
                uint4* dst = op_dst(layer, ch, t.c & 15, w, (t.blk >> 2) & 1) + lane;
#pragma unroll
                for (int n = 0; n < 16; n++) {
                    const int j = (n >> 1) + (n & 1) * 8;
                    const uint4 v = make_uint4(pack2(acc[j * 8], acc[j * 8 + 1]), pack2(acc[j * 8 + 2], acc[j * 8 + 3]), pack2(acc[j * 8 + 4], acc[j * 8 + 5]), pack2(acc[j * 8 + 6], acc[j * 8 + 7]));
                    if (j < 16 - NSB) stg128(dst + j * 32, v, out_pol(T_OP, layer, ch)); else sts128(sb + B_OUT + (w * NSB + j - (16 - NSB)) * 512 + lane * 16, v.x, v.y, v.z, v.w);
                }
            }
        } else if (type == T_CV) {
            float acc[128];
            if (layer) hist_task(acc, sb, w, ch, t.a + rank, st, ph, nd);
            else { conv_task(p, acc, sb, w, ch, t.a + rank, t.b, t.dry, st, ph, nd); staged = false; nd++; }
        } else {
            fin_task(p, ch, t.a + rank * t.c, t.c, t.b, t.dry);
        }
        if (staged) {
            __syncwarp();
            mbar_arrive1(sb + B_BAR + (BB_DONE + (w >> 2)) * 8);
            nd++;
        }
        PROF(threadIdx.x == 128, 3600 + ti * 4 + 2);
        __syncwarp();
    }
}

constexpr int P_Y = 131072  , P_PRM = P_Y  , P_K6 = P_PRM + 8192  ,
              P_P = P_Y + 40960  , P_U = P_P + 33280  , P_END = P_U + 17408, P_X = 98304  ;
static_assert(P_END <= B_BAR && P_END <= R_BAR, "prologue scratch");
#define KGUN 2
constexpr int KGU = KGUN;
__device__ __forceinline__ void csq(float& r, float& i) { const float t = r * i; r = fmaf(r, r, -(i * i)); i = t + t; }
__device__ __forceinline__ void cpow(float ar, float ph, float p, float& r, float& i) {
    const float e = ex2(ar * p);
    const float u = ph * p, n = fabsf(u) < 4194304.f ? (u + 12582912.f) - 12582912.f : u;
    const float t = (u - n) * 6.283185307179586f;
    r = e * __cosf(t); i = e * __sinf(t);
}
__device__ __forceinline__ void mma_tf32(float* c, float a0, float a1, float a2, float a3, float b0, float b1) {
    asm volatile("mma.sync.aligned.m16n8k8.row.col.f32.tf32.tf32.f32 {%0,%1,%2,%3},{%4,%5,%6,%7},{%8,%9},{%0,%1,%2,%3};"
                 : "+f"(c[0]), "+f"(c[1]), "+f"(c[2]), "+f"(c[3])
                 : "r"(__float_as_uint(a0)), "r"(__float_as_uint(a1)), "r"(__float_as_uint(a2)), "r"(__float_as_uint(a3)), "r"(__float_as_uint(b0)), "r"(__float_as_uint(b1)));
}

struct ProRegs { uint32_t v[2][4], ldt[2]; };
__device__ __forceinline__ void prologue_load(const ProArgs& a, int b, ProRegs& pr) {
    const int w = threadIdx.x >> 5;
#pragma unroll
    for (int i = 0; i < 2; i++) {
        const int gi = b * 512 + (w & 3) * 128 + ((w >> 2) & 1) * 64 + i * 32 + (threadIdx.x & 31);
        pr.ldt[i] = __ldg((const uint16_t*)a.ldt + b * 4 + (w & 3));
        pr.v[i][0] = __ldg((const uint16_t*)a.lAr + gi); pr.v[i][1] = __ldg((const uint16_t*)a.Ai + gi);
        pr.v[i][2] = __ldg((const uint16_t*)a.Cr + gi); pr.v[i][3] = __ldg((const uint16_t*)a.Ci + gi);
    }
}
__device__ __forceinline__ void prologue(const ProArgs& a, uint32_t sb, int b, int w, const ProRegs& pr, uint32_t zero, int lag) {
    const int tid = threadIdx.x, lane = tid & 31, g = lane >> 2, c = lane & 3;
    const int d0 = b * 4;
    if (w >= 8) {
        const int t2 = tid - 256;
        PROF(t2 == 0, 3516);
        const int gi = b * 128 + t2;
        if (t2 < 32) acc_init(a.mem0, b * 32 + t2, lag);
        if (t2 >= 112) ((uint4*)g_st2)[b * 16 + t2 - 112] = make_uint4(0, 0, 0, 0);
        if (gi < 13 * 64) g_cnt[gi] = 0;
        bar_sync(6, 384);
        if (gi < 512) g_st[0][(gi >> 8) * 2048 + (lds32(sb + S_TAG) ^ 1) * 256 + (gi & 255)] = make_float2(0.f, 0.f);
        asm volatile("{.reg .pred p; elect.sync _|p,0xffffffff; @p cp.async.bulk.prefetch.L2.global [%0],32768;}"
                     ::"l"((w == 8 ? a.Wq : w == 9 ? a.Wk : w == 10 ? a.Wv : a.Wo) + (size_t)b * 16384) : "memory");
        mbar_wait(sb + S_XBAR, 0);
        uint32_t l[16];
        int n = 0;
        while (true) {
            bool ok = true;
#pragma unroll
            for (int i = 0; i < 16; i++) asm volatile("ld.relaxed.gpu.global.u32 %0,[%1];" : "=r"(l[i]) : "l"(g_ln0 + i * 128 + t2) : "memory");
#pragma unroll
            for (int i = 0; i < 16; i++) ok = ok && l[i];
            if (__all_sync(0xffffffffu, ok)) break;
            if (++n > 2000000) __trap();
        }
#pragma unroll 1
        for (int h = 0; h < 2; h++) {
#pragma unroll
            for (int i = 0; i < 8; i++) {
                const int t = h * 1024 + i * 128 + t2;
                const uint2 x = lds64(sb + P_X + t * 16 + (b & 1) * 8);
                const float m = blo(l[i]), rs = rcp(bhi(l[i]));
                l[i] = l[i + 8];
                const uint32_t u0 = pack2(rbf(blo(x.x) - m) * rs, rbf(bhi(x.x) - m) * rs), u1 = pack2(rbf(blo(x.y) - m) * rs, rbf(bhi(x.y) - m) * rs);
                sts128(sb + P_X + t * 16, x.x, x.y, u0, u1);
                const uint32_t o = sb + P_U + ((t >> 3) & 1) * 2176 + ((t >> 4) + 8) * 16 + (t & 7) * 2;
                asm volatile("st.shared.u16 [%0],%1;" ::"r"(o), "h"((uint16_t)u0) : "memory");
                asm volatile("st.shared.u16 [%0],%1;" ::"r"(o + 4352), "h"((uint16_t)(u0 >> 16)) : "memory");
                asm volatile("st.shared.u16 [%0],%1;" ::"r"(o + 8704), "h"((uint16_t)u1) : "memory");
                asm volatile("st.shared.u16 [%0],%1;" ::"r"(o + 13056), "h"((uint16_t)(u1 >> 16)) : "memory");
            }
        }
        PROF(t2 == 0, 3517);
        bar_sync(9, 384);
        fence_async_smem();
#pragma unroll 1
        for (int j = 0; j < 16; j++) {
            const int d = d0 + w - 8;
            asm volatile("{.reg .pred p; elect.sync _|p,0xffffffff; @p cp.async.bulk.global.shared::cta.bulk_group [%0],[%1],%2;}" ::"l"(g_P + (((d >> 5) * 16 + j) * 32 + (d & 31)) * PW),
                         "r"(sb + P_P + ((w - 8) * 2080 + j * 128) * 4), "r"(PW * 4) : "memory");
        }
        asm volatile("cp.async.bulk.commit_group; cp.async.bulk.wait_group 0;" ::: "memory");
        bar_arrive(10, 384);
        return;
    }
#pragma unroll
    for (int i = 0; i < 2; i++) {
        const float dt = rbf(expf(blo(pr.ldt[i])));
        const float ar = -rbf(expf(blo(pr.v[i][0]))) * dt, ai = blo(pr.v[i][1]) * dt;
        sts128(sb + P_PRM + (w * 64 + i * 32 + lane) * 16, __float_as_uint(ar * 1.4426950408889634f), __float_as_uint(ai * 0.15915494309189535f),
               __float_as_uint(2.f * (blo(pr.v[i][2]) * dt)), __float_as_uint(2.f * (blo(pr.v[i][3]) * dt)));
    }
    if (tid < 64) sts128(sb + P_U + (tid >> 3) * 2176 + (tid & 7) * 16, 0, 0, 0, 0);
    bar_arrive(6, 384);
    __syncwarp();
    PROF(tid == 0, 3510);
    const int ch = w & 3, hf = w >> 2;
    {
        float k0[4] = {0, 0, 0, 0}, k1[4] = {0, 0, 0, 0}, k2[4] = {0, 0, 0, 0}, k3[4] = {0, 0, 0, 0}, k4[4] = {0, 0, 0, 0}, kl = 0;
#pragma unroll KGU
        for (int j = 0; j < 16; j++) {
            const uint4 q = lds128(sb + P_PRM + (w * 64 + j * 4 + c) * 16);
            const float cr = __uint_as_float(q.z), ci = __uint_as_float(q.w);
            float wr[4], wi[4], vr[4], vi[4];
            cpow(__uint_as_float(q.x), __uint_as_float(q.y), (float)g, wr[0], wi[0]);
            cpow(__uint_as_float(q.x), __uint_as_float(q.y), (float)(g + 8), vr[0], vi[0]);
#pragma unroll
            for (int i = 1; i < 4; i++) { wr[i] = wr[i - 1]; wi[i] = wi[i - 1]; csq(wr[i], wi[i]); vr[i] = vr[i - 1]; vi[i] = vi[i - 1]; csq(vr[i], vi[i]); }
            float hr = wr[3], hi = wi[3];
            csq(hr, hi);
            mma_tf32(k0, wr[0], vr[0], wi[0], vi[0], cr * hr - ci * hi, -(cr * hi + ci * hr));
            hr = vr[3]; hi = vi[3]; csq(hr, hi);
            mma_tf32(k1, wr[0], vr[0], wi[0], vi[0], cr * hr - ci * hi, -(cr * hi + ci * hr));
            csq(hr, hi);
            mma_tf32(k2, wr[1], vr[1], wi[1], vi[1], cr * hr - ci * hi, -(cr * hi + ci * hr));
            csq(hr, hi);
            mma_tf32(k3, wr[2], vr[2], wi[2], vi[2], cr * hr - ci * hi, -(cr * hi + ci * hr));
            csq(hr, hi);
            mma_tf32(k4, wr[3], vr[3], wi[3], vi[3], cr * hr - ci * hi, -(cr * hi + ci * hr));
            csq(hr, hi);
            kl += cr * hr - ci * hi;
        }
        kl += __shfl_xor_sync(0xffffffffu, kl, 1); kl += __shfl_xor_sync(0xffffffffu, kl, 2);
        const uint32_t o = sb + P_K6 + (ch * 656 + c * 32 + g) * 4, ol = sb + P_K6 + (ch * 656 + 640) * 4;
#define KST(k, base) sts32(o + (base) * 4, __float_as_uint(k[0])); sts32(o + (base) * 4 + 64, __float_as_uint(k[1])); \
                     sts32(o + (base) * 4 + 32, __float_as_uint(k[2])); sts32(o + (base) * 4 + 96, __float_as_uint(k[3]))
#define KAD(k, base) k[0] += __uint_as_float(lds32(o + (base) * 4)); k[1] += __uint_as_float(lds32(o + (base) * 4 + 64)); \
                     k[2] += __uint_as_float(lds32(o + (base) * 4 + 32)); k[3] += __uint_as_float(lds32(o + (base) * 4 + 96))
        if (hf == 0) {
            bar_sync(2 + ch, 64);
            KAD(k0, 0); KAD(k1, 128); KAD(k2, 256); KAD(k3, 384); KAD(k4, 512);
            kl += __uint_as_float(lds32(ol));
            __syncwarp();
        }
        KST(k0, 0); KST(k1, 128); KST(k2, 256); KST(k3, 384); KST(k4, 512);
        if (lane == 0) sts32(ol, __float_as_uint(kl));
        if (hf == 1) { __syncwarp(); bar_arrive(2 + ch, 64); }
    }
    PROF(tid == 0, 3511);
    bar_sync(8, 384);
    PROF(tid == 0, 3512);
    if (tid < 64) sts32(sb + P_P + ((tid >> 4) * 2080 + (tid & 15)) * 4, 0);
#pragma unroll 1
    for (int x = tid; x < 2048; x += 512) {
        uint32_t pw[2][4];
#pragma unroll
        for (int h = 0; h < 2; h++) {
            const int y = x + h * 256;
            const int i0 = y <= 256 ? y : 256 + (int)((pack2((float)y, 0.f) & 0xffff) - 0x4380);
            const int i1 = y <= 256 ? max(y - 1, 0) : 256 + (int)((pack2((float)(y - 1), 0.f) & 0xffff) - 0x4380);
#pragma unroll
            for (int k = 0; k < 4; k++) {
                const float lo = __uint_as_float(lds32(sb + P_K6 + k * 2624 + i0 * 4)), hi = __uint_as_float(lds32(sb + P_K6 + k * 2624 + i1 * 4));
                pw[h][k] = pack2(lo, y ? hi : 0.f);
            }
        }
#pragma unroll
        for (int h = 0; h < 2; h++)
#pragma unroll
            for (int k = 0; k < 4; k++) sts32(sb + P_P + (k * 2080 + x + h * 256 + 16) * 4, pw[h][k]);
    }
    bar_sync(9, 384);
    PROF(tid == 0, 3513);
    {
        float acc[16][4];
#pragma unroll
        for (int j = 0; j < 16; j++) acc[j][0] = acc[j][1] = acc[j][2] = acc[j][3] = 0;
#pragma unroll 1
        for (int e = hf * 4; e < hf * 4 + 4; e++) {
            uint32_t B[16][2];
            const uint32_t ua = sb + P_U + ch * 4352 + ((lane >> 3) & 1) * 2176 + (8 + (lane >> 4) * 8 + (lane & 7) - e) * 16;
            const uint32_t pa = sb + P_P + (ch * 2080 + 16 + e * 16 + g - 2 * c) * 4;
            uint4 A[16];
#define TLD(d) A[d] = make_uint4(lds32(pa + (d) * 512), lds32(pa + (d) * 512 + 32), lds32(pa + (d) * 512 - 32), 0)
            TLD(0); TLD(15);
#pragma unroll
            for (int j = 0; j < 8; j++) { const uint4 v = ldsm4(ua + j * 256); B[2 * j][0] = v.x; B[2 * j][1] = v.y; B[2 * j + 1][0] = v.z; B[2 * j + 1][1] = v.w; }
#pragma unroll
            for (int d = 0; d < 8; d++) {
                if (d < 7) { TLD(d + 1); TLD(14 - d); }
                A[d].w = A[d].x + zero; A[15 - d].w = A[15 - d].x + zero;
                sfence(zero);
#pragma unroll
                for (int j = 15 - d; j < 16; j++) mma16(acc[j], A[15 - d].x, A[15 - d].y, A[15 - d].z, A[15 - d].w, B[j - 15 + d][0], B[j - 15 + d][1]);
#pragma unroll
                for (int j = d; j < 16; j++) { mma16(acc[j], A[d].x, A[d].y, A[d].z, A[d].w, B[j - d][0], B[j - d][1]); sfence(zero); }
            }
        }
        PROF(tid == 0, 3514);
        const uint32_t o = sb + P_Y + (ch * 2560 + c * 40 + g) * 4;
#pragma unroll
        for (int j = 0; j < 8; j++) {
#pragma unroll
            for (int i = 0; i < 4; i++) { const float lo = acc[j][i], hi = acc[j + 8][i]; acc[j][i] = hf ? hi : lo; sts32(o + (j + 8 - hf * 8) * 640 + (i & 1) * 80 + (i >> 1) * 32, __float_as_uint(hf ? lo : hi)); }
        }
        bar_sync(2 + ch, 64);
#pragma unroll
        for (int j = 0; j < 8; j++) {
#pragma unroll
            for (int i = 0; i < 4; i++) acc[j][i] += __uint_as_float(lds32(o + (j + hf * 8) * 640 + (i & 1) * 80 + (i >> 1) * 32));
        }
#pragma unroll
        for (int j = 0; j < 8; j++) {
#pragma unroll
            for (int i = 0; i < 4; i++) sts32(o + (j + hf * 8) * 640 + (i & 1) * 80 + (i >> 1) * 32, __float_as_uint(acc[j][i]));
        }
    }
    const uint2 dk = __ldg((const uint2*)(a.Dk + d0));
    bar_sync(1, 256);
#pragma unroll 2
    for (int i = 0; i < 8; i++) {
        const int t = i * 256 + tid;
        const uint32_t o = sb + P_Y + (t + 4 * (t >> 4)) * 4;
        const uint4 xu = lds128(sb + P_X + t * 16);
        float y[4];
#pragma unroll
        for (int k = 0; k < 4; k++) y[k] = rbf(__uint_as_float(lds32(o + k * 10240)));
        uint2 r;
        r.x = pack2(blo(xu.x) + rbf(y[0] + rbf(blo(xu.z) * blo(dk.x))), bhi(xu.x) + rbf(y[1] + rbf(bhi(xu.z) * bhi(dk.x))));
        r.y = pack2(blo(xu.y) + rbf(y[2] + rbf(blo(xu.w) * blo(dk.y))), bhi(xu.y) + rbf(y[3] + rbf(bhi(xu.w) * bhi(dk.y))));
        {
            const bool up = t & 8;
            const uint32_t o = __shfl_xor_sync(0xffffffffu, up ? r.x : r.y, 8);
            ((uint2*)(g_xA[0] + ((t >> 4) * 32 + (d0 >> 4)) * 32 + (t & 7) * 4 + ((d0 >> 1) & 2) + up))[(d0 >> 3) & 1] = up ? make_uint2(o, r.y) : make_uint2(r.x, o);
        }
        if (i == 0) {
            const float e0 = blo(r.x), e1 = bhi(r.x), e2 = blo(r.y), e3 = bhi(r.y);
            asm volatile("red.relaxed.gpu.global.add.v2.f32 [%0],{%1,%2};" ::"l"(g_st[0] + (t >> 7) * 2048 + lds32(sb + S_TAG) * 256 + (b & 1) * 128 + (t & 127)),
                         "f"((e0 + e1) + (e2 + e3)), "f"((e0 * e0 + e1 * e1) + (e2 * e2 + e3 * e3)) : "memory");
        }
    }
    PROF(tid == 0, 3515);
    bar_sync(10, 384);
}

__global__ void __cluster_dims__(2, 1, 1) __launch_bounds__(384, 1) main_kernel(const __grid_constant__ Params p) {
    extern __shared__ __align__(1024) uint8_t smem[];
    const uint32_t sb = __shfl_sync(0xffffffffu, smem_u32(smem), 0);
    uint32_t rank; asm("mov.u32 %0,%%cluster_ctarank;" : "=r"(rank));
    const int wi = __shfl_sync(0xffffffffu, threadIdx.x >> 5, 0);
    const int cl = blockIdx.x >> 1, wg = wi >> 2;
    const bool rec = p.rec0 >= 0 && cl >= p.rec0 && cl < p.rec0 + 32;
    PROF(threadIdx.x == 0, 3500);
    ProRegs pr;
    if ((wi >> 1) == 4 && p.dopro && cl >= 2) {
        const int g = (threadIdx.x & 31) >> 2, c = threadIdx.x & 3, row = (blockIdx.x - 4) * 16 + (wi - 8) * 8 + g;
        const float4 r4 = row_stats((const uint4*)(p.pa.x + (size_t)row * 512) + c, 4);
        const float2 r = make_float2(r4.x + r4.z, r4.y + r4.w);
        const float2 l = ln_finish(r.x * (1.f / 512.f), fmaxf(r.y - r.x * r.x * (1.f / 512.f), 0.f) * (1.f / 512.f));
        if (c == (g >> 1)) asm volatile("st.relaxed.gpu.global.u32 [%0],%1;" ::"l"(g_ln0 + row), "r"(pack2(l.x, l.y)) : "memory");
        __syncwarp();
    }
    prologue_load(p.pa, max((int)blockIdx.x - 4, 0), pr);
    if (rec) rec_init(p, sb, cl - p.rec0, rank); else bulk_init(sb);
    if (threadIdx.x == 352 && p.dopro && cl >= 2) {
        mbar_init(sb + S_XBAR, 1);
        asm volatile("fence.mbarrier_init.release.cluster;" ::: "memory");
        mbar_expect(sb + S_XBAR, 32768);
        for (int j = 0; j < 8; j++) tma2d(sb + P_X + j * 4096, &p.tm[3], ((blockIdx.x - 4) >> 1) * 8, j * 256, sb + S_XBAR);
    }
    if (threadIdx.x == 320) {
        unsigned v;
        asm volatile("ld.relaxed.gpu.global.u32 %0,[%1];" : "=r"(v) : "l"(g_gate) : "memory");
        v = v / (4 * NCL) + p.dopro;
        sts64(sb + S_GATE, v * (4 * NCL), v & 1);
    }
    __syncwarp();
    asm volatile("barrier.cluster.arrive.relaxed.aligned;" ::: "memory");
    if (wg == 2) bar_arrive(8, 384);
    if (p.dopro && cl >= 2) prologue(p.pa, sb, blockIdx.x - 4, wi, pr, p.zero, p.lag); else if (wg < 2) bar_sync(8, 384);
    asm volatile("barrier.cluster.wait.aligned;" ::: "memory");
    fence_async_smem();
    bar_sync(wg == 2 ? 7 : 1, wg == 2 ? 128 : 256);
    if (p.dopro && (threadIdx.x == 32 || threadIdx.x == 352)) red_release(g_gate, 1);
    if (rec) {
        if (threadIdx.x == 0) {
            rec_fetch(&p.tm[1], sb + R_STK, (cl - p.rec0) * 128, rank * 256, 2, sb + R_BAR + RB_INIT * 8);
            rec_fetch(&p.tm[2], sb + R_STV, (cl - p.rec0) * 128, rank * 256, 2, sb + R_BAR + RB_INIT * 8);
        }
    }
    PROF(threadIdx.x == 0, 3506);
    __syncwarp();
    if (rec) {
        const int head = cl - p.rec0;
        if (wg == 2) {
            reg_dec<RH>();
            const int w = wi & 3;
            if (threadIdx.x == 256) rec_fetch(&p.tm[0], sb + R_STQ, head * 128, rank * 256, 2, sb + R_BAR + RB_INIT * 8);
            __syncwarp();
            wait_cnt_warp(g_gate, lds32(sb + S_GATE));
            if (p.dostats) x1_stats((head * 2 + rank) * 4 + w);
            __syncthreads();
            cluster_sync();
            if ((p.chains >> (w >> 1)) & 1) rec_attn(p, sb, w >> 1, w & 1, head, rank);
        } else {
            reg_inc<RW0>();
            rec_weights(p, sb, head, rank, wi);
        }
    } else {
        if (wg == 2) {
            reg_dec<40>();
            const int w = wi & 3;
            if (w == 0) bulk_producer(p, sb, cl, rank); else if (w >= 2) bulk_release(p, sb, cl, rank, w - 2); else bulk_relay(p, sb, cl);
        } else { reg_inc<232>(); bulk_consumer(p, sb, cl, rank, wi); }
    }
    __syncwarp();
    cluster_sync();
}

typedef CUresult (*EncFn)(CUtensorMap*, CUtensorMapDataType, cuuint32_t, void*, const cuuint64_t*, const cuuint64_t*, const cuuint32_t*, const cuuint32_t*,
                          CUtensorMapInterleave, CUtensorMapSwizzle, CUtensorMapL2promotion, CUtensorMapFloatOOBfill);
inline uint32_t mk(int type, int layer, int ch, int a, int b, int c) { return type | (layer << 3) | (ch << 4) | (a << 8) | (b << 16) | ((uint32_t)c << 24); }
constexpr int SMEM_BYTES = 232448;

struct Sched {
    Params* P; int n[NCL];
    void clear() { memset(P->task, 0, sizeof(P->task)); memset(n, 0, sizeof(n)); }
    void add(int cl, uint32_t t) { if (n[cl] < MAXT - 1) P->task[list_of(cl)][n[cl]++] = t; }
};

constexpr int REC0 = 4;
struct Cfg { int LAG, TS1, TS2, DQU, DQO, DUN, DHN, MARG, NQ1, FAST0, n0, oc, fc, nuns, ns2, nhg, hs, osl, nfin, dry, tl, c8, o9, lm, hd, DKB, DF; };
#define HALVES 1
#define PLAN 14, 2250, 2850, 2400, 900, 5400, 420, 1000, 4, 0, 12, 10, 14, 6, 4, 8, 8000, 0, 0, 8500, 1500, 12, 3, 1500, 400, 640, 3000
Cfg g_cfg = {PLAN};
double g_est;
bool g_planned = false;
struct Plan { uint32_t w[NCL][MAXT]; int n[NCL]; double end, rec; };
void simulate(Plan& L, int nc, const Cfg& C) {
    const int LAG = C.LAG, NQ1 = C.NQ1, FAST0 = C.FAST0, n0 = C.n0, oc = C.oc, fc = C.fc, nuns = C.nuns, ns2 = C.ns2, nhg = C.nhg;
    const double TS1 = C.TS1, TS2 = C.TS2, DQU = C.DQU, DQO = C.DQO, DUN = C.DUN, DHN = C.DHN, MARG = C.MARG, hs = C.hs;
    const double INF = 1e18, DKB = C.DKB, DOV = 700, DH = DHN, DHO = 1100, DF = C.DF, DFB = 200, POLL = 450, FILL = 500, PUB = 600;
    enum { Q0, O0, Q1, HB, O1, FI, NK };
    struct Grp { int n, left; double done; } G[NK][16];
    double fr[NCL], it[100] = {}, cv[16];
    int ns[16], last[2][NCL], uc = 0, nit = 0;
    memset(L.n, 0, sizeof(L.n)); L.end = 0;
    auto fast = [&](int c) { return c < FAST0 || c >= fc; };
    for (int c = 0; c < 16; c++) {
        ns[c] = c < nuns ? 1 : c == 15 ? 16 : c >= C.c8 ? 8 : ns2;
        const int cnt[NK] = {c < 2 ? 48 : (c & 1) ? 0 : 96, c >= oc ? OPS1 : c >= C.o9 ? 9 : 8, c == 15 ? 24 : fast(c) ? 16 : 48 / NQ1, c >= 2 && !(c & 1) ? 16 : 0, ns[c], c < C.nfin || ns[c] == 1 ? 0 : c >= 14 ? 8 : 4};
        for (int k = 0; k < NK; k++) G[k][c] = {cnt[k], cnt[k], 0};
        cv[c] = INF;
    }
    for (int i = 0; i < nc; i++) { fr[i] = 0; last[0][i] = last[1][i] = -1; }
    auto fin = [&](int k, int c) { if ((k == Q0 && c >= 2) || k == HB) c &= ~1; return G[k][c].left ? INF : G[k][c].done; };
    auto len = [&](int i) { return (i >= LAG && i < 64) ? (double)TS2 : (double)TS1; };
    auto end_it = [&](int i) { return i < nit ? it[i] + len(i) : INF; };
    auto nominal = [&](int i) { if (i < nit) return it[i]; double t = nit ? it[nit - 1] : 11000 - TS1; for (int j = nit - 1; j < i; j++) t += len(j); return t; };
    auto put = [&](int i, uint32_t w) { if (L.n[i] < MAXT - 2) L.w[i][L.n[i]++] = w; else L.end = INF; };
    auto rel = [&](int k, int c) {
        switch (k) {
            case Q0: return 0.0;
            case O0: return end_it(4 * c + 3) + PUB + POLL;
            case Q1: return cv[c] + POLL;
            case HB: return cv[c - 2] + 600 + POLL;
            case O1: return fmax(end_it(LAG + 4 * c + 3) + PUB + POLL, G[O1][c].left == 1 && !G[FI][c].n ? G[O1][c].done - DKB * 64 / ns[c] : 0);
            default: return fin(O1, c) + POLL;
        }
    };
    auto dur = [&](int k, int c) {
        switch (k) {
            case Q0: return DQO + (c < 2 ? 2.0 : 1.0) * DQU;
            case O0: return (16 - G[O0][c].n) * DKB + 1200;
            case HB: return DHO + DH * c;
            case Q1: return DQO + 48.0 / G[Q1][c].n * DQU;
            case O1: return DOV + DKB * 64 / ns[c] + (G[O1][c].left == 1 && !G[FI][c].n ? 700 + 800 * ns[c] : 0);
            default: return DF + DFB * ns[c] * (c >= 14 ? 0.5 : 1);
        }
    };
    auto o0_est = [&](int c) {
        double t = uc ? cv[uc - 1] - 900 : 0;
        for (int j = uc; j < c; j++) t = fmax(t, nominal(4 * j + 4) + PUB + POLL + FILL) + dur(O0, j) + DUN;
        return fmax(t, nominal(4 * c + 4) + PUB + POLL);
    };
    auto cv_est = [&](int c) { return c < uc ? cv[c] : o0_est(c) + FILL + dur(O0, c) + DUN + 900; };
    auto slot = [&](int k, int c, int i) { return k == O0 ? (i < 8 ? i : nc + 7 - i) : c == 15 ? i : i - 8; };
    while (true) {
        while (nit < 64 + LAG) {
            double t = nit ? end_it(nit - 1) : 0;
            if (nit < 64) t = fmax(t, fin(Q0, nit >> 2) + POLL);
            if (nit >= LAG) t = fmax(t, fin(Q1, (nit - LAG) >> 2) + (nit < 64 ? 0 : POLL));
            if (t >= INF) break;
            it[nit++] = t;
        }
        int i = -1;
        for (int j = 0; j < nc; j++) if (fr[j] < INF && (i < 0 || fr[j] < fr[i])) i = j;
        if (i < 0) break;
        const double t = fr[i];
        double lim = INF;
        if (i < 8 && last[0][i] == uc) {
            if (G[O0][uc].left || fin(HB, uc) >= INF) { fr[i] = t + 200; continue; }
            const double e = fmax(G[O0][uc].done, fin(HB, uc) - 2000) + DUN;
            for (int j = 0; j < 8; j++) { put(j, mk(T_CV, 0, uc, 2 * j, G[O0][uc].n, 0)); fr[j] = e; }
            cv[uc++] = e + 900;
            continue;
        }
        const bool hg = (unsigned)(i - 24) < (unsigned)nhg;
        double hlim = INF;
        for (int c = 2; c < 16 && hg; c++) if (G[HB][c].left) { hlim = cv_est(c - 2) + hs - C.hd * c; break; }
        int mine[2] = {-1, -1};
        for (int k = 0; k < 2; k++)
            for (int c = last[k][i] + 1; c < 16 && mine[k] < 0; c++) if ((unsigned)slot(O0 + k, c, i) < (unsigned)G[O0 + k][c].n) mine[k] = c;
        if (mine[0] >= 0) lim = i < 8 ? o0_est(mine[0]) - (uc ? 0 : C.dry) : nominal(4 * mine[0] + 4) + PUB + C.osl;
        else if (mine[1] >= 0) lim = cv_est(mine[1]) + POLL - (mine[1] ? C.lm : 0);
        else if ((i < 16 && G[O1][15].left) || (i < 8 && G[FI][15].left)) lim = fmin(lim, nominal(64 + LAG) + PUB - C.tl);
        int bk = -1, bc = 0; double bd = INF;
        for (int k = 0; k < NK; k++)
            for (int c = 0; c < 16; c++) {
                const bool urgent = k == O0 || k == Q1 || (k >= O1 && c == 15);
                if (!G[k][c].left || ((k == O0 || k == Q1) && c != mine[k - O0]) || (k >= O1 && c == 15 && i >= G[k][c].n)) continue;
                if (rel(k, c) > t || (t + dur(k, c) + (k == Q0 && c >= 2 ? DQU : 0) > lim && !urgent)) continue;
                if (i < 8 && uc && uc < 16 && k != O0) continue;
                if ((k == HB && !hg && i < nc - 2) || (k != HB && !urgent && t + dur(k, c) + (k == Q0 && c >= 2 ? DQU : 0) > hlim)) continue;
                const double dl = urgent ? -INF : k == HB ? -INF / 2 : k == Q0 ? nominal(4 * c) - 3000 : 1e9 + c * 2 + (k == O1);
                if (dl < bd) { bd = dl; bk = k; bc = c; }
            }
        if (bk < 0) {
            bool any = i < 8 && uc < 16;
            for (int k = 0; k < NK; k++) for (int c = 0; c < 16; c++) any = any || G[k][c].left;
            fr[i] = any ? t + 200 : INF;
            if (t > 400000) { L.end = INF; return; }
            continue;
        }
        Grp& g = G[bk][bc];
        const int n = g.n - g.left, c = bc;
        int nu = 1;
        double d = dur(bk, c);
        if (bk == Q0) for (nu = c < 2 ? 2 : 1; c >= 2 && nu < g.left && (nu < 2 || (nu < n0 && t + d + DQU < fmin(fmin(lim, hlim), bd - MARG))); nu++) d += DQU;
        if (bk == O0 && i >= 8) d += (g.n - 8) * DKB;
        if (bk == Q0 && !c && n >= 32) { nu = 1; d -= DQU; }
        if (bk == O0 || bk == Q1) last[bk - O0][i] = c;
        if (bk == O0 && !c && i < 8 && C.dry) put(i, mk(T_CV, 0, 1, 2 * i, 0, 128));
        g.left -= nu;
        const bool fini = bk == O1 && !g.left && !G[FI][c].n;
        const double e = fmax(fmax(t, rel(bk, c) + FILL) + (t < 1 ? 3500 : 0) + d, fini ? g.done + POLL + 700 + 800 * ns[c] : 0);
        fr[i] = e;
        g.done = fmax(g.done, e + (bk == O1 ? (c == 15 ? -500 : 1500) : bk == O0 ? 0 : (bk == Q1 && g.n < 24) || (bk == Q0 && !c && nu == 2) ? -500 : 1000));
        if (bk == FI || fini) L.end = fmax(L.end, e);
        put(i, bk == Q0 ? (c == 0 ? mk(T_QKV, 0, 0, n < 32 ? n : 2 * n - 32, nu, 32) : c == 1 ? mk(T_QKV, 0, c, n, 2, 24) : mk(T_QKV, 0, c, n, nu, 64))
             : bk == O0 ? (i < 8 ? mk(T_OP, 0, c, i * (16 - g.n), 16 - g.n, i) : mk(T_OP, 0, c, 64 - (nc - i) * 8, 8, slot(O0, c, i)))
             : bk == HB ? mk(T_CV, 1, c, 2 * n, 0, 0)
             : bk == Q1 ? mk(T_QKV, 1, c, slot(Q1, c, i) * 2, 48 / g.n, g.n)
             : bk == O1 ? mk(T_OP, 1, c, n * 64 / ns[c], 64 / ns[c], n + (fini ? 32 : c == 15 && HALVES ? 16 : 0))
                        : mk(T_FIN, 1, c, n * (32 / g.n), ns[c], 16 / g.n));
    }
    L.rec = end_it(63 + LAG);
}
void plan(Params& P) {
    P.rec0 = REC0; P.chains = 3; P.lag = g_cfg.LAG; P.dostats = 1; P.dopro = 1;
    static Plan L;
    int cls[NCL], nc = 0;
    for (int c = REC0 + 32; c < NCL; c++) cls[nc++] = c;
    for (int c = REC0 - 1; c >= 0; c--) cls[nc++] = c;
    simulate(L, nc, g_cfg);
    g_est = L.end;
    Sched S; S.P = &P; S.clear();
    for (int i = 0; i < nc; i++) {
        bool warm = false;
        for (int k = 0; k < L.n[i]; k++) {
            if (!warm && k + 1 < L.n[i] && (L.w[i][k + 1] & 255) == (mk(T_FIN, 1, 15, 0, 0, 0) & 255)) { S.add(cls[i], (L.w[i][k + 1] & ~0xff0000u) | 0x80000000u); warm = true; }
            S.add(cls[i], L.w[i][k]);
            if ((L.w[i][k] & 7) == T_FIN) warm = true;
        }
    }
}

#define TK0() do {} while (0)
#define TK() do { P.e0 = (P.chains & 1) ? 64 : 0; P.b1 = (P.chains & 2) ? P.lag : 1000; P.nit = (P.chains & 2) ? P.lag + 64 : 64; TK0(); } while (0)
}

extern "C" void kernel_launch(void* const* d_in, const int* in_sizes, int n_in, void* d_out, int out_size) {
    typedef const __nv_bfloat16* BP;
    static EncFn enc = nullptr;
    if (!enc) {
        void* fn = nullptr; cudaDriverEntryPointQueryResult qr;
        cudaGetDriverEntryPoint("cuTensorMapEncodeTiled", &fn, cudaEnableDefault, &qr);
        enc = (EncFn)fn;
        cudaFuncSetAttribute(main_kernel, cudaFuncAttributeMaxDynamicSharedMemorySize, SMEM_BYTES);
    }
    static Params P;
    for (int i = 0; i < 4; i++) {
        const cuuint64_t cols = i < 3 ? 4096 : 512, rows = i < 3 ? 512 : 4096;
        cuuint64_t d2[2] = {cols, rows}, d3[3] = {64, rows, cols / 64}, str[2] = {cols * 2, 128};
        cuuint32_t box[3] = {64, 64, 4}, es[3] = {1, 1, 1};
        enc(&P.tm[i < 3 ? i : 4], CU_TENSOR_MAP_DATA_TYPE_BFLOAT16, 2, d_in[9 + i], d2, str, box, es, CU_TENSOR_MAP_INTERLEAVE_NONE, CU_TENSOR_MAP_SWIZZLE_128B,
                       CU_TENSOR_MAP_L2_PROMOTION_L2_128B, CU_TENSOR_MAP_FLOAT_OOB_FILL_NONE);
        for (int m = 0; m <= i / 3; m++) {
            cuuint32_t box3[3] = {64, 32, m ? 4u : 2u};
            enc(&P.t3[i + m], CU_TENSOR_MAP_DATA_TYPE_BFLOAT16, 3, d_in[9 + i], d3, str, box3, es, CU_TENSOR_MAP_INTERLEAVE_NONE, CU_TENSOR_MAP_SWIZZLE_128B,
                CU_TENSOR_MAP_L2_PROMOTION_L2_128B, CU_TENSOR_MAP_FLOAT_OOB_FILL_NONE);
        }
    }
    {
        cuuint64_t dims[2] = {512, 2048}, str[1] = {1024};
        cuuint32_t box[2] = {8, 256}, es[2] = {1, 1};
        enc(&P.tm[3], CU_TENSOR_MAP_DATA_TYPE_BFLOAT16, 2, d_in[0], dims, str, box, es, CU_TENSOR_MAP_INTERLEAVE_NONE, CU_TENSOR_MAP_SWIZZLE_NONE,
            CU_TENSOR_MAP_L2_PROMOTION_NONE, CU_TENSOR_MAP_FLOAT_OOB_FILL_NONE);
    }
    for (int m = 0; m < 2; m++) {
        void* ga; cudaGetSymbolAddress(&ga, g_A);
        cuuint64_t dims[2] = {512, sizeof(AOps) / 1024}, str[1] = {1024};
        cuuint32_t box[2] = {256, m ? 16u : 8u}, es[2] = {1, 1};
        enc(&P.ta[m], CU_TENSOR_MAP_DATA_TYPE_BFLOAT16, 2, ga, dims, str, box, es, CU_TENSOR_MAP_INTERLEAVE_NONE, CU_TENSOR_MAP_SWIZZLE_NONE,
            CU_TENSOR_MAP_L2_PROMOTION_L2_128B, CU_TENSOR_MAP_FLOAT_OOB_FILL_NONE);
    }
    P.mem0 = (BP)d_in[8]; P.Wo = (BP)d_in[12]; P.Dskip = (BP)d_in[6]; P.out = (__nv_bfloat16*)d_out;
    cudaStream_t s = cudaStreamPerThread;
    P.pa = {(BP)d_in[0], (BP)d_in[1], (BP)d_in[2], (BP)d_in[3], (BP)d_in[4], (BP)d_in[5], (BP)d_in[6], (BP)d_in[9], (BP)d_in[10], (BP)d_in[11], (BP)d_in[12], (BP)d_in[8]};
    if (!g_planned) { plan(P); g_planned = true; }
    TK(); main_kernel<<<2 * NCL, 384, SMEM_BYTES, s>>>(P); TK();
}
```

```cpp
#include <cuda_runtime.h>
#include <cuda_bf16.h>
#include <cuda.h>
#include <stdint.h>
#include <string.h>
#include <math.h>

#define MAXTN 42
namespace {

constexpr int NCL = 66;
constexpr int NLIST = NCL - 32;
__host__ __device__ inline int list_of(int cl) { return cl < 4 ? cl : cl - 32; }
constexpr int MAXT = MAXTN;
#define PFC 1
#define QB1 2
#define QB2 4
#define QB3 6
#define LAGQ 3
#define CPOS 2
#define QPRE 1
#define QPOS 1
#define OPS1N 10
constexpr int OPS1 = OPS1N;
constexpr int MAXSPLIT = 16;
constexpr int PW = 144;

struct AOps { uint4 x[2][16 * 8 * 1024], o[2][16 * 64 * 1024]; };
__device__ AOps g_A;
#define g_xA g_A.x
#define g_o g_A.o
__device__ float2 g_st[2][16 * 2048];
__device__ float2 g_st2[2 * 16 * 128];
__device__ uint4 g_qkv[2][64 * 64 * 768];
__device__ uint4 g_pp[2][16 * MAXSPLIT * 8192];
__device__ uint4 g_acc[7 * 2048];
__device__ unsigned g_gate[32];
__device__ uint32_t g_P[16 * 16 * 32 * PW];
__device__ uint4 g_u[16 * 16 * 512];
__device__ float4 g_carry[2][17 * 16 * 4 * 256];
__device__ unsigned g_cnt[13 * 64];
__device__ uint32_t g_ln0[2048];

enum { C_QKV0 = 0, C_QKV1 = 1  , C_O0 = 2, C_O1 = 3, C_U = 4, C_OP1 = 5, C_CV = 6, C_ST = 7, C_H = 8, C_OP0 = 9   };
__device__ __forceinline__ unsigned* cnt_ptr(int kind, int chunk) { return g_cnt + kind * 64 + chunk; }

enum { T_END = 0, T_QKV = 1, T_OP = 2, T_CV = 3, T_FIN = 4 };
struct ProArgs { const __nv_bfloat16 *x, *lAr, *Ai, *Cr, *Ci, *ldt, *Dk, *Wq, *Wk, *Wv, *Wo, *mem0; };
struct Params {
    CUtensorMap tm[5];
    CUtensorMap t3[5];
    CUtensorMap ta[2];
    ProArgs pa;
    int dopro;
    const __nv_bfloat16* mem0;
    const __nv_bfloat16* Wo;
    const __nv_bfloat16* Dskip;
    __nv_bfloat16* out;
    int rec0;
    int chains;
    int lag;
    int b1, e0, nit;
    int zero, gpit;
    int dostats;
    uint32_t task[NLIST][MAXT];
};

__device__ __forceinline__ uint32_t smem_u32(const void* p) { return (uint32_t)__cvta_generic_to_shared(p); }
__device__ __forceinline__ uint32_t mapa(uint32_t a, uint32_t r) {
    uint32_t o; asm("mapa.shared::cluster.u32 %0,%1,%2;" : "=r"(o) : "r"(a), "r"(r)); return o;
}
__device__ __forceinline__ void mbar_init(uint32_t b, int c) { asm volatile("mbarrier.init.shared::cta.b64 [%0],%1;" ::"r"(b), "r"(c) : "memory"); }
__device__ __forceinline__ void mbar_expect(uint32_t b, int bytes) { asm volatile("mbarrier.arrive.expect_tx.shared::cta.b64 _,[%0],%1;" ::"r"(b), "r"(bytes) : "memory"); }
__device__ __forceinline__ void mbar_arrive(uint32_t b) { asm volatile("mbarrier.arrive.shared::cta.b64 _,[%0];" ::"r"(b) : "memory"); }
__device__ __forceinline__ void mbar_arrive_cluster(uint32_t b) { asm volatile("mbarrier.arrive.shared::cluster.b64 _,[%0];" ::"r"(b) : "memory"); }
__device__ __forceinline__ void mbar_arrive1(uint32_t b) { asm volatile("{.reg .pred p; elect.sync _|p,0xffffffff; @p mbarrier.arrive.shared::cta.b64 _,[%0];}" ::"r"(b) : "memory"); }
__device__ __forceinline__ void mbar_arrive1_cluster(uint32_t b) { asm volatile("{.reg .pred p; elect.sync _|p,0xffffffff; @p mbarrier.arrive.shared::cluster.b64 _,[%0];}" ::"r"(b) : "memory"); }
__device__ __forceinline__ void mbar_wait(uint32_t b, uint32_t ph) {
    asm volatile(
        "{.reg .pred p; .reg .u32 n; mov.u32 n,0;\n"
        "W%=: mbarrier.try_wait.parity.shared::cta.b64 p,[%0],%1;\n"
        "@p bra D%=;\n"
        "add.u32 n,n,1; setp.lt.u32 p,n,2000000; @p bra W%=;\n"
        "trap;\n"
        "D%=: }" ::"r"(b), "r"(ph) : "memory");
}
__device__ __forceinline__ bool mbar_test(uint32_t b, uint32_t ph) {
    uint32_t ok;
    asm volatile("{.reg .pred p; mbarrier.test_wait.parity.shared::cta.b64 p,[%1],%2; selp.u32 %0,1,0,p;}" : "=r"(ok) : "r"(b), "r"(ph) : "memory");
    return ok;
}
__device__ __forceinline__ bool wait_lds128(uint32_t b, uint32_t ph, uint32_t a, uint4& v) {
    uint32_t ok;
    asm volatile("{.reg .pred p; mbarrier.try_wait.parity.shared::cta.b64 p,[%5],%6,20000; ld.shared.v4.u32 {%0,%1,%2,%3},[%7]; selp.u32 %4,1,0,p;}"
                 : "=r"(v.x), "=r"(v.y), "=r"(v.z), "=r"(v.w), "=r"(ok) : "r"(b), "r"(ph), "r"(a) : "memory");
    return ok;
}
__device__ __forceinline__ bool wait_lds64(uint32_t b, uint32_t ph, uint32_t a, uint2& v) {
    uint32_t ok;
    asm volatile("{.reg .pred p; mbarrier.try_wait.parity.shared::cta.b64 p,[%3],%4,20000; ld.shared.v2.u32 {%0,%1},[%5]; selp.u32 %2,1,0,p;}"
                 : "=r"(v.x), "=r"(v.y), "=r"(ok) : "r"(b), "r"(ph), "r"(a) : "memory");
    return ok;
}
template <int PH> __device__ __forceinline__ void mbar_wait_c(uint32_t b) {
    asm volatile(
        "{.reg .pred p; .reg .u32 n; mov.u32 n,%2;\n"
        "W%=: mbarrier.try_wait.parity.shared::cta.b64 p,[%0],%1;\n"
        "@p bra D%=;\n"
        "add.u32 n,n,1; setp.lt.u32 p,n,2000000; @p bra W%=;\n"
        "trap;\n"
        "D%=: }" ::"r"(b), "n"(PH), "n"(PH) : "memory");
}
__device__ __forceinline__ void bar_sync(int id, int n) { asm volatile("bar.sync %0,%1;" ::"r"(id), "r"(n) : "memory"); }
__device__ __forceinline__ void bar_arrive(int id, int n) { asm volatile("bar.arrive %0,%1;" ::"r"(id), "r"(n) : "memory"); }
__device__ __forceinline__ void cluster_sync() { asm volatile("barrier.cluster.arrive.relaxed.aligned; barrier.cluster.wait.aligned;" ::: "memory"); }
__device__ __forceinline__ void fence_async() { asm volatile("fence.proxy.async;" ::: "memory"); }
__device__ __forceinline__ void fence_async_smem() { asm volatile("fence.proxy.async.shared::cta;" ::: "memory"); }
#define EFR 1
#define EFW 1
constexpr uint64_t POL_N = 0x1000000000000000ull, POL_F = 0x12F0000000000000ull;
constexpr uint64_t POL_LAST = EFR ? POL_F : POL_N  , POL_LATE = EFW ? POL_F : POL_N  , POL_SOON = EFW > 1 ? POL_F : POL_N;
__device__ __forceinline__ void bulk_g2s(uint32_t dst, const void* src, int bytes, uint32_t bar, uint64_t pol) {
    asm volatile("cp.async.bulk.shared::cluster.global.mbarrier::complete_tx::bytes.L2::cache_hint [%0],[%1],%2,[%3],%4;" ::"r"(dst), "l"(src), "r"(bytes), "r"(bar), "l"(pol) : "memory");
}
__device__ __forceinline__ void bulk_g2s_mc(uint32_t dst, const void* src, int bytes, uint32_t bar, uint64_t pol) {
    asm volatile("cp.async.bulk.shared::cluster.global.mbarrier::complete_tx::bytes.multicast::cluster.L2::cache_hint [%0],[%1],%2,[%3],%4,%5;" ::"r"(dst), "l"(src), "r"(bytes), "r"(bar), "h"((uint16_t)3), "l"(pol) : "memory");
}
__device__ __forceinline__ void bulk_s2s(uint32_t dst, uint32_t src, int bytes, uint32_t bar) {
    asm volatile("cp.async.bulk.shared::cluster.shared::cta.mbarrier::complete_tx::bytes [%0],[%1],%2,[%3];" ::"r"(dst), "r"(src), "r"(bytes), "r"(bar) : "memory");
}
__device__ __forceinline__ bool elect() {
    uint32_t r; asm volatile("{.reg .pred p; elect.sync _|p,0xffffffff; selp.u32 %0,1,0,p;}" : "=r"(r)); return r;
}
__device__ __forceinline__ void stg128(uint4* p, uint4 v, uint64_t pol) {
    asm volatile("st.global.L2::cache_hint.v4.u32 [%0],{%1,%2,%3,%4},%5;" ::"l"(p), "r"(v.x), "r"(v.y), "r"(v.z), "r"(v.w), "l"(pol));
}
__device__ __forceinline__ void stg32(uint32_t* p, uint32_t v, uint64_t pol) { asm volatile("st.global.L2::cache_hint.u32 [%0],%1,%2;" ::"l"(p), "r"(v), "l"(pol)); }
__device__ __forceinline__ uint4 ldcg128_last(const uint4* p) {
    uint4 v; asm volatile("ld.global.cg.L2::cache_hint.v4.u32 {%0,%1,%2,%3},[%4],%5;" : "=r"(v.x), "=r"(v.y), "=r"(v.z), "=r"(v.w) : "l"(p), "l"(POL_LAST) : "memory"); return v;
}
__device__ __forceinline__ void tma2d(uint32_t dst, const CUtensorMap* tm, int x, int y, uint32_t bar) {
    asm volatile("cp.async.bulk.tensor.2d.shared::cluster.global.mbarrier::complete_tx::bytes [%0],[%1,{%2,%3}],[%4];" ::"r"(dst), "l"(tm), "r"(x), "r"(y), "r"(bar) : "memory");
}
__device__ __forceinline__ void tma3d_mc(uint32_t dst, const CUtensorMap* tm, int y, int z, uint32_t bar, uint16_t mask) {
    asm volatile("{.reg .pred p; elect.sync _|p,0xffffffff;\n"
                 "@p cp.async.bulk.tensor.3d.shared::cluster.global.mbarrier::complete_tx::bytes.multicast::cluster [%0],[%1,{0,%2,%3}],[%4],%5;}"
                 ::"r"(dst), "l"(tm), "r"(y), "r"(z), "r"(bar), "h"(mask) : "memory");
}
__device__ __forceinline__ void tma2d_mc(uint32_t dst, const CUtensorMap* tm, int x, int y, uint32_t bar, uint16_t mask, uint64_t pol) {
    asm volatile("{.reg .pred p; elect.sync _|p,0xffffffff;\n"
                 "@p cp.async.bulk.tensor.2d.shared::cluster.global.mbarrier::complete_tx::bytes.multicast::cluster.L2::cache_hint [%0],[%1,{%2,%3}],[%4],%5,%6;}"
                 ::"r"(dst), "l"(tm), "r"(x), "r"(y), "r"(bar), "h"(mask), "l"(pol) : "memory");
}
__device__ __forceinline__ void bulk_g2s1(uint32_t dst, const void* src, int bytes, uint32_t bar, uint64_t pol) {
    asm volatile("{.reg .pred p; elect.sync _|p,0xffffffff;\n"
                 "@p cp.async.bulk.shared::cluster.global.mbarrier::complete_tx::bytes.L2::cache_hint [%0],[%1],%2,[%3],%4;}" ::"r"(dst), "l"(src), "r"(bytes), "r"(bar), "l"(pol) : "memory");
}
__device__ __forceinline__ void mbar_expect1(uint32_t b, int bytes) {
    asm volatile("{.reg .pred p; elect.sync _|p,0xffffffff; @p mbarrier.arrive.expect_tx.shared::cta.b64 _,[%0],%1;}" ::"r"(b), "r"(bytes) : "memory");
}
__device__ __forceinline__ void st_async4(uint32_t a, uint32_t x, uint32_t y, uint32_t z, uint32_t w, uint32_t mb) {
    asm volatile("st.async.shared::cluster.mbarrier::complete_tx::bytes.v4.b32 [%0],{%1,%2,%3,%4},[%5];" ::"r"(a), "r"(x), "r"(y), "r"(z), "r"(w), "r"(mb) : "memory");
}
__device__ __forceinline__ void st_async2(uint32_t a, uint32_t x, uint32_t y, uint32_t mb) {
    asm volatile("st.async.shared::cluster.mbarrier::complete_tx::bytes.v2.b32 [%0],{%1,%2},[%3];" ::"r"(a), "r"(x), "r"(y), "r"(mb) : "memory");
}
#define LDSQ "ld.shared"
__device__ __forceinline__ uint4 lds128(uint32_t a) { uint4 v; asm volatile(LDSQ ".v4.u32 {%0,%1,%2,%3},[%4];" : "=r"(v.x), "=r"(v.y), "=r"(v.z), "=r"(v.w) : "r"(a) : "memory"); return v; }
__device__ __forceinline__ uint2 lds64(uint32_t a) { uint2 v; asm volatile(LDSQ ".v2.u32 {%0,%1},[%2];" : "=r"(v.x), "=r"(v.y) : "r"(a) : "memory"); return v; }
__device__ __forceinline__ uint32_t lds32(uint32_t a) { uint32_t v; asm volatile(LDSQ ".u32 %0,[%1];" : "=r"(v) : "r"(a) : "memory"); return v; }
__device__ __forceinline__ void sts128(uint32_t a, uint32_t x, uint32_t y, uint32_t z, uint32_t w) { asm volatile("st.shared.v4.u32 [%0],{%1,%2,%3,%4};" ::"r"(a), "r"(x), "r"(y), "r"(z), "r"(w) : "memory"); }
__device__ __forceinline__ void sts64(uint32_t a, uint32_t x, uint32_t y) { asm volatile("st.shared.v2.u32 [%0],{%1,%2};" ::"r"(a), "r"(x), "r"(y) : "memory"); }
__device__ __forceinline__ void sts32(uint32_t a, uint32_t x) { asm volatile("st.shared.u32 [%0],%1;" ::"r"(a), "r"(x) : "memory"); }
__device__ __forceinline__ uint4 ldsm4(uint32_t a) { uint4 v; asm volatile("ldmatrix.sync.aligned.m8n8.x4.shared.b16 {%0,%1,%2,%3},[%4];" : "=r"(v.x), "=r"(v.y), "=r"(v.z), "=r"(v.w) : "r"(a) : "memory"); return v; }
__device__ __forceinline__ uint4 ldsm4t(uint32_t a) { uint4 v; asm volatile("ldmatrix.sync.aligned.m8n8.x4.trans.shared.b16 {%0,%1,%2,%3},[%4];" : "=r"(v.x), "=r"(v.y), "=r"(v.z), "=r"(v.w) : "r"(a) : "memory"); return v; }
__device__ __forceinline__ uint32_t movm(uint32_t a) { uint32_t d; asm volatile("movmatrix.sync.aligned.m8n8.trans.b16 %0,%1;" : "=r"(d) : "r"(a)); return d; }
__device__ __forceinline__ uint32_t pack2(float lo, float hi) { uint32_t d; asm("cvt.rn.bf16x2.f32 %0,%1,%2;" : "=r"(d) : "f"(hi), "f"(lo)); return d; }
__device__ __forceinline__ uint32_t hadd2(uint32_t a, uint32_t b) { uint32_t d; asm("add.rn.bf16x2 %0,%1,%2;" : "=r"(d) : "r"(a), "r"(b)); return d; }
__device__ __forceinline__ float blo(uint32_t v) { return __uint_as_float(v << 16); }
__device__ __forceinline__ float bhi(uint32_t v) { return __uint_as_float(v & 0xffff0000u); }
__device__ __forceinline__ float rbf(float x) { return __uint_as_float(pack2(0.f, x)); }
__device__ __forceinline__ float ex2(float x) { float y; asm("ex2.approx.ftz.f32 %0,%1;" : "=f"(y) : "f"(x)); return y; }
__device__ __forceinline__ float rcp(float x) { float y; asm("rcp.approx.ftz.f32 %0,%1;" : "=f"(y) : "f"(x)); return y; }
__device__ __forceinline__ void mma16(float* c, uint32_t a0, uint32_t a1, uint32_t a2, uint32_t a3, uint32_t b0, uint32_t b1) {
    asm volatile("mma.sync.aligned.m16n8k16.row.col.f32.bf16.bf16.f32 {%0,%1,%2,%3},{%4,%5,%6,%7},{%8,%9},{%0,%1,%2,%3};"
                 : "+f"(c[0]), "+f"(c[1]), "+f"(c[2]), "+f"(c[3]) : "r"(a0), "r"(a1), "r"(a2), "r"(a3), "r"(b0), "r"(b1));
}
__device__ __forceinline__ void mma8(float* c, uint32_t a0, uint32_t a1, uint32_t b0) {
    asm volatile("mma.sync.aligned.m16n8k8.row.col.f32.bf16.bf16.f32 {%0,%1,%2,%3},{%4,%5},{%6},{%0,%1,%2,%3};"
                 : "+f"(c[0]), "+f"(c[1]), "+f"(c[2]), "+f"(c[3]) : "r"(a0), "r"(a1), "r"(b0));
}
__device__ __forceinline__ uint4 ld_rlx128(const uint4* p) {
    uint4 v;
    asm volatile("{.reg .b128 t; ld.relaxed.gpu.global.b128 t,[%4]; mov.b128 {%0,%1,%2,%3},t;}" : "=r"(v.x), "=r"(v.y), "=r"(v.z), "=r"(v.w) : "l"(p) : "memory");
    return v;
}
__device__ __forceinline__ void st_rlx128(uint4* p, uint32_t x, uint32_t y, uint32_t z, uint32_t w) {
    asm volatile("{.reg .b128 t; mov.b128 t,{%1,%2,%3,%4}; st.relaxed.gpu.global.b128 [%0],t;}" ::"l"(p), "r"(x), "r"(y), "r"(z), "r"(w) : "memory");
}
__device__ __forceinline__ uint4 ldcg128(const uint4* p) { uint4 v; asm volatile("ld.global.cg.v4.u32 {%0,%1,%2,%3},[%4];" : "=r"(v.x), "=r"(v.y), "=r"(v.z), "=r"(v.w) : "l"(p) : "memory"); return v; }
__device__ __forceinline__ void red_release(unsigned* p, unsigned v) {
    asm volatile("fence.proxy.async; red.relaxed.gpu.global.add.u32 [%0],%1;" ::"l"(p), "r"(v) : "memory");
}
__device__ __forceinline__ void wait_cnt(const unsigned* p, unsigned target) {
    unsigned v; int n = 0;
    while (true) {
        asm volatile("ld.acquire.gpu.global.u32 %0,[%1];" : "=r"(v) : "l"(p) : "memory");
        if (v >= target) break;
        if (++n > 3000000) __trap();
        __nanosleep(40);
    }
}
__device__ __forceinline__ void wait_cnt_warp(const unsigned* p, unsigned target) {
    unsigned v; int n = 0;
    while (true) {
        asm volatile("ld.acquire.gpu.global.u32 %0,[%1];" : "=r"(v) : "l"(p) : "memory");
        if (__all_sync(0xffffffffu, v >= target)) break;
        if (++n > 3000000) __trap();
    }
}
__device__ __forceinline__ uint64_t mkdesc(uint32_t addr, uint32_t lbo, uint32_t sbo, uint32_t sw) {
    return (uint64_t)((addr & 0x3FFFF) >> 4) | ((uint64_t)(lbo >> 4) << 16) | ((uint64_t)(sbo >> 4) << 32) | ((uint64_t)sw << 62);
}
__device__ __forceinline__ void wg_fence() { asm volatile("wgmma.fence.sync.aligned;" ::: "memory"); }
__device__ __forceinline__ void wg_commit() { asm volatile("wgmma.commit_group.sync.aligned;" ::: "memory"); }
template <int N> __device__ __forceinline__ void wg_wait() { asm volatile("wgmma.wait_group.sync.aligned %0;" ::"n"(N) : "memory"); }
#define R8(c, o) "+f"(c[o]), "+f"(c[o + 1]), "+f"(c[o + 2]), "+f"(c[o + 3]), "+f"(c[o + 4]), "+f"(c[o + 5]), "+f"(c[o + 6]), "+f"(c[o + 7])
#define R32(c, o) R8(c, o), R8(c, o + 8), R8(c, o + 16), R8(c, o + 24)
#define S32A "%0,%1,%2,%3,%4,%5,%6,%7,%8,%9,%10,%11,%12,%13,%14,%15,%16,%17,%18,%19,%20,%21,%22,%23,%24,%25,%26,%27,%28,%29,%30,%31"
#define S32B ",%32,%33,%34,%35,%36,%37,%38,%39,%40,%41,%42,%43,%44,%45,%46,%47,%48,%49,%50,%51,%52,%53,%54,%55,%56,%57,%58,%59,%60,%61,%62,%63"
#define S32C ",%64,%65,%66,%67,%68,%69,%70,%71,%72,%73,%74,%75,%76,%77,%78,%79,%80,%81,%82,%83,%84,%85,%86,%87,%88,%89,%90,%91,%92,%93,%94,%95"
#define S32D ",%96,%97,%98,%99,%100,%101,%102,%103,%104,%105,%106,%107,%108,%109,%110,%111,%112,%113,%114,%115,%116,%117,%118,%119,%120,%121,%122,%123,%124,%125,%126,%127"
#define W8(c, o) "=f"(c[o]), "=f"(c[o + 1]), "=f"(c[o + 2]), "=f"(c[o + 3]), "=f"(c[o + 4]), "=f"(c[o + 5]), "=f"(c[o + 6]), "=f"(c[o + 7])
#define W32(c, o) W8(c, o), W8(c, o + 8), W8(c, o + 16), W8(c, o + 24)
template <bool ACC> __device__ __forceinline__ void wgmma256(float* c, uint64_t da, uint64_t db) {
    if (ACC) asm volatile("wgmma.mma_async.sync.aligned.m64n256k16.f32.bf16.bf16 {" S32A S32B S32C S32D "},%128,%129,1,1,1,0,1;"
                          : R32(c, 0), R32(c, 32), R32(c, 64), R32(c, 96) : "l"(da), "l"(db));
    else asm volatile("wgmma.mma_async.sync.aligned.m64n256k16.f32.bf16.bf16 {" S32A S32B S32C S32D "},%128,%129,0,1,1,0,1;"
                      : W32(c, 0), W32(c, 32), W32(c, 64), W32(c, 96) : "l"(da), "l"(db));
}
template <bool ACC> __device__ __forceinline__ void wgmma128r(float* c, const uint4& a, uint64_t db) {
    if (ACC) asm volatile("wgmma.mma_async.sync.aligned.m64n128k16.f32.bf16.bf16 {" S32A S32B "},{%64,%65,%66,%67},%68,1,1,1,1;"
                          : R32(c, 0), R32(c, 32) : "r"(a.x), "r"(a.y), "r"(a.z), "r"(a.w), "l"(db));
    else asm volatile("wgmma.mma_async.sync.aligned.m64n128k16.f32.bf16.bf16 {" S32A S32B "},{%64,%65,%66,%67},%68,0,1,1,1;"
                      : W32(c, 0), W32(c, 32) : "r"(a.x), "r"(a.y), "r"(a.z), "r"(a.w), "l"(db));
}
template <int N> __device__ __forceinline__ void reg_inc() { asm volatile("setmaxnreg.inc.sync.aligned.u32 %0;" ::"n"(N)); }
template <int N> __device__ __forceinline__ void reg_dec() { asm volatile("setmaxnreg.dec.sync.aligned.u32 %0;" ::"n"(N)); }

#define PROF(cond, idx) do {} while (0)
#define CPROF(k) do {} while (0)

constexpr int S_GATE = 232440, S_TAG = 232444, S_XBAR = 232432;
constexpr float SC_LOG2E = 0.08838834764831845f * 1.4426950408889634f;

__device__ __forceinline__ float2 ln_finish(float mean, float var) {
    float sd; asm("sqrt.approx.f32 %0,%1;" : "=f"(sd) : "f"(rbf(rbf(var) + 1e-5f)));
    sd = rbf(sd);
    return make_float2(rbf(mean), sd);
}

__device__ __forceinline__ float4 row_stats(const uint4* src, int stride) {
    const int g = (threadIdx.x & 31) >> 2;
    uint4 v[16];
#pragma unroll
    for (int i = 0; i < 16; i++) v[i] = ldcg128(src + i * stride);
    float a[4] = {0, 0, 0, 0}, q0[4] = {0, 0, 0, 0}, q1[4] = {0, 0, 0, 0}, q2[4] = {0, 0, 0, 0}, q3[4] = {0, 0, 0, 0};
#pragma unroll
    for (int i = 0; i < 16; i++) {
        mma16(a, v[i].x, v[i].y, v[i].z, v[i].w, 0x3f803f80u, 0x3f803f80u);
        mma8(q0, v[i].x, v[i].y, v[i].x); mma8(q1, v[i].x, v[i].y, v[i].y);
        mma8(q2, v[i].z, v[i].w, v[i].z); mma8(q3, v[i].z, v[i].w, v[i].w);
    }
    return make_float4(a[0], (g & 1) ? q0[1] + q2[1] : q0[0] + q2[0], a[2], (g & 1) ? q1[3] + q3[3] : q1[2] + q3[2]);
}
__device__ __forceinline__ void x1_stats(int i) {
    const int lane = threadIdx.x & 31, g = lane >> 2, c = lane & 3;
    const float4 r = row_stats(g_xA[0] + i * 512 + lane, 32);
    float2* dst = g_st[0] + (i >> 4) * 2048 + ((i < 32 ? 4 : 0) + (i & 1)) * 128 + ((i >> 1) & 7) * 16 + g;
    if (c == (g >> 1)) { dst[0] = make_float2(r.x, r.y); dst[8] = make_float2(r.z, r.w); g_ln0[i * 8 + g] = 0; }
    __syncwarp();
    if (lane == 0) red_release(cnt_ptr(C_ST, i >> 4), 1);
}
__global__ void stats_kernel() { x1_stats(blockIdx.x * 4 + (threadIdx.x >> 5)); }

#define NT 9
#define RH 104
#define RW0 200
#define NPD 9
#define NTO 12
#define DP1 11
#define GPW 0
#define GPJ 0
#define PACE 2
#define EARLY 4
#define G2I 3
#define VE 4
#define VF 8
constexpr int R_WV = 0, R_WO = 65536, R_T = 131072, R_M = R_T + 20480, R_LOC = R_M + 4096, R_REM = R_LOC + 6144, R_O = R_REM + 12288, R_SX = R_O + 2048,
              R_IL = R_SX + 5120, XS = R_IL + 128 - R_T, R_BAR = 231936, R_Z = R_BAR + 128  , R_STQ = 0, R_STK = 65536, R_STV = 131072;
static_assert(R_T + 2 * XS <= R_BAR && R_BAR + 256 <= S_XBAR, "smem map");
enum { RB_INIT = 0, RB_V = 4  , RB_QK = 8  , RB_T = 12  , RB_N = 16 };
enum { NB_MF = 1  , NB_LOC = 3  , NB_PAIR = 5  , NB_O = 9  , NB_XG = 11  , NB_W = 13 };
__device__ __forceinline__ uint32_t clk32() { return (uint32_t)clock64(); }

__device__ __forceinline__ char* acc_base() { return (char*)(((size_t)g_acc + 131071) & ~(size_t)131071); }
__device__ __forceinline__ uint32_t acc_slice(uint32_t s6) { return (s6 & 1) * 256 + (s6 >> 1) * 1024; }
__device__ __forceinline__ uint32_t acc_main(uint32_t rank, uint32_t tid) { return acc_slice(rank * 32 + (tid >> 3)) + (tid & 7) * 16; }
__device__ __forceinline__ uint32_t acc_extra(uint32_t rank, uint32_t tid) { return 65536 + acc_slice(((tid >> 5) & 1) + rank * 4 + (tid >> 6) * 8) + (tid & 31) * 4; }
__device__ __forceinline__ uint32_t acc_slot(uint32_t it) { return ((it ^ (it >> 1)) & 1) * 128 + (it & 2) * 256; }
__device__ __forceinline__ void acc_init(const __nv_bfloat16* mem0, int i, int lag) {
    const uint32_t tid = i & 255, rank = (i >> 8) & 1, slot = (i >> 9) & 3, X = i >> 11;
    uint32_t v[5] = {0, 0, 0, 0, 0};
    if (slot == ((X * lag + 3) & 3)) {
        const uint16_t* m = (const uint16_t*)mem0 + (tid & 3) * 1024 + rank * 256 + (tid >> 5) * 32 + ((tid >> 2) & 7);
#pragma unroll
        for (int k = 0; k < 4; k++) v[k] = __ldg(m + k * 8) | ((uint32_t)__ldg(m + k * 8 + 512) << 16);
        v[4] = (v[3] >> 16) | 0x42000000u; v[3] = (v[3] & 0xffff) | 0x42000000u;
    }
    *(uint4*)(acc_base() + X * 32768 + acc_slot(slot) + acc_main(rank, tid)) = make_uint4(v[0], v[1], v[2], v[3]);
    *(uint32_t*)(acc_base() + X * 1024 + acc_slot(slot) + acc_extra(rank, tid)) = v[4];
}
__global__ void acc_init_kernel(const __nv_bfloat16* mem0, int lag) { acc_init(mem0, blockIdx.x * 256 + threadIdx.x, lag); }

struct RecW { uint32_t am, ae, ah, dp, lp, lpw, vo, sb, bar, zero, ts, tn; };
__device__ __forceinline__ uint32_t vadd(uint32_t a, uint32_t b) { uint32_t d; asm volatile("add.u32 %0,%1,%2;" : "=r"(d) : "r"(a), "r"(b)); return d; }
__device__ __forceinline__ uint32_t vshr(uint32_t a, int n) { uint32_t d; asm volatile("shr.u32 %0,%1,%2;" : "=r"(d) : "r"(a), "r"(n)); return d; }
__device__ __forceinline__ uint64_t gptr(uint32_t lo, uint32_t hi) { uint64_t d; asm("mov.b64 %0,{%1,%2};" : "=l"(d) : "r"(lo), "r"(hi)); return d; }
__device__ __forceinline__ void sfence(uint32_t zero) { asm volatile("{.reg .pred p; setp.ne.u32 p,%0,0; @p exit;}" ::"r"(zero) : "memory"); }
#define SF sfence(k.zero)
#define TS(i) do {} while (0)
#define TSN(i) do {} while (0)
#define TSET(it, slot) do {} while (0)
struct Gat { uint32_t x, y, z, w, e; };
template <int X>
__device__ __forceinline__ void gat_issue(Gat& g, const RecW& k, uint32_t dep) {
    asm volatile("{.reg .b128 t; ld.relaxed.gpu.global.b128 t,[%5+%7]; mov.b128 {%0,%1,%2,%3},t; ld.relaxed.gpu.global.u32 %4,[%6+%8];}"
                 : "=r"(g.x), "=r"(g.y), "=r"(g.z), "=r"(g.w), "=r"(g.e) : "l"(gptr(k.am + dep, k.ah)), "l"(gptr(k.ae + dep, k.ah)), "n"(X * 32768), "n"(X * 1024) : "memory");
}
template <int X>
__device__ __forceinline__ bool gat_store(const Gat& g, const RecW& k) {
    uint32_t c;
    asm volatile("prmt.b32 %0,%1,%2,0x7632;" : "=r"(c) : "r"(g.w), "r"(g.e));
    SF;
    asm volatile("{.reg .b32 t; prmt.b32 t,%4,%6,0x5410; stmatrix.sync.aligned.m8n8.x4.trans.shared.b16 [%0+%5],{%1,%2,%3,t};}" ::"r"(k.lpw), "r"(g.x), "r"(g.y), "r"(g.z), "r"(g.w), "n"(R_M + X * XS), "r"(g.e) : "memory");
    return __all_sync(0xffffffffu, c == 0x42004200u);
}
template <int X>
__device__ __forceinline__ void gat_finish(bool ok, const RecW& k) {
    if (!ok) {
        int n = 0;
        while (true) {
            Gat g;
            gat_issue<X>(g, k, n & k.zero);
            if (gat_store<X>(g, k)) break;
            if (++n > 2000000) __trap();
        }
    }
    bar_sync(NB_MF + X, 256);
}
__device__ __forceinline__ uint4 lds128o(uint32_t a, int o) { uint4 v; asm volatile("{.reg .b32 t; add.u32 t,%4,%5; ld.shared.v4.u32 {%0,%1,%2,%3},[t];}" : "=r"(v.x), "=r"(v.y), "=r"(v.z), "=r"(v.w) : "r"(a), "r"(o) : "memory"); return v; }
__device__ __forceinline__ uint4 ldsm4o(uint32_t a, int o) { uint4 v; asm volatile("{.reg .b32 t; add.u32 t,%4,%5; ldmatrix.sync.aligned.m8n8.x4.shared.b16 {%0,%1,%2,%3},[t];}" : "=r"(v.x), "=r"(v.y), "=r"(v.z), "=r"(v.w) : "r"(a), "r"(o) : "memory"); return v; }
__device__ __forceinline__ uint4 ldsm4to(uint32_t a, int o) { uint4 v; asm volatile("{.reg .b32 t; add.u32 t,%4,%5; ldmatrix.sync.aligned.m8n8.x4.trans.shared.b16 {%0,%1,%2,%3},[t];}" : "=r"(v.x), "=r"(v.y), "=r"(v.z), "=r"(v.w) : "r"(a), "r"(o) : "memory"); return v; }
__device__ __forceinline__ uint2 lds64o(uint32_t a, int o) { uint2 v; asm volatile("{.reg .b32 t; add.u32 t,%2,%3; ld.shared.v2.u32 {%0,%1},[t];}" : "=r"(v.x), "=r"(v.y) : "r"(a), "r"(o) : "memory"); return v; }
__device__ __forceinline__ void sts128o(uint32_t a, int o, uint32_t x, uint32_t y, uint32_t z, uint32_t w) { asm volatile("{.reg .b32 t; add.u32 t,%0,%5; st.shared.v4.u32 [t],{%1,%2,%3,%4};}" ::"r"(a), "r"(x), "r"(y), "r"(z), "r"(w), "r"(o) : "memory"); }
__device__ __forceinline__ void sts64o(uint32_t a, int o, uint32_t x, uint32_t y) { asm volatile("{.reg .b32 t; add.u32 t,%0,%3; st.shared.v2.u32 [t],{%1,%2};}" ::"r"(a), "r"(x), "r"(y), "r"(o) : "memory"); }
__device__ __forceinline__ uint32_t vxor(uint32_t a, uint32_t b) { uint32_t d; asm volatile("xor.b32 %0,%1,%2;" : "=r"(d) : "r"(a), "r"(b)); return d; }
#define WLD(base, i) wt[i] = lds128o(k.lpw, (base) + (i) * 4096)
template <int PASS, int X, int NP>
__device__ __forceinline__ void rec_qkv(const RecW& k, int s, const uint32_t (*wq)[4], const uint32_t (*wk)[4], uint4* wt, Gat& g2, uint4 mf) {
    constexpr bool BWD = PASS == 2;
    float aq[4] = {0, 0, 0, 0}, ak[4] = {0, 0, 0, 0}, av[4] = {0, 0, 0, 0};
    constexpr int ma = R_M + X * XS;
    if (BWD) { TS(1); gat_finish<1>(gat_store<1>(g2, k), k); mf = ldsm4o(k.lp, ma + 7 * 512); }
    if (BWD) TS(2); else { TS(0); TSN(13); }
    uint32_t ra, rb;
#pragma unroll
    for (int ii = 0; ii < 8; ii++) {
        const int i = BWD ? 7 - ii : ii;
        const uint4 m = mf;
        if (ii < 7) mf = ldsm4o(k.lp, ma + (BWD ? i - 1 : i + 1) * 512);
        else { ra = vadd(k.lpw, k.dp + R_REM + X * XS + (s & 1) * 6144); rb = (ra & k.zero) + (k.bar + X * 16); }
        if (PASS == 1 && ii == G2I) gat_issue<1>(g2, k, 0);
        SF;
#pragma unroll
        for (int hh = 0; hh < 2; hh++) {
            const int h = BWD ? 1 - hh : hh, ks = 2 * i + h;
            const uint32_t b0 = h ? m.z : m.x, b1 = h ? m.w : m.y;
            mma16(aq, wq[ks][0], wq[ks][1], wq[ks][2], wq[ks][3], b0, b1);
            mma16(ak, wk[ks][0], wk[ks][1], wk[ks][2], wk[ks][3], b0, b1);
            SF;
            mma16(av, wt[ks].x, wt[ks].y, wt[ks].z, wt[ks].w, b0, b1);
            SF;
            if (!BWD && ks + NP < 16) WLD(R_WV, ks + NP < 16 ? ks + NP : 0);
            if (BWD && ks >= NT) WLD(R_WV, ks >= NT ? ks - NT : 0);
            SF;
        }
    }
    const uint32_t x0 = movm(pack2(aq[0], aq[1])), x1 = movm(pack2(aq[2], aq[3])), x2 = movm(pack2(ak[0], ak[1])), x3 = movm(pack2(ak[2], ak[3]));
    SF;
    asm volatile("stmatrix.sync.aligned.m8n8.x2.shared.b16 [%0+%3],{%1,%2};" ::"r"(k.vo), "r"(pack2(av[0], av[1])), "r"(pack2(av[2], av[3])), "n"(R_LOC + X * XS) : "memory");
    SF;
    st_async4(ra, x0, x1, x2, x3, rb);
    asm volatile("st.shared.v4.u32 [%0+%5],{%1,%2,%3,%4};" ::"r"(k.lpw), "r"(x0), "r"(x1), "r"(x2), "r"(x3), "n"(R_LOC + X * XS) : "memory");
    bar_arrive(NB_LOC + X, 320);
    SF;
    TS(BWD ? 4 : 3);
}
template <bool BWD, int X>
__device__ __forceinline__ void rec_out(const RecW& k, uint4* wt, Gat& g) {
    if (BWD) { WLD(R_WO, 17 - NTO); WLD(R_WO, 16 - NTO); }
    TS(BWD ? 8 : 5);
    bar_sync(NB_O + X, 320);
    float r0[4] = {0, 0, 0, 0}, r1[4] = {0, 0, 0, 0};
    constexpr int oa = R_O + X * XS;
    uint4 bn = lds128o(k.lp, oa + (BWD ? 3 : 0) * 512);
    TS(BWD ? 9 : 6);
    uint2 il;
    uint64_t pm, pe;
#pragma unroll
    for (int ii = 0; ii < 4; ii++) {
        const int i = BWD ? 3 - ii : ii;
        const uint4 b = bn;
        if (ii < 3) bn = lds128o(k.lp, oa + (BWD ? i - 1 : i + 1) * 512);
        else { asm volatile("ld.shared.v2.u32 {%0,%1},[%2+%3];" : "=r"(il.x), "=r"(il.y) : "r"((vshr(k.ae, 2) & 3) * 8 + k.sb), "n"(R_IL + X * XS) : "memory"); pm = gptr(vadd(k.am, 0), k.ah); pe = gptr(vadd(k.ae, 0), k.ah); }
        SF;
        if (BWD && EARLY == ii + 1) { gat_issue<0>(g, k, 0); SF; }
#pragma unroll
        for (int nn = 0; nn < 4; nn++) {
            const int n = BWD ? 3 - nn : nn, f = 4 * i + n, nx = BWD ? f - NTO + 2 : f + NTO - 2;
            mma16((n & 1) ? r1 : r0, wt[f].x, wt[f].y, wt[f].z, wt[f].w, n >> 1 ? b.z : b.x, n >> 1 ? b.w : b.y);
            SF;
            if (ii * 4 + nn >= 2 && nx >= 0 && nx < 16) WLD(R_WO, nx & 15);
            SF;
        }
    }
    const float i0 = __uint_as_float(il.x), i1 = __uint_as_float(il.y);
    asm volatile("red.relaxed.gpu.global.add.noftz.v4.bf16x2 [%0+%5],{%1,%2,%3,%4};" ::"l"(pm),
                 "r"(pack2(r0[0] * i0, r0[1] * i1)), "r"(pack2(r0[2] * i0, r0[3] * i1)), "r"(pack2(r1[0] * i0, r1[1] * i1)), "r"(pack2(r1[2] * i0, 1.f)), "n"(X * 32768) : "memory");
    asm volatile("red.relaxed.gpu.global.add.noftz.bf16x2 [%0+%2],%1;" ::"l"(pe), "r"(pack2(r1[3] * i1, 1.f)), "n"(X * 1024) : "memory");
    bar_arrive(NB_XG + X, 320);
    SF;
    TS(BWD ? 10 : 7);
}
__device__ __forceinline__ uint32_t pause(uint32_t v, int n) {
#pragma unroll
    for (int i = 0; i < n; i++) asm volatile("shfl.sync.bfly.b32 %0,%0,0,0x1f,0xffffffff;" : "+r"(v));
    return v;
}
template <bool DUAL, int X>
__device__ __forceinline__ void rec_step(RecW& k, int it, int s2, const uint32_t (*wq)[4], const uint32_t (*wk)[4], uint4* wt, uint4& mf) {
    constexpr int NP = NPD;
    uint4 wo[16];
    Gat g;
    rec_qkv<DUAL ? 1 : 0, X, NP>(k, X ? s2 : it, wq, wk, wt, g, mf);
    if (DUAL) rec_qkv<2, 1, NP>(k, s2, wq, wk, wt, g, mf);
    k.am = vxor(k.am, (it & 1) ? 128 : 512); k.ae = vxor(k.ae, (it & 1) ? 128 : 512);
    uint32_t wa = k.lpw;
#pragma unroll
    for (int i = 0; i < NTO; i++) {
        wo[i] = lds128o(wa, R_WO + i * 4096);
        if (i % PACE == PACE - 1) wa = k.lpw + (wo[i].x & k.zero);
        SF;
    }
    rec_out<false, X>(k, wo, g);
    if (DUAL) { rec_out<true, 1>(k, wo, g); if (!EARLY) gat_issue<0>(g, k, 0); SF; }
#pragma unroll
    for (int i = 0; i < NP; i++) { WLD(R_WV, i); SF; }
    if (!DUAL) gat_issue<X>(g, k, pause(wt[NP - 1].x & k.zero, DP1));
    TS(12);
    gat_finish<X>(gat_store<X>(g, k), k);
    mf = ldsm4o(k.lp, R_M + X * XS);
}

__device__ __forceinline__ void rec_fetch(const CUtensorMap* tm, uint32_t dst, int x, int y, int nx, uint32_t bar) {
#pragma unroll 1
    for (int j = 0; j < 8; j++) tma2d(dst + j * 8192, tm, x + (j / (8 / nx)) * 64, y + (j % (8 / nx)) * 64, bar);
}
__device__ __forceinline__ void rec_weights(const Params& p, uint32_t sb, int head, uint32_t rank, int w) {
    const int lane = threadIdx.x & 31, t = w & 3, WG = w >> 2;
    uint32_t wq[16][4], wk[16][4];
    const uint32_t rowo = (((lane >> 4) << 3) + (lane & 7)) * 128;
    const uint32_t woff = sb + WG * 32768 + rowo + (((2 * t + ((lane >> 3) & 1)) ^ (lane & 7)) << 4);
    const uint32_t qoff = sb + ((w & 1) ? R_STK : R_STQ) + WG * 32768 + rowo + (((2 * (t & 2) + ((lane >> 3) & 1)) ^ (lane & 7)) << 4);
    const uint32_t lw = sb + (lane ^ (lane >> 3)) * 16;
    PROF(threadIdx.x == 0, 3501);
    PROF(threadIdx.x == 0, 3502);
    mbar_wait(sb + R_BAR + RB_INIT * 8, 0);
    PROF(threadIdx.x == 0, 3503);
#pragma unroll
    for (int ks = 0; ks < 16; ks++) {
        uint4 a = ldsm4t(qoff + ks * 2048), b = ldsm4t((qoff ^ 32) + ks * 2048);
        wq[ks][0] = a.x; wq[ks][1] = a.y; wq[ks][2] = a.z; wq[ks][3] = a.w;
        wk[ks][0] = b.x; wk[ks][1] = b.y; wk[ks][2] = b.z; wk[ks][3] = b.w;
    }
    bar_sync(NB_W, 256);
#pragma unroll 4
    for (int ks = 0; ks < 16; ks++) { const uint4 a = ldsm4t(woff + R_STV + ks * 2048); sts128(lw + w * 512 + R_WV + ks * 4096, a.x, a.y, a.z, a.w); }
    bar_sync(NB_W, 256);
    if (threadIdx.x == 0) {
        mbar_expect(sb + R_BAR + RB_INIT * 8, 65536);
        rec_fetch(&p.tm[4], sb + R_STV, rank * 256, head * 128, 4, sb + R_BAR + RB_INIT * 8);
    }
    __syncwarp();
    mbar_wait(sb + R_BAR + RB_INIT * 8, 1);
#pragma unroll 4
    for (int f = 0; f < 16; f++) {
        const uint4 a = ldsm4t(sb + R_STV + (w >> 1) * 16384 + (f >> 1) * 2048 + rowo + ((((w & 1) * 4 + (f & 1) * 2 + ((lane >> 3) & 1)) ^ (lane & 7)) << 4));
        sts128(lw + w * 512 + R_WO + f * 4096, a.x, a.y, a.z, a.w);
    }
    PROF(threadIdx.x == 0, 3504);
    __syncthreads();
    cluster_sync();
    PROF(threadIdx.x == 0, 3505);
    RecW k;
    k.am = __shfl_sync(0xffffffffu, (uint32_t)(size_t)acc_base() + acc_slot(3) + acc_main(rank, threadIdx.x), lane);
    k.ae = __shfl_sync(0xffffffffu, (uint32_t)(size_t)acc_base() + acc_slot(3) + acc_extra(rank, threadIdx.x), lane);
    k.ah = (uint32_t)((size_t)acc_base() >> 32);
    k.sb = sb; k.zero = p.zero;

    k.dp = mapa(sb, rank ^ 1) - sb;
    k.lp = __shfl_sync(0xffffffffu, lw, lane);
    k.lpw = __shfl_sync(0xffffffffu, lw + w * 512, lane);
    k.vo = __shfl_sync(0xffffffffu, sb + 4096 + w * 256 + (((lane & 15) ^ ((w & 1) * 4 + ((lane >> 3) & 1) * 2)) << 4), lane);
    k.bar = sb + k.dp + R_BAR + (RB_QK + WG) * 8;
    int it = 0;
    uint4 wt[16];
#pragma unroll
    for (int i = 0; i < NPD; i++) WLD(R_WV, i);
    gat_finish<0>(false, k);
    uint4 mf = ldsm4o(k.lp, R_M);
#pragma unroll 1
    for (; it < min(p.b1, p.e0); it++) { TSET(it, w == GPW ? 0 : 3); rec_step<false, 0>(k, it, it, wq, wk, wt, mf); }
#pragma unroll 1
    for (; it < p.e0; it++) { TSET(it, w == GPW ? 0 : 3); rec_step<true, 0>(k, it, it - p.b1, wq, wk, wt, mf); }
    if (it < p.nit) { gat_finish<1>(false, k); mf = ldsm4o(k.lp, R_M + XS); }
#pragma unroll 1
    for (; it < p.nit; it++) { TSET(it, w == GPW ? 0 : 3); rec_step<false, 1>(k, it, it - p.b1, wq, wk, wt, mf); }
}

__device__ __forceinline__ void mma16_top(float* c, uint32_t a0, uint32_t a2, uint32_t b0, uint32_t b1) {
    asm volatile("{.reg .b32 j; mma.sync.aligned.m16n8k16.row.col.f32.bf16.bf16.f32 {%0,%1,%2,%3},{%4,j,%5,j},{%6,%7},{%0,%1,%2,%3};}"
                 : "+f"(c[0]), "+f"(c[1]), "+f"(c[2]), "+f"(c[3]) : "r"(a0), "r"(a2), "r"(b0), "r"(b1));
}
__device__ __forceinline__ void rec_load_tile(uint32_t sb, int X, int j, int s, int head, uint32_t rank) {
    const uint32_t bar = sb + R_BAR + (RB_T + X * 2 + j) * 8;
    mbar_expect1(bar, j ? 4096 : 16384);
    bulk_g2s1(sb + R_T + X * XS + j * 16384, g_qkv[X] + (size_t)(s * 32 + head) * 1536 + (j ? rank * 256 : 512), j ? 4096 : 16384, bar, POL_LAST);
}
__device__ __forceinline__ bool chunk_ready(int X, int j, int s) {
    unsigned v;
    asm volatile("ld.relaxed.gpu.global.u32 %0,[%1];" : "=r"(v) : "l"(cnt_ptr(C_QKV0 + X, (s >> 2) + j * 16)) : "memory");
    return __all_sync(0xffffffffu, v >= (256 >> j));
}
__device__ __forceinline__ uint4 hadd4(uint4 a, uint4 b) { return make_uint4(hadd2(a.x, b.x), hadd2(a.y, b.y), hadd2(a.z, b.z), hadd2(a.w, b.w)); }
struct RecH { uint32_t lw, lm, lq, lv, lu, sa, sp, xb, sb, zero, ts, tn; };
__device__ __forceinline__ void rec_publish(int X, int s) {
    asm volatile("{.reg .pred p; cp.async.bulk.wait_group 0; elect.sync _|p,0xffffffff; @p red.relaxed.gpu.global.add.u32 [%0],4;}" ::"l"(cnt_ptr(C_O0 + X, s >> 2)) : "memory");
}
__device__ __forceinline__ void rec_mattn(const RecH& k, uint32_t dp, int X, int j, int s, uint4 (*V)[4], uint4* vm, uint4* kmm) {
    const uint32_t sb = k.sb, to = R_T, lo = R_LOC, ro = R_REM + (s & 1) * 6144;
    const uint32_t bar = sb + R_BAR + (X * 2 + j) * 8;
    uint4 K[2][4];
    mbar_wait(sb + R_BAR + (RB_T + X * 2) * 8, s & 1);
    TS(1);
#pragma unroll
    for (int i = 0; i < 8; i++) K[i >> 2][i & 3] = ldsm4o(k.lm, (to + (i >> 2) * 1024 + ((i >> 1) & 1) * 4096 + (i & 1) * 512));
    asm volatile("cp.async.bulk.wait_group 0;" ::: "memory");
    bar_sync(NB_LOC + X, 320);
    fence_async_smem();
    asm volatile("{.reg .pred p; elect.sync _|p,0xffffffff; @p cp.async.bulk.shared::cluster.shared::cta.mbarrier::complete_tx::bytes [%0],[%1],1024,[%2];}"
                 ::"r"(k.xb + dp + ro + 4096), "r"(k.xb + lo + 4096), "r"(bar + dp + RB_V * 8) : "memory");
    uint4 u[4];
#pragma unroll
    for (int i = 0; i < 4; i++) u[i] = ldsm4o(k.lm, (lo + i * 512));
    TS(2);
    mbar_wait(bar + RB_QK * 8, s & 1);
    TS(3);
    float S[5][4];
#pragma unroll
    for (int i = 0; i < 5; i++) S[i][0] = S[i][1] = S[i][2] = S[i][3] = 0;
    {
        uint4 r[4];
#pragma unroll
        for (int i = 0; i < 4; i++) r[i] = ldsm4o(k.lm, (ro + i * 512));
        SF;
#pragma unroll
        for (int e = 0; e < 2; e++) {
            uint4& km = u[2 * e + 1];
            const uint32_t q0 = hadd2(u[2 * e].x, r[2 * e].x), q1 = hadd2(u[2 * e].y, r[2 * e].y);
            mma16_top(S[0], q0, q1, K[e][0].x, K[e][0].y);
            km.x = hadd2(km.x, r[2 * e + 1].x); km.y = hadd2(km.y, r[2 * e + 1].y);
            SF;
            mma16_top(S[1], q0, q1, K[e][1].x, K[e][1].y);
            const uint32_t q2 = hadd2(u[2 * e].z, r[2 * e].z), q3 = hadd2(u[2 * e].w, r[2 * e].w);
            SF;
            mma16_top(S[2], q0, q1, K[e][2].x, K[e][2].y);
            km.z = hadd2(km.z, r[2 * e + 1].z); km.w = hadd2(km.w, r[2 * e + 1].w);
            SF;
            mma16_top(S[3], q0, q1, K[e][3].x, K[e][3].y);
            mma16_top(S[4], q0, q1, km.x, km.y);
            SF;
#pragma unroll
            for (int i = 0; i < 4; i++) {
                mma16_top(S[i], q2, q3, K[e][i].z, K[e][i].w); SF;
            }
            mma16_top(S[4], q2, q3, km.z, km.w);
            SF;
        }
    }
#define VLD(a, b) _Pragma("unroll") for (int i = (a); i < (b); i++) V[i >> 2][i & 3] = ldsm4to((i & 1) ? lv2 : k.lv, (to + 8192 + (i >> 2) * 4096 + ((i >> 1) & 1) * 1024))
    const uint32_t lv2 = vxor(k.lv, 0x20), lh = k.lw - (vshr(k.lw - k.xb, 1) & 0xf8);
    VLD(0, VE);
    SF;
    const uint32_t sxr = k.sa, sxw = k.sp;
    sts128o(k.lw, sxw, __float_as_uint(S[0][0]), __float_as_uint(S[0][1]), __float_as_uint(S[1][0]), __float_as_uint(S[1][1]));
    SF;
    sts128o(k.lw, (sxw + 512), __float_as_uint(S[2][0]), __float_as_uint(S[2][1]), __float_as_uint(S[3][0]), __float_as_uint(S[3][1]));
    SF;
    sts64o(lh, (sxw + 1024), __float_as_uint(S[4][0]), __float_as_uint(S[4][1]));
    TS(4);
    bar_sync(NB_PAIR + X, 64);
    {
        const uint4 a = lds128o(k.lw, sxr), b = lds128o(k.lw, (sxr + 512));
        const uint2 c = lds64o(lh, (sxr + 1024));
        SF;
        VLD(VE, VF);
        SF;
        S[0][0] += __uint_as_float(a.x); S[0][1] += __uint_as_float(a.y); S[1][0] += __uint_as_float(a.z); S[1][1] += __uint_as_float(a.w);
        S[2][0] += __uint_as_float(b.x); S[2][1] += __uint_as_float(b.y); S[3][0] += __uint_as_float(b.z); S[3][1] += __uint_as_float(b.w);
        S[4][0] += __uint_as_float(c.x); S[4][1] += __uint_as_float(c.y);
    }
    float m = fmaxf(fmaxf(fmaxf(S[0][0], S[0][1]), fmaxf(S[1][0], S[1][1])), fmaxf(fmaxf(S[2][0], S[2][1]), fmaxf(S[3][0], S[3][1])));
    m = fmaxf(m, fmaxf(S[4][0], S[4][1]));
    m = fmaxf(m, __shfl_xor_sync(0xffffffffu, m, 1));
    const float m2 = __shfl_xor_sync(0xffffffffu, m, 2);
    SF;
    VLD(VF, 8);
    uint32_t ok;
    asm volatile("{.reg .pred p; mbarrier.test_wait.parity.shared::cta.b64 p,[%1],%2; selp.u32 %0,1,0,p;}" : "=r"(ok) : "r"(bar + RB_V * 8), "r"(s & 1) : "memory");
    uint4 vr0 = ldsm4o(k.lu, (ro + 4096)), vr1 = ldsm4o(k.lu, (ro + 4608));
    vm[0] = ldsm4o(k.lu, (lo + 4096)); vm[1] = ldsm4o(k.lu, (lo + 4608));
    SF;
    TS(5);
    m = fmaxf(m, m2) * -SC_LOG2E;
    uint32_t P[5];
#pragma unroll
    for (int i = 0; i < 5; i++) P[i] = pack2(ex2(fmaf(S[i][0], SC_LOG2E, m)), ex2(fmaf(S[i][1], SC_LOG2E, m)));
    float o[4][4], l[4] = {0, 0, 0, 0};
    const uint32_t ONE = 0x3f803f80u;
    mma16_top(l, ONE, ONE, P[0], P[1]);
#pragma unroll
    for (int t = 0; t < 4; t++) { o[t][0] = o[t][1] = o[t][2] = o[t][3] = 0; mma16(o[t], V[0][t].x, V[0][t].y, V[0][t].z, V[0][t].w, P[0], P[1]); }
    mma16_top(l, ONE, ONE, P[2], P[3]);
#pragma unroll
    for (int t = 0; t < 4; t++) mma16(o[t], V[1][t].x, V[1][t].y, V[1][t].z, V[1][t].w, P[2], P[3]);
    if (!__all_sync(0xffffffffu, ok)) {
        mbar_wait(bar + RB_V * 8, s & 1);
        vr0 = ldsm4o(k.lu, (ro + 4096)); vr1 = ldsm4o(k.lu, (ro + 4608));
    }
    TS(6);
    vm[0] = hadd4(vm[0], vr0); vm[1] = hadd4(vm[1], vr1);
    mma8(l, ONE, ONE, P[4]);
    mma8(o[0], vm[0].x, vm[0].y, P[4]); mma8(o[1], vm[0].z, vm[0].w, P[4]); mma8(o[2], vm[1].x, vm[1].y, P[4]); mma8(o[3], vm[1].z, vm[1].w, P[4]);
    asm volatile("{.reg .pred p; .reg .b32 t; setp.lt.u32 p,%0,%3; add.u32 t,%0,%4; @p st.shared.v2.f32 [t],{%1,%2};}" ::"r"(lh), "f"(rcp(l[0])), "f"(rcp(l[1])), "r"(k.xb + 32), "r"(R_IL) : "memory");
#pragma unroll
    for (int t = 0; t < 4; t += 2)
        asm volatile("{.reg .b32 t; add.u32 t,%0,%5; stmatrix.sync.aligned.m8n8.x4.trans.shared.b16 [t],{%1,%2,%3,%4};}" ::"r"(k.lm),
                     "r"(pack2(o[t][0], o[t][1])), "r"(pack2(o[t][2], o[t][3])), "r"(pack2(o[t + 1][0], o[t + 1][1])), "r"(pack2(o[t + 1][2], o[t + 1][3])), "r"(R_O - j * 1024 + t * 256) : "memory");
    bar_arrive(NB_O + X, 320);
    PROF(k.lw == k.xb, X * 64 + s);
    TS(7);
    kmm[0] = u[1]; kmm[1] = u[3];
    mbar_expect1(bar + RB_QK * 8, 2048); mbar_expect1(bar + RB_V * 8, 1024);
}
template <int MT>
__device__ __forceinline__ void rec_xattn(const RecH& k, int X, int j, int s, int head, bool early, const uint4 (*V)[4], const uint4* vmm, const uint4* kmm) {
    constexpr int NTL = 3 + 2 * MT;
    const uint32_t sb = k.sb, to = R_T;
    const uint32_t sxw = k.sa, sxr = k.sp;
    const uint32_t lq2 = vxor(k.lq, 0x20);
    float S[NTL][4];
#pragma unroll
    for (int i = 0; i < NTL; i++) S[i][0] = S[i][1] = S[i][2] = S[i][3] = 0;
    {
        uint4 q[2][2], kk[2][NTL];
#define XQ(e) q[e][0] = ldsm4o(k.lq, (to + 16384 + (e) * 1024)); q[e][1] = ldsm4o(lq2, (to + 16384 + (e) * 1024))
#define XK(e, i) kk[e][i] = ldsm4o(k.lm, (to + (e) * 1024 + (((i) - 1) >> 1) * 4096 + (((i) - 1) & 1) * 512))
        kk[0][0] = kmm[0]; kk[1][0] = kmm[1];
        if (!X) bar_sync(NB_XG, 320);
        XQ(0);
#pragma unroll
        for (int i = 1; i < NTL; i++) XK(0, i);
        SF;
#pragma unroll
        for (int i = 0; i < NTL; i++) { mma16(S[i], q[0][0].x, q[0][0].y, q[0][0].z, q[0][0].w, kk[0][i].x, kk[0][i].y); SF; }
        q[1][0] = ldsm4o(k.lq, (to + 16384 + 1024));
#pragma unroll
        for (int i = 0; i < NTL; i++) { mma16(S[i], q[0][1].x, q[0][1].y, q[0][1].z, q[0][1].w, kk[0][i].z, kk[0][i].w); SF; if (i + 1 < NTL) XK(1, i + 1); SF; }
        q[1][1] = ldsm4o(lq2, (to + 16384 + 1024));
        SF;
#pragma unroll
        for (int i = 0; i < NTL; i++) { mma16(S[i], q[1][0].x, q[1][0].y, q[1][0].z, q[1][0].w, kk[1][i].x, kk[1][i].y); SF; }
#pragma unroll
        for (int i = 0; i < NTL; i++) { mma16(S[i], q[1][1].x, q[1][1].y, q[1][1].z, q[1][1].w, kk[1][i].z, kk[1][i].w); SF; }
    }
#pragma unroll
    for (int i = 0; i < NTL; i++) sts128o(k.lw, (sxw + i * 512), __float_as_uint(S[i][0]), __float_as_uint(S[i][1]), __float_as_uint(S[i][2]), __float_as_uint(S[i][3]));
    SF;
    if (X) bar_sync(NB_XG + 1, 320); else bar_sync(NB_PAIR + 2, 64);
    TS(9);
    if (early && !X) rec_load_tile(sb, X, j, s + 1, head, MT);
#pragma unroll
    for (int i = 0; i < NTL; i++) {
        const uint4 r = lds128o(k.lw, (sxr + i * 512));
        S[i][0] += __uint_as_float(r.x); S[i][1] += __uint_as_float(r.y); S[i][2] += __uint_as_float(r.z); S[i][3] += __uint_as_float(r.w);
    }
    const int g = vshr(k.lw - k.xb, 6) & 7, c = (vshr(k.lw, 4) ^ (g >> 1)) & 3;
    const float NEG = -__int_as_float(0x7f800000);
    if (2 * c > g) { S[NTL - 2][0] = NEG; S[NTL - 1][2] = NEG; }
    if (2 * c + 1 > g) { S[NTL - 2][1] = NEG; S[NTL - 1][3] = NEG; }
    float m0 = fmaxf(S[0][0], S[0][1]), m1 = fmaxf(S[0][2], S[0][3]);
#pragma unroll
    for (int i = 1; i < NTL; i++) { if (i < NTL - 1) m0 = fmaxf(m0, fmaxf(S[i][0], S[i][1])); m1 = fmaxf(m1, fmaxf(S[i][2], S[i][3])); }
    m0 = fmaxf(m0, __shfl_xor_sync(0xffffffffu, m0, 1)); m1 = fmaxf(m1, __shfl_xor_sync(0xffffffffu, m1, 1));
    m0 = fmaxf(m0, __shfl_xor_sync(0xffffffffu, m0, 2)); m1 = fmaxf(m1, __shfl_xor_sync(0xffffffffu, m1, 2));
    m0 *= -SC_LOG2E; m1 *= -SC_LOG2E;
    uint32_t P[NTL][2];
#pragma unroll
    for (int i = 0; i < NTL; i++) {
        P[i][0] = i < NTL - 1 ? pack2(ex2(fmaf(S[i][0], SC_LOG2E, m0)), ex2(fmaf(S[i][1], SC_LOG2E, m0))) : 0u;
        P[i][1] = pack2(ex2(fmaf(S[i][2], SC_LOG2E, m1)), ex2(fmaf(S[i][3], SC_LOG2E, m1)));
    }
    float l[4] = {0, 0, 0, 0};
#pragma unroll
    for (int i = 0; i < NTL; i++) mma8(l, P[i][0], P[i][1], 0x3f803f80u);
    const float l0 = rcp(l[0]), l1 = rcp(l[2]);

#pragma unroll
    for (int e = 0; e < 2; e++) {
        const uint4 vm = vmm[e];
        uint32_t u[2][4];
#pragma unroll
        for (int n = 0; n < 4; n++) {
            float a[4] = {0, 0, 0, 0};
#pragma unroll
            for (int m = 0; m <= MT; m++) {
                const uint4 v = V[m][e * 2 + (n >> 1)];
                mma8(a, P[1 + 2 * m][0], P[1 + 2 * m][1], (n & 1) ? v.y : v.x); mma8(a, P[2 + 2 * m][0], P[2 + 2 * m][1], (n & 1) ? v.w : v.z);
            }
            mma8(a, P[0][0], P[0][1], n == 0 ? vm.x : n == 1 ? vm.y : n == 2 ? vm.z : vm.w);
            u[0][n] = pack2(a[0] * l0, a[1] * l0); u[1][n] = pack2(a[2] * l1, a[3] * l1);
        }
        sts128o(k.lw, sxr + e * 512, u[0][0], u[0][1], u[0][2], u[0][3]); sts128o(k.lw, sxr + e * 512 + 1024, u[1][0], u[1][1], u[1][2], u[1][3]);
    }
    if (early && X) rec_load_tile(sb, X, j, s + 1, head, MT);
    TS(10);
}
__device__ __forceinline__ void rec_attn(const Params& p, uint32_t sb, int X, int j, int head, uint32_t rank) {
    const int lane = threadIdx.x & 31;
    RecH k;
    k.xb = sb + X * XS + j * 1024;
    const uint32_t x2 = k.xb + j * 1024;
    k.lw = __shfl_sync(0xffffffffu, x2 + (lane ^ (lane >> 3)) * 16, lane);
    k.lm = __shfl_sync(0xffffffffu, x2 + ((lane & 7) * 4 + ((lane >> 3) ^ ((lane & 7) >> 1))) * 16, lane);
    k.lq = __shfl_sync(0xffffffffu, x2 + ((lane >> 3) & 1) * 512 + ((lane & 7) * 4 + ((lane >> 4) ^ ((lane & 7) >> 1))) * 16, lane);
    k.lv = __shfl_sync(0xffffffffu, x2 + (lane >> 4) * 512 + ((lane & 7) * 4 + (((lane >> 3) & 1) ^ ((lane & 7) >> 1))) * 16, lane);
    k.lu = __shfl_sync(0xffffffffu, k.xb + ((lane & 6) * 4 + (((lane >> 3) * 2 + (lane & 1)) ^ (lane & 6))) * 16, lane);
    k.sa = __shfl_sync(0xffffffffu, R_SX + j * 512, 0); k.sp = __shfl_sync(0xffffffffu, R_SX + 2560 - j * 4608, 0);
    k.sb = sb; k.zero = p.zero;
    const uint32_t dp = mapa(sb, rank ^ 1) - sb;
    char* zp = acc_base() + (j ? X * 32768 + acc_main(rank, head * 8) : X * 1024 + acc_extra(rank, head * 8));
    mbar_expect1(sb + R_BAR + (RB_QK + X * 2 + j) * 8, 2048); mbar_expect1(sb + R_BAR + (RB_V + X * 2 + j) * 8, 1024);
    bool early = false;
#pragma unroll 1
    for (int s = 0; s < 64; s++) {
        TSET(X ? s + p.b1 : s, j == GPJ ? 1 + X : 3);
        TS(0);
        if (!early) {
            if (!j) wait_cnt_warp(cnt_ptr(C_QKV0 + X, s >> 2), 256);
            early = !j || chunk_ready(X, 1, s);
            if (early) rec_load_tile(sb, X, j, s, head, rank);
        }
        uint4 V[2][4], vm[2], km[2];
        rec_mattn(k, dp, X, j, s, V, vm, km);
        if (!early) { wait_cnt_warp(cnt_ptr(C_QKV0 + X, (s >> 2) + 16), 128); rec_load_tile(sb, X, 1, s, head, rank); }
        early = s < 63 && ((s & 3) != 3 || chunk_ready(X, j, s + 1));
        mbar_wait(sb + R_BAR + (RB_T + X * 2 + 1) * 8, s & 1);
        if (rank) rec_xattn<1>(k, X, j, s, head, early, V, vm, km); else rec_xattn<0>(k, X, j, s, head, early, V, vm, km);
        fence_async_smem();
        __syncwarp();
        asm volatile("{.reg .pred p; elect.sync _|p,0xffffffff;\n"
                     "@p cp.async.bulk.global.shared::cta.bulk_group.L2::cache_hint [%0],[%1],2048,%2;\n"
                     "@p cp.async.bulk.global.shared::cta.bulk_group [%3],[%4],%5;\n"
                     "cp.async.bulk.commit_group;}"
                     ::"l"(g_o[X] + ((s >> 2) * 64 + head * 2 + j) * 1024 + ((s & 3) * 2 + rank) * 128), "r"(x2 + k.sp),
                       "l"((X && s < 40) ? POL_LATE : POL_SOON), "l"(zp + acc_slot(s + 2 + X * p.lag)), "r"(sb + R_Z), "r"(j ? 128 : 32) : "memory");
        if (s == 61) rec_publish(X, 64);
        if ((s & 3) == 3) {
            if (!early && s < 63 && chunk_ready(X, j, s + 1)) { rec_load_tile(sb, X, j, s + 1, head, rank); early = true; }
            rec_publish(X, s);
            PROF(lane == 0 && j, 3900 + X * 16 + (s >> 2));
        }
    }
}

__device__ __forceinline__ void rec_init(const Params& p, uint32_t sb, int head, uint32_t rank) {
    const uint32_t b = sb + R_BAR;
    const int i = threadIdx.x - 320;
    if (i >= 0 && i < RB_N) {
        mbar_init(b + i * 8, 1);
        asm volatile("fence.mbarrier_init.release.cluster;" ::: "memory");
    }
    if (i == 0) mbar_expect(b + RB_INIT * 8, 196608);
    if (i >= 0 && i < 32) sts32(sb + R_Z + i * 4, 0);
}

#define NSTGN 8
constexpr int NSTG = NSTGN, STG_B = 24576;
#define LAGH 3
constexpr int NSB = 8;
constexpr int B_OUT = NSTG * STG_B  , B_UT = B_OUT, B_YT = B_UT + 16384, B_SP = B_YT  ,
              B_ST = 229376  , B_BAR = 231936;
static_assert(B_OUT + NSB * 4096 <= B_ST && B_ST + 2048 <= B_BAR && B_YT + 10240 <= B_ST, "smem map");
enum { BB_FULL = 0, BB_EMPTY = 8, BB_SF = 16  , BB_GO = 18, BB_LOW = 19, BB_DONE = 20  , BB_IDLE = 22  , BB_N = 30 };
enum { NB_REL = 2  , NB_C = 11, NB_WG = 12  , NB_PH = 14 };

__device__ __forceinline__ void bulk_init(uint32_t sb) {
    const int i = threadIdx.x - 320;
    if (i >= 0 && i < BB_N) {
        mbar_init(sb + B_BAR + i * 8, (i >= BB_EMPTY && i < BB_EMPTY + NSTG) ? 4 : i >= BB_DONE ? 4 : 1);
        asm volatile("fence.mbarrier_init.release.cluster;" ::: "memory");
    }
}

struct Task { int type, layer, ch, a, b, c, blk; bool pair, dry; };
__device__ __forceinline__ Task task_of(uint32_t tk, uint32_t rank) {
    Task t;
    t.type = tk & 7; t.layer = (tk >> 3) & 1; t.a = (tk >> 8) & 255; t.b = (tk >> 16) & 255; t.c = (tk >> 24) & 127; t.dry = tk >> 31;
    t.pair = t.type <= T_OP && (t.c & 64);
    t.ch = ((tk >> 4) & 15) + (t.pair ? rank : 0);
    t.blk = t.type == T_QKV ? t.a + (t.pair ? 0 : rank) : 192 + (t.pair ? (t.c >> 2) & 4 : rank * 4);
    return t;
}
__device__ __forceinline__ int qkv_blk(const Task& t, int u) {
    const int v = t.blk + (t.pair ? 1 : 2 * t.c) * u;
    return 2 * (v < 64 ? v + 32 : v - 64);
}
__device__ __forceinline__ void bulk_producer(const Params& p, uint32_t sb, int cl, uint32_t rank) {
    int st = 0; uint32_t ph = 1;
    const int tag = __shfl_sync(0xffffffffu, lds32(sb + S_TAG), 0);
    bool gated = false;
#define ACQ(bytes) do { mbar_wait(sb + B_BAR + (BB_EMPTY + st) * 8, ph); mbar_expect1(sb + B_BAR + (BB_FULL + st) * 8, bytes); } while (0)
#define NEXT do { if (++st == NSTG) { st = 0; ph ^= 1; } } while (0)
#pragma unroll 1
    for (int ti = 0; ti < MAXT; ti++) {
        const Task t = task_of(p.task[list_of(cl)][ti], rank);
        const int layer = t.layer, ch = t.ch;
        if (t.type == T_END) break;
        if (t.type <= T_OP) {
            const bool qkv = t.type == T_QKV;
            const int nh = (qkv ? 8 : 2) * t.b;
            const bool halves = !qkv && (t.c & 80) == 16;
            const unsigned* dep = cnt_ptr(qkv ? (layer ? C_CV : C_ST) : C_O0 + layer, ch + (halves && !rank));
            const unsigned need = qkv ? (layer ? 32 : ch < 2 ? 0 : 16) : 512;
            const uint16_t mb = t.pair ? 3 : 1 << rank, ma = t.pair ? 1 << rank : 3;
            const int pend = min(nh, gated ? NSTG : 4);
            auto ready = [&](int h) {
                if (h < pend) {
                    unsigned v = 0;
                    if (gated) asm volatile("ld.relaxed.gpu.global.u32 %0,[%1];" : "=r"(v) : "l"(dep) : "memory");
                    return gated && __all_sync(0xffffffffu, v >= need);
                }
                if (!gated) { wait_cnt_warp(g_gate, lds32(sb + S_GATE)); gated = true; }
                if (need) wait_cnt_warp(dep, need);
                return true;
            };
            bool open = true;
            if (qkv) {
#pragma unroll 1
                while (st) { ACQ(0); NEXT; }
#pragma unroll 1
                for (int h = 0; h < nh; h++) {
                    const int blk = qkv_blk(t, h >> 3);
                    ACQ(16384 + (h < 2 ? (layer ? 8192 : 1024) : 0));
                    if (!t.pair || !rank) tma3d_mc(sb + st * STG_B, &p.t3[blk >> 6], (h & 7) * 64, blk & 63, sb + B_BAR + (BB_FULL + st) * 8, mb);
                    if (!t.pair || rank) tma3d_mc(sb + st * STG_B + 8192, &p.t3[blk >> 6], (h & 7) * 64 + 32, blk & 63, sb + B_BAR + (BB_FULL + st) * 8, mb);
                    NEXT;
                    if (open && h && ready(h + 1)) {
                        open = false;
                        const float2* sp = g_st[layer] + ch * 2048 + (need ? 0 : tag * 256);
                        bulk_g2s1(sb + 16384, sp, layer ? 8192 : 1024, sb + B_BAR + BB_FULL * 8, POL_N);
                        bulk_g2s1(sb + STG_B + 16384, sp + (layer ? 1024 : 128), layer ? 8192 : 1024, sb + B_BAR + (BB_FULL + 1) * 8, POL_N);
                    }
                }
                continue;
            }
            if (PFC && !layer && (t.c & 15) < 8) {
                const int q = (t.c & 15) * 2 + rank;
                asm volatile("{.reg .pred p; elect.sync _|p,0xffffffff; @p cp.async.bulk.prefetch.L2.global [%0],8192; @p cp.async.bulk.prefetch.L2.global [%1],%2;}"
                             ::"l"(g_xA[0] + (ch * 16 + q) * 512), "l"(g_P + q * 16 * 32 * PW), "r"((2 + (ch & 1)) * 32 * PW * 4) : "memory");
            }
            const CUtensorMap *tb = &p.t3[4 - t.pair], *ta = &p.ta[t.pair];
            const uint32_t db = sb + 8192 + (t.pair ? rank * 8192 : 0), da = sb + (t.pair ? 0 : rank * 4096);
            const int zb = (t.blk & 63) + (t.pair ? rank * 2 : 0), ya = 4096 + ((layer * 16 + ch) * 64 + t.a) * 16 + (t.pair ? 0 : rank * 8), row = t.a * 64;
            int h = 0;
            const int s0 = st;
            if (halves) mbar_expect1(sb + B_BAR + BB_LOW * 8, NSTG * 4096);
#pragma unroll 1
            for (; (halves && h < NSTG) || !ready(h); h++) { ACQ(halves ? STG_B - 4096 : STG_B); tma3d_mc(db + st * STG_B, tb, row + h * 32, zb, sb + B_BAR + (BB_FULL + st) * 8, mb); NEXT; }
#pragma unroll 1
            for (int k = 0; k < h; k++) {
                const int s2 = (s0 + k) & (NSTG - 1);
                tma2d_mc(da + s2 * STG_B, ta, (k & 1) * 256, ya + (k >> 1) * 16, sb + B_BAR + (halves && rank ? BB_LOW : BB_FULL + s2) * 8, ma, POL_LAST);
            }
#pragma unroll 1
            for (; h < nh; h++) {
                ACQ(STG_B);
                tma3d_mc(db + st * STG_B, tb, row + h * 32, zb, sb + B_BAR + (BB_FULL + st) * 8, mb);
                tma2d_mc(da + st * STG_B, ta, (h & 1) * 256, ya + (h >> 1) * 16, sb + B_BAR + (BB_FULL + st) * 8, ma, POL_LAST);
                NEXT;
            }
#pragma unroll 1
            for (h = 0; h < 4 && !layer; h++) { ACQ(0); NEXT; }
        } else if (t.type == T_CV) {
            const int q = t.a + rank;
            if (!gated) { wait_cnt_warp(g_gate, lds32(sb + S_GATE)); gated = true; }
            if (layer) {
                wait_cnt_warp(cnt_ptr(C_U, ch - 2), 32);
#pragma unroll 1
                for (int j = ch + 1; j >= 2; j--) {
                    ACQ(16 * PW * 4 + (j > 2 ? 4096 : 0));
                    bulk_g2s1(sb + st * STG_B, g_P + (((q >> 1) * 16 + j) * 2 + (q & 1)) * 16 * PW, 16 * PW * 4, sb + B_BAR + (BB_FULL + st) * 8, POL_N);
                    if (j > 2) bulk_g2s1(sb + st * STG_B + 12288, g_u + (((q >> 1) * 16 + ch + 1 - j) * 2 + (q & 1)) * 256, 4096, sb + B_BAR + (BB_FULL + st) * 8, POL_N);
                    NEXT;
                }
            } else {
#pragma unroll 1
                for (int j = min(ch, 1 + (ch & 1)); j >= 0; j--) {
                    if (j == 0 && ch >= 2) {
                        wait_cnt_warp(cnt_ptr(C_H, ch & ~1), 64);
#pragma unroll 1
                        for (int i = 0; i < ((ch & 1) || ch == 2 ? 1 : 2); i++) {
                            ACQ(16384);
                            bulk_g2s1(sb + st * STG_B, g_carry[i] + (ch * 16 + q) * 1024, 16384, sb + B_BAR + (BB_FULL + st) * 8, POL_LAST);
                            NEXT;
                        }
                    }
                    ACQ(32 * PW * 4);
                    bulk_g2s1(sb + st * STG_B, g_P + (q * 16 + j) * 32 * PW, 32 * PW * 4, sb + B_BAR + (BB_FULL + st) * 8, POL_N);
                    NEXT;
                }
            }
        }
    }
}

__device__ __forceinline__ uint4* qkv_dst(int layer, int ch, int w, int blk);
__device__ __forceinline__ uint4* op_dst(int layer, int ch, int slot, int w, uint32_t rank);
__device__ __forceinline__ uint64_t out_pol(int type, int layer, int ch) { return (type == T_QKV ? (!layer && ch > 1) : (layer && ch < 10)) ? POL_LATE : POL_SOON; }
__device__ __forceinline__ void bulk_relay(const Params& p, uint32_t sb, int cl) {
    for (int ti = 0; ti < MAXT; ti++) {
        const int type = p.task[list_of(cl)][ti] & 7;
        if (type == T_END) break;
        if (type != T_QKV) continue;
        bar_sync(NB_PH, 64);
        const uint32_t ph = lds32(sb + B_ST + 8);
#pragma unroll 1
        for (int h = 2; h < 8; h++) {
            mbar_wait(sb + B_BAR + (BB_FULL + h) * 8, ph);
            if (h == 4 || h == 7) { bar_arrive(NB_REL + (h == 7) * 2, 160); bar_arrive(NB_REL + (h == 7) * 2 + 1, 160); }
        }
    }
}
__device__ __forceinline__ void bulk_release(const Params& p, uint32_t sb, int cl, uint32_t rank, int wg) {
    int nd = 0;
    for (int ti = 0; ti < MAXT; ti++) {
        const Task t = task_of(p.task[list_of(cl)][ti], rank);
        const int type = t.type, layer = t.layer, ch = t.ch;
        if (type == T_END) break;
        if (type == T_FIN || (type == T_OP && (t.c & 32))) continue;
        if (type == T_OP && !layer) {
            mbar_wait(sb + B_BAR + (BB_DONE + wg) * 8, nd & 1);
            nd++;
            const int s0 = __shfl_sync(0xffffffffu, lds32(sb + B_ST + wg * 4), 0) + wg * 2;
            fence_async_smem();
#pragma unroll 1
            for (int w = 0; w < 4; w++)
                asm volatile("{.reg .pred p; elect.sync _|p,0xffffffff; @p cp.async.bulk.global.shared::cta.bulk_group.L2::cache_hint [%0],[%1],8192,%2; cp.async.bulk.commit_group;}"
                             ::"l"(op_dst(0, ch, t.c & 15, wg * 4 + w, rank)), "r"(sb + ((s0 + (w >> 1)) & (NSTG - 1)) * STG_B + (w & 1) * 8192), "l"(POL_SOON) : "memory");
            mbar_arrive1(sb + B_BAR + (BB_SF + wg) * 8);
            asm volatile("{.reg .pred p; elect.sync _|p,0xffffffff;\n"
                         "cp.async.bulk.wait_group 3; @p red.relaxed.gpu.global.add.u32 [%0],1; cp.async.bulk.wait_group 2; @p red.relaxed.gpu.global.add.u32 [%0+64],1;\n"
                         "cp.async.bulk.wait_group 1; @p red.relaxed.gpu.global.add.u32 [%0+128],1; cp.async.bulk.wait_group 0; @p red.relaxed.gpu.global.add.u32 [%0+192],1;}"
                         ::"l"(cnt_ptr(C_OP0 + rank * 2 + wg, ch)) : "memory");
#pragma unroll 1
            for (int i = 0; i < 8; i++) mbar_arrive1_cluster(mapa(sb + B_BAR + (BB_EMPTY + ((s0 + (i >> 2)) & (NSTG - 1))) * 8, i & 1));
            continue;
        }
#pragma unroll 1
        for (int u = 0; u < (type == T_QKV ? t.b : 1); u++) {
            const int blk = qkv_blk(t, u);
            unsigned* cnt = cnt_ptr(type == T_QKV ? C_QKV0 + layer : type == T_OP ? C_OP1 : layer ? C_H : C_CV, ch + (type == T_QKV && blk < 64 ? 16 : 0));
            const uint4* dst = type == T_QKV ? qkv_dst(layer, ch, wg * 4, blk) : op_dst(1, ch, t.c & 15, wg * 4, (t.blk >> 2) & 1) + 256;
            mbar_wait(sb + B_BAR + (BB_DONE + wg) * 8, nd & 1);
            nd++;
            if (type != T_CV) {
                fence_async_smem();
#pragma unroll
                for (int w = 0; w < 4; w++)
                    asm volatile("{.reg .pred p; elect.sync _|p,0xffffffff; @p cp.async.bulk.global.shared::cta.bulk_group.L2::cache_hint [%0],[%1],4096,%2;}"
                                 ::"l"(dst + (type == T_QKV ? (w >> 1) * 49152 + (w & 1) * 256 : w * 1024)), "r"(sb + B_OUT + (wg * 4 + w) * 4096), "l"(out_pol(type, layer, ch)) : "memory");
                asm volatile("cp.async.bulk.commit_group; cp.async.bulk.wait_group 0;" ::: "memory");
            }
            if (type != T_QKV) fence_async();
            if (!t.dry) asm volatile("{.reg .pred p; elect.sync _|p,0xffffffff; @p red.relaxed.gpu.global.add.u32 [%0],%1;}" ::"l"(cnt), "r"(type == T_QKV ? 2 : type == T_OP ? t.b : 1) : "memory");
            PROF(wg && (threadIdx.x & 31) == 0 && (type == T_CV || u + 2 == t.b), 3900 + ti);
            if (type == T_CV && !layer && !t.dry) {
                asm volatile("{.reg .pred p; elect.sync _|p,0xffffffff; @p cp.async.bulk.global.shared::cta.bulk_group [%0],[%1],4096;\n"
                             "cp.async.bulk.commit_group; cp.async.bulk.wait_group 0; @p red.relaxed.gpu.global.add.u32 [%2],1;}"
                             ::"l"(g_u + ((t.a + rank) * 16 + ch) * 512 + wg * 256), "r"(sb + B_UT + (ch & 1) * 8192 + wg * 4096), "l"(cnt_ptr(C_U, ch)) : "memory");
            }
            mbar_arrive1(sb + B_BAR + (BB_SF + wg) * 8);
        }
        PROF(wg && (threadIdx.x & 31) == 0, 3600 + ti * 4 + 3);
    }
}

__device__ __forceinline__ void stage_release(uint32_t sb, int w, int st) {
    if (!(w & 2)) mbar_arrive1_cluster(mapa(sb + B_BAR + (BB_EMPTY + st) * 8, w & 1));
}
template <bool ACC>
__device__ __forceinline__ void gemm_run(float* acc, uint32_t sb, int w, int h0, int h1, uint32_t& r0, uint32_t& r1, int& st, uint32_t& ph) {
    const uint64_t da0 = mkdesc(sb + (w >> 2) * 4096, 16, 512, 2), db0 = mkdesc(sb + 8192, 4096, 1024, 1);
    const uint32_t rel0 = mapa(sb + B_BAR + BB_EMPTY * 8, w & 1);
#pragma unroll 1
    for (int h = h0; h < h1; h++) {
        const uint64_t da = da0 + st * (STG_B >> 4), db = db0 + st * (STG_B >> 4);
        mbar_wait(sb + B_BAR + (BB_FULL + st) * 8, ph);
        if (ACC) wg_wait<1>();
        wg_fence();
        wgmma256<ACC>(acc, da, db);
        wgmma256<true>(acc, da + 2, db + 128);
        wg_commit();
        if (ACC) mbar_arrive1_cluster((w == 2 && h == LAGH - 1) ? sb + B_BAR + BB_GO * 8 : r0);
        r0 = r1;
        if (!(w & 2)) r1 = rel0 + st * 8;
        if (++st == NSTG) { st = 0; ph ^= 1; }
    }
}

__device__ __forceinline__ uint4* qkv_dst(int layer, int ch, int w, int blk) {
    return g_qkv[layer] + (size_t)((ch * 4 + (w >> 1)) * 32 + ((blk & 63) >> 1)) * 1536 + (blk >> 6) * 512 + (w & 1) * 256;
}
__device__ __forceinline__ uint4* op_dst(int layer, int ch, int slot, int w, uint32_t rank) {
    return g_pp[layer] + (size_t)(ch * MAXSPLIT + slot) * 8192 + (w * 32 + rank * 16) * 32;
}
__device__ __forceinline__ uint32_t ln2(uint32_t x, uint32_t m, uint32_t rh, uint32_t rl) {
    uint32_t d; asm volatile("{.reg .b32 t,u; sub.rn.bf16x2 t,%1,%2; mul.rn.bf16x2 u,t,%4; fma.rn.bf16x2 %0,t,%3,u;}" : "=r"(d) : "r"(x), "r"(m), "r"(rh), "r"(rl)); return d;
}
__device__ __forceinline__ void ldcg128p(uint4& v, const uint4* p, uint32_t on) {
    asm volatile("{.reg .pred p; setp.ne.u32 p,%5,0; @p ld.global.cg.v4.u32 {%0,%1,%2,%3},[%4];}" : "+r"(v.x), "+r"(v.y), "+r"(v.z), "+r"(v.w) : "l"(p), "r"(on) : "memory");
}
__device__ __forceinline__ void qkv_task(uint32_t sb, int w, int layer, int ch, int nu, int& ng, int& nd, uint32_t& ph, int ti, uint32_t zero,
                                         uint4* A, uint32_t& pre, const uint4* xn, const unsigned* dn, unsigned need) {
    constexpr int type = T_QKV;
    static_assert(NSTG == 8, "ring");
    const int lane = threadIdx.x & 31;
    const uint64_t db0 = mkdesc(sb, 4096, 1024, 1);
    const uint32_t rel = (w & 2) ? sb + B_BAR + BB_IDLE * 8 : mapa(sb + B_BAR + BB_EMPTY * 8, w & 1), full = sb + B_BAR + BB_FULL * 8;
    const uint32_t lo = sb + B_OUT + w * 4096 + (lane ^ (lane >> 3)) * 16;
    const uint4* xa = g_xA[layer] + (ch * 8 + w) * 1024 + lane;
    uint32_t m0, m1, h0, h1, l0, l1;
    {
        mbar_wait(full, ph);
        mbar_wait(full + 8, ph);
        CPROF(1);
        const uint32_t sa = sb + (lane >> 4) * STG_B + 16384 + (w * 16 + (lane & 15)) * 8;
        uint2 v[8];
#pragma unroll
        for (int i = 0; i < 8; i++) v[i] = lds64(sa + i * 1024 * layer);
#pragma unroll
        for (int i = 0; i < 4 * QB1; i++) ldcg128p(A[i], xa + i * 32, !pre);
        bar_sync(NB_WG + (w >> 2), 128);
        float sm = 0, M2 = 0, D = 0;
#pragma unroll
        for (int i = 0; i < 8; i++) { sm += __uint_as_float(v[i].x); M2 += __uint_as_float(v[i].y); }
        if (!layer) { sm = __uint_as_float(v[0].x); M2 = __uint_as_float(v[0].y); }
        sm += __shfl_xor_sync(0xffffffffu, sm, 16);
#pragma unroll
        for (int i = 0; i < 8; i++) { const float d = __uint_as_float(v[i].x) * (1.f / 32.f) - sm * (1.f / 512.f); D += 32.f * d * d; }
        M2 += layer ? D : sm * sm * (-1.f / 1024.f);
        M2 = fmaxf(M2 + __shfl_xor_sync(0xffffffffu, M2, 16), 0.f);
        const float2 o = ln_finish(sm * (1.f / 512.f), M2 * (1.f / 512.f));
        const float r = rcp(o.y), rh = rbf(r);
        const uint32_t mm = pack2(o.x, o.x), hl = pack2(r - rh, rh);
        m0 = __shfl_sync(0xffffffffu, mm, lane >> 2); m1 = __shfl_sync(0xffffffffu, mm, (lane >> 2) + 8);
        l0 = __shfl_sync(0xffffffffu, hl, lane >> 2); l1 = __shfl_sync(0xffffffffu, hl, (lane >> 2) + 8);
        h0 = __byte_perm(l0, 0, 0x3232); h1 = __byte_perm(l1, 0, 0x3232); l0 = __byte_perm(l0, 0, 0x1010); l1 = __byte_perm(l1, 0, 0x1010);
    }
    float acc[64];
#define QNRM(i) A[i] = make_uint4(ln2(A[i].x, m0, h0, l0), ln2(A[i].y, m1, h1, l1), ln2(A[i].z, m0, h0, l0), ln2(A[i].w, m1, h1, l1))
#pragma unroll
    for (int h = 0; h < 8; h++) {
        const uint64_t db = db0 + h * (STG_B >> 4);
        const int b0 = h == 0 ? QB1 : h == QB1 ? QB2 : h == QB2 ? QB3 : 8, b1 = h == 0 ? QB2 : h == QB1 ? QB3 : 8;
        if (b0 < b1) {
            const uint4* xb = xa + (A[4 * b0 - 1].x & zero);
#pragma unroll
            for (int i = 4 * b0; i < 4 * b1; i++) { if (b0 < QB3) ldcg128p(A[i], xb + i * 32, !pre); else A[i] = ldcg128(xb + i * 32); }
            bar_sync(NB_WG + (w >> 2), 128);
        }
        QNRM(4 * h); QNRM(4 * h + 1); QNRM(4 * h + 2); QNRM(4 * h + 3);
        if (h == 2 || h == 5) bar_sync(NB_REL + (h == 5) * 2 + (w >> 2), 160);
        if (h) wg_wait<1>();
        wg_fence();
        if (h) wgmma128r<true>(acc, A[4 * h], db); else wgmma128r<false>(acc, A[0], db);
        wgmma128r<true>(acc, A[4 * h + 1], db + 128);
        wgmma128r<true>(acc, A[4 * h + 2], db + 512);
        wgmma128r<true>(acc, A[4 * h + 3], db + 640);
        wg_commit();
        if (h >= 2) mbar_arrive1_cluster(rel + (h - 2) * 8);
    }
    ph ^= 1;
    pre = 0;
#pragma unroll 1
    for (int u = 1;; u++) {
        mbar_wait(sb + B_BAR + (BB_SF + (w >> 2)) * 8, (nd & 1) ^ 1);
        if (u < nu) mbar_wait(full, ph);
        wg_wait<1>();
        mbar_arrive1_cluster(rel + 48);
        wg_wait<0>();
        mbar_arrive1_cluster(rel + 56);
        uint4 o[8];
#pragma unroll
        for (int n = 0; n < 8; n++) {
            const float* a = acc + (n >> 1) * 16 + (n & 1) * 2;
            o[n] = make_uint4(pack2(a[0], a[1]), pack2(a[4], a[5]), pack2(a[8], a[9]), pack2(a[12], a[13]));
            sts128(lo + n * 512, o[n].x, o[n].y, o[n].z, o[n].w);
        }
        __syncwarp();
        mbar_arrive1(sb + B_BAR + (BB_DONE + (w >> 2)) * 8);
        nd++;
        CPROF(min(2 + u, 7));
        if (u == nu) break;
        if (LAGQ) { if (w >> 2) mbar_wait(sb + B_BAR + BB_GO * 8, ng & 1); ng++; }
        unsigned v;
        asm volatile("ld.relaxed.gpu.global.u32 %0,[%1];" : "=r"(v) : "l"(dn) : "memory");
        const uint64_t db1 = mkdesc(sb + (u >> 10), 4096, 1024, 1);
#pragma unroll
        for (int h = 0; h < 8; h++) {
            const uint64_t db = db1 + h * (STG_B >> 4);
            if (h) { mbar_wait(full + h * 8, ph); wg_wait<1>(); }
            if (QPOS == 0) {
            if (h == 2) pre = u + 1 == nu && v >= need;
            if (h >= 2 && h - 2 < QB3) {
#pragma unroll
                for (int i = 4 * (h - 2); i < 4 * (h - 1); i++) ldcg128p(A[i], xn + i * 32, pre);
            }
            }
            wg_fence();
            if (h) wgmma128r<true>(acc, A[4 * h], db); else wgmma128r<false>(acc, A[0], db);
            wgmma128r<true>(acc, A[4 * h + 1], db + 128);
            wgmma128r<true>(acc, A[4 * h + 2], db + 512);
            wgmma128r<true>(acc, A[4 * h + 3], db + 640);
            wg_commit();
            if (h >= 2) mbar_arrive1_cluster(rel + (h - 2) * 8);
            if (h == LAGQ - 1 && w == 2) mbar_arrive1(sb + B_BAR + BB_GO * 8);
            if (QPOS == 1) {
            if (h == 2) pre = u + 1 == nu && v >= need;
            if (h >= 2 && h - 2 < QB3) {
#pragma unroll
                for (int i = 4 * (h - 2); i < 4 * (h - 1); i++) ldcg128p(A[i], xn + i * 32, pre);
            }
            }
        }
        ph ^= 1;
    }
}

template <int NB>
__device__ __forceinline__ void load_resid(uint32_t* r, int layer, int ch, int w, int cb) {
#pragma unroll
    for (int i = 0; i < NB; i++) {
        const uint4 v = ldcg128(g_xA[layer] + ((ch * 8 + w) * 32 + cb + i) * 32 + (threadIdx.x & 31));
        r[4 * i] = v.x; r[4 * i + 1] = v.y; r[4 * i + 2] = v.z; r[4 * i + 3] = v.w;
    }
}
template <int NS>
__device__ __forceinline__ void part_load(uint4* v, int layer, int ch, int w, int cb, int ns) {
    const uint4* src = g_pp[layer] + (size_t)ch * MAXSPLIT * 8192 + (w * 32 + cb) * 32 + (threadIdx.x & 31);
#pragma unroll
    for (int i = 0; i < 2 * NS; i++) {
        asm volatile("{.reg .pred p; .reg .b128 t; setp.gt.s32 p,%6,0; mov.b128 t,{0,0,0,0}; @p ld.relaxed.gpu.global.L2::cache_hint.b128 t,[%4],%5; mov.b128 {%0,%1,%2,%3},t;}"
                     : "=r"(v[i].x), "=r"(v[i].y), "=r"(v[i].z), "=r"(v[i].w) : "l"(src + (i / NS) * 32 + (i % NS) * 8192), "l"(POL_LAST), "r"(ns - i % NS) : "memory");
    }
}
template <int NS>
__device__ __forceinline__ void part_sum(float* x, const uint4* v, const uint32_t* r) {
    const int dg = ((threadIdx.x & 31) >> 2) - 2 * (threadIdx.x & 3);
    const uint32_t idm = dg == 0 ? 0x00003f80u : dg == 1 ? 0x3f800000u : 0u;
#pragma unroll
    for (int b = 0; b < 2; b++) {
        float* y = x + b * 8;
#pragma unroll
        for (int i = 0; i < 8; i++) y[i] = 0;
#pragma unroll
        for (int s = 0; s < NS; s++) { mma8(y, v[b * NS + s].x, v[b * NS + s].y, idm); mma8(y + 4, v[b * NS + s].z, v[b * NS + s].w, idm); }
#pragma unroll
        for (int i = 0; i < 4; i++) { y[2 * i] = rbf(rbf(y[2 * i]) + blo(r[b * 4 + i])); y[2 * i + 1] = rbf(rbf(y[2 * i + 1]) + bhi(r[b * 4 + i])); }
    }
}

__device__ __forceinline__ float4 row_stats32(const float* x) {
    float a = (x[0] + x[1]) + (x[4] + x[5]) + (x[8] + x[9]) + (x[12] + x[13]);
    float b = (x[2] + x[3]) + (x[6] + x[7]) + (x[10] + x[11]) + (x[14] + x[15]);
    a += __shfl_xor_sync(0xffffffffu, a, 1); b += __shfl_xor_sync(0xffffffffu, b, 1);
    a += __shfl_xor_sync(0xffffffffu, a, 2); b += __shfl_xor_sync(0xffffffffu, b, 2);
    const float ma = a * (1.f / 32.f), mb = b * (1.f / 32.f);
    float qa = 0, qb = 0;
#pragma unroll
    for (int i = 0; i < 4; i++) {
        float d0 = x[4 * i] - ma, d1 = x[4 * i + 1] - ma, d2 = x[4 * i + 2] - mb, d3 = x[4 * i + 3] - mb;
        qa += d0 * d0 + d1 * d1; qb += d2 * d2 + d3 * d3;
    }
    qa += __shfl_xor_sync(0xffffffffu, qa, 1); qb += __shfl_xor_sync(0xffffffffu, qb, 1);
    qa += __shfl_xor_sync(0xffffffffu, qa, 2); qb += __shfl_xor_sync(0xffffffffu, qb, 2);
    return make_float4(a, qa, b, qb);
}

__device__ __forceinline__ void conv_stage(float* Y, uint32_t pbase, uint32_t ubase) {
    const int lane = threadIdx.x & 31, w = threadIdx.x >> 5, g = lane >> 2, c = lane & 3;
#pragma unroll
    for (int cp = 0; cp < 2; cp++) {
        const int chl = w * 4 + cp * 2 + (lane >> 4);
        const uint4 b = ldsm4(ubase + chl * 256 + ((lane >> 3) & 1) * 128 + (((lane & 7) ^ (chl & 7)) << 4));
#pragma unroll
        for (int h = 0; h < 2; h++) {
            const uint32_t pa = pbase + ((w * 4 + cp * 2 + h) * PW + 16 + g - 2 * c) * 4;
            uint32_t lo = lds32(pa - 32);
#pragma unroll
            for (int d = 0; d < 8; d++) {
                const uint32_t a0 = lds32(pa + d * 64), a1 = lds32(pa + d * 64 + 32);
                mma16(Y + ((cp * 2 + h) * 8 + d) * 4, a0, a1, lo, a0, h ? b.z : b.x, h ? b.w : b.y);
                lo = a1;
            }
        }
    }
}

__device__ __forceinline__ void conv_combine(const float* y8, float* cur, float* nxt) {
    const int lane = threadIdx.x & 31, c = lane & 3;
    cur[0] = y8[0]; cur[1] = y8[1] + y8[4]; cur[2] = y8[2]; cur[3] = y8[3] + y8[6];
    nxt[0] = y8[29]; nxt[1] = 0.f; nxt[2] = y8[31]; nxt[3] = 0.f;
#pragma unroll
    for (int e = 1; e < 4; e++) {
        const int src = (lane & ~3) | ((c - e) & 3);
        const float v0 = __shfl_sync(0xffffffffu, y8[8 * e] + y8[8 * e - 3], src), v1 = __shfl_sync(0xffffffffu, y8[8 * e + 1] + y8[8 * e + 4], src);
        const float v2 = __shfl_sync(0xffffffffu, y8[8 * e + 2] + y8[8 * e - 1], src), v3 = __shfl_sync(0xffffffffu, y8[8 * e + 3] + y8[8 * e + 6], src);
        if (c >= e) { cur[0] += v0; cur[1] += v1; cur[2] += v2; cur[3] += v3; }
        else { nxt[0] += v0; nxt[1] += v1; nxt[2] += v2; nxt[3] += v3; }
    }
}

__device__ __forceinline__ void hist_task(float* Y, uint32_t sb, int w, int ch, int q, int& st, uint32_t& ph, int nd) {
    const int lane = threadIdx.x & 31, chl = w * 2 + (lane >> 4);
    const uint32_t ua = sb + 12288 + chl * 256 + ((lane >> 3) & 1) * 128 + (((lane & 7) ^ (chl & 7)) << 4);
    const uint32_t pa = sb + (w * 2 * PW + 16 + (lane >> 2) - 2 * (lane & 3)) * 4;
#pragma unroll
    for (int i = 0; i < 128; i++) Y[i] = 0;
    uint4 b1 = make_uint4(0, 0, 0, 0);
#pragma unroll 1
    for (int j = ch + 1; j >= 2; j--) {
        const uint4 b0 = b1;
        mbar_wait(sb + B_BAR + (BB_FULL + st) * 8, ph);
        b1 = ldsm4(ua + st * STG_B);
        if (j == 2) b1 = make_uint4(0, 0, 0, 0);
#pragma unroll
        for (int h = 0; h < 2; h++) {
            const uint32_t o = pa + st * STG_B + h * PW * 4;
            uint32_t lo = lds32(o - 32);
#pragma unroll
            for (int d = 0; d < 8; d++) {
                const uint32_t a0 = lds32(o + d * 64), a1 = lds32(o + d * 64 + 32);
                mma16(Y + (h * 16 + d) * 4, a0, a1, lo, a0, h ? b0.z : b0.x, h ? b0.w : b0.y);
                mma16(Y + (h * 16 + 8 + d) * 4, a0, a1, lo, a0, h ? b1.z : b1.x, h ? b1.w : b1.y);
                lo = a1;
            }
        }
        bar_sync(NB_WG + (w >> 2), 128);
        stage_release(sb, w, st);
        if (++st == NSTG) { st = 0; ph ^= 1; }
    }
    mbar_wait(sb + B_BAR + (BB_SF + (w >> 2)) * 8, (nd & 1) ^ 1);
#pragma unroll
    for (int h = 0; h < 2; h++) {
        const int o = ((ch * 16 + (q >> 1)) * 4 + (w & 1) * 2 + h) * 256 + ((q & 1) * 4 + (w >> 1)) * 32 + lane;
        float c0[4], n0[4], c1[4], n1[4];
        conv_combine(Y + h * 64, c0, n0); conv_combine(Y + h * 64 + 32, c1, n1);
        g_carry[0][o] = make_float4(c0[0], c0[1], c0[2], c0[3]);
        g_carry[0][o + 16384] = make_float4(c1[0] + n0[0], c1[1] + n0[1], c1[2] + n0[2], c1[3] + n0[3]);
        g_carry[1][o + 32768] = make_float4(n1[0], n1[1], n1[2], n1[3]);
    }
}

__device__ __forceinline__ void conv_task(const Params& p, float* Y, uint32_t sb, int w, int ch, int q, int ns, bool dry, int& st, uint32_t& ph, int nd) {
    const int tid = threadIdx.x, lane = tid & 31, g = lane >> 2, c = lane & 3;
    uint32_t dk[4];
    const uint32_t sg = (~ch & 2) << 30;
    int sr = st;
    float x[16];
    PROF(tid == 128, 2048 + ch * 8);
#pragma unroll
    for (int i = 0; i < 128; i++) Y[i] = 0;
#pragma unroll 1
    for (int j = min(ch, 1 + (ch & 1)); j >= 1; j--) {
        mbar_wait(sb + B_BAR + (BB_FULL + st) * 8, ph);
        conv_stage(Y, sb + st * STG_B, sb + B_UT + ((ch - j) & 1) * 8192);
        if (++st == NSTG) { st = 0; ph ^= 1; }
    }
#define CONV_CARRY _Pragma("unroll 1") \
    for (int i = 0; i < min(ch, (ch & 1) ? 2 : 3); i++) { \
        if (i) mbar_wait(sb + B_BAR + (BB_FULL + st) * 8, ph); \
        const uint32_t ca = sb + (i ? st * STG_B : B_SP) + tid * 16; \
_Pragma("unroll") \
        for (int k = 0; k < 4; k++) { \
            const uint4 cr = lds128(ca + k * 4096); \
            Y[k * 32] += __uint_as_float(cr.x); Y[k * 32 + 1] += __uint_as_float(cr.y); Y[k * 32 + 2] += __uint_as_float(cr.z); Y[k * 32 + 3] += __uint_as_float(cr.w); \
        } \
        if (i && ++st == NSTG) { st = 0; ph ^= 1; } \
    } \
    bar_sync(NB_C, 256); \
_Pragma("unroll 1") \
    for (; sr != st; sr = (sr + 1) & (NSTG - 1)) stage_release(sb, w, sr); \
    mbar_wait(sb + B_BAR + (BB_SF + (w >> 2)) * 8, (nd & 1) ^ 1); \
    mbar_wait(sb + B_BAR + (BB_SF + 1 - (w >> 2)) * 8, (nd & 1) ^ 1);
    const uint32_t ut = sb + B_UT + (ch & 1) * 8192;
    if (CPOS == 0) { CONV_CARRY }
    PROF(tid == 128, 2048 + ch * 8 + 7);
    {
        uint4 v[2 * OPS1];
        wait_cnt_warp(cnt_ptr(C_OP0 + (q >> 3) * 2 + (w >> 2), ch + (w & 3) * 16), ns);
        part_load<OPS1>(v, 0, ch, w, 2 * q, ns);
        uint32_t rs[8];
        load_resid<2>(rs, 0, ch, w, 2 * q);
        if (CPOS == 1) { CONV_CARRY }
        part_sum<OPS1>(x, v, rs);
        const float4 s = row_stats32(x);
        float2* dst = g_st2 + ((ch & 1) * 16 + q) * 128 + w * 16 + g + c * 8;
        asm volatile("{.reg .pred p; setp.ne.u32 p,%2,0; @p st.relaxed.gpu.global.b64 [%0],%1;}" ::"l"(dst),
                     "l"(((uint64_t)((__float_as_uint(c ? s.w : s.y) & 0x7fffffffu) | sg) << 32) | __float_as_uint(c ? s.z : s.x)), "r"((uint32_t)(c < 2 && !dry)) : "memory");
        PROF(tid == 128, 2048 + ch * 8 + 1);
    }
#pragma unroll
    for (int i = 0; i < 4; i++) asm volatile("ld.global.nc.u32 %0,[%1];" : "=r"(dk[i]) : "l"(p.Dskip + q * 32 + i * 8 + 2 * c));
    if (CPOS == 2) { CONV_CARRY }
    float2 ln0, ln1;
    {
        const float2* src = g_st2 + ((ch & 1) * 16 + (lane >> 4) * 8) * 128 + w * 16 + (lane & 15);
        uint64_t v[8];
        int n = 0;
#pragma unroll
        for (int i = 0; i < 8; i++) v[i] = (uint64_t)~sg << 32;
        while (true) {
            bool bad = false;
#pragma unroll
            for (int i = 0; i < 8; i++) asm volatile("{.reg .pred p; setp.lt.s32 p,%2,0; @p ld.relaxed.gpu.global.b64 %0,[%1];}" : "+l"(v[i]) : "l"(src + i * 128), "r"((uint32_t)(v[i] >> 32) ^ sg) : "memory");
#pragma unroll
            for (int i = 0; i < 8; i++) bad = bad || (int)((uint32_t)(v[i] >> 32) ^ sg) < 0;
            if (!__any_sync(0xffffffffu, bad && !dry)) break;
            if (++n > 2000000) __trap();
        }
        float sm = 0;
#pragma unroll
        for (int i = 0; i < 8; i++) sm += __uint_as_float((uint32_t)v[i]);
        sm += __shfl_xor_sync(0xffffffffu, sm, 16);
        const float mean = sm * (1.f / 512.f);
        float M2 = 0;
#pragma unroll
        for (int i = 0; i < 8; i++) { const float d = __uint_as_float((uint32_t)v[i]) * (1.f / 32.f) - mean; M2 += fabsf(__uint_as_float((uint32_t)(v[i] >> 32))) + 32.f * d * d; }
        M2 += __shfl_xor_sync(0xffffffffu, M2, 16);
        const float2 o = ln_finish(mean, M2 * (1.f / 512.f));
        ln0.x = __shfl_sync(0xffffffffu, o.x, g); ln0.y = __shfl_sync(0xffffffffu, o.y, g);
        ln1.x = __shfl_sync(0xffffffffu, o.x, g + 8); ln1.y = __shfl_sync(0xffffffffu, o.y, g + 8);
    }
    PROF(tid == 128, 2048 + ch * 8 + 2);
    uint32_t u[8];
#pragma unroll
    for (int i = 0; i < 8; i++) {
        const float2 l = (i & 1) ? ln1 : ln0;
        u[i] = pack2(__fdividef(rbf(x[2 * i] - l.x), l.y), __fdividef(rbf(x[2 * i + 1] - l.x), l.y));
        const int chl = (i >> 1) * 8 + g;
        sts32(ut + chl * 256 + (i & 1) * 128 + ((w ^ g) << 4) + c * 4, movm(u[i]));
    }
    bar_sync(NB_C, 256);
    mbar_wait(sb + B_BAR + (BB_FULL + st) * 8, ph);
    PROF(tid == 128, 2048 + ch * 8 + 3);
    conv_stage(Y, sb + st * STG_B, ut);
    uint32_t yp[4][2];
    float nxt[4][4];
    {
        float y[4][4];
#pragma unroll
        for (int k = 0; k < 4; k++) conv_combine(Y + k * 32, y[k], nxt[k]);
#pragma unroll
        for (int i = 0; i < 4; i++) { yp[i][0] = pack2(y[0][i], y[1][i]); yp[i][1] = pack2(y[2][i], y[3][i]); }
    }
#pragma unroll
    for (int i = 0; i < 4; i++) sts64(sb + B_YT + (16 * (2 * c + (i & 1)) + g + (i >> 1) * 8) * 80 + w * 8, yp[i][0], yp[i][1]);
    bar_sync(NB_C, 256);
    stage_release(sb, w, st);
    if (++st == NSTG) { st = 0; ph ^= 1; }
    PROF(tid == 128, 2048 + ch * 8 + 4);
    uint32_t xo[8];
    uint4* dA = g_xA[1] + ((ch * 8 + w) * 32 + 2 * q) * 32 + lane;
#pragma unroll
    for (int i = 0; i < 8; i++) {
        const int col = (i >> 1) * 8 + 2 * c;
        const uint32_t yv = lds32(sb + B_YT + (w * 16 + g + (i & 1) * 8) * 80 + col * 2);
        const uint32_t dv = dk[i >> 1];
        x[2 * i] = rbf(x[2 * i] + rbf(blo(yv) + rbf(blo(u[i]) * blo(dv))));
        x[2 * i + 1] = rbf(x[2 * i + 1] + rbf(bhi(yv) + rbf(bhi(u[i]) * bhi(dv))));
        xo[i] = pack2(x[2 * i], x[2 * i + 1]);
        if ((i & 3) == 3) dA[(i >> 2) * 32] = make_uint4(xo[i - 3], xo[i - 2], xo[i - 1], xo[i]);
    }
    {
        const float4 s = row_stats32(x);
        float2* dst = g_st[1] + (ch * 16 + q) * 128 + w * 16 + g;
        if (c == 0) dst[0] = make_float2(s.x, s.y);
        if (c == 1) dst[8] = make_float2(s.z, s.w);
        __syncwarp();
    }
    PROF(tid == 128, 2048 + ch * 8 + 5);
    mbar_arrive1(sb + B_BAR + (BB_DONE + (w >> 2)) * 8);
    bar_sync(NB_C, 256);
#pragma unroll
    for (int k = 0; k < 4; k++) sts128(sb + B_SP + k * 4096 + tid * 16, __float_as_uint(nxt[k][0]), __float_as_uint(nxt[k][1]), __float_as_uint(nxt[k][2]), __float_as_uint(nxt[k][3]));
    PROF(tid == 128, 2048 + ch * 8 + 6);
}

__device__ __forceinline__ void out_store(const Params& p, const float* x, int ch, int cb, bool on) {
    const int lane = threadIdx.x & 31, w = threadIdx.x >> 5, g = lane >> 2, c = lane & 3;
#pragma unroll
    for (int h = 0; h < 2; h++) {
        const float* y = x + h * 2;
        uint32_t v0 = pack2(y[0], y[1]), v1 = pack2(y[4], y[5]), v2 = pack2(y[8], y[9]), v3 = pack2(y[12], y[13]);
        uint32_t t0 = (c & 1) ? v0 : v1, t1 = (c & 1) ? v2 : v3;
        t0 = __shfl_xor_sync(0xffffffffu, t0, 1); t1 = __shfl_xor_sync(0xffffffffu, t1, 1);
        if (c & 1) { v0 = t0; v2 = t1; } else { v1 = t0; v3 = t1; }
        t0 = (c & 2) ? v0 : v2; t1 = (c & 2) ? v1 : v3;
        t0 = __shfl_xor_sync(0xffffffffu, t0, 2); t1 = __shfl_xor_sync(0xffffffffu, t1, 2);
        if (c & 2) { v0 = t0; v1 = t1; } else { v2 = t0; v3 = t1; }
        asm volatile("{.reg .pred p; setp.ne.u32 p,%6,0; @p st.global.L2::cache_hint.v4.u32 [%0],{%1,%2,%3,%4},%5;}"
                     ::"l"(p.out + (size_t)(ch * 128 + w * 16 + g + h * 8) * 512 + cb * 16 + c * 8), "r"(v0), "r"(v1), "r"(v2), "r"(v3), "l"(POL_LATE), "r"((uint32_t)on));
    }
}
__device__ __forceinline__ void fin_task(const Params& p, int ch, int cb0, int ncb, int ns, bool dry) {
    const int w = threadIdx.x >> 5;
    uint32_t rs[8];
    wait_cnt_warp(cnt_ptr(C_CV, ch), 32);
    load_resid<2>(rs, 1, ch, w, cb0);
    wait_cnt_warp(cnt_ptr(C_OP1, ch), dry ? 0 : 256);
    for (int cb = cb0; cb < cb0 + ncb; cb += 2) {
        float x[16];
        if (cb != cb0) load_resid<2>(rs, 1, ch, w, cb);
        uint4 v[32];
        part_load<16>(v, 1, ch, w, cb, ns);
        part_sum<16>(x, v, rs);
        out_store(p, x, ch, cb, !dry);
    }
}

__device__ __forceinline__ void bulk_consumer(const Params& p, uint32_t sb, int cl, uint32_t rank, int w) {
    int st = 0; uint32_t ph = 0; int nd = 0, ng = 0;
    for (int ti = 0; ti < MAXT; ti++) {
        const Task t = task_of(p.task[list_of(cl)][ti], rank);
        const int type = t.type, layer = t.layer, ch = t.ch;
        if (type == T_END) break;
        bool staged = type != T_FIN;
        PROF(threadIdx.x == 0, 3600 + ti * 4);
        CPROF(0);
        if (type == T_QKV) {
            staged = false;
            #pragma unroll 1
            while (st) {
                if (!(w & 3)) { mbar_wait(sb + B_BAR + (BB_FULL + st) * 8, ph); stage_release(sb, 0, st); stage_release(sb, 1, st); }
                if (++st == NSTG) { st = 0; ph ^= 1; }
            }
            uint4 A[32];
#pragma unroll
            for (int i = 0; i < 32; i++) A[i] = make_uint4(0, 0, 0, 0);
            uint32_t pre = 0;
            Task c = t;
#pragma unroll 1
            while (true) {
                const Task n = task_of(p.task[list_of(cl)][ti + 1], rank);
                if (w == 3) { sts32(sb + B_ST + 8, ph); bar_arrive(NB_PH, 64); }
                qkv_task(sb, w, c.layer, c.ch, c.b, ng, nd, ph, ti, p.zero, A, pre, g_xA[n.layer] + (n.ch * 8 + w) * 1024 + (threadIdx.x & 31),
                         cnt_ptr(C_CV, n.ch), n.type != T_QKV || !QPRE ? ~0u : n.layer ? 32 : 0);
                PROF(threadIdx.x == 128, 3600 + ti * 4 + 1);
                if (n.type != T_QKV) break;
                PROF(threadIdx.x == 128, 3600 + ti * 4 + 2);
                c = n; ti++;
                PROF(threadIdx.x == 0, 3600 + ti * 4);
                { const int layer = c.layer; CPROF(0); }
            }
        } else if (type == T_OP) {
            const int lane = threadIdx.x & 31;
            float acc[128];
            uint32_t r0 = sb + B_BAR + BB_IDLE * 8, r1 = r0;
            if (w >> 2) { mbar_wait(sb + B_BAR + BB_GO * 8, ng & 1); if ((t.c & 80) == 16) mbar_wait(sb + B_BAR + BB_LOW * 8, 0); }
            ng++;
            gemm_run<false>(acc, sb, w, 0, 1, r0, r1, st, ph);
            gemm_run<true>(acc, sb, w, 1, 2 * t.b, r0, r1, st, ph);
            mbar_wait(sb + B_BAR + (BB_SF + (w >> 2)) * 8, (nd & 1) ^ 1);
            wg_wait<1>();
            mbar_arrive1_cluster(r0);
            wg_wait<0>();
            mbar_arrive1_cluster(r1);
            PROF(threadIdx.x == 128, 3600 + ti * 4 + 1);
            if (t.c & 32) {
                staged = false;
                const int dg = (lane >> 2) - 2 * (lane & 3);
                const uint32_t idm = dg == 0 ? 0x00003f80u : dg == 1 ? 0x3f800000u : 0u;
                wait_cnt_warp(cnt_ptr(C_OP1, ch), 256 - 4 * t.b);
#pragma unroll 1
                for (int i = 0; i < (t.c & 15); i++) {
                    const uint4* src = op_dst(1, ch, i, w, (t.blk >> 2) & 1) + lane;
                    uint4 v[16];
#pragma unroll
                    for (int j = 0; j < 16; j++) v[j] = ldcg128_last(src + j * 32);
#pragma unroll
                    for (int j = 0; j < 16; j++) { mma8(acc + j * 8, v[j].x, v[j].y, idm); mma8(acc + j * 8 + 4, v[j].z, v[j].w, idm); }
                }
#pragma unroll
                for (int j = 0; j < 16; j += 4) {
                    uint32_t rs[16];
                    load_resid<4>(rs, 1, ch, w, (t.blk & 4) * 4 + j);
#pragma unroll
                    for (int i = 0; i < 16; i++) { float* y = acc + j * 8 + 2 * i; y[0] = rbf(y[0]) + blo(rs[i]); y[1] = rbf(y[1]) + bhi(rs[i]); }
                    out_store(p, acc + j * 8, ch, (t.blk & 4) * 4 + j, true); out_store(p, acc + j * 8 + 16, ch, (t.blk & 4) * 4 + j + 2, true);
                }
            } else if (!layer) {
                const int s2 = st + (w >> 1);
                const uint32_t o = sb + (s2 & (NSTG - 1)) * STG_B + (w & 1) * 8192 + lane * 16;
                mbar_wait(sb + B_BAR + (BB_FULL + (s2 & (NSTG - 1))) * 8, ph ^ (s2 >= NSTG));
#pragma unroll
                for (int j = 0; j < 16; j++)
                    sts128(o + j * 512, pack2(acc[j * 8], acc[j * 8 + 1]), pack2(acc[j * 8 + 2], acc[j * 8 + 3]), pack2(acc[j * 8 + 4], acc[j * 8 + 5]), pack2(acc[j * 8 + 6], acc[j * 8 + 7]));
                sts32(sb + B_ST + (w >> 2) * 4, st);
                st += 4;
                if (st >= NSTG) { st -= NSTG; ph ^= 1; }
            } else {
                uint4* dst = op_dst(layer, ch, t.c & 15, w, (t.blk >> 2) & 1) + lane;
#pragma unroll
                for (int n = 0; n < 16; n++) {
                    const int j = (n >> 1) + (n & 1) * 8;
                    const uint4 v = make_uint4(pack2(acc[j * 8], acc[j * 8 + 1]), pack2(acc[j * 8 + 2], acc[j * 8 + 3]), pack2(acc[j * 8 + 4], acc[j * 8 + 5]), pack2(acc[j * 8 + 6], acc[j * 8 + 7]));
                    if (j < 16 - NSB) stg128(dst + j * 32, v, out_pol(T_OP, layer, ch)); else sts128(sb + B_OUT + (w * NSB + j - (16 - NSB)) * 512 + lane * 16, v.x, v.y, v.z, v.w);
                }
            }
        } else if (type == T_CV) {
            float acc[128];
            if (layer) hist_task(acc, sb, w, ch, t.a + rank, st, ph, nd);
            else { conv_task(p, acc, sb, w, ch, t.a + rank, t.b, t.dry, st, ph, nd); staged = false; nd++; }
        } else {
            fin_task(p, ch, t.a + rank * t.c, t.c, t.b, t.dry);
        }
        if (staged) {
            __syncwarp();
            mbar_arrive1(sb + B_BAR + (BB_DONE + (w >> 2)) * 8);
            nd++;
        }
        PROF(threadIdx.x == 128, 3600 + ti * 4 + 2);
        __syncwarp();
    }
}

constexpr int P_Y = 131072  , P_PRM = P_Y  , P_K6 = P_PRM + 8192  ,
              P_P = P_Y + 40960  , P_U = P_P + 33280  , P_END = P_U + 17408, P_X = 98304  ;
static_assert(P_END <= B_BAR && P_END <= R_BAR, "prologue scratch");
#define KGUN 2
constexpr int KGU = KGUN;
__device__ __forceinline__ void csq(float& r, float& i) { const float t = r * i; r = fmaf(r, r, -(i * i)); i = t + t; }
__device__ __forceinline__ void cpow(float ar, float ph, float p, float& r, float& i) {
    const float e = ex2(ar * p);
    const float u = ph * p, n = fabsf(u) < 4194304.f ? (u + 12582912.f) - 12582912.f : u;
    const float t = (u - n) * 6.283185307179586f;
    r = e * __cosf(t); i = e * __sinf(t);
}
__device__ __forceinline__ void mma_tf32(float* c, float a0, float a1, float a2, float a3, float b0, float b1) {
    asm volatile("mma.sync.aligned.m16n8k8.row.col.f32.tf32.tf32.f32 {%0,%1,%2,%3},{%4,%5,%6,%7},{%8,%9},{%0,%1,%2,%3};"
                 : "+f"(c[0]), "+f"(c[1]), "+f"(c[2]), "+f"(c[3])
                 : "r"(__float_as_uint(a0)), "r"(__float_as_uint(a1)), "r"(__float_as_uint(a2)), "r"(__float_as_uint(a3)), "r"(__float_as_uint(b0)), "r"(__float_as_uint(b1)));
}

struct ProRegs { uint32_t v[2][4], ldt[2]; };
__device__ __forceinline__ void prologue_load(const ProArgs& a, int b, ProRegs& pr) {
    const int w = threadIdx.x >> 5;
#pragma unroll
    for (int i = 0; i < 2; i++) {
        const int gi = b * 512 + (w & 3) * 128 + ((w >> 2) & 1) * 64 + i * 32 + (threadIdx.x & 31);
        pr.ldt[i] = __ldg((const uint16_t*)a.ldt + b * 4 + (w & 3));
        pr.v[i][0] = __ldg((const uint16_t*)a.lAr + gi); pr.v[i][1] = __ldg((const uint16_t*)a.Ai + gi);
        pr.v[i][2] = __ldg((const uint16_t*)a.Cr + gi); pr.v[i][3] = __ldg((const uint16_t*)a.Ci + gi);
    }
}
__device__ __forceinline__ void prologue(const ProArgs& a, uint32_t sb, int b, int w, const ProRegs& pr, uint32_t zero, int lag) {
    const int tid = threadIdx.x, lane = tid & 31, g = lane >> 2, c = lane & 3;
    const int d0 = b * 4;
    if (w >= 8) {
        const int t2 = tid - 256;
        PROF(t2 == 0, 3516);
        const int gi = b * 128 + t2;
        if (t2 < 32) acc_init(a.mem0, b * 32 + t2, lag);
        if (t2 >= 112) ((uint4*)g_st2)[b * 16 + t2 - 112] = make_uint4(0, 0, 0, 0);
        if (gi < 13 * 64) g_cnt[gi] = 0;
        bar_sync(6, 384);
        if (gi < 512) g_st[0][(gi >> 8) * 2048 + (lds32(sb + S_TAG) ^ 1) * 256 + (gi & 255)] = make_float2(0.f, 0.f);
        asm volatile("{.reg .pred p; elect.sync _|p,0xffffffff; @p cp.async.bulk.prefetch.L2.global [%0],32768;}"
                     ::"l"((w == 8 ? a.Wq : w == 9 ? a.Wk : w == 10 ? a.Wv : a.Wo) + (size_t)b * 16384) : "memory");
        mbar_wait(sb + S_XBAR, 0);
        uint32_t l[16];
        int n = 0;
        while (true) {
            bool ok = true;
#pragma unroll
            for (int i = 0; i < 16; i++) asm volatile("ld.relaxed.gpu.global.u32 %0,[%1];" : "=r"(l[i]) : "l"(g_ln0 + i * 128 + t2) : "memory");
#pragma unroll
            for (int i = 0; i < 16; i++) ok = ok && l[i];
            if (__all_sync(0xffffffffu, ok)) break;
            if (++n > 2000000) __trap();
        }
#pragma unroll 1
        for (int h = 0; h < 2; h++) {
#pragma unroll
            for (int i = 0; i < 8; i++) {
                const int t = h * 1024 + i * 128 + t2;
                const uint2 x = lds64(sb + P_X + t * 16 + (b & 1) * 8);
                const float m = blo(l[i]), rs = rcp(bhi(l[i]));
                l[i] = l[i + 8];
                const uint32_t u0 = pack2(rbf(blo(x.x) - m) * rs, rbf(bhi(x.x) - m) * rs), u1 = pack2(rbf(blo(x.y) - m) * rs, rbf(bhi(x.y) - m) * rs);
                sts128(sb + P_X + t * 16, x.x, x.y, u0, u1);
                const uint32_t o = sb + P_U + ((t >> 3) & 1) * 2176 + ((t >> 4) + 8) * 16 + (t & 7) * 2;
                asm volatile("st.shared.u16 [%0],%1;" ::"r"(o), "h"((uint16_t)u0) : "memory");
                asm volatile("st.shared.u16 [%0],%1;" ::"r"(o + 4352), "h"((uint16_t)(u0 >> 16)) : "memory");
                asm volatile("st.shared.u16 [%0],%1;" ::"r"(o + 8704), "h"((uint16_t)u1) : "memory");
                asm volatile("st.shared.u16 [%0],%1;" ::"r"(o + 13056), "h"((uint16_t)(u1 >> 16)) : "memory");
            }
        }
        PROF(t2 == 0, 3517);
        bar_sync(9, 384);
        fence_async_smem();
#pragma unroll 1
        for (int j = 0; j < 16; j++) {
            const int d = d0 + w - 8;
            asm volatile("{.reg .pred p; elect.sync _|p,0xffffffff; @p cp.async.bulk.global.shared::cta.bulk_group [%0],[%1],%2;}" ::"l"(g_P + (((d >> 5) * 16 + j) * 32 + (d & 31)) * PW),
                         "r"(sb + P_P + ((w - 8) * 2080 + j * 128) * 4), "r"(PW * 4) : "memory");
        }
        asm volatile("cp.async.bulk.commit_group; cp.async.bulk.wait_group 0;" ::: "memory");
        bar_arrive(10, 384);
        return;
    }
#pragma unroll
    for (int i = 0; i < 2; i++) {
        const float dt = rbf(expf(blo(pr.ldt[i])));
        const float ar = -rbf(expf(blo(pr.v[i][0]))) * dt, ai = blo(pr.v[i][1]) * dt;
        sts128(sb + P_PRM + (w * 64 + i * 32 + lane) * 16, __float_as_uint(ar * 1.4426950408889634f), __float_as_uint(ai * 0.15915494309189535f),
               __float_as_uint(2.f * (blo(pr.v[i][2]) * dt)), __float_as_uint(2.f * (blo(pr.v[i][3]) * dt)));
    }
    if (tid < 64) sts128(sb + P_U + (tid >> 3) * 2176 + (tid & 7) * 16, 0, 0, 0, 0);
    bar_arrive(6, 384);
    __syncwarp();
    PROF(tid == 0, 3510);
    const int ch = w & 3, hf = w >> 2;
    {
        float k0[4] = {0, 0, 0, 0}, k1[4] = {0, 0, 0, 0}, k2[4] = {0, 0, 0, 0}, k3[4] = {0, 0, 0, 0}, k4[4] = {0, 0, 0, 0}, kl = 0;
#pragma unroll KGU
        for (int j = 0; j < 16; j++) {
            const uint4 q = lds128(sb + P_PRM + (w * 64 + j * 4 + c) * 16);
            const float cr = __uint_as_float(q.z), ci = __uint_as_float(q.w);
            float wr[4], wi[4], vr[4], vi[4];
            cpow(__uint_as_float(q.x), __uint_as_float(q.y), (float)g, wr[0], wi[0]);
            cpow(__uint_as_float(q.x), __uint_as_float(q.y), (float)(g + 8), vr[0], vi[0]);
#pragma unroll
            for (int i = 1; i < 4; i++) { wr[i] = wr[i - 1]; wi[i] = wi[i - 1]; csq(wr[i], wi[i]); vr[i] = vr[i - 1]; vi[i] = vi[i - 1]; csq(vr[i], vi[i]); }
            float hr = wr[3], hi = wi[3];
            csq(hr, hi);
            mma_tf32(k0, wr[0], vr[0], wi[0], vi[0], cr * hr - ci * hi, -(cr * hi + ci * hr));
            hr = vr[3]; hi = vi[3]; csq(hr, hi);
            mma_tf32(k1, wr[0], vr[0], wi[0], vi[0], cr * hr - ci * hi, -(cr * hi + ci * hr));
            csq(hr, hi);
            mma_tf32(k2, wr[1], vr[1], wi[1], vi[1], cr * hr - ci * hi, -(cr * hi + ci * hr));
            csq(hr, hi);
            mma_tf32(k3, wr[2], vr[2], wi[2], vi[2], cr * hr - ci * hi, -(cr * hi + ci * hr));
            csq(hr, hi);
            mma_tf32(k4, wr[3], vr[3], wi[3], vi[3], cr * hr - ci * hi, -(cr * hi + ci * hr));
            csq(hr, hi);
            kl += cr * hr - ci * hi;
        }
        kl += __shfl_xor_sync(0xffffffffu, kl, 1); kl += __shfl_xor_sync(0xffffffffu, kl, 2);
        const uint32_t o = sb + P_K6 + (ch * 656 + c * 32 + g) * 4, ol = sb + P_K6 + (ch * 656 + 640) * 4;
#define KST(k, base) sts32(o + (base) * 4, __float_as_uint(k[0])); sts32(o + (base) * 4 + 64, __float_as_uint(k[1])); \
                     sts32(o + (base) * 4 + 32, __float_as_uint(k[2])); sts32(o + (base) * 4 + 96, __float_as_uint(k[3]))
#define KAD(k, base) k[0] += __uint_as_float(lds32(o + (base) * 4)); k[1] += __uint_as_float(lds32(o + (base) * 4 + 64)); \
                     k[2] += __uint_as_float(lds32(o + (base) * 4 + 32)); k[3] += __uint_as_float(lds32(o + (base) * 4 + 96))
        if (hf == 0) {
            bar_sync(2 + ch, 64);
            KAD(k0, 0); KAD(k1, 128); KAD(k2, 256); KAD(k3, 384); KAD(k4, 512);
            kl += __uint_as_float(lds32(ol));
            __syncwarp();
        }
        KST(k0, 0); KST(k1, 128); KST(k2, 256); KST(k3, 384); KST(k4, 512);
        if (lane == 0) sts32(ol, __float_as_uint(kl));
        if (hf == 1) { __syncwarp(); bar_arrive(2 + ch, 64); }
    }
    PROF(tid == 0, 3511);
    bar_sync(8, 384);
    PROF(tid == 0, 3512);
    if (tid < 64) sts32(sb + P_P + ((tid >> 4) * 2080 + (tid & 15)) * 4, 0);
#pragma unroll 1
    for (int x = tid; x < 2048; x += 512) {
        uint32_t pw[2][4];
#pragma unroll
        for (int h = 0; h < 2; h++) {
            const int y = x + h * 256;
            const int i0 = y <= 256 ? y : 256 + (int)((pack2((float)y, 0.f) & 0xffff) - 0x4380);
            const int i1 = y <= 256 ? max(y - 1, 0) : 256 + (int)((pack2((float)(y - 1), 0.f) & 0xffff) - 0x4380);
#pragma unroll
            for (int k = 0; k < 4; k++) {
                const float lo = __uint_as_float(lds32(sb + P_K6 + k * 2624 + i0 * 4)), hi = __uint_as_float(lds32(sb + P_K6 + k * 2624 + i1 * 4));
                pw[h][k] = pack2(lo, y ? hi : 0.f);
            }
        }
#pragma unroll
        for (int h = 0; h < 2; h++)
#pragma unroll
            for (int k = 0; k < 4; k++) sts32(sb + P_P + (k * 2080 + x + h * 256 + 16) * 4, pw[h][k]);
    }
    bar_sync(9, 384);
    PROF(tid == 0, 3513);
    {
        float acc[16][4];
#pragma unroll
        for (int j = 0; j < 16; j++) acc[j][0] = acc[j][1] = acc[j][2] = acc[j][3] = 0;
#pragma unroll 1
        for (int e = hf * 4; e < hf * 4 + 4; e++) {
            uint32_t B[16][2];
            const uint32_t ua = sb + P_U + ch * 4352 + ((lane >> 3) & 1) * 2176 + (8 + (lane >> 4) * 8 + (lane & 7) - e) * 16;
            const uint32_t pa = sb + P_P + (ch * 2080 + 16 + e * 16 + g - 2 * c) * 4;
            uint4 A[16];
#define TLD(d) A[d] = make_uint4(lds32(pa + (d) * 512), lds32(pa + (d) * 512 + 32), lds32(pa + (d) * 512 - 32), 0)
            TLD(0); TLD(15);
#pragma unroll
            for (int j = 0; j < 8; j++) { const uint4 v = ldsm4(ua + j * 256); B[2 * j][0] = v.x; B[2 * j][1] = v.y; B[2 * j + 1][0] = v.z; B[2 * j + 1][1] = v.w; }
#pragma unroll
            for (int d = 0; d < 8; d++) {
                if (d < 7) { TLD(d + 1); TLD(14 - d); }
                A[d].w = A[d].x + zero; A[15 - d].w = A[15 - d].x + zero;
                sfence(zero);
#pragma unroll
                for (int j = 15 - d; j < 16; j++) mma16(acc[j], A[15 - d].x, A[15 - d].y, A[15 - d].z, A[15 - d].w, B[j - 15 + d][0], B[j - 15 + d][1]);
#pragma unroll
                for (int j = d; j < 16; j++) { mma16(acc[j], A[d].x, A[d].y, A[d].z, A[d].w, B[j - d][0], B[j - d][1]); sfence(zero); }
            }
        }
        PROF(tid == 0, 3514);
        const uint32_t o = sb + P_Y + (ch * 2560 + c * 40 + g) * 4;
#pragma unroll
        for (int j = 0; j < 8; j++) {
#pragma unroll
            for (int i = 0; i < 4; i++) { const float lo = acc[j][i], hi = acc[j + 8][i]; acc[j][i] = hf ? hi : lo; sts32(o + (j + 8 - hf * 8) * 640 + (i & 1) * 80 + (i >> 1) * 32, __float_as_uint(hf ? lo : hi)); }
        }
        bar_sync(2 + ch, 64);
#pragma unroll
        for (int j = 0; j < 8; j++) {
#pragma unroll
            for (int i = 0; i < 4; i++) acc[j][i] += __uint_as_float(lds32(o + (j + hf * 8) * 640 + (i & 1) * 80 + (i >> 1) * 32));
        }
#pragma unroll
        for (int j = 0; j < 8; j++) {
#pragma unroll
            for (int i = 0; i < 4; i++) sts32(o + (j + hf * 8) * 640 + (i & 1) * 80 + (i >> 1) * 32, __float_as_uint(acc[j][i]));
        }
    }
    const uint2 dk = __ldg((const uint2*)(a.Dk + d0));
    bar_sync(1, 256);
#pragma unroll 2
    for (int i = 0; i < 8; i++) {
        const int t = i * 256 + tid;
        const uint32_t o = sb + P_Y + (t + 4 * (t >> 4)) * 4;
        const uint4 xu = lds128(sb + P_X + t * 16);
        float y[4];
#pragma unroll
        for (int k = 0; k < 4; k++) y[k] = rbf(__uint_as_float(lds32(o + k * 10240)));
        uint2 r;
        r.x = pack2(blo(xu.x) + rbf(y[0] + rbf(blo(xu.z) * blo(dk.x))), bhi(xu.x) + rbf(y[1] + rbf(bhi(xu.z) * bhi(dk.x))));
        r.y = pack2(blo(xu.y) + rbf(y[2] + rbf(blo(xu.w) * blo(dk.y))), bhi(xu.y) + rbf(y[3] + rbf(bhi(xu.w) * bhi(dk.y))));
        {
            const bool up = t & 8;
            const uint32_t o = __shfl_xor_sync(0xffffffffu, up ? r.x : r.y, 8);
            ((uint2*)(g_xA[0] + ((t >> 4) * 32 + (d0 >> 4)) * 32 + (t & 7) * 4 + ((d0 >> 1) & 2) + up))[(d0 >> 3) & 1] = up ? make_uint2(o, r.y) : make_uint2(r.x, o);
        }
        if (i == 0) {
            const float e0 = blo(r.x), e1 = bhi(r.x), e2 = blo(r.y), e3 = bhi(r.y);
            asm volatile("red.relaxed.gpu.global.add.v2.f32 [%0],{%1,%2};" ::"l"(g_st[0] + (t >> 7) * 2048 + lds32(sb + S_TAG) * 256 + (b & 1) * 128 + (t & 127)),
                         "f"((e0 + e1) + (e2 + e3)), "f"((e0 * e0 + e1 * e1) + (e2 * e2 + e3 * e3)) : "memory");
        }
    }
    PROF(tid == 0, 3515);
    bar_sync(10, 384);
}

__global__ void __cluster_dims__(2, 1, 1) __launch_bounds__(384, 1) main_kernel(const __grid_constant__ Params p) {
    extern __shared__ __align__(1024) uint8_t smem[];
    const uint32_t sb = __shfl_sync(0xffffffffu, smem_u32(smem), 0);
    uint32_t rank; asm("mov.u32 %0,%%cluster_ctarank;" : "=r"(rank));
    const int wi = __shfl_sync(0xffffffffu, threadIdx.x >> 5, 0);
    const int cl = blockIdx.x >> 1, wg = wi >> 2;
    const bool rec = p.rec0 >= 0 && cl >= p.rec0 && cl < p.rec0 + 32;
    PROF(threadIdx.x == 0, 3500);
    ProRegs pr;
    if ((wi >> 1) == 4 && p.dopro && cl >= 2) {
        const int g = (threadIdx.x & 31) >> 2, c = threadIdx.x & 3, row = (blockIdx.x - 4) * 16 + (wi - 8) * 8 + g;
        const float4 r4 = row_stats((const uint4*)(p.pa.x + (size_t)row * 512) + c, 4);
        const float2 r = make_float2(r4.x + r4.z, r4.y + r4.w);
        const float2 l = ln_finish(r.x * (1.f / 512.f), fmaxf(r.y - r.x * r.x * (1.f / 512.f), 0.f) * (1.f / 512.f));
        if (c == (g >> 1)) asm volatile("st.relaxed.gpu.global.u32 [%0],%1;" ::"l"(g_ln0 + row), "r"(pack2(l.x, l.y)) : "memory");
        __syncwarp();
    }
    prologue_load(p.pa, max((int)blockIdx.x - 4, 0), pr);
    if (rec) rec_init(p, sb, cl - p.rec0, rank); else bulk_init(sb);
    if (threadIdx.x == 352 && p.dopro && cl >= 2) {
        mbar_init(sb + S_XBAR, 1);
        asm volatile("fence.mbarrier_init.release.cluster;" ::: "memory");
        mbar_expect(sb + S_XBAR, 32768);
        for (int j = 0; j < 8; j++) tma2d(sb + P_X + j * 4096, &p.tm[3], ((blockIdx.x - 4) >> 1) * 8, j * 256, sb + S_XBAR);
    }
    if (threadIdx.x == 320) {
        unsigned v;
        asm volatile("ld.relaxed.gpu.global.u32 %0,[%1];" : "=r"(v) : "l"(g_gate) : "memory");
        v = v / (4 * NCL) + p.dopro;
        sts64(sb + S_GATE, v * (4 * NCL), v & 1);
    }
    __syncwarp();
    asm volatile("barrier.cluster.arrive.relaxed.aligned;" ::: "memory");
    if (wg == 2) bar_arrive(8, 384);
    if (p.dopro && cl >= 2) prologue(p.pa, sb, blockIdx.x - 4, wi, pr, p.zero, p.lag); else if (wg < 2) bar_sync(8, 384);
    asm volatile("barrier.cluster.wait.aligned;" ::: "memory");
    fence_async_smem();
    bar_sync(wg == 2 ? 7 : 1, wg == 2 ? 128 : 256);
    if (p.dopro && (threadIdx.x == 32 || threadIdx.x == 352)) red_release(g_gate, 1);
    if (rec) {
        if (threadIdx.x == 0) {
            rec_fetch(&p.tm[1], sb + R_STK, (cl - p.rec0) * 128, rank * 256, 2, sb + R_BAR + RB_INIT * 8);
            rec_fetch(&p.tm[2], sb + R_STV, (cl - p.rec0) * 128, rank * 256, 2, sb + R_BAR + RB_INIT * 8);
        }
    }
    PROF(threadIdx.x == 0, 3506);
    __syncwarp();
    if (rec) {
        const int head = cl - p.rec0;
        if (wg == 2) {
            reg_dec<RH>();
            const int w = wi & 3;
            if (threadIdx.x == 256) rec_fetch(&p.tm[0], sb + R_STQ, head * 128, rank * 256, 2, sb + R_BAR + RB_INIT * 8);
            __syncwarp();
            wait_cnt_warp(g_gate, lds32(sb + S_GATE));
            if (p.dostats) x1_stats((head * 2 + rank) * 4 + w);
            __syncthreads();
            cluster_sync();
            if ((p.chains >> (w >> 1)) & 1) rec_attn(p, sb, w >> 1, w & 1, head, rank);
        } else {
            reg_inc<RW0>();
            rec_weights(p, sb, head, rank, wi);
        }
    } else {
        if (wg == 2) {
            reg_dec<40>();
            const int w = wi & 3;
            if (w == 0) bulk_producer(p, sb, cl, rank); else if (w >= 2) bulk_release(p, sb, cl, rank, w - 2); else bulk_relay(p, sb, cl);
        } else { reg_inc<232>(); bulk_consumer(p, sb, cl, rank, wi); }
    }
    __syncwarp();
    cluster_sync();
}

typedef CUresult (*EncFn)(CUtensorMap*, CUtensorMapDataType, cuuint32_t, void*, const cuuint64_t*, const cuuint64_t*, const cuuint32_t*, const cuuint32_t*,
                          CUtensorMapInterleave, CUtensorMapSwizzle, CUtensorMapL2promotion, CUtensorMapFloatOOBfill);
inline uint32_t mk(int type, int layer, int ch, int a, int b, int c) { return type | (layer << 3) | (ch << 4) | (a << 8) | (b << 16) | ((uint32_t)c << 24); }
constexpr int SMEM_BYTES = 232448;

struct Sched {
    Params* P; int n[NCL];
    void clear() { memset(P->task, 0, sizeof(P->task)); memset(n, 0, sizeof(n)); }
    void add(int cl, uint32_t t) { if (n[cl] < MAXT - 1) P->task[list_of(cl)][n[cl]++] = t; }
};

constexpr int REC0 = 4;
struct Cfg { int LAG, TS1, TS2, DQU, DQO, DUN, DHN, MARG, NQ1, FAST0, n0, oc, fc, nuns, ns2, nhg, hs, osl, nfin, dry, tl, c8, o9, lm, hd, DKB, DF, oe; };
#define HALVES 1
#define PLAN 14, 2250, 2850, 2400, 900, 5400, 420, 1000, 4, 0, 12, 10, 14, 6, 4, 8, 8000, 0, 0, 8500, 1500, 12, 3, 1500, 400, 640, 3000, 0
Cfg g_cfg = {PLAN};
double g_est;
bool g_planned = false;
struct Plan { uint32_t w[NCL][MAXT]; int n[NCL]; double end, rec; };
void simulate(Plan& L, int nc, const Cfg& C) {
    const int LAG = C.LAG, NQ1 = C.NQ1, FAST0 = C.FAST0, n0 = C.n0, oc = C.oc, fc = C.fc, nuns = C.nuns, ns2 = C.ns2, nhg = C.nhg;
    const double TS1 = C.TS1, TS2 = C.TS2, DQU = C.DQU, DQO = C.DQO, DUN = C.DUN, DHN = C.DHN, MARG = C.MARG, hs = C.hs;
    const double INF = 1e18, DKB = C.DKB, DOV = 700, DH = DHN, DHO = 1100, DF = C.DF, DFB = 200, POLL = 450, FILL = 500, PUB = 600;
    enum { Q0, O0, Q1, HB, O1, FI, NK };
    struct Grp { int n, left; double done; } G[NK][16];
    double fr[NCL], it[100] = {}, cv[16];
    int ns[16], last[2][NCL], uc = 0, nit = 0;
    memset(L.n, 0, sizeof(L.n)); L.end = 0;
    auto fast = [&](int c) { return c < FAST0 || c >= fc; };
    for (int c = 0; c < 16; c++) {
        ns[c] = c < nuns ? 1 : c == 15 ? 16 : c >= C.c8 ? 8 : ns2;
        const int cnt[NK] = {c < 2 ? 48 : (c & 1) ? 0 : 96, c >= oc || (c && c <= C.oe) ? OPS1 : c >= C.o9 ? 9 : 8, c == 15 ? 24 : fast(c) ? 16 : 48 / NQ1, c >= 2 && !(c & 1) ? 16 : 0, ns[c], c < C.nfin || ns[c] == 1 ? 0 : c >= 14 ? 8 : 4};
        for (int k = 0; k < NK; k++) G[k][c] = {cnt[k], cnt[k], 0};
        cv[c] = INF;
    }
    for (int i = 0; i < nc; i++) { fr[i] = 0; last[0][i] = last[1][i] = -1; }
    auto fin = [&](int k, int c) { if ((k == Q0 && c >= 2) || k == HB) c &= ~1; return G[k][c].left ? INF : G[k][c].done; };
    auto len = [&](int i) { return (i >= LAG && i < 64) ? (double)TS2 : (double)TS1; };
    auto end_it = [&](int i) { return i < nit ? it[i] + len(i) : INF; };
    auto nominal = [&](int i) { if (i < nit) return it[i]; double t = nit ? it[nit - 1] : 11000 - TS1; for (int j = nit - 1; j < i; j++) t += len(j); return t; };
    auto put = [&](int i, uint32_t w) { if (L.n[i] < MAXT - 2) L.w[i][L.n[i]++] = w; else L.end = INF; };
    auto rel = [&](int k, int c) {
        switch (k) {
            case Q0: return 0.0;
            case O0: return end_it(4 * c + 3) + PUB + POLL;
            case Q1: return cv[c] + POLL;
            case HB: return cv[c - 2] + 600 + POLL;
            case O1: return fmax(end_it(LAG + 4 * c + 3) + PUB + POLL, G[O1][c].left == 1 && !G[FI][c].n ? G[O1][c].done - DKB * 64 / ns[c] : 0);
            default: return fin(O1, c) + POLL;
        }
    };
    auto dur = [&](int k, int c) {
        switch (k) {
            case Q0: return DQO + (c < 2 ? 2.0 : 1.0) * DQU;
            case O0: return (16 - G[O0][c].n) * DKB + 1200;
            case HB: return DHO + DH * c;
            case Q1: return DQO + 48.0 / G[Q1][c].n * DQU;
            case O1: return DOV + DKB * 64 / ns[c] + (G[O1][c].left == 1 && !G[FI][c].n ? 700 + 800 * ns[c] : 0);
            default: return DF + DFB * ns[c] * (c >= 14 ? 0.5 : 1);
        }
    };
    auto o0_est = [&](int c) {
        double t = uc ? cv[uc - 1] - 900 : 0;
        for (int j = uc; j < c; j++) t = fmax(t, nominal(4 * j + 4) + PUB + POLL + FILL) + dur(O0, j) + DUN;
        return fmax(t, nominal(4 * c + 4) + PUB + POLL);
    };
    auto cv_est = [&](int c) { return c < uc ? cv[c] : o0_est(c) + FILL + dur(O0, c) + DUN + 900; };
    auto slot = [&](int k, int c, int i) { return k == O0 ? (i < 8 ? i : nc + 7 - i) : c == 15 ? i : i - 8; };
    while (true) {
        while (nit < 64 + LAG) {
            double t = nit ? end_it(nit - 1) : 0;
            if (nit < 64) t = fmax(t, fin(Q0, nit >> 2) + POLL);
            if (nit >= LAG) t = fmax(t, fin(Q1, (nit - LAG) >> 2) + (nit < 64 ? 0 : POLL));
            if (t >= INF) break;
            it[nit++] = t;
        }
        int i = -1;
        for (int j = 0; j < nc; j++) if (fr[j] < INF && (i < 0 || fr[j] < fr[i])) i = j;
        if (i < 0) break;
        const double t = fr[i];
        double lim = INF;
        if (i < 8 && last[0][i] == uc) {
            if (G[O0][uc].left || fin(HB, uc) >= INF) { fr[i] = t + 200; continue; }
            const double e = fmax(G[O0][uc].done, fin(HB, uc) - 2000) + DUN;
            for (int j = 0; j < 8; j++) { put(j, mk(T_CV, 0, uc, 2 * j, G[O0][uc].n, 0)); fr[j] = e; }
            cv[uc++] = e + 900;
            continue;
        }
        const bool hg = (unsigned)(i - 24) < (unsigned)nhg;
        double hlim = INF;
        for (int c = 2; c < 16 && hg; c++) if (G[HB][c].left) { hlim = cv_est(c - 2) + hs - C.hd * c; break; }
        int mine[2] = {-1, -1};
        for (int k = 0; k < 2; k++)
            for (int c = last[k][i] + 1; c < 16 && mine[k] < 0; c++) if ((unsigned)slot(O0 + k, c, i) < (unsigned)G[O0 + k][c].n) mine[k] = c;
        if (mine[0] >= 0) lim = i < 8 ? o0_est(mine[0]) - (uc ? 0 : C.dry) : nominal(4 * mine[0] + 4) + PUB + C.osl;
        else if (mine[1] >= 0) lim = cv_est(mine[1]) + POLL - (mine[1] ? C.lm : 0);
        else if ((i < 16 && G[O1][15].left) || (i < 8 && G[FI][15].left)) lim = fmin(lim, nominal(64 + LAG) + PUB - C.tl);
        int bk = -1, bc = 0; double bd = INF;
        for (int k = 0; k < NK; k++)
            for (int c = 0; c < 16; c++) {
                const bool urgent = k == O0 || k == Q1 || (k >= O1 && c == 15);
                if (!G[k][c].left || ((k == O0 || k == Q1) && c != mine[k - O0]) || (k >= O1 && c == 15 && i >= G[k][c].n)) continue;
                if (rel(k, c) > t || (t + dur(k, c) + (k == Q0 && c >= 2 ? DQU : 0) > lim && !urgent)) continue;
                if (i < 8 && uc && uc < 16 && k != O0) continue;
                if ((k == HB && !hg && i < nc - 2) || (k != HB && !urgent && t + dur(k, c) + (k == Q0 && c >= 2 ? DQU : 0) > hlim)) continue;
                const double dl = urgent ? -INF : k == HB ? -INF / 2 : k == Q0 ? nominal(4 * c) - 3000 : 1e9 + c * 2 + (k == O1);
                if (dl < bd) { bd = dl; bk = k; bc = c; }
            }
        if (bk < 0) {
            bool any = i < 8 && uc < 16;
            for (int k = 0; k < NK; k++) for (int c = 0; c < 16; c++) any = any || G[k][c].left;
            fr[i] = any ? t + 200 : INF;
            if (t > 400000) { L.end = INF; return; }
            continue;
        }
        Grp& g = G[bk][bc];
        const int n = g.n - g.left, c = bc;
        int nu = 1;
        double d = dur(bk, c);
        if (bk == Q0) for (nu = c < 2 ? 2 : 1; c >= 2 && nu < g.left && (nu < 2 || (nu < n0 && t + d + DQU < fmin(fmin(lim, hlim), bd - MARG))); nu++) d += DQU;
        if (bk == O0 && i >= 8) d += (g.n - 8) * DKB;
        if (bk == Q0 && !c && n >= 32) { nu = 1; d -= DQU; }
        if (bk == O0 || bk == Q1) last[bk - O0][i] = c;
        if (bk == O0 && !c && i < 8 && C.dry) put(i, mk(T_CV, 0, 1, 2 * i, 0, 128));
        g.left -= nu;
        const bool fini = bk == O1 && !g.left && !G[FI][c].n;
        const double e = fmax(fmax(t, rel(bk, c) + FILL) + (t < 1 ? 3500 : 0) + d, fini ? g.done + POLL + 700 + 800 * ns[c] : 0);
        fr[i] = e;
        g.done = fmax(g.done, e + (bk == O1 ? (c == 15 ? -500 : 1500) : bk == O0 ? 0 : (bk == Q1 && g.n < 24) || (bk == Q0 && !c && nu == 2) ? -500 : 1000));
        if (bk == FI || fini) L.end = fmax(L.end, e);
        put(i, bk == Q0 ? (c == 0 ? mk(T_QKV, 0, 0, n < 32 ? n : 2 * n - 32, nu, 32) : c == 1 ? mk(T_QKV, 0, c, n, 2, 24) : mk(T_QKV, 0, c, n, nu, 64))
             : bk == O0 ? (i < 8 ? mk(T_OP, 0, c, i * (16 - g.n), 16 - g.n, i) : mk(T_OP, 0, c, 64 - (nc - i) * 8, 8, slot(O0, c, i)))
             : bk == HB ? mk(T_CV, 1, c, 2 * n, 0, 0)
             : bk == Q1 ? mk(T_QKV, 1, c, slot(Q1, c, i) * 2, 48 / g.n, g.n)
             : bk == O1 ? mk(T_OP, 1, c, n * 64 / ns[c], 64 / ns[c], n + (fini ? 32 : c == 15 && HALVES ? 16 : 0))
                        : mk(T_FIN, 1, c, n * (32 / g.n), ns[c], 16 / g.n));
    }
    L.rec = end_it(63 + LAG);
}
void plan(Params& P) {
    P.rec0 = REC0; P.chains = 3; P.lag = g_cfg.LAG; P.dostats = 1; P.dopro = 1;
    static Plan L;
    int cls[NCL], nc = 0;
    for (int c = REC0 + 32; c < NCL; c++) cls[nc++] = c;
    for (int c = REC0 - 1; c >= 0; c--) cls[nc++] = c;
    simulate(L, nc, g_cfg);
    g_est = L.end;
    Sched S; S.P = &P; S.clear();
    for (int i = 0; i < nc; i++) {
        bool warm = false;
        for (int k = 0; k < L.n[i]; k++) {
            if (!warm && k + 1 < L.n[i] && (L.w[i][k + 1] & 255) == (mk(T_FIN, 1, 15, 0, 0, 0) & 255)) { S.add(cls[i], (L.w[i][k + 1] & ~0xff0000u) | 0x80000000u); warm = true; }
            S.add(cls[i], L.w[i][k]);
            if ((L.w[i][k] & 7) == T_FIN) warm = true;
        }
    }
}

#define TK0() do {} while (0)
#define TK() do { P.e0 = (P.chains & 1) ? 64 : 0; P.b1 = (P.chains & 2) ? P.lag : 1000; P.nit = (P.chains & 2) ? P.lag + 64 : 64; TK0(); } while (0)
}

extern "C" void kernel_launch(void* const* d_in, const int* in_sizes, int n_in, void* d_out, int out_size) {
    typedef const __nv_bfloat16* BP;
    static EncFn enc = nullptr;
    if (!enc) {
        void* fn = nullptr; cudaDriverEntryPointQueryResult qr;
        cudaGetDriverEntryPoint("cuTensorMapEncodeTiled", &fn, cudaEnableDefault, &qr);
        enc = (EncFn)fn;
        cudaFuncSetAttribute(main_kernel, cudaFuncAttributeMaxDynamicSharedMemorySize, SMEM_BYTES);
    }
    static Params P;
    for (int i = 0; i < 4; i++) {
        const cuuint64_t cols = i < 3 ? 4096 : 512, rows = i < 3 ? 512 : 4096;
        cuuint64_t d2[2] = {cols, rows}, d3[3] = {64, rows, cols / 64}, str[2] = {cols * 2, 128};
        cuuint32_t box[3] = {64, 64, 4}, es[3] = {1, 1, 1};
        enc(&P.tm[i < 3 ? i : 4], CU_TENSOR_MAP_DATA_TYPE_BFLOAT16, 2, d_in[9 + i], d2, str, box, es, CU_TENSOR_MAP_INTERLEAVE_NONE, CU_TENSOR_MAP_SWIZZLE_128B,
                       CU_TENSOR_MAP_L2_PROMOTION_L2_128B, CU_TENSOR_MAP_FLOAT_OOB_FILL_NONE);
        for (int m = 0; m <= i / 3; m++) {
            cuuint32_t box3[3] = {64, 32, m ? 4u : 2u};
            enc(&P.t3[i + m], CU_TENSOR_MAP_DATA_TYPE_BFLOAT16, 3, d_in[9 + i], d3, str, box3, es, CU_TENSOR_MAP_INTERLEAVE_NONE, CU_TENSOR_MAP_SWIZZLE_128B,
                CU_TENSOR_MAP_L2_PROMOTION_L2_128B, CU_TENSOR_MAP_FLOAT_OOB_FILL_NONE);
        }
    }
    {
        cuuint64_t dims[2] = {512, 2048}, str[1] = {1024};
        cuuint32_t box[2] = {8, 256}, es[2] = {1, 1};
        enc(&P.tm[3], CU_TENSOR_MAP_DATA_TYPE_BFLOAT16, 2, d_in[0], dims, str, box, es, CU_TENSOR_MAP_INTERLEAVE_NONE, CU_TENSOR_MAP_SWIZZLE_NONE,
            CU_TENSOR_MAP_L2_PROMOTION_NONE, CU_TENSOR_MAP_FLOAT_OOB_FILL_NONE);
    }
    for (int m = 0; m < 2; m++) {
        void* ga; cudaGetSymbolAddress(&ga, g_A);
        cuuint64_t dims[2] = {512, sizeof(AOps) / 1024}, str[1] = {1024};
        cuuint32_t box[2] = {256, m ? 16u : 8u}, es[2] = {1, 1};
        enc(&P.ta[m], CU_TENSOR_MAP_DATA_TYPE_BFLOAT16, 2, ga, dims, str, box, es, CU_TENSOR_MAP_INTERLEAVE_NONE, CU_TENSOR_MAP_SWIZZLE_NONE,
            CU_TENSOR_MAP_L2_PROMOTION_L2_128B, CU_TENSOR_MAP_FLOAT_OOB_FILL_NONE);
    }
    P.mem0 = (BP)d_in[8]; P.Wo = (BP)d_in[12]; P.Dskip = (BP)d_in[6]; P.out = (__nv_bfloat16*)d_out;
    cudaStream_t s = cudaStreamPerThread;
    P.pa = {(BP)d_in[0], (BP)d_in[1], (BP)d_in[2], (BP)d_in[3], (BP)d_in[4], (BP)d_in[5], (BP)d_in[6], (BP)d_in[9], (BP)d_in[10], (BP)d_in[11], (BP)d_in[12], (BP)d_in[8]};
    if (!g_planned) { plan(P); g_planned = true; }
    TK(); main_kernel<<<2 * NCL, 384, SMEM_BYTES, s>>>(P); TK();
}
```
